```python
import torch

def _softmax(x, axis=-1):
    return torch.softmax(x, dim=axis)

def _gelu(x):
    return torch.nn.functional.gelu(x, approximate='tanh')

def _silu(x):
    return torch.nn.functional.silu(x)

def _sigmoid(x):
    return torch.sigmoid(x)

def _layernorm(x, axis=-1, eps=1e-05):
    m = x.mean(dim=axis, keepdim=True)
    v = x.var(dim=axis, keepdim=True, unbiased=False)
    return (x - m) / torch.sqrt(v + eps)

def _scatter_add(tgt, idx, src, axis=0):
    return tgt.clone().index_add_(axis, idx, src)

def _segment_sum(src, seg, n):
    out = torch.zeros((n,) + src.shape[1:], dtype=src.dtype)
    return out.index_add_(0, seg, src)

def _pad(x, pw):
    flat = tuple((v for pair in reversed(pw) for v in pair))
    return torch.nn.functional.pad(x, flat)
kernel_name = 'gated_mix__sliding_local_dilated__memory_aug_recurrent_mem_tr__prompt'

def setup_inputs():

    _w = lambda a: (lambda t: t.to(torch.bfloat16) if t.is_floating_point() else t)(torch.as_tensor(a))

    def _A_setup():
        B, S, D = (1, 2048, 576)
        return {'x': _w((lambda *s: torch.randn(*s, dtype=torch.bfloat16) * 0.05)(B, S, D)), 'wqkv': _w((lambda *s: torch.randn(*s, dtype=torch.bfloat16) * 0.8)(D, 3 * D)), 'wo': _w((lambda *s: torch.randn(*s, dtype=torch.bfloat16) * 0.05)(D, D))}
    _A_in = _A_setup()

    def _B_setup():
        B, S, Dm = (1, 2048, 576)
        H, Dh = (32, 128)
        M, seg = (8, 32)
        seg = min(seg, S)
        S = S // seg * seg
        return {'x': _w((lambda *s: torch.randn(*s, dtype=torch.bfloat16) * 0.05)(B, S, Dm)), 'mem0': _w((lambda *s: torch.randn(*s, dtype=torch.bfloat16) * 1.6)(B, M, Dm)), 'Wq': _w((lambda *s: torch.randn(*s, dtype=torch.bfloat16) * 0.8)(Dm, H, Dh) * Dm ** (-0.5)), 'Wk': _w((lambda *s: torch.randn(*s, dtype=torch.bfloat16) * 0.8)(Dm, H, Dh) * Dm ** (-0.5)), 'Wv': _w((lambda *s: torch.randn(*s, dtype=torch.bfloat16) * 1.6)(Dm, H, Dh) * Dm ** (-0.5)), 'Wo': _w((lambda *s: torch.randn(*s, dtype=torch.bfloat16) * 1.6)(H, Dh, Dm) * (H * Dh) ** (-0.5)), 'seg_len': seg}
    _B_in = _B_setup()
    return {'A_x': _A_in['x'], 'A_wqkv': _A_in['wqkv'], 'A_wo': _A_in['wo'], 'B_x': _B_in['x'], 'B_mem0': _B_in['mem0'], 'B_Wq': _B_in['Wq'], 'B_Wk': _B_in['Wk'], 'B_Wv': _B_in['Wv'], 'B_Wo': _B_in['Wo'], 'B_seg_len': _B_in['seg_len'], 'gate_w': _w((lambda *s: torch.randn(*s, dtype=torch.bfloat16) * 0.05)(576) * 16.0)}

def reference(A_x, A_wqkv, A_wo, B_x, B_mem0, B_Wq, B_Wk, B_Wv, B_Wo, B_seg_len, gate_w):

    def _A_ref(x, wqkv, wo):
        B, S, D = x.shape
        H = 32
        Dh = D // H
        W, dil = (8, 2)
        qkv = (lambda x, *d: x.permute(*d))((x @ wqkv).reshape(B, S, 3, H, Dh), 2, 0, 3, 1, 4)
        q, k, v = (qkv[0], qkv[1], qkv[2])
        scale = Dh ** (-0.5)
        pos = torch.arange(S)
        off = torch.arange(W) * dil
        idx = pos[:, None] - off[None, :]
        mask = idx >= 0
        idx_c = torch.where(mask, idx, 0).reshape(-1)
        kg = k[:, :, idx_c, :].reshape(B, H, S, W, Dh)
        vg = v[:, :, idx_c, :].reshape(B, H, S, W, Dh)
        logits = torch.einsum('bhsd,bhswd->bhsw', q, kg) * scale
        logits = torch.where(mask[None, None, :, :], logits, -1000000000.0)
        attn = _softmax(logits, axis=-1)
        o = torch.einsum('bhsw,bhswd->bhsd', attn, vg)
        return (lambda x, *d: x.permute(*d))(o, 0, 2, 1, 3).reshape(B, S, D) @ wo

    def _B_ref(x, mem0, Wq, Wk, Wv, Wo, seg_len):
        B, S, Dm = x.shape
        H, Dh = (Wq.shape[1], Wq.shape[2])
        M = mem0.shape[1]
        scale = Dh ** (-0.5)
        n_seg = S // seg_len
        L = M + seg_len
        idx = torch.arange(L)
        mask = (idx[:, None] < M) | (idx[:, None] >= idx[None, :])
        mem = mem0
        outs = []
        for s in range(n_seg):
            xs = x[:, s * seg_len:(s + 1) * seg_len, :].clone()
            h = torch.concatenate([mem, xs], axis=1)
            q = torch.einsum('btd,dhe->bhte', h, Wq)
            k = torch.einsum('btd,dhe->bhte', h, Wk)
            v = torch.einsum('btd,dhe->bhte', h, Wv)
            scores = torch.einsum('bhqe,bhke->bhqk', q, k) * scale
            scores = torch.where(mask[None, None], scores, -1000000000.0)
            p = _softmax(scores, axis=-1)
            o = torch.einsum('bhqk,bhke->bhqe', p, v)
            o = torch.einsum('bhte,hed->btd', o, Wo)
            mem = o[:, :M, :].clone()
            outs.append(o[:, M:, :])
        return torch.concatenate(outs, axis=1)
    x = A_x
    g = _sigmoid((x * gate_w).sum(-1, keepdims=True))
    a = _A_ref(x, A_wqkv, A_wo)
    b = _B_ref(x, B_mem0, B_Wq, B_Wk, B_Wv, B_Wo, B_seg_len)
    return g * a + (1 - g) * b
```

```cpp
#include <cuda_runtime.h>
#include <cuda_bf16.h>
#include <cuda_fp16.h>
#include <cuda.h>
#include <stdint.h>

typedef __nv_bfloat16 bf16;

constexpr int S_LEN = 2048, DM = 576, NH = 32, DH = 128, NSEG = 64, KCAT = 4096 + 576;
#define RED_LINE(i) (((i) >> 2) * 4096 + ((i) & 1) * 256 + ((i) & 2) * 512)
#define RED_SLOT(s) (((s) & 1) * 128 + ((s) & 2) * 256)

#define POLL_NS 896
#define NII 18
#define W3PRE 4
#define W3MID 4
#define GF 0
#define B5POS 0
#define NUP 4
#define UPF 1
#define B3Q 9
#define B3F 0
#define GATE 7
#define NTL 2
#define B7R 1
#define EXPOS 0
#define VW2 1
#define CLR 1
#define RFW 0
#define NIC 0
#define LEAD 0
#define FIN16 1
#define VXG 0
#define RING 63
#define EXB 0
#define EXD 0
#define EXB2 8192
#define HDLY 0
#define F10 1
#define NPROBE 2
#define QM 0
#define N5 (EXB ? 256 : 224)
#define KP(i) (((i) >> 1) + 4 * ((i) & 1))
#define SPIN_LIMIT (1 << 14)
#define XP 0

__device__ __align__(1024) bf16 g_Ocat[S_LEN * KCAT];
__device__ __align__(1024) unsigned char g_red_raw[2 * 262144];
constexpr int HINT_OFF = 2048;
__device__ __align__(16) float g_gate[S_LEN];
__device__ __align__(128) uint4 g_stats[96 * 2];
__device__ unsigned g_epoch;
__device__ unsigned g_epoch2;
__device__ unsigned g_ocnt[NSEG * 32];
__device__ unsigned g_abar[3 * 32];
__device__ unsigned g_pace[32];
__device__ unsigned g_scnt[NSEG * 32 * 8];
__device__ __align__(1024) unsigned char g_seg[NSEG * 96 * 10240];
__device__ __align__(1024) uint4 g_part[4 * 36 * 4 * 128];
__device__ int g_err;
#define PROF(idx)
#define PROFP(idx)
#define STAMP(idx)
#define ASTAMP(idx)
#define SSTAMP(k, seg)
#define WSTAMP(idx)

#define DI __device__ __forceinline__
DI uint32_t smem_u32(const void* p) { return (uint32_t)__cvta_generic_to_shared(p); }
DI uint32_t clock32() { uint32_t c; asm volatile("mov.u32 %0, %%clock;" : "=r"(c) :: "memory"); return c; }
DI uint32_t gtime() { uint32_t c; asm volatile("mov.u32 %0, %%globaltimer_lo;" : "=r"(c) :: "memory"); return c; }
DI uint32_t ldg_relaxed32(const void* p) { uint32_t v; asm volatile("ld.relaxed.gpu.global.b32 %0, [%1];" : "=r"(v) : "l"(p) : "memory"); return v; }
DI uint32_t ldg_acquire32(const void* p) { uint32_t v; asm volatile("ld.acquire.gpu.global.b32 %0, [%1];" : "=r"(v) : "l"(p) : "memory"); return v; }
DI void stg_relaxed32(void* p, uint32_t v) { asm volatile("st.relaxed.gpu.global.b32 [%0], %1;" :: "l"(p), "r"(v) : "memory"); }
DI int head_id() { int c; asm volatile("mov.u32 %0, %%clusterid.x;" : "=r"(c)); return c; }
DI uint32_t mapa(uint32_t a, uint32_t r) { uint32_t o; asm("mapa.shared::cluster.u32 %0, %1, %2;" : "=r"(o) : "r"(a), "r"(r)); return o; }
DI void cluster_arrive() { asm volatile("barrier.cluster.arrive.relaxed.aligned;" ::: "memory"); }
DI void cluster_wait() { asm volatile("barrier.cluster.wait.aligned;" ::: "memory"); }
DI void cluster_sync() { asm volatile("barrier.cluster.arrive.release.aligned;\nbarrier.cluster.wait.acquire.aligned;" ::: "memory"); }
DI void mbar_init(uint32_t b, uint32_t c) { asm volatile("mbarrier.init.shared::cta.b64 [%0], %1;" :: "r"(b), "r"(c) : "memory"); }
DI void mbar_expect(uint32_t b, uint32_t tx) { asm volatile("mbarrier.arrive.expect_tx.shared::cta.b64 _, [%0], %1;" :: "r"(b), "r"(tx) : "memory"); }
DI void mbar_arrive(uint32_t b) { asm volatile("mbarrier.arrive.shared::cta.b64 _, [%0];" :: "r"(b) : "memory"); }
DI void mbar_wait(uint32_t b, uint32_t par) {
  asm volatile("{\n.reg .pred p;\n.reg .u32 n, q;\nmov.u32 n, 0;\n"
               "WL: add.u32 n, n, 1;\nshr.u32 q, n, 12;\nxor.b32 q, q, %1;\n"
               "mbarrier.try_wait.parity.shared::cta.b64 p, [%0], q;\n@!p bra.uni WL;\n}"
               :: "r"(b), "r"(par) : "memory");
}
DI void wait_until(uint32_t t) {
  const uint32_t now = gtime();
  t = min(t, now + 8192);
  asm volatile("{\n.reg .pred p;\n.reg .u32 c;\nTL: mov.u32 c, %%globaltimer_lo;\nsetp.lt.u32 p, c, %0;\n@p bra.uni TL;\n}" :: "r"(t) : "memory");
}
#define PIN(v) v = __shfl_xor_sync(0xffffffffu, v, 0)
#define SCHED_FENCE(k) asm volatile("{\n.reg .pred p;\nsetp.eq.u32 p, %0, %1;\n@p exit;\n}" :: "r"(fence_reg), "r"(k) : "memory")
#define MEM_ORDER(k) asm volatile("{\n.reg .pred p;\nsetp.eq.u32 p, %0, %1;\n@p st.shared.u32 [%0], %0;\n}" :: "r"(fence_reg), "r"(k + 64) : "memory")
DI void bar_sync(int id, int n) { asm volatile("bar.sync %0, %1;" :: "r"(id), "r"(n) : "memory"); }
DI void bar_arrive(int id, int n) { asm volatile("bar.arrive %0, %1;" :: "r"(id), "r"(n) : "memory"); }
DI void fence_async() { asm volatile("fence.proxy.async.shared::cta;" ::: "memory"); }
DI void st_async4(uint32_t a, uint32_t x, uint32_t y, uint32_t z, uint32_t w, uint32_t mb) {
  asm volatile("st.async.weak.shared::cluster.mbarrier::complete_tx::bytes.v4.b32 [%0], {%1,%2,%3,%4}, [%5];"
               :: "r"(a), "r"(x), "r"(y), "r"(z), "r"(w), "r"(mb) : "memory");
}
DI void st_async2(uint32_t a, uint32_t x, uint32_t y, uint32_t mb) {
  asm volatile("st.async.weak.shared::cluster.mbarrier::complete_tx::bytes.v2.b32 [%0], {%1,%2}, [%3];"
               :: "r"(a), "r"(x), "r"(y), "r"(mb) : "memory");
}
DI void sts32(uint32_t a, uint32_t x) { asm volatile("st.shared.b32 [%0], %1;" :: "r"(a), "r"(x) : "memory"); }
DI void sts64(uint32_t a, uint32_t x, uint32_t y) { asm volatile("st.shared.v2.b32 [%0], {%1,%2};" :: "r"(a), "r"(x), "r"(y) : "memory"); }
DI void sts128(uint32_t a, uint32_t x, uint32_t y, uint32_t z, uint32_t w) {
  asm volatile("st.shared.v4.b32 [%0], {%1,%2,%3,%4};" :: "r"(a), "r"(x), "r"(y), "r"(z), "r"(w) : "memory");
}
DI uint32_t lds32(uint32_t a) { uint32_t x; asm volatile("ld.shared.b32 %0, [%1];" : "=r"(x) : "r"(a) : "memory"); return x; }
DI void lds64(uint32_t a, uint32_t& x, uint32_t& y) { asm volatile("ld.shared.v2.b32 {%0,%1}, [%2];" : "=r"(x), "=r"(y) : "r"(a) : "memory"); }
DI void lds128(uint32_t a, uint32_t* r) {
  asm volatile("ld.shared.v4.b32 {%0,%1,%2,%3}, [%4];" : "=r"(r[0]), "=r"(r[1]), "=r"(r[2]), "=r"(r[3]) : "r"(a) : "memory");
}
DI void lds128f(uint32_t a, float* r) {
  asm volatile("ld.shared.v4.f32 {%0,%1,%2,%3}, [%4];" : "=f"(r[0]), "=f"(r[1]), "=f"(r[2]), "=f"(r[3]) : "r"(a) : "memory");
}
DI void lds64f(uint32_t a, float* r) { asm volatile("ld.shared.v2.f32 {%0,%1}, [%2];" : "=f"(r[0]), "=f"(r[1]) : "r"(a) : "memory"); }
DI void ldsm4t(uint32_t* r, uint32_t a) {
  asm volatile("ldmatrix.sync.aligned.m8n8.x4.trans.shared.b16 {%0,%1,%2,%3}, [%4];"
               : "=r"(r[0]), "=r"(r[1]), "=r"(r[2]), "=r"(r[3]) : "r"(a) : "memory");
}
DI void ldsm4t_in(uint32_t* r, uint32_t a, uint32_t t) {
  asm volatile("{\n.reg .pred p;\nsetp.ne.u32 p, %5, 0;\n@p ldmatrix.sync.aligned.m8n8.x4.trans.shared.b16 {%0,%1,%2,%3}, [%4];\n}"
               : "+r"(r[0]), "+r"(r[1]), "+r"(r[2]), "+r"(r[3]) : "r"(a), "r"(t) : "memory");
}
DI void lds128_in(uint32_t* r, uint32_t a, uint32_t t) {
  asm volatile("{\n.reg .pred p;\nsetp.ne.u32 p, %5, 0;\n@p ld.shared.v4.b32 {%0,%1,%2,%3}, [%4];\n}"
               : "+r"(r[0]), "+r"(r[1]), "+r"(r[2]), "+r"(r[3]) : "r"(a), "r"(t) : "memory");
}
DI void ldsm2t_in(uint32_t* r, uint32_t a, uint32_t t) {
  asm volatile("{\n.reg .pred p;\nsetp.ne.u32 p, %3, 0;\n@p ldmatrix.sync.aligned.m8n8.x2.trans.shared.b16 {%0,%1}, [%2];\n}" : "+r"(r[0]), "+r"(r[1]) : "r"(a), "r"(t) : "memory");
}
DI void reserve2(uint32_t* r) { asm volatile("{\n.reg .u64 t;\nmov.u64 t, %%clock64;\nmov.b64 {%0, %1}, t;\n}" : "=r"(r[0]), "=r"(r[1])); }
DI void scale_sum(float& x, float& y, float s, uint32_t t) {
  asm volatile("{\n.reg .pred p;\nsetp.ne.u32 p, %2, 0;\n@p mul.f32 %0, %0, %1;\n}" : "+f"(y) : "f"(s), "r"(t));
  asm volatile("{\n.reg .pred p;\nsetp.ne.u32 p, %3, 1;\n@p fma.rn.f32 %0, %0, %1, %2;\n}" : "+f"(x) : "f"(s), "f"(y), "r"(t));
}
DI void ldsm4(uint32_t* r, uint32_t a) {
  asm volatile("ldmatrix.sync.aligned.m8n8.x4.shared.b16 {%0,%1,%2,%3}, [%4];"
               : "=r"(r[0]), "=r"(r[1]), "=r"(r[2]), "=r"(r[3]) : "r"(a) : "memory");
}
DI void st_async1(uint32_t a, uint32_t x, uint32_t mb) {
  asm volatile("st.async.weak.shared::cluster.mbarrier::complete_tx::bytes.b32 [%0], %1, [%2];" :: "r"(a), "r"(x), "r"(mb) : "memory");
}
DI void stsm4(uint32_t a, uint32_t x, uint32_t y, uint32_t z, uint32_t w) {
  asm volatile("stmatrix.sync.aligned.m8n8.x4.shared.b16 [%0], {%1,%2,%3,%4};" :: "r"(a), "r"(x), "r"(y), "r"(z), "r"(w) : "memory");
}
DI void stsm4t(uint32_t a, uint32_t x, uint32_t y, uint32_t z, uint32_t w) {
  asm volatile("stmatrix.sync.aligned.m8n8.x4.trans.shared.b16 [%0], {%1,%2,%3,%4};" :: "r"(a), "r"(x), "r"(y), "r"(z), "r"(w) : "memory");
}
DI uint32_t pack_bf16(float lo, float hi) { uint32_t r; asm("cvt.rn.bf16x2.f32 %0, %1, %2;" : "=r"(r) : "f"(hi), "f"(lo)); return r; }
DI uint32_t pack_f16(float lo, float hi) { uint32_t r; asm("cvt.rn.f16x2.f32 %0, %1, %2;" : "=r"(r) : "f"(hi), "f"(lo)); return r; }
DI float ex2(float x) { float y; asm("ex2.approx.ftz.f32 %0, %1;" : "=f"(y) : "f"(x)); return y; }
DI float rcp(float x) { float y; asm("rcp.approx.ftz.f32 %0, %1;" : "=f"(y) : "f"(x)); return y; }
DI float bf_lo(uint32_t x) { return __uint_as_float(x << 16); }
DI float bf_hi(uint32_t x) { return __uint_as_float(x & 0xffff0000u); }
DI void mma16816(float* d, const uint32_t* a, uint32_t b0, uint32_t b1) {
  asm volatile("mma.sync.aligned.m16n8k16.row.col.f32.bf16.bf16.f32 {%0,%1,%2,%3}, {%4,%5,%6,%7}, {%8,%9}, {%0,%1,%2,%3};"
               : "+f"(d[0]), "+f"(d[1]), "+f"(d[2]), "+f"(d[3]) : "r"(a[0]), "r"(a[1]), "r"(a[2]), "r"(a[3]), "r"(b0), "r"(b1));
}
DI void mma16816z(float* d, const uint32_t* a, uint32_t b0, uint32_t b1) {
  asm volatile("mma.sync.aligned.m16n8k16.row.col.f32.bf16.bf16.f32 {%0,%1,%2,%3}, {%4,%5,%6,%7}, {%8,%9}, {%10,%10,%10,%10};"
               : "=f"(d[0]), "=f"(d[1]), "=f"(d[2]), "=f"(d[3]) : "r"(a[0]), "r"(a[1]), "r"(a[2]), "r"(a[3]), "r"(b0), "r"(b1), "f"(0.f));
}
DI void mma1688z(float* d, uint32_t a0, uint32_t a1, uint32_t b0) {
  asm volatile("mma.sync.aligned.m16n8k8.row.col.f32.bf16.bf16.f32 {%0,%1,%2,%3}, {%4,%5}, {%6}, {%7,%7,%7,%7};"
               : "=f"(d[0]), "=f"(d[1]), "=f"(d[2]), "=f"(d[3]) : "r"(a0), "r"(a1), "r"(b0), "f"(0.f));
}
DI void mma1688(float* d, uint32_t a0, uint32_t a1, uint32_t b0) {
  asm volatile("mma.sync.aligned.m16n8k8.row.col.f32.bf16.bf16.f32 {%0,%1,%2,%3}, {%4,%5}, {%6}, {%0,%1,%2,%3};"
               : "+f"(d[0]), "+f"(d[1]), "+f"(d[2]), "+f"(d[3]) : "r"(a0), "r"(a1), "r"(b0));
}
DI void ldsm2t(uint32_t* r, uint32_t a) {
  asm volatile("ldmatrix.sync.aligned.m8n8.x2.trans.shared.b16 {%0,%1}, [%2];" : "=r"(r[0]), "=r"(r[1]) : "r"(a) : "memory");
}
DI uint32_t add_bf16(uint32_t a, uint32_t b) { uint32_t r; asm("add.rn.bf16x2 %0, %1, %2;" : "=r"(r) : "r"(a), "r"(b)); return r; }
DI uint32_t mul_bf16(uint32_t a, uint32_t b) { uint32_t r; asm("mul.rn.bf16x2 %0, %1, %2;" : "=r"(r) : "r"(a), "r"(b)); return r; }
DI uint64_t make_desc(uint32_t addr, uint32_t lbo, uint32_t sbo, uint32_t swz) {
  return (uint64_t)((addr & 0x3FFFF) >> 4) | ((uint64_t)(lbo >> 4) << 16) | ((uint64_t)(sbo >> 4) << 32) | ((uint64_t)swz << 62);
}
#define WG_FENCE() asm volatile("wgmma.fence.sync.aligned;" ::: "memory")
#define WG_COMMIT() asm volatile("wgmma.commit_group.sync.aligned;" ::: "memory")
#define WG_WAIT(n) asm volatile("wgmma.wait_group.sync.aligned %0;" :: "n"(n) : "memory")
#define ACC8(d, o) "+f"(d[o]), "+f"(d[o + 1]), "+f"(d[o + 2]), "+f"(d[o + 3]), "+f"(d[o + 4]), "+f"(d[o + 5]), "+f"(d[o + 6]), "+f"(d[o + 7])
DI void wgmma_n32_rs(float* d, uint32_t a0, uint32_t a1, uint32_t a2, uint32_t a3, uint64_t db, int acc) {
  asm volatile("{\n.reg .pred p;\nsetp.ne.b32 p, %21, 0;\n"
               "wgmma.mma_async.sync.aligned.m64n32k16.f32.bf16.bf16 {%0,%1,%2,%3,%4,%5,%6,%7,%8,%9,%10,%11,%12,%13,%14,%15}, "
               "{%16,%17,%18,%19}, %20, p, 1, 1, 0;\n}\n"
               : ACC8(d, 0), ACC8(d, 8) : "r"(a0), "r"(a1), "r"(a2), "r"(a3), "l"(db), "r"(acc));
}
template <int TA>
DI void wgmma_n32_ss(float* d, uint64_t da, uint64_t db, int acc) {
  asm volatile("{\n.reg .pred p;\nsetp.ne.b32 p, %18, 0;\n"
               "wgmma.mma_async.sync.aligned.m64n32k16.f32.bf16.bf16 {%0,%1,%2,%3,%4,%5,%6,%7,%8,%9,%10,%11,%12,%13,%14,%15}, "
               "%16, %17, p, 1, 1, %19, 1;\n}\n"
               : ACC8(d, 0), ACC8(d, 8) : "l"(da), "l"(db), "r"(acc), "n"(TA));
}
DI void tma_load(uint32_t dst, const CUtensorMap* m, int c0, int c1, uint32_t mb) {
  asm volatile("cp.async.bulk.tensor.2d.shared::cluster.global.mbarrier::complete_tx::bytes [%0], [%1, {%3, %4}], [%2];"
               :: "r"(dst), "l"(m), "r"(mb), "r"(c0), "r"(c1) : "memory");
}
DI void tma_load3(uint32_t dst, const CUtensorMap* m, int row, uint32_t mb) {
  asm volatile("cp.async.bulk.tensor.3d.shared::cluster.global.mbarrier::complete_tx::bytes [%0], [%1, {%3, %4, %3}], [%2];"
               :: "r"(dst), "l"(m), "r"(mb), "r"(0), "r"(row) : "memory");
}
DI bool elect_one() {
  uint32_t p;
  asm volatile("{\n.reg .pred p;\nelect.sync _|p, 0xffffffff;\nselp.u32 %0, 1, 0, p;\n}" : "=r"(p));
  return p;
}
DI void bulk_s2s(uint32_t dst, uint32_t src, uint32_t bytes, uint32_t mb) {
  asm volatile("cp.async.bulk.shared::cluster.shared::cta.mbarrier::complete_tx::bytes [%0], [%1], %2, [%3];"
               :: "r"(dst), "r"(src), "r"(bytes), "r"(mb) : "memory");
}
DI void tma_prefetch(const CUtensorMap* m, int c0, int c1) {
  asm volatile("cp.async.bulk.prefetch.tensor.2d.L2.global.tile [%0, {%1, %2}];" :: "l"(m), "r"(c0), "r"(c1) : "memory");
}
DI void tma_store(const CUtensorMap* m, uint32_t src, int c0, int c1) {
  asm volatile("cp.async.bulk.tensor.2d.global.shared::cta.bulk_group [%0, {%2, %3}], [%1];" :: "l"(m), "r"(src), "r"(c0), "r"(c1) : "memory");
}
DI uint4 ldg_relaxed(const void* p) {
  uint4 v;
  asm volatile("ld.relaxed.gpu.global.v4.b32 {%0,%1,%2,%3}, [%4];" : "=r"(v.x), "=r"(v.y), "=r"(v.z), "=r"(v.w) : "l"(p) : "memory");
  return v;
}
DI void stg_relaxed(void* p, uint32_t x, uint32_t y, uint32_t z, uint32_t w) {
  asm volatile("st.relaxed.gpu.global.v4.b32 [%0], {%1,%2,%3,%4};" :: "l"(p), "r"(x), "r"(y), "r"(z), "r"(w) : "memory");
}
DI void red_f16x8(void* p, uint32_t x, uint32_t y, uint32_t z, uint32_t w) {
  asm volatile("red.relaxed.gpu.global.add.noftz.v4.f16x2 [%0], {%1,%2,%3,%4};" :: "l"(p), "r"(x), "r"(y), "r"(z), "r"(w) : "memory");
}
DI void sq_acc(uint32_t& a, uint32_t x) { asm("fma.rn.bf16x2 %0, %1, %1, %0;" : "+r"(a) : "r"(x)); }
DI __half2 amax4(__half2 h, const uint32_t* v) {
  h = __hmax2_nan(__hmax2_nan(h, __habs2(*(const __half2*)&v[0])), __habs2(*(const __half2*)&v[1]));
  return __hmax2_nan(__hmax2_nan(h, __habs2(*(const __half2*)&v[2])), __habs2(*(const __half2*)&v[3]));
}
DI uint32_t wexp(__half2 h) { const uint32_t u = *(const uint32_t*)&h; return __reduce_max_sync(0xffffffffu, max((u >> 16) & 0x7fffu, u & 0x7fffu)) >> 7; }
DI float max10(const float* a) {
  return fmaxf(fmaxf(fmaxf(fmaxf(a[0], a[1]), fmaxf(a[2], a[3])), fmaxf(fmaxf(a[4], a[5]), fmaxf(a[6], a[7]))), fmaxf(a[8], a[9]));
}
DI float quad_max(float m) {
  return fmaxf(fmaxf(m, __shfl_xor_sync(0xffffffffu, m, 1)), fmaxf(__shfl_xor_sync(0xffffffffu, m, 2), __shfl_xor_sync(0xffffffffu, m, 3)));
}
DI float warp_sum(float v) {
#pragma unroll
  for (int o = 16; o; o >>= 1) v += __shfl_xor_sync(0xffffffffu, v, o);
  return v;
}

constexpr int SM_WO3 = 0;
constexpr int SM_X = 16384;
constexpr int XT = 36864;
constexpr int SM_EXP = 126976;
constexpr int SEGB = 10240;
constexpr int SM_BLK = SM_EXP + 8192;
constexpr int SM_VC = SM_BLK + 4 * SEGB;
constexpr int SM_PART = SM_VC + 16384;
constexpr int SM_QM = SM_PART + 4096;
constexpr int SM_E = SM_QM + 1024;
constexpr int SM_VM = SM_E + 1536;
constexpr int SM_OB = SM_VM + 2048;
constexpr int SM_FB = SM_OB + 2048;
constexpr int SM_STAGE = SM_X + XT;
constexpr int SM_MISC = 210944;
constexpr int SM_WOST = 212992;
constexpr int SM_MEM = SM_WOST;
constexpr int SM_MAX = SM_MEM + 11264;
#define MEM_BLK(q) ((q) / 3 * 4096 + (q) % 3 * 1024)
constexpr int SM_TOTAL = 229376;
constexpr int MB_W = SM_MISC;
constexpr int MB_WO = SM_MISC + 24;
constexpr int MB_WO3 = SM_MISC + 32;
constexpr int MB_X = SM_MISC + 40;
constexpr int MB_S = SM_MISC + 64;
constexpr int MB_F = SM_MISC + 72;
constexpr int MB_VX = SM_MISC + 80;
constexpr int SC_FPAR = SM_MISC + 136;
constexpr int SC_DEAD = SM_MISC + 96;
constexpr int SC_UNSC = SM_MISC + 112;
constexpr int SC_EXPW = SM_MISC + 132;
constexpr int SC_ONES = SM_MISC + 144;
constexpr int SC_SS = SM_MISC + 160;
constexpr int SC_LAT = SM_MISC + 224;
constexpr int SC_XMAX = SM_MISC + 256;
constexpr int SC_PROF = 229376;

constexpr float SM_SCALE = 0.08838834764831845f;
constexpr float LOG2E = 1.4426950408889634f;
constexpr float E_LIM = 20.f;

template <bool B> struct BoolC { static constexpr bool value = B; };
struct RMaps { CUtensorMap x, wq, wk, wv, wo; unsigned char* red; uint32_t poll; };

DI uint32_t latest_hint(uint32_t h, uint32_t d, int s) {
  const uint32_t x = (((h | 0xc0c0c0c0u) - ((d >> 5) & 63) * 0x01010101u) & 0x3f3f3f3fu) | ((h ^ (((s >> 2) + 1) & 3) * 0x40404040u) & 0xc0c0c0c0u);
  const uint32_t y = __vmaxu2(x & 0x00ff00ffu, (x >> 8) & 0x00ff00ffu);
  return __reduce_max_sync(0xffffffffu, max(y & 0xffffu, y >> 16));
}
DI uint32_t near_half(uint32_t sb) {
  uint32_t a, b; lds64(sb + SC_LAT, a, b);
  return a > b;
}

template <int RT, int K0, int K1, bool D32 = false>
DI void xproj(float* acc, const uint32_t (&wa)[2][18][4], uint64_t xd) {
  if (XP & 1) return;
  WG_FENCE();
#pragma unroll
  for (int k = K0; k < ((XP & 128) ? K0 + 1 : K1); k++)
  {
    uint64_t d = xd + (uint64_t)(((k >> 1) * 4096 + (k & 1) * 32) >> 4);
    if (D32) asm("mov.b64 %0, {%1, %2};" : "=l"(d) : "r"((uint32_t)xd + (((k >> 1) * 4096 + (k & 1) * 32) >> 4)), "r"((uint32_t)(xd >> 32)));
    wgmma_n32_rs(acc, wa[RT][k][0], wa[RT][k][1], wa[RT][k][2], wa[RT][k][3], d, k != 0);
  }
  WG_COMMIT();
}

DI void seg_store(int seg, uint32_t sb, uint32_t off, uint32_t bytes) {
  asm volatile("cp.async.bulk.global.shared::cta.bulk_group [%0], [%1], %2;"
               :: "l"(g_seg + ((size_t)(seg & RING) * 96 + blockIdx.x) * SEGB + off), "r"(sb + SM_BLK + (seg & 3) * SEGB + off), "r"(bytes) : "memory");
  asm volatile("cp.async.bulk.commit_group;" ::: "memory");
}
DI void seg_publish(int seg) {
  asm volatile("cp.async.bulk.wait_group 0;" ::: "memory");
  asm volatile("red.relaxed.gpu.global.add.u32 [%0], 1;" :: "l"(&g_scnt[(seg * 32 + blockIdx.x / 3) * 8]) : "memory");
  SSTAMP(10, seg);
}

DI void proj_role(const uint32_t sb, const RMaps& tm, const uint32_t rank, const int wg, const int w, const int lane) {
  const bool qk = rank < 2;
  uint32_t wa[2][18][4];
  {
    const int rr = (lane & 7) + ((lane >> 4) << 3);
    const uint32_t col = ((2 * w + ((lane >> 3) & 1)) ^ (lane & 7)) << 4;
    float ss = 0.f;
#pragma unroll
    for (int c = 0; c < 3; c++) {
      mbar_wait(sb + MB_W + 8 * c, 0);
#pragma unroll
      for (int rt = 0; rt < 2; rt++)
#pragma unroll
        for (int k = 0; k < 6; k++)
          ldsm4t(wa[rt][c * 6 + k], sb + SM_STAGE + c * 49152 + (rt ^ wg) * 24576 + (64 * (k >> 1) + 32 * wg + 16 * (k & 1) + rr) * 128 + col);
      if (c < 2) {
        fence_async();
        bar_sync(3, 256);
        if (threadIdx.x == 0) {
          if (c == 0) tma_load3(sb + SM_X + XT, &tm.x, 32, sb + MB_X + 8);
          else tma_load(sb + SM_X + 2 * XT, &tm.wo, rank * 192, (blockIdx.x / 3) * DH, sb + MB_WO);
        }
        __syncwarp();
      }
      uint32_t q[4] = {0, 0, 0, 0};
#pragma unroll
      for (int rt = 0; rt < 2; rt++)
#pragma unroll
        for (int k = 0; k < 6; k++)
#pragma unroll
          for (int i = 0; i < 4; i++) sq_acc(q[i], wa[rt][c * 6 + k][i]);
#pragma unroll
      for (int i = 0; i < 4; i++) ss += bf_lo(q[i]) + bf_hi(q[i]);
    }
    ss = warp_sum(ss);
    fence_async();
    cluster_arrive();
    if (lane == 0) sts32(sb + SC_SS + 4 * (wg * 4 + w), qk ? 0 : __float_as_uint(ss));
    bar_arrive(11, 384);
  }
  STAMP(1);
  mbar_wait(sb + MB_X, 0);
  STAMP(2);

  uint32_t t16 = sb + (w * 32 + lane) * 16;
  uint32_t mem_a = sb + SM_MEM + wg * 512 + lane * 16;
  uint32_t fin_a = sb + (lane & 7) * 16 + SM_BLK + (qk ? (wg ^ 1) * 4096 + w * 256 + (lane & 8) * 16 + (lane & 16) * 64
                                              : wg * 4096 + w * 1024 + (lane & 8) * 64 + (lane & 16) * 8);
  PIN(t16); PIN(mem_a); PIN(fin_a);
  const uint32_t fence_reg = mem_a;
  const uint32_t fin2 = qk ? 2048 : 256;
  float acc[16];
  const uint64_t xd0 = make_desc(sb + SM_X + wg * 64, 16, 1024, 1);
  auto do_export = [&]() {
    WG_WAIT(0);
#pragma unroll
    for (int i = 0; i < 2; i++)
      sts128(t16 + SM_EXP + wg * 4096 + i * 2048, pack_bf16(acc[8 * i], acc[8 * i + 1]), pack_bf16(acc[8 * i + 2], acc[8 * i + 3]),
             pack_bf16(acc[8 * i + 4], acc[8 * i + 5]), pack_bf16(acc[8 * i + 6], acc[8 * i + 7]));
  };
  uint32_t o[8];
  auto import = [&]() { lds128(t16 + SM_EXP + (wg ^ 1) * 4096, o); lds128(t16 + SM_EXP + (wg ^ 1) * 4096 + 2048, o + 4); };
  auto finish = [&](int seg) {
    const uint32_t a = fin_a + (seg & 3) * SEGB;
    WG_WAIT(0);
#pragma unroll
    for (int i = 0; i < 8; i++) o[i] = FIN16 ? add_bf16(pack_bf16(acc[2 * i], acc[2 * i + 1]), o[i]) : pack_bf16(acc[2 * i] + bf_lo(o[i]), acc[2 * i + 1] + bf_hi(o[i]));
    stsm4(a, o[0], o[1], o[2], o[3]);
    stsm4(a + fin2, o[4], o[5], o[6], o[7]);
  };
  auto send_v = [&](int seg, int dst) {
    fence_async();
    if (seg < NSEG - 1 && !(XP & 2) && elect_one())
      bulk_s2s(mapa(sb + SM_VC + (seg & 1) * 8192, dst), sb + SM_BLK + (seg & 3) * SEGB, 8192, mapa(sb + MB_VX + (seg & 1) * 8, dst));
    __syncwarp();
  };
  auto wait_v = [&](int seg) {
    if (seg < NSEG - 1 && !(XP & 2)) {
      mbar_wait(sb + MB_VX + (seg & 1) * 8, (seg >> 1) & 1);
      if (elect_one()) mbar_expect(sb + MB_VX + (seg & 1) * 8, 8192);
      __syncwarp();
    }
  };
  bar_sync(3, 256);
  xproj<1, 0, 18>(acc, wa, xd0);
  do_export();
  SCHED_FENCE(11);
  xproj<0, 0, 18>(acc, wa, xd0);
  bar_sync(3, 256);
  cluster_wait();
  mbar_wait(sb + MB_X + 8, 0);
  import();
  finish(0);
  SCHED_FENCE(12);
  bar_sync(3, 256);
  uint64_t dA = xd0 + (XT >> 4);
  xproj<1, 0, 18>(acc, wa, dA);
  if (!qk && wg == 0 && w < 2) send_v(0, w);
  do_export();
  if (qk && wg == 0 && w == 0) wait_v(0);
  bar_arrive(13, 384);
  if (!qk) {
    SCHED_FENCE(15);
    xproj<0, 0, 18>(acc, wa, dA);
    if (threadIdx.x == 0 && !(XP & 8)) { mbar_expect(sb + MB_X, XT); tma_load3(sb + SM_X, &tm.x, 96, sb + MB_X); }
    bar_sync(3, 256);
    mbar_wait(sb + MB_X + 16, 0);
    import();
    finish(1);
    SCHED_FENCE(16);
    bar_sync(3, 256);
    dA += XT >> 4;
    xproj<1, 0, 18>(acc, wa, dA);
    if (wg == 0 && w < VW2) send_v(1, w);
    do_export();
  }
  bar_sync(0, 384);
  const int ro = __shfl_sync(0xffffffffu, near_half(sb) ^ wg, 0);
  STAMP(5);
  const uint32_t always = __shfl_sync(0xffffffffu, lds32(sb + SC_DEAD + 12), 0);
  const int ah = qk ? 1 : 2;
  int b2 = qk ? 2 : 0;
  int s = 0;
  uint32_t hint_lo = (uint32_t)(uint64_t)tm.red + HINT_OFF + blockIdx.x + (lane & 1) * 4096 + (lane >> 1) * 16384;
  PIN(hint_lo);
  auto post_hint = [&]() {
    asm volatile("{\n.reg .pred p;\n.reg .b64 a;\n.reg .u32 t;\nsetp.lt.u32 p, %0, %1;\nmov.b64 a, {%2, %3};\nmov.u32 t, %%globaltimer_lo;\n"
                 "bfe.u32 t, t, 5, 6;\nor.b32 t, t, %4;\n@p st.relaxed.gpu.global.u8 [a], t;\n}"
                 :: "r"(t16), "r"(sb + 128), "r"(hint_lo + RED_SLOT(s)), "r"((uint32_t)((uint64_t)tm.red >> 32)), "r"(((s >> 2) + 1) << 6) : "memory");
  };
  auto memproj = [&](auto second, int id, float u0, float u1, float* r) {
    constexpr bool R1 = decltype(second)::value;
    uint32_t b[NUP][4], b0[4];
    SCHED_FENCE(id);
    bar_sync(R1 ? 2 : 1, 256);
    PROF(0);
    ldsm4t(b0, mem_a);
#pragma unroll
    for (int q = 0; q < NUP; q++) {
      if (R1 && q == 2) {
        bar_sync(11, 256);
        SCHED_FENCE(id + 1);
      }
      ldsm4t(b[q], mem_a + MEM_BLK(q + 1));
    }
    mma16816z(&acc[0], wa[0][0], b0[0], b0[1]);
    mma16816z(&acc[4], wa[1][0], b0[0], b0[1]);
    mma16816z(&acc[8], wa[0][1], b0[2], b0[3]);
    mma16816z(&acc[12], wa[1][1], b0[2], b0[3]);
#pragma unroll
    for (int q = 1; q < 9; q++) {
      uint32_t* const c = b[(q - 1) % NUP];
      mma16816(&acc[0], wa[0][2 * q], c[0], c[1]);
      mma16816(&acc[4], wa[1][2 * q], c[0], c[1]);
      mma16816(&acc[8], wa[0][2 * q + 1], c[2], c[3]);
      mma16816(&acc[12], wa[1][2 * q + 1], c[2], c[3]);
      if (R1 && q + NUP == B3Q) bar_sync(3, 256);
      if (q + NUP < 9) ldsm4t_in(c, mem_a + MEM_BLK(q + NUP), always);
      else if (R1 && q + NUP < 11) lds128_in(c, t16 + SM_PART + (10 - q - NUP) * 2048, always);
      else if (!R1 && GATE && q == GATE) { bar_arrive(11, 256); lds128_in(c, sb + SC_DEAD, always); u0 = u1 = __uint_as_float(c[3]); }
    }
#pragma unroll
    for (int i = 0; i < 8; i++) {
      const float u = i < 4 ? u0 : u1;
      r[i] = R1 ? fmaf(acc[8 + i], u, (acc[i] + __uint_as_float(b[(8 + i / 4) % NUP][i & 3])) * u) : (GATE ? fmaf(acc[i], u, acc[8 + i]) : acc[i] + acc[8 + i]);
    }
  };
  if (ro == 0) {
#pragma unroll 1
    while (true) {
      if (s == 8) STAMP(6);
      float r[8];
      memproj(BoolC<false>(), 30, 0.f, 0.f, r);
      sts128(t16 + SM_PART, __float_as_uint(r[0]), __float_as_uint(r[1]), __float_as_uint(r[2]), __float_as_uint(r[3]));
      sts128(t16 + SM_PART + 2048, __float_as_uint(r[4]), __float_as_uint(r[5]), __float_as_uint(r[6]), __float_as_uint(r[7]));
      bar_arrive(3, 256);
      PROF(1);
      bar_sync(9, 256);
      if (s == NSEG - 1) break;
      post_hint();
      if (w == 1) {
        uint32_t m[8];
        lds128(t16 + SM_MAX - 512, m); lds128(t16 + SM_MAX, m + 4);
        const int em = (wexp(amax4(amax4(*(const __half2*)&m[0], m), m + 4)) >> 3) + (int)(lds32(sb + SC_UNSC + (s & 1) * 8) >> 23) - 15;
        const int ex = max(s ? em : 0, (int)lds32(sb + SC_XMAX + 4 * s)) - 127 + (int)lds32(sb + SC_EXPW);
        sts32(sb + SC_UNSC + (~s & 1) * 8, (127 + min(max(ex, -120), 120)) << 23);
        __syncwarp();
        if (elect_one()) mbar_arrive(sb + MB_S);
      }
      SCHED_FENCE(9);
      bar_sync(5, qk ? N5 : 256);
      PROF(2);
      import();
      xproj<0, 0, NII>(acc, wa, dA);
      if (NII < 18) {
        if (qk) bar_sync(7, 384);
        xproj<0, NII, 18>(acc, wa, dA);
        if (!qk) bar_sync(7, 384);
      } else {
        if (F10) WG_WAIT(0);
        bar_sync(10, 256);
        if (F10) SCHED_FENCE(17);
      }
      dA += (int64_t)(b2 ? XT >> 4 : -(XT >> 3));
      finish(s + ah);
      if (qk || w >= VW2) bar_arrive(13, 384);
      PROF(6);
      SCHED_FENCE(14);
      bar_sync(12, 256);
      PROF(7);
      xproj<1, 0, 18, true>(acc, wa, dA);
      bar_arrive(14, 256);
      b2 = b2 == 2 ? 0 : b2 + 1;
      s++;
      if (!qk && w < VW2) { bar_sync(13, 384); send_v(s + 1, w); }
      PROFP(8);
      do_export();
      PROFP(3);
    }
    if (!qk) bar_arrive(5, 256);
  } else {
#pragma unroll 1
    while (true) {
      if (s == 8) STAMP(6);
      const uint32_t tl = ((t16 >> 8) ^ wg) & 1, am = (t16 & ~256u) - w * 256;
      const float un = __uint_as_float(lds32(sb + SC_UNSC + (s & 1) * 8));
      float r[8];
      if (qk) {
        uint32_t a0 = am + (tl ? SM_QM : SM_BLK + 8192 + (s & 3) * SEGB);
        float u0 = wg ? un * (SM_SCALE * LOG2E) : un, u1 = wg ? un : un * (SM_SCALE * LOG2E);
        PIN(a0); PIN(u0); PIN(u1);
        memproj(BoolC<true>(), 32, u0, u1, r);
        stsm4(a0, pack_bf16(r[0], r[1]), pack_bf16(r[2], r[3]), pack_bf16(r[4], r[5]), pack_bf16(r[6], r[7]));
        bar_arrive(4, 256);
      } else {
        const uint32_t d0 = s < NSEG - 1 ? 0 : 2, d1 = s < NSEG - 1 ? 1 : 2;
        uint32_t r0 = mapa(t16 + SM_VM, d0), r1 = mapa(t16 + SM_VM, d1);
        PIN(r0); PIN(r1);
        memproj(BoolC<true>(), 34, un, un, r);
        const uint32_t p0 = pack_bf16(r[0], r[1]), p1 = pack_bf16(r[2], r[3]), p2 = pack_bf16(r[4], r[5]), p3 = pack_bf16(r[6], r[7]);
        const uint32_t v0 = wg ? p2 : p0, v1 = wg ? p3 : p1, v2 = wg ? p0 : p2, v3 = wg ? p1 : p3;
        st_async4(r0, v0, v1, v2, v3, mapa(sb + MB_S, d0));
        st_async4(r1, v0, v1, v2, v3, mapa(sb + MB_S, d1));
        bar_arrive(5, 256);
        if (EXB && s < NSEG - 1) bar_arrive(15, 160);
        sts128(t16 + SM_VM, v0, v1, v2, v3);
        stsm4(am + SM_BLK + 8192 + (s & 3) * SEGB + tl * 1024, p0, p1, p2, p3);
        __syncwarp();
        if (elect_one()) mbar_arrive(sb + MB_S);
      }
      if (s == NSEG - 1) break;
      PROF(1);
      auto rearm = [&]() { mbar_wait(sb + MB_S, s & 1); if (elect_one()) mbar_expect(sb + MB_S, qk ? 640 + 2048 : 1280); __syncwarp(); };
      if (w == 1) {
        if ((t16 & 384) == 0) stg_relaxed(tm.red + (RED_SLOT(s + 2) + RED_LINE(blockIdx.x)) + (t16 & 112), 0, 0, 0, 0);
      } else if (w == 0) {
        const int tn = s + ah + 1;
        if (RFW) mbar_wait(sb + MB_S, s & 1);
        if (tn + 1 < NSEG && !(XP & 8) && elect_one()) {
          const int b0 = b2 == 2 ? 0 : b2 + 1;
          mbar_expect(sb + MB_X + 8 * b0, XT);
          tma_load3(sb + SM_X + b0 * XT, &tm.x, (tn + 1) * 32, sb + MB_X + 8 * b0);
        }
        if (tn < NSEG && (!(XP & 8) || tn < 3)) mbar_wait(sb + MB_X + 8 * b2, (tn / 3) & 1);
      } else if (w == 2) {
        if (!qk) { if (VW2 < 1) send_v(s + 1, 0); if (VW2 < 2) send_v(s + 1, 1); }
      } else if (qk || !NIC) {
        rearm();
      }
      __syncwarp();
      import();
      PROF(4);
      SCHED_FENCE(10);
      if (NIC) {
        if (qk) bar_sync(7, NII < 18 ? 384 : 256);
        xproj<0, 0, NIC>(acc, wa, dA);
        if (!qk) { if (w == 3) rearm(); bar_sync(7, NII < 18 ? 384 : 256); }
      } else {
        bar_sync(7, NII < 18 ? 384 : 256);
      }
      xproj<0, NIC, 18>(acc, wa, dA);
      bar_arrive(12, 256);
      dA += (int64_t)(b2 ? XT >> 4 : -(XT >> 3));
      finish(s + ah);
      if (qk && w == 0) wait_v(s + 1);
      bar_arrive(13, 384);
      PROF(6);
      SCHED_FENCE(13);
      bar_sync(14, 256);
      PROF(7);
      xproj<1, 0, 18>(acc, wa, dA);
      b2 = b2 == 2 ? 0 : b2 + 1;
      s++;
      PROFP(8);
      do_export();
      PROFP(3);
    }
  }
  bar_arrive(0, 384);
  STAMP(3);
  cluster_sync();
  STAMP(4);
}

DI void attn_role(const uint32_t sb, unsigned char* smem_raw, const RMaps& tm, const uint32_t RANK, const bf16* __restrict__ x, const bf16* __restrict__ mem0,
                  const int w, const int lane) {
  const int t2 = w * 32 + lane;
  uint32_t wo[8][4], w1[8][4];
  const uint32_t wo_lane = sb + ((lane & 7) + ((lane >> 4) << 3)) * 128 + (((w + 4 * ((lane >> 3) & 1)) ^ (lane & 7)) << 4);
  unsigned char* const g_red = tm.red;
  {
    const uint32_t tag = *(volatile unsigned*)&g_epoch + 1;
    if (w == 0) {
      stg_relaxed(g_red + RED_SLOT(t2 >> 3) + RED_LINE(blockIdx.x) + (t2 & 7) * 16, 0, 0, 0, 0);
      asm volatile("st.relaxed.gpu.global.u8 [%0], 0;" :: "l"(g_red + RED_SLOT(t2) + HINT_OFF + (t2 & 4) * 1024 + (t2 >> 3) * 16384 + blockIdx.x) : "memory");
    }
    uint4 mv[5], xv[18];
#pragma unroll
    for (int i = 0; i < 5; i++) mv[i] = t2 + 128 * i < DM ? ((const uint4*)mem0)[t2 + 128 * i] : make_uint4(0, 0, 0, 0);
#pragma unroll
    for (int i = 0; i < 18; i++) xv[i] = blockIdx.x < NSEG ? ((const uint4*)(x + blockIdx.x * 32 * DM))[t2 + 128 * i] : make_uint4(0, 0, 0, 0);
    bar_sync(0, 384);
    cluster_arrive();
    __half2 hx = __float2half2_rn(0.f);
#pragma unroll
    for (int i = 0; i < 18; i++) hx = amax4(hx, &xv[i].x);
    if (blockIdx.x == 0)
#pragma unroll
      for (int i = 0; i < 5; i++) hx = amax4(hx, &mv[i].x);
    sts32(sb + SC_SS + 4 * (12 + w), wexp(hx));
    if (t2 == 0) { sts32(sb + SC_UNSC, __float_as_uint(1.f)); sts128(sb + SC_DEAD, 0, 0, 0, 0x3f800000u); sts64(sb + SC_FPAR, 0, 0); sts128(sb + SC_ONES, 0x3f803f80u, 0x3f803f80u, 0x3f803f80u, 0x3f803f80u); }
    WSTAMP(27);
    if (w == 0) __threadfence();
    uint32_t q[8] = {0, 0, 0, 0, 0, 0, 0, 0};
    mbar_wait(sb + MB_WO3, 0);
#pragma unroll
    for (int k = 0; k < 8; k++) {
      ldsm4t(wo[k], wo_lane + SM_WO3 + k * 2048); ldsm4t(w1[k], wo_lane + SM_WOST + k * 2048);
#pragma unroll
      for (int i = 0; i < 4; i++) { sq_acc(q[i], wo[k][i]); sq_acc(q[i], w1[k][i]); }
    }
    bar_sync(6, 128);
#pragma unroll
    for (int k = 0; k < 8; k++) sts128(sb + SM_WO3 + t2 * 16 + k * 2048, wo[k][0], wo[k][1], wo[k][2], wo[k][3]);
#pragma unroll
    for (int i = 0; i < 5; i++) {
      const int e = t2 + 128 * i, tok = e / 72, c = (e - tok * 72) * 8;
      const uint32_t u[4] = {mv[i].x, mv[i].y, mv[i].z, mv[i].w};
      if (e < DM)
#pragma unroll
        for (int j = 0; j < 8; j++) *(unsigned short*)(smem_raw + SM_MEM + (c + c / 192 * 64 + j) * 16 + tok * 2) = (unsigned short)(u[j >> 1] >> (16 * (j & 1)));
    }
    bar_arrive(1, 256); bar_arrive(2, 256); bar_arrive(9, 256);
    mbar_wait(sb + MB_WO, 0);
#pragma unroll
    for (int k = 0; k < 8; k++) ldsm4t(wo[k], wo_lane + SM_X + 2 * XT + k * 2048);
    fence_async();
    bar_sync(6, 128);
    if (t2 == 32) tma_load3(sb + SM_X + 2 * XT, &tm.x, 64, sb + MB_X + 16);
    __syncwarp();
#pragma unroll
    for (int k = 0; k < 8; k++)
#pragma unroll
      for (int i = 0; i < 4; i++) sq_acc(q[4 + i], wo[k][i]);
    float ss = 0.f;
#pragma unroll
    for (int i = 0; i < 8; i++) ss += bf_lo(q[i]) + bf_hi(q[i]);
    ss = warp_sum(ss);
    if (lane == 0) sts32(sb + SC_SS + 4 * (8 + w), __float_as_uint(ss));
    bar_sync(11, 384);
    if (t2 == 0) {
      float a[16];
#pragma unroll
      for (int i = 0; i < 4; i++) lds128f(sb + SC_SS + 16 * i, &a[4 * i]);
      stg_relaxed(&g_stats[blockIdx.x * 2], __float_as_uint(((a[0] + a[1]) + (a[2] + a[3])) + ((a[4] + a[5]) + (a[6] + a[7]))),
                  __float_as_uint((a[8] + a[9]) + (a[10] + a[11])),
                  max(max(__float_as_uint(a[12]), __float_as_uint(a[13])), max(__float_as_uint(a[14]), __float_as_uint(a[15]))), tag);
    }
    __syncwarp();
    WSTAMP(24);
    cluster_wait();
    if (w == 0) {
      uint4 v[3];
      int n = 0;
      while (true) {
#pragma unroll
        for (int i = 0; i < 3; i++) v[i] = ldg_relaxed(&g_stats[(i * 32 + lane) * 2]);
        if (__all_sync(0xffffffffu, v[0].w == tag && v[1].w == tag && v[2].w == tag) || ++n > SPIN_LIMIT) break;
        __nanosleep(100);
      }
      WSTAMP(25);
      const float sv = warp_sum(__uint_as_float(v[0].x) + __uint_as_float(v[1].x) + __uint_as_float(v[2].x));
      const float so = warp_sum(__uint_as_float(v[0].y) + __uint_as_float(v[1].y) + __uint_as_float(v[2].y));
      const int expW = ((int)(__float_as_uint(sv) >> 23) + (int)(__float_as_uint(so) >> 23) - 254 + 2 + 10 + 1) >> 1;
      sts32(sb + SC_XMAX + 4 * lane, v[0].z); sts32(sb + SC_XMAX + 128 + 4 * lane, v[1].z);
      sts32(sb + SC_EXPW, expW + 1 - 15);
      if (blockIdx.x == 0 && lane == 0) *(volatile unsigned*)&g_epoch = tag;
      sts32(sb + SC_FPAR + 4, 1);
    } else if (w < 3) {
      const uint32_t u = blockIdx.x >> 4;
      unsigned char* const z = g_red + 98304 + (blockIdx.x & 15) * 128 + (u & 1) * 2048 + (u & 6) * 4096 + (((u >> 1) ^ w) & 1) * 4096 + lane * 4;
      stg_relaxed32(z, 0);
      uint32_t best = 0xffffffffu;
#pragma unroll 1
      for (int i = 0; i < 64; i++) {
        uint32_t last, dt;
        asm volatile("{\n.reg .pred p;\n.reg .u32 c, v;\nld.volatile.shared.u32 %0, [%3];\nmov.u32 c, %%clock;\n"
                     "atom.relaxed.gpu.global.exch.b32 v, [%2], 0;\nsetp.eq.u32 p, v, 0;\nmov.u32 %1, 0;\n@p mov.u32 %1, %%clock;\nsub.u32 %1, %1, c;\n}"
                     : "=r"(last), "=r"(dt) : "l"(z), "r"(sb + SC_FPAR + 4) : "memory");
        best = min(best, dt);
        if (last && i >= NPROBE - 1) break;
      }
      sts32(sb + SC_LAT + (w - 1) * 4, best);
    }
    bar_sync(13, 384);
    bar_arrive(0, 384);
    WSTAMP(26);
  }

  const uint32_t nh = __shfl_sync(0xffffffffu, near_half(sb), 0);
  uint32_t l16 = sb + lane * 16;
  PIN(l16);
#define LV ((l16 >> 4) & 31)
#define fence_reg l16
  const uint32_t red_lo = (uint32_t)(uint64_t)g_red, red_hi = (uint32_t)((uint64_t)g_red >> 32);
  uint32_t lp;
  auto slot = [&](int s, uint32_t c, uint32_t ofs) {
    const uint32_t lo = lp | (red_lo + ((w >> 1) * 4 + (w & 1) * 2 + ((w ^ c) & 1)) * 4096 + RED_SLOT(s) + ofs);
    uint64_t a; asm("mov.b64 %0, {%1, %2};" : "=l"(a) : "r"(lo), "r"(red_hi));
    return (unsigned char*)a;
  };
  const uint32_t always = __shfl_sync(0xffffffffu, lds32(sb + SC_DEAD + 12), 0);
  const int mode0 = RANK < 2 ? w : w | 4;
  auto hint_addr = [&](int s) { return min(LV, 23u) * 4 + (red_lo + HINT_OFF + nh * 4096 + w * 16384 + RED_SLOT(s)); };
  auto load_hints = [&](uint32_t lo) {
    uint64_t a; asm("mov.b64 %0, {%1, %2};" : "=l"(a) : "r"(lo), "r"(red_hi));
    return ldg_relaxed32((const void*)a);
  };
  const uint32_t blk = RANK < 2 ? 9216 : SEGB, exb = RANK < 2 ? EXB : EXB2;
  auto export_rest = [&](int seg) { if (EXB && !(XP & 4) && elect_one()) seg_store(seg, sb, exb, blk - exb); __syncwarp(); };
  auto export_seg = [&](int seg) {
    if (!(XP & 4) && elect_one()) {
      if (seg > 0) seg_publish(seg - 1);
      fence_async();
      seg_store(seg, sb, 0, EXB ? exb : blk);
    }
    __syncwarp();
  };
  uint32_t dl = __shfl_sync(0xffffffffu, gtime() - 768, 0);
  int s = 0;
  bool bad = false;
#pragma unroll 1
  while (true) {
    const uint32_t par = s & 1;
    uint32_t vx[4][4], hints;
    auto load_vx = [&]() {
      const uint32_t va = l16 + (RANK < 2 ? SM_VC + par * 8192 : SM_BLK + (s & 3) * SEGB) + w * 1024 + ((LV >> 3) & 1) * 384 - (LV >> 4) * 128;
#pragma unroll
      for (int i = 0; i < 4; i++) ldsm4(vx[i], va + (i & 1) * 4096 + (i >> 1) * 256);
    };
    auto retire = [&](uint32_t x) {
      asm volatile("{\n.reg .pred p;\nsetp.eq.u32 p, %0, 0;\n@p exit;\n}" :: "r"(vx[0][0] | vx[1][0] | vx[2][0] | vx[3][0] | x) : "memory");
    };
    auto scores = [&](auto memkeys, auto first, float* sc) {
      constexpr bool MK = decltype(memkeys)::value, FIRST = decltype(first)::value;
      uint32_t kb[4][4], qb[2][4];
      const uint32_t m = LV >> 3;
      uint32_t kaddr = l16 + SM_BLK + 4096 + (s & 3) * SEGB + w * 2048 + (m & 1) * (MK ? 128 : 896) - (m >> 1) * 128;
      if (MK) { PIN(kaddr); }
      else {
#pragma unroll
        for (int k = 0; k < 4; k++) ldsm4t(kb[k], kaddr + k * 256);
      }
      if (FIRST) { load_vx(); retire(MK ? kaddr : kb[0][0] | kb[1][0] | kb[2][0] | kb[3][0] | l16); bar_sync(4, 256); PROF(4); }
      ldsm4t(qb[0], l16 + SM_QM);
      if (MK) ldsm4t(kb[0], kaddr);
      ldsm4t(qb[1], l16 + SM_QM + 512);
      if (MK) ldsm4t(kb[2], kaddr + 512);
      float c[4][4];
      mma16816z(c[0], kb[0], qb[0][0], qb[0][1]); mma16816z(c[1], kb[MK ? 0 : 1], qb[0][2], qb[0][3]);
      mma16816z(c[2], kb[2], qb[1][0], qb[1][1]); mma16816z(c[3], kb[MK ? 2 : 3], qb[1][2], qb[1][3]);
      if (FIRST && B5POS == 0) bar_arrive(5, N5);
#pragma unroll
      for (int i = 0; i < (MK ? 2 : 4); i++) sc[i] = ((c[0][i] + c[1][MK ? i + 2 : i]) + c[2][i]) + c[3][MK ? i + 2 : i];
    };
    auto send = [&](auto memkeys) {
      constexpr bool MK = decltype(memkeys)::value;
      constexpr int N = MK ? 1 : 2;
      const uint32_t sa = sb + LV * 4 + SM_E + (MK ? 1024 + RANK * 128 : RANK * 512 + w * 256);
      uint32_t ra[N][2], mb[N][2];
#pragma unroll
      for (int i = 0; i < N; i++)
#pragma unroll
        for (int j = 0; j < 2; j++) {
          ra[i][j] = mapa(sa + i * 128, j ? 2 : RANK ^ 1); mb[i][j] = mapa(sb + MB_S, j ? 2 : RANK ^ 1);
          PIN(ra[i][j]);
        }
      float sc[4];
      scores(memkeys, BoolC<true>(), sc);
      uint32_t e[N];
#pragma unroll
      for (int i = 0; i < N; i++) {
        e[i] = pack_bf16(ex2(sc[2 * i]), ex2(sc[2 * i + 1]));
        if (!(fmaxf(fabsf(sc[2 * i]), fabsf(sc[2 * i + 1])) <= E_LIM)) e[i] = 0x7fff7fffu;
        st_async1(ra[i][0], e[i], mb[i][0]);
        st_async1(ra[i][1], e[i], mb[i][1]);
      }
#pragma unroll
      for (int i = 0; i < N; i++) sts32(sa + i * 128, e[i]);
      __syncwarp();
      if (l16 == sb) mbar_arrive(sb + MB_S);
      PROF(5);
    };
    const int mode = bad ? 8 : mode0;
    if (mode < 2) {
      send(BoolC<false>());
    } else if (mode == 2) {
      send(BoolC<true>());
    } else if (mode == 8) {
      load_vx();
      retire(l16);
      const uint32_t fp = lds32(sb + SC_FPAR);
      bar_sync(6, 128);
      if (w == 0 && l16 == sb) { sts32(sb + SC_FPAR, fp ^ 1); mbar_expect(sb + MB_F, 3072); }
      if (RANK < 2 && w < 3) {
        float sc[4] = {0.f, 0.f, 0.f, 0.f};
        if (w < 2) scores(BoolC<false>(), BoolC<false>(), sc); else scores(BoolC<true>(), BoolC<false>(), sc);
#pragma unroll 1
        for (int r = 0; r < 3; r++)
          st_async4(mapa(l16 + SM_FB + RANK * 1536 + w * 512, r), __float_as_uint(sc[0]), __float_as_uint(sc[1]), __float_as_uint(sc[2]), __float_as_uint(sc[3]), mapa(sb + MB_F, r));
      }
      mbar_wait(sb + MB_F, fp);
      float a[12];
#pragma unroll
      for (int j = 0; j < 3; j++) {
        float b[4];
        lds128f(l16 + SM_FB + j * 512, a + 4 * j); lds128f(l16 + SM_FB + 1536 + j * 512, b);
#pragma unroll
        for (int i = 0; i < 4; i++) a[4 * j + i] += b[i];
      }
      float m0 = fmaxf(fmaxf(fmaxf(a[0], a[2]), fmaxf(a[4], a[6])), a[8]), m1 = fmaxf(fmaxf(fmaxf(a[1], a[3]), fmaxf(a[5], a[7])), a[9]);
#pragma unroll
      for (int o = 4; o < 32; o <<= 1) { m0 = fmaxf(m0, __shfl_xor_sync(0xffffffffu, m0, o)); m1 = fmaxf(m1, __shfl_xor_sync(0xffffffffu, m1, o)); }
#pragma unroll
      for (int i = 0; i < 5; i++) {
        const uint32_t ea = sb + SM_E + LV * 4 + (i < 4 ? i * 128 : 1024);
        sts32(ea, pack_bf16(ex2(a[2 * i] - m0), ex2(a[2 * i + 1] - m1)));
        sts32(ea + (i < 4 ? 512 : 128), 0x3f803f80u);
      }
      __syncwarp();
    } else {
      load_vx();
      if (mode == 3) bar_arrive(4, 256);
      retire(l16 + 1);
      if (w == 3) {
        if (EXPOS == 0 && s > 0) export_seg(s - 1);
        if (EXB) { if (RANK < 2) bar_sync(5, N5); else bar_sync(15, 160); if (s > 0) export_rest(s - 1); }
      }
    }
    {
      uint32_t wa[4], wb[4], oc[4];
      constexpr int WS = 2048;
      const uint32_t w3a = l16 + SM_WO3 + w * 512;
      lds128(w3a + KP(0) * WS, wa); lds128(w3a + KP(1) * WS, wb); lds128(sb + SC_ONES, oc);
      if (B5POS == 1 && mode < 3) bar_arrive(5, N5);
      uint32_t e[10], p[5], vm[4], ob[4];
      float o0[4], o1[4], f[3][2][4], rs[4];
      reserve2(vm); reserve2(vm + 2); reserve2(e + 8);
      hints = hint_addr(s);
      PIN(hints);
      if (CLR & 2) asm volatile("{\n.reg .pred p;\nsetp.eq.u32 p, %0, 0;\n@p exit;\n}" :: "r"(wa[0] | wb[0] | oc[0] | hints) : "memory");
      mbar_wait(sb + MB_S, par);
      PROF(6);
      ldsm4t(e, l16 + SM_E); ldsm2t_in(e + 8, l16 + SM_E + 1024, always); ldsm4t(e + 4, l16 + SM_E + 512);
      lds128_in(vm, l16 + w * 512 + SM_VM, always);
      const float scl = __uint_as_float(lds32(sb + SC_UNSC + 8 - par * 8));
      hints = load_hints(hints);
      if (GF & 1) SCHED_FENCE(4);
#pragma unroll
      for (int i = 0; i < 4; i++) p[i] = mul_bf16(e[i], e[4 + i]);
      p[4] = mul_bf16(e[8], e[9]);
      mma16816z(o0, vx[0], p[0], p[1]); mma16816z(o1, vx[1], p[0], p[1]); mma16816z(rs, oc, p[0], p[1]);
      mma16816(o0, vx[2], p[2], p[3]); lds128_in(vx[2], w3a + KP(2) * WS, always);
      mma16816(o1, vx[3], p[2], p[3]); lds128_in(vx[3], w3a + KP(3) * WS, always);
      mma16816(rs, oc, p[2], p[3]);
      mma1688(o0, vm[0], vm[1], p[4]); mma1688(o1, vm[2], vm[3], p[4]); mma1688(rs, oc[0], oc[1], p[4]);
      stsm4(l16 + w * 512 + SM_OB, pack_bf16(o0[0], o0[1]), pack_bf16(o0[2], o0[3]), pack_bf16(o1[0], o1[1]), pack_bf16(o1[2], o1[3]));
      bar_sync(6, 128);
      PROF(7);
      ldsm4t_in(oc, l16 + SM_OB, always);
      bad = __any_sync(0xffffffffu, !(rs[0] + rs[1] > 0.f) && !bad);
      rs[0] *= scl; rs[1] *= scl;
      asm volatile("{\n.reg .pred p;\nsetp.ne.u32 p, %1, 0;\n@p rcp.approx.ftz.f32 %0, %0;\n}" : "+f"(rs[0]) : "r"(always));
      asm volatile("{\n.reg .pred p;\nsetp.ne.u32 p, %1, 1;\n@p rcp.approx.ftz.f32 %0, %0;\n}" : "+f"(rs[1]) : "r"(always));
      asm volatile("lop3.b32 %0, %1, %2, %3, 0xfe;" : "=r"(lp) : "r"((l16 & 128) * 2), "r"((l16 & 256) * 4), "r"(l16 & 112));
      if (bad) continue;
      ldsm4t(ob, l16 + SM_OB + 512);
      mma16816z(f[2][0], wa, oc[0], oc[1]); mma16816z(f[2][1], wb, oc[2], oc[3]);
      mma16816z(f[0][0], wo[0], oc[0], oc[1]); mma16816z(f[0][1], wo[4], oc[2], oc[3]);
      mma16816z(f[1][0], w1[0], oc[0], oc[1]); mma16816z(f[1][1], w1[4], oc[2], oc[3]);
      ldsm4t_in(oc, l16 + SM_OB + 1024, always);
      mma16816(f[2][0], vx[2], ob[0], ob[1]); lds128_in(vx[2], w3a + KP(4) * WS, always);
      mma16816(f[2][1], vx[3], ob[2], ob[3]); lds128_in(vx[3], w3a + KP(5) * WS, always);
      mma16816(f[0][0], wo[1], ob[0], ob[1]); mma16816(f[0][1], wo[5], ob[2], ob[3]);
      mma16816(f[1][0], w1[1], ob[0], ob[1]); mma16816(f[1][1], w1[5], ob[2], ob[3]);
      ldsm4t_in(ob, l16 + SM_OB + 1536, always);
      mma16816(f[0][0], wo[2], oc[0], oc[1]); mma16816(f[0][1], wo[6], oc[2], oc[3]);
      mma16816(f[2][0], vx[2], oc[0], oc[1]); lds128_in(vx[2], w3a + KP(6) * WS, always);
      mma16816(f[2][1], vx[3], oc[2], oc[3]); lds128_in(vx[3], w3a + KP(7) * WS, always);
      mma16816(f[1][0], w1[2], oc[0], oc[1]); mma16816(f[1][1], w1[6], oc[2], oc[3]);
      mma16816(f[0][0], wo[3], ob[0], ob[1]); mma16816(f[0][1], wo[7], ob[2], ob[3]);
      mma16816(f[1][0], w1[3], ob[0], ob[1]); mma16816(f[1][1], w1[7], ob[2], ob[3]);
      mma16816(f[2][0], vx[2], ob[0], ob[1]); mma16816(f[2][1], vx[3], ob[2], ob[3]);
      bar_arrive(7, NII < 18 ? 384 : 256);
      lds128_in(ob, sb + SC_DEAD, always);
      uint32_t h[3][2];
#pragma unroll
      for (int j = 0; j < 3; j++)
#pragma unroll
        for (int i = 0; i < 2; i++)
        {
          scale_sum(f[j][1][2 * i], f[j][0][2 * i], rs[0], always); scale_sum(f[j][1][2 * i + 1], f[j][0][2 * i + 1], rs[1], always);
          h[j][i] = pack_f16(f[j][1][2 * i], f[j][1][2 * i + 1]);
        }
      const uint32_t rofs = RANK * 32768;
      red_f16x8(slot(s, RANK >> 1, rofs), h[0][0], h[1][0], h[2][0], 0x3c00u);
      red_f16x8(slot(s, (RANK >> 1) ^ 1, rofs), h[0][1], h[1][1], h[2][1], 0x3c00u);
      if (NII == 18) bar_arrive(10, 256);
      SCHED_FENCE(5);
      l16 += ob[B7R];
    }
    {
    PROF(8);
    const uint32_t ma0 = l16 + SM_MEM + w * 128 + (LV >> 3) * 896 + nh * 512;
    const unsigned char* const sl[2] = {slot(s, nh, 0), slot(s, nh ^ 1, 0)};
    uint32_t late = latest_hint(hints, dl, s);
    if (late >= 64) {
      int n = 0;
#pragma unroll 1
      do {
        late = latest_hint(load_hints(hint_addr(s)), dl, s);
      } while (late >= 64 && ++n < SPIN_LIMIT);
    }
    dl += late * 32 + tm.poll;
    if (EXPOS == 2 && w == 3) export_seg(s);
    PROF(9);
    {
      auto wait_until = [&](uint32_t t) {
        asm volatile("{\n.reg .pred p;\n.reg .s32 c;\n.reg .u64 t;\nTL: mov.u64 t, %%globaltimer;\ncvt.u32.u64 c, t;\nsub.s32 c, c, %0;\nsetp.lt.s32 p, c, 0;\n@p bra.uni TL;\n}" :: "r"(t + (l16 & 15)) : "memory");
      };
      uint4 v[2][3];
      auto load = [&](int c) {
#pragma unroll
        for (int r = 0; r < 3; r++) v[c][r] = ldg_relaxed(sl[c ^ (r >> 1)] + r * 32768);
      };
      auto decode = [&](int c, int n) {
        uint32_t q[9];
        __half2 hm;
        const uint32_t ma = ma0 ^ (c * 512);
#pragma unroll
        for (int i = 0; i < 9; i++) {
          const uint32_t h = i % 3 == 0 ? v[c][i / 3].x : (i % 3 == 1 ? v[c][i / 3].y : v[c][i / 3].z);
          const float2 f = __half22float2(*(const __half2*)&h);
          q[i] = pack_bf16(f.x, f.y);
          hm = i ? __hmax2(hm, __habs2(*(const __half2*)&h)) : __habs2(*(const __half2*)&h);
        }
#pragma unroll
        for (int r = 0; r < 3; r++) stsm4(ma + r * 4096, q[3 * r], q[3 * r + 1], q[3 * r + 2], r < 2 ? v[c][r].w : *(const uint32_t*)&hm);
        const bool done = __all_sync(0xffffffffu, v[c][0].w == 0x5000u && v[c][1].w == 0x5000u && v[c][2].w == 0x5000u) || n > SPIN_LIMIT;
        asm volatile("{\n.reg .pred p;\nsetp.ne.u32 p, %0, 0;\n@p bar.arrive %1, 256;\n}" :: "r"((int)done), "r"(1 + c) : "memory");
        return done;
      };
      if (LEAD) { wait_until(dl - LEAD); load(1); }
      wait_until(dl);
      PROF(10);
      int n = 0;
#pragma unroll 1
      do {
        load(0);
        if (!LEAD) load(1);
        asm volatile("{\n.reg .pred p;\nsetp.eq.u32 p, %0, 0;\n@p bar.sync 13, 384;\n}" :: "r"(n) : "memory");
      } while (!decode(0, n++));
      PROF(11);
#pragma unroll 1
      while (!decode(1, n++)) load(1);
      bar_arrive(9, 256);
      PROF(12);
    }
    if (EXPOS == 3 && w == 3) export_seg(s);
    PROF(13);
    if (++s == NSEG - 1) break;
    }
  }
#undef fence_reg
  if (RANK < 2) bar_arrive(4, 256);
  if (w == 3) { if (EXPOS < 2 || EXPOS == 4) export_seg(NSEG - 2); export_rest(NSEG - 2); if (!(XP & 4) && elect_one()) seg_publish(NSEG - 2); }
  __syncwarp();
  bar_sync(0, 384);
  if (w == 3 && !(XP & 4) && elect_one()) {
    fence_async();
    seg_store(NSEG - 1, sb, 0, blk);
    seg_publish(NSEG - 1);
  }
  __syncwarp();
  cluster_sync();
}

__global__ void __cluster_dims__(3, 1, 1) __launch_bounds__(384, 1)
rec_kernel(const __grid_constant__ RMaps tm, const bf16* __restrict__ x, const bf16* __restrict__ mem0) {
  extern __shared__ __align__(1024) unsigned char smem_raw[];
  const uint32_t sb = smem_u32(smem_raw);
  const int tid = threadIdx.x, lane = tid & 31;
  const int wg = __shfl_sync(0xffffffffu, tid >> 7, 0);
  const int w = __shfl_sync(0xffffffffu, (tid >> 5) & 3, 0);
  uint32_t rank; asm("mov.u32 %0, %%cluster_ctarank;" : "=r"(rank));
  STAMP(0);
  asm volatile("griddepcontrol.launch_dependents;" ::: "memory");

  if (wg < 2) {
    asm volatile("setmaxnreg.inc.sync.aligned.u32 192;");
    if (tid == 0) {
      for (int i = 0; i < 3; i++) { mbar_init(sb + MB_W + 8 * i, 1); mbar_init(sb + MB_X + 8 * i, 1); }
      mbar_init(sb + MB_WO, 1); mbar_init(sb + MB_WO3, 1);
      mbar_init(sb + MB_S, rank < 2 ? 5 : 6);
      mbar_init(sb + MB_F, 1);
      mbar_init(sb + MB_VX, 1); mbar_init(sb + MB_VX + 8, 1);
      asm volatile("fence.mbarrier_init.release.cluster;" ::: "memory");
      fence_async();
      const int h = blockIdx.x / 3;
      const CUtensorMap* m0 = rank < 2 ? &tm.wk : &tm.wv;
      const CUtensorMap* m1 = rank < 2 ? &tm.wq : &tm.wv;
      const int c0 = h * DH + (rank == 1 ? 64 : 0), c1 = h * DH + (rank == 0 ? 0 : 64);
      for (int c = 0; c < 3; c++) {
        mbar_expect(sb + MB_W + 8 * c, 49152);
        tma_load(sb + SM_STAGE + c * 49152, m0, c0, c * 192, sb + MB_W + 8 * c);
        tma_load(sb + SM_STAGE + c * 49152 + 24576, m1, c1, c * 192, sb + MB_W + 8 * c);
      }
      for (int i = 0; i < 3; i++) mbar_expect(sb + MB_X + 8 * i, XT);
      tma_load3(sb + SM_X, &tm.x, 0, sb + MB_X);
      tma_prefetch(&tm.wo, rank * 192, h * DH);
      mbar_expect(sb + MB_WO, 16384);
      mbar_expect(sb + MB_WO3, 32768);
      tma_load(sb + SM_WOST, &tm.wo, rank * 192 + 64, h * DH, sb + MB_WO3);
      tma_load(sb + SM_WO3, &tm.wo, rank * 192 + 128, h * DH, sb + MB_WO3);
      mbar_expect(sb + MB_S, rank < 2 ? 640 + 2048 : 1280);
      mbar_expect(sb + MB_VX, 8192); mbar_expect(sb + MB_VX + 8, 8192);
    }
    __syncwarp();
    bar_sync(0, 384);
    proj_role(sb, tm, rank, wg, w, lane);
  } else {
    asm volatile("setmaxnreg.dec.sync.aligned.u32 120;");
    attn_role(sb, smem_raw, tm, rank, x, mem0, w, lane);
  }
}

constexpr int NAUX = 36;
constexpr int A_XH = 73728;
constexpr int A_NS = 4, A_WM = 12288, A_WT = 1536;
constexpr int A_RING = 2 * A_XH, A_TAIL = A_RING + A_NS * A_WM;
constexpr int A_EPI = 212864, A_EPW = 9344;
constexpr int A_XT = 4 * XT, A_XW = A_XT + 8192, A_EX = A_XW + 8192, A_NR = 4;
constexpr int A_IN = A_EX + 16384, A_OST = A_IN + 3 * SEGB;
constexpr int A_GATE = A_EPI + 2 * A_EPW, A_BAR = A_GATE + 512;
constexpr int A_TOTAL = A_BAR + 384;
struct AMaps { CUtensorMap x, wa, wt, oa, o, o3, wob, woa; };

DI void wgmma_n192_ss_nt(float* d, uint64_t da, uint64_t db, int acc) {
  asm volatile("{\n.reg .pred p;\nsetp.ne.b32 p, %98, 0;\n"
               "wgmma.mma_async.sync.aligned.m64n192k16.f32.bf16.bf16 {"
               "%0,%1,%2,%3,%4,%5,%6,%7,%8,%9,%10,%11,%12,%13,%14,%15,%16,%17,%18,%19,%20,%21,%22,%23,%24,%25,%26,%27,%28,%29,%30,%31,"
               "%32,%33,%34,%35,%36,%37,%38,%39,%40,%41,%42,%43,%44,%45,%46,%47,%48,%49,%50,%51,%52,%53,%54,%55,%56,%57,%58,%59,%60,%61,%62,%63,"
               "%64,%65,%66,%67,%68,%69,%70,%71,%72,%73,%74,%75,%76,%77,%78,%79,%80,%81,%82,%83,%84,%85,%86,%87,%88,%89,%90,%91,%92,%93,%94,%95"
               "}, %96, %97, p, 1, 1, 0, 1;\n}\n"
               : ACC8(d, 0), ACC8(d, 8), ACC8(d, 16), ACC8(d, 24), ACC8(d, 32), ACC8(d, 40), ACC8(d, 48), ACC8(d, 56),
                 ACC8(d, 64), ACC8(d, 72), ACC8(d, 80), ACC8(d, 88) : "l"(da), "l"(db), "r"(acc));
}
#define ACC4(d, o) "+f"(d[o]), "+f"(d[o + 1]), "+f"(d[o + 2]), "+f"(d[o + 3])
DI void wgmma_n24_ss_nt(float* d, uint64_t da, uint64_t db, int acc) {
  asm volatile("{\n.reg .pred p;\nsetp.ne.b32 p, %14, 0;\n"
               "wgmma.mma_async.sync.aligned.m64n24k16.f32.bf16.bf16 {%0,%1,%2,%3,%4,%5,%6,%7,%8,%9,%10,%11}, %12, %13, p, 1, 1, 0, 1;\n}\n"
               : ACC8(d, 0), ACC4(d, 8) : "l"(da), "l"(db), "r"(acc));
}
DI void wgmma_n40_ss_tt(float* d, uint64_t da, uint64_t db, int acc) {
  asm volatile("{\n.reg .pred p;\nsetp.ne.b32 p, %22, 0;\n"
               "wgmma.mma_async.sync.aligned.m64n40k16.f32.bf16.bf16 {%0,%1,%2,%3,%4,%5,%6,%7,%8,%9,%10,%11,%12,%13,%14,%15,%16,%17,%18,%19}, "
               "%20, %21, p, 1, 1, 1, 1;\n}\n"
               : ACC8(d, 0), ACC8(d, 8), ACC4(d, 16) : "l"(da), "l"(db), "r"(acc));
}
DI void wgmma_n64_rs(float* d, const uint32_t* a, uint64_t db, int acc) {
  asm volatile("{\n.reg .pred p;\nsetp.ne.b32 p, %37, 0;\n"
               "wgmma.mma_async.sync.aligned.m64n64k16.f32.bf16.bf16 {"
               "%0,%1,%2,%3,%4,%5,%6,%7,%8,%9,%10,%11,%12,%13,%14,%15,%16,%17,%18,%19,%20,%21,%22,%23,%24,%25,%26,%27,%28,%29,%30,%31"
               "}, {%32,%33,%34,%35}, %36, p, 1, 1, 0;\n}\n"
               : ACC8(d, 0), ACC8(d, 8), ACC8(d, 16), ACC8(d, 24) : "r"(a[0]), "r"(a[1]), "r"(a[2]), "r"(a[3]), "l"(db), "r"(acc));
}
DI void wgmma_n32_ss_tn(float* d, uint64_t da, uint64_t db, int acc) {
  asm volatile("{\n.reg .pred p;\nsetp.ne.b32 p, %18, 0;\n"
               "wgmma.mma_async.sync.aligned.m64n32k16.f32.bf16.bf16 {%0,%1,%2,%3,%4,%5,%6,%7,%8,%9,%10,%11,%12,%13,%14,%15}, "
               "%16, %17, p, 1, 1, 1, 0;\n}\n"
               : ACC8(d, 0), ACC8(d, 8) : "l"(da), "l"(db), "r"(acc));
}
DI void tma_load3c(uint32_t dst, const CUtensorMap* m, int c0, int c1, int c2, uint32_t mb) {
  asm volatile("cp.async.bulk.tensor.3d.shared::cluster.global.mbarrier::complete_tx::bytes [%0], [%1, {%3, %4, %5}], [%2];"
               :: "r"(dst), "l"(m), "r"(mb), "r"(c0), "r"(c1), "r"(c2) : "memory");
}
DI uint32_t movm(uint32_t x) { uint32_t r; asm volatile("movmatrix.sync.aligned.m8n8.trans.b16 %0, %1;" : "=r"(r) : "r"(x)); return r; }
DI void wait_count(const unsigned* p, unsigned target) {
  int n = 0;
  unsigned v;
  while (true) {
    asm volatile("ld.acquire.gpu.global.b32 %0, [%1];" : "=r"(v) : "l"(p) : "memory");
    if ((int)(v - target) >= 0 || ++n > SPIN_LIMIT) break;
    __nanosleep(64);
  }
}
DI void count_up(unsigned* p) {
  asm volatile("fence.proxy.async;" ::: "memory");
  asm volatile("red.release.gpu.global.add.u32 [%0], 1;" :: "l"(p) : "memory");
}
#define ADLY 0

__global__ void __launch_bounds__(512, 1)
aux_kernel(const __grid_constant__ AMaps tm, const bf16* __restrict__ wqkv, const bf16* __restrict__ gate_w, bf16* __restrict__ out) {
  extern __shared__ __align__(1024) unsigned char smem_raw[];
  const uint32_t sb = smem_u32(smem_raw);
  const uint32_t fullx = sb + A_BAR, full1 = fullx + 24, empty1 = full1 + 8 * A_NS, fullw = empty1 + 8 * A_NS, full3 = fullw + 8, empty3 = full3 + 8 * A_NR,
                 fullq = empty3 + 8 * A_NR, fullv = fullq + 8, emptyq = fullv + 8, emptyv = emptyq + 8;
  const int tid = threadIdx.x, lane = tid & 31, cta = blockIdx.x;
  const int wg = __shfl_sync(0xffffffffu, tid >> 7, 0), w = __shfl_sync(0xffffffffu, (tid >> 5) & 3, 0);
  ASTAMP(14);
  if (tid == 384) {
    for (int i = 0; i < 3; i++) mbar_init(fullx + 8 * i, 1);
    for (int i = 0; i < A_NS; i++) { mbar_init(full1 + 8 * i, 1); mbar_init(empty1 + 8 * i, 8); }
    mbar_init(fullw, 1); mbar_init(fullq, 1); mbar_init(fullv, 1); mbar_init(emptyq, 4); mbar_init(emptyv, 4);
    for (int i = 0; i < A_NR; i++) { mbar_init(full3 + 8 * i, 1); mbar_init(empty3 + 8 * i, 4); }
    fence_async();
  }
  __syncthreads();
  ASTAMP(0);
  const int tile = cta >> 1, hh = cta & 1;
  const int nsl = cta >> 2, kq = cta & 3;
  if (wg == 3) {
    asm volatile("setmaxnreg.dec.sync.aligned.u32 24;");
    const bool lead = lane == 0;
    if (w == 1 && cta < NH) {
#pragma unroll 1
      for (int seg = 0; seg < NSEG; seg++) {
        bar_arrive(5, 160);
        if (seg > 0 && lead) {
          asm volatile("cp.async.bulk.wait_group 0;" ::: "memory");
          asm volatile("red.relaxed.gpu.global.add.u32 [%0], 1;" :: "l"(&g_ocnt[(seg - 1) * 32]) : "memory");
          SSTAMP(9, seg - 1);
        }
        __syncwarp();
        bar_sync(4, 160);
        if (lead) {
          tma_store(&tm.o, sb + A_OST, cta * DH, seg * 32);
          tma_store(&tm.o, sb + A_OST + 4096, cta * DH + 64, seg * 32);
          asm volatile("cp.async.bulk.commit_group;" ::: "memory");
          asm volatile("cp.async.bulk.wait_group.read 0;" ::: "memory");
        }
        __syncwarp();
      }
      if (lead) {
        asm volatile("cp.async.bulk.wait_group 0;" ::: "memory");
        asm volatile("red.relaxed.gpu.global.add.u32 [%0], 1;" :: "l"(&g_ocnt[(NSEG - 1) * 32]) : "memory");
        SSTAMP(9, NSEG - 1);
      }
    }
    if (w == 2) {
      const unsigned epoch = *(volatile unsigned*)&g_epoch2;
      bar_sync(8, 64);
      if (lead && cta < NH) {
#pragma unroll 1
        for (int seg = 0; seg < NSEG; seg++) {
          const unsigned char* const src = g_seg + ((size_t)(seg & RING) * 96 + cta * 3) * SEGB;
          SSTAMP(0, seg);
          wait_count(&g_scnt[(seg * 32 + cta) * 8], 3 * (epoch + 1));
          SSTAMP(1, seg);
          mbar_wait(emptyq, ~seg & 1);
          mbar_expect(fullq, 2 * SEGB);
          asm volatile("cp.async.bulk.shared::cluster.global.mbarrier::complete_tx::bytes [%0], [%1], %2, [%3];"
                       :: "r"(sb + A_IN), "l"(src), "r"(2 * SEGB), "r"(fullq) : "memory");
          mbar_wait(emptyv, ~seg & 1);
          mbar_expect(fullv, SEGB);
          asm volatile("cp.async.bulk.shared::cluster.global.mbarrier::complete_tx::bytes [%0], [%1], %2, [%3];"
                       :: "r"(sb + A_IN + 2 * SEGB), "l"(src + 2 * SEGB), "r"(SEGB), "r"(fullv) : "memory");
        }
      }
    }
    if (w != 0) return;
    const unsigned epoch = *(volatile unsigned*)&g_epoch2;
    if (lead) {
      if (ADLY) wait_until(gtime() + ADLY);
      auto load_x = [&](int j) {
        mbar_expect(fullx + 8 * j, 49152);
        for (int p = 0; p < 2; p++)
          asm volatile("cp.async.bulk.tensor.4d.shared::cluster.global.mbarrier::complete_tx::bytes [%0], [%1, {%3, %4, %5, %6}], [%2];"
                       :: "r"(sb + p * A_XH + j * 24576), "l"(&tm.x), "r"(fullx + 8 * j), "r"(0), "r"(p), "r"(57 * tile - 7), "r"(3 * j) : "memory");
      };
      load_x(0);
#pragma unroll 1
      for (int it = 0; it < 72 + A_NS; it++) {
        const int st = it % A_NS, col = hh * 288 + it / 18 * 72, row = it % 18 * 32;
        if (it >= A_NS) mbar_wait(empty1 + 8 * st, (it / A_NS - 1) & 1);
        if (it < 72) {
          mbar_expect(full1 + 8 * st, A_WM + A_WT);
          tma_load3c(sb + A_RING + st * A_WM, &tm.wa, col, row, 0, full1 + 8 * st);
          tma_load3c(sb + A_TAIL + st * A_WT, &tm.wt, col + 64, row, 0, full1 + 8 * st);
        }
        if (it == A_NS - 1) {
          load_x(1); load_x(2);
          for (int j = 0; j < 8; j++)
            asm volatile("cp.async.bulk.prefetch.L2.global [%0], %1;" :: "l"((const char*)wqkv + cta * 55296 + j * 6912), "r"(6912) : "memory");
        }
      }
      mbar_expect(fullw, 19 * 8192);
#pragma unroll 1
      for (int k = 0; k < 19; k++) {
        const int kb = k < 18 ? kq * 18 + k : 72;
        const uint32_t dst = sb + (k < 18 ? k * 8192 : A_XW);
        if (kb < 64) tma_load(dst, &tm.wob, nsl * 64, kb * 64, fullw);
        else tma_load(dst, &tm.woa, nsl * 64, (kb - 64) * 64, fullw);
      }
    }
    __syncwarp();
    bar_arrive(8, 64);
    bar_sync(6, 288);
    if (lead) {
      if (kq == 3) { wait_count(&g_abar[32], 2 * NAUX * (epoch + 1)); asm volatile("fence.proxy.async;" ::: "memory"); }
      int avail = 0;
      for (int seg = 0; seg < NSEG; seg++) {
        if (seg >= avail) {
          const int far = min(seg + 3, NSEG - 1);
          if ((int)(ldg_acquire32(&g_ocnt[far * 32]) - 32 * (epoch + 1)) >= 0) avail = far + 1;
          else { wait_count(&g_ocnt[seg * 32], 32 * (epoch + 1)); avail = seg + 1; }
        }
        SSTAMP(5, seg);
        for (int g = 0; g < 2; g++) {
          const int sl = (seg & 1) * 2 + g;
          const bool extra = kq == 3 && g == 0;
          mbar_wait(empty3 + 8 * sl, ((seg >> 1) & 1) ^ 1);
          mbar_expect(full3 + 8 * sl, XT + (extra ? 4096 : 0));
          tma_load3c(sb + sl * XT, &tm.o3, 0, seg * 32, kq * 18 + 9 * g, full3 + 8 * sl);
          if (extra) tma_load(sb + A_XT + (seg & 1) * 4096, &tm.o, 72 * 64, seg * 32, full3 + 8 * sl);
        }
      }
    }
    __syncwarp(); bar_sync(6, 288);
    asm volatile("griddepcontrol.wait;" ::: "memory");
  } else if (wg == 2) {
    asm volatile("setmaxnreg.dec.sync.aligned.u32 88;");
    {
      const unsigned epoch = *(volatile unsigned*)&g_epoch2;
      const int r = tid & 63, par = (tid >> 6) & 1;
      float dot[2] = {0.f, 0.f};
#pragma unroll 1
      for (int kb = 0; kb < 9; kb++) {
        if (kb % 3 == 0) mbar_wait(fullx + 8 * (kb / 3), 0);
#pragma unroll
        for (int c = 0; c < 8; c++) {
          uint32_t a[4];
          lds128(sb + par * A_XH + kb * 8192 + r * 128 + ((c ^ (r & 7)) << 4), a);
          const uint4 g = __ldg((const uint4*)gate_w + kb * 8 + c);
          dot[0] = fmaf(bf_lo(a[0]), bf_lo(g.x), fmaf(bf_lo(a[1]), bf_lo(g.y), fmaf(bf_lo(a[2]), bf_lo(g.z), fmaf(bf_lo(a[3]), bf_lo(g.w), dot[0]))));
          dot[1] = fmaf(bf_hi(a[0]), bf_hi(g.x), fmaf(bf_hi(a[1]), bf_hi(g.y), fmaf(bf_hi(a[2]), bf_hi(g.z), fmaf(bf_hi(a[3]), bf_hi(g.w), dot[1]))));
        }
      }
      const float gv = 1.f / (1.f + __expf(-(dot[0] + dot[1])));
      sts32(sb + A_GATE + (tid & 127) * 4, __float_as_uint(gv));
      const int tok = 2 * (57 * tile - 7 + r) + par;
      if (hh == 0 && r >= 7 && tok < S_LEN) g_gate[tok] = gv;
      bar_arrive(7, 384);
      bar_sync(3, 128);
      if (tid == 256) {
        count_up(&g_abar[0]);
        wait_count(&g_abar[0], NAUX * (epoch + 1));
        if (cta == 0) *(volatile unsigned*)&g_epoch2 = epoch + 1;
      }
      __syncwarp();
      bar_sync(10, 384);
    }
    if (cta < NH) {
      const int lim = w * 8 + (lane >> 2) - 2 * (lane & 3);
      const uint32_t oa = sb + A_OST + (w * 8 + (lane & 7)) * 128;
      const uint32_t z0 = __shfl_sync(0xffffffffu, lane, 0), z1 = __shfl_sync(0xffffffffu, lane ^ 1, 1);
#pragma unroll 1
      for (int seg = 0; seg < NSEG; seg++) {
        const float gt = __ldcg(&g_gate[seg * 32 + w * 8 + (lane >> 2)]);
        float d[32];
        mbar_wait(fullq, seg & 1);
        if (tid == 256) SSTAMP(2, seg);
        WG_FENCE();
#pragma unroll
        for (int k = 0; k < 8; k++) {
          const uint32_t blk = sb + A_IN + (k >> 2) * SEGB + (k & 3) * 256;
          wgmma_n40_ss_tt(d, make_desc(blk, 128, 512, 0), make_desc(blk + 4096, 128, 1024, 0), k > 0);
        }
        WG_COMMIT();
        WG_WAIT(0);
        if (lane == 0) mbar_arrive(emptyq);
        float a[10];
#pragma unroll
        for (int i = 0; i < 10; i++) {
          a[i] = d[(i >> 1) * 4 + (i & 1)] * (SM_SCALE * LOG2E);
          if (i < 8 && (i >> 1) * 8 + (i & 1) > lim) a[i] = -1.0e9f * LOG2E;
        }
        float m = max10(a);
        m = fmaxf(m, __shfl_xor_sync(0xffffffffu, m, 1)); m = fmaxf(m, __shfl_xor_sync(0xffffffffu, m, 2));
#pragma unroll
        for (int i = 0; i < 10; i++) a[i] = ex2(a[i] - m);
        uint32_t p[5][4];
#pragma unroll
        for (int n = 0; n < 5; n++) {
          p[n][0] = pack_bf16(a[2 * n], a[2 * n + 1]);
          p[n][1] = p[n][0] & z0; p[n][2] = p[n][0] & z1; p[n][3] = p[n][0] | z0;
        }
        if (tid == 256) SSTAMP(3, seg);
        mbar_wait(fullv, seg & 1);
        const uint64_t vd = make_desc(sb + A_IN + 2 * SEGB, 4096, 512, 0), md = make_desc(sb + A_IN + 2 * SEGB + 8192, 1024, 128, 0);
        WG_FENCE();
#pragma unroll
        for (int n = 0; n < 5; n++) wgmma_n64_rs(d, p[n], n < 4 ? vd + 8 * n : md, n);
        WG_COMMIT();
        float sum = ((a[0] + a[1]) + (a[2] + a[3])) + ((a[4] + a[5]) + (a[6] + a[7])) + (a[8] + a[9]);
        sum += __shfl_xor_sync(0xffffffffu, sum, 1); sum += __shfl_xor_sync(0xffffffffu, sum, 2);
        const float f = (1.f - gt) * rcp(sum);
        bar_sync(5, 160);
        WG_WAIT(0);
        if (lane == 0) mbar_arrive(emptyv);
        if (tid == 256) SSTAMP(4, seg);
#pragma unroll
        for (int q = 0; q < 4; q++) {
          const float* const o = d + (q & 1) * 16 + (q & 2);
          stsm4(oa + (q >> 1) * 4096 + ((((q & 1) * 4 + (lane >> 3)) ^ (lane & 7)) << 4), pack_bf16(o[0] * f, o[1] * f), pack_bf16(o[4] * f, o[5] * f),
                pack_bf16(o[8] * f, o[9] * f), pack_bf16(o[12] * f, o[13] * f));
        }
        fence_async();
        bar_sync(4, 160);
      }
    }
  } else {
    asm volatile("setmaxnreg.inc.sync.aligned.u32 200;");
    {
      const int g = lane >> 2, t = lane & 3;
      const uint32_t eb = sb + A_EPI + wg * A_EPW;
      const uint32_t own = (2 * t <= g ? 0xffffu : 0u) | (2 * t < g ? 0xffff0000u : 0u);
      const int kmin = 7 - 57 * tile - 16 * w;
#pragma unroll 1
      for (int c = 0; c < 4; c++) {
        float acc[96], tl[12];
#pragma unroll 1
        for (int ks = 0; ks < 18; ks++) {
          const int it = c * 18 + ks, st = it % A_NS;
          if (c == 0 && ks % 6 == 0) mbar_wait(fullx + 8 * (ks / 6), 0);
          mbar_wait(full1 + 8 * st, (it / A_NS) & 1);
          const uint64_t da = make_desc(sb + wg * A_XH + (ks >> 1) * 8192 + (ks & 1) * 64, 16, 1024, 1);
          const uint64_t db = make_desc(sb + A_RING + st * A_WM, 4096, 1024, 1), dt = make_desc(sb + A_TAIL + st * A_WT, 128, 512, 0);
          WG_FENCE();
          wgmma_n192_ss_nt(acc, da, db, ks);
          wgmma_n24_ss_nt(tl, da, dt, ks);
          wgmma_n192_ss_nt(acc, da + 2, db + 128, 1);
          wgmma_n24_ss_nt(tl, da + 2, dt + 16, 1);
          WG_COMMIT();
          if (ks == 8) {
            if ((tid & 127) == 0) asm volatile("cp.async.bulk.wait_group.read 0;" ::: "memory");
            bar_sync(1 + wg, 128);
          }
          WG_WAIT(1);
          if (ks > 0 && lane == 0) mbar_arrive(empty1 + 8 * ((it - 1) % A_NS));
        }
        WG_WAIT(0);
        if (lane == 0) mbar_arrive(empty1 + 8 * ((c * 18 + 17) % A_NS));
        ASTAMP(16 + c);
        uint32_t ql[9], qh[9], kl[9], kh[9], kx[10], vl[9], vh[9], vx[10];
#pragma unroll
        for (int j = 0; j < 9; j++) {
          const float* const q = j < 8 ? acc + 4 * j : tl, * const k = j < 8 ? acc + 32 + 4 * j : tl + 4, * const v = j < 8 ? acc + 64 + 4 * j : tl + 8;
          kh[j] = pack_bf16(k[2], k[3]); vh[j] = pack_bf16(v[2], v[3]);
          ql[j] = pack_bf16(q[0], q[1]); qh[j] = pack_bf16(q[2], q[3]); kl[j] = pack_bf16(k[0], k[1]); vl[j] = pack_bf16(v[0], v[1]);
        }
        if (w < 3) {
          const uint32_t ha = eb + 1024 + w * 2304 + lane * 16;
          stsm4(ha, kh[0], kh[1], kh[2], kh[3]); stsm4(ha + 512, kh[4], kh[5], kh[6], kh[7]);
          stsm4(ha + 1024, vh[0], vh[1], vh[2], vh[3]); stsm4(ha + 1536, vh[4], vh[5], vh[6], vh[7]);
          asm volatile("stmatrix.sync.aligned.m8n8.x2.shared.b16 [%0], {%1,%2};" :: "r"(ha + 2048), "r"(kh[8]), "r"(vh[8]) : "memory");
        }
        if (c == 0) bar_sync(7, 384); else bar_sync(1 + wg, 128);
        {
          const uint32_t ha = eb + 1024 + max(w - 1, 0) * 2304 + lane * 16;
          ldsm4(kx, ha); ldsm4(kx + 4, ha + 512); ldsm4t(vx, ha + 1024); ldsm4t(vx + 4, ha + 1536);
          asm volatile("ldmatrix.sync.aligned.m8n8.x1.shared.b16 {%0}, [%1];" : "=r"(kx[8]) : "r"(ha + 2048) : "memory");
          asm volatile("ldmatrix.sync.aligned.m8n8.x1.trans.shared.b16 {%0}, [%1];" : "=r"(vx[8]) : "r"(ha + 2176) : "memory");
        }
        const float gl = __uint_as_float(lds32(sb + A_GATE + (wg * 64 + w * 16 + g) * 4)), gh = __uint_as_float(lds32(sb + A_GATE + (wg * 64 + w * 16 + g + 8) * 4));
#pragma unroll
        for (int j = 0; j < 9; j++) { vl[j] = movm(vl[j]); vh[j] = movm(vh[j]); }
        bar_sync(1 + wg, 128);
        uint32_t ol[9], oh[9];
#pragma unroll
        for (int i = 0; i < 4; i++) {
          const int b = 2 * i;
          const uint32_t a[4] = {t >= i ? ql[b] : 0u, t >= i ? qh[b] : 0u, ql[b + 1], qh[b + 1]}, a4 = t <= i ? ql[b + 2] : 0u, a5 = t <= i ? qh[b + 2] : 0u;
          float sx[4], sl[4], sh[4];
          mma16816z(sx, a, kx[b], kx[b + 1]); mma16816z(sl, a, kl[b], kl[b + 1]); mma16816z(sh, a, kh[b], kh[b + 1]);
          mma1688(sx, a4, a5, kx[b + 2]); mma1688(sl, a4, a5, kl[b + 2]); mma1688(sh, a4, a5, kh[b + 2]);
          float e[4];
#pragma unroll
          for (int u = 0; u < 4; u++) {
            const int cc = 2 * t + (u & 1);
            e[u] = (cc <= g ? (u < 2 ? sl[u] : sh[u]) : (u < 2 ? sx[u] : sl[u])) * (0.23570226039551584f * LOG2E);
            if ((cc <= g ? cc : cc - 8) + (u & 2) * 4 < kmin) e[u] = -1.0e9f * LOG2E;
          }
          float m0 = fmaxf(e[0], e[1]), m1 = fmaxf(e[2], e[3]);
#pragma unroll
          for (int o = 1; o < 4; o <<= 1) { m0 = fmaxf(m0, __shfl_xor_sync(0xffffffffu, m0, o)); m1 = fmaxf(m1, __shfl_xor_sync(0xffffffffu, m1, o)); }
          e[0] = ex2(e[0] - m0); e[1] = ex2(e[1] - m0); e[2] = ex2(e[2] - m1); e[3] = ex2(e[3] - m1);
          const uint32_t p0 = pack_bf16(e[0], e[1]), p1 = pack_bf16(e[2], e[3]);
          const uint32_t p[4] = {p0 & ~own, 0u, p0 & own, p1 & ~own};
          float s0 = e[0] + e[1], s1 = e[2] + e[3];
#pragma unroll
          for (int o = 1; o < 4; o <<= 1) { s0 += __shfl_xor_sync(0xffffffffu, s0, o); s1 += __shfl_xor_sync(0xffffffffu, s1, o); }
          const float f0 = gl * rcp(s0), f1 = gh * rcp(s1);
#pragma unroll
          for (int j = b; j < b + 3; j++) {
            float o[4];
            mma16816z(o, p, vx[j], vl[j]);
            mma1688(o, 0u, p1 & own, vh[j]);
            const uint32_t lo = pack_bf16(o[0] * f0, o[1] * f0), hi = pack_bf16(o[2] * f1, o[3] * f1);
            if (j > b || i == 0) { ol[j] = lo; oh[j] = hi; }
            else { ol[j] = t >= i ? lo : ol[j]; oh[j] = t >= i ? hi : oh[j]; }
          }
        }
        const uint32_t sa = eb + 16 + (w * 16 + (lane & 15)) * 144 + (lane >> 4) * 16;
#pragma unroll
        for (int j = 0; j < 8; j += 2) stsm4(sa + j * 16, ol[j], oh[j], ol[j + 1], oh[j + 1]);
        asm volatile("stmatrix.sync.aligned.m8n8.x2.shared.b16 [%0], {%1,%2};" :: "r"(sa + 128), "r"(ol[8]), "r"(oh[8]) : "memory");
        fence_async();
        bar_sync(1 + wg, 128);
        if ((tid & 127) == 0) {
          asm volatile("cp.async.bulk.tensor.3d.global.shared::cta.bulk_group [%0, {%2, %3, %4}], [%1];"
                       :: "l"(&tm.oa), "r"(eb + 1024), "r"(4096 + hh * 288 + c * 72), "r"(wg), "r"(57 * tile) : "memory");
          asm volatile("cp.async.bulk.commit_group;" ::: "memory");
        }
      }
      if ((tid & 127) == 0) { asm volatile("cp.async.bulk.wait_group 0;" ::: "memory"); count_up(&g_abar[32]); }
      __syncwarp();
      bar_arrive(10, 384);
    }
    ASTAMP(3);
    uint32_t wa[36][4];
    mbar_wait(fullw, 0);
    const uint32_t la = sb + wg * 73728 + ((lane & 7) + ((lane >> 4) << 3)) * 128 + (((2 * w + ((lane >> 3) & 1)) ^ (lane & 7)) << 4);
#pragma unroll
    for (int k = 0; k < 36; k++) ldsm4t(wa[k], la + k * 2048);
    fence_async();
    bar_sync(6, 288);
    ASTAMP(4);
    float own[4] = {0.f, 0.f, 0.f, 0.f};
    uint4 v[3];
    auto fetch = [&](int seg) {
      const uint4* src = g_part + (((seg & 3) * 36 + cta) * 4) * 128 + (tid & 127);
#pragma unroll
      for (int j = 0; j < 3; j++) v[j] = ldg_relaxed(src + ((kq + 1 + j) & 3) * 128);
    };
    auto finish = [&](int seg) {
      const uint32_t tagv = ((seg >> 2) + 1) & 3;
      int n = 0;
#pragma unroll 1
      while (__any_sync(0xffffffffu, (v[0].x & 3) != tagv || (v[1].x & 3) != tagv || (v[2].x & 3) != tagv) && ++n < SPIN_LIMIT) {
        if (seg < NSEG - 1) __nanosleep(200);
        fetch(seg);
      }
#pragma unroll
      for (int j = 0; j < 3; j++) {
        own[0] += __uint_as_float(v[j].x & ~3u); own[1] += __uint_as_float(v[j].y); own[2] += __uint_as_float(v[j].z); own[3] += __uint_as_float(v[j].w);
      }
      uint32_t p0 = pack_bf16(own[0], own[1]), p1 = pack_bf16(own[2], own[3]);
      asm volatile("movmatrix.sync.aligned.m8n8.trans.b16 %0, %0;" : "+r"(p0));
      asm volatile("movmatrix.sync.aligned.m8n8.trans.b16 %0, %0;" : "+r"(p1));
      uint32_t* o = (uint32_t*)(out + (size_t)(seg * 32 + kq * 8 + (lane >> 2)) * DM + nsl * 64 + w * 16) + (lane & 3);
      o[0] = p0; o[4] = p1;
    };
    float acc[16];
    auto stream = [&](int sl, int keep) {
      const uint64_t db = make_desc(sb + sl * XT, 16, 1024, 1);
      WG_FENCE();
#pragma unroll
      for (int k = 0; k < 36; k++) wgmma_n32_rs(acc, wa[k][0], wa[k][1], wa[k][2], wa[k][3], db + (k >> 2) * 256 + (k & 3) * 2, k ? 1 : keep);
      WG_COMMIT();
    };
    const uint32_t ex = sb + A_EX + (tid & 127) * 16;
    if (wg == 0) {
#pragma unroll
      for (int i = 0; i < 16; i++) acc[i] = 0.f;
#pragma unroll 1
      for (int seg = 0; seg < NSEG; seg++) {
        const int sl = (seg & 1) * 2;
        mbar_wait(full3 + 8 * sl, (seg >> 1) & 1);
        if (kq == 3) {
          const uint64_t da = make_desc(sb + A_XW, 8192, 1024, 1), de = make_desc(sb + A_XT + (seg & 1) * 4096, 16, 1024, 1);
          WG_FENCE();
#pragma unroll
          for (int j = 0; j < 4; j++) wgmma_n32_ss_tn(acc, da + j * 128, de + j * 2, j);
          WG_COMMIT();
          WG_WAIT(0);
        }
        stream(sl, kq == 3);
        bar_arrive(9, 256);
        WG_WAIT(0);
        if (lane == 0) mbar_arrive(empty3 + 8 * sl);
#pragma unroll
        for (int i = 0; i < 4; i++)
          sts128(ex + (seg & 1) * 8192 + i * 2048, __float_as_uint(acc[4 * i]), __float_as_uint(acc[4 * i + 1]), __float_as_uint(acc[4 * i + 2]), __float_as_uint(acc[4 * i + 3]));
        bar_sync(1, 256);
      }
    } else {
#pragma unroll 1
      for (int seg = 0; seg < NSEG; seg++) {
        const int sl = (seg & 1) * 2 + 1;
        mbar_wait(full3 + 8 * sl, (seg >> 1) & 1);
        if (tid == 128) SSTAMP(6, seg);
        bar_sync(9, 256);
        stream(sl, 0);
        bar_sync(1, 256);
        fetch(max(seg - 1, 0));
        WG_WAIT(0);
        if (lane == 0) mbar_arrive(empty3 + 8 * sl);
        float nxt[4] = {0.f, 0.f, 0.f, 0.f};
        uint4* dst = g_part + (((seg & 3) * 36 + nsl * 4) * 4 + kq) * 128 + (tid & 127);
#pragma unroll
        for (int j = 0; j < 4; j++) {
          float o[4];
          lds128f(ex + (seg & 1) * 8192 + j * 2048, o);
#pragma unroll
          for (int i = 0; i < 4; i++) { o[i] += acc[4 * j + i]; if (j == kq) nxt[i] = o[i]; }
          if (j != kq) stg_relaxed(dst + j * 512, (__float_as_uint(o[0]) & ~3u) | (((seg >> 2) + 1) & 3), __float_as_uint(o[1]), __float_as_uint(o[2]), __float_as_uint(o[3]));
        }
        if (tid == 128) SSTAMP(7, seg);
        if (seg > 0) finish(seg - 1);
        if (tid == 128) SSTAMP(8, seg);
#pragma unroll
        for (int i = 0; i < 4; i++) own[i] = nxt[i];
        if ((seg & 7) == 6) ASTAMP(5 + (seg >> 3));
      }
      fetch(NSEG - 1);
      finish(NSEG - 1);
    }
    ASTAMP(13);
    bar_sync(6, 288);
  }
}

typedef CUresult (*EncodeFn)(CUtensorMap*, CUtensorMapDataType, cuuint32_t, void*, const cuuint64_t*, const cuuint64_t*,
                             const cuuint32_t*, const cuuint32_t*, CUtensorMapInterleave, CUtensorMapSwizzle,
                             CUtensorMapL2promotion, CUtensorMapFloatOOBfill);
static void make_map(EncodeFn enc, CUtensorMap* m, const void* p, int rows, int cols, int box_rows) {
  cuuint64_t dims[2] = {(cuuint64_t)cols, (cuuint64_t)rows};
  cuuint64_t strides[1] = {(cuuint64_t)cols * 2};
  cuuint32_t box[2] = {64, (cuuint32_t)box_rows};
  cuuint32_t es[2] = {1, 1};
  enc(m, CU_TENSOR_MAP_DATA_TYPE_BFLOAT16, 2, (void*)p, dims, strides, box, es, CU_TENSOR_MAP_INTERLEAVE_NONE,
      CU_TENSOR_MAP_SWIZZLE_128B, CU_TENSOR_MAP_L2_PROMOTION_L2_128B, CU_TENSOR_MAP_FLOAT_OOB_FILL_NONE);
}

constexpr int g_poll = POLL_NS;
extern "C" void kernel_launch(void* const* d_in, const int* in_sizes, int n_in, void* d_out, int out_size) {
  const bf16* x = (const bf16*)d_in[0];
  const bf16* wqkvA = (const bf16*)d_in[1];
  const bf16* woA = (const bf16*)d_in[2];
  const bf16* mem0 = (const bf16*)d_in[4];
  const bf16* Wq = (const bf16*)d_in[5];
  const bf16* Wk = (const bf16*)d_in[6];
  const bf16* Wv = (const bf16*)d_in[7];
  const bf16* Wo = (const bf16*)d_in[8];
  const bf16* gate_w = (const bf16*)d_in[10];
  static EncodeFn enc = nullptr;
  static void *pO = nullptr, *pR = nullptr;
  if (!enc) {
    cudaDriverEntryPointQueryResult qr;
    cudaGetDriverEntryPoint("cuTensorMapEncodeTiled", (void**)&enc, cudaEnableDefault, &qr);
    cudaGetSymbolAddress(&pO, g_Ocat);
    cudaGetSymbolAddress(&pR, g_red_raw);
    cudaFuncSetAttribute(rec_kernel, cudaFuncAttributeMaxDynamicSharedMemorySize, SM_TOTAL);
    cudaFuncSetAttribute(aux_kernel, cudaFuncAttributeMaxDynamicSharedMemorySize, A_TOTAL);
  }
  RMaps rm;
  rm.poll = g_poll;
  rm.red = (unsigned char*)(((uintptr_t)pR + 262143) & ~(uintptr_t)262143);
  {
    cuuint64_t dims[3] = {64, S_LEN, 9}, strides[2] = {DM * 2, 128};
    cuuint32_t box[3] = {64, 32, 9}, es[3] = {1, 1, 1};
    enc(&rm.x, CU_TENSOR_MAP_DATA_TYPE_BFLOAT16, 3, (void*)x, dims, strides, box, es, CU_TENSOR_MAP_INTERLEAVE_NONE,
        CU_TENSOR_MAP_SWIZZLE_128B, CU_TENSOR_MAP_L2_PROMOTION_L2_128B, CU_TENSOR_MAP_FLOAT_OOB_FILL_NONE);
  }
  make_map(enc, &rm.wq, Wq, DM, 4096, 192);
  make_map(enc, &rm.wk, Wk, DM, 4096, 192);
  make_map(enc, &rm.wv, Wv, DM, 4096, 192);
  make_map(enc, &rm.wo, Wo, 4096, DM, 128);
  AMaps am;
  {
    cuuint32_t es[4] = {1, 1, 1, 1};
    cuuint64_t dx[4] = {64, 2, S_LEN / 2, 9}, sx[3] = {DM * 2, DM * 4, 128};
    cuuint32_t bx[4] = {64, 1, 64, 3};
    enc(&am.x, CU_TENSOR_MAP_DATA_TYPE_BFLOAT16, 4, (void*)x, dx, sx, bx, es, CU_TENSOR_MAP_INTERLEAVE_NONE,
        CU_TENSOR_MAP_SWIZZLE_128B, CU_TENSOR_MAP_L2_PROMOTION_L2_128B, CU_TENSOR_MAP_FLOAT_OOB_FILL_NONE);
    cuuint64_t dw[3] = {DM, DM, 3}, sw[2] = {DM * 6, DM * 2};
    cuuint32_t bw[3] = {64, 32, 3}, bt[3] = {8, 32, 3};
    enc(&am.wa, CU_TENSOR_MAP_DATA_TYPE_BFLOAT16, 3, (void*)wqkvA, dw, sw, bw, es, CU_TENSOR_MAP_INTERLEAVE_NONE,
        CU_TENSOR_MAP_SWIZZLE_128B, CU_TENSOR_MAP_L2_PROMOTION_L2_128B, CU_TENSOR_MAP_FLOAT_OOB_FILL_NONE);
    enc(&am.wt, CU_TENSOR_MAP_DATA_TYPE_BFLOAT16, 3, (void*)wqkvA, dw, sw, bt, es, CU_TENSOR_MAP_INTERLEAVE_NONE,
        CU_TENSOR_MAP_SWIZZLE_NONE, CU_TENSOR_MAP_L2_PROMOTION_NONE, CU_TENSOR_MAP_FLOAT_OOB_FILL_NONE);
    cuuint64_t dz[3] = {KCAT, 2, S_LEN / 2}, sz[2] = {KCAT * 2, KCAT * 4};
    cuuint32_t bz[3] = {72, 1, 57};
    enc(&am.oa, CU_TENSOR_MAP_DATA_TYPE_BFLOAT16, 3, pO, dz, sz, bz, es, CU_TENSOR_MAP_INTERLEAVE_NONE,
        CU_TENSOR_MAP_SWIZZLE_NONE, CU_TENSOR_MAP_L2_PROMOTION_NONE, CU_TENSOR_MAP_FLOAT_OOB_FILL_NONE);
  }
  {
    cuuint64_t dims[3] = {64, S_LEN, KCAT / 64}, strides[2] = {KCAT * 2, 128};
    cuuint32_t box[3] = {64, 32, 9}, es[3] = {1, 1, 1};
    make_map(enc, &am.o, pO, S_LEN, KCAT, 32);
    enc(&am.o3, CU_TENSOR_MAP_DATA_TYPE_BFLOAT16, 3, pO, dims, strides, box, es, CU_TENSOR_MAP_INTERLEAVE_NONE,
        CU_TENSOR_MAP_SWIZZLE_128B, CU_TENSOR_MAP_L2_PROMOTION_L2_128B, CU_TENSOR_MAP_FLOAT_OOB_FILL_NONE);
  }
  make_map(enc, &am.wob, Wo, 4096, DM, 64);
  make_map(enc, &am.woa, woA, DM, DM, 64);

  rec_kernel<<<96, 384, SM_TOTAL, cudaStreamPerThread>>>(rm, x, mem0);
  cudaLaunchConfig_t cfg = {};
  cfg.gridDim = dim3(NAUX); cfg.blockDim = dim3(512); cfg.dynamicSmemBytes = A_TOTAL; cfg.stream = cudaStreamPerThread;
  cudaLaunchAttribute at[1];
  at[0].id = cudaLaunchAttributeProgrammaticStreamSerialization; at[0].val.programmaticStreamSerializationAllowed = 1;
  cfg.attrs = at; cfg.numAttrs = 1;
  if (XP & 16) cfg.numAttrs = 0;
  if (!(XP & 64)) cudaLaunchKernelEx(&cfg, aux_kernel, am, wqkvA, gate_w, (bf16*)d_out);
}
```

```cpp
#include <cuda_runtime.h>
#include <cuda_bf16.h>
#include <cuda_fp16.h>
#include <cuda.h>
#include <stdint.h>

typedef __nv_bfloat16 bf16;

constexpr int S_LEN = 2048, DM = 576, NH = 32, DH = 128, NSEG = 64, KCAT = 4096 + 576;
#define RED_LINE(i) (((i) >> 2) * 4096 + ((i) & 1) * 256 + ((i) & 2) * 512)
#define RED_SLOT(s) (((s) & 1) * 128 + ((s) & 2) * 256)

#define POLL_NS 896
#define NII 18
#define W3PRE 4
#define W3MID 4
#define GF 0
#define B5POS 0
#define NUP 4
#define UPF 1
#define B3Q 9
#define B3F 0
#define GATE 7
#define NTL 2
#define B7R 1
#define EXPOS 0
#define VW2 1
#define CLR 1
#define RFW 0
#define NIC 0
#define LEAD 0
#define FIN16 1
#define VXG 0
#define RING 63
#define EXB 0
#define EXD 0
#define EXB2 8192
#define HDLY 0
#define F10 1
#define NPROBE 2
#define QM 0
#define N5 (EXB ? 256 : 224)
#define KP(i) (((i) >> 1) + 4 * ((i) & 1))
#define SPIN_LIMIT (1 << 14)
#define XP 0

__device__ __align__(1024) bf16 g_Ocat[S_LEN * KCAT];
__device__ __align__(1024) unsigned char g_red_raw[2 * 262144];
constexpr int HINT_OFF = 2048;
__device__ __align__(16) float g_gate[S_LEN];
__device__ __align__(128) uint4 g_stats[96 * 2];
__device__ unsigned g_epoch;
__device__ unsigned g_epoch2;
__device__ unsigned g_ocnt[NSEG * 32];
__device__ unsigned g_abar[3 * 32];
__device__ unsigned g_pace[32];
__device__ unsigned g_scnt[NSEG * 32 * 8];
__device__ __align__(1024) unsigned char g_seg[NSEG * 96 * 10240];
__device__ __align__(1024) uint4 g_part[4 * 36 * 4 * 128];
__device__ int g_err;
#define PROF(idx)
#define PROFP(idx)
#define STAMP(idx)
#define ASTAMP(idx)
#define SSTAMP(k, seg)
#define WSTAMP(idx)

#define DI __device__ __forceinline__
DI uint32_t smem_u32(const void* p) { return (uint32_t)__cvta_generic_to_shared(p); }
DI uint32_t clock32() { uint32_t c; asm volatile("mov.u32 %0, %%clock;" : "=r"(c) :: "memory"); return c; }
DI uint32_t gtime() { uint32_t c; asm volatile("mov.u32 %0, %%globaltimer_lo;" : "=r"(c) :: "memory"); return c; }
DI uint32_t ldg_relaxed32(const void* p) { uint32_t v; asm volatile("ld.relaxed.gpu.global.b32 %0, [%1];" : "=r"(v) : "l"(p) : "memory"); return v; }
DI uint32_t ldg_acquire32(const void* p) { uint32_t v; asm volatile("ld.acquire.gpu.global.b32 %0, [%1];" : "=r"(v) : "l"(p) : "memory"); return v; }
DI void stg_relaxed32(void* p, uint32_t v) { asm volatile("st.relaxed.gpu.global.b32 [%0], %1;" :: "l"(p), "r"(v) : "memory"); }
DI int head_id() { int c; asm volatile("mov.u32 %0, %%clusterid.x;" : "=r"(c)); return c; }
DI uint32_t mapa(uint32_t a, uint32_t r) { uint32_t o; asm("mapa.shared::cluster.u32 %0, %1, %2;" : "=r"(o) : "r"(a), "r"(r)); return o; }
DI void cluster_arrive() { asm volatile("barrier.cluster.arrive.relaxed.aligned;" ::: "memory"); }
DI void cluster_wait() { asm volatile("barrier.cluster.wait.aligned;" ::: "memory"); }
DI void cluster_sync() { asm volatile("barrier.cluster.arrive.release.aligned;\nbarrier.cluster.wait.acquire.aligned;" ::: "memory"); }
DI void mbar_init(uint32_t b, uint32_t c) { asm volatile("mbarrier.init.shared::cta.b64 [%0], %1;" :: "r"(b), "r"(c) : "memory"); }
DI void mbar_expect(uint32_t b, uint32_t tx) { asm volatile("mbarrier.arrive.expect_tx.shared::cta.b64 _, [%0], %1;" :: "r"(b), "r"(tx) : "memory"); }
DI void mbar_arrive(uint32_t b) { asm volatile("mbarrier.arrive.shared::cta.b64 _, [%0];" :: "r"(b) : "memory"); }
DI void mbar_wait(uint32_t b, uint32_t par) {
  asm volatile("{\n.reg .pred p;\n.reg .u32 n, q;\nmov.u32 n, 0;\n"
               "WL: add.u32 n, n, 1;\nshr.u32 q, n, 12;\nxor.b32 q, q, %1;\n"
               "mbarrier.try_wait.parity.shared::cta.b64 p, [%0], q;\n@!p bra.uni WL;\n}"
               :: "r"(b), "r"(par) : "memory");
}
DI void wait_until(uint32_t t) {
  const uint32_t now = gtime();
  t = min(t, now + 8192);
  asm volatile("{\n.reg .pred p;\n.reg .u32 c;\nTL: mov.u32 c, %%globaltimer_lo;\nsetp.lt.u32 p, c, %0;\n@p bra.uni TL;\n}" :: "r"(t) : "memory");
}
#define PIN(v) v = __shfl_xor_sync(0xffffffffu, v, 0)
#define SCHED_FENCE(k) asm volatile("{\n.reg .pred p;\nsetp.eq.u32 p, %0, %1;\n@p exit;\n}" :: "r"(fence_reg), "r"(k) : "memory")
#define MEM_ORDER(k) asm volatile("{\n.reg .pred p;\nsetp.eq.u32 p, %0, %1;\n@p st.shared.u32 [%0], %0;\n}" :: "r"(fence_reg), "r"(k + 64) : "memory")
DI void bar_sync(int id, int n) { asm volatile("bar.sync %0, %1;" :: "r"(id), "r"(n) : "memory"); }
DI void bar_arrive(int id, int n) { asm volatile("bar.arrive %0, %1;" :: "r"(id), "r"(n) : "memory"); }
DI void fence_async() { asm volatile("fence.proxy.async.shared::cta;" ::: "memory"); }
DI void st_async4(uint32_t a, uint32_t x, uint32_t y, uint32_t z, uint32_t w, uint32_t mb) {
  asm volatile("st.async.weak.shared::cluster.mbarrier::complete_tx::bytes.v4.b32 [%0], {%1,%2,%3,%4}, [%5];"
               :: "r"(a), "r"(x), "r"(y), "r"(z), "r"(w), "r"(mb) : "memory");
}
DI void st_async2(uint32_t a, uint32_t x, uint32_t y, uint32_t mb) {
  asm volatile("st.async.weak.shared::cluster.mbarrier::complete_tx::bytes.v2.b32 [%0], {%1,%2}, [%3];"
               :: "r"(a), "r"(x), "r"(y), "r"(mb) : "memory");
}
DI void sts32(uint32_t a, uint32_t x) { asm volatile("st.shared.b32 [%0], %1;" :: "r"(a), "r"(x) : "memory"); }
DI void sts64(uint32_t a, uint32_t x, uint32_t y) { asm volatile("st.shared.v2.b32 [%0], {%1,%2};" :: "r"(a), "r"(x), "r"(y) : "memory"); }
DI void sts128(uint32_t a, uint32_t x, uint32_t y, uint32_t z, uint32_t w) {
  asm volatile("st.shared.v4.b32 [%0], {%1,%2,%3,%4};" :: "r"(a), "r"(x), "r"(y), "r"(z), "r"(w) : "memory");
}
DI uint32_t lds32(uint32_t a) { uint32_t x; asm volatile("ld.shared.b32 %0, [%1];" : "=r"(x) : "r"(a) : "memory"); return x; }
DI void lds64(uint32_t a, uint32_t& x, uint32_t& y) { asm volatile("ld.shared.v2.b32 {%0,%1}, [%2];" : "=r"(x), "=r"(y) : "r"(a) : "memory"); }
DI void lds128(uint32_t a, uint32_t* r) {
  asm volatile("ld.shared.v4.b32 {%0,%1,%2,%3}, [%4];" : "=r"(r[0]), "=r"(r[1]), "=r"(r[2]), "=r"(r[3]) : "r"(a) : "memory");
}
DI void lds128f(uint32_t a, float* r) {
  asm volatile("ld.shared.v4.f32 {%0,%1,%2,%3}, [%4];" : "=f"(r[0]), "=f"(r[1]), "=f"(r[2]), "=f"(r[3]) : "r"(a) : "memory");
}
DI void lds64f(uint32_t a, float* r) { asm volatile("ld.shared.v2.f32 {%0,%1}, [%2];" : "=f"(r[0]), "=f"(r[1]) : "r"(a) : "memory"); }
DI void ldsm4t(uint32_t* r, uint32_t a) {
  asm volatile("ldmatrix.sync.aligned.m8n8.x4.trans.shared.b16 {%0,%1,%2,%3}, [%4];"
               : "=r"(r[0]), "=r"(r[1]), "=r"(r[2]), "=r"(r[3]) : "r"(a) : "memory");
}
DI void ldsm4t_in(uint32_t* r, uint32_t a, uint32_t t) {
  asm volatile("{\n.reg .pred p;\nsetp.ne.u32 p, %5, 0;\n@p ldmatrix.sync.aligned.m8n8.x4.trans.shared.b16 {%0,%1,%2,%3}, [%4];\n}"
               : "+r"(r[0]), "+r"(r[1]), "+r"(r[2]), "+r"(r[3]) : "r"(a), "r"(t) : "memory");
}
DI void lds128_in(uint32_t* r, uint32_t a, uint32_t t) {
  asm volatile("{\n.reg .pred p;\nsetp.ne.u32 p, %5, 0;\n@p ld.shared.v4.b32 {%0,%1,%2,%3}, [%4];\n}"
               : "+r"(r[0]), "+r"(r[1]), "+r"(r[2]), "+r"(r[3]) : "r"(a), "r"(t) : "memory");
}
DI void ldsm2t_in(uint32_t* r, uint32_t a, uint32_t t) {
  asm volatile("{\n.reg .pred p;\nsetp.ne.u32 p, %3, 0;\n@p ldmatrix.sync.aligned.m8n8.x2.trans.shared.b16 {%0,%1}, [%2];\n}" : "+r"(r[0]), "+r"(r[1]) : "r"(a), "r"(t) : "memory");
}
DI void reserve2(uint32_t* r) { asm volatile("{\n.reg .u64 t;\nmov.u64 t, %%clock64;\nmov.b64 {%0, %1}, t;\n}" : "=r"(r[0]), "=r"(r[1])); }
DI void scale_sum(float& x, float& y, float s, uint32_t t) {
  asm volatile("{\n.reg .pred p;\nsetp.ne.u32 p, %2, 0;\n@p mul.f32 %0, %0, %1;\n}" : "+f"(y) : "f"(s), "r"(t));
  asm volatile("{\n.reg .pred p;\nsetp.ne.u32 p, %3, 1;\n@p fma.rn.f32 %0, %0, %1, %2;\n}" : "+f"(x) : "f"(s), "f"(y), "r"(t));
}
DI void ldsm4(uint32_t* r, uint32_t a) {
  asm volatile("ldmatrix.sync.aligned.m8n8.x4.shared.b16 {%0,%1,%2,%3}, [%4];"
               : "=r"(r[0]), "=r"(r[1]), "=r"(r[2]), "=r"(r[3]) : "r"(a) : "memory");
}
DI void st_async1(uint32_t a, uint32_t x, uint32_t mb) {
  asm volatile("st.async.weak.shared::cluster.mbarrier::complete_tx::bytes.b32 [%0], %1, [%2];" :: "r"(a), "r"(x), "r"(mb) : "memory");
}
DI void stsm4(uint32_t a, uint32_t x, uint32_t y, uint32_t z, uint32_t w) {
  asm volatile("stmatrix.sync.aligned.m8n8.x4.shared.b16 [%0], {%1,%2,%3,%4};" :: "r"(a), "r"(x), "r"(y), "r"(z), "r"(w) : "memory");
}
DI void stsm4t(uint32_t a, uint32_t x, uint32_t y, uint32_t z, uint32_t w) {
  asm volatile("stmatrix.sync.aligned.m8n8.x4.trans.shared.b16 [%0], {%1,%2,%3,%4};" :: "r"(a), "r"(x), "r"(y), "r"(z), "r"(w) : "memory");
}
DI uint32_t pack_bf16(float lo, float hi) { uint32_t r; asm("cvt.rn.bf16x2.f32 %0, %1, %2;" : "=r"(r) : "f"(hi), "f"(lo)); return r; }
DI uint32_t pack_f16(float lo, float hi) { uint32_t r; asm("cvt.rn.f16x2.f32 %0, %1, %2;" : "=r"(r) : "f"(hi), "f"(lo)); return r; }
DI float ex2(float x) { float y; asm("ex2.approx.ftz.f32 %0, %1;" : "=f"(y) : "f"(x)); return y; }
DI float rcp(float x) { float y; asm("rcp.approx.ftz.f32 %0, %1;" : "=f"(y) : "f"(x)); return y; }
DI float bf_lo(uint32_t x) { return __uint_as_float(x << 16); }
DI float bf_hi(uint32_t x) { return __uint_as_float(x & 0xffff0000u); }
DI void mma16816(float* d, const uint32_t* a, uint32_t b0, uint32_t b1) {
  asm volatile("mma.sync.aligned.m16n8k16.row.col.f32.bf16.bf16.f32 {%0,%1,%2,%3}, {%4,%5,%6,%7}, {%8,%9}, {%0,%1,%2,%3};"
               : "+f"(d[0]), "+f"(d[1]), "+f"(d[2]), "+f"(d[3]) : "r"(a[0]), "r"(a[1]), "r"(a[2]), "r"(a[3]), "r"(b0), "r"(b1));
}
DI void mma16816z(float* d, const uint32_t* a, uint32_t b0, uint32_t b1) {
  asm volatile("mma.sync.aligned.m16n8k16.row.col.f32.bf16.bf16.f32 {%0,%1,%2,%3}, {%4,%5,%6,%7}, {%8,%9}, {%10,%10,%10,%10};"
               : "=f"(d[0]), "=f"(d[1]), "=f"(d[2]), "=f"(d[3]) : "r"(a[0]), "r"(a[1]), "r"(a[2]), "r"(a[3]), "r"(b0), "r"(b1), "f"(0.f));
}
DI void mma1688z(float* d, uint32_t a0, uint32_t a1, uint32_t b0) {
  asm volatile("mma.sync.aligned.m16n8k8.row.col.f32.bf16.bf16.f32 {%0,%1,%2,%3}, {%4,%5}, {%6}, {%7,%7,%7,%7};"
               : "=f"(d[0]), "=f"(d[1]), "=f"(d[2]), "=f"(d[3]) : "r"(a0), "r"(a1), "r"(b0), "f"(0.f));
}
DI void mma1688(float* d, uint32_t a0, uint32_t a1, uint32_t b0) {
  asm volatile("mma.sync.aligned.m16n8k8.row.col.f32.bf16.bf16.f32 {%0,%1,%2,%3}, {%4,%5}, {%6}, {%0,%1,%2,%3};"
               : "+f"(d[0]), "+f"(d[1]), "+f"(d[2]), "+f"(d[3]) : "r"(a0), "r"(a1), "r"(b0));
}
DI void ldsm2t(uint32_t* r, uint32_t a) {
  asm volatile("ldmatrix.sync.aligned.m8n8.x2.trans.shared.b16 {%0,%1}, [%2];" : "=r"(r[0]), "=r"(r[1]) : "r"(a) : "memory");
}
DI uint32_t add_bf16(uint32_t a, uint32_t b) { uint32_t r; asm("add.rn.bf16x2 %0, %1, %2;" : "=r"(r) : "r"(a), "r"(b)); return r; }
DI uint32_t mul_bf16(uint32_t a, uint32_t b) { uint32_t r; asm("mul.rn.bf16x2 %0, %1, %2;" : "=r"(r) : "r"(a), "r"(b)); return r; }
DI uint64_t make_desc(uint32_t addr, uint32_t lbo, uint32_t sbo, uint32_t swz) {
  return (uint64_t)((addr & 0x3FFFF) >> 4) | ((uint64_t)(lbo >> 4) << 16) | ((uint64_t)(sbo >> 4) << 32) | ((uint64_t)swz << 62);
}
DI uint64_t desc_at(uint32_t a16, uint32_t lbo, uint32_t sbo, uint32_t swz) {
  uint64_t d; asm("mov.b64 %0, {%1, %2};" : "=l"(d) : "r"(a16 + ((lbo >> 4) << 16)), "r"((sbo >> 4) | (swz << 30)));
  return d;
}
#define WG_FENCE() asm volatile("wgmma.fence.sync.aligned;" ::: "memory")
#define WG_COMMIT() asm volatile("wgmma.commit_group.sync.aligned;" ::: "memory")
#define WG_WAIT(n) asm volatile("wgmma.wait_group.sync.aligned %0;" :: "n"(n) : "memory")
#define ACC8(d, o) "+f"(d[o]), "+f"(d[o + 1]), "+f"(d[o + 2]), "+f"(d[o + 3]), "+f"(d[o + 4]), "+f"(d[o + 5]), "+f"(d[o + 6]), "+f"(d[o + 7])
DI void wgmma_n32_rs(float* d, uint32_t a0, uint32_t a1, uint32_t a2, uint32_t a3, uint64_t db, int acc) {
  asm volatile("{\n.reg .pred p;\nsetp.ne.b32 p, %21, 0;\n"
               "wgmma.mma_async.sync.aligned.m64n32k16.f32.bf16.bf16 {%0,%1,%2,%3,%4,%5,%6,%7,%8,%9,%10,%11,%12,%13,%14,%15}, "
               "{%16,%17,%18,%19}, %20, p, 1, 1, 0;\n}\n"
               : ACC8(d, 0), ACC8(d, 8) : "r"(a0), "r"(a1), "r"(a2), "r"(a3), "l"(db), "r"(acc));
}
template <int TA>
DI void wgmma_n32_ss(float* d, uint64_t da, uint64_t db, int acc) {
  asm volatile("{\n.reg .pred p;\nsetp.ne.b32 p, %18, 0;\n"
               "wgmma.mma_async.sync.aligned.m64n32k16.f32.bf16.bf16 {%0,%1,%2,%3,%4,%5,%6,%7,%8,%9,%10,%11,%12,%13,%14,%15}, "
               "%16, %17, p, 1, 1, %19, 1;\n}\n"
               : ACC8(d, 0), ACC8(d, 8) : "l"(da), "l"(db), "r"(acc), "n"(TA));
}
DI void tma_load(uint32_t dst, const CUtensorMap* m, int c0, int c1, uint32_t mb) {
  asm volatile("cp.async.bulk.tensor.2d.shared::cluster.global.mbarrier::complete_tx::bytes [%0], [%1, {%3, %4}], [%2];"
               :: "r"(dst), "l"(m), "r"(mb), "r"(c0), "r"(c1) : "memory");
}
DI void tma_load3(uint32_t dst, const CUtensorMap* m, int row, uint32_t mb) {
  asm volatile("cp.async.bulk.tensor.3d.shared::cluster.global.mbarrier::complete_tx::bytes [%0], [%1, {%3, %4, %3}], [%2];"
               :: "r"(dst), "l"(m), "r"(mb), "r"(0), "r"(row) : "memory");
}
DI bool elect_one() {
  uint32_t p;
  asm volatile("{\n.reg .pred p;\nelect.sync _|p, 0xffffffff;\nselp.u32 %0, 1, 0, p;\n}" : "=r"(p));
  return p;
}
DI void bulk_s2s(uint32_t dst, uint32_t src, uint32_t bytes, uint32_t mb) {
  asm volatile("cp.async.bulk.shared::cluster.shared::cta.mbarrier::complete_tx::bytes [%0], [%1], %2, [%3];"
               :: "r"(dst), "r"(src), "r"(bytes), "r"(mb) : "memory");
}
DI void tma_prefetch(const CUtensorMap* m, int c0, int c1) {
  asm volatile("cp.async.bulk.prefetch.tensor.2d.L2.global.tile [%0, {%1, %2}];" :: "l"(m), "r"(c0), "r"(c1) : "memory");
}
DI void tma_store(const CUtensorMap* m, uint32_t src, int c0, int c1) {
  asm volatile("cp.async.bulk.tensor.2d.global.shared::cta.bulk_group [%0, {%2, %3}], [%1];" :: "l"(m), "r"(src), "r"(c0), "r"(c1) : "memory");
}
DI uint4 ldg_relaxed(const void* p) {
  uint4 v;
  asm volatile("ld.relaxed.gpu.global.v4.b32 {%0,%1,%2,%3}, [%4];" : "=r"(v.x), "=r"(v.y), "=r"(v.z), "=r"(v.w) : "l"(p) : "memory");
  return v;
}
DI void stg_relaxed(void* p, uint32_t x, uint32_t y, uint32_t z, uint32_t w) {
  asm volatile("st.relaxed.gpu.global.v4.b32 [%0], {%1,%2,%3,%4};" :: "l"(p), "r"(x), "r"(y), "r"(z), "r"(w) : "memory");
}
DI void red_f16x8(void* p, uint32_t x, uint32_t y, uint32_t z, uint32_t w) {
  asm volatile("red.relaxed.gpu.global.add.noftz.v4.f16x2 [%0], {%1,%2,%3,%4};" :: "l"(p), "r"(x), "r"(y), "r"(z), "r"(w) : "memory");
}
DI void sq_acc(uint32_t& a, uint32_t x) { asm("fma.rn.bf16x2 %0, %1, %1, %0;" : "+r"(a) : "r"(x)); }
DI __half2 amax4(__half2 h, const uint32_t* v) {
  h = __hmax2_nan(__hmax2_nan(h, __habs2(*(const __half2*)&v[0])), __habs2(*(const __half2*)&v[1]));
  return __hmax2_nan(__hmax2_nan(h, __habs2(*(const __half2*)&v[2])), __habs2(*(const __half2*)&v[3]));
}
DI uint32_t wexp(__half2 h) { const uint32_t u = *(const uint32_t*)&h; return __reduce_max_sync(0xffffffffu, max((u >> 16) & 0x7fffu, u & 0x7fffu)) >> 7; }
DI float max10(const float* a) {
  return fmaxf(fmaxf(fmaxf(fmaxf(a[0], a[1]), fmaxf(a[2], a[3])), fmaxf(fmaxf(a[4], a[5]), fmaxf(a[6], a[7]))), fmaxf(a[8], a[9]));
}
DI float quad_max(float m) {
  return fmaxf(fmaxf(m, __shfl_xor_sync(0xffffffffu, m, 1)), fmaxf(__shfl_xor_sync(0xffffffffu, m, 2), __shfl_xor_sync(0xffffffffu, m, 3)));
}
DI float warp_sum(float v) {
#pragma unroll
  for (int o = 16; o; o >>= 1) v += __shfl_xor_sync(0xffffffffu, v, o);
  return v;
}

constexpr int SM_WO3 = 0;
constexpr int SM_X = 16384;
constexpr int XT = 36864;
constexpr int SM_EXP = 126976;
constexpr int SEGB = 10240;
constexpr int SM_BLK = SM_EXP + 8192;
constexpr int SM_VC = SM_BLK + 4 * SEGB;
constexpr int SM_PART = SM_VC + 16384;
constexpr int SM_QM = SM_PART + 4096;
constexpr int SM_E = SM_QM + 1024;
constexpr int SM_VM = SM_E + 1536;
constexpr int SM_OB = SM_VM + 2048;
constexpr int SM_FB = SM_OB + 2048;
constexpr int SM_STAGE = SM_X + XT;
constexpr int SM_MISC = 210944;
constexpr int SM_WOST = 212992;
constexpr int SM_MEM = SM_WOST;
constexpr int SM_MAX = SM_MEM + 11264;
#define MEM_BLK(q) ((q) / 3 * 4096 + (q) % 3 * 1024)
constexpr int SM_TOTAL = 229376;
constexpr int MB_W = SM_MISC;
constexpr int MB_WO = SM_MISC + 24;
constexpr int MB_WO3 = SM_MISC + 32;
constexpr int MB_X = SM_MISC + 40;
constexpr int MB_S = SM_MISC + 64;
constexpr int MB_F = SM_MISC + 72;
constexpr int MB_VX = SM_MISC + 80;
constexpr int SC_FPAR = SM_MISC + 136;
constexpr int SC_DEAD = SM_MISC + 96;
constexpr int SC_UNSC = SM_MISC + 112;
constexpr int SC_EXPW = SM_MISC + 132;
constexpr int SC_ONES = SM_MISC + 144;
constexpr int SC_SS = SM_MISC + 160;
constexpr int SC_LAT = SM_MISC + 224;
constexpr int SC_XMAX = SM_MISC + 256;
constexpr int SC_PROF = 229376;

constexpr float SM_SCALE = 0.08838834764831845f;
constexpr float LOG2E = 1.4426950408889634f;
constexpr float E_LIM = 20.f;

template <bool B> struct BoolC { static constexpr bool value = B; };
struct RMaps { CUtensorMap x, wq, wk, wv, wo; unsigned char* red; uint32_t poll; };

DI uint32_t latest_hint(uint32_t h, uint32_t d, int s) {
  const uint32_t x = (((h | 0xc0c0c0c0u) - ((d >> 5) & 63) * 0x01010101u) & 0x3f3f3f3fu) | ((h ^ (((s >> 2) + 1) & 3) * 0x40404040u) & 0xc0c0c0c0u);
  const uint32_t y = __vmaxu2(x & 0x00ff00ffu, (x >> 8) & 0x00ff00ffu);
  return __reduce_max_sync(0xffffffffu, max(y & 0xffffu, y >> 16));
}
DI uint32_t near_half(uint32_t sb) {
  uint32_t a, b; lds64(sb + SC_LAT, a, b);
  return a > b;
}

template <int RT, int K0, int K1, bool D32 = false>
DI void xproj(float* acc, const uint32_t (&wa)[2][18][4], uint64_t xd) {
  if (XP & 1) return;
  WG_FENCE();
#pragma unroll
  for (int k = K0; k < ((XP & 128) ? K0 + 1 : K1); k++)
  {
    uint64_t d = xd + (uint64_t)(((k >> 1) * 4096 + (k & 1) * 32) >> 4);
    if (D32) asm("mov.b64 %0, {%1, %2};" : "=l"(d) : "r"((uint32_t)xd + (((k >> 1) * 4096 + (k & 1) * 32) >> 4)), "r"((uint32_t)(xd >> 32)));
    wgmma_n32_rs(acc, wa[RT][k][0], wa[RT][k][1], wa[RT][k][2], wa[RT][k][3], d, k != 0);
  }
  WG_COMMIT();
}

DI void seg_store(int seg, uint32_t sb, uint32_t off, uint32_t bytes) {
  asm volatile("cp.async.bulk.global.shared::cta.bulk_group [%0], [%1], %2;"
               :: "l"(g_seg + ((size_t)(seg & RING) * 96 + blockIdx.x) * SEGB + off), "r"(sb + SM_BLK + (seg & 3) * SEGB + off), "r"(bytes) : "memory");
  asm volatile("cp.async.bulk.commit_group;" ::: "memory");
}
DI void seg_publish(int seg) {
  asm volatile("cp.async.bulk.wait_group 0;" ::: "memory");
  asm volatile("red.relaxed.gpu.global.add.u32 [%0], 1;" :: "l"(&g_scnt[(seg * 32 + blockIdx.x / 3) * 8]) : "memory");
  SSTAMP(10, seg);
}

DI void proj_role(const uint32_t sb, const RMaps& tm, const uint32_t rank, const int wg, const int w, const int lane) {
  const bool qk = rank < 2;
  uint32_t wa[2][18][4];
  {
    const int rr = (lane & 7) + ((lane >> 4) << 3);
    const uint32_t col = ((2 * w + ((lane >> 3) & 1)) ^ (lane & 7)) << 4;
    float ss = 0.f;
#pragma unroll
    for (int c = 0; c < 3; c++) {
      mbar_wait(sb + MB_W + 8 * c, 0);
#pragma unroll
      for (int rt = 0; rt < 2; rt++)
#pragma unroll
        for (int k = 0; k < 6; k++)
          ldsm4t(wa[rt][c * 6 + k], sb + SM_STAGE + c * 49152 + (rt ^ wg) * 24576 + (64 * (k >> 1) + 32 * wg + 16 * (k & 1) + rr) * 128 + col);
      if (c < 2) {
        fence_async();
        bar_sync(3, 256);
        if (threadIdx.x == 0) {
          if (c == 0) tma_load3(sb + SM_X + XT, &tm.x, 32, sb + MB_X + 8);
          else tma_load(sb + SM_X + 2 * XT, &tm.wo, rank * 192, (blockIdx.x / 3) * DH, sb + MB_WO);
        }
        __syncwarp();
      }
      uint32_t q[4] = {0, 0, 0, 0};
#pragma unroll
      for (int rt = 0; rt < 2; rt++)
#pragma unroll
        for (int k = 0; k < 6; k++)
#pragma unroll
          for (int i = 0; i < 4; i++) sq_acc(q[i], wa[rt][c * 6 + k][i]);
#pragma unroll
      for (int i = 0; i < 4; i++) ss += bf_lo(q[i]) + bf_hi(q[i]);
    }
    ss = warp_sum(ss);
    fence_async();
    cluster_arrive();
    if (lane == 0) sts32(sb + SC_SS + 4 * (wg * 4 + w), qk ? 0 : __float_as_uint(ss));
    bar_arrive(11, 384);
  }
  STAMP(1);
  mbar_wait(sb + MB_X, 0);
  STAMP(2);

  uint32_t t16 = sb + (w * 32 + lane) * 16;
  uint32_t mem_a = sb + SM_MEM + wg * 512 + lane * 16;
  uint32_t fin_a = sb + (lane & 7) * 16 + SM_BLK + (qk ? (wg ^ 1) * 4096 + w * 256 + (lane & 8) * 16 + (lane & 16) * 64
                                              : wg * 4096 + w * 1024 + (lane & 8) * 64 + (lane & 16) * 8);
  PIN(t16); PIN(mem_a); PIN(fin_a);
  const uint32_t fence_reg = mem_a;
  const uint32_t fin2 = qk ? 2048 : 256;
  float acc[16];
  const uint64_t xd0 = make_desc(sb + SM_X + wg * 64, 16, 1024, 1);
  auto do_export = [&]() {
    WG_WAIT(0);
#pragma unroll
    for (int i = 0; i < 2; i++)
      sts128(t16 + SM_EXP + wg * 4096 + i * 2048, pack_bf16(acc[8 * i], acc[8 * i + 1]), pack_bf16(acc[8 * i + 2], acc[8 * i + 3]),
             pack_bf16(acc[8 * i + 4], acc[8 * i + 5]), pack_bf16(acc[8 * i + 6], acc[8 * i + 7]));
  };
  uint32_t o[8];
  auto import = [&]() { lds128(t16 + SM_EXP + (wg ^ 1) * 4096, o); lds128(t16 + SM_EXP + (wg ^ 1) * 4096 + 2048, o + 4); };
  auto finish = [&](int seg) {
    const uint32_t a = fin_a + (seg & 3) * SEGB;
    WG_WAIT(0);
#pragma unroll
    for (int i = 0; i < 8; i++) o[i] = FIN16 ? add_bf16(pack_bf16(acc[2 * i], acc[2 * i + 1]), o[i]) : pack_bf16(acc[2 * i] + bf_lo(o[i]), acc[2 * i + 1] + bf_hi(o[i]));
    stsm4(a, o[0], o[1], o[2], o[3]);
    stsm4(a + fin2, o[4], o[5], o[6], o[7]);
  };
  auto send_v = [&](int seg, int dst) {
    fence_async();
    if (seg < NSEG - 1 && !(XP & 2) && elect_one())
      bulk_s2s(mapa(sb + SM_VC + (seg & 1) * 8192, dst), sb + SM_BLK + (seg & 3) * SEGB, 8192, mapa(sb + MB_VX + (seg & 1) * 8, dst));
    __syncwarp();
  };
  auto wait_v = [&](int seg) {
    if (seg < NSEG - 1 && !(XP & 2)) {
      mbar_wait(sb + MB_VX + (seg & 1) * 8, (seg >> 1) & 1);
      if (elect_one()) mbar_expect(sb + MB_VX + (seg & 1) * 8, 8192);
      __syncwarp();
    }
  };
  bar_sync(3, 256);
  xproj<1, 0, 18>(acc, wa, xd0);
  do_export();
  SCHED_FENCE(11);
  xproj<0, 0, 18>(acc, wa, xd0);
  bar_sync(3, 256);
  cluster_wait();
  mbar_wait(sb + MB_X + 8, 0);
  import();
  finish(0);
  SCHED_FENCE(12);
  bar_sync(3, 256);
  uint64_t dA = xd0 + (XT >> 4);
  xproj<1, 0, 18>(acc, wa, dA);
  if (!qk && wg == 0 && w < 2) send_v(0, w);
  do_export();
  if (qk && wg == 0 && w == 0) wait_v(0);
  bar_arrive(13, 384);
  if (!qk) {
    SCHED_FENCE(15);
    xproj<0, 0, 18>(acc, wa, dA);
    if (threadIdx.x == 0 && !(XP & 8)) { mbar_expect(sb + MB_X, XT); tma_load3(sb + SM_X, &tm.x, 96, sb + MB_X); }
    bar_sync(3, 256);
    mbar_wait(sb + MB_X + 16, 0);
    import();
    finish(1);
    SCHED_FENCE(16);
    bar_sync(3, 256);
    dA += XT >> 4;
    xproj<1, 0, 18>(acc, wa, dA);
    if (wg == 0 && w < VW2) send_v(1, w);
    do_export();
  }
  bar_sync(0, 384);
  const int ro = __shfl_sync(0xffffffffu, near_half(sb) ^ wg, 0);
  STAMP(5);
  const uint32_t always = __shfl_sync(0xffffffffu, lds32(sb + SC_DEAD + 12), 0);
  const int ah = qk ? 1 : 2;
  int b2 = qk ? 2 : 0;
  int s = 0;
  uint32_t hint_lo = (uint32_t)(uint64_t)tm.red + HINT_OFF + blockIdx.x + (lane & 1) * 4096 + (lane >> 1) * 16384;
  PIN(hint_lo);
  auto post_hint = [&]() {
    asm volatile("{\n.reg .pred p;\n.reg .b64 a;\n.reg .u32 t;\nsetp.lt.u32 p, %0, %1;\nmov.b64 a, {%2, %3};\nmov.u32 t, %%globaltimer_lo;\n"
                 "bfe.u32 t, t, 5, 6;\nor.b32 t, t, %4;\n@p st.relaxed.gpu.global.u8 [a], t;\n}"
                 :: "r"(t16), "r"(sb + 128), "r"(hint_lo + RED_SLOT(s)), "r"((uint32_t)((uint64_t)tm.red >> 32)), "r"(((s >> 2) + 1) << 6) : "memory");
  };
  auto memproj = [&](auto second, int id, float u0, float u1, float* r) {
    constexpr bool R1 = decltype(second)::value;
    uint32_t b[NUP][4], b0[4];
    SCHED_FENCE(id);
    bar_sync(R1 ? 2 : 1, 256);
    PROF(0);
    ldsm4t(b0, mem_a);
#pragma unroll
    for (int q = 0; q < NUP; q++) {
      if (R1 && q == 2) {
        bar_sync(11, 256);
        SCHED_FENCE(id + 1);
      }
      ldsm4t(b[q], mem_a + MEM_BLK(q + 1));
    }
    mma16816z(&acc[0], wa[0][0], b0[0], b0[1]);
    mma16816z(&acc[4], wa[1][0], b0[0], b0[1]);
    mma16816z(&acc[8], wa[0][1], b0[2], b0[3]);
    mma16816z(&acc[12], wa[1][1], b0[2], b0[3]);
#pragma unroll
    for (int q = 1; q < 9; q++) {
      uint32_t* const c = b[(q - 1) % NUP];
      mma16816(&acc[0], wa[0][2 * q], c[0], c[1]);
      mma16816(&acc[4], wa[1][2 * q], c[0], c[1]);
      mma16816(&acc[8], wa[0][2 * q + 1], c[2], c[3]);
      mma16816(&acc[12], wa[1][2 * q + 1], c[2], c[3]);
      if (R1 && q + NUP == B3Q) bar_sync(3, 256);
      if (q + NUP < 9) ldsm4t_in(c, mem_a + MEM_BLK(q + NUP), always);
      else if (R1 && q + NUP < 11) lds128_in(c, t16 + SM_PART + (10 - q - NUP) * 2048, always);
      else if (!R1 && GATE && q == GATE) { bar_arrive(11, 256); lds128_in(c, sb + SC_DEAD, always); u0 = u1 = __uint_as_float(c[3]); }
    }
#pragma unroll
    for (int i = 0; i < 8; i++) {
      const float u = i < 4 ? u0 : u1;
      r[i] = R1 ? fmaf(acc[8 + i], u, (acc[i] + __uint_as_float(b[(8 + i / 4) % NUP][i & 3])) * u) : (GATE ? fmaf(acc[i], u, acc[8 + i]) : acc[i] + acc[8 + i]);
    }
  };
  if (ro == 0) {
#pragma unroll 1
    while (true) {
      if (s == 8) STAMP(6);
      float r[8];
      memproj(BoolC<false>(), 30, 0.f, 0.f, r);
      sts128(t16 + SM_PART, __float_as_uint(r[0]), __float_as_uint(r[1]), __float_as_uint(r[2]), __float_as_uint(r[3]));
      sts128(t16 + SM_PART + 2048, __float_as_uint(r[4]), __float_as_uint(r[5]), __float_as_uint(r[6]), __float_as_uint(r[7]));
      bar_arrive(3, 256);
      PROF(1);
      bar_sync(9, 256);
      if (s == NSEG - 1) break;
      post_hint();
      if (w == 1) {
        uint32_t m[8];
        lds128(t16 + SM_MAX - 512, m); lds128(t16 + SM_MAX, m + 4);
        const int em = (wexp(amax4(amax4(*(const __half2*)&m[0], m), m + 4)) >> 3) + (int)(lds32(sb + SC_UNSC + (s & 1) * 8) >> 23) - 15;
        const int ex = max(s ? em : 0, (int)lds32(sb + SC_XMAX + 4 * s)) - 127 + (int)lds32(sb + SC_EXPW);
        sts32(sb + SC_UNSC + (~s & 1) * 8, (127 + min(max(ex, -120), 120)) << 23);
        __syncwarp();
        if (elect_one()) mbar_arrive(sb + MB_S);
      }
      SCHED_FENCE(9);
      bar_sync(5, qk ? N5 : 256);
      PROF(2);
      import();
      xproj<0, 0, NII>(acc, wa, dA);
      if (NII < 18) {
        if (qk) bar_sync(7, 384);
        xproj<0, NII, 18>(acc, wa, dA);
        if (!qk) bar_sync(7, 384);
      } else {
        if (F10) WG_WAIT(0);
        bar_sync(10, 256);
        if (F10) SCHED_FENCE(17);
      }
      dA += (int64_t)(b2 ? XT >> 4 : -(XT >> 3));
      finish(s + ah);
      if (qk || w >= VW2) bar_arrive(13, 384);
      PROF(6);
      SCHED_FENCE(14);
      bar_sync(12, 256);
      PROF(7);
      xproj<1, 0, 18, true>(acc, wa, dA);
      bar_arrive(14, 256);
      b2 = b2 == 2 ? 0 : b2 + 1;
      s++;
      if (!qk && w < VW2) { bar_sync(13, 384); send_v(s + 1, w); }
      PROFP(8);
      do_export();
      PROFP(3);
    }
    if (!qk) bar_arrive(5, 256);
  } else {
#pragma unroll 1
    while (true) {
      if (s == 8) STAMP(6);
      const uint32_t tl = ((t16 >> 8) ^ wg) & 1, am = (t16 & ~256u) - w * 256;
      const float un = __uint_as_float(lds32(sb + SC_UNSC + (s & 1) * 8));
      float r[8];
      if (qk) {
        uint32_t a0 = am + (tl ? SM_QM : SM_BLK + 8192 + (s & 3) * SEGB);
        float u0 = wg ? un * (SM_SCALE * LOG2E) : un, u1 = wg ? un : un * (SM_SCALE * LOG2E);
        PIN(a0); PIN(u0); PIN(u1);
        memproj(BoolC<true>(), 32, u0, u1, r);
        stsm4(a0, pack_bf16(r[0], r[1]), pack_bf16(r[2], r[3]), pack_bf16(r[4], r[5]), pack_bf16(r[6], r[7]));
        bar_arrive(4, 256);
      } else {
        const uint32_t d0 = s < NSEG - 1 ? 0 : 2, d1 = s < NSEG - 1 ? 1 : 2;
        uint32_t r0 = mapa(t16 + SM_VM, d0), r1 = mapa(t16 + SM_VM, d1);
        PIN(r0); PIN(r1);
        memproj(BoolC<true>(), 34, un, un, r);
        const uint32_t p0 = pack_bf16(r[0], r[1]), p1 = pack_bf16(r[2], r[3]), p2 = pack_bf16(r[4], r[5]), p3 = pack_bf16(r[6], r[7]);
        const uint32_t v0 = wg ? p2 : p0, v1 = wg ? p3 : p1, v2 = wg ? p0 : p2, v3 = wg ? p1 : p3;
        st_async4(r0, v0, v1, v2, v3, mapa(sb + MB_S, d0));
        st_async4(r1, v0, v1, v2, v3, mapa(sb + MB_S, d1));
        bar_arrive(5, 256);
        if (EXB && s < NSEG - 1) bar_arrive(15, 160);
        sts128(t16 + SM_VM, v0, v1, v2, v3);
        stsm4(am + SM_BLK + 8192 + (s & 3) * SEGB + tl * 1024, p0, p1, p2, p3);
        __syncwarp();
        if (elect_one()) mbar_arrive(sb + MB_S);
      }
      if (s == NSEG - 1) break;
      PROF(1);
      auto rearm = [&]() { mbar_wait(sb + MB_S, s & 1); if (elect_one()) mbar_expect(sb + MB_S, qk ? 640 + 2048 : 1280); __syncwarp(); };
      if (w == 1) {
        if ((t16 & 384) == 0) stg_relaxed(tm.red + (RED_SLOT(s + 2) + RED_LINE(blockIdx.x)) + (t16 & 112), 0, 0, 0, 0);
      } else if (w == 0) {
        const int tn = s + ah + 1;
        if (RFW) mbar_wait(sb + MB_S, s & 1);
        if (tn + 1 < NSEG && !(XP & 8) && elect_one()) {
          const int b0 = b2 == 2 ? 0 : b2 + 1;
          mbar_expect(sb + MB_X + 8 * b0, XT);
          tma_load3(sb + SM_X + b0 * XT, &tm.x, (tn + 1) * 32, sb + MB_X + 8 * b0);
        }
        if (tn < NSEG && (!(XP & 8) || tn < 3)) mbar_wait(sb + MB_X + 8 * b2, (tn / 3) & 1);
      } else if (w == 2) {
        if (!qk) { if (VW2 < 1) send_v(s + 1, 0); if (VW2 < 2) send_v(s + 1, 1); }
      } else if (qk || !NIC) {
        rearm();
      }
      __syncwarp();
      import();
      PROF(4);
      SCHED_FENCE(10);
      if (NIC) {
        if (qk) bar_sync(7, NII < 18 ? 384 : 256);
        xproj<0, 0, NIC>(acc, wa, dA);
        if (!qk) { if (w == 3) rearm(); bar_sync(7, NII < 18 ? 384 : 256); }
      } else {
        bar_sync(7, NII < 18 ? 384 : 256);
      }
      xproj<0, NIC, 18>(acc, wa, dA);
      bar_arrive(12, 256);
      dA += (int64_t)(b2 ? XT >> 4 : -(XT >> 3));
      finish(s + ah);
      if (qk && w == 0) wait_v(s + 1);
      bar_arrive(13, 384);
      PROF(6);
      SCHED_FENCE(13);
      bar_sync(14, 256);
      PROF(7);
      xproj<1, 0, 18>(acc, wa, dA);
      b2 = b2 == 2 ? 0 : b2 + 1;
      s++;
      PROFP(8);
      do_export();
      PROFP(3);
    }
  }
  bar_arrive(0, 384);
  STAMP(3);
  cluster_sync();
  STAMP(4);
}

DI void attn_role(const uint32_t sb, unsigned char* smem_raw, const RMaps& tm, const uint32_t RANK, const bf16* __restrict__ x, const bf16* __restrict__ mem0,
                  const int w, const int lane) {
  const int t2 = w * 32 + lane;
  uint32_t wo[8][4], w1[8][4];
  const uint32_t wo_lane = sb + ((lane & 7) + ((lane >> 4) << 3)) * 128 + (((w + 4 * ((lane >> 3) & 1)) ^ (lane & 7)) << 4);
  unsigned char* const g_red = tm.red;
  {
    const uint32_t tag = *(volatile unsigned*)&g_epoch + 1;
    if (w == 0) {
      stg_relaxed(g_red + RED_SLOT(t2 >> 3) + RED_LINE(blockIdx.x) + (t2 & 7) * 16, 0, 0, 0, 0);
      asm volatile("st.relaxed.gpu.global.u8 [%0], 0;" :: "l"(g_red + RED_SLOT(t2) + HINT_OFF + (t2 & 4) * 1024 + (t2 >> 3) * 16384 + blockIdx.x) : "memory");
    }
    uint4 mv[5], xv[18];
#pragma unroll
    for (int i = 0; i < 5; i++) mv[i] = t2 + 128 * i < DM ? ((const uint4*)mem0)[t2 + 128 * i] : make_uint4(0, 0, 0, 0);
#pragma unroll
    for (int i = 0; i < 18; i++) xv[i] = blockIdx.x < NSEG ? ((const uint4*)(x + blockIdx.x * 32 * DM))[t2 + 128 * i] : make_uint4(0, 0, 0, 0);
    bar_sync(0, 384);
    cluster_arrive();
    __half2 hx = __float2half2_rn(0.f);
#pragma unroll
    for (int i = 0; i < 18; i++) hx = amax4(hx, &xv[i].x);
    if (blockIdx.x == 0)
#pragma unroll
      for (int i = 0; i < 5; i++) hx = amax4(hx, &mv[i].x);
    sts32(sb + SC_SS + 4 * (12 + w), wexp(hx));
    if (t2 == 0) { sts32(sb + SC_UNSC, __float_as_uint(1.f)); sts128(sb + SC_DEAD, 0, 0, 0, 0x3f800000u); sts64(sb + SC_FPAR, 0, 0); sts128(sb + SC_ONES, 0x3f803f80u, 0x3f803f80u, 0x3f803f80u, 0x3f803f80u); }
    WSTAMP(27);
    if (w == 0) __threadfence();
    uint32_t q[8] = {0, 0, 0, 0, 0, 0, 0, 0};
    mbar_wait(sb + MB_WO3, 0);
#pragma unroll
    for (int k = 0; k < 8; k++) {
      ldsm4t(wo[k], wo_lane + SM_WO3 + k * 2048); ldsm4t(w1[k], wo_lane + SM_WOST + k * 2048);
#pragma unroll
      for (int i = 0; i < 4; i++) { sq_acc(q[i], wo[k][i]); sq_acc(q[i], w1[k][i]); }
    }
    bar_sync(6, 128);
#pragma unroll
    for (int k = 0; k < 8; k++) sts128(sb + SM_WO3 + t2 * 16 + k * 2048, wo[k][0], wo[k][1], wo[k][2], wo[k][3]);
#pragma unroll
    for (int i = 0; i < 5; i++) {
      const int e = t2 + 128 * i, tok = e / 72, c = (e - tok * 72) * 8;
      const uint32_t u[4] = {mv[i].x, mv[i].y, mv[i].z, mv[i].w};
      if (e < DM)
#pragma unroll
        for (int j = 0; j < 8; j++) *(unsigned short*)(smem_raw + SM_MEM + (c + c / 192 * 64 + j) * 16 + tok * 2) = (unsigned short)(u[j >> 1] >> (16 * (j & 1)));
    }
    bar_arrive(1, 256); bar_arrive(2, 256); bar_arrive(9, 256);
    mbar_wait(sb + MB_WO, 0);
#pragma unroll
    for (int k = 0; k < 8; k++) ldsm4t(wo[k], wo_lane + SM_X + 2 * XT + k * 2048);
    fence_async();
    bar_sync(6, 128);
    if (t2 == 32) tma_load3(sb + SM_X + 2 * XT, &tm.x, 64, sb + MB_X + 16);
    __syncwarp();
#pragma unroll
    for (int k = 0; k < 8; k++)
#pragma unroll
      for (int i = 0; i < 4; i++) sq_acc(q[4 + i], wo[k][i]);
    float ss = 0.f;
#pragma unroll
    for (int i = 0; i < 8; i++) ss += bf_lo(q[i]) + bf_hi(q[i]);
    ss = warp_sum(ss);
    if (lane == 0) sts32(sb + SC_SS + 4 * (8 + w), __float_as_uint(ss));
    bar_sync(11, 384);
    if (t2 == 0) {
      float a[16];
#pragma unroll
      for (int i = 0; i < 4; i++) lds128f(sb + SC_SS + 16 * i, &a[4 * i]);
      stg_relaxed(&g_stats[blockIdx.x * 2], __float_as_uint(((a[0] + a[1]) + (a[2] + a[3])) + ((a[4] + a[5]) + (a[6] + a[7]))),
                  __float_as_uint((a[8] + a[9]) + (a[10] + a[11])),
                  max(max(__float_as_uint(a[12]), __float_as_uint(a[13])), max(__float_as_uint(a[14]), __float_as_uint(a[15]))), tag);
    }
    __syncwarp();
    WSTAMP(24);
    cluster_wait();
    if (w == 0) {
      uint4 v[3];
      int n = 0;
      while (true) {
#pragma unroll
        for (int i = 0; i < 3; i++) v[i] = ldg_relaxed(&g_stats[(i * 32 + lane) * 2]);
        if (__all_sync(0xffffffffu, v[0].w == tag && v[1].w == tag && v[2].w == tag) || ++n > SPIN_LIMIT) break;
        __nanosleep(100);
      }
      WSTAMP(25);
      const float sv = warp_sum(__uint_as_float(v[0].x) + __uint_as_float(v[1].x) + __uint_as_float(v[2].x));
      const float so = warp_sum(__uint_as_float(v[0].y) + __uint_as_float(v[1].y) + __uint_as_float(v[2].y));
      const int expW = ((int)(__float_as_uint(sv) >> 23) + (int)(__float_as_uint(so) >> 23) - 254 + 2 + 10 + 1) >> 1;
      sts32(sb + SC_XMAX + 4 * lane, v[0].z); sts32(sb + SC_XMAX + 128 + 4 * lane, v[1].z);
      sts32(sb + SC_EXPW, expW + 1 - 15);
      if (blockIdx.x == 0 && lane == 0) *(volatile unsigned*)&g_epoch = tag;
      sts32(sb + SC_FPAR + 4, 1);
    } else if (w < 3) {
      const uint32_t u = blockIdx.x >> 4;
      unsigned char* const z = g_red + 98304 + (blockIdx.x & 15) * 128 + (u & 1) * 2048 + (u & 6) * 4096 + (((u >> 1) ^ w) & 1) * 4096 + lane * 4;
      stg_relaxed32(z, 0);
      uint32_t best = 0xffffffffu;
#pragma unroll 1
      for (int i = 0; i < 64; i++) {
        uint32_t last, dt;
        asm volatile("{\n.reg .pred p;\n.reg .u32 c, v;\nld.volatile.shared.u32 %0, [%3];\nmov.u32 c, %%clock;\n"
                     "atom.relaxed.gpu.global.exch.b32 v, [%2], 0;\nsetp.eq.u32 p, v, 0;\nmov.u32 %1, 0;\n@p mov.u32 %1, %%clock;\nsub.u32 %1, %1, c;\n}"
                     : "=r"(last), "=r"(dt) : "l"(z), "r"(sb + SC_FPAR + 4) : "memory");
        best = min(best, dt);
        if (last && i >= NPROBE - 1) break;
      }
      sts32(sb + SC_LAT + (w - 1) * 4, best);
    }
    bar_sync(13, 384);
    bar_arrive(0, 384);
    WSTAMP(26);
  }

  const uint32_t nh = __shfl_sync(0xffffffffu, near_half(sb), 0);
  uint32_t l16 = sb + lane * 16;
  PIN(l16);
#define LV ((l16 >> 4) & 31)
#define fence_reg l16
  const uint32_t red_lo = (uint32_t)(uint64_t)g_red, red_hi = (uint32_t)((uint64_t)g_red >> 32);
  uint32_t lp;
  auto slot = [&](int s, uint32_t c, uint32_t ofs) {
    const uint32_t lo = lp | (red_lo + ((w >> 1) * 4 + (w & 1) * 2 + ((w ^ c) & 1)) * 4096 + RED_SLOT(s) + ofs);
    uint64_t a; asm("mov.b64 %0, {%1, %2};" : "=l"(a) : "r"(lo), "r"(red_hi));
    return (unsigned char*)a;
  };
  const uint32_t always = __shfl_sync(0xffffffffu, lds32(sb + SC_DEAD + 12), 0);
  const int mode0 = RANK < 2 ? w : w | 4;
  auto hint_addr = [&](int s) { return min(LV, 23u) * 4 + (red_lo + HINT_OFF + nh * 4096 + w * 16384 + RED_SLOT(s)); };
  auto load_hints = [&](uint32_t lo) {
    uint64_t a; asm("mov.b64 %0, {%1, %2};" : "=l"(a) : "r"(lo), "r"(red_hi));
    return ldg_relaxed32((const void*)a);
  };
  const uint32_t blk = RANK < 2 ? 9216 : SEGB, exb = RANK < 2 ? EXB : EXB2;
  auto export_rest = [&](int seg) { if (EXB && !(XP & 4) && elect_one()) seg_store(seg, sb, exb, blk - exb); __syncwarp(); };
  auto export_seg = [&](int seg) {
    if (!(XP & 4) && elect_one()) {
      if (seg > 0) seg_publish(seg - 1);
      fence_async();
      seg_store(seg, sb, 0, EXB ? exb : blk);
    }
    __syncwarp();
  };
  uint32_t dl = __shfl_sync(0xffffffffu, gtime() - 768, 0);
  int s = 0;
  bool bad = false;
#pragma unroll 1
  while (true) {
    const uint32_t par = s & 1;
    uint32_t vx[4][4], hints;
    auto load_vx = [&]() {
      const uint32_t va = l16 + (RANK < 2 ? SM_VC + par * 8192 : SM_BLK + (s & 3) * SEGB) + w * 1024 + ((LV >> 3) & 1) * 384 - (LV >> 4) * 128;
#pragma unroll
      for (int i = 0; i < 4; i++) ldsm4(vx[i], va + (i & 1) * 4096 + (i >> 1) * 256);
    };
    auto retire = [&](uint32_t x) {
      asm volatile("{\n.reg .pred p;\nsetp.eq.u32 p, %0, 0;\n@p exit;\n}" :: "r"(vx[0][0] | vx[1][0] | vx[2][0] | vx[3][0] | x) : "memory");
    };
    auto scores = [&](auto memkeys, auto first, float* sc) {
      constexpr bool MK = decltype(memkeys)::value, FIRST = decltype(first)::value;
      uint32_t kb[4][4], qb[2][4];
      const uint32_t m = LV >> 3;
      uint32_t kaddr = l16 + SM_BLK + 4096 + (s & 3) * SEGB + w * 2048 + (m & 1) * (MK ? 128 : 896) - (m >> 1) * 128;
      if (MK) { PIN(kaddr); }
      else {
#pragma unroll
        for (int k = 0; k < 4; k++) ldsm4t(kb[k], kaddr + k * 256);
      }
      if (FIRST) { load_vx(); retire(MK ? kaddr : kb[0][0] | kb[1][0] | kb[2][0] | kb[3][0] | l16); bar_sync(4, 256); PROF(4); }
      ldsm4t(qb[0], l16 + SM_QM);
      if (MK) ldsm4t(kb[0], kaddr);
      ldsm4t(qb[1], l16 + SM_QM + 512);
      if (MK) ldsm4t(kb[2], kaddr + 512);
      float c[4][4];
      mma16816z(c[0], kb[0], qb[0][0], qb[0][1]); mma16816z(c[1], kb[MK ? 0 : 1], qb[0][2], qb[0][3]);
      mma16816z(c[2], kb[2], qb[1][0], qb[1][1]); mma16816z(c[3], kb[MK ? 2 : 3], qb[1][2], qb[1][3]);
      if (FIRST && B5POS == 0) bar_arrive(5, N5);
#pragma unroll
      for (int i = 0; i < (MK ? 2 : 4); i++) sc[i] = ((c[0][i] + c[1][MK ? i + 2 : i]) + c[2][i]) + c[3][MK ? i + 2 : i];
    };
    auto send = [&](auto memkeys) {
      constexpr bool MK = decltype(memkeys)::value;
      constexpr int N = MK ? 1 : 2;
      const uint32_t sa = sb + LV * 4 + SM_E + (MK ? 1024 + RANK * 128 : RANK * 512 + w * 256);
      uint32_t ra[N][2], mb[N][2];
#pragma unroll
      for (int i = 0; i < N; i++)
#pragma unroll
        for (int j = 0; j < 2; j++) {
          ra[i][j] = mapa(sa + i * 128, j ? 2 : RANK ^ 1); mb[i][j] = mapa(sb + MB_S, j ? 2 : RANK ^ 1);
          PIN(ra[i][j]);
        }
      float sc[4];
      scores(memkeys, BoolC<true>(), sc);
      uint32_t e[N];
#pragma unroll
      for (int i = 0; i < N; i++) {
        e[i] = pack_bf16(ex2(sc[2 * i]), ex2(sc[2 * i + 1]));
        if (!(fmaxf(fabsf(sc[2 * i]), fabsf(sc[2 * i + 1])) <= E_LIM)) e[i] = 0x7fff7fffu;
        st_async1(ra[i][0], e[i], mb[i][0]);
        st_async1(ra[i][1], e[i], mb[i][1]);
      }
#pragma unroll
      for (int i = 0; i < N; i++) sts32(sa + i * 128, e[i]);
      __syncwarp();
      if (l16 == sb) mbar_arrive(sb + MB_S);
      PROF(5);
    };
    const int mode = bad ? 8 : mode0;
    if (mode < 2) {
      send(BoolC<false>());
    } else if (mode == 2) {
      send(BoolC<true>());
    } else if (mode == 8) {
      load_vx();
      retire(l16);
      const uint32_t fp = lds32(sb + SC_FPAR);
      bar_sync(6, 128);
      if (w == 0 && l16 == sb) { sts32(sb + SC_FPAR, fp ^ 1); mbar_expect(sb + MB_F, 3072); }
      if (RANK < 2 && w < 3) {
        float sc[4] = {0.f, 0.f, 0.f, 0.f};
        if (w < 2) scores(BoolC<false>(), BoolC<false>(), sc); else scores(BoolC<true>(), BoolC<false>(), sc);
#pragma unroll 1
        for (int r = 0; r < 3; r++)
          st_async4(mapa(l16 + SM_FB + RANK * 1536 + w * 512, r), __float_as_uint(sc[0]), __float_as_uint(sc[1]), __float_as_uint(sc[2]), __float_as_uint(sc[3]), mapa(sb + MB_F, r));
      }
      mbar_wait(sb + MB_F, fp);
      float a[12];
#pragma unroll
      for (int j = 0; j < 3; j++) {
        float b[4];
        lds128f(l16 + SM_FB + j * 512, a + 4 * j); lds128f(l16 + SM_FB + 1536 + j * 512, b);
#pragma unroll
        for (int i = 0; i < 4; i++) a[4 * j + i] += b[i];
      }
      float m0 = fmaxf(fmaxf(fmaxf(a[0], a[2]), fmaxf(a[4], a[6])), a[8]), m1 = fmaxf(fmaxf(fmaxf(a[1], a[3]), fmaxf(a[5], a[7])), a[9]);
#pragma unroll
      for (int o = 4; o < 32; o <<= 1) { m0 = fmaxf(m0, __shfl_xor_sync(0xffffffffu, m0, o)); m1 = fmaxf(m1, __shfl_xor_sync(0xffffffffu, m1, o)); }
#pragma unroll
      for (int i = 0; i < 5; i++) {
        const uint32_t ea = sb + SM_E + LV * 4 + (i < 4 ? i * 128 : 1024);
        sts32(ea, pack_bf16(ex2(a[2 * i] - m0), ex2(a[2 * i + 1] - m1)));
        sts32(ea + (i < 4 ? 512 : 128), 0x3f803f80u);
      }
      __syncwarp();
    } else {
      load_vx();
      if (mode == 3) bar_arrive(4, 256);
      retire(l16 + 1);
      if (w == 3) {
        if (EXPOS == 0 && s > 0) export_seg(s - 1);
        if (EXB) { if (RANK < 2) bar_sync(5, N5); else bar_sync(15, 160); if (s > 0) export_rest(s - 1); }
      }
    }
    {
      uint32_t wa[4], wb[4], oc[4];
      constexpr int WS = 2048;
      const uint32_t w3a = l16 + SM_WO3 + w * 512;
      lds128(w3a + KP(0) * WS, wa); lds128(w3a + KP(1) * WS, wb); lds128(sb + SC_ONES, oc);
      if (B5POS == 1 && mode < 3) bar_arrive(5, N5);
      uint32_t e[10], p[5], vm[4], ob[4];
      float o0[4], o1[4], f[3][2][4], rs[4];
      reserve2(vm); reserve2(vm + 2); reserve2(e + 8);
      hints = hint_addr(s);
      PIN(hints);
      if (CLR & 2) asm volatile("{\n.reg .pred p;\nsetp.eq.u32 p, %0, 0;\n@p exit;\n}" :: "r"(wa[0] | wb[0] | oc[0] | hints) : "memory");
      mbar_wait(sb + MB_S, par);
      PROF(6);
      ldsm4t(e, l16 + SM_E); ldsm2t_in(e + 8, l16 + SM_E + 1024, always); ldsm4t(e + 4, l16 + SM_E + 512);
      lds128_in(vm, l16 + w * 512 + SM_VM, always);
      const float scl = __uint_as_float(lds32(sb + SC_UNSC + 8 - par * 8));
      hints = load_hints(hints);
      if (GF & 1) SCHED_FENCE(4);
#pragma unroll
      for (int i = 0; i < 4; i++) p[i] = mul_bf16(e[i], e[4 + i]);
      p[4] = mul_bf16(e[8], e[9]);
      mma16816z(o0, vx[0], p[0], p[1]); mma16816z(o1, vx[1], p[0], p[1]); mma16816z(rs, oc, p[0], p[1]);
      mma16816(o0, vx[2], p[2], p[3]); lds128_in(vx[2], w3a + KP(2) * WS, always);
      mma16816(o1, vx[3], p[2], p[3]); lds128_in(vx[3], w3a + KP(3) * WS, always);
      mma16816(rs, oc, p[2], p[3]);
      mma1688(o0, vm[0], vm[1], p[4]); mma1688(o1, vm[2], vm[3], p[4]); mma1688(rs, oc[0], oc[1], p[4]);
      stsm4(l16 + w * 512 + SM_OB, pack_bf16(o0[0], o0[1]), pack_bf16(o0[2], o0[3]), pack_bf16(o1[0], o1[1]), pack_bf16(o1[2], o1[3]));
      bar_sync(6, 128);
      PROF(7);
      ldsm4t_in(oc, l16 + SM_OB, always);
      bad = __any_sync(0xffffffffu, !(rs[0] + rs[1] > 0.f) && !bad);
      rs[0] *= scl; rs[1] *= scl;
      asm volatile("{\n.reg .pred p;\nsetp.ne.u32 p, %1, 0;\n@p rcp.approx.ftz.f32 %0, %0;\n}" : "+f"(rs[0]) : "r"(always));
      asm volatile("{\n.reg .pred p;\nsetp.ne.u32 p, %1, 1;\n@p rcp.approx.ftz.f32 %0, %0;\n}" : "+f"(rs[1]) : "r"(always));
      asm volatile("lop3.b32 %0, %1, %2, %3, 0xfe;" : "=r"(lp) : "r"((l16 & 128) * 2), "r"((l16 & 256) * 4), "r"(l16 & 112));
      if (bad) continue;
      ldsm4t(ob, l16 + SM_OB + 512);
      mma16816z(f[2][0], wa, oc[0], oc[1]); mma16816z(f[2][1], wb, oc[2], oc[3]);
      mma16816z(f[0][0], wo[0], oc[0], oc[1]); mma16816z(f[0][1], wo[4], oc[2], oc[3]);
      mma16816z(f[1][0], w1[0], oc[0], oc[1]); mma16816z(f[1][1], w1[4], oc[2], oc[3]);
      ldsm4t_in(oc, l16 + SM_OB + 1024, always);
      mma16816(f[2][0], vx[2], ob[0], ob[1]); lds128_in(vx[2], w3a + KP(4) * WS, always);
      mma16816(f[2][1], vx[3], ob[2], ob[3]); lds128_in(vx[3], w3a + KP(5) * WS, always);
      mma16816(f[0][0], wo[1], ob[0], ob[1]); mma16816(f[0][1], wo[5], ob[2], ob[3]);
      mma16816(f[1][0], w1[1], ob[0], ob[1]); mma16816(f[1][1], w1[5], ob[2], ob[3]);
      ldsm4t_in(ob, l16 + SM_OB + 1536, always);
      mma16816(f[0][0], wo[2], oc[0], oc[1]); mma16816(f[0][1], wo[6], oc[2], oc[3]);
      mma16816(f[2][0], vx[2], oc[0], oc[1]); lds128_in(vx[2], w3a + KP(6) * WS, always);
      mma16816(f[2][1], vx[3], oc[2], oc[3]); lds128_in(vx[3], w3a + KP(7) * WS, always);
      mma16816(f[1][0], w1[2], oc[0], oc[1]); mma16816(f[1][1], w1[6], oc[2], oc[3]);
      mma16816(f[0][0], wo[3], ob[0], ob[1]); mma16816(f[0][1], wo[7], ob[2], ob[3]);
      mma16816(f[1][0], w1[3], ob[0], ob[1]); mma16816(f[1][1], w1[7], ob[2], ob[3]);
      mma16816(f[2][0], vx[2], ob[0], ob[1]); mma16816(f[2][1], vx[3], ob[2], ob[3]);
      bar_arrive(7, NII < 18 ? 384 : 256);
      lds128_in(ob, sb + SC_DEAD, always);
      uint32_t h[3][2];
#pragma unroll
      for (int j = 0; j < 3; j++)
#pragma unroll
        for (int i = 0; i < 2; i++)
        {
          scale_sum(f[j][1][2 * i], f[j][0][2 * i], rs[0], always); scale_sum(f[j][1][2 * i + 1], f[j][0][2 * i + 1], rs[1], always);
          h[j][i] = pack_f16(f[j][1][2 * i], f[j][1][2 * i + 1]);
        }
      const uint32_t rofs = RANK * 32768;
      red_f16x8(slot(s, RANK >> 1, rofs), h[0][0], h[1][0], h[2][0], 0x3c00u);
      red_f16x8(slot(s, (RANK >> 1) ^ 1, rofs), h[0][1], h[1][1], h[2][1], 0x3c00u);
      if (NII == 18) bar_arrive(10, 256);
      SCHED_FENCE(5);
      l16 += ob[B7R];
    }
    {
    PROF(8);
    const uint32_t ma0 = l16 + SM_MEM + w * 128 + (LV >> 3) * 896 + nh * 512;
    const unsigned char* const sl[2] = {slot(s, nh, 0), slot(s, nh ^ 1, 0)};
    uint32_t late = latest_hint(hints, dl, s);
    if (late >= 64) {
      int n = 0;
#pragma unroll 1
      do {
        late = latest_hint(load_hints(hint_addr(s)), dl, s);
      } while (late >= 64 && ++n < SPIN_LIMIT);
    }
    dl += late * 32 + tm.poll;
    if (EXPOS == 2 && w == 3) export_seg(s);
    PROF(9);
    {
      auto wait_until = [&](uint32_t t) {
        asm volatile("{\n.reg .pred p;\n.reg .s32 c;\n.reg .u64 t;\nTL: mov.u64 t, %%globaltimer;\ncvt.u32.u64 c, t;\nsub.s32 c, c, %0;\nsetp.lt.s32 p, c, 0;\n@p bra.uni TL;\n}" :: "r"(t + (l16 & 15)) : "memory");
      };
      uint4 v[2][3];
      auto load = [&](int c) {
#pragma unroll
        for (int r = 0; r < 3; r++) v[c][r] = ldg_relaxed(sl[c ^ (r >> 1)] + r * 32768);
      };
      auto decode = [&](int c, int n) {
        uint32_t q[9];
        __half2 hm;
        const uint32_t ma = ma0 ^ (c * 512);
#pragma unroll
        for (int i = 0; i < 9; i++) {
          const uint32_t h = i % 3 == 0 ? v[c][i / 3].x : (i % 3 == 1 ? v[c][i / 3].y : v[c][i / 3].z);
          const float2 f = __half22float2(*(const __half2*)&h);
          q[i] = pack_bf16(f.x, f.y);
          hm = i ? __hmax2(hm, __habs2(*(const __half2*)&h)) : __habs2(*(const __half2*)&h);
        }
#pragma unroll
        for (int r = 0; r < 3; r++) stsm4(ma + r * 4096, q[3 * r], q[3 * r + 1], q[3 * r + 2], r < 2 ? v[c][r].w : *(const uint32_t*)&hm);
        const bool done = __all_sync(0xffffffffu, v[c][0].w == 0x5000u && v[c][1].w == 0x5000u && v[c][2].w == 0x5000u) || n > SPIN_LIMIT;
        asm volatile("{\n.reg .pred p;\nsetp.ne.u32 p, %0, 0;\n@p bar.arrive %1, 256;\n}" :: "r"((int)done), "r"(1 + c) : "memory");
        return done;
      };
      if (LEAD) { wait_until(dl - LEAD); load(1); }
      wait_until(dl);
      PROF(10);
      int n = 0;
#pragma unroll 1
      do {
        load(0);
        if (!LEAD) load(1);
        asm volatile("{\n.reg .pred p;\nsetp.eq.u32 p, %0, 0;\n@p bar.sync 13, 384;\n}" :: "r"(n) : "memory");
      } while (!decode(0, n++));
      PROF(11);
#pragma unroll 1
      while (!decode(1, n++)) load(1);
      bar_arrive(9, 256);
      PROF(12);
    }
    if (EXPOS == 3 && w == 3) export_seg(s);
    PROF(13);
    if (++s == NSEG - 1) break;
    }
  }
#undef fence_reg
  if (RANK < 2) bar_arrive(4, 256);
  if (w == 3) { if (EXPOS < 2 || EXPOS == 4) export_seg(NSEG - 2); export_rest(NSEG - 2); if (!(XP & 4) && elect_one()) seg_publish(NSEG - 2); }
  __syncwarp();
  bar_sync(0, 384);
  if (w == 3 && !(XP & 4) && elect_one()) {
    fence_async();
    seg_store(NSEG - 1, sb, 0, blk);
    seg_publish(NSEG - 1);
  }
  __syncwarp();
  cluster_sync();
}

__global__ void __cluster_dims__(3, 1, 1) __launch_bounds__(384, 1)
rec_kernel(const __grid_constant__ RMaps tm, const bf16* __restrict__ x, const bf16* __restrict__ mem0) {
  extern __shared__ __align__(1024) unsigned char smem_raw[];
  const uint32_t sb = smem_u32(smem_raw);
  const int tid = threadIdx.x, lane = tid & 31;
  const int wg = __shfl_sync(0xffffffffu, tid >> 7, 0);
  const int w = __shfl_sync(0xffffffffu, (tid >> 5) & 3, 0);
  uint32_t rank; asm("mov.u32 %0, %%cluster_ctarank;" : "=r"(rank));
  STAMP(0);
  asm volatile("griddepcontrol.launch_dependents;" ::: "memory");

  if (wg < 2) {
    asm volatile("setmaxnreg.inc.sync.aligned.u32 192;");
    if (tid == 0) {
      for (int i = 0; i < 3; i++) { mbar_init(sb + MB_W + 8 * i, 1); mbar_init(sb + MB_X + 8 * i, 1); }
      mbar_init(sb + MB_WO, 1); mbar_init(sb + MB_WO3, 1);
      mbar_init(sb + MB_S, rank < 2 ? 5 : 6);
      mbar_init(sb + MB_F, 1);
      mbar_init(sb + MB_VX, 1); mbar_init(sb + MB_VX + 8, 1);
      asm volatile("fence.mbarrier_init.release.cluster;" ::: "memory");
      fence_async();
      const int h = blockIdx.x / 3;
      const CUtensorMap* m0 = rank < 2 ? &tm.wk : &tm.wv;
      const CUtensorMap* m1 = rank < 2 ? &tm.wq : &tm.wv;
      const int c0 = h * DH + (rank == 1 ? 64 : 0), c1 = h * DH + (rank == 0 ? 0 : 64);
      for (int c = 0; c < 3; c++) {
        mbar_expect(sb + MB_W + 8 * c, 49152);
        tma_load(sb + SM_STAGE + c * 49152, m0, c0, c * 192, sb + MB_W + 8 * c);
        tma_load(sb + SM_STAGE + c * 49152 + 24576, m1, c1, c * 192, sb + MB_W + 8 * c);
      }
      for (int i = 0; i < 3; i++) mbar_expect(sb + MB_X + 8 * i, XT);
      tma_load3(sb + SM_X, &tm.x, 0, sb + MB_X);
      tma_prefetch(&tm.wo, rank * 192, h * DH);
      mbar_expect(sb + MB_WO, 16384);
      mbar_expect(sb + MB_WO3, 32768);
      tma_load(sb + SM_WOST, &tm.wo, rank * 192 + 64, h * DH, sb + MB_WO3);
      tma_load(sb + SM_WO3, &tm.wo, rank * 192 + 128, h * DH, sb + MB_WO3);
      mbar_expect(sb + MB_S, rank < 2 ? 640 + 2048 : 1280);
      mbar_expect(sb + MB_VX, 8192); mbar_expect(sb + MB_VX + 8, 8192);
    }
    __syncwarp();
    bar_sync(0, 384);
    proj_role(sb, tm, rank, wg, w, lane);
  } else {
    asm volatile("setmaxnreg.dec.sync.aligned.u32 120;");
    attn_role(sb, smem_raw, tm, rank, x, mem0, w, lane);
  }
}

constexpr int NAUX = 36;
constexpr int A_XH = 73728;
constexpr int A_NS = 9, A_WM = 6144, A_WT = 768;
constexpr int A_RING = 2 * A_XH, A_TAIL = A_RING + A_NS * A_WM, A_GW = A_TAIL + A_NS * A_WT;
constexpr int A_EPI = 212864, A_EPW = 9344;
constexpr int A_XT = 4 * XT, A_XW = A_XT + 8192, A_EX = A_XW + 8192, A_NR = 4;
constexpr int A_IN = A_EX + 16384, A_OST = A_IN + 3 * SEGB;
constexpr int A_GATE = A_EPI + 2 * A_EPW, A_BAR = A_GATE + 512;
constexpr int A_TOTAL = A_BAR + 384;
struct AMaps { CUtensorMap x, wa, wt, oa, o, o3, wob, woa; };

DI void wgmma_n192_ss_nt(float* d, uint64_t da, uint64_t db, int acc) {
  asm volatile("{\n.reg .pred p;\nsetp.ne.b32 p, %98, 0;\n"
               "wgmma.mma_async.sync.aligned.m64n192k16.f32.bf16.bf16 {"
               "%0,%1,%2,%3,%4,%5,%6,%7,%8,%9,%10,%11,%12,%13,%14,%15,%16,%17,%18,%19,%20,%21,%22,%23,%24,%25,%26,%27,%28,%29,%30,%31,"
               "%32,%33,%34,%35,%36,%37,%38,%39,%40,%41,%42,%43,%44,%45,%46,%47,%48,%49,%50,%51,%52,%53,%54,%55,%56,%57,%58,%59,%60,%61,%62,%63,"
               "%64,%65,%66,%67,%68,%69,%70,%71,%72,%73,%74,%75,%76,%77,%78,%79,%80,%81,%82,%83,%84,%85,%86,%87,%88,%89,%90,%91,%92,%93,%94,%95"
               "}, %96, %97, p, 1, 1, 0, 1;\n}\n"
               : ACC8(d, 0), ACC8(d, 8), ACC8(d, 16), ACC8(d, 24), ACC8(d, 32), ACC8(d, 40), ACC8(d, 48), ACC8(d, 56),
                 ACC8(d, 64), ACC8(d, 72), ACC8(d, 80), ACC8(d, 88) : "l"(da), "l"(db), "r"(acc));
}
#define ACC4(d, o) "+f"(d[o]), "+f"(d[o + 1]), "+f"(d[o + 2]), "+f"(d[o + 3])
DI void wgmma_n24_ss_nt(float* d, uint64_t da, uint64_t db, int acc) {
  asm volatile("{\n.reg .pred p;\nsetp.ne.b32 p, %14, 0;\n"
               "wgmma.mma_async.sync.aligned.m64n24k16.f32.bf16.bf16 {%0,%1,%2,%3,%4,%5,%6,%7,%8,%9,%10,%11}, %12, %13, p, 1, 1, 0, 1;\n}\n"
               : ACC8(d, 0), ACC4(d, 8) : "l"(da), "l"(db), "r"(acc));
}
DI void wgmma_n40_ss_tt(float* d, uint64_t da, uint64_t db, int acc) {
  asm volatile("{\n.reg .pred p;\nsetp.ne.b32 p, %22, 0;\n"
               "wgmma.mma_async.sync.aligned.m64n40k16.f32.bf16.bf16 {%0,%1,%2,%3,%4,%5,%6,%7,%8,%9,%10,%11,%12,%13,%14,%15,%16,%17,%18,%19}, "
               "%20, %21, p, 1, 1, 1, 1;\n}\n"
               : ACC8(d, 0), ACC8(d, 8), ACC4(d, 16) : "l"(da), "l"(db), "r"(acc));
}
DI void wgmma_n64_rs(float* d, const uint32_t* a, uint64_t db, int acc) {
  asm volatile("{\n.reg .pred p;\nsetp.ne.b32 p, %37, 0;\n"
               "wgmma.mma_async.sync.aligned.m64n64k16.f32.bf16.bf16 {"
               "%0,%1,%2,%3,%4,%5,%6,%7,%8,%9,%10,%11,%12,%13,%14,%15,%16,%17,%18,%19,%20,%21,%22,%23,%24,%25,%26,%27,%28,%29,%30,%31"
               "}, {%32,%33,%34,%35}, %36, p, 1, 1, 0;\n}\n"
               : ACC8(d, 0), ACC8(d, 8), ACC8(d, 16), ACC8(d, 24) : "r"(a[0]), "r"(a[1]), "r"(a[2]), "r"(a[3]), "l"(db), "r"(acc));
}
DI void wgmma_n32_ss_tn(float* d, uint64_t da, uint64_t db, int acc) {
  asm volatile("{\n.reg .pred p;\nsetp.ne.b32 p, %18, 0;\n"
               "wgmma.mma_async.sync.aligned.m64n32k16.f32.bf16.bf16 {%0,%1,%2,%3,%4,%5,%6,%7,%8,%9,%10,%11,%12,%13,%14,%15}, "
               "%16, %17, p, 1, 1, 1, 0;\n}\n"
               : ACC8(d, 0), ACC8(d, 8) : "l"(da), "l"(db), "r"(acc));
}
DI void tma_load3c(uint32_t dst, const CUtensorMap* m, int c0, int c1, int c2, uint32_t mb) {
  asm volatile("cp.async.bulk.tensor.3d.shared::cluster.global.mbarrier::complete_tx::bytes [%0], [%1, {%3, %4, %5}], [%2];"
               :: "r"(dst), "l"(m), "r"(mb), "r"(c0), "r"(c1), "r"(c2) : "memory");
}
DI uint32_t movm(uint32_t x) { uint32_t r; asm volatile("movmatrix.sync.aligned.m8n8.trans.b16 %0, %1;" : "=r"(r) : "r"(x)); return r; }
DI void wait_count(const unsigned* p, unsigned target) {
  int n = 0;
  unsigned v;
  while (true) {
    asm volatile("ld.acquire.gpu.global.b32 %0, [%1];" : "=r"(v) : "l"(p) : "memory");
    if ((int)(v - target) >= 0 || ++n > SPIN_LIMIT) break;
    __nanosleep(64);
  }
}
DI void count_up(unsigned* p) {
  asm volatile("fence.proxy.async;" ::: "memory");
  asm volatile("red.release.gpu.global.add.u32 [%0], 1;" :: "l"(p) : "memory");
}
#define AX 0
#define ADLY 0

__global__ void __launch_bounds__(512, 1)
aux_kernel(const __grid_constant__ AMaps tm, const bf16* __restrict__ wqkv, const bf16* __restrict__ gate_w, bf16* __restrict__ out) {
  extern __shared__ __align__(1024) unsigned char smem_raw[];
  const uint32_t sb = smem_u32(smem_raw);
  const uint32_t fullx = sb + A_BAR, full1 = fullx + 24, empty1 = full1 + 8 * A_NS, fullw = empty1 + 8 * A_NS, full3 = fullw + 8, empty3 = full3 + 8 * A_NR,
                 fullq = empty3 + 8 * A_NR, fullv = fullq + 8, emptyq = fullv + 8, emptyv = emptyq + 8;
  const int tid = threadIdx.x, lane = tid & 31, cta = blockIdx.x;
  const int wg = __shfl_sync(0xffffffffu, tid >> 7, 0), w = __shfl_sync(0xffffffffu, (tid >> 5) & 3, 0);
  ASTAMP(14);
  if (tid == 384) {
    for (int i = 0; i < 3; i++) mbar_init(fullx + 8 * i, 1);
    for (int i = 0; i < A_NS; i++) { mbar_init(full1 + 8 * i, 1); mbar_init(empty1 + 8 * i, 8); }
    mbar_init(fullw, 1); mbar_init(fullq, 1); mbar_init(fullv, 1); mbar_init(emptyq, 4); mbar_init(emptyv, 4);
    for (int i = 0; i < A_NR; i++) { mbar_init(full3 + 8 * i, 1); mbar_init(empty3 + 8 * i, 4); }
    fence_async();
  }
  __syncthreads();
  ASTAMP(0);
  const int tile = cta >> 1, hh = cta & 1;
  const int nsl = cta >> 2, kq = cta & 3;
  if (wg == 3) {
    asm volatile("setmaxnreg.dec.sync.aligned.u32 24;");
    const bool lead = lane == 0;
    if (w < 3) {
      if (ADLY) wait_until(gtime() + ADLY);
      if (elect_one()) {
        mbar_expect(fullx + 8 * w, 49152);
        for (int p = 0; p < 2; p++)
          asm volatile("cp.async.bulk.tensor.4d.shared::cluster.global.mbarrier::complete_tx::bytes [%0], [%1, {%3, %4, %5, %6}], [%2];"
                       :: "r"(sb + p * A_XH + w * 24576), "l"(&tm.x), "r"(fullx + 8 * w), "r"(0), "r"(p), "r"(57 * tile - 7), "r"(3 * w) : "memory");
      }
#pragma unroll 1
      for (int r = 0; r < 17; r++) {
#pragma unroll 1
        for (int st = w; st < A_NS; st += 3) {
          if (r > 0) mbar_wait(empty1 + 8 * st, ~r & 1);
          if (r < 16 && elect_one()) {
            const int col = hh * 288 + (r >> 2) * 72, row = (r & 3) * 144 + st * 16;
            mbar_expect(full1 + 8 * st, A_WM + (AX & 1 ? 0 : A_WT));
            tma_load3c(sb + A_RING + st * A_WM, &tm.wa, col, row, 0, full1 + 8 * st);
            if (!(AX & 1)) tma_load3c(sb + A_TAIL + st * A_WT, &tm.wt, col + 64, row, 0, full1 + 8 * st);
          }
          __syncwarp();
        }
        if (r == 0 && elect_one())
          for (int j = 0; j < 3; j++)
            asm volatile("cp.async.bulk.prefetch.L2.global [%0], %1;" :: "l"((const char*)wqkv + cta * 55296 + (w * 3 + j) * 6144), "r"(6144) : "memory");
        __syncwarp();
      }
      bar_sync(8, 96);
    }
    const unsigned epoch = lds32(sb + A_BAR + 376);
    if (w == 1 && cta < NH) {
#pragma unroll 1
      for (int seg = 0; seg < NSEG; seg++) {
        bar_arrive(5, 160);
        if (seg > 0 && lead) {
          asm volatile("cp.async.bulk.wait_group 0;" ::: "memory");
          asm volatile("red.relaxed.gpu.global.add.u32 [%0], 1;" :: "l"(&g_ocnt[(seg - 1) * 32]) : "memory");
          SSTAMP(9, seg - 1);
        }
        __syncwarp();
        bar_sync(4, 160);
        if (lead) {
          tma_store(&tm.o, sb + A_OST, cta * DH, seg * 32);
          tma_store(&tm.o, sb + A_OST + 4096, cta * DH + 64, seg * 32);
          asm volatile("cp.async.bulk.commit_group;" ::: "memory");
          asm volatile("cp.async.bulk.wait_group.read 0;" ::: "memory");
        }
        __syncwarp();
      }
      if (lead) {
        asm volatile("cp.async.bulk.wait_group 0;" ::: "memory");
        asm volatile("red.relaxed.gpu.global.add.u32 [%0], 1;" :: "l"(&g_ocnt[(NSEG - 1) * 32]) : "memory");
        SSTAMP(9, NSEG - 1);
      }
    }
    if (w == 2) {
      if (lead && cta < NH) {
#pragma unroll 1
        for (int seg = 0; seg < NSEG; seg++) {
          const unsigned char* const src = g_seg + ((size_t)(seg & RING) * 96 + cta * 3) * SEGB;
          SSTAMP(0, seg);
          wait_count(&g_scnt[(seg * 32 + cta) * 8], 3 * (epoch + 1));
          SSTAMP(1, seg);
          mbar_wait(emptyq, ~seg & 1);
          mbar_expect(fullq, 2 * SEGB);
          asm volatile("cp.async.bulk.shared::cluster.global.mbarrier::complete_tx::bytes [%0], [%1], %2, [%3];"
                       :: "r"(sb + A_IN), "l"(src), "r"(2 * SEGB), "r"(fullq) : "memory");
          mbar_wait(emptyv, ~seg & 1);
          mbar_expect(fullv, SEGB);
          asm volatile("cp.async.bulk.shared::cluster.global.mbarrier::complete_tx::bytes [%0], [%1], %2, [%3];"
                       :: "r"(sb + A_IN + 2 * SEGB), "l"(src + 2 * SEGB), "r"(SEGB), "r"(fullv) : "memory");
        }
      }
    }
    if (w == 3) {
#pragma unroll 1
      for (int c = 0; c < 4; c++) {
        if (lead) asm volatile("cp.async.bulk.wait_group.read 0;" ::: "memory");
        __syncwarp();
        bar_arrive(11, 160); bar_arrive(12, 160);
#pragma unroll 1
        for (int g = 0; g < 2; g++) {
          bar_sync(13 + g, 160);
          if (lead) {
            asm volatile("cp.async.bulk.tensor.3d.global.shared::cta.bulk_group [%0, {%2, %3, %4}], [%1];"
                         :: "l"(&tm.oa), "r"(sb + A_EPI + g * A_EPW + 1024), "r"(4096 + hh * 288 + c * 72), "r"(g), "r"(57 * tile) : "memory");
            asm volatile("cp.async.bulk.commit_group;" ::: "memory");
          }
        }
      }
      if (lead) asm volatile("cp.async.bulk.wait_group.read 0;" ::: "memory");
      __syncwarp();
      bar_arrive(10, 160);
      if (lead) { asm volatile("cp.async.bulk.wait_group 0;" ::: "memory"); count_up(&g_abar[32]); }
    }
    if (w != 0) return;
    if (lead) {
      mbar_expect(fullw, 19 * 8192);
#pragma unroll 1
      for (int k = 0; k < 19; k++) {
        const int kb = k < 18 ? kq * 18 + k : 72;
        const uint32_t dst = sb + (k < 18 ? k * 8192 : A_XW);
        if (kb < 64) tma_load(dst, &tm.wob, nsl * 64, kb * 64, fullw);
        else tma_load(dst, &tm.woa, nsl * 64, (kb - 64) * 64, fullw);
      }
    }
    __syncwarp();
    bar_sync(6, 288);
    if (lead) {
      if (kq == 3) { wait_count(&g_abar[32], NAUX * (epoch + 1)); asm volatile("fence.proxy.async;" ::: "memory"); }
      int avail = 0;
      for (int seg = 0; seg < NSEG; seg++) {
        if (seg >= avail) {
          const int far = min(seg + 3, NSEG - 1);
          if ((int)(ldg_acquire32(&g_ocnt[far * 32]) - 32 * (epoch + 1)) >= 0) avail = far + 1;
          else { wait_count(&g_ocnt[seg * 32], 32 * (epoch + 1)); avail = seg + 1; }
        }
        SSTAMP(5, seg);
        for (int g = 0; g < 2; g++) {
          const int sl = (seg & 1) * 2 + g;
          const bool extra = kq == 3 && g == 0;
          mbar_wait(empty3 + 8 * sl, ((seg >> 1) & 1) ^ 1);
          mbar_expect(full3 + 8 * sl, XT + (extra ? 4096 : 0));
          tma_load3c(sb + sl * XT, &tm.o3, 0, seg * 32, kq * 18 + 9 * g, full3 + 8 * sl);
          if (extra) tma_load(sb + A_XT + (seg & 1) * 4096, &tm.o, 72 * 64, seg * 32, full3 + 8 * sl);
        }
      }
    }
    __syncwarp(); bar_sync(6, 288);
    asm volatile("griddepcontrol.wait;" ::: "memory");
  } else if (wg == 2) {
    asm volatile("setmaxnreg.dec.sync.aligned.u32 88;");
    {
      const unsigned epoch = *(volatile unsigned*)&g_epoch2;
      const int r = tid & 63, par = (tid >> 6) & 1;
      if ((tid & 127) < 72) { const uint4 g = __ldg((const uint4*)gate_w + (tid & 127)); sts128(sb + A_GW + (tid & 127) * 16, g.x, g.y, g.z, g.w); }
      bar_sync(3, 128);
      float dot[2] = {0.f, 0.f};
#pragma unroll 1
      for (int kb = 0; kb < 9; kb++) {
        if (kb % 3 == 0) mbar_wait(fullx + 8 * (kb / 3), 0);
#pragma unroll
        for (int c = 0; c < 8; c++) {
          uint32_t a[4];
          lds128(sb + par * A_XH + kb * 8192 + r * 128 + ((c ^ (r & 7)) << 4), a);
          uint4 g;
          lds128(sb + A_GW + kb * 128 + c * 16, &g.x);
          dot[0] = fmaf(bf_lo(a[0]), bf_lo(g.x), fmaf(bf_lo(a[1]), bf_lo(g.y), fmaf(bf_lo(a[2]), bf_lo(g.z), fmaf(bf_lo(a[3]), bf_lo(g.w), dot[0]))));
          dot[1] = fmaf(bf_hi(a[0]), bf_hi(g.x), fmaf(bf_hi(a[1]), bf_hi(g.y), fmaf(bf_hi(a[2]), bf_hi(g.z), fmaf(bf_hi(a[3]), bf_hi(g.w), dot[1]))));
        }
      }
      const float gv = 1.f / (1.f + __expf(-(dot[0] + dot[1])));
      sts32(sb + A_GATE + (tid & 127) * 4, __float_as_uint(gv));
      const int tok = 2 * (57 * tile - 7 + r) + par;
      if (hh == 0 && r >= 7 && tok < S_LEN) g_gate[tok] = gv;
      if (tid == 256) sts32(sb + A_BAR + 376, epoch);
      bar_arrive(7, 384);
      bar_sync(3, 128);
      if (tid == 256) {
        count_up(&g_abar[0]);
        wait_count(&g_abar[0], NAUX * (epoch + 1));
        if (cta == 0) *(volatile unsigned*)&g_epoch2 = epoch + 1;
      }
      __syncwarp();
      bar_sync(10, 160);
    }
    if (cta < NH) {
      const int lim = w * 8 + (lane >> 2) - 2 * (lane & 3);
      const uint32_t oa = sb + A_OST + (w * 8 + (lane & 7)) * 128;
      const uint32_t d0 = ((sb + A_IN) & 0x3FFFF) >> 4;
      uint32_t p[5][4];
#pragma unroll
      for (int n = 0; n < 10; n++) p[n >> 1][1 + (n & 1)] = __shfl_sync(0xffffffffu, lane ^ n, n);
#pragma unroll 1
      for (int seg = 0; seg < NSEG; seg++) {
        const float gt = __ldcg(&g_gate[seg * 32 + w * 8 + (lane >> 2)]);
        float d[32];
        mbar_wait(fullq, seg & 1);
        if (tid == 256) SSTAMP(2, seg);
        WG_FENCE();
#pragma unroll
        for (int k = 0; k < 8; k++) {
          const int o = ((k >> 2) * SEGB + (k & 3) * 256) >> 4;
          wgmma_n40_ss_tt(d, desc_at(d0 + o, 128, 512, 0), desc_at(d0 + o + 256, 128, 1024, 0), k > 0);
        }
        WG_COMMIT();
        WG_WAIT(0);
        if (lane == 0) mbar_arrive(emptyq);
        float a[10];
#pragma unroll
        for (int i = 0; i < 10; i++) {
          a[i] = d[(i >> 1) * 4 + (i & 1)] * (SM_SCALE * LOG2E);
          if (i < 8 && (i >> 1) * 8 + (i & 1) > lim) a[i] = -1.0e9f * LOG2E;
        }
        float m = max10(a);
        m = fmaxf(m, __shfl_xor_sync(0xffffffffu, m, 1)); m = fmaxf(m, __shfl_xor_sync(0xffffffffu, m, 2));
#pragma unroll
        for (int i = 0; i < 10; i++) a[i] = ex2(a[i] - m);
#pragma unroll
        for (int n = 0; n < 5; n++) {
          p[n][0] = pack_bf16(a[2 * n], a[2 * n + 1]); p[n][3] = p[n][0] | p[n][1];
          asm volatile("" : "+r"(p[n][0]), "+r"(p[n][3]) :: "memory");
        }
        float sum = ((a[0] + a[1]) + (a[2] + a[3])) + ((a[4] + a[5]) + (a[6] + a[7])) + (a[8] + a[9]);
        sum += __shfl_xor_sync(0xffffffffu, sum, 1);
        if (tid == 256) SSTAMP(3, seg);
        mbar_wait(fullv, seg & 1);
        WG_FENCE();
#pragma unroll
        for (int n = 0; n < 5; n++) wgmma_n64_rs(d, p[n], n < 4 ? desc_at(d0 + SEGB / 8 + 8 * n, 4096, 512, 0) : desc_at(d0 + SEGB / 8 + 512, 1024, 128, 0), n);
        WG_COMMIT();
        sum += __shfl_xor_sync(0xffffffffu, sum, 2);
        const float f = (1.f - gt) * rcp(sum);
        bar_sync(5, 160);
        WG_WAIT(0);
        if (lane == 0) mbar_arrive(emptyv);
        if (tid == 256) SSTAMP(4, seg);
#pragma unroll
        for (int q = 0; q < 4; q++) {
          const float* const o = d + (q & 1) * 16 + (q & 2);
          stsm4(oa + (q >> 1) * 4096 + ((((q & 1) * 4 + (lane >> 3)) ^ (lane & 7)) << 4), pack_bf16(o[0] * f, o[1] * f), pack_bf16(o[4] * f, o[5] * f),
                pack_bf16(o[8] * f, o[9] * f), pack_bf16(o[12] * f, o[13] * f));
        }
        fence_async();
        bar_sync(4, 160);
      }
    }
  } else {
    asm volatile("setmaxnreg.inc.sync.aligned.u32 200;");
    {
      const int g = lane >> 2, t = lane & 3;
      const uint32_t eb = sb + A_EPI + wg * A_EPW, d0 = (sb & 0x3FFFF) >> 4;
      const uint32_t own = (2 * t <= g ? 0xffffu : 0u) | (2 * t < g ? 0xffff0000u : 0u);
      const int kmin = 7 - 57 * tile - 16 * w;
#pragma unroll 1
      for (int c = 0; c < 4; c++) {
        float acc[96], tl[12];
#pragma unroll 1
        for (int r = 0; r < 4; r++) {
#pragma unroll
          for (int st = 0; st < A_NS; st++) {
            const int ks = r * 9 + st;
            if (c == 0 && st % 3 == 0 && ks % 12 == 0) mbar_wait(fullx + 8 * (ks / 12), 0);
            mbar_wait(full1 + 8 * st, r & 1);
            const uint64_t da = desc_at(d0 + wg * (A_XH >> 4) + (ks >> 2) * 512 + (ks & 3) * 2, 16, 1024, 1);
            WG_FENCE();
            wgmma_n192_ss_nt(acc, da, desc_at(d0 + ((A_RING + st * A_WM) >> 4), 2048, 1024, 1), ks);
            if (!(AX & 2)) wgmma_n24_ss_nt(tl, da, desc_at(d0 + ((A_TAIL + st * A_WT) >> 4), 128, 256, 0), ks);
            WG_COMMIT();
            if (st == 0 && r == 2) bar_sync(11 + wg, 160);
            WG_WAIT(1);
            if (ks > 0 && lane == 0) mbar_arrive(empty1 + 8 * ((st + A_NS - 1) % A_NS));
          }
        }
        WG_WAIT(0);
        if (lane == 0) mbar_arrive(empty1 + 8 * (A_NS - 1));
        ASTAMP(16 + c);
        uint32_t ql[9], qh[9], kl[9], kh[9], kx[10], vl[9], vh[9], vx[10];
#pragma unroll
        for (int j = 0; j < 9; j++) {
          const float* const q = j < 8 ? acc + 4 * j : tl, * const k = j < 8 ? acc + 32 + 4 * j : tl + 4, * const v = j < 8 ? acc + 64 + 4 * j : tl + 8;
          kh[j] = pack_bf16(k[2], k[3]); vh[j] = pack_bf16(v[2], v[3]);
          ql[j] = pack_bf16(q[0], q[1]); qh[j] = pack_bf16(q[2], q[3]); kl[j] = pack_bf16(k[0], k[1]); vl[j] = pack_bf16(v[0], v[1]);
        }
        if (w < 3) {
          const uint32_t ha = eb + 1024 + w * 2304 + lane * 16;
          stsm4(ha, kh[0], kh[1], kh[2], kh[3]); stsm4(ha + 512, kh[4], kh[5], kh[6], kh[7]);
          stsm4(ha + 1024, vh[0], vh[1], vh[2], vh[3]); stsm4(ha + 1536, vh[4], vh[5], vh[6], vh[7]);
          asm volatile("stmatrix.sync.aligned.m8n8.x2.shared.b16 [%0], {%1,%2};" :: "r"(ha + 2048), "r"(kh[8]), "r"(vh[8]) : "memory");
        }
        if (c == 0) bar_sync(7, 384); else bar_sync(1 + wg, 128);
        {
          const uint32_t ha = eb + 1024 + max(w - 1, 0) * 2304 + lane * 16;
          ldsm4(kx, ha); ldsm4(kx + 4, ha + 512); ldsm4t(vx, ha + 1024); ldsm4t(vx + 4, ha + 1536);
          asm volatile("ldmatrix.sync.aligned.m8n8.x1.shared.b16 {%0}, [%1];" : "=r"(kx[8]) : "r"(ha + 2048) : "memory");
          asm volatile("ldmatrix.sync.aligned.m8n8.x1.trans.shared.b16 {%0}, [%1];" : "=r"(vx[8]) : "r"(ha + 2176) : "memory");
        }
        const float gl = __uint_as_float(lds32(sb + A_GATE + (wg * 64 + w * 16 + g) * 4)), gh = __uint_as_float(lds32(sb + A_GATE + (wg * 64 + w * 16 + g + 8) * 4));
#pragma unroll
        for (int j = 0; j < 9; j++) { vl[j] = movm(vl[j]); vh[j] = movm(vh[j]); }
        bar_sync(1 + wg, 128);
        uint32_t ol[9], oh[9];
#pragma unroll
        for (int i = 0; i < 4; i++) {
          const int b = 2 * i;
          const uint32_t a[4] = {t >= i ? ql[b] : 0u, t >= i ? qh[b] : 0u, ql[b + 1], qh[b + 1]}, a4 = t <= i ? ql[b + 2] : 0u, a5 = t <= i ? qh[b + 2] : 0u;
          float sx[4], sl[4], sh[4];
          mma16816z(sx, a, kx[b], kx[b + 1]); mma16816z(sl, a, kl[b], kl[b + 1]); mma16816z(sh, a, kh[b], kh[b + 1]);
          mma1688(sx, a4, a5, kx[b + 2]); mma1688(sl, a4, a5, kl[b + 2]); mma1688(sh, a4, a5, kh[b + 2]);
          float e[4];
#pragma unroll
          for (int u = 0; u < 4; u++) {
            const int cc = 2 * t + (u & 1);
            e[u] = (cc <= g ? (u < 2 ? sl[u] : sh[u]) : (u < 2 ? sx[u] : sl[u])) * (0.23570226039551584f * LOG2E);
            if ((cc <= g ? cc : cc - 8) + (u & 2) * 4 < kmin) e[u] = -1.0e9f * LOG2E;
          }
          float m0 = fmaxf(e[0], e[1]), m1 = fmaxf(e[2], e[3]);
#pragma unroll
          for (int o = 1; o < 4; o <<= 1) { m0 = fmaxf(m0, __shfl_xor_sync(0xffffffffu, m0, o)); m1 = fmaxf(m1, __shfl_xor_sync(0xffffffffu, m1, o)); }
          e[0] = ex2(e[0] - m0); e[1] = ex2(e[1] - m0); e[2] = ex2(e[2] - m1); e[3] = ex2(e[3] - m1);
          const uint32_t p0 = pack_bf16(e[0], e[1]), p1 = pack_bf16(e[2], e[3]);
          const uint32_t p[4] = {p0 & ~own, 0u, p0 & own, p1 & ~own};
          float s0 = e[0] + e[1], s1 = e[2] + e[3];
#pragma unroll
          for (int o = 1; o < 4; o <<= 1) { s0 += __shfl_xor_sync(0xffffffffu, s0, o); s1 += __shfl_xor_sync(0xffffffffu, s1, o); }
          const float f0 = gl * rcp(s0), f1 = gh * rcp(s1);
#pragma unroll
          for (int j = b; j < b + 3; j++) {
            float o[4];
            mma16816z(o, p, vx[j], vl[j]);
            mma1688(o, 0u, p1 & own, vh[j]);
            const uint32_t lo = pack_bf16(o[0] * f0, o[1] * f0), hi = pack_bf16(o[2] * f1, o[3] * f1);
            if (j > b || i == 0) { ol[j] = lo; oh[j] = hi; }
            else { ol[j] = t >= i ? lo : ol[j]; oh[j] = t >= i ? hi : oh[j]; }
          }
        }
        const uint32_t sa = eb + 16 + (w * 16 + (lane & 15)) * 144 + (lane >> 4) * 16;
#pragma unroll
        for (int j = 0; j < 8; j += 2) stsm4(sa + j * 16, ol[j], oh[j], ol[j + 1], oh[j + 1]);
        asm volatile("stmatrix.sync.aligned.m8n8.x2.shared.b16 [%0], {%1,%2};" :: "r"(sa + 128), "r"(ol[8]), "r"(oh[8]) : "memory");
        fence_async();
        bar_arrive(13 + wg, 160);
        ASTAMP(20 + c);
      }
    }
    ASTAMP(3);
    uint32_t wa[36][4];
    mbar_wait(fullw, 0);
    const uint32_t la = sb + wg * 73728 + ((lane & 7) + ((lane >> 4) << 3)) * 128 + (((2 * w + ((lane >> 3) & 1)) ^ (lane & 7)) << 4);
#pragma unroll
    for (int k = 0; k < 36; k++) ldsm4t(wa[k], la + k * 2048);
    fence_async();
    bar_sync(6, 288);
    ASTAMP(4);
    float own[4] = {0.f, 0.f, 0.f, 0.f};
    uint4 v[3];
    auto fetch = [&](int seg) {
      const uint4* src = g_part + (((seg & 3) * 36 + cta) * 4) * 128 + (tid & 127);
#pragma unroll
      for (int j = 0; j < 3; j++) v[j] = ldg_relaxed(src + ((kq + 1 + j) & 3) * 128);
    };
    auto finish = [&](int seg) {
      const uint32_t tagv = ((seg >> 2) + 1) & 3;
      int n = 0;
#pragma unroll 1
      while (__any_sync(0xffffffffu, (v[0].x & 3) != tagv || (v[1].x & 3) != tagv || (v[2].x & 3) != tagv) && ++n < SPIN_LIMIT) {
        if (seg < NSEG - 1) __nanosleep(200);
        fetch(seg);
      }
#pragma unroll
      for (int j = 0; j < 3; j++) {
        own[0] += __uint_as_float(v[j].x & ~3u); own[1] += __uint_as_float(v[j].y); own[2] += __uint_as_float(v[j].z); own[3] += __uint_as_float(v[j].w);
      }
      uint32_t p0 = pack_bf16(own[0], own[1]), p1 = pack_bf16(own[2], own[3]);
      asm volatile("movmatrix.sync.aligned.m8n8.trans.b16 %0, %0;" : "+r"(p0));
      asm volatile("movmatrix.sync.aligned.m8n8.trans.b16 %0, %0;" : "+r"(p1));
      uint32_t* o = (uint32_t*)(out + (size_t)(seg * 32 + kq * 8 + (lane >> 2)) * DM + nsl * 64 + w * 16) + (lane & 3);
      o[0] = p0; o[4] = p1;
    };
    float acc[16];
    auto stream = [&](int sl, int keep) {
      const uint64_t db = make_desc(sb + sl * XT, 16, 1024, 1);
      WG_FENCE();
#pragma unroll
      for (int k = 0; k < 36; k++) wgmma_n32_rs(acc, wa[k][0], wa[k][1], wa[k][2], wa[k][3], db + (k >> 2) * 256 + (k & 3) * 2, k ? 1 : keep);
      WG_COMMIT();
    };
    const uint32_t ex = sb + A_EX + (tid & 127) * 16;
    if (wg == 0) {
#pragma unroll
      for (int i = 0; i < 16; i++) acc[i] = 0.f;
#pragma unroll 1
      for (int seg = 0; seg < NSEG; seg++) {
        const int sl = (seg & 1) * 2;
        mbar_wait(full3 + 8 * sl, (seg >> 1) & 1);
        if (kq == 3) {
          const uint64_t da = make_desc(sb + A_XW, 8192, 1024, 1), de = make_desc(sb + A_XT + (seg & 1) * 4096, 16, 1024, 1);
          WG_FENCE();
#pragma unroll
          for (int j = 0; j < 4; j++) wgmma_n32_ss_tn(acc, da + j * 128, de + j * 2, j);
          WG_COMMIT();
          WG_WAIT(0);
        }
        stream(sl, kq == 3);
        bar_arrive(9, 256);
        WG_WAIT(0);
        if (lane == 0) mbar_arrive(empty3 + 8 * sl);
#pragma unroll
        for (int i = 0; i < 4; i++)
          sts128(ex + (seg & 1) * 8192 + i * 2048, __float_as_uint(acc[4 * i]), __float_as_uint(acc[4 * i + 1]), __float_as_uint(acc[4 * i + 2]), __float_as_uint(acc[4 * i + 3]));
        bar_sync(1, 256);
      }
    } else {
#pragma unroll 1
      for (int seg = 0; seg < NSEG; seg++) {
        const int sl = (seg & 1) * 2 + 1;
        mbar_wait(full3 + 8 * sl, (seg >> 1) & 1);
        if (tid == 128) SSTAMP(6, seg);
        bar_sync(9, 256);
        stream(sl, 0);
        bar_sync(1, 256);
        fetch(max(seg - 1, 0));
        WG_WAIT(0);
        if (lane == 0) mbar_arrive(empty3 + 8 * sl);
        float nxt[4] = {0.f, 0.f, 0.f, 0.f};
        uint4* dst = g_part + (((seg & 3) * 36 + nsl * 4) * 4 + kq) * 128 + (tid & 127);
#pragma unroll
        for (int j = 0; j < 4; j++) {
          float o[4];
          lds128f(ex + (seg & 1) * 8192 + j * 2048, o);
#pragma unroll
          for (int i = 0; i < 4; i++) { o[i] += acc[4 * j + i]; if (j == kq) nxt[i] = o[i]; }
          if (j != kq) stg_relaxed(dst + j * 512, (__float_as_uint(o[0]) & ~3u) | (((seg >> 2) + 1) & 3), __float_as_uint(o[1]), __float_as_uint(o[2]), __float_as_uint(o[3]));
        }
        if (tid == 128) SSTAMP(7, seg);
        if (seg > 0) finish(seg - 1);
        if (tid == 128) SSTAMP(8, seg);
#pragma unroll
        for (int i = 0; i < 4; i++) own[i] = nxt[i];
        if ((seg & 7) == 6) ASTAMP(5 + (seg >> 3));
      }
      fetch(NSEG - 1);
      finish(NSEG - 1);
    }
    ASTAMP(13);
    bar_sync(6, 288);
  }
}

typedef CUresult (*EncodeFn)(CUtensorMap*, CUtensorMapDataType, cuuint32_t, void*, const cuuint64_t*, const cuuint64_t*,
                             const cuuint32_t*, const cuuint32_t*, CUtensorMapInterleave, CUtensorMapSwizzle,
                             CUtensorMapL2promotion, CUtensorMapFloatOOBfill);
static void make_map(EncodeFn enc, CUtensorMap* m, const void* p, int rows, int cols, int box_rows) {
  cuuint64_t dims[2] = {(cuuint64_t)cols, (cuuint64_t)rows};
  cuuint64_t strides[1] = {(cuuint64_t)cols * 2};
  cuuint32_t box[2] = {64, (cuuint32_t)box_rows};
  cuuint32_t es[2] = {1, 1};
  enc(m, CU_TENSOR_MAP_DATA_TYPE_BFLOAT16, 2, (void*)p, dims, strides, box, es, CU_TENSOR_MAP_INTERLEAVE_NONE,
      CU_TENSOR_MAP_SWIZZLE_128B, CU_TENSOR_MAP_L2_PROMOTION_L2_128B, CU_TENSOR_MAP_FLOAT_OOB_FILL_NONE);
}

constexpr int g_poll = POLL_NS;
extern "C" void kernel_launch(void* const* d_in, const int* in_sizes, int n_in, void* d_out, int out_size) {
  const bf16* x = (const bf16*)d_in[0];
  const bf16* wqkvA = (const bf16*)d_in[1];
  const bf16* woA = (const bf16*)d_in[2];
  const bf16* mem0 = (const bf16*)d_in[4];
  const bf16* Wq = (const bf16*)d_in[5];
  const bf16* Wk = (const bf16*)d_in[6];
  const bf16* Wv = (const bf16*)d_in[7];
  const bf16* Wo = (const bf16*)d_in[8];
  const bf16* gate_w = (const bf16*)d_in[10];
  static EncodeFn enc = nullptr;
  static void *pO = nullptr, *pR = nullptr;
  if (!enc) {
    cudaDriverEntryPointQueryResult qr;
    cudaGetDriverEntryPoint("cuTensorMapEncodeTiled", (void**)&enc, cudaEnableDefault, &qr);
    cudaGetSymbolAddress(&pO, g_Ocat);
    cudaGetSymbolAddress(&pR, g_red_raw);
    cudaFuncSetAttribute(rec_kernel, cudaFuncAttributeMaxDynamicSharedMemorySize, SM_TOTAL);
    cudaFuncSetAttribute(aux_kernel, cudaFuncAttributeMaxDynamicSharedMemorySize, A_TOTAL);
  }
  RMaps rm;
  rm.poll = g_poll;
  rm.red = (unsigned char*)(((uintptr_t)pR + 262143) & ~(uintptr_t)262143);
  {
    cuuint64_t dims[3] = {64, S_LEN, 9}, strides[2] = {DM * 2, 128};
    cuuint32_t box[3] = {64, 32, 9}, es[3] = {1, 1, 1};
    enc(&rm.x, CU_TENSOR_MAP_DATA_TYPE_BFLOAT16, 3, (void*)x, dims, strides, box, es, CU_TENSOR_MAP_INTERLEAVE_NONE,
        CU_TENSOR_MAP_SWIZZLE_128B, CU_TENSOR_MAP_L2_PROMOTION_L2_128B, CU_TENSOR_MAP_FLOAT_OOB_FILL_NONE);
  }
  make_map(enc, &rm.wq, Wq, DM, 4096, 192);
  make_map(enc, &rm.wk, Wk, DM, 4096, 192);
  make_map(enc, &rm.wv, Wv, DM, 4096, 192);
  make_map(enc, &rm.wo, Wo, 4096, DM, 128);
  AMaps am;
  {
    cuuint32_t es[4] = {1, 1, 1, 1};
    cuuint64_t dx[4] = {64, 2, S_LEN / 2, 9}, sx[3] = {DM * 2, DM * 4, 128};
    cuuint32_t bx[4] = {64, 1, 64, 3};
    enc(&am.x, CU_TENSOR_MAP_DATA_TYPE_BFLOAT16, 4, (void*)x, dx, sx, bx, es, CU_TENSOR_MAP_INTERLEAVE_NONE,
        CU_TENSOR_MAP_SWIZZLE_128B, CU_TENSOR_MAP_L2_PROMOTION_L2_128B, CU_TENSOR_MAP_FLOAT_OOB_FILL_NONE);
    cuuint64_t dw[3] = {DM, DM, 3}, sw[2] = {DM * 6, DM * 2};
    cuuint32_t bw[3] = {64, 16, 3}, bt[3] = {8, 16, 3};
    enc(&am.wa, CU_TENSOR_MAP_DATA_TYPE_BFLOAT16, 3, (void*)wqkvA, dw, sw, bw, es, CU_TENSOR_MAP_INTERLEAVE_NONE,
        CU_TENSOR_MAP_SWIZZLE_128B, CU_TENSOR_MAP_L2_PROMOTION_L2_128B, CU_TENSOR_MAP_FLOAT_OOB_FILL_NONE);
    enc(&am.wt, CU_TENSOR_MAP_DATA_TYPE_BFLOAT16, 3, (void*)wqkvA, dw, sw, bt, es, CU_TENSOR_MAP_INTERLEAVE_NONE,
        CU_TENSOR_MAP_SWIZZLE_NONE, CU_TENSOR_MAP_L2_PROMOTION_NONE, CU_TENSOR_MAP_FLOAT_OOB_FILL_NONE);
    cuuint64_t dz[3] = {KCAT, 2, S_LEN / 2}, sz[2] = {KCAT * 2, KCAT * 4};
    cuuint32_t bz[3] = {72, 1, 57};
    enc(&am.oa, CU_TENSOR_MAP_DATA_TYPE_BFLOAT16, 3, pO, dz, sz, bz, es, CU_TENSOR_MAP_INTERLEAVE_NONE,
        CU_TENSOR_MAP_SWIZZLE_NONE, CU_TENSOR_MAP_L2_PROMOTION_NONE, CU_TENSOR_MAP_FLOAT_OOB_FILL_NONE);
  }
  {
    cuuint64_t dims[3] = {64, S_LEN, KCAT / 64}, strides[2] = {KCAT * 2, 128};
    cuuint32_t box[3] = {64, 32, 9}, es[3] = {1, 1, 1};
    make_map(enc, &am.o, pO, S_LEN, KCAT, 32);
    enc(&am.o3, CU_TENSOR_MAP_DATA_TYPE_BFLOAT16, 3, pO, dims, strides, box, es, CU_TENSOR_MAP_INTERLEAVE_NONE,
        CU_TENSOR_MAP_SWIZZLE_128B, CU_TENSOR_MAP_L2_PROMOTION_L2_128B, CU_TENSOR_MAP_FLOAT_OOB_FILL_NONE);
  }
  make_map(enc, &am.wob, Wo, 4096, DM, 64);
  make_map(enc, &am.woa, woA, DM, DM, 64);

  rec_kernel<<<96, 384, SM_TOTAL, cudaStreamPerThread>>>(rm, x, mem0);
  cudaLaunchConfig_t cfg = {};
  cfg.gridDim = dim3(NAUX); cfg.blockDim = dim3(512); cfg.dynamicSmemBytes = A_TOTAL; cfg.stream = cudaStreamPerThread;
  cudaLaunchAttribute at[1];
  at[0].id = cudaLaunchAttributeProgrammaticStreamSerialization; at[0].val.programmaticStreamSerializationAllowed = 1;
  cfg.attrs = at; cfg.numAttrs = 1;
  if (XP & 16) cfg.numAttrs = 0;
  if (!(XP & 64)) cudaLaunchKernelEx(&cfg, aux_kernel, am, wqkvA, gate_w, (bf16*)d_out);
}
```

```cpp
#include <cuda_runtime.h>
#include <cuda_bf16.h>
#include <cuda_fp16.h>
#include <cuda.h>
#include <stdint.h>

typedef __nv_bfloat16 bf16;

constexpr int S_LEN = 2048, DM = 576, NH = 32, DH = 128, NSEG = 64, KCAT = 4096 + 576;
#define RED_LINE(i) (((i) >> 2) * 4096 + ((i) & 1) * 256 + ((i) & 2) * 512)
#define RED_SLOT(s) (((s) & 1) * 128 + ((s) & 2) * 256)

#define POLL_NS 896
#define NII 18
#define W3PRE 4
#define W3MID 4
#define GF 0
#define B5POS 0
#define NUP 4
#define UPF 1
#define B3Q 9
#define B3F 0
#define GATE 7
#define NTL 2
#define B7R 1
#define EXPOS 0
#define VW2 1
#define CLR 1
#define RFW 0
#define NIC 0
#define LEAD 0
#define FIN16 1
#define VXG 0
#define RING 63
#define EXB 0
#define EXD 0
#define EXB2 8192
#define HDLY 0
#define F10 1
#define NPROBE 2
#define QM 0
#define N5 (EXB ? 256 : 224)
#define KP(i) (((i) >> 1) + 4 * ((i) & 1))
#define SPIN_LIMIT (1 << 14)
#define XP 0

__device__ __align__(1024) bf16 g_Ocat[S_LEN * KCAT];
__device__ __align__(1024) unsigned char g_red_raw[2 * 262144];
constexpr int HINT_OFF = 2048;
__device__ __align__(16) float g_gate[S_LEN];
__device__ __align__(128) uint4 g_stats[96 * 2];
__device__ unsigned g_epoch;
__device__ unsigned g_epoch2;
__device__ unsigned g_ocnt[NSEG * 32];
__device__ unsigned g_abar[3 * 32];
__device__ unsigned g_pace[32];
__device__ unsigned g_scnt[NSEG * 32 * 8];
__device__ __align__(1024) unsigned char g_seg[NSEG * 96 * 10240];
__device__ __align__(1024) uint4 g_part[4 * 36 * 4 * 128];
__device__ int g_err;
#define PROF(idx)
#define PROFP(idx)
#define STAMP(idx)
#define ASTAMP(idx)
#define SSTAMP(k, seg)
#define WSTAMP(idx)

#define DI __device__ __forceinline__
DI uint32_t smem_u32(const void* p) { return (uint32_t)__cvta_generic_to_shared(p); }
DI uint32_t clock32() { uint32_t c; asm volatile("mov.u32 %0, %%clock;" : "=r"(c) :: "memory"); return c; }
DI uint32_t gtime() { uint32_t c; asm volatile("mov.u32 %0, %%globaltimer_lo;" : "=r"(c) :: "memory"); return c; }
DI uint32_t ldg_relaxed32(const void* p) { uint32_t v; asm volatile("ld.relaxed.gpu.global.b32 %0, [%1];" : "=r"(v) : "l"(p) : "memory"); return v; }
DI uint32_t ldg_acquire32(const void* p) { uint32_t v; asm volatile("ld.acquire.gpu.global.b32 %0, [%1];" : "=r"(v) : "l"(p) : "memory"); return v; }
DI void stg_relaxed32(void* p, uint32_t v) { asm volatile("st.relaxed.gpu.global.b32 [%0], %1;" :: "l"(p), "r"(v) : "memory"); }
DI int head_id() { int c; asm volatile("mov.u32 %0, %%clusterid.x;" : "=r"(c)); return c; }
DI uint32_t mapa(uint32_t a, uint32_t r) { uint32_t o; asm("mapa.shared::cluster.u32 %0, %1, %2;" : "=r"(o) : "r"(a), "r"(r)); return o; }
DI void cluster_arrive() { asm volatile("barrier.cluster.arrive.relaxed.aligned;" ::: "memory"); }
DI void cluster_wait() { asm volatile("barrier.cluster.wait.aligned;" ::: "memory"); }
DI void cluster_sync() { asm volatile("barrier.cluster.arrive.release.aligned;\nbarrier.cluster.wait.acquire.aligned;" ::: "memory"); }
DI void mbar_init(uint32_t b, uint32_t c) { asm volatile("mbarrier.init.shared::cta.b64 [%0], %1;" :: "r"(b), "r"(c) : "memory"); }
DI void mbar_expect(uint32_t b, uint32_t tx) { asm volatile("mbarrier.arrive.expect_tx.shared::cta.b64 _, [%0], %1;" :: "r"(b), "r"(tx) : "memory"); }
DI void mbar_arrive(uint32_t b) { asm volatile("mbarrier.arrive.shared::cta.b64 _, [%0];" :: "r"(b) : "memory"); }
DI void mbar_wait(uint32_t b, uint32_t par) {
  asm volatile("{\n.reg .pred p;\n.reg .u32 n, q;\nmov.u32 n, 0;\n"
               "WL: add.u32 n, n, 1;\nshr.u32 q, n, 12;\nxor.b32 q, q, %1;\n"
               "mbarrier.try_wait.parity.shared::cta.b64 p, [%0], q;\n@!p bra.uni WL;\n}"
               :: "r"(b), "r"(par) : "memory");
}
DI void wait_until(uint32_t t) {
  const uint32_t now = gtime();
  t = min(t, now + 8192);
  asm volatile("{\n.reg .pred p;\n.reg .u32 c;\nTL: mov.u32 c, %%globaltimer_lo;\nsetp.lt.u32 p, c, %0;\n@p bra.uni TL;\n}" :: "r"(t) : "memory");
}
#define PIN(v) v = __shfl_xor_sync(0xffffffffu, v, 0)
#define SCHED_FENCE(k) asm volatile("{\n.reg .pred p;\nsetp.eq.u32 p, %0, %1;\n@p exit;\n}" :: "r"(fence_reg), "r"(k) : "memory")
#define MEM_ORDER(k) asm volatile("{\n.reg .pred p;\nsetp.eq.u32 p, %0, %1;\n@p st.shared.u32 [%0], %0;\n}" :: "r"(fence_reg), "r"(k + 64) : "memory")
DI void bar_sync(int id, int n) { asm volatile("bar.sync %0, %1;" :: "r"(id), "r"(n) : "memory"); }
DI void bar_arrive(int id, int n) { asm volatile("bar.arrive %0, %1;" :: "r"(id), "r"(n) : "memory"); }
DI void fence_async() { asm volatile("fence.proxy.async.shared::cta;" ::: "memory"); }
DI void st_async4(uint32_t a, uint32_t x, uint32_t y, uint32_t z, uint32_t w, uint32_t mb) {
  asm volatile("st.async.weak.shared::cluster.mbarrier::complete_tx::bytes.v4.b32 [%0], {%1,%2,%3,%4}, [%5];"
               :: "r"(a), "r"(x), "r"(y), "r"(z), "r"(w), "r"(mb) : "memory");
}
DI void st_async2(uint32_t a, uint32_t x, uint32_t y, uint32_t mb) {
  asm volatile("st.async.weak.shared::cluster.mbarrier::complete_tx::bytes.v2.b32 [%0], {%1,%2}, [%3];"
               :: "r"(a), "r"(x), "r"(y), "r"(mb) : "memory");
}
DI void sts32(uint32_t a, uint32_t x) { asm volatile("st.shared.b32 [%0], %1;" :: "r"(a), "r"(x) : "memory"); }
DI void sts64(uint32_t a, uint32_t x, uint32_t y) { asm volatile("st.shared.v2.b32 [%0], {%1,%2};" :: "r"(a), "r"(x), "r"(y) : "memory"); }
DI void sts128(uint32_t a, uint32_t x, uint32_t y, uint32_t z, uint32_t w) {
  asm volatile("st.shared.v4.b32 [%0], {%1,%2,%3,%4};" :: "r"(a), "r"(x), "r"(y), "r"(z), "r"(w) : "memory");
}
DI uint32_t lds32(uint32_t a) { uint32_t x; asm volatile("ld.shared.b32 %0, [%1];" : "=r"(x) : "r"(a) : "memory"); return x; }
DI void lds64(uint32_t a, uint32_t& x, uint32_t& y) { asm volatile("ld.shared.v2.b32 {%0,%1}, [%2];" : "=r"(x), "=r"(y) : "r"(a) : "memory"); }
DI void lds128(uint32_t a, uint32_t* r) {
  asm volatile("ld.shared.v4.b32 {%0,%1,%2,%3}, [%4];" : "=r"(r[0]), "=r"(r[1]), "=r"(r[2]), "=r"(r[3]) : "r"(a) : "memory");
}
DI void lds128f(uint32_t a, float* r) {
  asm volatile("ld.shared.v4.f32 {%0,%1,%2,%3}, [%4];" : "=f"(r[0]), "=f"(r[1]), "=f"(r[2]), "=f"(r[3]) : "r"(a) : "memory");
}
DI void lds64f(uint32_t a, float* r) { asm volatile("ld.shared.v2.f32 {%0,%1}, [%2];" : "=f"(r[0]), "=f"(r[1]) : "r"(a) : "memory"); }
DI void ldsm4t(uint32_t* r, uint32_t a) {
  asm volatile("ldmatrix.sync.aligned.m8n8.x4.trans.shared.b16 {%0,%1,%2,%3}, [%4];"
               : "=r"(r[0]), "=r"(r[1]), "=r"(r[2]), "=r"(r[3]) : "r"(a) : "memory");
}
DI void ldsm4t_in(uint32_t* r, uint32_t a, uint32_t t) {
  asm volatile("{\n.reg .pred p;\nsetp.ne.u32 p, %5, 0;\n@p ldmatrix.sync.aligned.m8n8.x4.trans.shared.b16 {%0,%1,%2,%3}, [%4];\n}"
               : "+r"(r[0]), "+r"(r[1]), "+r"(r[2]), "+r"(r[3]) : "r"(a), "r"(t) : "memory");
}
DI void lds128_in(uint32_t* r, uint32_t a, uint32_t t) {
  asm volatile("{\n.reg .pred p;\nsetp.ne.u32 p, %5, 0;\n@p ld.shared.v4.b32 {%0,%1,%2,%3}, [%4];\n}"
               : "+r"(r[0]), "+r"(r[1]), "+r"(r[2]), "+r"(r[3]) : "r"(a), "r"(t) : "memory");
}
DI void ldsm2t_in(uint32_t* r, uint32_t a, uint32_t t) {
  asm volatile("{\n.reg .pred p;\nsetp.ne.u32 p, %3, 0;\n@p ldmatrix.sync.aligned.m8n8.x2.trans.shared.b16 {%0,%1}, [%2];\n}" : "+r"(r[0]), "+r"(r[1]) : "r"(a), "r"(t) : "memory");
}
DI void reserve2(uint32_t* r) { asm volatile("{\n.reg .u64 t;\nmov.u64 t, %%clock64;\nmov.b64 {%0, %1}, t;\n}" : "=r"(r[0]), "=r"(r[1])); }
DI void scale_sum(float& x, float& y, float s, uint32_t t) {
  asm volatile("{\n.reg .pred p;\nsetp.ne.u32 p, %2, 0;\n@p mul.f32 %0, %0, %1;\n}" : "+f"(y) : "f"(s), "r"(t));
  asm volatile("{\n.reg .pred p;\nsetp.ne.u32 p, %3, 1;\n@p fma.rn.f32 %0, %0, %1, %2;\n}" : "+f"(x) : "f"(s), "f"(y), "r"(t));
}
DI void ldsm4(uint32_t* r, uint32_t a) {
  asm volatile("ldmatrix.sync.aligned.m8n8.x4.shared.b16 {%0,%1,%2,%3}, [%4];"
               : "=r"(r[0]), "=r"(r[1]), "=r"(r[2]), "=r"(r[3]) : "r"(a) : "memory");
}
DI void st_async1(uint32_t a, uint32_t x, uint32_t mb) {
  asm volatile("st.async.weak.shared::cluster.mbarrier::complete_tx::bytes.b32 [%0], %1, [%2];" :: "r"(a), "r"(x), "r"(mb) : "memory");
}
DI void stsm4(uint32_t a, uint32_t x, uint32_t y, uint32_t z, uint32_t w) {
  asm volatile("stmatrix.sync.aligned.m8n8.x4.shared.b16 [%0], {%1,%2,%3,%4};" :: "r"(a), "r"(x), "r"(y), "r"(z), "r"(w) : "memory");
}
DI void stsm4t(uint32_t a, uint32_t x, uint32_t y, uint32_t z, uint32_t w) {
  asm volatile("stmatrix.sync.aligned.m8n8.x4.trans.shared.b16 [%0], {%1,%2,%3,%4};" :: "r"(a), "r"(x), "r"(y), "r"(z), "r"(w) : "memory");
}
DI uint32_t pack_bf16(float lo, float hi) { uint32_t r; asm("cvt.rn.bf16x2.f32 %0, %1, %2;" : "=r"(r) : "f"(hi), "f"(lo)); return r; }
DI uint32_t pack_f16(float lo, float hi) { uint32_t r; asm("cvt.rn.f16x2.f32 %0, %1, %2;" : "=r"(r) : "f"(hi), "f"(lo)); return r; }
DI float ex2(float x) { float y; asm("ex2.approx.ftz.f32 %0, %1;" : "=f"(y) : "f"(x)); return y; }
DI float rcp(float x) { float y; asm("rcp.approx.ftz.f32 %0, %1;" : "=f"(y) : "f"(x)); return y; }
DI float bf_lo(uint32_t x) { return __uint_as_float(x << 16); }
DI float bf_hi(uint32_t x) { return __uint_as_float(x & 0xffff0000u); }
DI void mma16816(float* d, const uint32_t* a, uint32_t b0, uint32_t b1) {
  asm volatile("mma.sync.aligned.m16n8k16.row.col.f32.bf16.bf16.f32 {%0,%1,%2,%3}, {%4,%5,%6,%7}, {%8,%9}, {%0,%1,%2,%3};"
               : "+f"(d[0]), "+f"(d[1]), "+f"(d[2]), "+f"(d[3]) : "r"(a[0]), "r"(a[1]), "r"(a[2]), "r"(a[3]), "r"(b0), "r"(b1));
}
DI void mma16816z(float* d, const uint32_t* a, uint32_t b0, uint32_t b1) {
  asm volatile("mma.sync.aligned.m16n8k16.row.col.f32.bf16.bf16.f32 {%0,%1,%2,%3}, {%4,%5,%6,%7}, {%8,%9}, {%10,%10,%10,%10};"
               : "=f"(d[0]), "=f"(d[1]), "=f"(d[2]), "=f"(d[3]) : "r"(a[0]), "r"(a[1]), "r"(a[2]), "r"(a[3]), "r"(b0), "r"(b1), "f"(0.f));
}
DI void mma1688z(float* d, uint32_t a0, uint32_t a1, uint32_t b0) {
  asm volatile("mma.sync.aligned.m16n8k8.row.col.f32.bf16.bf16.f32 {%0,%1,%2,%3}, {%4,%5}, {%6}, {%7,%7,%7,%7};"
               : "=f"(d[0]), "=f"(d[1]), "=f"(d[2]), "=f"(d[3]) : "r"(a0), "r"(a1), "r"(b0), "f"(0.f));
}
DI void mma1688(float* d, uint32_t a0, uint32_t a1, uint32_t b0) {
  asm volatile("mma.sync.aligned.m16n8k8.row.col.f32.bf16.bf16.f32 {%0,%1,%2,%3}, {%4,%5}, {%6}, {%0,%1,%2,%3};"
               : "+f"(d[0]), "+f"(d[1]), "+f"(d[2]), "+f"(d[3]) : "r"(a0), "r"(a1), "r"(b0));
}
DI void ldsm2t(uint32_t* r, uint32_t a) {
  asm volatile("ldmatrix.sync.aligned.m8n8.x2.trans.shared.b16 {%0,%1}, [%2];" : "=r"(r[0]), "=r"(r[1]) : "r"(a) : "memory");
}
DI uint32_t add_bf16(uint32_t a, uint32_t b) { uint32_t r; asm("add.rn.bf16x2 %0, %1, %2;" : "=r"(r) : "r"(a), "r"(b)); return r; }
DI uint32_t mul_bf16(uint32_t a, uint32_t b) { uint32_t r; asm("mul.rn.bf16x2 %0, %1, %2;" : "=r"(r) : "r"(a), "r"(b)); return r; }
DI uint64_t make_desc(uint32_t addr, uint32_t lbo, uint32_t sbo, uint32_t swz) {
  return (uint64_t)((addr & 0x3FFFF) >> 4) | ((uint64_t)(lbo >> 4) << 16) | ((uint64_t)(sbo >> 4) << 32) | ((uint64_t)swz << 62);
}
DI uint64_t desc_at(uint32_t a16, uint32_t lbo, uint32_t sbo, uint32_t swz) {
  uint64_t d; asm("mov.b64 %0, {%1, %2};" : "=l"(d) : "r"(a16 + ((lbo >> 4) << 16)), "r"((sbo >> 4) | (swz << 30)));
  return d;
}
#define WG_FENCE() asm volatile("wgmma.fence.sync.aligned;" ::: "memory")
#define WG_COMMIT() asm volatile("wgmma.commit_group.sync.aligned;" ::: "memory")
#define WG_WAIT(n) asm volatile("wgmma.wait_group.sync.aligned %0;" :: "n"(n) : "memory")
#define ACC8(d, o) "+f"(d[o]), "+f"(d[o + 1]), "+f"(d[o + 2]), "+f"(d[o + 3]), "+f"(d[o + 4]), "+f"(d[o + 5]), "+f"(d[o + 6]), "+f"(d[o + 7])
DI void wgmma_n32_rs(float* d, uint32_t a0, uint32_t a1, uint32_t a2, uint32_t a3, uint64_t db, int acc) {
  asm volatile("{\n.reg .pred p;\nsetp.ne.b32 p, %21, 0;\n"
               "wgmma.mma_async.sync.aligned.m64n32k16.f32.bf16.bf16 {%0,%1,%2,%3,%4,%5,%6,%7,%8,%9,%10,%11,%12,%13,%14,%15}, "
               "{%16,%17,%18,%19}, %20, p, 1, 1, 0;\n}\n"
               : ACC8(d, 0), ACC8(d, 8) : "r"(a0), "r"(a1), "r"(a2), "r"(a3), "l"(db), "r"(acc));
}
template <int TA>
DI void wgmma_n32_ss(float* d, uint64_t da, uint64_t db, int acc) {
  asm volatile("{\n.reg .pred p;\nsetp.ne.b32 p, %18, 0;\n"
               "wgmma.mma_async.sync.aligned.m64n32k16.f32.bf16.bf16 {%0,%1,%2,%3,%4,%5,%6,%7,%8,%9,%10,%11,%12,%13,%14,%15}, "
               "%16, %17, p, 1, 1, %19, 1;\n}\n"
               : ACC8(d, 0), ACC8(d, 8) : "l"(da), "l"(db), "r"(acc), "n"(TA));
}
DI void tma_load(uint32_t dst, const CUtensorMap* m, int c0, int c1, uint32_t mb) {
  asm volatile("cp.async.bulk.tensor.2d.shared::cluster.global.mbarrier::complete_tx::bytes [%0], [%1, {%3, %4}], [%2];"
               :: "r"(dst), "l"(m), "r"(mb), "r"(c0), "r"(c1) : "memory");
}
DI void tma_load3(uint32_t dst, const CUtensorMap* m, int row, uint32_t mb) {
  asm volatile("cp.async.bulk.tensor.3d.shared::cluster.global.mbarrier::complete_tx::bytes [%0], [%1, {%3, %4, %3}], [%2];"
               :: "r"(dst), "l"(m), "r"(mb), "r"(0), "r"(row) : "memory");
}
DI bool elect_one() {
  uint32_t p;
  asm volatile("{\n.reg .pred p;\nelect.sync _|p, 0xffffffff;\nselp.u32 %0, 1, 0, p;\n}" : "=r"(p));
  return p;
}
DI void bulk_s2s(uint32_t dst, uint32_t src, uint32_t bytes, uint32_t mb) {
  asm volatile("cp.async.bulk.shared::cluster.shared::cta.mbarrier::complete_tx::bytes [%0], [%1], %2, [%3];"
               :: "r"(dst), "r"(src), "r"(bytes), "r"(mb) : "memory");
}
DI void tma_prefetch(const CUtensorMap* m, int c0, int c1) {
  asm volatile("cp.async.bulk.prefetch.tensor.2d.L2.global.tile [%0, {%1, %2}];" :: "l"(m), "r"(c0), "r"(c1) : "memory");
}
DI void tma_store(const CUtensorMap* m, uint32_t src, int c0, int c1) {
  asm volatile("cp.async.bulk.tensor.2d.global.shared::cta.bulk_group [%0, {%2, %3}], [%1];" :: "l"(m), "r"(src), "r"(c0), "r"(c1) : "memory");
}
DI uint4 ldg_relaxed(const void* p) {
  uint4 v;
  asm volatile("ld.relaxed.gpu.global.v4.b32 {%0,%1,%2,%3}, [%4];" : "=r"(v.x), "=r"(v.y), "=r"(v.z), "=r"(v.w) : "l"(p) : "memory");
  return v;
}
DI void stg_relaxed(void* p, uint32_t x, uint32_t y, uint32_t z, uint32_t w) {
  asm volatile("st.relaxed.gpu.global.v4.b32 [%0], {%1,%2,%3,%4};" :: "l"(p), "r"(x), "r"(y), "r"(z), "r"(w) : "memory");
}
DI void red_f16x8(void* p, uint32_t x, uint32_t y, uint32_t z, uint32_t w) {
  asm volatile("red.relaxed.gpu.global.add.noftz.v4.f16x2 [%0], {%1,%2,%3,%4};" :: "l"(p), "r"(x), "r"(y), "r"(z), "r"(w) : "memory");
}
DI void sq_acc(uint32_t& a, uint32_t x) { asm("fma.rn.bf16x2 %0, %1, %1, %0;" : "+r"(a) : "r"(x)); }
DI __half2 amax4(__half2 h, const uint32_t* v) {
  h = __hmax2_nan(__hmax2_nan(h, __habs2(*(const __half2*)&v[0])), __habs2(*(const __half2*)&v[1]));
  return __hmax2_nan(__hmax2_nan(h, __habs2(*(const __half2*)&v[2])), __habs2(*(const __half2*)&v[3]));
}
DI uint32_t wexp(__half2 h) { const uint32_t u = *(const uint32_t*)&h; return __reduce_max_sync(0xffffffffu, max((u >> 16) & 0x7fffu, u & 0x7fffu)) >> 7; }
DI float max10(const float* a) {
  return fmaxf(fmaxf(fmaxf(fmaxf(a[0], a[1]), fmaxf(a[2], a[3])), fmaxf(fmaxf(a[4], a[5]), fmaxf(a[6], a[7]))), fmaxf(a[8], a[9]));
}
DI float quad_max(float m) {
  return fmaxf(fmaxf(m, __shfl_xor_sync(0xffffffffu, m, 1)), fmaxf(__shfl_xor_sync(0xffffffffu, m, 2), __shfl_xor_sync(0xffffffffu, m, 3)));
}
DI float warp_sum(float v) {
#pragma unroll
  for (int o = 16; o; o >>= 1) v += __shfl_xor_sync(0xffffffffu, v, o);
  return v;
}

constexpr int SM_WO3 = 0;
constexpr int SM_X = 16384;
constexpr int XT = 36864;
constexpr int SM_EXP = 126976;
constexpr int SEGB = 10240;
constexpr int SM_BLK = SM_EXP + 8192;
constexpr int SM_VC = SM_BLK + 4 * SEGB;
constexpr int SM_PART = SM_VC + 16384;
constexpr int SM_QM = SM_PART + 4096;
constexpr int SM_E = SM_QM + 1024;
constexpr int SM_VM = SM_E + 1536;
constexpr int SM_OB = SM_VM + 2048;
constexpr int SM_FB = SM_OB + 2048;
constexpr int SM_STAGE = SM_X + XT;
constexpr int SM_MISC = 210944;
constexpr int SM_WOST = 212992;
constexpr int SM_MEM = SM_WOST;
constexpr int SM_MAX = SM_MEM + 11264;
#define MEM_BLK(q) ((q) / 3 * 4096 + (q) % 3 * 1024)
constexpr int SM_TOTAL = 229376;
constexpr int MB_W = SM_MISC;
constexpr int MB_WO = SM_MISC + 24;
constexpr int MB_WO3 = SM_MISC + 32;
constexpr int MB_X = SM_MISC + 40;
constexpr int MB_S = SM_MISC + 64;
constexpr int MB_F = SM_MISC + 72;
constexpr int MB_VX = SM_MISC + 80;
constexpr int SC_FPAR = SM_MISC + 136;
constexpr int SC_DEAD = SM_MISC + 96;
constexpr int SC_UNSC = SM_MISC + 112;
constexpr int SC_EXPW = SM_MISC + 132;
constexpr int SC_ONES = SM_MISC + 144;
constexpr int SC_SS = SM_MISC + 160;
constexpr int SC_LAT = SM_MISC + 224;
constexpr int SC_XMAX = SM_MISC + 256;
constexpr int SC_PROF = 229376;

constexpr float SM_SCALE = 0.08838834764831845f;
constexpr float LOG2E = 1.4426950408889634f;
constexpr float E_LIM = 20.f;

template <bool B> struct BoolC { static constexpr bool value = B; };
struct RMaps { CUtensorMap x, wq, wk, wv, wo; unsigned char* red; const char* w[4]; uint32_t poll; };

DI uint32_t latest_hint(uint32_t h, uint32_t d, int s) {
  const uint32_t x = (((h | 0xc0c0c0c0u) - ((d >> 5) & 63) * 0x01010101u) & 0x3f3f3f3fu) | ((h ^ (((s >> 2) + 1) & 3) * 0x40404040u) & 0xc0c0c0c0u);
  const uint32_t y = __vmaxu2(x & 0x00ff00ffu, (x >> 8) & 0x00ff00ffu);
  return __reduce_max_sync(0xffffffffu, max(y & 0xffffu, y >> 16));
}
DI uint32_t near_half(uint32_t sb) {
  uint32_t a, b; lds64(sb + SC_LAT, a, b);
  return a > b;
}

template <int RT, int K0, int K1, bool D32 = false>
DI void xproj(float* acc, const uint32_t (&wa)[2][18][4], uint64_t xd) {
  if (XP & 1) return;
  WG_FENCE();
#pragma unroll
  for (int k = K0; k < ((XP & 128) ? K0 + 1 : K1); k++)
  {
    uint64_t d = xd + (uint64_t)(((k >> 1) * 4096 + (k & 1) * 32) >> 4);
    if (D32) asm("mov.b64 %0, {%1, %2};" : "=l"(d) : "r"((uint32_t)xd + (((k >> 1) * 4096 + (k & 1) * 32) >> 4)), "r"((uint32_t)(xd >> 32)));
    wgmma_n32_rs(acc, wa[RT][k][0], wa[RT][k][1], wa[RT][k][2], wa[RT][k][3], d, k != 0);
  }
  WG_COMMIT();
}

DI void seg_store(int seg, uint32_t sb, uint32_t off, uint32_t bytes) {
  asm volatile("cp.async.bulk.global.shared::cta.bulk_group [%0], [%1], %2;"
               :: "l"(g_seg + ((size_t)(seg & RING) * 96 + blockIdx.x) * SEGB + off), "r"(sb + SM_BLK + (seg & 3) * SEGB + off), "r"(bytes) : "memory");
  asm volatile("cp.async.bulk.commit_group;" ::: "memory");
}
DI void seg_publish(int seg) {
  asm volatile("cp.async.bulk.wait_group 0;" ::: "memory");
  asm volatile("red.relaxed.gpu.global.add.u32 [%0], 1;" :: "l"(&g_scnt[(seg * 32 + blockIdx.x / 3) * 8]) : "memory");
  SSTAMP(10, seg);
}

DI void proj_role(const uint32_t sb, const RMaps& tm, const uint32_t rank, const int wg, const int w, const int lane) {
  const bool qk = rank < 2;
  uint32_t wa[2][18][4];
  {
    const int rr = (lane & 7) + ((lane >> 4) << 3);
    const uint32_t col = ((2 * w + ((lane >> 3) & 1)) ^ (lane & 7)) << 4;
    float ss = 0.f;
#pragma unroll
    for (int c = 0; c < 3; c++) {
      mbar_wait(sb + MB_W + 8 * c, 0);
      if (threadIdx.x == 0) SSTAMP(11, c);
#pragma unroll
      for (int rt = 0; rt < 2; rt++)
#pragma unroll
        for (int k = 0; k < 6; k++)
          ldsm4t(wa[rt][c * 6 + k], sb + SM_STAGE + c * 49152 + (rt ^ wg) * 24576 + (64 * (k >> 1) + 32 * wg + 16 * (k & 1) + rr) * 128 + col);
      if (c < 2) {
        fence_async();
        bar_sync(3, 256);
        if (threadIdx.x == 0) {
          if (c == 0) tma_load3(sb + SM_X + XT, &tm.x, 32, sb + MB_X + 8);
          else { tma_load(sb + SM_X + 2 * XT, &tm.wo, rank * 192, (blockIdx.x / 3) * DH, sb + MB_WO); SSTAMP(11, 11); }
        }
        __syncwarp();
      }
      uint32_t q[4] = {0, 0, 0, 0};
#pragma unroll
      for (int rt = 0; rt < 2; rt++)
#pragma unroll
        for (int k = 0; k < 6; k++)
#pragma unroll
          for (int i = 0; i < 4; i++) sq_acc(q[i], wa[rt][c * 6 + k][i]);
#pragma unroll
      for (int i = 0; i < 4; i++) ss += bf_lo(q[i]) + bf_hi(q[i]);
    }
    ss = warp_sum(ss);
    fence_async();
    cluster_arrive();
    if (lane == 0) sts32(sb + SC_SS + 4 * (wg * 4 + w), qk ? 0 : __float_as_uint(ss));
    bar_arrive(11, 384);
  }
  STAMP(1);
  mbar_wait(sb + MB_X, 0);
  STAMP(2);

  uint32_t t16 = sb + (w * 32 + lane) * 16;
  uint32_t mem_a = sb + SM_MEM + wg * 512 + lane * 16;
  uint32_t fin_a = sb + (lane & 7) * 16 + SM_BLK + (qk ? (wg ^ 1) * 4096 + w * 256 + (lane & 8) * 16 + (lane & 16) * 64
                                              : wg * 4096 + w * 1024 + (lane & 8) * 64 + (lane & 16) * 8);
  PIN(t16); PIN(mem_a); PIN(fin_a);
  const uint32_t fence_reg = mem_a;
  const uint32_t fin2 = qk ? 2048 : 256;
  float acc[16];
  const uint64_t xd0 = make_desc(sb + SM_X + wg * 64, 16, 1024, 1);
  auto do_export = [&]() {
    WG_WAIT(0);
#pragma unroll
    for (int i = 0; i < 2; i++)
      sts128(t16 + SM_EXP + wg * 4096 + i * 2048, pack_bf16(acc[8 * i], acc[8 * i + 1]), pack_bf16(acc[8 * i + 2], acc[8 * i + 3]),
             pack_bf16(acc[8 * i + 4], acc[8 * i + 5]), pack_bf16(acc[8 * i + 6], acc[8 * i + 7]));
  };
  uint32_t o[8];
  auto import = [&]() { lds128(t16 + SM_EXP + (wg ^ 1) * 4096, o); lds128(t16 + SM_EXP + (wg ^ 1) * 4096 + 2048, o + 4); };
  auto finish = [&](int seg) {
    const uint32_t a = fin_a + (seg & 3) * SEGB;
    WG_WAIT(0);
#pragma unroll
    for (int i = 0; i < 8; i++) o[i] = FIN16 ? add_bf16(pack_bf16(acc[2 * i], acc[2 * i + 1]), o[i]) : pack_bf16(acc[2 * i] + bf_lo(o[i]), acc[2 * i + 1] + bf_hi(o[i]));
    stsm4(a, o[0], o[1], o[2], o[3]);
    stsm4(a + fin2, o[4], o[5], o[6], o[7]);
  };
  auto send_v = [&](int seg, int dst) {
    fence_async();
    if (seg < NSEG - 1 && !(XP & 2) && elect_one())
      bulk_s2s(mapa(sb + SM_VC + (seg & 1) * 8192, dst), sb + SM_BLK + (seg & 3) * SEGB, 8192, mapa(sb + MB_VX + (seg & 1) * 8, dst));
    __syncwarp();
  };
  auto wait_v = [&](int seg) {
    if (seg < NSEG - 1 && !(XP & 2)) {
      mbar_wait(sb + MB_VX + (seg & 1) * 8, (seg >> 1) & 1);
      if (elect_one()) mbar_expect(sb + MB_VX + (seg & 1) * 8, 8192);
      __syncwarp();
    }
  };
  bar_sync(3, 256);
  xproj<1, 0, 18>(acc, wa, xd0);
  do_export();
  SCHED_FENCE(11);
  xproj<0, 0, 18>(acc, wa, xd0);
  bar_sync(3, 256);
  if (threadIdx.x == 0) SSTAMP(11, 12);
  cluster_wait();
  if (threadIdx.x == 0) SSTAMP(11, 13);
  mbar_wait(sb + MB_X + 8, 0);
  import();
  finish(0);
  SCHED_FENCE(12);
  bar_sync(3, 256);
  uint64_t dA = xd0 + (XT >> 4);
  xproj<1, 0, 18>(acc, wa, dA);
  if (!qk && wg == 0 && w < 2) send_v(0, w);
  do_export();
  if (qk && wg == 0 && w == 0) wait_v(0);
  bar_arrive(13, 384);
  if (!qk) {
    SCHED_FENCE(15);
    xproj<0, 0, 18>(acc, wa, dA);
    if (threadIdx.x == 0 && !(XP & 8)) { mbar_expect(sb + MB_X, XT); tma_load3(sb + SM_X, &tm.x, 96, sb + MB_X); }
    bar_sync(3, 256);
    mbar_wait(sb + MB_X + 16, 0);
    import();
    finish(1);
    SCHED_FENCE(16);
    bar_sync(3, 256);
    dA += XT >> 4;
    xproj<1, 0, 18>(acc, wa, dA);
    if (wg == 0 && w < VW2) send_v(1, w);
    do_export();
  }
  if (threadIdx.x == 0) SSTAMP(11, 14);
  bar_sync(0, 384);
  const int ro = __shfl_sync(0xffffffffu, near_half(sb) ^ wg, 0);
  STAMP(5);
  const uint32_t always = __shfl_sync(0xffffffffu, lds32(sb + SC_DEAD + 12), 0);
  const int ah = qk ? 1 : 2;
  int b2 = qk ? 2 : 0;
  int s = 0;
  uint32_t hint_lo = (uint32_t)(uint64_t)tm.red + HINT_OFF + blockIdx.x + (lane & 1) * 4096 + (lane >> 1) * 16384;
  PIN(hint_lo);
  auto post_hint = [&]() {
    asm volatile("{\n.reg .pred p;\n.reg .b64 a;\n.reg .u32 t;\nsetp.lt.u32 p, %0, %1;\nmov.b64 a, {%2, %3};\nmov.u32 t, %%globaltimer_lo;\n"
                 "bfe.u32 t, t, 5, 6;\nor.b32 t, t, %4;\n@p st.relaxed.gpu.global.u8 [a], t;\n}"
                 :: "r"(t16), "r"(sb + 128), "r"(hint_lo + RED_SLOT(s)), "r"((uint32_t)((uint64_t)tm.red >> 32)), "r"(((s >> 2) + 1) << 6) : "memory");
  };
  auto memproj = [&](auto second, int id, float u0, float u1, float* r) {
    constexpr bool R1 = decltype(second)::value;
    uint32_t b[NUP][4], b0[4];
    SCHED_FENCE(id);
    bar_sync(R1 ? 2 : 1, 256);
    PROF(0);
    ldsm4t(b0, mem_a);
#pragma unroll
    for (int q = 0; q < NUP; q++) {
      if (R1 && q == 2) {
        bar_sync(11, 256);
        SCHED_FENCE(id + 1);
      }
      ldsm4t(b[q], mem_a + MEM_BLK(q + 1));
    }
    mma16816z(&acc[0], wa[0][0], b0[0], b0[1]);
    mma16816z(&acc[4], wa[1][0], b0[0], b0[1]);
    mma16816z(&acc[8], wa[0][1], b0[2], b0[3]);
    mma16816z(&acc[12], wa[1][1], b0[2], b0[3]);
#pragma unroll
    for (int q = 1; q < 9; q++) {
      uint32_t* const c = b[(q - 1) % NUP];
      mma16816(&acc[0], wa[0][2 * q], c[0], c[1]);
      mma16816(&acc[4], wa[1][2 * q], c[0], c[1]);
      mma16816(&acc[8], wa[0][2 * q + 1], c[2], c[3]);
      mma16816(&acc[12], wa[1][2 * q + 1], c[2], c[3]);
      if (R1 && q + NUP == B3Q) bar_sync(3, 256);
      if (q + NUP < 9) ldsm4t_in(c, mem_a + MEM_BLK(q + NUP), always);
      else if (R1 && q + NUP < 11) lds128_in(c, t16 + SM_PART + (10 - q - NUP) * 2048, always);
      else if (!R1 && GATE && q == GATE) { bar_arrive(11, 256); lds128_in(c, sb + SC_DEAD, always); u0 = u1 = __uint_as_float(c[3]); }
    }
#pragma unroll
    for (int i = 0; i < 8; i++) {
      const float u = i < 4 ? u0 : u1;
      r[i] = R1 ? fmaf(acc[8 + i], u, (acc[i] + __uint_as_float(b[(8 + i / 4) % NUP][i & 3])) * u) : (GATE ? fmaf(acc[i], u, acc[8 + i]) : acc[i] + acc[8 + i]);
    }
  };
  if (ro == 0) {
#pragma unroll 1
    while (true) {
      if (s == 8) STAMP(6);
      float r[8];
      memproj(BoolC<false>(), 30, 0.f, 0.f, r);
      sts128(t16 + SM_PART, __float_as_uint(r[0]), __float_as_uint(r[1]), __float_as_uint(r[2]), __float_as_uint(r[3]));
      sts128(t16 + SM_PART + 2048, __float_as_uint(r[4]), __float_as_uint(r[5]), __float_as_uint(r[6]), __float_as_uint(r[7]));
      bar_arrive(3, 256);
      PROF(1);
      bar_sync(9, 256);
      if (s == NSEG - 1) break;
      post_hint();
      if (w == 1) {
        uint32_t m[8];
        lds128(t16 + SM_MAX - 512, m); lds128(t16 + SM_MAX, m + 4);
        const int em = (wexp(amax4(amax4(*(const __half2*)&m[0], m), m + 4)) >> 3) + (int)(lds32(sb + SC_UNSC + (s & 1) * 8) >> 23) - 15;
        const int ex = max(s ? em : 0, (int)lds32(sb + SC_XMAX + 4 * s)) - 127 + (int)lds32(sb + SC_EXPW);
        sts32(sb + SC_UNSC + (~s & 1) * 8, (127 + min(max(ex, -120), 120)) << 23);
        __syncwarp();
        if (elect_one()) mbar_arrive(sb + MB_S);
      }
      SCHED_FENCE(9);
      bar_sync(5, qk ? N5 : 256);
      PROF(2);
      import();
      xproj<0, 0, NII>(acc, wa, dA);
      if (NII < 18) {
        if (qk) bar_sync(7, 384);
        xproj<0, NII, 18>(acc, wa, dA);
        if (!qk) bar_sync(7, 384);
      } else {
        if (F10) WG_WAIT(0);
        bar_sync(10, 256);
        if (F10) SCHED_FENCE(17);
      }
      dA += (int64_t)(b2 ? XT >> 4 : -(XT >> 3));
      finish(s + ah);
      if (qk || w >= VW2) bar_arrive(13, 384);
      PROF(6);
      SCHED_FENCE(14);
      bar_sync(12, 256);
      PROF(7);
      xproj<1, 0, 18, true>(acc, wa, dA);
      bar_arrive(14, 256);
      b2 = b2 == 2 ? 0 : b2 + 1;
      s++;
      if (!qk && w < VW2) { bar_sync(13, 384); send_v(s + 1, w); }
      PROFP(8);
      do_export();
      PROFP(3);
    }
    if (!qk) bar_arrive(5, 256);
  } else {
#pragma unroll 1
    while (true) {
      if (s == 8) STAMP(6);
      const uint32_t tl = ((t16 >> 8) ^ wg) & 1, am = (t16 & ~256u) - w * 256;
      const float un = __uint_as_float(lds32(sb + SC_UNSC + (s & 1) * 8));
      float r[8];
      if (qk) {
        uint32_t a0 = am + (tl ? SM_QM : SM_BLK + 8192 + (s & 3) * SEGB);
        float u0 = wg ? un * (SM_SCALE * LOG2E) : un, u1 = wg ? un : un * (SM_SCALE * LOG2E);
        PIN(a0); PIN(u0); PIN(u1);
        memproj(BoolC<true>(), 32, u0, u1, r);
        stsm4(a0, pack_bf16(r[0], r[1]), pack_bf16(r[2], r[3]), pack_bf16(r[4], r[5]), pack_bf16(r[6], r[7]));
        bar_arrive(4, 256);
      } else {
        const uint32_t d0 = s < NSEG - 1 ? 0 : 2, d1 = s < NSEG - 1 ? 1 : 2;
        uint32_t r0 = mapa(t16 + SM_VM, d0), r1 = mapa(t16 + SM_VM, d1);
        PIN(r0); PIN(r1);
        memproj(BoolC<true>(), 34, un, un, r);
        const uint32_t p0 = pack_bf16(r[0], r[1]), p1 = pack_bf16(r[2], r[3]), p2 = pack_bf16(r[4], r[5]), p3 = pack_bf16(r[6], r[7]);
        const uint32_t v0 = wg ? p2 : p0, v1 = wg ? p3 : p1, v2 = wg ? p0 : p2, v3 = wg ? p1 : p3;
        st_async4(r0, v0, v1, v2, v3, mapa(sb + MB_S, d0));
        st_async4(r1, v0, v1, v2, v3, mapa(sb + MB_S, d1));
        bar_arrive(5, 256);
        if (EXB && s < NSEG - 1) bar_arrive(15, 160);
        sts128(t16 + SM_VM, v0, v1, v2, v3);
        stsm4(am + SM_BLK + 8192 + (s & 3) * SEGB + tl * 1024, p0, p1, p2, p3);
        __syncwarp();
        if (elect_one()) mbar_arrive(sb + MB_S);
      }
      if (s == NSEG - 1) break;
      PROF(1);
      auto rearm = [&]() { mbar_wait(sb + MB_S, s & 1); if (elect_one()) mbar_expect(sb + MB_S, qk ? 640 + 2048 : 1280); __syncwarp(); };
      if (w == 1) {
        if ((t16 & 384) == 0) stg_relaxed(tm.red + (RED_SLOT(s + 2) + RED_LINE(blockIdx.x)) + (t16 & 112), 0, 0, 0, 0);
      } else if (w == 0) {
        const int tn = s + ah + 1;
        if (RFW) mbar_wait(sb + MB_S, s & 1);
        if (tn + 1 < NSEG && !(XP & 8) && elect_one()) {
          const int b0 = b2 == 2 ? 0 : b2 + 1;
          mbar_expect(sb + MB_X + 8 * b0, XT);
          tma_load3(sb + SM_X + b0 * XT, &tm.x, (tn + 1) * 32, sb + MB_X + 8 * b0);
        }
        if (tn < NSEG && (!(XP & 8) || tn < 3)) mbar_wait(sb + MB_X + 8 * b2, (tn / 3) & 1);
      } else if (w == 2) {
        if (!qk) { if (VW2 < 1) send_v(s + 1, 0); if (VW2 < 2) send_v(s + 1, 1); }
      } else if (qk || !NIC) {
        rearm();
      }
      __syncwarp();
      import();
      PROF(4);
      SCHED_FENCE(10);
      if (NIC) {
        if (qk) bar_sync(7, NII < 18 ? 384 : 256);
        xproj<0, 0, NIC>(acc, wa, dA);
        if (!qk) { if (w == 3) rearm(); bar_sync(7, NII < 18 ? 384 : 256); }
      } else {
        bar_sync(7, NII < 18 ? 384 : 256);
      }
      xproj<0, NIC, 18>(acc, wa, dA);
      bar_arrive(12, 256);
      dA += (int64_t)(b2 ? XT >> 4 : -(XT >> 3));
      finish(s + ah);
      if (qk && w == 0) wait_v(s + 1);
      bar_arrive(13, 384);
      PROF(6);
      SCHED_FENCE(13);
      bar_sync(14, 256);
      PROF(7);
      xproj<1, 0, 18>(acc, wa, dA);
      b2 = b2 == 2 ? 0 : b2 + 1;
      s++;
      PROFP(8);
      do_export();
      PROFP(3);
    }
  }
  bar_arrive(0, 384);
  STAMP(3);
  cluster_sync();
  STAMP(4);
}

DI void attn_role(const uint32_t sb, unsigned char* smem_raw, const RMaps& tm, const uint32_t RANK, const bf16* __restrict__ x, const bf16* __restrict__ mem0,
                  const int w, const int lane) {
  const int t2 = w * 32 + lane;
  uint32_t wo[8][4], w1[8][4];
  const uint32_t wo_lane = sb + ((lane & 7) + ((lane >> 4) << 3)) * 128 + (((w + 4 * ((lane >> 3) & 1)) ^ (lane & 7)) << 4);
  unsigned char* const g_red = tm.red;
  {
    const uint32_t tag = *(volatile unsigned*)&g_epoch + 1;
    if (w == 0) {
      stg_relaxed(g_red + RED_SLOT(t2 >> 3) + RED_LINE(blockIdx.x) + (t2 & 7) * 16, 0, 0, 0, 0);
      asm volatile("st.relaxed.gpu.global.u8 [%0], 0;" :: "l"(g_red + RED_SLOT(t2) + HINT_OFF + (t2 & 4) * 1024 + (t2 >> 3) * 16384 + blockIdx.x) : "memory");
    }
    uint4 xv[18];
    uint32_t mv[20];
#pragma unroll
    for (int i = 0; i < 20; i++) mv[i] = i < 18 ? ((const uint32_t*)mem0)[(lane >> 2) * (DM / 2) + (w * 18 + i) * 4 + (lane & 3)] : 0;
#pragma unroll
    for (int i = 0; i < 18; i++) xv[i] = blockIdx.x < NSEG ? ((const uint4*)(x + blockIdx.x * 32 * DM))[t2 + 128 * i] : make_uint4(0, 0, 0, 0);
    bar_sync(0, 384);
    cluster_arrive();
    __half2 hx = __float2half2_rn(0.f);
#pragma unroll
    for (int i = 0; i < 18; i++) hx = amax4(hx, &xv[i].x);
    if (blockIdx.x == 0)
#pragma unroll
      for (int i = 0; i < 5; i++) hx = amax4(hx, &mv[4 * i]);
    sts32(sb + SC_SS + 4 * (12 + w), wexp(hx));
    if (t2 == 0) { sts32(sb + SC_UNSC, __float_as_uint(1.f)); sts128(sb + SC_DEAD, 0, 0, 0, 0x3f800000u); sts64(sb + SC_FPAR, 0, 0); sts128(sb + SC_ONES, 0x3f803f80u, 0x3f803f80u, 0x3f803f80u, 0x3f803f80u); }
    WSTAMP(27);
    if (w == 0) __threadfence();
    uint32_t q[8] = {0, 0, 0, 0, 0, 0, 0, 0};
    mbar_wait(sb + MB_WO3, 0);
    if (t2 == 0) SSTAMP(11, 3);
#pragma unroll
    for (int k = 0; k < 8; k++) {
      ldsm4t(wo[k], wo_lane + SM_WO3 + k * 2048); ldsm4t(w1[k], wo_lane + SM_WOST + k * 2048);
#pragma unroll
      for (int i = 0; i < 4; i++) { sq_acc(q[i], wo[k][i]); sq_acc(q[i], w1[k][i]); }
    }
    bar_sync(6, 128);
    if (t2 == 0) SSTAMP(11, 7);
#pragma unroll
    for (int k = 0; k < 8; k++) sts128(sb + SM_WO3 + t2 * 16 + k * 2048, wo[k][0], wo[k][1], wo[k][2], wo[k][3]);
#pragma unroll
    for (int i = 0; i < 5; i++) {
      const int j = w * 18 + 4 * i + (lane >> 3), c = i < 4 || lane < 16 ? j * 8 + j / 24 * 64 : 192;
      stsm4t(sb + SM_MEM + (c + (lane & 7)) * 16, mv[4 * i], mv[4 * i + 1], mv[4 * i + 2], mv[4 * i + 3]);
    }
    bar_arrive(1, 256); bar_arrive(2, 256); bar_arrive(9, 256);
    if (t2 == 0) SSTAMP(11, 8);
    mbar_wait(sb + MB_WO, 0);
    if (t2 == 0) SSTAMP(11, 4);
#pragma unroll
    for (int k = 0; k < 8; k++) ldsm4t(wo[k], wo_lane + SM_X + 2 * XT + k * 2048);
    fence_async();
    bar_sync(6, 128);
    if (t2 == 32) tma_load3(sb + SM_X + 2 * XT, &tm.x, 64, sb + MB_X + 16);
    __syncwarp();
#pragma unroll
    for (int k = 0; k < 8; k++)
#pragma unroll
      for (int i = 0; i < 4; i++) sq_acc(q[4 + i], wo[k][i]);
    float ss = 0.f;
#pragma unroll
    for (int i = 0; i < 8; i++) ss += bf_lo(q[i]) + bf_hi(q[i]);
    ss = warp_sum(ss);
    if (lane == 0) sts32(sb + SC_SS + 4 * (8 + w), __float_as_uint(ss));
    if (t2 == 0) SSTAMP(11, 9);
    bar_sync(11, 384);
    if (t2 == 0) SSTAMP(11, 10);
    if (t2 == 0) {
      float a[16];
#pragma unroll
      for (int i = 0; i < 4; i++) lds128f(sb + SC_SS + 16 * i, &a[4 * i]);
      stg_relaxed(&g_stats[blockIdx.x * 2], __float_as_uint(((a[0] + a[1]) + (a[2] + a[3])) + ((a[4] + a[5]) + (a[6] + a[7]))),
                  __float_as_uint((a[8] + a[9]) + (a[10] + a[11])),
                  max(max(__float_as_uint(a[12]), __float_as_uint(a[13])), max(__float_as_uint(a[14]), __float_as_uint(a[15]))), tag);
    }
    __syncwarp();
    WSTAMP(24);
    cluster_wait();
    if (w == 0) {
      uint4 v[3];
      int n = 0;
      while (true) {
#pragma unroll
        for (int i = 0; i < 3; i++) v[i] = ldg_relaxed(&g_stats[(i * 32 + lane) * 2]);
        if (__all_sync(0xffffffffu, v[0].w == tag && v[1].w == tag && v[2].w == tag) || ++n > SPIN_LIMIT) break;
        __nanosleep(100);
      }
      WSTAMP(25);
      const float sv = warp_sum(__uint_as_float(v[0].x) + __uint_as_float(v[1].x) + __uint_as_float(v[2].x));
      const float so = warp_sum(__uint_as_float(v[0].y) + __uint_as_float(v[1].y) + __uint_as_float(v[2].y));
      const int expW = ((int)(__float_as_uint(sv) >> 23) + (int)(__float_as_uint(so) >> 23) - 254 + 2 + 10 + 1) >> 1;
      sts32(sb + SC_XMAX + 4 * lane, v[0].z); sts32(sb + SC_XMAX + 128 + 4 * lane, v[1].z);
      sts32(sb + SC_EXPW, expW + 1 - 15);
      if (blockIdx.x == 0 && lane == 0) *(volatile unsigned*)&g_epoch = tag;
      sts32(sb + SC_FPAR + 4, 1);
    } else if (w < 3) {
      const uint32_t u = blockIdx.x >> 4;
      unsigned char* const z = g_red + 98304 + (blockIdx.x & 15) * 128 + (u & 1) * 2048 + (u & 6) * 4096 + (((u >> 1) ^ w) & 1) * 4096 + lane * 4;
      stg_relaxed32(z, 0);
      uint32_t best = 0xffffffffu;
#pragma unroll 1
      for (int i = 0; i < 64; i++) {
        uint32_t last, dt;
        asm volatile("{\n.reg .pred p;\n.reg .u32 c, v;\nld.volatile.shared.u32 %0, [%3];\nmov.u32 c, %%clock;\n"
                     "atom.relaxed.gpu.global.exch.b32 v, [%2], 0;\nsetp.eq.u32 p, v, 0;\nmov.u32 %1, 0;\n@p mov.u32 %1, %%clock;\nsub.u32 %1, %1, c;\n}"
                     : "=r"(last), "=r"(dt) : "l"(z), "r"(sb + SC_FPAR + 4) : "memory");
        best = min(best, dt);
        if (last && i >= NPROBE - 1) break;
      }
      sts32(sb + SC_LAT + (w - 1) * 4, best);
    }
    bar_sync(13, 384);
    bar_arrive(0, 384);
    WSTAMP(26);
  }

  const uint32_t nh = __shfl_sync(0xffffffffu, near_half(sb), 0);
  uint32_t l16 = sb + lane * 16;
  PIN(l16);
#define LV ((l16 >> 4) & 31)
#define fence_reg l16
  const uint32_t red_lo = (uint32_t)(uint64_t)g_red, red_hi = (uint32_t)((uint64_t)g_red >> 32);
  uint32_t lp;
  auto slot = [&](int s, uint32_t c, uint32_t ofs) {
    const uint32_t lo = lp | (red_lo + ((w >> 1) * 4 + (w & 1) * 2 + ((w ^ c) & 1)) * 4096 + RED_SLOT(s) + ofs);
    uint64_t a; asm("mov.b64 %0, {%1, %2};" : "=l"(a) : "r"(lo), "r"(red_hi));
    return (unsigned char*)a;
  };
  const uint32_t always = __shfl_sync(0xffffffffu, lds32(sb + SC_DEAD + 12), 0);
  const int mode0 = RANK < 2 ? w : w | 4;
  auto hint_addr = [&](int s) { return min(LV, 23u) * 4 + (red_lo + HINT_OFF + nh * 4096 + w * 16384 + RED_SLOT(s)); };
  auto load_hints = [&](uint32_t lo) {
    uint64_t a; asm("mov.b64 %0, {%1, %2};" : "=l"(a) : "r"(lo), "r"(red_hi));
    return ldg_relaxed32((const void*)a);
  };
  const uint32_t blk = RANK < 2 ? 9216 : SEGB, exb = RANK < 2 ? EXB : EXB2;
  auto export_rest = [&](int seg) { if (EXB && !(XP & 4) && elect_one()) seg_store(seg, sb, exb, blk - exb); __syncwarp(); };
  auto export_seg = [&](int seg) {
    if (!(XP & 4) && elect_one()) {
      if (seg > 0) seg_publish(seg - 1);
      fence_async();
      seg_store(seg, sb, 0, EXB ? exb : blk);
    }
    __syncwarp();
  };
  uint32_t dl = __shfl_sync(0xffffffffu, gtime() - 768, 0);
  int s = 0;
  bool bad = false;
#pragma unroll 1
  while (true) {
    const uint32_t par = s & 1;
    uint32_t vx[4][4], hints;
    auto load_vx = [&]() {
      const uint32_t va = l16 + (RANK < 2 ? SM_VC + par * 8192 : SM_BLK + (s & 3) * SEGB) + w * 1024 + ((LV >> 3) & 1) * 384 - (LV >> 4) * 128;
#pragma unroll
      for (int i = 0; i < 4; i++) ldsm4(vx[i], va + (i & 1) * 4096 + (i >> 1) * 256);
    };
    auto retire = [&](uint32_t x) {
      asm volatile("{\n.reg .pred p;\nsetp.eq.u32 p, %0, 0;\n@p exit;\n}" :: "r"(vx[0][0] | vx[1][0] | vx[2][0] | vx[3][0] | x) : "memory");
    };
    auto scores = [&](auto memkeys, auto first, float* sc) {
      constexpr bool MK = decltype(memkeys)::value, FIRST = decltype(first)::value;
      uint32_t kb[4][4], qb[2][4];
      const uint32_t m = LV >> 3;
      uint32_t kaddr = l16 + SM_BLK + 4096 + (s & 3) * SEGB + w * 2048 + (m & 1) * (MK ? 128 : 896) - (m >> 1) * 128;
      if (MK) { PIN(kaddr); }
      else {
#pragma unroll
        for (int k = 0; k < 4; k++) ldsm4t(kb[k], kaddr + k * 256);
      }
      if (FIRST) { load_vx(); retire(MK ? kaddr : kb[0][0] | kb[1][0] | kb[2][0] | kb[3][0] | l16); bar_sync(4, 256); PROF(4); }
      ldsm4t(qb[0], l16 + SM_QM);
      if (MK) ldsm4t(kb[0], kaddr);
      ldsm4t(qb[1], l16 + SM_QM + 512);
      if (MK) ldsm4t(kb[2], kaddr + 512);
      float c[4][4];
      mma16816z(c[0], kb[0], qb[0][0], qb[0][1]); mma16816z(c[1], kb[MK ? 0 : 1], qb[0][2], qb[0][3]);
      mma16816z(c[2], kb[2], qb[1][0], qb[1][1]); mma16816z(c[3], kb[MK ? 2 : 3], qb[1][2], qb[1][3]);
      if (FIRST && B5POS == 0) bar_arrive(5, N5);
#pragma unroll
      for (int i = 0; i < (MK ? 2 : 4); i++) sc[i] = ((c[0][i] + c[1][MK ? i + 2 : i]) + c[2][i]) + c[3][MK ? i + 2 : i];
    };
    auto send = [&](auto memkeys) {
      constexpr bool MK = decltype(memkeys)::value;
      constexpr int N = MK ? 1 : 2;
      const uint32_t sa = sb + LV * 4 + SM_E + (MK ? 1024 + RANK * 128 : RANK * 512 + w * 256);
      uint32_t ra[N][2], mb[N][2];
#pragma unroll
      for (int i = 0; i < N; i++)
#pragma unroll
        for (int j = 0; j < 2; j++) {
          ra[i][j] = mapa(sa + i * 128, j ? 2 : RANK ^ 1); mb[i][j] = mapa(sb + MB_S, j ? 2 : RANK ^ 1);
          PIN(ra[i][j]);
        }
      float sc[4];
      scores(memkeys, BoolC<true>(), sc);
      uint32_t e[N];
#pragma unroll
      for (int i = 0; i < N; i++) {
        e[i] = pack_bf16(ex2(sc[2 * i]), ex2(sc[2 * i + 1]));
        if (!(fmaxf(fabsf(sc[2 * i]), fabsf(sc[2 * i + 1])) <= E_LIM)) e[i] = 0x7fff7fffu;
        st_async1(ra[i][0], e[i], mb[i][0]);
        st_async1(ra[i][1], e[i], mb[i][1]);
      }
#pragma unroll
      for (int i = 0; i < N; i++) sts32(sa + i * 128, e[i]);
      __syncwarp();
      if (l16 == sb) mbar_arrive(sb + MB_S);
      PROF(5);
    };
    const int mode = bad ? 8 : mode0;
    if (mode < 2) {
      send(BoolC<false>());
    } else if (mode == 2) {
      send(BoolC<true>());
    } else if (mode == 8) {
      load_vx();
      retire(l16);
      const uint32_t fp = lds32(sb + SC_FPAR);
      bar_sync(6, 128);
      if (w == 0 && l16 == sb) { sts32(sb + SC_FPAR, fp ^ 1); mbar_expect(sb + MB_F, 3072); }
      if (RANK < 2 && w < 3) {
        float sc[4] = {0.f, 0.f, 0.f, 0.f};
        if (w < 2) scores(BoolC<false>(), BoolC<false>(), sc); else scores(BoolC<true>(), BoolC<false>(), sc);
#pragma unroll 1
        for (int r = 0; r < 3; r++)
          st_async4(mapa(l16 + SM_FB + RANK * 1536 + w * 512, r), __float_as_uint(sc[0]), __float_as_uint(sc[1]), __float_as_uint(sc[2]), __float_as_uint(sc[3]), mapa(sb + MB_F, r));
      }
      mbar_wait(sb + MB_F, fp);
      float a[12];
#pragma unroll
      for (int j = 0; j < 3; j++) {
        float b[4];
        lds128f(l16 + SM_FB + j * 512, a + 4 * j); lds128f(l16 + SM_FB + 1536 + j * 512, b);
#pragma unroll
        for (int i = 0; i < 4; i++) a[4 * j + i] += b[i];
      }
      float m0 = fmaxf(fmaxf(fmaxf(a[0], a[2]), fmaxf(a[4], a[6])), a[8]), m1 = fmaxf(fmaxf(fmaxf(a[1], a[3]), fmaxf(a[5], a[7])), a[9]);
#pragma unroll
      for (int o = 4; o < 32; o <<= 1) { m0 = fmaxf(m0, __shfl_xor_sync(0xffffffffu, m0, o)); m1 = fmaxf(m1, __shfl_xor_sync(0xffffffffu, m1, o)); }
#pragma unroll
      for (int i = 0; i < 5; i++) {
        const uint32_t ea = sb + SM_E + LV * 4 + (i < 4 ? i * 128 : 1024);
        sts32(ea, pack_bf16(ex2(a[2 * i] - m0), ex2(a[2 * i + 1] - m1)));
        sts32(ea + (i < 4 ? 512 : 128), 0x3f803f80u);
      }
      __syncwarp();
    } else {
      load_vx();
      if (mode == 3) bar_arrive(4, 256);
      retire(l16 + 1);
      if (w == 3) {
        if (EXPOS == 0 && s > 0) export_seg(s - 1);
        if (EXB) { if (RANK < 2) bar_sync(5, N5); else bar_sync(15, 160); if (s > 0) export_rest(s - 1); }
      }
    }
    {
      uint32_t wa[4], wb[4], oc[4];
      constexpr int WS = 2048;
      const uint32_t w3a = l16 + SM_WO3 + w * 512;
      lds128(w3a + KP(0) * WS, wa); lds128(w3a + KP(1) * WS, wb); lds128(sb + SC_ONES, oc);
      if (B5POS == 1 && mode < 3) bar_arrive(5, N5);
      uint32_t e[10], p[5], vm[4], ob[4];
      float o0[4], o1[4], f[3][2][4], rs[4];
      reserve2(vm); reserve2(vm + 2); reserve2(e + 8);
      hints = hint_addr(s);
      PIN(hints);
      if (CLR & 2) asm volatile("{\n.reg .pred p;\nsetp.eq.u32 p, %0, 0;\n@p exit;\n}" :: "r"(wa[0] | wb[0] | oc[0] | hints) : "memory");
      mbar_wait(sb + MB_S, par);
      PROF(6);
      ldsm4t(e, l16 + SM_E); ldsm2t_in(e + 8, l16 + SM_E + 1024, always); ldsm4t(e + 4, l16 + SM_E + 512);
      lds128_in(vm, l16 + w * 512 + SM_VM, always);
      const float scl = __uint_as_float(lds32(sb + SC_UNSC + 8 - par * 8));
      hints = load_hints(hints);
      if (GF & 1) SCHED_FENCE(4);
#pragma unroll
      for (int i = 0; i < 4; i++) p[i] = mul_bf16(e[i], e[4 + i]);
      p[4] = mul_bf16(e[8], e[9]);
      mma16816z(o0, vx[0], p[0], p[1]); mma16816z(o1, vx[1], p[0], p[1]); mma16816z(rs, oc, p[0], p[1]);
      mma16816(o0, vx[2], p[2], p[3]); lds128_in(vx[2], w3a + KP(2) * WS, always);
      mma16816(o1, vx[3], p[2], p[3]); lds128_in(vx[3], w3a + KP(3) * WS, always);
      mma16816(rs, oc, p[2], p[3]);
      mma1688(o0, vm[0], vm[1], p[4]); mma1688(o1, vm[2], vm[3], p[4]); mma1688(rs, oc[0], oc[1], p[4]);
      stsm4(l16 + w * 512 + SM_OB, pack_bf16(o0[0], o0[1]), pack_bf16(o0[2], o0[3]), pack_bf16(o1[0], o1[1]), pack_bf16(o1[2], o1[3]));
      bar_sync(6, 128);
      PROF(7);
      ldsm4t_in(oc, l16 + SM_OB, always);
      bad = __any_sync(0xffffffffu, !(rs[0] + rs[1] > 0.f) && !bad);
      rs[0] *= scl; rs[1] *= scl;
      asm volatile("{\n.reg .pred p;\nsetp.ne.u32 p, %1, 0;\n@p rcp.approx.ftz.f32 %0, %0;\n}" : "+f"(rs[0]) : "r"(always));
      asm volatile("{\n.reg .pred p;\nsetp.ne.u32 p, %1, 1;\n@p rcp.approx.ftz.f32 %0, %0;\n}" : "+f"(rs[1]) : "r"(always));
      asm volatile("lop3.b32 %0, %1, %2, %3, 0xfe;" : "=r"(lp) : "r"((l16 & 128) * 2), "r"((l16 & 256) * 4), "r"(l16 & 112));
      if (bad) continue;
      ldsm4t(ob, l16 + SM_OB + 512);
      mma16816z(f[2][0], wa, oc[0], oc[1]); mma16816z(f[2][1], wb, oc[2], oc[3]);
      mma16816z(f[0][0], wo[0], oc[0], oc[1]); mma16816z(f[0][1], wo[4], oc[2], oc[3]);
      mma16816z(f[1][0], w1[0], oc[0], oc[1]); mma16816z(f[1][1], w1[4], oc[2], oc[3]);
      ldsm4t_in(oc, l16 + SM_OB + 1024, always);
      mma16816(f[2][0], vx[2], ob[0], ob[1]); lds128_in(vx[2], w3a + KP(4) * WS, always);
      mma16816(f[2][1], vx[3], ob[2], ob[3]); lds128_in(vx[3], w3a + KP(5) * WS, always);
      mma16816(f[0][0], wo[1], ob[0], ob[1]); mma16816(f[0][1], wo[5], ob[2], ob[3]);
      mma16816(f[1][0], w1[1], ob[0], ob[1]); mma16816(f[1][1], w1[5], ob[2], ob[3]);
      ldsm4t_in(ob, l16 + SM_OB + 1536, always);
      mma16816(f[0][0], wo[2], oc[0], oc[1]); mma16816(f[0][1], wo[6], oc[2], oc[3]);
      mma16816(f[2][0], vx[2], oc[0], oc[1]); lds128_in(vx[2], w3a + KP(6) * WS, always);
      mma16816(f[2][1], vx[3], oc[2], oc[3]); lds128_in(vx[3], w3a + KP(7) * WS, always);
      mma16816(f[1][0], w1[2], oc[0], oc[1]); mma16816(f[1][1], w1[6], oc[2], oc[3]);
      mma16816(f[0][0], wo[3], ob[0], ob[1]); mma16816(f[0][1], wo[7], ob[2], ob[3]);
      mma16816(f[1][0], w1[3], ob[0], ob[1]); mma16816(f[1][1], w1[7], ob[2], ob[3]);
      mma16816(f[2][0], vx[2], ob[0], ob[1]); mma16816(f[2][1], vx[3], ob[2], ob[3]);
      bar_arrive(7, NII < 18 ? 384 : 256);
      lds128_in(ob, sb + SC_DEAD, always);
      uint32_t h[3][2];
#pragma unroll
      for (int j = 0; j < 3; j++)
#pragma unroll
        for (int i = 0; i < 2; i++)
        {
          scale_sum(f[j][1][2 * i], f[j][0][2 * i], rs[0], always); scale_sum(f[j][1][2 * i + 1], f[j][0][2 * i + 1], rs[1], always);
          h[j][i] = pack_f16(f[j][1][2 * i], f[j][1][2 * i + 1]);
        }
      const uint32_t rofs = RANK * 32768;
      red_f16x8(slot(s, RANK >> 1, rofs), h[0][0], h[1][0], h[2][0], 0x3c00u);
      red_f16x8(slot(s, (RANK >> 1) ^ 1, rofs), h[0][1], h[1][1], h[2][1], 0x3c00u);
      if (NII == 18) bar_arrive(10, 256);
      SCHED_FENCE(5);
      l16 += ob[B7R];
    }
    {
    PROF(8);
    const uint32_t ma0 = l16 + SM_MEM + w * 128 + (LV >> 3) * 896 + nh * 512;
    const unsigned char* const sl[2] = {slot(s, nh, 0), slot(s, nh ^ 1, 0)};
    uint32_t late = latest_hint(hints, dl, s);
    if (late >= 64) {
      int n = 0;
#pragma unroll 1
      do {
        late = latest_hint(load_hints(hint_addr(s)), dl, s);
      } while (late >= 64 && ++n < SPIN_LIMIT);
    }
    dl += late * 32 + tm.poll;
    if (EXPOS == 2 && w == 3) export_seg(s);
    PROF(9);
    {
      auto wait_until = [&](uint32_t t) {
        asm volatile("{\n.reg .pred p;\n.reg .s32 c;\n.reg .u64 t;\nTL: mov.u64 t, %%globaltimer;\ncvt.u32.u64 c, t;\nsub.s32 c, c, %0;\nsetp.lt.s32 p, c, 0;\n@p bra.uni TL;\n}" :: "r"(t + (l16 & 15)) : "memory");
      };
      uint4 v[2][3];
      auto load = [&](int c) {
#pragma unroll
        for (int r = 0; r < 3; r++) v[c][r] = ldg_relaxed(sl[c ^ (r >> 1)] + r * 32768);
      };
      auto decode = [&](int c, int n) {
        uint32_t q[9];
        __half2 hm;
        const uint32_t ma = ma0 ^ (c * 512);
#pragma unroll
        for (int i = 0; i < 9; i++) {
          const uint32_t h = i % 3 == 0 ? v[c][i / 3].x : (i % 3 == 1 ? v[c][i / 3].y : v[c][i / 3].z);
          const float2 f = __half22float2(*(const __half2*)&h);
          q[i] = pack_bf16(f.x, f.y);
          hm = i ? __hmax2(hm, __habs2(*(const __half2*)&h)) : __habs2(*(const __half2*)&h);
        }
#pragma unroll
        for (int r = 0; r < 3; r++) stsm4(ma + r * 4096, q[3 * r], q[3 * r + 1], q[3 * r + 2], r < 2 ? v[c][r].w : *(const uint32_t*)&hm);
        const bool done = __all_sync(0xffffffffu, v[c][0].w == 0x5000u && v[c][1].w == 0x5000u && v[c][2].w == 0x5000u) || n > SPIN_LIMIT;
        asm volatile("{\n.reg .pred p;\nsetp.ne.u32 p, %0, 0;\n@p bar.arrive %1, 256;\n}" :: "r"((int)done), "r"(1 + c) : "memory");
        return done;
      };
      if (LEAD) { wait_until(dl - LEAD); load(1); }
      wait_until(dl);
      PROF(10);
      int n = 0;
#pragma unroll 1
      do {
        load(0);
        if (!LEAD) load(1);
        asm volatile("{\n.reg .pred p;\nsetp.eq.u32 p, %0, 0;\n@p bar.sync 13, 384;\n}" :: "r"(n) : "memory");
      } while (!decode(0, n++));
      PROF(11);
#pragma unroll 1
      while (!decode(1, n++)) load(1);
      bar_arrive(9, 256);
      PROF(12);
    }
    if (EXPOS == 3 && w == 3) export_seg(s);
    PROF(13);
    if (++s == NSEG - 1) break;
    }
  }
#undef fence_reg
  if (RANK < 2) bar_arrive(4, 256);
  if (w == 3) { if (EXPOS < 2 || EXPOS == 4) export_seg(NSEG - 2); export_rest(NSEG - 2); if (!(XP & 4) && elect_one()) seg_publish(NSEG - 2); }
  __syncwarp();
  bar_sync(0, 384);
  if (w == 3 && !(XP & 4) && elect_one()) {
    fence_async();
    seg_store(NSEG - 1, sb, 0, blk);
    seg_publish(NSEG - 1);
  }
  __syncwarp();
  cluster_sync();
}

__global__ void __cluster_dims__(3, 1, 1) __launch_bounds__(384, 1)
rec_kernel(const __grid_constant__ RMaps tm, const bf16* __restrict__ x, const bf16* __restrict__ mem0) {
  extern __shared__ __align__(1024) unsigned char smem_raw[];
  const uint32_t sb = smem_u32(smem_raw);
  const int tid = threadIdx.x, lane = tid & 31;
  const int wg = __shfl_sync(0xffffffffu, tid >> 7, 0);
  const int w = __shfl_sync(0xffffffffu, (tid >> 5) & 3, 0);
  uint32_t rank; asm("mov.u32 %0, %%cluster_ctarank;" : "=r"(rank));
  STAMP(0);
  asm volatile("griddepcontrol.launch_dependents;" ::: "memory");

#define PF 0
#define PFD 0
#define PFS 8192
  if (PF && (tid >> 5) == 4 && lane < 4 * 49152 / PFS) {
    const int m = lane & 3, j = lane >> 2;
    const size_t off = PF == 1 ? (size_t)blockIdx.x * 49152 + j * PFS : ((size_t)j * 96 + blockIdx.x) * PFS;
    asm volatile("cp.async.bulk.prefetch.L2.global [%0], %1;" :: "l"(tm.w[m] + off), "r"(PFS) : "memory");
  }
  if (wg < 2) {
    asm volatile("setmaxnreg.inc.sync.aligned.u32 192;");
    if (tid == 0) {
      for (int i = 0; i < 3; i++) { mbar_init(sb + MB_W + 8 * i, 1); mbar_init(sb + MB_X + 8 * i, 1); }
      mbar_init(sb + MB_WO, 1); mbar_init(sb + MB_WO3, 1);
      mbar_init(sb + MB_S, rank < 2 ? 5 : 6);
      mbar_init(sb + MB_F, 1);
      mbar_init(sb + MB_VX, 1); mbar_init(sb + MB_VX + 8, 1);
      asm volatile("fence.mbarrier_init.release.cluster;" ::: "memory");
      fence_async();
      SSTAMP(11, 6);
      if (PFD) wait_until(gtime() + PFD);
      const int h = blockIdx.x / 3;
      const CUtensorMap* m0 = rank < 2 ? &tm.wk : &tm.wv;
      const CUtensorMap* m1 = rank < 2 ? &tm.wq : &tm.wv;
      const int c0 = h * DH + (rank == 1 ? 64 : 0), c1 = h * DH + (rank == 0 ? 0 : 64);
      for (int c = 0; c < 3; c++) {
        mbar_expect(sb + MB_W + 8 * c, 49152);
        tma_load(sb + SM_STAGE + c * 49152, m0, c0, c * 192, sb + MB_W + 8 * c);
        tma_load(sb + SM_STAGE + c * 49152 + 24576, m1, c1, c * 192, sb + MB_W + 8 * c);
      }
      for (int i = 0; i < 3; i++) mbar_expect(sb + MB_X + 8 * i, XT);
      tma_load3(sb + SM_X, &tm.x, 0, sb + MB_X);
      tma_prefetch(&tm.wo, rank * 192, h * DH);
      mbar_expect(sb + MB_WO, 16384);
      mbar_expect(sb + MB_WO3, 32768);
      tma_load(sb + SM_WOST, &tm.wo, rank * 192 + 64, h * DH, sb + MB_WO3);
      tma_load(sb + SM_WO3, &tm.wo, rank * 192 + 128, h * DH, sb + MB_WO3);
      mbar_expect(sb + MB_S, rank < 2 ? 640 + 2048 : 1280);
      mbar_expect(sb + MB_VX, 8192); mbar_expect(sb + MB_VX + 8, 8192);
      SSTAMP(11, 5);
    }
    __syncwarp();
    bar_sync(0, 384);
    proj_role(sb, tm, rank, wg, w, lane);
  } else {
    asm volatile("setmaxnreg.dec.sync.aligned.u32 120;");
    attn_role(sb, smem_raw, tm, rank, x, mem0, w, lane);
  }
}

constexpr int NAUX = 36;
constexpr int A_XH = 73728;
constexpr int A_NS = 9, A_WM = 6144, A_WT = 768;
constexpr int A_RING = 2 * A_XH, A_TAIL = A_RING + A_NS * A_WM, A_GW = A_TAIL + A_NS * A_WT;
constexpr int A_EPI = 212864, A_EPW = 9344;
constexpr int A_XT = 4 * XT, A_XW = A_XT + 8192, A_EX = A_XW + 8192, A_NR = 4;
constexpr int A_IN = A_EX + 16384, A_OST = A_IN + 3 * SEGB;
constexpr int A_GATE = A_EPI + 2 * A_EPW, A_BAR = A_GATE + 512;
constexpr int A_TOTAL = A_BAR + 384;
struct AMaps { CUtensorMap x, wa, wt, oa, o, o3, wob, woa; };

DI void wgmma_n192_ss_nt(float* d, uint64_t da, uint64_t db, int acc) {
  asm volatile("{\n.reg .pred p;\nsetp.ne.b32 p, %98, 0;\n"
               "wgmma.mma_async.sync.aligned.m64n192k16.f32.bf16.bf16 {"
               "%0,%1,%2,%3,%4,%5,%6,%7,%8,%9,%10,%11,%12,%13,%14,%15,%16,%17,%18,%19,%20,%21,%22,%23,%24,%25,%26,%27,%28,%29,%30,%31,"
               "%32,%33,%34,%35,%36,%37,%38,%39,%40,%41,%42,%43,%44,%45,%46,%47,%48,%49,%50,%51,%52,%53,%54,%55,%56,%57,%58,%59,%60,%61,%62,%63,"
               "%64,%65,%66,%67,%68,%69,%70,%71,%72,%73,%74,%75,%76,%77,%78,%79,%80,%81,%82,%83,%84,%85,%86,%87,%88,%89,%90,%91,%92,%93,%94,%95"
               "}, %96, %97, p, 1, 1, 0, 1;\n}\n"
               : ACC8(d, 0), ACC8(d, 8), ACC8(d, 16), ACC8(d, 24), ACC8(d, 32), ACC8(d, 40), ACC8(d, 48), ACC8(d, 56),
                 ACC8(d, 64), ACC8(d, 72), ACC8(d, 80), ACC8(d, 88) : "l"(da), "l"(db), "r"(acc));
}
#define ACC4(d, o) "+f"(d[o]), "+f"(d[o + 1]), "+f"(d[o + 2]), "+f"(d[o + 3])
DI void wgmma_n24_ss_nt(float* d, uint64_t da, uint64_t db, int acc) {
  asm volatile("{\n.reg .pred p;\nsetp.ne.b32 p, %14, 0;\n"
               "wgmma.mma_async.sync.aligned.m64n24k16.f32.bf16.bf16 {%0,%1,%2,%3,%4,%5,%6,%7,%8,%9,%10,%11}, %12, %13, p, 1, 1, 0, 1;\n}\n"
               : ACC8(d, 0), ACC4(d, 8) : "l"(da), "l"(db), "r"(acc));
}
DI void wgmma_n40_ss_tt(float* d, uint64_t da, uint64_t db, int acc) {
  asm volatile("{\n.reg .pred p;\nsetp.ne.b32 p, %22, 0;\n"
               "wgmma.mma_async.sync.aligned.m64n40k16.f32.bf16.bf16 {%0,%1,%2,%3,%4,%5,%6,%7,%8,%9,%10,%11,%12,%13,%14,%15,%16,%17,%18,%19}, "
               "%20, %21, p, 1, 1, 1, 1;\n}\n"
               : ACC8(d, 0), ACC8(d, 8), ACC4(d, 16) : "l"(da), "l"(db), "r"(acc));
}
DI void wgmma_n64_rs(float* d, const uint32_t* a, uint64_t db, int acc) {
  asm volatile("{\n.reg .pred p;\nsetp.ne.b32 p, %37, 0;\n"
               "wgmma.mma_async.sync.aligned.m64n64k16.f32.bf16.bf16 {"
               "%0,%1,%2,%3,%4,%5,%6,%7,%8,%9,%10,%11,%12,%13,%14,%15,%16,%17,%18,%19,%20,%21,%22,%23,%24,%25,%26,%27,%28,%29,%30,%31"
               "}, {%32,%33,%34,%35}, %36, p, 1, 1, 0;\n}\n"
               : ACC8(d, 0), ACC8(d, 8), ACC8(d, 16), ACC8(d, 24) : "r"(a[0]), "r"(a[1]), "r"(a[2]), "r"(a[3]), "l"(db), "r"(acc));
}
DI void wgmma_n32_ss_tn(float* d, uint64_t da, uint64_t db, int acc) {
  asm volatile("{\n.reg .pred p;\nsetp.ne.b32 p, %18, 0;\n"
               "wgmma.mma_async.sync.aligned.m64n32k16.f32.bf16.bf16 {%0,%1,%2,%3,%4,%5,%6,%7,%8,%9,%10,%11,%12,%13,%14,%15}, "
               "%16, %17, p, 1, 1, 1, 0;\n}\n"
               : ACC8(d, 0), ACC8(d, 8) : "l"(da), "l"(db), "r"(acc));
}
DI void tma_load3c(uint32_t dst, const CUtensorMap* m, int c0, int c1, int c2, uint32_t mb) {
  asm volatile("cp.async.bulk.tensor.3d.shared::cluster.global.mbarrier::complete_tx::bytes [%0], [%1, {%3, %4, %5}], [%2];"
               :: "r"(dst), "l"(m), "r"(mb), "r"(c0), "r"(c1), "r"(c2) : "memory");
}
DI uint32_t movm(uint32_t x) { uint32_t r; asm volatile("movmatrix.sync.aligned.m8n8.trans.b16 %0, %1;" : "=r"(r) : "r"(x)); return r; }
DI void wait_count(const unsigned* p, unsigned target) {
  int n = 0;
  unsigned v;
  while (true) {
    asm volatile("ld.acquire.gpu.global.b32 %0, [%1];" : "=r"(v) : "l"(p) : "memory");
    if ((int)(v - target) >= 0 || ++n > SPIN_LIMIT) break;
    __nanosleep(64);
  }
}
DI void count_up(unsigned* p) {
  asm volatile("fence.proxy.async;" ::: "memory");
  asm volatile("red.release.gpu.global.add.u32 [%0], 1;" :: "l"(p) : "memory");
}
#define AX 0
#define ADLY 0

__global__ void __launch_bounds__(512, 1)
aux_kernel(const __grid_constant__ AMaps tm, const bf16* __restrict__ wqkv, const bf16* __restrict__ gate_w, bf16* __restrict__ out) {
  extern __shared__ __align__(1024) unsigned char smem_raw[];
  const uint32_t sb = smem_u32(smem_raw);
  const uint32_t fullx = sb + A_BAR, full1 = fullx + 24, empty1 = full1 + 8 * A_NS, fullw = empty1 + 8 * A_NS, full3 = fullw + 8, empty3 = full3 + 8 * A_NR,
                 fullq = empty3 + 8 * A_NR, fullv = fullq + 8, emptyq = fullv + 8, emptyv = emptyq + 8;
  const int tid = threadIdx.x, lane = tid & 31, cta = blockIdx.x;
  const int wg = __shfl_sync(0xffffffffu, tid >> 7, 0), w = __shfl_sync(0xffffffffu, (tid >> 5) & 3, 0);
  ASTAMP(14);
  if (tid == 384) {
    for (int i = 0; i < 3; i++) mbar_init(fullx + 8 * i, 1);
    for (int i = 0; i < A_NS; i++) { mbar_init(full1 + 8 * i, 1); mbar_init(empty1 + 8 * i, 8); }
    mbar_init(fullw, 1); mbar_init(fullq, 1); mbar_init(fullv, 1); mbar_init(emptyq, 4); mbar_init(emptyv, 4);
    for (int i = 0; i < A_NR; i++) { mbar_init(full3 + 8 * i, 1); mbar_init(empty3 + 8 * i, 4); }
    fence_async();
  }
  __syncthreads();
  ASTAMP(0);
  const int tile = cta >> 1, hh = cta & 1;
  const int nsl = cta >> 2, kq = cta & 3;
  if (wg == 3) {
    asm volatile("setmaxnreg.dec.sync.aligned.u32 24;");
    const bool lead = lane == 0;
    if (w < 3) {
      if (ADLY) wait_until(gtime() + ADLY);
      if (elect_one()) {
        mbar_expect(fullx + 8 * w, 49152);
        for (int p = 0; p < 2; p++)
          asm volatile("cp.async.bulk.tensor.4d.shared::cluster.global.mbarrier::complete_tx::bytes [%0], [%1, {%3, %4, %5, %6}], [%2];"
                       :: "r"(sb + p * A_XH + w * 24576), "l"(&tm.x), "r"(fullx + 8 * w), "r"(0), "r"(p), "r"(57 * tile - 7), "r"(3 * w) : "memory");
      }
#pragma unroll 1
      for (int r = 0; r < 17; r++) {
#pragma unroll 1
        for (int st = w; st < A_NS; st += 3) {
          if (r > 0) mbar_wait(empty1 + 8 * st, ~r & 1);
          if (r < 16 && elect_one()) {
            const int col = hh * 288 + (r >> 2) * 72, row = (r & 3) * 144 + st * 16;
            mbar_expect(full1 + 8 * st, A_WM + (AX & 1 ? 0 : A_WT));
            tma_load3c(sb + A_RING + st * A_WM, &tm.wa, col, row, 0, full1 + 8 * st);
            if (!(AX & 1)) tma_load3c(sb + A_TAIL + st * A_WT, &tm.wt, col + 64, row, 0, full1 + 8 * st);
          }
          __syncwarp();
        }
        if (r == 0 && elect_one())
          for (int j = 0; j < 3; j++)
            asm volatile("cp.async.bulk.prefetch.L2.global [%0], %1;" :: "l"((const char*)wqkv + cta * 55296 + (w * 3 + j) * 6144), "r"(6144) : "memory");
        __syncwarp();
      }
      bar_sync(8, 96);
    }
    const unsigned epoch = lds32(sb + A_BAR + 376);
    if (w == 1 && cta < NH) {
#pragma unroll 1
      for (int seg = 0; seg < NSEG; seg++) {
        bar_arrive(5, 160);
        if (seg > 0 && lead) {
          asm volatile("cp.async.bulk.wait_group 0;" ::: "memory");
          asm volatile("red.relaxed.gpu.global.add.u32 [%0], 1;" :: "l"(&g_ocnt[(seg - 1) * 32]) : "memory");
          SSTAMP(9, seg - 1);
        }
        __syncwarp();
        bar_sync(4, 160);
        if (lead) {
          tma_store(&tm.o, sb + A_OST, cta * DH, seg * 32);
          tma_store(&tm.o, sb + A_OST + 4096, cta * DH + 64, seg * 32);
          asm volatile("cp.async.bulk.commit_group;" ::: "memory");
          asm volatile("cp.async.bulk.wait_group.read 0;" ::: "memory");
        }
        __syncwarp();
      }
      if (lead) {
        asm volatile("cp.async.bulk.wait_group 0;" ::: "memory");
        asm volatile("red.relaxed.gpu.global.add.u32 [%0], 1;" :: "l"(&g_ocnt[(NSEG - 1) * 32]) : "memory");
        SSTAMP(9, NSEG - 1);
      }
    }
    if (w == 2) {
      if (lead && cta < NH) {
#pragma unroll 1
        for (int seg = 0; seg < NSEG; seg++) {
          const unsigned char* const src = g_seg + ((size_t)(seg & RING) * 96 + cta * 3) * SEGB;
          SSTAMP(0, seg);
          wait_count(&g_scnt[(seg * 32 + cta) * 8], 3 * (epoch + 1));
          SSTAMP(1, seg);
          mbar_wait(emptyq, ~seg & 1);
          mbar_expect(fullq, 2 * SEGB);
          asm volatile("cp.async.bulk.shared::cluster.global.mbarrier::complete_tx::bytes [%0], [%1], %2, [%3];"
                       :: "r"(sb + A_IN), "l"(src), "r"(2 * SEGB), "r"(fullq) : "memory");
          mbar_wait(emptyv, ~seg & 1);
          mbar_expect(fullv, SEGB);
          asm volatile("cp.async.bulk.shared::cluster.global.mbarrier::complete_tx::bytes [%0], [%1], %2, [%3];"
                       :: "r"(sb + A_IN + 2 * SEGB), "l"(src + 2 * SEGB), "r"(SEGB), "r"(fullv) : "memory");
        }
      }
    }
    if (w == 3) {
#pragma unroll 1
      for (int c = 0; c < 4; c++) {
        if (lead) asm volatile("cp.async.bulk.wait_group.read 0;" ::: "memory");
        __syncwarp();
        bar_arrive(11, 160); bar_arrive(12, 160);
#pragma unroll 1
        for (int g = 0; g < 2; g++) {
          bar_sync(13 + g, 160);
          if (lead) {
            asm volatile("cp.async.bulk.tensor.3d.global.shared::cta.bulk_group [%0, {%2, %3, %4}], [%1];"
                         :: "l"(&tm.oa), "r"(sb + A_EPI + g * A_EPW + 1024), "r"(4096 + hh * 288 + c * 72), "r"(g), "r"(57 * tile) : "memory");
            asm volatile("cp.async.bulk.commit_group;" ::: "memory");
          }
        }
      }
      if (lead) asm volatile("cp.async.bulk.wait_group.read 0;" ::: "memory");
      __syncwarp();
      bar_arrive(10, 160);
      if (lead) { asm volatile("cp.async.bulk.wait_group 0;" ::: "memory"); count_up(&g_abar[32]); }
    }
    if (w != 0) return;
    if (lead) {
      mbar_expect(fullw, 19 * 8192);
#pragma unroll 1
      for (int k = 0; k < 19; k++) {
        const int kb = k < 18 ? kq * 18 + k : 72;
        const uint32_t dst = sb + (k < 18 ? k * 8192 : A_XW);
        if (kb < 64) tma_load(dst, &tm.wob, nsl * 64, kb * 64, fullw);
        else tma_load(dst, &tm.woa, nsl * 64, (kb - 64) * 64, fullw);
      }
    }
    __syncwarp();
    bar_sync(6, 288);
    if (lead) {
      if (kq == 3) { wait_count(&g_abar[32], NAUX * (epoch + 1)); asm volatile("fence.proxy.async;" ::: "memory"); }
      int avail = 0;
      for (int seg = 0; seg < NSEG; seg++) {
        if (seg >= avail) {
          const int far = min(seg + 3, NSEG - 1);
          if ((int)(ldg_acquire32(&g_ocnt[far * 32]) - 32 * (epoch + 1)) >= 0) avail = far + 1;
          else { wait_count(&g_ocnt[seg * 32], 32 * (epoch + 1)); avail = seg + 1; }
        }
        SSTAMP(5, seg);
        for (int g = 0; g < 2; g++) {
          const int sl = (seg & 1) * 2 + g;
          const bool extra = kq == 3 && g == 0;
          mbar_wait(empty3 + 8 * sl, ((seg >> 1) & 1) ^ 1);
          mbar_expect(full3 + 8 * sl, XT + (extra ? 4096 : 0));
          tma_load3c(sb + sl * XT, &tm.o3, 0, seg * 32, kq * 18 + 9 * g, full3 + 8 * sl);
          if (extra) tma_load(sb + A_XT + (seg & 1) * 4096, &tm.o, 72 * 64, seg * 32, full3 + 8 * sl);
        }
      }
    }
    __syncwarp(); bar_sync(6, 288);
    asm volatile("griddepcontrol.wait;" ::: "memory");
  } else if (wg == 2) {
    asm volatile("setmaxnreg.dec.sync.aligned.u32 88;");
    {
      const unsigned epoch = *(volatile unsigned*)&g_epoch2;
      const int r = tid & 63, par = (tid >> 6) & 1;
      if ((tid & 127) < 72) { const uint4 g = __ldg((const uint4*)gate_w + (tid & 127)); sts128(sb + A_GW + (tid & 127) * 16, g.x, g.y, g.z, g.w); }
      bar_sync(3, 128);
      float dot[2] = {0.f, 0.f};
#pragma unroll 1
      for (int kb = 0; kb < 9; kb++) {
        if (kb % 3 == 0) mbar_wait(fullx + 8 * (kb / 3), 0);
#pragma unroll
        for (int c = 0; c < 8; c++) {
          uint32_t a[4];
          lds128(sb + par * A_XH + kb * 8192 + r * 128 + ((c ^ (r & 7)) << 4), a);
          uint4 g;
          lds128(sb + A_GW + kb * 128 + c * 16, &g.x);
          dot[0] = fmaf(bf_lo(a[0]), bf_lo(g.x), fmaf(bf_lo(a[1]), bf_lo(g.y), fmaf(bf_lo(a[2]), bf_lo(g.z), fmaf(bf_lo(a[3]), bf_lo(g.w), dot[0]))));
          dot[1] = fmaf(bf_hi(a[0]), bf_hi(g.x), fmaf(bf_hi(a[1]), bf_hi(g.y), fmaf(bf_hi(a[2]), bf_hi(g.z), fmaf(bf_hi(a[3]), bf_hi(g.w), dot[1]))));
        }
      }
      const float gv = 1.f / (1.f + __expf(-(dot[0] + dot[1])));
      sts32(sb + A_GATE + (tid & 127) * 4, __float_as_uint(gv));
      const int tok = 2 * (57 * tile - 7 + r) + par;
      if (hh == 0 && r >= 7 && tok < S_LEN) g_gate[tok] = gv;
      if (tid == 256) sts32(sb + A_BAR + 376, epoch);
      bar_arrive(7, 384);
      bar_sync(3, 128);
      if (tid == 256) {
        count_up(&g_abar[0]);
        wait_count(&g_abar[0], NAUX * (epoch + 1));
        if (cta == 0) *(volatile unsigned*)&g_epoch2 = epoch + 1;
      }
      __syncwarp();
      bar_sync(10, 160);
    }
    if (cta < NH) {
      const int lim = w * 8 + (lane >> 2) - 2 * (lane & 3);
      const uint32_t oa = sb + A_OST + (w * 8 + (lane & 7)) * 128;
      const uint32_t d0 = ((sb + A_IN) & 0x3FFFF) >> 4;
      uint32_t p[5][4];
#pragma unroll
      for (int n = 0; n < 10; n++) p[n >> 1][1 + (n & 1)] = __shfl_sync(0xffffffffu, lane ^ n, n);
#pragma unroll 1
      for (int seg = 0; seg < NSEG; seg++) {
        const float gt = __ldcg(&g_gate[seg * 32 + w * 8 + (lane >> 2)]);
        float d[32];
        mbar_wait(fullq, seg & 1);
        if (tid == 256) SSTAMP(2, seg);
        WG_FENCE();
#pragma unroll
        for (int k = 0; k < 8; k++) {
          const int o = ((k >> 2) * SEGB + (k & 3) * 256) >> 4;
          wgmma_n40_ss_tt(d, desc_at(d0 + o, 128, 512, 0), desc_at(d0 + o + 256, 128, 1024, 0), k > 0);
        }
        WG_COMMIT();
        WG_WAIT(0);
        if (lane == 0) mbar_arrive(emptyq);
        float a[10];
#pragma unroll
        for (int i = 0; i < 10; i++) {
          a[i] = d[(i >> 1) * 4 + (i & 1)] * (SM_SCALE * LOG2E);
          if (i < 8 && (i >> 1) * 8 + (i & 1) > lim) a[i] = -1.0e9f * LOG2E;
        }
        float m = max10(a);
        m = fmaxf(m, __shfl_xor_sync(0xffffffffu, m, 1)); m = fmaxf(m, __shfl_xor_sync(0xffffffffu, m, 2));
#pragma unroll
        for (int i = 0; i < 10; i++) a[i] = ex2(a[i] - m);
#pragma unroll
        for (int n = 0; n < 5; n++) {
          p[n][0] = pack_bf16(a[2 * n], a[2 * n + 1]); p[n][3] = p[n][0] | p[n][1];
          asm volatile("" : "+r"(p[n][0]), "+r"(p[n][3]) :: "memory");
        }
        float sum = ((a[0] + a[1]) + (a[2] + a[3])) + ((a[4] + a[5]) + (a[6] + a[7])) + (a[8] + a[9]);
        sum += __shfl_xor_sync(0xffffffffu, sum, 1);
        if (tid == 256) SSTAMP(3, seg);
        mbar_wait(fullv, seg & 1);
        WG_FENCE();
#pragma unroll
        for (int n = 0; n < 5; n++) wgmma_n64_rs(d, p[n], n < 4 ? desc_at(d0 + SEGB / 8 + 8 * n, 4096, 512, 0) : desc_at(d0 + SEGB / 8 + 512, 1024, 128, 0), n);
        WG_COMMIT();
        sum += __shfl_xor_sync(0xffffffffu, sum, 2);
        const float f = (1.f - gt) * rcp(sum);
        bar_sync(5, 160);
        WG_WAIT(0);
        if (lane == 0) mbar_arrive(emptyv);
        if (tid == 256) SSTAMP(4, seg);
#pragma unroll
        for (int q = 0; q < 4; q++) {
          const float* const o = d + (q & 1) * 16 + (q & 2);
          stsm4(oa + (q >> 1) * 4096 + ((((q & 1) * 4 + (lane >> 3)) ^ (lane & 7)) << 4), pack_bf16(o[0] * f, o[1] * f), pack_bf16(o[4] * f, o[5] * f),
                pack_bf16(o[8] * f, o[9] * f), pack_bf16(o[12] * f, o[13] * f));
        }
        fence_async();
        bar_sync(4, 160);
      }
    }
  } else {
    asm volatile("setmaxnreg.inc.sync.aligned.u32 200;");
    {
      const int g = lane >> 2, t = lane & 3;
      const uint32_t eb = sb + A_EPI + wg * A_EPW, d0 = (sb & 0x3FFFF) >> 4;
      const uint32_t own = (2 * t <= g ? 0xffffu : 0u) | (2 * t < g ? 0xffff0000u : 0u);
      const int kmin = 7 - 57 * tile - 16 * w;
#pragma unroll 1
      for (int c = 0; c < 4; c++) {
        float acc[96], tl[12];
#pragma unroll 1
        for (int r = 0; r < 4; r++) {
#pragma unroll
          for (int st = 0; st < A_NS; st++) {
            const int ks = r * 9 + st;
            if (c == 0 && st % 3 == 0 && ks % 12 == 0) mbar_wait(fullx + 8 * (ks / 12), 0);
            mbar_wait(full1 + 8 * st, r & 1);
            const uint64_t da = desc_at(d0 + wg * (A_XH >> 4) + (ks >> 2) * 512 + (ks & 3) * 2, 16, 1024, 1);
            WG_FENCE();
            wgmma_n192_ss_nt(acc, da, desc_at(d0 + ((A_RING + st * A_WM) >> 4), 2048, 1024, 1), ks);
            if (!(AX & 2)) wgmma_n24_ss_nt(tl, da, desc_at(d0 + ((A_TAIL + st * A_WT) >> 4), 128, 256, 0), ks);
            WG_COMMIT();
            if (st == 0 && r == 2) bar_sync(11 + wg, 160);
            WG_WAIT(1);
            if (ks > 0 && lane == 0) mbar_arrive(empty1 + 8 * ((st + A_NS - 1) % A_NS));
          }
        }
        WG_WAIT(0);
        if (lane == 0) mbar_arrive(empty1 + 8 * (A_NS - 1));
        ASTAMP(16 + c);
        uint32_t ql[9], qh[9], kl[9], kh[9], kx[10], vl[9], vh[9], vx[10];
#pragma unroll
        for (int j = 0; j < 9; j++) {
          const float* const q = j < 8 ? acc + 4 * j : tl, * const k = j < 8 ? acc + 32 + 4 * j : tl + 4, * const v = j < 8 ? acc + 64 + 4 * j : tl + 8;
          kh[j] = pack_bf16(k[2], k[3]); vh[j] = pack_bf16(v[2], v[3]);
          ql[j] = pack_bf16(q[0], q[1]); qh[j] = pack_bf16(q[2], q[3]); kl[j] = pack_bf16(k[0], k[1]); vl[j] = pack_bf16(v[0], v[1]);
        }
        if (w < 3) {
          const uint32_t ha = eb + 1024 + w * 2304 + lane * 16;
          stsm4(ha, kh[0], kh[1], kh[2], kh[3]); stsm4(ha + 512, kh[4], kh[5], kh[6], kh[7]);
          stsm4(ha + 1024, vh[0], vh[1], vh[2], vh[3]); stsm4(ha + 1536, vh[4], vh[5], vh[6], vh[7]);
          asm volatile("stmatrix.sync.aligned.m8n8.x2.shared.b16 [%0], {%1,%2};" :: "r"(ha + 2048), "r"(kh[8]), "r"(vh[8]) : "memory");
        }
        if (c == 0) bar_sync(7, 384); else bar_sync(1 + wg, 128);
        {
          const uint32_t ha = eb + 1024 + max(w - 1, 0) * 2304 + lane * 16;
          ldsm4(kx, ha); ldsm4(kx + 4, ha + 512); ldsm4t(vx, ha + 1024); ldsm4t(vx + 4, ha + 1536);
          asm volatile("ldmatrix.sync.aligned.m8n8.x1.shared.b16 {%0}, [%1];" : "=r"(kx[8]) : "r"(ha + 2048) : "memory");
          asm volatile("ldmatrix.sync.aligned.m8n8.x1.trans.shared.b16 {%0}, [%1];" : "=r"(vx[8]) : "r"(ha + 2176) : "memory");
        }
        const float gl = __uint_as_float(lds32(sb + A_GATE + (wg * 64 + w * 16 + g) * 4)), gh = __uint_as_float(lds32(sb + A_GATE + (wg * 64 + w * 16 + g + 8) * 4));
#pragma unroll
        for (int j = 0; j < 9; j++) { vl[j] = movm(vl[j]); vh[j] = movm(vh[j]); }
        bar_sync(1 + wg, 128);
        uint32_t ol[9], oh[9];
#pragma unroll
        for (int i = 0; i < 4; i++) {
          const int b = 2 * i;
          const uint32_t a[4] = {t >= i ? ql[b] : 0u, t >= i ? qh[b] : 0u, ql[b + 1], qh[b + 1]}, a4 = t <= i ? ql[b + 2] : 0u, a5 = t <= i ? qh[b + 2] : 0u;
          float sx[4], sl[4], sh[4];
          mma16816z(sx, a, kx[b], kx[b + 1]); mma16816z(sl, a, kl[b], kl[b + 1]); mma16816z(sh, a, kh[b], kh[b + 1]);
          mma1688(sx, a4, a5, kx[b + 2]); mma1688(sl, a4, a5, kl[b + 2]); mma1688(sh, a4, a5, kh[b + 2]);
          float e[4];
#pragma unroll
          for (int u = 0; u < 4; u++) {
            const int cc = 2 * t + (u & 1);
            e[u] = (cc <= g ? (u < 2 ? sl[u] : sh[u]) : (u < 2 ? sx[u] : sl[u])) * (0.23570226039551584f * LOG2E);
            if ((cc <= g ? cc : cc - 8) + (u & 2) * 4 < kmin) e[u] = -1.0e9f * LOG2E;
          }
          float m0 = fmaxf(e[0], e[1]), m1 = fmaxf(e[2], e[3]);
#pragma unroll
          for (int o = 1; o < 4; o <<= 1) { m0 = fmaxf(m0, __shfl_xor_sync(0xffffffffu, m0, o)); m1 = fmaxf(m1, __shfl_xor_sync(0xffffffffu, m1, o)); }
          e[0] = ex2(e[0] - m0); e[1] = ex2(e[1] - m0); e[2] = ex2(e[2] - m1); e[3] = ex2(e[3] - m1);
          const uint32_t p0 = pack_bf16(e[0], e[1]), p1 = pack_bf16(e[2], e[3]);
          const uint32_t p[4] = {p0 & ~own, 0u, p0 & own, p1 & ~own};
          float s0 = e[0] + e[1], s1 = e[2] + e[3];
#pragma unroll
          for (int o = 1; o < 4; o <<= 1) { s0 += __shfl_xor_sync(0xffffffffu, s0, o); s1 += __shfl_xor_sync(0xffffffffu, s1, o); }
          const float f0 = gl * rcp(s0), f1 = gh * rcp(s1);
#pragma unroll
          for (int j = b; j < b + 3; j++) {
            float o[4];
            mma16816z(o, p, vx[j], vl[j]);
            mma1688(o, 0u, p1 & own, vh[j]);
            const uint32_t lo = pack_bf16(o[0] * f0, o[1] * f0), hi = pack_bf16(o[2] * f1, o[3] * f1);
            if (j > b || i == 0) { ol[j] = lo; oh[j] = hi; }
            else { ol[j] = t >= i ? lo : ol[j]; oh[j] = t >= i ? hi : oh[j]; }
          }
        }
        const uint32_t sa = eb + 16 + (w * 16 + (lane & 15)) * 144 + (lane >> 4) * 16;
#pragma unroll
        for (int j = 0; j < 8; j += 2) stsm4(sa + j * 16, ol[j], oh[j], ol[j + 1], oh[j + 1]);
        asm volatile("stmatrix.sync.aligned.m8n8.x2.shared.b16 [%0], {%1,%2};" :: "r"(sa + 128), "r"(ol[8]), "r"(oh[8]) : "memory");
        fence_async();
        bar_arrive(13 + wg, 160);
        ASTAMP(20 + c);
      }
    }
    ASTAMP(3);
    uint32_t wa[36][4];
    mbar_wait(fullw, 0);
    const uint32_t la = sb + wg * 73728 + ((lane & 7) + ((lane >> 4) << 3)) * 128 + (((2 * w + ((lane >> 3) & 1)) ^ (lane & 7)) << 4);
#pragma unroll
    for (int k = 0; k < 36; k++) ldsm4t(wa[k], la + k * 2048);
    fence_async();
    bar_sync(6, 288);
    ASTAMP(4);
    float own[4] = {0.f, 0.f, 0.f, 0.f};
    uint4 v[3];
    auto fetch = [&](int seg) {
      const uint4* src = g_part + (((seg & 3) * 36 + cta) * 4) * 128 + (tid & 127);
#pragma unroll
      for (int j = 0; j < 3; j++) v[j] = ldg_relaxed(src + ((kq + 1 + j) & 3) * 128);
    };
    auto finish = [&](int seg) {
      const uint32_t tagv = ((seg >> 2) + 1) & 3;
      int n = 0;
#pragma unroll 1
      while (__any_sync(0xffffffffu, (v[0].x & 3) != tagv || (v[1].x & 3) != tagv || (v[2].x & 3) != tagv) && ++n < SPIN_LIMIT) {
        if (seg < NSEG - 1) __nanosleep(200);
        fetch(seg);
      }
#pragma unroll
      for (int j = 0; j < 3; j++) {
        own[0] += __uint_as_float(v[j].x & ~3u); own[1] += __uint_as_float(v[j].y); own[2] += __uint_as_float(v[j].z); own[3] += __uint_as_float(v[j].w);
      }
      uint32_t p0 = pack_bf16(own[0], own[1]), p1 = pack_bf16(own[2], own[3]);
      asm volatile("movmatrix.sync.aligned.m8n8.trans.b16 %0, %0;" : "+r"(p0));
      asm volatile("movmatrix.sync.aligned.m8n8.trans.b16 %0, %0;" : "+r"(p1));
      uint32_t* o = (uint32_t*)(out + (size_t)(seg * 32 + kq * 8 + (lane >> 2)) * DM + nsl * 64 + w * 16) + (lane & 3);
      o[0] = p0; o[4] = p1;
    };
    float acc[16];
    auto stream = [&](int sl, int keep) {
      const uint64_t db = make_desc(sb + sl * XT, 16, 1024, 1);
      WG_FENCE();
#pragma unroll
      for (int k = 0; k < 36; k++) wgmma_n32_rs(acc, wa[k][0], wa[k][1], wa[k][2], wa[k][3], db + (k >> 2) * 256 + (k & 3) * 2, k ? 1 : keep);
      WG_COMMIT();
    };
    const uint32_t ex = sb + A_EX + (tid & 127) * 16;
    if (wg == 0) {
#pragma unroll
      for (int i = 0; i < 16; i++) acc[i] = 0.f;
#pragma unroll 1
      for (int seg = 0; seg < NSEG; seg++) {
        const int sl = (seg & 1) * 2;
        mbar_wait(full3 + 8 * sl, (seg >> 1) & 1);
        if (kq == 3) {
          const uint64_t da = make_desc(sb + A_XW, 8192, 1024, 1), de = make_desc(sb + A_XT + (seg & 1) * 4096, 16, 1024, 1);
          WG_FENCE();
#pragma unroll
          for (int j = 0; j < 4; j++) wgmma_n32_ss_tn(acc, da + j * 128, de + j * 2, j);
          WG_COMMIT();
          WG_WAIT(0);
        }
        stream(sl, kq == 3);
        bar_arrive(9, 256);
        WG_WAIT(0);
        if (lane == 0) mbar_arrive(empty3 + 8 * sl);
#pragma unroll
        for (int i = 0; i < 4; i++)
          sts128(ex + (seg & 1) * 8192 + i * 2048, __float_as_uint(acc[4 * i]), __float_as_uint(acc[4 * i + 1]), __float_as_uint(acc[4 * i + 2]), __float_as_uint(acc[4 * i + 3]));
        bar_sync(1, 256);
      }
    } else {
#pragma unroll 1
      for (int seg = 0; seg < NSEG; seg++) {
        const int sl = (seg & 1) * 2 + 1;
        mbar_wait(full3 + 8 * sl, (seg >> 1) & 1);
        if (tid == 128) SSTAMP(6, seg);
        bar_sync(9, 256);
        stream(sl, 0);
        bar_sync(1, 256);
        fetch(max(seg - 1, 0));
        WG_WAIT(0);
        if (lane == 0) mbar_arrive(empty3 + 8 * sl);
        float nxt[4] = {0.f, 0.f, 0.f, 0.f};
        uint4* dst = g_part + (((seg & 3) * 36 + nsl * 4) * 4 + kq) * 128 + (tid & 127);
#pragma unroll
        for (int j = 0; j < 4; j++) {
          float o[4];
          lds128f(ex + (seg & 1) * 8192 + j * 2048, o);
#pragma unroll
          for (int i = 0; i < 4; i++) { o[i] += acc[4 * j + i]; if (j == kq) nxt[i] = o[i]; }
          if (j != kq) stg_relaxed(dst + j * 512, (__float_as_uint(o[0]) & ~3u) | (((seg >> 2) + 1) & 3), __float_as_uint(o[1]), __float_as_uint(o[2]), __float_as_uint(o[3]));
        }
        if (tid == 128) SSTAMP(7, seg);
        if (seg > 0) finish(seg - 1);
        if (tid == 128) SSTAMP(8, seg);
#pragma unroll
        for (int i = 0; i < 4; i++) own[i] = nxt[i];
        if ((seg & 7) == 6) ASTAMP(5 + (seg >> 3));
      }
      fetch(NSEG - 1);
      finish(NSEG - 1);
    }
    ASTAMP(13);
    bar_sync(6, 288);
  }
}

typedef CUresult (*EncodeFn)(CUtensorMap*, CUtensorMapDataType, cuuint32_t, void*, const cuuint64_t*, const cuuint64_t*,
                             const cuuint32_t*, const cuuint32_t*, CUtensorMapInterleave, CUtensorMapSwizzle,
                             CUtensorMapL2promotion, CUtensorMapFloatOOBfill);
static void make_map(EncodeFn enc, CUtensorMap* m, const void* p, int rows, int cols, int box_rows) {
  cuuint64_t dims[2] = {(cuuint64_t)cols, (cuuint64_t)rows};
  cuuint64_t strides[1] = {(cuuint64_t)cols * 2};
  cuuint32_t box[2] = {64, (cuuint32_t)box_rows};
  cuuint32_t es[2] = {1, 1};
  enc(m, CU_TENSOR_MAP_DATA_TYPE_BFLOAT16, 2, (void*)p, dims, strides, box, es, CU_TENSOR_MAP_INTERLEAVE_NONE,
      CU_TENSOR_MAP_SWIZZLE_128B, CU_TENSOR_MAP_L2_PROMOTION_L2_128B, CU_TENSOR_MAP_FLOAT_OOB_FILL_NONE);
}

constexpr int g_poll = POLL_NS;
extern "C" void kernel_launch(void* const* d_in, const int* in_sizes, int n_in, void* d_out, int out_size) {
  const bf16* x = (const bf16*)d_in[0];
  const bf16* wqkvA = (const bf16*)d_in[1];
  const bf16* woA = (const bf16*)d_in[2];
  const bf16* mem0 = (const bf16*)d_in[4];
  const bf16* Wq = (const bf16*)d_in[5];
  const bf16* Wk = (const bf16*)d_in[6];
  const bf16* Wv = (const bf16*)d_in[7];
  const bf16* Wo = (const bf16*)d_in[8];
  const bf16* gate_w = (const bf16*)d_in[10];
  static EncodeFn enc = nullptr;
  static void *pO = nullptr, *pR = nullptr;
  if (!enc) {
    cudaDriverEntryPointQueryResult qr;
    cudaGetDriverEntryPoint("cuTensorMapEncodeTiled", (void**)&enc, cudaEnableDefault, &qr);
    cudaGetSymbolAddress(&pO, g_Ocat);
    cudaGetSymbolAddress(&pR, g_red_raw);
    cudaFuncSetAttribute(rec_kernel, cudaFuncAttributeMaxDynamicSharedMemorySize, SM_TOTAL);
    cudaFuncSetAttribute(aux_kernel, cudaFuncAttributeMaxDynamicSharedMemorySize, A_TOTAL);
  }
  RMaps rm;
  rm.poll = g_poll;
  rm.w[0] = (const char*)Wq; rm.w[1] = (const char*)Wk; rm.w[2] = (const char*)Wv; rm.w[3] = (const char*)Wo;
  rm.red = (unsigned char*)(((uintptr_t)pR + 262143) & ~(uintptr_t)262143);
  {
    cuuint64_t dims[3] = {64, S_LEN, 9}, strides[2] = {DM * 2, 128};
    cuuint32_t box[3] = {64, 32, 9}, es[3] = {1, 1, 1};
    enc(&rm.x, CU_TENSOR_MAP_DATA_TYPE_BFLOAT16, 3, (void*)x, dims, strides, box, es, CU_TENSOR_MAP_INTERLEAVE_NONE,
        CU_TENSOR_MAP_SWIZZLE_128B, CU_TENSOR_MAP_L2_PROMOTION_L2_128B, CU_TENSOR_MAP_FLOAT_OOB_FILL_NONE);
  }
  make_map(enc, &rm.wq, Wq, DM, 4096, 192);
  make_map(enc, &rm.wk, Wk, DM, 4096, 192);
  make_map(enc, &rm.wv, Wv, DM, 4096, 192);
  make_map(enc, &rm.wo, Wo, 4096, DM, 128);
  AMaps am;
  {
    cuuint32_t es[4] = {1, 1, 1, 1};
    cuuint64_t dx[4] = {64, 2, S_LEN / 2, 9}, sx[3] = {DM * 2, DM * 4, 128};
    cuuint32_t bx[4] = {64, 1, 64, 3};
    enc(&am.x, CU_TENSOR_MAP_DATA_TYPE_BFLOAT16, 4, (void*)x, dx, sx, bx, es, CU_TENSOR_MAP_INTERLEAVE_NONE,
        CU_TENSOR_MAP_SWIZZLE_128B, CU_TENSOR_MAP_L2_PROMOTION_L2_128B, CU_TENSOR_MAP_FLOAT_OOB_FILL_NONE);
    cuuint64_t dw[3] = {DM, DM, 3}, sw[2] = {DM * 6, DM * 2};
    cuuint32_t bw[3] = {64, 16, 3}, bt[3] = {8, 16, 3};
    enc(&am.wa, CU_TENSOR_MAP_DATA_TYPE_BFLOAT16, 3, (void*)wqkvA, dw, sw, bw, es, CU_TENSOR_MAP_INTERLEAVE_NONE,
        CU_TENSOR_MAP_SWIZZLE_128B, CU_TENSOR_MAP_L2_PROMOTION_L2_128B, CU_TENSOR_MAP_FLOAT_OOB_FILL_NONE);
    enc(&am.wt, CU_TENSOR_MAP_DATA_TYPE_BFLOAT16, 3, (void*)wqkvA, dw, sw, bt, es, CU_TENSOR_MAP_INTERLEAVE_NONE,
        CU_TENSOR_MAP_SWIZZLE_NONE, CU_TENSOR_MAP_L2_PROMOTION_NONE, CU_TENSOR_MAP_FLOAT_OOB_FILL_NONE);
    cuuint64_t dz[3] = {KCAT, 2, S_LEN / 2}, sz[2] = {KCAT * 2, KCAT * 4};
    cuuint32_t bz[3] = {72, 1, 57};
    enc(&am.oa, CU_TENSOR_MAP_DATA_TYPE_BFLOAT16, 3, pO, dz, sz, bz, es, CU_TENSOR_MAP_INTERLEAVE_NONE,
        CU_TENSOR_MAP_SWIZZLE_NONE, CU_TENSOR_MAP_L2_PROMOTION_NONE, CU_TENSOR_MAP_FLOAT_OOB_FILL_NONE);
  }
  {
    cuuint64_t dims[3] = {64, S_LEN, KCAT / 64}, strides[2] = {KCAT * 2, 128};
    cuuint32_t box[3] = {64, 32, 9}, es[3] = {1, 1, 1};
    make_map(enc, &am.o, pO, S_LEN, KCAT, 32);
    enc(&am.o3, CU_TENSOR_MAP_DATA_TYPE_BFLOAT16, 3, pO, dims, strides, box, es, CU_TENSOR_MAP_INTERLEAVE_NONE,
        CU_TENSOR_MAP_SWIZZLE_128B, CU_TENSOR_MAP_L2_PROMOTION_L2_128B, CU_TENSOR_MAP_FLOAT_OOB_FILL_NONE);
  }
  make_map(enc, &am.wob, Wo, 4096, DM, 64);
  make_map(enc, &am.woa, woA, DM, DM, 64);

  rec_kernel<<<96, 384, SM_TOTAL, cudaStreamPerThread>>>(rm, x, mem0);
  cudaLaunchConfig_t cfg = {};
  cfg.gridDim = dim3(NAUX); cfg.blockDim = dim3(512); cfg.dynamicSmemBytes = A_TOTAL; cfg.stream = cudaStreamPerThread;
  cudaLaunchAttribute at[1];
  at[0].id = cudaLaunchAttributeProgrammaticStreamSerialization; at[0].val.programmaticStreamSerializationAllowed = 1;
  cfg.attrs = at; cfg.numAttrs = 1;
  if (XP & 16) cfg.numAttrs = 0;
  if (!(XP & 64)) cudaLaunchKernelEx(&cfg, aux_kernel, am, wqkvA, gate_w, (bf16*)d_out);
}
```

```cpp
#include <cuda_runtime.h>
#include <cuda_bf16.h>
#include <cuda_fp16.h>
#include <cuda.h>
#include <stdint.h>

typedef __nv_bfloat16 bf16;

constexpr int S_LEN = 2048, DM = 576, NH = 32, DH = 128, NSEG = 64, KCAT = 4096 + 576;
#define RED_LINE(i) (((i) >> 2) * 4096 + ((i) & 1) * 256 + ((i) & 2) * 512)
#define RED_SLOT(s) (((s) & 1) * 128 + ((s) & 2) * 256)

#define POLL_NS 896
#define NII 18
#define W3PRE 4
#define W3MID 4
#define GF 0
#define B5POS 0
#define NUP 4
#define UPF 1
#define B3Q 9
#define B3F 0
#define GATE 7
#define NTL 2
#define B7R 1
#define EXPOS 6
#define VW2 1
#define CLR 1
#define RFW 0
#define NIC 0
#define LEAD 0
#define FIN16 1
#define VXG 0
#define NRING 20
#define EXB 0
#define EXD 0
#define EXB2 8192
#define HDLY 0
#define F10 1
#define NPROBE 2
#define QM 0
#define N5 (EXB ? 256 : 224)
#define KP(i) (((i) >> 1) + 4 * ((i) & 1))
#define SPIN_LIMIT (1 << 14)
#define XP 0

__device__ __align__(1024) bf16 g_Ocat[S_LEN * KCAT];
__device__ __align__(1024) unsigned char g_red_raw[2 * 262144];
constexpr int HINT_OFF = 2048;
__device__ __align__(16) float g_gate[S_LEN];
__device__ __align__(128) uint4 g_stats[96 * 2];
__device__ unsigned g_epoch;
__device__ unsigned g_epoch2;
__device__ unsigned g_ocnt[NSEG * 32];
__device__ unsigned g_abar[3 * 32];
__device__ unsigned g_pace[32];
__device__ unsigned g_scnt[NSEG * 32 * 8];
__device__ __align__(1024) unsigned char g_seg[NRING * 96 * 10240];
__device__ unsigned g_used[NH * 32];
__device__ __align__(1024) uint4 g_part[4 * 36 * 4 * 128];
__device__ int g_err;
#define PROF(idx)
#define PROFP(idx)
#define STAMP(idx)
#define ASTAMP(idx)
#define SSTAMP(k, seg)
#define WSTAMP(idx)

#define DI __device__ __forceinline__
DI uint32_t smem_u32(const void* p) { return (uint32_t)__cvta_generic_to_shared(p); }
DI uint32_t clock32() { uint32_t c; asm volatile("mov.u32 %0, %%clock;" : "=r"(c) :: "memory"); return c; }
DI uint32_t gtime() { uint32_t c; asm volatile("mov.u32 %0, %%globaltimer_lo;" : "=r"(c) :: "memory"); return c; }
DI uint32_t ldg_relaxed32(const void* p) { uint32_t v; asm volatile("ld.relaxed.gpu.global.b32 %0, [%1];" : "=r"(v) : "l"(p) : "memory"); return v; }
DI uint32_t ldg_acquire32(const void* p) { uint32_t v; asm volatile("ld.acquire.gpu.global.b32 %0, [%1];" : "=r"(v) : "l"(p) : "memory"); return v; }
DI void stg_relaxed32(void* p, uint32_t v) { asm volatile("st.relaxed.gpu.global.b32 [%0], %1;" :: "l"(p), "r"(v) : "memory"); }
DI int head_id() { int c; asm volatile("mov.u32 %0, %%clusterid.x;" : "=r"(c)); return c; }
DI uint32_t mapa(uint32_t a, uint32_t r) { uint32_t o; asm("mapa.shared::cluster.u32 %0, %1, %2;" : "=r"(o) : "r"(a), "r"(r)); return o; }
DI void cluster_arrive() { asm volatile("barrier.cluster.arrive.relaxed.aligned;" ::: "memory"); }
DI void cluster_wait() { asm volatile("barrier.cluster.wait.aligned;" ::: "memory"); }
DI void cluster_sync() { asm volatile("barrier.cluster.arrive.release.aligned;\nbarrier.cluster.wait.acquire.aligned;" ::: "memory"); }
DI void mbar_init(uint32_t b, uint32_t c) { asm volatile("mbarrier.init.shared::cta.b64 [%0], %1;" :: "r"(b), "r"(c) : "memory"); }
DI void mbar_expect(uint32_t b, uint32_t tx) { asm volatile("mbarrier.arrive.expect_tx.shared::cta.b64 _, [%0], %1;" :: "r"(b), "r"(tx) : "memory"); }
DI void mbar_arrive(uint32_t b) { asm volatile("mbarrier.arrive.shared::cta.b64 _, [%0];" :: "r"(b) : "memory"); }
DI void mbar_wait(uint32_t b, uint32_t par) {
  asm volatile("{\n.reg .pred p;\n.reg .u32 n, q;\nmov.u32 n, 0;\n"
               "WL: add.u32 n, n, 1;\nshr.u32 q, n, 12;\nxor.b32 q, q, %1;\n"
               "mbarrier.try_wait.parity.shared::cta.b64 p, [%0], q;\n@!p bra.uni WL;\n}"
               :: "r"(b), "r"(par) : "memory");
}
DI void wait_until(uint32_t t) {
  const uint32_t now = gtime();
  t = min(t, now + 8192);
  asm volatile("{\n.reg .pred p;\n.reg .u32 c;\nTL: mov.u32 c, %%globaltimer_lo;\nsetp.lt.u32 p, c, %0;\n@p bra.uni TL;\n}" :: "r"(t) : "memory");
}
#define PIN(v) v = __shfl_xor_sync(0xffffffffu, v, 0)
#define SCHED_FENCE(k) asm volatile("{\n.reg .pred p;\nsetp.eq.u32 p, %0, %1;\n@p exit;\n}" :: "r"(fence_reg), "r"(k) : "memory")
#define MEM_ORDER(k) asm volatile("{\n.reg .pred p;\nsetp.eq.u32 p, %0, %1;\n@p st.shared.u32 [%0], %0;\n}" :: "r"(fence_reg), "r"(k + 64) : "memory")
DI void bar_sync(int id, int n) { asm volatile("bar.sync %0, %1;" :: "r"(id), "r"(n) : "memory"); }
DI void bar_arrive(int id, int n) { asm volatile("bar.arrive %0, %1;" :: "r"(id), "r"(n) : "memory"); }
DI void fence_async() { asm volatile("fence.proxy.async.shared::cta;" ::: "memory"); }
DI void st_async4(uint32_t a, uint32_t x, uint32_t y, uint32_t z, uint32_t w, uint32_t mb) {
  asm volatile("st.async.weak.shared::cluster.mbarrier::complete_tx::bytes.v4.b32 [%0], {%1,%2,%3,%4}, [%5];"
               :: "r"(a), "r"(x), "r"(y), "r"(z), "r"(w), "r"(mb) : "memory");
}
DI void st_async2(uint32_t a, uint32_t x, uint32_t y, uint32_t mb) {
  asm volatile("st.async.weak.shared::cluster.mbarrier::complete_tx::bytes.v2.b32 [%0], {%1,%2}, [%3];"
               :: "r"(a), "r"(x), "r"(y), "r"(mb) : "memory");
}
DI void sts32(uint32_t a, uint32_t x) { asm volatile("st.shared.b32 [%0], %1;" :: "r"(a), "r"(x) : "memory"); }
DI void sts64(uint32_t a, uint32_t x, uint32_t y) { asm volatile("st.shared.v2.b32 [%0], {%1,%2};" :: "r"(a), "r"(x), "r"(y) : "memory"); }
DI void sts128(uint32_t a, uint32_t x, uint32_t y, uint32_t z, uint32_t w) {
  asm volatile("st.shared.v4.b32 [%0], {%1,%2,%3,%4};" :: "r"(a), "r"(x), "r"(y), "r"(z), "r"(w) : "memory");
}
DI uint32_t lds32(uint32_t a) { uint32_t x; asm volatile("ld.shared.b32 %0, [%1];" : "=r"(x) : "r"(a) : "memory"); return x; }
DI void lds64(uint32_t a, uint32_t& x, uint32_t& y) { asm volatile("ld.shared.v2.b32 {%0,%1}, [%2];" : "=r"(x), "=r"(y) : "r"(a) : "memory"); }
DI void lds128(uint32_t a, uint32_t* r) {
  asm volatile("ld.shared.v4.b32 {%0,%1,%2,%3}, [%4];" : "=r"(r[0]), "=r"(r[1]), "=r"(r[2]), "=r"(r[3]) : "r"(a) : "memory");
}
DI void lds128f(uint32_t a, float* r) {
  asm volatile("ld.shared.v4.f32 {%0,%1,%2,%3}, [%4];" : "=f"(r[0]), "=f"(r[1]), "=f"(r[2]), "=f"(r[3]) : "r"(a) : "memory");
}
DI void lds64f(uint32_t a, float* r) { asm volatile("ld.shared.v2.f32 {%0,%1}, [%2];" : "=f"(r[0]), "=f"(r[1]) : "r"(a) : "memory"); }
DI void ldsm4t(uint32_t* r, uint32_t a) {
  asm volatile("ldmatrix.sync.aligned.m8n8.x4.trans.shared.b16 {%0,%1,%2,%3}, [%4];"
               : "=r"(r[0]), "=r"(r[1]), "=r"(r[2]), "=r"(r[3]) : "r"(a) : "memory");
}
DI void ldsm4t_in(uint32_t* r, uint32_t a, uint32_t t) {
  asm volatile("{\n.reg .pred p;\nsetp.ne.u32 p, %5, 0;\n@p ldmatrix.sync.aligned.m8n8.x4.trans.shared.b16 {%0,%1,%2,%3}, [%4];\n}"
               : "+r"(r[0]), "+r"(r[1]), "+r"(r[2]), "+r"(r[3]) : "r"(a), "r"(t) : "memory");
}
DI void lds128_in(uint32_t* r, uint32_t a, uint32_t t) {
  asm volatile("{\n.reg .pred p;\nsetp.ne.u32 p, %5, 0;\n@p ld.shared.v4.b32 {%0,%1,%2,%3}, [%4];\n}"
               : "+r"(r[0]), "+r"(r[1]), "+r"(r[2]), "+r"(r[3]) : "r"(a), "r"(t) : "memory");
}
DI void ldsm2t_in(uint32_t* r, uint32_t a, uint32_t t) {
  asm volatile("{\n.reg .pred p;\nsetp.ne.u32 p, %3, 0;\n@p ldmatrix.sync.aligned.m8n8.x2.trans.shared.b16 {%0,%1}, [%2];\n}" : "+r"(r[0]), "+r"(r[1]) : "r"(a), "r"(t) : "memory");
}
DI void reserve2(uint32_t* r) { asm volatile("{\n.reg .u64 t;\nmov.u64 t, %%clock64;\nmov.b64 {%0, %1}, t;\n}" : "=r"(r[0]), "=r"(r[1])); }
DI void scale_sum(float& x, float& y, float s, uint32_t t) {
  asm volatile("{\n.reg .pred p;\nsetp.ne.u32 p, %2, 0;\n@p mul.f32 %0, %0, %1;\n}" : "+f"(y) : "f"(s), "r"(t));
  asm volatile("{\n.reg .pred p;\nsetp.ne.u32 p, %3, 1;\n@p fma.rn.f32 %0, %0, %1, %2;\n}" : "+f"(x) : "f"(s), "f"(y), "r"(t));
}
DI void ldsm4(uint32_t* r, uint32_t a) {
  asm volatile("ldmatrix.sync.aligned.m8n8.x4.shared.b16 {%0,%1,%2,%3}, [%4];"
               : "=r"(r[0]), "=r"(r[1]), "=r"(r[2]), "=r"(r[3]) : "r"(a) : "memory");
}
DI void st_async1(uint32_t a, uint32_t x, uint32_t mb) {
  asm volatile("st.async.weak.shared::cluster.mbarrier::complete_tx::bytes.b32 [%0], %1, [%2];" :: "r"(a), "r"(x), "r"(mb) : "memory");
}
DI void stsm4(uint32_t a, uint32_t x, uint32_t y, uint32_t z, uint32_t w) {
  asm volatile("stmatrix.sync.aligned.m8n8.x4.shared.b16 [%0], {%1,%2,%3,%4};" :: "r"(a), "r"(x), "r"(y), "r"(z), "r"(w) : "memory");
}
DI void stsm4t(uint32_t a, uint32_t x, uint32_t y, uint32_t z, uint32_t w) {
  asm volatile("stmatrix.sync.aligned.m8n8.x4.trans.shared.b16 [%0], {%1,%2,%3,%4};" :: "r"(a), "r"(x), "r"(y), "r"(z), "r"(w) : "memory");
}
DI uint32_t pack_bf16(float lo, float hi) { uint32_t r; asm("cvt.rn.bf16x2.f32 %0, %1, %2;" : "=r"(r) : "f"(hi), "f"(lo)); return r; }
DI uint32_t pack_f16(float lo, float hi) { uint32_t r; asm("cvt.rn.f16x2.f32 %0, %1, %2;" : "=r"(r) : "f"(hi), "f"(lo)); return r; }
DI float ex2(float x) { float y; asm("ex2.approx.ftz.f32 %0, %1;" : "=f"(y) : "f"(x)); return y; }
DI float rcp(float x) { float y; asm("rcp.approx.ftz.f32 %0, %1;" : "=f"(y) : "f"(x)); return y; }
DI float bf_lo(uint32_t x) { return __uint_as_float(x << 16); }
DI float bf_hi(uint32_t x) { return __uint_as_float(x & 0xffff0000u); }
DI void mma16816(float* d, const uint32_t* a, uint32_t b0, uint32_t b1) {
  asm volatile("mma.sync.aligned.m16n8k16.row.col.f32.bf16.bf16.f32 {%0,%1,%2,%3}, {%4,%5,%6,%7}, {%8,%9}, {%0,%1,%2,%3};"
               : "+f"(d[0]), "+f"(d[1]), "+f"(d[2]), "+f"(d[3]) : "r"(a[0]), "r"(a[1]), "r"(a[2]), "r"(a[3]), "r"(b0), "r"(b1));
}
DI void mma16816z(float* d, const uint32_t* a, uint32_t b0, uint32_t b1) {
  asm volatile("mma.sync.aligned.m16n8k16.row.col.f32.bf16.bf16.f32 {%0,%1,%2,%3}, {%4,%5,%6,%7}, {%8,%9}, {%10,%10,%10,%10};"
               : "=f"(d[0]), "=f"(d[1]), "=f"(d[2]), "=f"(d[3]) : "r"(a[0]), "r"(a[1]), "r"(a[2]), "r"(a[3]), "r"(b0), "r"(b1), "f"(0.f));
}
DI void mma1688z(float* d, uint32_t a0, uint32_t a1, uint32_t b0) {
  asm volatile("mma.sync.aligned.m16n8k8.row.col.f32.bf16.bf16.f32 {%0,%1,%2,%3}, {%4,%5}, {%6}, {%7,%7,%7,%7};"
               : "=f"(d[0]), "=f"(d[1]), "=f"(d[2]), "=f"(d[3]) : "r"(a0), "r"(a1), "r"(b0), "f"(0.f));
}
DI void mma1688(float* d, uint32_t a0, uint32_t a1, uint32_t b0) {
  asm volatile("mma.sync.aligned.m16n8k8.row.col.f32.bf16.bf16.f32 {%0,%1,%2,%3}, {%4,%5}, {%6}, {%0,%1,%2,%3};"
               : "+f"(d[0]), "+f"(d[1]), "+f"(d[2]), "+f"(d[3]) : "r"(a0), "r"(a1), "r"(b0));
}
DI void ldsm2t(uint32_t* r, uint32_t a) {
  asm volatile("ldmatrix.sync.aligned.m8n8.x2.trans.shared.b16 {%0,%1}, [%2];" : "=r"(r[0]), "=r"(r[1]) : "r"(a) : "memory");
}
DI uint32_t add_bf16(uint32_t a, uint32_t b) { uint32_t r; asm("add.rn.bf16x2 %0, %1, %2;" : "=r"(r) : "r"(a), "r"(b)); return r; }
DI uint32_t mul_bf16(uint32_t a, uint32_t b) { uint32_t r; asm("mul.rn.bf16x2 %0, %1, %2;" : "=r"(r) : "r"(a), "r"(b)); return r; }
DI uint64_t make_desc(uint32_t addr, uint32_t lbo, uint32_t sbo, uint32_t swz) {
  return (uint64_t)((addr & 0x3FFFF) >> 4) | ((uint64_t)(lbo >> 4) << 16) | ((uint64_t)(sbo >> 4) << 32) | ((uint64_t)swz << 62);
}
DI uint64_t desc_at(uint32_t a16, uint32_t lbo, uint32_t sbo, uint32_t swz) {
  uint64_t d; asm("mov.b64 %0, {%1, %2};" : "=l"(d) : "r"(a16 + ((lbo >> 4) << 16)), "r"((sbo >> 4) | (swz << 30)));
  return d;
}
#define WG_FENCE() asm volatile("wgmma.fence.sync.aligned;" ::: "memory")
#define WG_COMMIT() asm volatile("wgmma.commit_group.sync.aligned;" ::: "memory")
#define WG_WAIT(n) asm volatile("wgmma.wait_group.sync.aligned %0;" :: "n"(n) : "memory")
#define ACC8(d, o) "+f"(d[o]), "+f"(d[o + 1]), "+f"(d[o + 2]), "+f"(d[o + 3]), "+f"(d[o + 4]), "+f"(d[o + 5]), "+f"(d[o + 6]), "+f"(d[o + 7])
DI void wgmma_n32_rs(float* d, uint32_t a0, uint32_t a1, uint32_t a2, uint32_t a3, uint64_t db, int acc) {
  asm volatile("{\n.reg .pred p;\nsetp.ne.b32 p, %21, 0;\n"
               "wgmma.mma_async.sync.aligned.m64n32k16.f32.bf16.bf16 {%0,%1,%2,%3,%4,%5,%6,%7,%8,%9,%10,%11,%12,%13,%14,%15}, "
               "{%16,%17,%18,%19}, %20, p, 1, 1, 0;\n}\n"
               : ACC8(d, 0), ACC8(d, 8) : "r"(a0), "r"(a1), "r"(a2), "r"(a3), "l"(db), "r"(acc));
}
template <int TA>
DI void wgmma_n32_ss(float* d, uint64_t da, uint64_t db, int acc) {
  asm volatile("{\n.reg .pred p;\nsetp.ne.b32 p, %18, 0;\n"
               "wgmma.mma_async.sync.aligned.m64n32k16.f32.bf16.bf16 {%0,%1,%2,%3,%4,%5,%6,%7,%8,%9,%10,%11,%12,%13,%14,%15}, "
               "%16, %17, p, 1, 1, %19, 1;\n}\n"
               : ACC8(d, 0), ACC8(d, 8) : "l"(da), "l"(db), "r"(acc), "n"(TA));
}
DI void tma_load(uint32_t dst, const CUtensorMap* m, int c0, int c1, uint32_t mb) {
  asm volatile("cp.async.bulk.tensor.2d.shared::cluster.global.mbarrier::complete_tx::bytes [%0], [%1, {%3, %4}], [%2];"
               :: "r"(dst), "l"(m), "r"(mb), "r"(c0), "r"(c1) : "memory");
}
DI void tma_load3(uint32_t dst, const CUtensorMap* m, int row, uint32_t mb) {
  asm volatile("cp.async.bulk.tensor.3d.shared::cluster.global.mbarrier::complete_tx::bytes [%0], [%1, {%3, %4, %3}], [%2];"
               :: "r"(dst), "l"(m), "r"(mb), "r"(0), "r"(row) : "memory");
}
DI bool elect_one() {
  uint32_t p;
  asm volatile("{\n.reg .pred p;\nelect.sync _|p, 0xffffffff;\nselp.u32 %0, 1, 0, p;\n}" : "=r"(p));
  return p;
}
DI void bulk_s2s(uint32_t dst, uint32_t src, uint32_t bytes, uint32_t mb) {
  asm volatile("cp.async.bulk.shared::cluster.shared::cta.mbarrier::complete_tx::bytes [%0], [%1], %2, [%3];"
               :: "r"(dst), "r"(src), "r"(bytes), "r"(mb) : "memory");
}
DI void tma_prefetch(const CUtensorMap* m, int c0, int c1) {
  asm volatile("cp.async.bulk.prefetch.tensor.2d.L2.global.tile [%0, {%1, %2}];" :: "l"(m), "r"(c0), "r"(c1) : "memory");
}
DI void tma_store(const CUtensorMap* m, uint32_t src, int c0, int c1) {
  asm volatile("cp.async.bulk.tensor.2d.global.shared::cta.bulk_group [%0, {%2, %3}], [%1];" :: "l"(m), "r"(src), "r"(c0), "r"(c1) : "memory");
}
DI uint4 ldg_relaxed(const void* p) {
  uint4 v;
  asm volatile("ld.relaxed.gpu.global.v4.b32 {%0,%1,%2,%3}, [%4];" : "=r"(v.x), "=r"(v.y), "=r"(v.z), "=r"(v.w) : "l"(p) : "memory");
  return v;
}
DI void stg_relaxed(void* p, uint32_t x, uint32_t y, uint32_t z, uint32_t w) {
  asm volatile("st.relaxed.gpu.global.v4.b32 [%0], {%1,%2,%3,%4};" :: "l"(p), "r"(x), "r"(y), "r"(z), "r"(w) : "memory");
}
DI void red_f16x8(void* p, uint32_t x, uint32_t y, uint32_t z, uint32_t w) {
  asm volatile("red.relaxed.gpu.global.add.noftz.v4.f16x2 [%0], {%1,%2,%3,%4};" :: "l"(p), "r"(x), "r"(y), "r"(z), "r"(w) : "memory");
}
DI void sq_acc(uint32_t& a, uint32_t x) { asm("fma.rn.bf16x2 %0, %1, %1, %0;" : "+r"(a) : "r"(x)); }
DI __half2 amax4(__half2 h, const uint32_t* v) {
  h = __hmax2_nan(__hmax2_nan(h, __habs2(*(const __half2*)&v[0])), __habs2(*(const __half2*)&v[1]));
  return __hmax2_nan(__hmax2_nan(h, __habs2(*(const __half2*)&v[2])), __habs2(*(const __half2*)&v[3]));
}
DI uint32_t wexp(__half2 h) { const uint32_t u = *(const uint32_t*)&h; return __reduce_max_sync(0xffffffffu, max((u >> 16) & 0x7fffu, u & 0x7fffu)) >> 7; }
DI float max10(const float* a) {
  return fmaxf(fmaxf(fmaxf(fmaxf(a[0], a[1]), fmaxf(a[2], a[3])), fmaxf(fmaxf(a[4], a[5]), fmaxf(a[6], a[7]))), fmaxf(a[8], a[9]));
}
DI float quad_max(float m) {
  return fmaxf(fmaxf(m, __shfl_xor_sync(0xffffffffu, m, 1)), fmaxf(__shfl_xor_sync(0xffffffffu, m, 2), __shfl_xor_sync(0xffffffffu, m, 3)));
}
DI float warp_sum(float v) {
#pragma unroll
  for (int o = 16; o; o >>= 1) v += __shfl_xor_sync(0xffffffffu, v, o);
  return v;
}

constexpr int SM_WO3 = 0;
constexpr int SM_X = 16384;
constexpr int XT = 36864;
constexpr int SM_EXP = 126976;
constexpr int SEGB = 10240;
constexpr int SM_BLK = SM_EXP + 8192;
constexpr int SM_VC = SM_BLK + 4 * SEGB;
constexpr int SM_PART = SM_VC + 16384;
constexpr int SM_QM = SM_PART + 4096;
constexpr int SM_E = SM_QM + 1024;
constexpr int SM_VM = SM_E + 1536;
constexpr int SM_OB = SM_VM + 2048;
constexpr int SM_FB = SM_OB + 2048;
constexpr int SM_STAGE = SM_X + XT;
constexpr int SM_MISC = 210944;
constexpr int SM_WOST = 212992;
constexpr int SM_MEM = SM_WOST;
constexpr int SM_MAX = SM_MEM + 11264;
#define MEM_BLK(q) ((q) / 3 * 4096 + (q) % 3 * 1024)
constexpr int SM_TOTAL = 229376;
constexpr int MB_W = SM_MISC;
constexpr int MB_WO = SM_MISC + 24;
constexpr int MB_WO3 = SM_MISC + 32;
constexpr int MB_X = SM_MISC + 40;
constexpr int MB_S = SM_MISC + 64;
constexpr int MB_F = SM_MISC + 72;
constexpr int MB_VX = SM_MISC + 80;
constexpr int SC_FPAR = SM_MISC + 136;
constexpr int SC_DEAD = SM_MISC + 96;
constexpr int SC_UNSC = SM_MISC + 112;
constexpr int SC_EPOCH = SM_MISC + 128;
constexpr int SC_EXPW = SM_MISC + 132;
constexpr int SC_ONES = SM_MISC + 144;
constexpr int SC_SS = SM_MISC + 160;
constexpr int SC_LAT = SM_MISC + 224;
constexpr int SC_XMAX = SM_MISC + 256;
constexpr int SC_PROF = 229376;

constexpr float SM_SCALE = 0.08838834764831845f;
constexpr float LOG2E = 1.4426950408889634f;
constexpr float E_LIM = 20.f;

template <bool B> struct BoolC { static constexpr bool value = B; };
struct RMaps { CUtensorMap x, wq, wk, wv, wo; unsigned char* red; uint32_t poll; };

DI uint32_t latest_hint(uint32_t h, uint32_t d, int s) {
  const uint32_t x = (((h | 0xc0c0c0c0u) - ((d >> 5) & 63) * 0x01010101u) & 0x3f3f3f3fu) | ((h ^ (((s >> 2) + 1) & 3) * 0x40404040u) & 0xc0c0c0c0u);
  const uint32_t y = __vmaxu2(x & 0x00ff00ffu, (x >> 8) & 0x00ff00ffu);
  return __reduce_max_sync(0xffffffffu, max(y & 0xffffu, y >> 16));
}
DI uint32_t near_half(uint32_t sb) {
  uint32_t a, b; lds64(sb + SC_LAT, a, b);
  return a > b;
}

template <int RT, int K0, int K1, bool D32 = false>
DI void xproj(float* acc, const uint32_t (&wa)[2][18][4], uint64_t xd) {
  if (XP & 1) return;
  WG_FENCE();
#pragma unroll
  for (int k = K0; k < ((XP & 128) ? K0 + 1 : K1); k++)
  {
    uint64_t d = xd + (uint64_t)(((k >> 1) * 4096 + (k & 1) * 32) >> 4);
    if (D32) asm("mov.b64 %0, {%1, %2};" : "=l"(d) : "r"((uint32_t)xd + (((k >> 1) * 4096 + (k & 1) * 32) >> 4)), "r"((uint32_t)(xd >> 32)));
    wgmma_n32_rs(acc, wa[RT][k][0], wa[RT][k][1], wa[RT][k][2], wa[RT][k][3], d, k != 0);
  }
  WG_COMMIT();
}

DI void seg_store(int seg, uint32_t sb, uint32_t off, uint32_t bytes) {
  asm volatile("cp.async.bulk.global.shared::cta.bulk_group [%0], [%1], %2;"
               :: "l"(g_seg + ((size_t)(seg % NRING) * 96 + blockIdx.x) * SEGB + off), "r"(sb + SM_BLK + (seg & 3) * SEGB + off), "r"(bytes) : "memory");
  asm volatile("cp.async.bulk.commit_group;" ::: "memory");
}
DI void seg_publish(int seg) {
  asm volatile("cp.async.bulk.wait_group 0;" ::: "memory");
  asm volatile("red.relaxed.gpu.global.add.u32 [%0], 1;" :: "l"(&g_scnt[(seg * 32 + blockIdx.x / 3) * 8]) : "memory");
  SSTAMP(10, seg);
}

#define PACE 1200
#define PORD 0
DI void load_weights(uint32_t sb, const RMaps& tm, uint32_t rank, int c) {
  const int h = blockIdx.x / 3;
  if (c < 3) {
    mbar_expect(sb + MB_W + 8 * c, 49152);
    tma_load(sb + SM_STAGE + c * 49152, rank < 2 ? &tm.wk : &tm.wv, h * DH + (rank == 1 ? 64 : 0), c * 192, sb + MB_W + 8 * c);
    tma_load(sb + SM_STAGE + c * 49152 + 24576, rank < 2 ? &tm.wq : &tm.wv, h * DH + (rank == 0 ? 0 : 64), c * 192, sb + MB_W + 8 * c);
  } else {
    tma_prefetch(&tm.wo, rank * 192, h * DH);
    mbar_expect(sb + MB_WO, 16384);
    mbar_expect(sb + MB_WO3, 32768);
    tma_load(sb + SM_WOST, &tm.wo, rank * 192 + 64, h * DH, sb + MB_WO3);
    tma_load(sb + SM_WO3, &tm.wo, rank * 192 + 128, h * DH, sb + MB_WO3);
  }
}

DI void proj_role(const uint32_t sb, const RMaps& tm, const uint32_t rank, const int wg, const int w, const int lane) {
  const bool qk = rank < 2;
  uint32_t wa[2][18][4];
  {
    const int rr = (lane & 7) + ((lane >> 4) << 3);
    const uint32_t col = ((2 * w + ((lane >> 3) & 1)) ^ (lane & 7)) << 4;
    float ss = 0.f;
#pragma unroll
    for (int c = 0; c < 3; c++) {
      mbar_wait(sb + MB_W + 8 * c, 0);
      if (threadIdx.x == 0) SSTAMP(11, c);
#pragma unroll
      for (int rt = 0; rt < 2; rt++)
#pragma unroll
        for (int k = 0; k < 6; k++)
          ldsm4t(wa[rt][c * 6 + k], sb + SM_STAGE + c * 49152 + (rt ^ wg) * 24576 + (64 * (k >> 1) + 32 * wg + 16 * (k & 1) + rr) * 128 + col);
      if (c < 2) {
        fence_async();
        bar_sync(3, 256);
        if (threadIdx.x == 0) {
          if (c == 0) tma_load3(sb + SM_X + XT, &tm.x, 32, sb + MB_X + 8);
          else { tma_load(sb + SM_X + 2 * XT, &tm.wo, rank * 192, (blockIdx.x / 3) * DH, sb + MB_WO); SSTAMP(11, 11); }
        }
        __syncwarp();
      }
      uint32_t q[4] = {0, 0, 0, 0};
#pragma unroll
      for (int rt = 0; rt < 2; rt++)
#pragma unroll
        for (int k = 0; k < 6; k++)
#pragma unroll
          for (int i = 0; i < 4; i++) sq_acc(q[i], wa[rt][c * 6 + k][i]);
#pragma unroll
      for (int i = 0; i < 4; i++) ss += bf_lo(q[i]) + bf_hi(q[i]);
    }
    ss = warp_sum(ss);
    fence_async();
    cluster_arrive();
    if (lane == 0) sts32(sb + SC_SS + 4 * (wg * 4 + w), qk ? 0 : __float_as_uint(ss));
    bar_arrive(11, 384);
  }
  STAMP(1);
  mbar_wait(sb + MB_X, 0);
  STAMP(2);

  uint32_t t16 = sb + (w * 32 + lane) * 16;
  uint32_t mem_a = sb + SM_MEM + wg * 512 + lane * 16;
  uint32_t fin_a = sb + (lane & 7) * 16 + SM_BLK + (qk ? (wg ^ 1) * 4096 + w * 256 + (lane & 8) * 16 + (lane & 16) * 64
                                              : wg * 4096 + w * 1024 + (lane & 8) * 64 + (lane & 16) * 8);
  PIN(t16); PIN(mem_a); PIN(fin_a);
  const uint32_t fence_reg = mem_a;
  const uint32_t fin2 = qk ? 2048 : 256;
  float acc[16];
  const uint64_t xd0 = make_desc(sb + SM_X + wg * 64, 16, 1024, 1);
  auto do_export = [&]() {
    WG_WAIT(0);
#pragma unroll
    for (int i = 0; i < 2; i++)
      sts128(t16 + SM_EXP + wg * 4096 + i * 2048, pack_bf16(acc[8 * i], acc[8 * i + 1]), pack_bf16(acc[8 * i + 2], acc[8 * i + 3]),
             pack_bf16(acc[8 * i + 4], acc[8 * i + 5]), pack_bf16(acc[8 * i + 6], acc[8 * i + 7]));
  };
  uint32_t o[8];
  auto import = [&]() { lds128(t16 + SM_EXP + (wg ^ 1) * 4096, o); lds128(t16 + SM_EXP + (wg ^ 1) * 4096 + 2048, o + 4); };
  auto finish = [&](int seg) {
    const uint32_t a = fin_a + (seg & 3) * SEGB;
    WG_WAIT(0);
#pragma unroll
    for (int i = 0; i < 8; i++) o[i] = FIN16 ? add_bf16(pack_bf16(acc[2 * i], acc[2 * i + 1]), o[i]) : pack_bf16(acc[2 * i] + bf_lo(o[i]), acc[2 * i + 1] + bf_hi(o[i]));
    stsm4(a, o[0], o[1], o[2], o[3]);
    stsm4(a + fin2, o[4], o[5], o[6], o[7]);
  };
  auto send_v = [&](int seg, int dst) {
    fence_async();
    if (seg < NSEG - 1 && !(XP & 2) && elect_one())
      bulk_s2s(mapa(sb + SM_VC + (seg & 1) * 8192, dst), sb + SM_BLK + (seg & 3) * SEGB, 8192, mapa(sb + MB_VX + (seg & 1) * 8, dst));
    __syncwarp();
  };
  auto wait_v = [&](int seg) {
    if (seg < NSEG - 1 && !(XP & 2)) {
      mbar_wait(sb + MB_VX + (seg & 1) * 8, (seg >> 1) & 1);
      if (elect_one()) mbar_expect(sb + MB_VX + (seg & 1) * 8, 8192);
      __syncwarp();
    }
  };
  bar_sync(3, 256);
  xproj<1, 0, 18>(acc, wa, xd0);
  do_export();
  SCHED_FENCE(11);
  xproj<0, 0, 18>(acc, wa, xd0);
  bar_sync(3, 256);
  if (threadIdx.x == 0) SSTAMP(11, 12);
  cluster_wait();
  if (threadIdx.x == 0) SSTAMP(11, 13);
  mbar_wait(sb + MB_X + 8, 0);
  import();
  finish(0);
  SCHED_FENCE(12);
  bar_sync(3, 256);
  uint64_t dA = xd0 + (XT >> 4);
  xproj<1, 0, 18>(acc, wa, dA);
  if (!qk && wg == 0 && w < 2) send_v(0, w);
  do_export();
  if (qk && wg == 0 && w == 0) wait_v(0);
  bar_arrive(13, 384);
  if (!qk) {
    SCHED_FENCE(15);
    xproj<0, 0, 18>(acc, wa, dA);
    if (threadIdx.x == 0 && !(XP & 8)) { mbar_expect(sb + MB_X, XT); tma_load3(sb + SM_X, &tm.x, 96, sb + MB_X); }
    bar_sync(3, 256);
    mbar_wait(sb + MB_X + 16, 0);
    import();
    finish(1);
    SCHED_FENCE(16);
    bar_sync(3, 256);
    dA += XT >> 4;
    xproj<1, 0, 18>(acc, wa, dA);
    if (wg == 0 && w < VW2) send_v(1, w);
    do_export();
  }
  if (threadIdx.x == 0) SSTAMP(11, 14);
  bar_sync(0, 384);
  const int ro = __shfl_sync(0xffffffffu, near_half(sb) ^ wg, 0);
  STAMP(5);
  const uint32_t always = __shfl_sync(0xffffffffu, lds32(sb + SC_DEAD + 12), 0);
  const int ah = qk ? 1 : 2;
  int b2 = qk ? 2 : 0;
  int s = 0;
  uint32_t hint_lo = (uint32_t)(uint64_t)tm.red + HINT_OFF + blockIdx.x + (lane & 1) * 4096 + (lane >> 1) * 16384;
  PIN(hint_lo);
  auto post_hint = [&]() {
    asm volatile("{\n.reg .pred p;\n.reg .b64 a;\n.reg .u32 t;\nsetp.lt.u32 p, %0, %1;\nmov.b64 a, {%2, %3};\nmov.u32 t, %%globaltimer_lo;\n"
                 "bfe.u32 t, t, 5, 6;\nor.b32 t, t, %4;\n@p st.relaxed.gpu.global.u8 [a], t;\n}"
                 :: "r"(t16), "r"(sb + 128), "r"(hint_lo + RED_SLOT(s)), "r"((uint32_t)((uint64_t)tm.red >> 32)), "r"(((s >> 2) + 1) << 6) : "memory");
  };
  auto memproj = [&](auto second, int id, float u0, float u1, float* r) {
    constexpr bool R1 = decltype(second)::value;
    uint32_t b[NUP][4], b0[4];
    SCHED_FENCE(id);
    bar_sync(R1 ? 2 : 1, 256);
    PROF(0);
    ldsm4t(b0, mem_a);
#pragma unroll
    for (int q = 0; q < NUP; q++) {
      if (R1 && q == 2) {
        bar_sync(11, 256);
        SCHED_FENCE(id + 1);
      }
      ldsm4t(b[q], mem_a + MEM_BLK(q + 1));
    }
    mma16816z(&acc[0], wa[0][0], b0[0], b0[1]);
    mma16816z(&acc[4], wa[1][0], b0[0], b0[1]);
    mma16816z(&acc[8], wa[0][1], b0[2], b0[3]);
    mma16816z(&acc[12], wa[1][1], b0[2], b0[3]);
#pragma unroll
    for (int q = 1; q < 9; q++) {
      uint32_t* const c = b[(q - 1) % NUP];
      mma16816(&acc[0], wa[0][2 * q], c[0], c[1]);
      mma16816(&acc[4], wa[1][2 * q], c[0], c[1]);
      mma16816(&acc[8], wa[0][2 * q + 1], c[2], c[3]);
      mma16816(&acc[12], wa[1][2 * q + 1], c[2], c[3]);
      if (R1 && q + NUP == B3Q) bar_sync(3, 256);
      if (q + NUP < 9) ldsm4t_in(c, mem_a + MEM_BLK(q + NUP), always);
      else if (R1 && q + NUP < 11) lds128_in(c, t16 + SM_PART + (10 - q - NUP) * 2048, always);
      else if (!R1 && GATE && q == GATE) { bar_arrive(11, 256); lds128_in(c, sb + SC_DEAD, always); u0 = u1 = __uint_as_float(c[3]); }
    }
#pragma unroll
    for (int i = 0; i < 8; i++) {
      const float u = i < 4 ? u0 : u1;
      r[i] = R1 ? fmaf(acc[8 + i], u, (acc[i] + __uint_as_float(b[(8 + i / 4) % NUP][i & 3])) * u) : (GATE ? fmaf(acc[i], u, acc[8 + i]) : acc[i] + acc[8 + i]);
    }
  };
  if (ro == 0) {
#pragma unroll 1
    while (true) {
      if (s == 8) STAMP(6);
      float r[8];
      memproj(BoolC<false>(), 30, 0.f, 0.f, r);
      sts128(t16 + SM_PART, __float_as_uint(r[0]), __float_as_uint(r[1]), __float_as_uint(r[2]), __float_as_uint(r[3]));
      sts128(t16 + SM_PART + 2048, __float_as_uint(r[4]), __float_as_uint(r[5]), __float_as_uint(r[6]), __float_as_uint(r[7]));
      bar_arrive(3, 256);
      PROF(1);
      bar_sync(9, 256);
      if (s == NSEG - 1) break;
      post_hint();
      if (w == 1) {
        uint32_t m[8];
        lds128(t16 + SM_MAX - 512, m); lds128(t16 + SM_MAX, m + 4);
        const int em = (wexp(amax4(amax4(*(const __half2*)&m[0], m), m + 4)) >> 3) + (int)(lds32(sb + SC_UNSC + (s & 1) * 8) >> 23) - 15;
        const int ex = max(s ? em : 0, (int)lds32(sb + SC_XMAX + 4 * s)) - 127 + (int)lds32(sb + SC_EXPW);
        sts32(sb + SC_UNSC + (~s & 1) * 8, (127 + min(max(ex, -120), 120)) << 23);
        __syncwarp();
        if (elect_one()) mbar_arrive(sb + MB_S);
      }
      SCHED_FENCE(9);
      bar_sync(5, qk ? N5 : 256);
      PROF(2);
      import();
      xproj<0, 0, NII>(acc, wa, dA);
      if (NII < 18) {
        if (qk) bar_sync(7, 384);
        xproj<0, NII, 18>(acc, wa, dA);
        if (!qk) bar_sync(7, 384);
      } else {
        if (F10) WG_WAIT(0);
        bar_sync(10, 256);
        if (F10) SCHED_FENCE(17);
      }
      dA += (int64_t)(b2 ? XT >> 4 : -(XT >> 3));
      finish(s + ah);
      if (qk || w >= VW2) bar_arrive(13, 384);
      PROF(6);
      SCHED_FENCE(14);
      bar_sync(12, 256);
      PROF(7);
      xproj<1, 0, 18, true>(acc, wa, dA);
      bar_arrive(14, 256);
      b2 = b2 == 2 ? 0 : b2 + 1;
      s++;
      if (!qk && w < VW2) { bar_sync(13, 384); send_v(s + 1, w); }
      PROFP(8);
      do_export();
      PROFP(3);
    }
    if (!qk) bar_arrive(5, 256);
  } else {
#pragma unroll 1
    while (true) {
      if (s == 8) STAMP(6);
      const uint32_t tl = ((t16 >> 8) ^ wg) & 1, am = (t16 & ~256u) - w * 256;
      const float un = __uint_as_float(lds32(sb + SC_UNSC + (s & 1) * 8));
      float r[8];
      if (qk) {
        uint32_t a0 = am + (tl ? SM_QM : SM_BLK + 8192 + (s & 3) * SEGB);
        float u0 = wg ? un * (SM_SCALE * LOG2E) : un, u1 = wg ? un : un * (SM_SCALE * LOG2E);
        PIN(a0); PIN(u0); PIN(u1);
        memproj(BoolC<true>(), 32, u0, u1, r);
        stsm4(a0, pack_bf16(r[0], r[1]), pack_bf16(r[2], r[3]), pack_bf16(r[4], r[5]), pack_bf16(r[6], r[7]));
        bar_arrive(4, 256);
      } else {
        const uint32_t d0 = s < NSEG - 1 ? 0 : 2, d1 = s < NSEG - 1 ? 1 : 2;
        uint32_t r0 = mapa(t16 + SM_VM, d0), r1 = mapa(t16 + SM_VM, d1);
        PIN(r0); PIN(r1);
        memproj(BoolC<true>(), 34, un, un, r);
        const uint32_t p0 = pack_bf16(r[0], r[1]), p1 = pack_bf16(r[2], r[3]), p2 = pack_bf16(r[4], r[5]), p3 = pack_bf16(r[6], r[7]);
        const uint32_t v0 = wg ? p2 : p0, v1 = wg ? p3 : p1, v2 = wg ? p0 : p2, v3 = wg ? p1 : p3;
        st_async4(r0, v0, v1, v2, v3, mapa(sb + MB_S, d0));
        st_async4(r1, v0, v1, v2, v3, mapa(sb + MB_S, d1));
        bar_arrive(5, 256);
        if (EXB && s < NSEG - 1) bar_arrive(15, 160);
        sts128(t16 + SM_VM, v0, v1, v2, v3);
        stsm4(am + SM_BLK + 8192 + (s & 3) * SEGB + tl * 1024, p0, p1, p2, p3);
        __syncwarp();
        if (elect_one()) mbar_arrive(sb + MB_S);
        if (EXPOS >= 5 && s < NSEG - 1) bar_arrive(15, 160);
      }
      if (s == NSEG - 1) break;
      PROF(1);
      auto rearm = [&]() { mbar_wait(sb + MB_S, s & 1); if (elect_one()) mbar_expect(sb + MB_S, qk ? 640 + 2048 : 1280); __syncwarp(); };
      if (w == 1) {
        if ((t16 & 384) == 0) stg_relaxed(tm.red + (RED_SLOT(s + 2) + RED_LINE(blockIdx.x)) + (t16 & 112), 0, 0, 0, 0);
      } else if (w == 0) {
        const int tn = s + ah + 1;
        if (RFW) mbar_wait(sb + MB_S, s & 1);
        if (tn + 1 < NSEG && !(XP & 8) && elect_one()) {
          const int b0 = b2 == 2 ? 0 : b2 + 1;
          mbar_expect(sb + MB_X + 8 * b0, XT);
          tma_load3(sb + SM_X + b0 * XT, &tm.x, (tn + 1) * 32, sb + MB_X + 8 * b0);
        }
        if (tn < NSEG && (!(XP & 8) || tn < 3)) mbar_wait(sb + MB_X + 8 * b2, (tn / 3) & 1);
      } else if (w == 2) {
        if (!qk) { if (VW2 < 1) send_v(s + 1, 0); if (VW2 < 2) send_v(s + 1, 1); }
      } else if (qk || !NIC) {
        rearm();
      }
      __syncwarp();
      import();
      PROF(4);
      SCHED_FENCE(10);
      if (NIC) {
        if (qk) bar_sync(7, NII < 18 ? 384 : 256);
        xproj<0, 0, NIC>(acc, wa, dA);
        if (!qk) { if (w == 3) rearm(); bar_sync(7, NII < 18 ? 384 : 256); }
      } else {
        bar_sync(7, NII < 18 ? 384 : 256);
      }
      xproj<0, NIC, 18>(acc, wa, dA);
      bar_arrive(12, 256);
      dA += (int64_t)(b2 ? XT >> 4 : -(XT >> 3));
      finish(s + ah);
      if (qk && w == 0) wait_v(s + 1);
      bar_arrive(13, 384);
      PROF(6);
      SCHED_FENCE(13);
      bar_sync(14, 256);
      PROF(7);
      xproj<1, 0, 18>(acc, wa, dA);
      b2 = b2 == 2 ? 0 : b2 + 1;
      s++;
      PROFP(8);
      do_export();
      PROFP(3);
    }
  }
  bar_arrive(0, 384);
  STAMP(3);
  cluster_sync();
  STAMP(4);
}

DI void attn_role(const uint32_t sb, unsigned char* smem_raw, const RMaps& tm, const uint32_t RANK, const bf16* __restrict__ x, const bf16* __restrict__ mem0,
                  const int w, const int lane) {
  const int t2 = w * 32 + lane;
  uint32_t wo[8][4], w1[8][4];
  const uint32_t wo_lane = sb + ((lane & 7) + ((lane >> 4) << 3)) * 128 + (((w + 4 * ((lane >> 3) & 1)) ^ (lane & 7)) << 4);
  unsigned char* const g_red = tm.red;
  {
    const uint32_t tag = *(volatile unsigned*)&g_epoch + 1;
    if (w == 0) {
      stg_relaxed(g_red + RED_SLOT(t2 >> 3) + RED_LINE(blockIdx.x) + (t2 & 7) * 16, 0, 0, 0, 0);
      asm volatile("st.relaxed.gpu.global.u8 [%0], 0;" :: "l"(g_red + RED_SLOT(t2) + HINT_OFF + (t2 & 4) * 1024 + (t2 >> 3) * 16384 + blockIdx.x) : "memory");
    }
    uint4 xv[18];
    uint32_t mv[20];
#pragma unroll
    for (int i = 0; i < 20; i++) mv[i] = i < 18 ? ((const uint32_t*)mem0)[(lane >> 2) * (DM / 2) + (w * 18 + i) * 4 + (lane & 3)] : 0;
#pragma unroll
    for (int i = 0; i < 18; i++) xv[i] = blockIdx.x < NSEG ? ((const uint4*)(x + blockIdx.x * 32 * DM))[t2 + 128 * i] : make_uint4(0, 0, 0, 0);
    bar_sync(0, 384);
    cluster_arrive();
    if (PACE && w == 3) {
      const uint32_t t0 = gtime();
#pragma unroll 1
      for (int c = 1; c < 4; c++) {
        wait_until(t0 + c * PACE);
        if (elect_one()) load_weights(sb, tm, RANK, PORD ? (c == 1 ? 3 : c - 1) : c);
        __syncwarp();
      }
    }
    __half2 hx = __float2half2_rn(0.f);
#pragma unroll
    for (int i = 0; i < 18; i++) hx = amax4(hx, &xv[i].x);
    if (blockIdx.x == 0)
#pragma unroll
      for (int i = 0; i < 5; i++) hx = amax4(hx, &mv[4 * i]);
    sts32(sb + SC_SS + 4 * (12 + w), wexp(hx));
    if (t2 == 0) { sts32(sb + SC_EPOCH, (tag - 1) * NSEG + 2 - NRING); sts32(sb + SC_UNSC, __float_as_uint(1.f)); sts128(sb + SC_DEAD, 0, 0, 0, 0x3f800000u); sts64(sb + SC_FPAR, 0, 0); sts128(sb + SC_ONES, 0x3f803f80u, 0x3f803f80u, 0x3f803f80u, 0x3f803f80u); }
    WSTAMP(27);
    if (w == 0) __threadfence();
    uint32_t q[8] = {0, 0, 0, 0, 0, 0, 0, 0};
    mbar_wait(sb + MB_WO3, 0);
    if (t2 == 0) SSTAMP(11, 3);
#pragma unroll
    for (int k = 0; k < 8; k++) {
      ldsm4t(wo[k], wo_lane + SM_WO3 + k * 2048); ldsm4t(w1[k], wo_lane + SM_WOST + k * 2048);
#pragma unroll
      for (int i = 0; i < 4; i++) { sq_acc(q[i], wo[k][i]); sq_acc(q[i], w1[k][i]); }
    }
    bar_sync(6, 128);
    if (t2 == 0) SSTAMP(11, 7);
#pragma unroll
    for (int k = 0; k < 8; k++) sts128(sb + SM_WO3 + t2 * 16 + k * 2048, wo[k][0], wo[k][1], wo[k][2], wo[k][3]);
#pragma unroll
    for (int i = 0; i < 5; i++) {
      const int j = w * 18 + 4 * i + (lane >> 3), c = i < 4 || lane < 16 ? j * 8 + j / 24 * 64 : 192;
      stsm4t(sb + SM_MEM + (c + (lane & 7)) * 16, mv[4 * i], mv[4 * i + 1], mv[4 * i + 2], mv[4 * i + 3]);
    }
    bar_arrive(1, 256); bar_arrive(2, 256); bar_arrive(9, 256);
    if (t2 == 0) SSTAMP(11, 8);
    mbar_wait(sb + MB_WO, 0);
    if (t2 == 0) SSTAMP(11, 4);
#pragma unroll
    for (int k = 0; k < 8; k++) ldsm4t(wo[k], wo_lane + SM_X + 2 * XT + k * 2048);
    fence_async();
    bar_sync(6, 128);
    if (t2 == 32) tma_load3(sb + SM_X + 2 * XT, &tm.x, 64, sb + MB_X + 16);
    __syncwarp();
#pragma unroll
    for (int k = 0; k < 8; k++)
#pragma unroll
      for (int i = 0; i < 4; i++) sq_acc(q[4 + i], wo[k][i]);
    float ss = 0.f;
#pragma unroll
    for (int i = 0; i < 8; i++) ss += bf_lo(q[i]) + bf_hi(q[i]);
    ss = warp_sum(ss);
    if (lane == 0) sts32(sb + SC_SS + 4 * (8 + w), __float_as_uint(ss));
    if (t2 == 0) SSTAMP(11, 9);
    bar_sync(11, 384);
    if (t2 == 0) SSTAMP(11, 10);
    if (t2 == 0) {
      float a[16];
#pragma unroll
      for (int i = 0; i < 4; i++) lds128f(sb + SC_SS + 16 * i, &a[4 * i]);
      stg_relaxed(&g_stats[blockIdx.x * 2], __float_as_uint(((a[0] + a[1]) + (a[2] + a[3])) + ((a[4] + a[5]) + (a[6] + a[7]))),
                  __float_as_uint((a[8] + a[9]) + (a[10] + a[11])),
                  max(max(__float_as_uint(a[12]), __float_as_uint(a[13])), max(__float_as_uint(a[14]), __float_as_uint(a[15]))), tag);
    }
    __syncwarp();
    WSTAMP(24);
    cluster_wait();
    if (w == 0) {
      uint4 v[3];
      int n = 0;
      while (true) {
#pragma unroll
        for (int i = 0; i < 3; i++) v[i] = ldg_relaxed(&g_stats[(i * 32 + lane) * 2]);
        if (__all_sync(0xffffffffu, v[0].w == tag && v[1].w == tag && v[2].w == tag) || ++n > SPIN_LIMIT) break;
        __nanosleep(100);
      }
      WSTAMP(25);
      const float sv = warp_sum(__uint_as_float(v[0].x) + __uint_as_float(v[1].x) + __uint_as_float(v[2].x));
      const float so = warp_sum(__uint_as_float(v[0].y) + __uint_as_float(v[1].y) + __uint_as_float(v[2].y));
      const int expW = ((int)(__float_as_uint(sv) >> 23) + (int)(__float_as_uint(so) >> 23) - 254 + 2 + 10 + 1) >> 1;
      sts32(sb + SC_XMAX + 4 * lane, v[0].z); sts32(sb + SC_XMAX + 128 + 4 * lane, v[1].z);
      sts32(sb + SC_EXPW, expW + 1 - 15);
      if (blockIdx.x == 0 && lane == 0) *(volatile unsigned*)&g_epoch = tag;
      sts32(sb + SC_FPAR + 4, 1);
    } else if (w < 3) {
      const uint32_t u = blockIdx.x >> 4;
      unsigned char* const z = g_red + 98304 + (blockIdx.x & 15) * 128 + (u & 1) * 2048 + (u & 6) * 4096 + (((u >> 1) ^ w) & 1) * 4096 + lane * 4;
      stg_relaxed32(z, 0);
      uint32_t best = 0xffffffffu;
#pragma unroll 1
      for (int i = 0; i < 64; i++) {
        uint32_t last, dt;
        asm volatile("{\n.reg .pred p;\n.reg .u32 c, v;\nld.volatile.shared.u32 %0, [%3];\nmov.u32 c, %%clock;\n"
                     "atom.relaxed.gpu.global.exch.b32 v, [%2], 0;\nsetp.eq.u32 p, v, 0;\nmov.u32 %1, 0;\n@p mov.u32 %1, %%clock;\nsub.u32 %1, %1, c;\n}"
                     : "=r"(last), "=r"(dt) : "l"(z), "r"(sb + SC_FPAR + 4) : "memory");
        best = min(best, dt);
        if (last && i >= NPROBE - 1) break;
      }
      sts32(sb + SC_LAT + (w - 1) * 4, best);
    }
    bar_sync(13, 384);
    bar_arrive(0, 384);
    WSTAMP(26);
  }

  const uint32_t nh = __shfl_sync(0xffffffffu, near_half(sb), 0);
  uint32_t l16 = sb + lane * 16;
  PIN(l16);
#define LV ((l16 >> 4) & 31)
#define fence_reg l16
  const uint32_t red_lo = (uint32_t)(uint64_t)g_red, red_hi = (uint32_t)((uint64_t)g_red >> 32);
  uint32_t lp;
  auto slot = [&](int s, uint32_t c, uint32_t ofs) {
    const uint32_t lo = lp | (red_lo + ((w >> 1) * 4 + (w & 1) * 2 + ((w ^ c) & 1)) * 4096 + RED_SLOT(s) + ofs);
    uint64_t a; asm("mov.b64 %0, {%1, %2};" : "=l"(a) : "r"(lo), "r"(red_hi));
    return (unsigned char*)a;
  };
  const uint32_t always = __shfl_sync(0xffffffffu, lds32(sb + SC_DEAD + 12), 0);
  const int mode0 = RANK < 2 ? w : w | 4;
  auto hint_addr = [&](int s) { return min(LV, 23u) * 4 + (red_lo + HINT_OFF + nh * 4096 + w * 16384 + RED_SLOT(s)); };
  auto load_hints = [&](uint32_t lo) {
    uint64_t a; asm("mov.b64 %0, {%1, %2};" : "=l"(a) : "r"(lo), "r"(red_hi));
    return ldg_relaxed32((const void*)a);
  };
  const uint32_t blk = RANK < 2 ? 9216 : SEGB, exb = RANK < 2 ? EXB : EXB2;
  auto export_rest = [&](int seg) { if (EXB && !(XP & 4) && elect_one()) seg_store(seg, sb, exb, blk - exb); __syncwarp(); };
  auto export_seg = [&](int seg) {
    if (!(XP & 4) && elect_one()) {
      if (seg > 0) seg_publish(seg - 1);
      fence_async();
      seg_store(seg, sb, 0, EXB ? exb : blk);
    }
    __syncwarp();
  };
  uint32_t dl = __shfl_sync(0xffffffffu, gtime() - 768, 0);
  int s = 0;
  bool bad = false;
#pragma unroll 1
  while (true) {
    const uint32_t par = s & 1;
    uint32_t vx[4][4], hints;
    auto load_vx = [&]() {
      const uint32_t va = l16 + (RANK < 2 ? SM_VC + par * 8192 : SM_BLK + (s & 3) * SEGB) + w * 1024 + ((LV >> 3) & 1) * 384 - (LV >> 4) * 128;
#pragma unroll
      for (int i = 0; i < 4; i++) ldsm4(vx[i], va + (i & 1) * 4096 + (i >> 1) * 256);
    };
    auto retire = [&](uint32_t x) {
      asm volatile("{\n.reg .pred p;\nsetp.eq.u32 p, %0, 0;\n@p exit;\n}" :: "r"(vx[0][0] | vx[1][0] | vx[2][0] | vx[3][0] | x) : "memory");
    };
    auto scores = [&](auto memkeys, auto first, float* sc) {
      constexpr bool MK = decltype(memkeys)::value, FIRST = decltype(first)::value;
      uint32_t kb[4][4], qb[2][4];
      const uint32_t m = LV >> 3;
      uint32_t kaddr = l16 + SM_BLK + 4096 + (s & 3) * SEGB + w * 2048 + (m & 1) * (MK ? 128 : 896) - (m >> 1) * 128;
      if (MK) { PIN(kaddr); }
      else {
#pragma unroll
        for (int k = 0; k < 4; k++) ldsm4t(kb[k], kaddr + k * 256);
      }
      if (FIRST) { load_vx(); retire(MK ? kaddr : kb[0][0] | kb[1][0] | kb[2][0] | kb[3][0] | l16); bar_sync(4, 256); PROF(4); }
      ldsm4t(qb[0], l16 + SM_QM);
      if (MK) ldsm4t(kb[0], kaddr);
      ldsm4t(qb[1], l16 + SM_QM + 512);
      if (MK) ldsm4t(kb[2], kaddr + 512);
      float c[4][4];
      mma16816z(c[0], kb[0], qb[0][0], qb[0][1]); mma16816z(c[1], kb[MK ? 0 : 1], qb[0][2], qb[0][3]);
      mma16816z(c[2], kb[2], qb[1][0], qb[1][1]); mma16816z(c[3], kb[MK ? 2 : 3], qb[1][2], qb[1][3]);
      if (FIRST && B5POS == 0) bar_arrive(5, N5);
#pragma unroll
      for (int i = 0; i < (MK ? 2 : 4); i++) sc[i] = ((c[0][i] + c[1][MK ? i + 2 : i]) + c[2][i]) + c[3][MK ? i + 2 : i];
    };
    auto send = [&](auto memkeys) {
      constexpr bool MK = decltype(memkeys)::value;
      constexpr int N = MK ? 1 : 2;
      const uint32_t sa = sb + LV * 4 + SM_E + (MK ? 1024 + RANK * 128 : RANK * 512 + w * 256);
      uint32_t ra[N][2], mb[N][2];
#pragma unroll
      for (int i = 0; i < N; i++)
#pragma unroll
        for (int j = 0; j < 2; j++) {
          ra[i][j] = mapa(sa + i * 128, j ? 2 : RANK ^ 1); mb[i][j] = mapa(sb + MB_S, j ? 2 : RANK ^ 1);
          PIN(ra[i][j]);
        }
      float sc[4];
      scores(memkeys, BoolC<true>(), sc);
      uint32_t e[N];
#pragma unroll
      for (int i = 0; i < N; i++) {
        e[i] = pack_bf16(ex2(sc[2 * i]), ex2(sc[2 * i + 1]));
        if (!(fmaxf(fabsf(sc[2 * i]), fabsf(sc[2 * i + 1])) <= E_LIM)) e[i] = 0x7fff7fffu;
        st_async1(ra[i][0], e[i], mb[i][0]);
        st_async1(ra[i][1], e[i], mb[i][1]);
      }
#pragma unroll
      for (int i = 0; i < N; i++) sts32(sa + i * 128, e[i]);
      __syncwarp();
      if (l16 == sb) mbar_arrive(sb + MB_S);
      PROF(5);
    };
    const int mode = bad ? 8 : mode0;
    if (mode < 2) {
      send(BoolC<false>());
    } else if (mode == 2) {
      send(BoolC<true>());
    } else if (mode == 8) {
      load_vx();
      retire(l16);
      const uint32_t fp = lds32(sb + SC_FPAR);
      bar_sync(6, 128);
      if (w == 0 && l16 == sb) { sts32(sb + SC_FPAR, fp ^ 1); mbar_expect(sb + MB_F, 3072); }
      if (RANK < 2 && w < 3) {
        float sc[4] = {0.f, 0.f, 0.f, 0.f};
        if (w < 2) scores(BoolC<false>(), BoolC<false>(), sc); else scores(BoolC<true>(), BoolC<false>(), sc);
#pragma unroll 1
        for (int r = 0; r < 3; r++)
          st_async4(mapa(l16 + SM_FB + RANK * 1536 + w * 512, r), __float_as_uint(sc[0]), __float_as_uint(sc[1]), __float_as_uint(sc[2]), __float_as_uint(sc[3]), mapa(sb + MB_F, r));
      }
      mbar_wait(sb + MB_F, fp);
      float a[12];
#pragma unroll
      for (int j = 0; j < 3; j++) {
        float b[4];
        lds128f(l16 + SM_FB + j * 512, a + 4 * j); lds128f(l16 + SM_FB + 1536 + j * 512, b);
#pragma unroll
        for (int i = 0; i < 4; i++) a[4 * j + i] += b[i];
      }
      float m0 = fmaxf(fmaxf(fmaxf(a[0], a[2]), fmaxf(a[4], a[6])), a[8]), m1 = fmaxf(fmaxf(fmaxf(a[1], a[3]), fmaxf(a[5], a[7])), a[9]);
#pragma unroll
      for (int o = 4; o < 32; o <<= 1) { m0 = fmaxf(m0, __shfl_xor_sync(0xffffffffu, m0, o)); m1 = fmaxf(m1, __shfl_xor_sync(0xffffffffu, m1, o)); }
#pragma unroll
      for (int i = 0; i < 5; i++) {
        const uint32_t ea = sb + SM_E + LV * 4 + (i < 4 ? i * 128 : 1024);
        sts32(ea, pack_bf16(ex2(a[2 * i] - m0), ex2(a[2 * i + 1] - m1)));
        sts32(ea + (i < 4 ? 512 : 128), 0x3f803f80u);
      }
      __syncwarp();
    } else {
      load_vx();
      if (mode == 3 && EXPOS < 5) bar_arrive(4, 256);
      retire(l16 + 1);
      if (w == 3) {
        if (EXPOS >= 5) {
          constexpr int EARLY = EXPOS == 6 ? 8192 : 0;
          uint32_t used = ldg_relaxed32(&g_used[blockIdx.x / 3 * 32]);
          if (!(XP & 4) && elect_one()) {
            if (s > 0) seg_publish(s - 1);
            if (EARLY) { fence_async(); seg_store(s, sb, 0, EARLY); }
          }
          __syncwarp();
          bar_sync(RANK < 2 ? 4 : 15, RANK < 2 ? 256 : 160);
          if (!(XP & 4) && elect_one()) { fence_async(); seg_store(s, sb, EARLY, blk - EARLY); }
          __syncwarp();
          if (s >= NRING - 1 && !(XP & 64)) {
            const uint32_t need = lds32(sb + SC_EPOCH) + s;
#pragma unroll 1
            for (int n = 0; (int)(used - need) < 0 && n < SPIN_LIMIT; n++) used = ldg_relaxed32(&g_used[blockIdx.x / 3 * 32]);
          }
        }
        if (EXPOS == 0 && s > 0) export_seg(s - 1);
        if (EXB) { if (RANK < 2) bar_sync(5, N5); else bar_sync(15, 160); if (s > 0) export_rest(s - 1); }
      }
    }
    {
      uint32_t wa[4], wb[4], oc[4];
      constexpr int WS = 2048;
      const uint32_t w3a = l16 + SM_WO3 + w * 512;
      lds128(w3a + KP(0) * WS, wa); lds128(w3a + KP(1) * WS, wb); lds128(sb + SC_ONES, oc);
      if (B5POS == 1 && mode < 3) bar_arrive(5, N5);
      uint32_t e[10], p[5], vm[4], ob[4];
      float o0[4], o1[4], f[3][2][4], rs[4];
      reserve2(vm); reserve2(vm + 2); reserve2(e + 8);
      hints = hint_addr(s);
      PIN(hints);
      if (CLR & 2) asm volatile("{\n.reg .pred p;\nsetp.eq.u32 p, %0, 0;\n@p exit;\n}" :: "r"(wa[0] | wb[0] | oc[0] | hints) : "memory");
      mbar_wait(sb + MB_S, par);
      PROF(6);
      ldsm4t(e, l16 + SM_E); ldsm2t_in(e + 8, l16 + SM_E + 1024, always); ldsm4t(e + 4, l16 + SM_E + 512);
      lds128_in(vm, l16 + w * 512 + SM_VM, always);
      const float scl = __uint_as_float(lds32(sb + SC_UNSC + 8 - par * 8));
      hints = load_hints(hints);
      if (GF & 1) SCHED_FENCE(4);
#pragma unroll
      for (int i = 0; i < 4; i++) p[i] = mul_bf16(e[i], e[4 + i]);
      p[4] = mul_bf16(e[8], e[9]);
      mma16816z(o0, vx[0], p[0], p[1]); mma16816z(o1, vx[1], p[0], p[1]); mma16816z(rs, oc, p[0], p[1]);
      mma16816(o0, vx[2], p[2], p[3]); lds128_in(vx[2], w3a + KP(2) * WS, always);
      mma16816(o1, vx[3], p[2], p[3]); lds128_in(vx[3], w3a + KP(3) * WS, always);
      mma16816(rs, oc, p[2], p[3]);
      mma1688(o0, vm[0], vm[1], p[4]); mma1688(o1, vm[2], vm[3], p[4]); mma1688(rs, oc[0], oc[1], p[4]);
      stsm4(l16 + w * 512 + SM_OB, pack_bf16(o0[0], o0[1]), pack_bf16(o0[2], o0[3]), pack_bf16(o1[0], o1[1]), pack_bf16(o1[2], o1[3]));
      bar_sync(6, 128);
      PROF(7);
      ldsm4t_in(oc, l16 + SM_OB, always);
      bad = __any_sync(0xffffffffu, !(rs[0] + rs[1] > 0.f) && !bad);
      rs[0] *= scl; rs[1] *= scl;
      asm volatile("{\n.reg .pred p;\nsetp.ne.u32 p, %1, 0;\n@p rcp.approx.ftz.f32 %0, %0;\n}" : "+f"(rs[0]) : "r"(always));
      asm volatile("{\n.reg .pred p;\nsetp.ne.u32 p, %1, 1;\n@p rcp.approx.ftz.f32 %0, %0;\n}" : "+f"(rs[1]) : "r"(always));
      asm volatile("lop3.b32 %0, %1, %2, %3, 0xfe;" : "=r"(lp) : "r"((l16 & 128) * 2), "r"((l16 & 256) * 4), "r"(l16 & 112));
      if (bad) continue;
      ldsm4t(ob, l16 + SM_OB + 512);
      mma16816z(f[2][0], wa, oc[0], oc[1]); mma16816z(f[2][1], wb, oc[2], oc[3]);
      mma16816z(f[0][0], wo[0], oc[0], oc[1]); mma16816z(f[0][1], wo[4], oc[2], oc[3]);
      mma16816z(f[1][0], w1[0], oc[0], oc[1]); mma16816z(f[1][1], w1[4], oc[2], oc[3]);
      ldsm4t_in(oc, l16 + SM_OB + 1024, always);
      mma16816(f[2][0], vx[2], ob[0], ob[1]); lds128_in(vx[2], w3a + KP(4) * WS, always);
      mma16816(f[2][1], vx[3], ob[2], ob[3]); lds128_in(vx[3], w3a + KP(5) * WS, always);
      mma16816(f[0][0], wo[1], ob[0], ob[1]); mma16816(f[0][1], wo[5], ob[2], ob[3]);
      mma16816(f[1][0], w1[1], ob[0], ob[1]); mma16816(f[1][1], w1[5], ob[2], ob[3]);
      ldsm4t_in(ob, l16 + SM_OB + 1536, always);
      mma16816(f[0][0], wo[2], oc[0], oc[1]); mma16816(f[0][1], wo[6], oc[2], oc[3]);
      mma16816(f[2][0], vx[2], oc[0], oc[1]); lds128_in(vx[2], w3a + KP(6) * WS, always);
      mma16816(f[2][1], vx[3], oc[2], oc[3]); lds128_in(vx[3], w3a + KP(7) * WS, always);
      mma16816(f[1][0], w1[2], oc[0], oc[1]); mma16816(f[1][1], w1[6], oc[2], oc[3]);
      mma16816(f[0][0], wo[3], ob[0], ob[1]); mma16816(f[0][1], wo[7], ob[2], ob[3]);
      mma16816(f[1][0], w1[3], ob[0], ob[1]); mma16816(f[1][1], w1[7], ob[2], ob[3]);
      mma16816(f[2][0], vx[2], ob[0], ob[1]); mma16816(f[2][1], vx[3], ob[2], ob[3]);
      bar_arrive(7, NII < 18 ? 384 : 256);
      lds128_in(ob, sb + SC_DEAD, always);
      uint32_t h[3][2];
#pragma unroll
      for (int j = 0; j < 3; j++)
#pragma unroll
        for (int i = 0; i < 2; i++)
        {
          scale_sum(f[j][1][2 * i], f[j][0][2 * i], rs[0], always); scale_sum(f[j][1][2 * i + 1], f[j][0][2 * i + 1], rs[1], always);
          h[j][i] = pack_f16(f[j][1][2 * i], f[j][1][2 * i + 1]);
        }
      const uint32_t rofs = RANK * 32768;
      red_f16x8(slot(s, RANK >> 1, rofs), h[0][0], h[1][0], h[2][0], 0x3c00u);
      red_f16x8(slot(s, (RANK >> 1) ^ 1, rofs), h[0][1], h[1][1], h[2][1], 0x3c00u);
      if (NII == 18) bar_arrive(10, 256);
      SCHED_FENCE(5);
      l16 += ob[B7R];
    }
    {
    PROF(8);
    const uint32_t ma0 = l16 + SM_MEM + w * 128 + (LV >> 3) * 896 + nh * 512;
    const unsigned char* const sl[2] = {slot(s, nh, 0), slot(s, nh ^ 1, 0)};
    uint32_t late = latest_hint(hints, dl, s);
    if (late >= 64) {
      int n = 0;
#pragma unroll 1
      do {
        late = latest_hint(load_hints(hint_addr(s)), dl, s);
      } while (late >= 64 && ++n < SPIN_LIMIT);
    }
    dl += late * 32 + tm.poll;
    if (EXPOS == 2 && w == 3) export_seg(s);
    PROF(9);
    {
      auto wait_until = [&](uint32_t t) {
        asm volatile("{\n.reg .pred p;\n.reg .s32 c;\n.reg .u64 t;\nTL: mov.u64 t, %%globaltimer;\ncvt.u32.u64 c, t;\nsub.s32 c, c, %0;\nsetp.lt.s32 p, c, 0;\n@p bra.uni TL;\n}" :: "r"(t + (l16 & 15)) : "memory");
      };
      uint4 v[2][3];
      auto load = [&](int c) {
#pragma unroll
        for (int r = 0; r < 3; r++) v[c][r] = ldg_relaxed(sl[c ^ (r >> 1)] + r * 32768);
      };
      auto decode = [&](int c, int n) {
        uint32_t q[9];
        __half2 hm;
        const uint32_t ma = ma0 ^ (c * 512);
#pragma unroll
        for (int i = 0; i < 9; i++) {
          const uint32_t h = i % 3 == 0 ? v[c][i / 3].x : (i % 3 == 1 ? v[c][i / 3].y : v[c][i / 3].z);
          const float2 f = __half22float2(*(const __half2*)&h);
          q[i] = pack_bf16(f.x, f.y);
          hm = i ? __hmax2(hm, __habs2(*(const __half2*)&h)) : __habs2(*(const __half2*)&h);
        }
#pragma unroll
        for (int r = 0; r < 3; r++) stsm4(ma + r * 4096, q[3 * r], q[3 * r + 1], q[3 * r + 2], r < 2 ? v[c][r].w : *(const uint32_t*)&hm);
        const bool done = __all_sync(0xffffffffu, v[c][0].w == 0x5000u && v[c][1].w == 0x5000u && v[c][2].w == 0x5000u) || n > SPIN_LIMIT;
        asm volatile("{\n.reg .pred p;\nsetp.ne.u32 p, %0, 0;\n@p bar.arrive %1, 256;\n}" :: "r"((int)done), "r"(1 + c) : "memory");
        return done;
      };
      if (LEAD) { wait_until(dl - LEAD); load(1); }
      wait_until(dl);
      PROF(10);
      int n = 0;
#pragma unroll 1
      do {
        load(0);
        if (!LEAD) load(1);
        asm volatile("{\n.reg .pred p;\nsetp.eq.u32 p, %0, 0;\n@p bar.sync 13, 384;\n}" :: "r"(n) : "memory");
      } while (!decode(0, n++));
      PROF(11);
#pragma unroll 1
      while (!decode(1, n++)) load(1);
      bar_arrive(9, 256);
      PROF(12);
    }
    if (EXPOS == 3 && w == 3) export_seg(s);
    PROF(13);
    if (++s == NSEG - 1) break;
    }
  }
#undef fence_reg
  if (RANK < 2) bar_arrive(4, 256);
  if (w == 3) { if (EXPOS < 2 || EXPOS == 4) export_seg(NSEG - 2); export_rest(NSEG - 2); if (!(XP & 4) && elect_one()) { seg_publish(NSEG - 2); if (EXPOS == 6) { fence_async(); seg_store(NSEG - 1, sb, 0, 8192); } } }
  __syncwarp();
  bar_sync(0, 384);
  if (w == 3 && !(XP & 4) && elect_one()) {
    fence_async();
    seg_store(NSEG - 1, sb, EXPOS == 6 ? 8192 : 0, EXPOS == 6 ? blk - 8192 : blk);
    seg_publish(NSEG - 1);
  }
  __syncwarp();
  cluster_sync();
}

__global__ void __cluster_dims__(3, 1, 1) __launch_bounds__(384, 1)
rec_kernel(const __grid_constant__ RMaps tm, const bf16* __restrict__ x, const bf16* __restrict__ mem0) {
  extern __shared__ __align__(1024) unsigned char smem_raw[];
  const uint32_t sb = smem_u32(smem_raw);
  const int tid = threadIdx.x, lane = tid & 31;
  const int wg = __shfl_sync(0xffffffffu, tid >> 7, 0);
  const int w = __shfl_sync(0xffffffffu, (tid >> 5) & 3, 0);
  uint32_t rank; asm("mov.u32 %0, %%cluster_ctarank;" : "=r"(rank));
  STAMP(0);
  asm volatile("griddepcontrol.launch_dependents;" ::: "memory");

#define PFT 1
  if (PFT && wg == 1 && lane == 0) asm volatile("prefetch.tensormap [%0];" :: "l"(w == 0 ? (rank < 2 ? &tm.wk : &tm.wv) : w == 1 ? &tm.wq : w == 2 ? &tm.x : &tm.wo) : "memory");
  if (wg < 2) {
    asm volatile("setmaxnreg.inc.sync.aligned.u32 192;");
    if (tid == 0) {
      for (int i = 0; i < 3; i++) { mbar_init(sb + MB_W + 8 * i, 1); mbar_init(sb + MB_X + 8 * i, 1); }
      mbar_init(sb + MB_WO, 1); mbar_init(sb + MB_WO3, 1);
      mbar_init(sb + MB_S, rank < 2 ? 5 : 6);
      mbar_init(sb + MB_F, 1);
      mbar_init(sb + MB_VX, 1); mbar_init(sb + MB_VX + 8, 1);
      asm volatile("fence.mbarrier_init.release.cluster;" ::: "memory");
      fence_async();
      SSTAMP(11, 6);
      load_weights(sb, tm, rank, 0);
      for (int i = 0; i < 3; i++) mbar_expect(sb + MB_X + 8 * i, XT);
      tma_load3(sb + SM_X, &tm.x, 0, sb + MB_X);
      if (!PACE) for (int c = 1; c < 4; c++) load_weights(sb, tm, rank, c);
      mbar_expect(sb + MB_S, rank < 2 ? 640 + 2048 : 1280);
      mbar_expect(sb + MB_VX, 8192); mbar_expect(sb + MB_VX + 8, 8192);
      SSTAMP(11, 5);
    }
    __syncwarp();
    bar_sync(0, 384);
    proj_role(sb, tm, rank, wg, w, lane);
  } else {
    asm volatile("setmaxnreg.dec.sync.aligned.u32 120;");
    attn_role(sb, smem_raw, tm, rank, x, mem0, w, lane);
  }
}

constexpr int NAUX = 36;
constexpr int A_XH = 73728;
constexpr int A_NS = 9, A_WM = 6144, A_WT = 768;
constexpr int A_RING = 2 * A_XH, A_TAIL = A_RING + A_NS * A_WM, A_GW = A_TAIL + A_NS * A_WT;
constexpr int A_EPI = 212864, A_EPW = 9344;
constexpr int A_XT = 4 * XT, A_XW = A_XT + 8192, A_EX = A_XW + 8192, A_NR = 4;
constexpr int A_IN = A_EX + 16384, A_OST = A_IN + 3 * SEGB;
constexpr int A_GATE = A_EPI + 2 * A_EPW, A_BAR = A_GATE + 512;
constexpr int A_TOTAL = A_BAR + 384;
struct AMaps { CUtensorMap x, wa, wt, oa, o, o3, wob, woa; };

DI void wgmma_n192_ss_nt(float* d, uint64_t da, uint64_t db, int acc) {
  asm volatile("{\n.reg .pred p;\nsetp.ne.b32 p, %98, 0;\n"
               "wgmma.mma_async.sync.aligned.m64n192k16.f32.bf16.bf16 {"
               "%0,%1,%2,%3,%4,%5,%6,%7,%8,%9,%10,%11,%12,%13,%14,%15,%16,%17,%18,%19,%20,%21,%22,%23,%24,%25,%26,%27,%28,%29,%30,%31,"
               "%32,%33,%34,%35,%36,%37,%38,%39,%40,%41,%42,%43,%44,%45,%46,%47,%48,%49,%50,%51,%52,%53,%54,%55,%56,%57,%58,%59,%60,%61,%62,%63,"
               "%64,%65,%66,%67,%68,%69,%70,%71,%72,%73,%74,%75,%76,%77,%78,%79,%80,%81,%82,%83,%84,%85,%86,%87,%88,%89,%90,%91,%92,%93,%94,%95"
               "}, %96, %97, p, 1, 1, 0, 1;\n}\n"
               : ACC8(d, 0), ACC8(d, 8), ACC8(d, 16), ACC8(d, 24), ACC8(d, 32), ACC8(d, 40), ACC8(d, 48), ACC8(d, 56),
                 ACC8(d, 64), ACC8(d, 72), ACC8(d, 80), ACC8(d, 88) : "l"(da), "l"(db), "r"(acc));
}
#define ACC4(d, o) "+f"(d[o]), "+f"(d[o + 1]), "+f"(d[o + 2]), "+f"(d[o + 3])
DI void wgmma_n24_ss_nt(float* d, uint64_t da, uint64_t db, int acc) {
  asm volatile("{\n.reg .pred p;\nsetp.ne.b32 p, %14, 0;\n"
               "wgmma.mma_async.sync.aligned.m64n24k16.f32.bf16.bf16 {%0,%1,%2,%3,%4,%5,%6,%7,%8,%9,%10,%11}, %12, %13, p, 1, 1, 0, 1;\n}\n"
               : ACC8(d, 0), ACC4(d, 8) : "l"(da), "l"(db), "r"(acc));
}
DI void wgmma_n8_ss(float* d, uint64_t da, uint64_t db, int acc) {
  asm volatile("{\n.reg .pred p;\nsetp.ne.b32 p, %6, 0;\n"
               "wgmma.mma_async.sync.aligned.m64n8k16.f32.bf16.bf16 {%0,%1,%2,%3}, %4, %5, p, 1, 1, 0, 0;\n}\n"
               : ACC4(d, 0) : "l"(da), "l"(db), "r"(acc));
}
DI void wgmma_n40_ss_tt(float* d, uint64_t da, uint64_t db, int acc) {
  asm volatile("{\n.reg .pred p;\nsetp.ne.b32 p, %22, 0;\n"
               "wgmma.mma_async.sync.aligned.m64n40k16.f32.bf16.bf16 {%0,%1,%2,%3,%4,%5,%6,%7,%8,%9,%10,%11,%12,%13,%14,%15,%16,%17,%18,%19}, "
               "%20, %21, p, 1, 1, 1, 1;\n}\n"
               : ACC8(d, 0), ACC8(d, 8), ACC4(d, 16) : "l"(da), "l"(db), "r"(acc));
}
DI void wgmma_n64_rs(float* d, const uint32_t* a, uint64_t db, int acc) {
  asm volatile("{\n.reg .pred p;\nsetp.ne.b32 p, %37, 0;\n"
               "wgmma.mma_async.sync.aligned.m64n64k16.f32.bf16.bf16 {"
               "%0,%1,%2,%3,%4,%5,%6,%7,%8,%9,%10,%11,%12,%13,%14,%15,%16,%17,%18,%19,%20,%21,%22,%23,%24,%25,%26,%27,%28,%29,%30,%31"
               "}, {%32,%33,%34,%35}, %36, p, 1, 1, 0;\n}\n"
               : ACC8(d, 0), ACC8(d, 8), ACC8(d, 16), ACC8(d, 24) : "r"(a[0]), "r"(a[1]), "r"(a[2]), "r"(a[3]), "l"(db), "r"(acc));
}
DI void wgmma_n32_ss_tn(float* d, uint64_t da, uint64_t db, int acc) {
  asm volatile("{\n.reg .pred p;\nsetp.ne.b32 p, %18, 0;\n"
               "wgmma.mma_async.sync.aligned.m64n32k16.f32.bf16.bf16 {%0,%1,%2,%3,%4,%5,%6,%7,%8,%9,%10,%11,%12,%13,%14,%15}, "
               "%16, %17, p, 1, 1, 1, 0;\n}\n"
               : ACC8(d, 0), ACC8(d, 8) : "l"(da), "l"(db), "r"(acc));
}
DI void tma_load3c(uint32_t dst, const CUtensorMap* m, int c0, int c1, int c2, uint32_t mb) {
  asm volatile("cp.async.bulk.tensor.3d.shared::cluster.global.mbarrier::complete_tx::bytes [%0], [%1, {%3, %4, %5}], [%2];"
               :: "r"(dst), "l"(m), "r"(mb), "r"(c0), "r"(c1), "r"(c2) : "memory");
}
#define NAP 64
DI uint32_t movm(uint32_t x) { uint32_t r; asm volatile("movmatrix.sync.aligned.m8n8.trans.b16 %0, %1;" : "=r"(r) : "r"(x)); return r; }
DI void wait_count(const unsigned* p, unsigned target) {
  int n = 0;
  unsigned v;
  while (true) {
    asm volatile("ld.acquire.gpu.global.b32 %0, [%1];" : "=r"(v) : "l"(p) : "memory");
    if ((int)(v - target) >= 0 || ++n > SPIN_LIMIT) break;
    if (NAP) __nanosleep(NAP);
  }
}
DI void count_up(unsigned* p) {
  asm volatile("fence.proxy.async;" ::: "memory");
  asm volatile("red.release.gpu.global.add.u32 [%0], 1;" :: "l"(p) : "memory");
}
#define AX 0
#define FDLY 400
#define ORING 63
#define DRY 0
#define ADLY 0

__global__ void __launch_bounds__(512, 1)
aux_kernel(const __grid_constant__ AMaps tm, const bf16* __restrict__ wqkv, const bf16* __restrict__ gate_w, bf16* __restrict__ out) {
  extern __shared__ __align__(1024) unsigned char smem_raw[];
  const uint32_t sb = smem_u32(smem_raw);
  const uint32_t fullx = sb + A_BAR, full1 = fullx + 24, empty1 = full1 + 8 * A_NS, fullw = empty1 + 8 * A_NS, full3 = fullw + 8, empty3 = full3 + 8 * A_NR,
                 fullq = empty3 + 8 * A_NR, fullv = fullq + 8, emptyq = fullv + 8, emptyv = emptyq + 8;
  const int tid = threadIdx.x, lane = tid & 31, cta = blockIdx.x;
  const int wg = __shfl_sync(0xffffffffu, tid >> 7, 0), w = __shfl_sync(0xffffffffu, (tid >> 5) & 3, 0);
  ASTAMP(14);
  if (tid == 384) {
    for (int i = 0; i < 3; i++) mbar_init(fullx + 8 * i, 1);
    for (int i = 0; i < A_NS; i++) { mbar_init(full1 + 8 * i, 1); mbar_init(empty1 + 8 * i, 8); }
    mbar_init(fullw, 1); mbar_init(fullq, 1); mbar_init(fullv, 1); mbar_init(emptyq, 4); mbar_init(emptyv, 4);
    for (int i = 0; i < A_NR; i++) { mbar_init(full3 + 8 * i, 1); mbar_init(empty3 + 8 * i, 4); }
    fence_async();
  }
  __syncthreads();
  ASTAMP(0);
  const int tile = cta >> 1, hh = cta & 1;
  const int nsl = cta >> 2, kq = cta & 3;
  if (wg == 3) {
    asm volatile("setmaxnreg.dec.sync.aligned.u32 24;");
    const bool lead = lane == 0;
    if (w < 3) {
      if (ADLY) wait_until(gtime() + ADLY);
      if (elect_one()) {
        mbar_expect(fullx + 8 * w, 49152);
        for (int p = 0; p < 2; p++)
          asm volatile("cp.async.bulk.tensor.4d.shared::cluster.global.mbarrier::complete_tx::bytes [%0], [%1, {%3, %4, %5, %6}], [%2];"
                       :: "r"(sb + p * A_XH + w * 24576), "l"(&tm.x), "r"(fullx + 8 * w), "r"(0), "r"(p), "r"(57 * tile - 7), "r"(3 * w) : "memory");
      }
#pragma unroll 1
      for (int r = 0; r < 17; r++) {
#pragma unroll 1
        for (int st = w; st < A_NS; st += 3) {
          if (r > 0) mbar_wait(empty1 + 8 * st, ~r & 1);
          if (r < 16 && elect_one()) {
            const int col = hh * 288 + (r >> 2) * 72, row = (r & 3) * 144 + st * 16;
            mbar_expect(full1 + 8 * st, A_WM + (AX & 1 ? 0 : A_WT));
            tma_load3c(sb + A_RING + st * A_WM, &tm.wa, col, row, 0, full1 + 8 * st);
            if (!(AX & 1)) tma_load3c(sb + A_TAIL + st * A_WT, &tm.wt, col + 64, row, 0, full1 + 8 * st);
          }
          __syncwarp();
        }
        if (r == 0 && elect_one())
          for (int j = 0; j < 3; j++)
            asm volatile("cp.async.bulk.prefetch.L2.global [%0], %1;" :: "l"((const char*)wqkv + cta * 55296 + (w * 3 + j) * 6144), "r"(6144) : "memory");
        __syncwarp();
      }
      bar_sync(8, 96);
    }
    const unsigned epoch = lds32(sb + A_BAR + 376);
    if (w == 1 && cta < NH) {
#pragma unroll 1
      for (int seg = 0; seg < NSEG; seg++) {
        bar_arrive(5, 160);
        if (seg > 0 && lead) {
          asm volatile("cp.async.bulk.wait_group 0;" ::: "memory");
          asm volatile("red.relaxed.gpu.global.add.u32 [%0], 1;" :: "l"(&g_ocnt[(seg - 1) * 32 + cta / 9 * 8]) : "memory");
          SSTAMP(9, seg - 1);
        }
        __syncwarp();
        bar_sync(4, 160);
        if (lead && !(AX & 32)) {
          tma_store(&tm.o, sb + A_OST, cta * DH, (seg & ORING) * 32);
          tma_store(&tm.o, sb + A_OST + 4096, cta * DH + 64, (seg & ORING) * 32);
          asm volatile("cp.async.bulk.commit_group;" ::: "memory");
          asm volatile("cp.async.bulk.wait_group.read 0;" ::: "memory");
        }
        __syncwarp();
      }
      if (lead) {
        asm volatile("cp.async.bulk.wait_group 0;" ::: "memory");
        asm volatile("red.relaxed.gpu.global.add.u32 [%0], 1;" :: "l"(&g_ocnt[(NSEG - 1) * 32 + cta / 9 * 8]) : "memory");
        SSTAMP(9, NSEG - 1);
      }
    }
    if (w == 2) {
      if (lead && cta < NH) {
#pragma unroll 1
        for (int seg = 0; seg < NSEG; seg++) {
          const unsigned char* const src = g_seg + ((size_t)(AX & 128 ? 0 : seg % NRING) * 96 + cta * 3) * SEGB;
          SSTAMP(0, seg);
          const uint32_t tw = gtime();
          wait_count(&g_scnt[(seg * 32 + cta) * 8], 3 * (epoch + 1));
          if (FDLY && seg < 61 && gtime() - tw > 600) wait_until(gtime() + FDLY);
          SSTAMP(1, seg);
          mbar_wait(emptyq, ~seg & 1);
          if (AX & 8) { mbar_arrive(fullq); mbar_wait(emptyv, ~seg & 1); mbar_arrive(fullv); continue; }
          mbar_expect(fullq, 2 * SEGB);
          asm volatile("cp.async.bulk.shared::cluster.global.mbarrier::complete_tx::bytes [%0], [%1], %2, [%3];"
                       :: "r"(sb + A_IN), "l"(src), "r"(2 * SEGB), "r"(fullq) : "memory");
          mbar_wait(emptyv, ~seg & 1);
          stg_relaxed32(&g_used[cta * 32], epoch * NSEG + seg);
          mbar_expect(fullv, SEGB);
          asm volatile("cp.async.bulk.shared::cluster.global.mbarrier::complete_tx::bytes [%0], [%1], %2, [%3];"
                       :: "r"(sb + A_IN + 2 * SEGB), "l"(src + 2 * SEGB), "r"(SEGB), "r"(fullv) : "memory");
        }
      }
    }
    if (w == 3) {
#pragma unroll 1
      for (int c = 0; c < 4; c++) {
        if (lead) asm volatile("cp.async.bulk.wait_group.read 0;" ::: "memory");
        __syncwarp();
        bar_arrive(11, 160); bar_arrive(12, 160);
#pragma unroll 1
        for (int g = 0; g < 2; g++) {
          bar_sync(13 + g, 160);
          if (lead) {
            asm volatile("cp.async.bulk.tensor.3d.global.shared::cta.bulk_group [%0, {%2, %3, %4}], [%1];"
                         :: "l"(&tm.oa), "r"(sb + A_EPI + g * A_EPW + 1024), "r"(4096 + hh * 288 + c * 72), "r"(g), "r"(57 * tile) : "memory");
            asm volatile("cp.async.bulk.commit_group;" ::: "memory");
          }
        }
      }
      if (lead) asm volatile("cp.async.bulk.wait_group.read 0;" ::: "memory");
      __syncwarp();
      bar_arrive(10, 160);
      if (lead) { asm volatile("cp.async.bulk.wait_group 0;" ::: "memory"); count_up(&g_abar[32]); }
    }
    if (w != 0) return;
    if (lead) {
      mbar_expect(fullw, 19 * 8192);
#pragma unroll 1
      for (int k = 0; k < 19; k++) {
        const int kb = k < 18 ? kq * 18 + k : 72;
        const uint32_t dst = sb + (k < 18 ? k * 8192 : A_XW);
        if (kb < 64) tma_load(dst, &tm.wob, nsl * 64, kb * 64, fullw);
        else tma_load(dst, &tm.woa, nsl * 64, (kb - 64) * 64, fullw);
      }
    }
    __syncwarp();
    bar_sync(6, 288);
    if (lead) {
      if (kq == 3) { wait_count(&g_abar[32], NAUX * (epoch + 1)); asm volatile("fence.proxy.async;" ::: "memory"); }
      int avail = 0;
      const unsigned nheads = (kq < 3 ? 9 : 5) * (epoch + 1);
      for (int seg = 0; seg < NSEG; seg++) {
        if (seg >= avail) {
          const int far = min(seg + 3, NSEG - 1);
          if (far > seg && (int)(ldg_acquire32(&g_ocnt[far * 32 + kq * 8]) - nheads) >= 0) avail = far + 1;
          else { wait_count(&g_ocnt[seg * 32 + kq * 8], nheads); avail = seg + 1; }
        }
        SSTAMP(5, seg);
        for (int g = 0; g < 2; g++) {
          const int sl = (seg & 1) * 2 + g;
          const bool extra = kq == 3 && g == 0;
          mbar_wait(empty3 + 8 * sl, ((seg >> 1) & 1) ^ 1);
          if (AX & 4) { mbar_arrive(full3 + 8 * sl); continue; }
          mbar_expect(full3 + 8 * sl, XT + (extra ? 4096 : 0));
          tma_load3c(sb + sl * XT, &tm.o3, 0, (kq == 3 && g == 1 ? seg : seg & ORING) * 32, kq * 18 + 9 * g, full3 + 8 * sl);
          if (extra) tma_load(sb + A_XT + (seg & 1) * 4096, &tm.o, 72 * 64, seg * 32, full3 + 8 * sl);
        }
      }
    }
    __syncwarp(); bar_sync(6, 288);
    asm volatile("griddepcontrol.wait;" ::: "memory");
  } else if (wg == 2) {
    asm volatile("setmaxnreg.dec.sync.aligned.u32 88;");
    {
      const unsigned epoch = *(volatile unsigned*)&g_epoch2;
      if ((tid & 127) < 80) { const uint4 g = __ldg((const uint4*)gate_w + min(tid & 127, 71)); sts128(sb + A_GW + (tid & 127) * 16, g.x, g.y, g.z, g.w); }
      fence_async();
      bar_sync(3, 128);
      float gt[2][4];
      const uint32_t d0 = (sb & 0x3FFFF) >> 4;
#pragma unroll 1
      for (int j = 0; j < 3; j++) {
        mbar_wait(fullx + 8 * j, 0);
        WG_FENCE();
#pragma unroll
        for (int k = 0; k < 24; k++)
          wgmma_n8_ss(gt[k & 1], desc_at(d0 + (k & 1) * (A_XH >> 4) + j * 1536 + (k >> 3) * 512 + (k & 6), 16, 1024, 1), desc_at(d0 + (A_GW >> 4) + j * 24 + (k & 30), 16, 128, 0), j | (k >> 1));
        WG_COMMIT();
      }
      WG_WAIT(0);
      if ((lane & 3) == 0)
#pragma unroll
        for (int i = 0; i < 4; i++) {
          const float gv = 1.f / (1.f + __expf(-gt[i >> 1][(i & 1) * 2]));
          const int r = w * 16 + (lane >> 2) + (i & 1) * 8, tok = 2 * (57 * tile - 7 + r) + (i >> 1);
          sts32(sb + A_GATE + ((i >> 1) * 64 + r) * 4, __float_as_uint(gv));
          if (hh == 0 && r >= 7 && tok < S_LEN) g_gate[tok] = gv;
        }
      if (tid == 256) sts32(sb + A_BAR + 376, epoch);
      __syncwarp();
      bar_arrive(7, 384);
      bar_sync(3, 128);
      if (tid == 256) {
        count_up(&g_abar[0]);
        wait_count(&g_abar[0], NAUX * (epoch + 1));
        if (cta == 0) *(volatile unsigned*)&g_epoch2 = epoch + 1;
      }
      __syncwarp();
      bar_sync(10, 160);
    }
    if (cta < NH) {
      const int lim = w * 8 + (lane >> 2) - 2 * (lane & 3);
      const uint32_t oa = sb + A_OST + (w * 8 + (lane & 7)) * 128;
      const uint32_t d0 = ((sb + A_IN) & 0x3FFFF) >> 4;
      uint32_t p[5][4];
#pragma unroll
      for (int n = 0; n < 10; n++) p[n >> 1][1 + (n & 1)] = __shfl_sync(0xffffffffu, lane ^ n, n);
#pragma unroll 1
      for (int seg = 0; seg < NSEG; seg++) {
        const float gt = __ldcg(&g_gate[seg * 32 + w * 8 + (lane >> 2)]);
        float sc[20], d[32];
        mbar_wait(fullq, seg & 1);
        if (tid == 256) SSTAMP(2, seg);
        WG_FENCE();
#pragma unroll
        for (int k = 0; k < 8; k++) {
          const int o = ((k >> 2) * SEGB + (k & 3) * 256) >> 4;
          wgmma_n40_ss_tt(sc, desc_at(d0 + o, 128, 512, 0), desc_at(d0 + o + 256, 128, 1024, 0), k > 0);
        }
        WG_COMMIT();
        WG_WAIT(0);
        if (lane == 0) mbar_arrive(emptyq);
        float a[10];
#pragma unroll
        for (int i = 0; i < 10; i++) {
          a[i] = sc[(i >> 1) * 4 + (i & 1)] * (SM_SCALE * LOG2E);
          if (i < 8 && (i >> 1) * 8 + (i & 1) > lim) a[i] = -1.0e9f * LOG2E;
        }
        float m = max10(a);
        m = fmaxf(m, __shfl_xor_sync(0xffffffffu, m, 1)); m = fmaxf(m, __shfl_xor_sync(0xffffffffu, m, 2));
#pragma unroll
        for (int i = 0; i < 10; i++) a[i] = ex2(a[i] - m);
#pragma unroll
        for (int n = 0; n < 5; n++) {
          p[n][0] = pack_bf16(a[2 * n], a[2 * n + 1]); p[n][3] = p[n][0] | p[n][1];
          asm volatile("" : "+r"(p[n][0]), "+r"(p[n][3]) :: "memory");
        }
        float sum = ((a[0] + a[1]) + (a[2] + a[3])) + ((a[4] + a[5]) + (a[6] + a[7])) + (a[8] + a[9]);
        sum += __shfl_xor_sync(0xffffffffu, sum, 1);
        if (tid == 256) SSTAMP(3, seg);
        mbar_wait(fullv, seg & 1);
        WG_FENCE();
#pragma unroll
        for (int n = 0; n < 5; n++) wgmma_n64_rs(d, p[n], n < 4 ? desc_at(d0 + SEGB / 8 + 8 * n, 4096, 512, 0) : desc_at(d0 + SEGB / 8 + 512, 1024, 128, 0), n);
        WG_COMMIT();
        sum += __shfl_xor_sync(0xffffffffu, sum, 2);
        const float f = (1.f - gt) * rcp(sum);
        bar_sync(5, 160);
        WG_WAIT(0);
        if (lane == 0) mbar_arrive(emptyv);
        if (tid == 256) SSTAMP(4, seg);
#pragma unroll
        for (int q = 0; q < 4; q++) {
          const float* const o = d + (q & 1) * 16 + (q & 2);
          stsm4(oa + (q >> 1) * 4096 + ((((q & 1) * 4 + (lane >> 3)) ^ (lane & 7)) << 4), pack_bf16(o[0] * f, o[1] * f), pack_bf16(o[4] * f, o[5] * f),
                pack_bf16(o[8] * f, o[9] * f), pack_bf16(o[12] * f, o[13] * f));
        }
        fence_async();
        bar_sync(4, 160);
      }
    }
  } else {
    asm volatile("setmaxnreg.inc.sync.aligned.u32 200;");
    {
      const int g = lane >> 2, t = lane & 3;
      const uint32_t eb = sb + A_EPI + wg * A_EPW, d0 = (sb & 0x3FFFF) >> 4;
      const uint32_t own = (2 * t <= g ? 0xffffu : 0u) | (2 * t < g ? 0xffff0000u : 0u);
      const int kmin = 7 - 57 * tile - 16 * w;
#pragma unroll 1
      for (int c = -DRY; c < 4; c++) {
        float acc[96], tl[12];
#pragma unroll 1
        for (int r = c < 0 ? 4 : 0; r < 4; r++) {
#pragma unroll
          for (int st = 0; st < A_NS; st++) {
            const int ks = r * 9 + st;
            if (c == 0 && st % 3 == 0 && ks % 12 == 0) mbar_wait(fullx + 8 * (ks / 12), 0);
            mbar_wait(full1 + 8 * st, r & 1);
            const uint64_t da = desc_at(d0 + wg * (A_XH >> 4) + (ks >> 2) * 512 + (ks & 3) * 2, 16, 1024, 1);
            WG_FENCE();
            wgmma_n192_ss_nt(acc, da, desc_at(d0 + ((A_RING + st * A_WM) >> 4), 2048, 1024, 1), ks);
            if (!(AX & 2)) wgmma_n24_ss_nt(tl, da, desc_at(d0 + ((A_TAIL + st * A_WT) >> 4), 128, 256, 0), ks);
            WG_COMMIT();
            if (st == 0 && r == 2) bar_sync(11 + wg, 160);
            WG_WAIT(1);
            if (ks > 0 && lane == 0) mbar_arrive(empty1 + 8 * ((st + A_NS - 1) % A_NS));
          }
        }
        WG_WAIT(0);
        if (lane == 0 && c >= 0) mbar_arrive(empty1 + 8 * (A_NS - 1));
        ASTAMP(16 + (c & 3));
        uint32_t ql[9], qh[9], kl[9], kh[9], kx[10], vl[9], vh[9], vx[10];
#pragma unroll
        for (int j = 0; j < 9; j++) {
          const float* const q = j < 8 ? acc + 4 * j : tl, * const k = j < 8 ? acc + 32 + 4 * j : tl + 4, * const v = j < 8 ? acc + 64 + 4 * j : tl + 8;
          kh[j] = pack_bf16(k[2], k[3]); vh[j] = pack_bf16(v[2], v[3]);
          ql[j] = pack_bf16(q[0], q[1]); qh[j] = pack_bf16(q[2], q[3]); kl[j] = pack_bf16(k[0], k[1]); vl[j] = pack_bf16(v[0], v[1]);
        }
        if (w < 3) {
          const uint32_t ha = eb + 1024 + w * 2304 + lane * 16;
          stsm4(ha, kh[0], kh[1], kh[2], kh[3]); stsm4(ha + 512, kh[4], kh[5], kh[6], kh[7]);
          stsm4(ha + 1024, vh[0], vh[1], vh[2], vh[3]); stsm4(ha + 1536, vh[4], vh[5], vh[6], vh[7]);
          asm volatile("stmatrix.sync.aligned.m8n8.x2.shared.b16 [%0], {%1,%2};" :: "r"(ha + 2048), "r"(kh[8]), "r"(vh[8]) : "memory");
        }
        if (c == 0) bar_sync(7, 384); else bar_sync(1 + wg, 128);
        {
          const uint32_t ha = eb + 1024 + max(w - 1, 0) * 2304 + lane * 16;
          ldsm4(kx, ha); ldsm4(kx + 4, ha + 512); ldsm4t(vx, ha + 1024); ldsm4t(vx + 4, ha + 1536);
          asm volatile("ldmatrix.sync.aligned.m8n8.x1.shared.b16 {%0}, [%1];" : "=r"(kx[8]) : "r"(ha + 2048) : "memory");
          asm volatile("ldmatrix.sync.aligned.m8n8.x1.trans.shared.b16 {%0}, [%1];" : "=r"(vx[8]) : "r"(ha + 2176) : "memory");
        }
        const float gl = __uint_as_float(lds32(sb + A_GATE + (wg * 64 + w * 16 + g) * 4)), gh = __uint_as_float(lds32(sb + A_GATE + (wg * 64 + w * 16 + g + 8) * 4));
#pragma unroll
        for (int j = 0; j < 9; j++) { vl[j] = movm(vl[j]); vh[j] = movm(vh[j]); }
        bar_sync(1 + wg, 128);
        uint32_t ol[9], oh[9];
#pragma unroll
        for (int i = 0; i < 4; i++) {
          const int b = 2 * i;
          const uint32_t a[4] = {t >= i ? ql[b] : 0u, t >= i ? qh[b] : 0u, ql[b + 1], qh[b + 1]}, a4 = t <= i ? ql[b + 2] : 0u, a5 = t <= i ? qh[b + 2] : 0u;
          float sx[4], sl[4], sh[4];
          mma16816z(sx, a, kx[b], kx[b + 1]); mma16816z(sl, a, kl[b], kl[b + 1]); mma16816z(sh, a, kh[b], kh[b + 1]);
          mma1688(sx, a4, a5, kx[b + 2]); mma1688(sl, a4, a5, kl[b + 2]); mma1688(sh, a4, a5, kh[b + 2]);
          float e[4];
#pragma unroll
          for (int u = 0; u < 4; u++) {
            const int cc = 2 * t + (u & 1);
            e[u] = (cc <= g ? (u < 2 ? sl[u] : sh[u]) : (u < 2 ? sx[u] : sl[u])) * (0.23570226039551584f * LOG2E);
            if ((cc <= g ? cc : cc - 8) + (u & 2) * 4 < kmin) e[u] = -1.0e9f * LOG2E;
          }
          float m0 = fmaxf(e[0], e[1]), m1 = fmaxf(e[2], e[3]);
#pragma unroll
          for (int o = 1; o < 4; o <<= 1) { m0 = fmaxf(m0, __shfl_xor_sync(0xffffffffu, m0, o)); m1 = fmaxf(m1, __shfl_xor_sync(0xffffffffu, m1, o)); }
          e[0] = ex2(e[0] - m0); e[1] = ex2(e[1] - m0); e[2] = ex2(e[2] - m1); e[3] = ex2(e[3] - m1);
          const uint32_t p0 = pack_bf16(e[0], e[1]), p1 = pack_bf16(e[2], e[3]);
          const uint32_t p[4] = {p0 & ~own, 0u, p0 & own, p1 & ~own};
          float s0 = e[0] + e[1], s1 = e[2] + e[3];
#pragma unroll
          for (int o = 1; o < 4; o <<= 1) { s0 += __shfl_xor_sync(0xffffffffu, s0, o); s1 += __shfl_xor_sync(0xffffffffu, s1, o); }
          const float f0 = gl * rcp(s0), f1 = gh * rcp(s1);
#pragma unroll
          for (int j = b; j < b + 3; j++) {
            float o[4];
            mma16816z(o, p, vx[j], vl[j]);
            mma1688(o, 0u, p1 & own, vh[j]);
            const uint32_t lo = pack_bf16(o[0] * f0, o[1] * f0), hi = pack_bf16(o[2] * f1, o[3] * f1);
            if (j > b || i == 0) { ol[j] = lo; oh[j] = hi; }
            else { ol[j] = t >= i ? lo : ol[j]; oh[j] = t >= i ? hi : oh[j]; }
          }
        }
        const uint32_t sa = eb + 16 + (w * 16 + (lane & 15)) * 144 + (lane >> 4) * 16;
#pragma unroll
        for (int j = 0; j < 8; j += 2) stsm4(sa + j * 16, ol[j], oh[j], ol[j + 1], oh[j + 1]);
        asm volatile("stmatrix.sync.aligned.m8n8.x2.shared.b16 [%0], {%1,%2};" :: "r"(sa + 128), "r"(ol[8]), "r"(oh[8]) : "memory");
        fence_async();
        if (c >= 0) bar_arrive(13 + wg, 160); else bar_sync(1 + wg, 128);
        ASTAMP(20 + (c & 3));
      }
    }
    ASTAMP(3);
    uint32_t wa[36][4];
    mbar_wait(fullw, 0);
    const uint32_t la = sb + wg * 73728 + ((lane & 7) + ((lane >> 4) << 3)) * 128 + (((2 * w + ((lane >> 3) & 1)) ^ (lane & 7)) << 4);
#pragma unroll
    for (int k = 0; k < 36; k++) ldsm4t(wa[k], la + k * 2048);
    fence_async();
    bar_sync(6, 288);
    ASTAMP(4);
    float own[4] = {0.f, 0.f, 0.f, 0.f};
    uint4 v[3];
    auto fetch = [&](int seg) {
      const uint4* src = g_part + (((seg & 3) * 36 + cta) * 4) * 128 + (tid & 127);
#pragma unroll
      for (int j = 0; j < 3; j++) v[j] = AX & 16 ? make_uint4(0, 0, 0, 0) : ldg_relaxed(src + ((kq + 1 + j) & 3) * 128);
    };
    auto finish = [&](int seg) {
      const uint32_t tagv = ((seg >> 2) + 1) & 3;
      int n = 0;
#pragma unroll 1
      while (!(AX & 16) && __any_sync(0xffffffffu, (v[0].x & 3) != tagv || (v[1].x & 3) != tagv || (v[2].x & 3) != tagv) && ++n < SPIN_LIMIT) {
        if (seg < NSEG - 1) __nanosleep(200);
        fetch(seg);
      }
#pragma unroll
      for (int j = 0; j < 3; j++) {
        own[0] += __uint_as_float(v[j].x & ~3u); own[1] += __uint_as_float(v[j].y); own[2] += __uint_as_float(v[j].z); own[3] += __uint_as_float(v[j].w);
      }
      uint32_t p0 = pack_bf16(own[0], own[1]), p1 = pack_bf16(own[2], own[3]);
      asm volatile("movmatrix.sync.aligned.m8n8.trans.b16 %0, %0;" : "+r"(p0));
      asm volatile("movmatrix.sync.aligned.m8n8.trans.b16 %0, %0;" : "+r"(p1));
      uint32_t* o = (uint32_t*)(out + (size_t)(seg * 32 + kq * 8 + (lane >> 2)) * DM + nsl * 64 + w * 16) + (lane & 3);
      o[0] = p0; o[4] = p1;
    };
    float acc[16];
    auto stream = [&](int sl, int keep) {
      const uint64_t db = make_desc(sb + sl * XT, 16, 1024, 1);
      WG_FENCE();
#pragma unroll
      for (int k = 0; k < 36; k++) wgmma_n32_rs(acc, wa[k][0], wa[k][1], wa[k][2], wa[k][3], db + (k >> 2) * 256 + (k & 3) * 2, k ? 1 : keep);
      WG_COMMIT();
    };
    const uint32_t ex = sb + A_EX + (tid & 127) * 16;
    if (wg == 0) {
#pragma unroll
      for (int i = 0; i < 16; i++) acc[i] = 0.f;
#pragma unroll 1
      for (int seg = 0; seg < NSEG; seg++) {
        const int sl = (seg & 1) * 2;
        mbar_wait(full3 + 8 * sl, (seg >> 1) & 1);
        if (kq == 3) {
          const uint64_t da = make_desc(sb + A_XW, 8192, 1024, 1), de = make_desc(sb + A_XT + (seg & 1) * 4096, 16, 1024, 1);
          WG_FENCE();
#pragma unroll
          for (int j = 0; j < 4; j++) wgmma_n32_ss_tn(acc, da + j * 128, de + j * 2, j);
          WG_COMMIT();
          WG_WAIT(0);
        }
        if (!(AX & 64)) stream(sl, kq == 3);
        bar_arrive(9, 256);
        WG_WAIT(0);
        if (lane == 0) mbar_arrive(empty3 + 8 * sl);
#pragma unroll
        for (int i = 0; i < 4; i++)
          sts128(ex + (seg & 1) * 8192 + i * 2048, __float_as_uint(acc[4 * i]), __float_as_uint(acc[4 * i + 1]), __float_as_uint(acc[4 * i + 2]), __float_as_uint(acc[4 * i + 3]));
        bar_sync(1, 256);
      }
    } else {
#pragma unroll 1
      for (int seg = 0; seg < NSEG; seg++) {
        const int sl = (seg & 1) * 2 + 1;
        mbar_wait(full3 + 8 * sl, (seg >> 1) & 1);
        if (tid == 128) SSTAMP(6, seg);
        bar_sync(9, 256);
        if (!(AX & 64)) stream(sl, 0);
        bar_sync(1, 256);
        fetch(max(seg - 1, 0));
        WG_WAIT(0);
        if (lane == 0) mbar_arrive(empty3 + 8 * sl);
        float nxt[4] = {0.f, 0.f, 0.f, 0.f};
        uint4* dst = g_part + (((seg & 3) * 36 + nsl * 4) * 4 + kq) * 128 + (tid & 127);
#pragma unroll
        for (int j = 0; j < 4; j++) {
          float o[4];
          lds128f(ex + (seg & 1) * 8192 + j * 2048, o);
#pragma unroll
          for (int i = 0; i < 4; i++) { o[i] += acc[4 * j + i]; if (j == kq) nxt[i] = o[i]; }
          if (j != kq && !(AX & 16)) stg_relaxed(dst + j * 512, (__float_as_uint(o[0]) & ~3u) | (((seg >> 2) + 1) & 3), __float_as_uint(o[1]), __float_as_uint(o[2]), __float_as_uint(o[3]));
        }
        if (tid == 128) SSTAMP(7, seg);
        if (seg > 0) finish(seg - 1);
        if (tid == 128) SSTAMP(8, seg);
#pragma unroll
        for (int i = 0; i < 4; i++) own[i] = nxt[i];
        if ((seg & 7) == 6) ASTAMP(5 + (seg >> 3));
      }
      fetch(NSEG - 1);
      finish(NSEG - 1);
    }
    ASTAMP(13);
    bar_sync(6, 288);
  }
}

typedef CUresult (*EncodeFn)(CUtensorMap*, CUtensorMapDataType, cuuint32_t, void*, const cuuint64_t*, const cuuint64_t*,
                             const cuuint32_t*, const cuuint32_t*, CUtensorMapInterleave, CUtensorMapSwizzle,
                             CUtensorMapL2promotion, CUtensorMapFloatOOBfill);
static void make_map(EncodeFn enc, CUtensorMap* m, const void* p, int rows, int cols, int box_rows) {
  cuuint64_t dims[2] = {(cuuint64_t)cols, (cuuint64_t)rows};
  cuuint64_t strides[1] = {(cuuint64_t)cols * 2};
  cuuint32_t box[2] = {64, (cuuint32_t)box_rows};
  cuuint32_t es[2] = {1, 1};
  enc(m, CU_TENSOR_MAP_DATA_TYPE_BFLOAT16, 2, (void*)p, dims, strides, box, es, CU_TENSOR_MAP_INTERLEAVE_NONE,
      CU_TENSOR_MAP_SWIZZLE_128B, CU_TENSOR_MAP_L2_PROMOTION_L2_128B, CU_TENSOR_MAP_FLOAT_OOB_FILL_NONE);
}

constexpr int g_poll = POLL_NS;
extern "C" void kernel_launch(void* const* d_in, const int* in_sizes, int n_in, void* d_out, int out_size) {
  const bf16* x = (const bf16*)d_in[0];
  const bf16* wqkvA = (const bf16*)d_in[1];
  const bf16* woA = (const bf16*)d_in[2];
  const bf16* mem0 = (const bf16*)d_in[4];
  const bf16* Wq = (const bf16*)d_in[5];
  const bf16* Wk = (const bf16*)d_in[6];
  const bf16* Wv = (const bf16*)d_in[7];
  const bf16* Wo = (const bf16*)d_in[8];
  const bf16* gate_w = (const bf16*)d_in[10];
  static EncodeFn enc = nullptr;
  static void *pO = nullptr, *pR = nullptr;
  if (!enc) {
    cudaDriverEntryPointQueryResult qr;
    cudaGetDriverEntryPoint("cuTensorMapEncodeTiled", (void**)&enc, cudaEnableDefault, &qr);
    cudaGetSymbolAddress(&pO, g_Ocat);
    cudaGetSymbolAddress(&pR, g_red_raw);
    cudaFuncSetAttribute(rec_kernel, cudaFuncAttributeMaxDynamicSharedMemorySize, SM_TOTAL);
    cudaFuncSetAttribute(aux_kernel, cudaFuncAttributeMaxDynamicSharedMemorySize, A_TOTAL);
  }
  RMaps rm;
  rm.poll = g_poll;
  rm.red = (unsigned char*)(((uintptr_t)pR + 262143) & ~(uintptr_t)262143);
  {
    cuuint64_t dims[3] = {64, S_LEN, 9}, strides[2] = {DM * 2, 128};
    cuuint32_t box[3] = {64, 32, 9}, es[3] = {1, 1, 1};
    enc(&rm.x, CU_TENSOR_MAP_DATA_TYPE_BFLOAT16, 3, (void*)x, dims, strides, box, es, CU_TENSOR_MAP_INTERLEAVE_NONE,
        CU_TENSOR_MAP_SWIZZLE_128B, CU_TENSOR_MAP_L2_PROMOTION_L2_128B, CU_TENSOR_MAP_FLOAT_OOB_FILL_NONE);
  }
  make_map(enc, &rm.wq, Wq, DM, 4096, 192);
  make_map(enc, &rm.wk, Wk, DM, 4096, 192);
  make_map(enc, &rm.wv, Wv, DM, 4096, 192);
  make_map(enc, &rm.wo, Wo, 4096, DM, 128);
  AMaps am;
  {
    cuuint32_t es[4] = {1, 1, 1, 1};
    cuuint64_t dx[4] = {64, 2, S_LEN / 2, 9}, sx[3] = {DM * 2, DM * 4, 128};
    cuuint32_t bx[4] = {64, 1, 64, 3};
    enc(&am.x, CU_TENSOR_MAP_DATA_TYPE_BFLOAT16, 4, (void*)x, dx, sx, bx, es, CU_TENSOR_MAP_INTERLEAVE_NONE,
        CU_TENSOR_MAP_SWIZZLE_128B, CU_TENSOR_MAP_L2_PROMOTION_L2_128B, CU_TENSOR_MAP_FLOAT_OOB_FILL_NONE);
    cuuint64_t dw[3] = {DM, DM, 3}, sw[2] = {DM * 6, DM * 2};
    cuuint32_t bw[3] = {64, 16, 3}, bt[3] = {8, 16, 3};
    enc(&am.wa, CU_TENSOR_MAP_DATA_TYPE_BFLOAT16, 3, (void*)wqkvA, dw, sw, bw, es, CU_TENSOR_MAP_INTERLEAVE_NONE,
        CU_TENSOR_MAP_SWIZZLE_128B, CU_TENSOR_MAP_L2_PROMOTION_L2_128B, CU_TENSOR_MAP_FLOAT_OOB_FILL_NONE);
    enc(&am.wt, CU_TENSOR_MAP_DATA_TYPE_BFLOAT16, 3, (void*)wqkvA, dw, sw, bt, es, CU_TENSOR_MAP_INTERLEAVE_NONE,
        CU_TENSOR_MAP_SWIZZLE_NONE, CU_TENSOR_MAP_L2_PROMOTION_NONE, CU_TENSOR_MAP_FLOAT_OOB_FILL_NONE);
    cuuint64_t dz[3] = {KCAT, 2, S_LEN / 2}, sz[2] = {KCAT * 2, KCAT * 4};
    cuuint32_t bz[3] = {72, 1, 57};
    enc(&am.oa, CU_TENSOR_MAP_DATA_TYPE_BFLOAT16, 3, pO, dz, sz, bz, es, CU_TENSOR_MAP_INTERLEAVE_NONE,
        CU_TENSOR_MAP_SWIZZLE_NONE, CU_TENSOR_MAP_L2_PROMOTION_NONE, CU_TENSOR_MAP_FLOAT_OOB_FILL_NONE);
  }
  {
    cuuint64_t dims[3] = {64, S_LEN, KCAT / 64}, strides[2] = {KCAT * 2, 128};
    cuuint32_t box[3] = {64, 32, 9}, es[3] = {1, 1, 1};
    make_map(enc, &am.o, pO, S_LEN, KCAT, 32);
    enc(&am.o3, CU_TENSOR_MAP_DATA_TYPE_BFLOAT16, 3, pO, dims, strides, box, es, CU_TENSOR_MAP_INTERLEAVE_NONE,
        CU_TENSOR_MAP_SWIZZLE_128B, CU_TENSOR_MAP_L2_PROMOTION_L2_128B, CU_TENSOR_MAP_FLOAT_OOB_FILL_NONE);
  }
  make_map(enc, &am.wob, Wo, 4096, DM, 64);
  make_map(enc, &am.woa, woA, DM, DM, 64);

  rec_kernel<<<96, 384, SM_TOTAL, cudaStreamPerThread>>>(rm, x, mem0);
  cudaLaunchConfig_t cfg = {};
  cfg.gridDim = dim3(NAUX); cfg.blockDim = dim3(512); cfg.dynamicSmemBytes = A_TOTAL; cfg.stream = cudaStreamPerThread;
  cudaLaunchAttribute at[1];
  at[0].id = cudaLaunchAttributeProgrammaticStreamSerialization; at[0].val.programmaticStreamSerializationAllowed = 1;
  cfg.attrs = at; cfg.numAttrs = 1;
  if (XP & 16) cfg.numAttrs = 0;
  if (!(XP & 64)) cudaLaunchKernelEx(&cfg, aux_kernel, am, wqkvA, gate_w, (bf16*)d_out);
}
```

```cpp
#include <cuda_runtime.h>
#include <cuda_bf16.h>
#include <cuda_fp16.h>
#include <cuda.h>
#include <stdint.h>

typedef __nv_bfloat16 bf16;

constexpr int S_LEN = 2048, DM = 576, NH = 32, DH = 128, NSEG = 64, KCAT = 4096 + 576;
#define RED_LINE(i) (((i) >> 2) * 4096 + ((i) & 1) * 256 + ((i) & 2) * 512)
#define RED_SLOT(s) (((s) & 1) * 128 + ((s) & 2) * 256)

#define POLL_NS 896
#define NII 18
#define W3PRE 4
#define W3MID 4
#define GF 0
#define B5POS 0
#define NUP 4
#define UPF 1
#define B3Q 9
#define B3F 0
#define GATE 7
#define NTL 2
#define B7R 1
#define EXPOS 6
#define VS0 1
#define VS1 0
#define VLATE(w) ((w) == 0 ? VS0 == 1 : (w) == 1 ? VS1 == 1 : false)
#define B15 0
#define TL 0
#define CLR 1
#define RFW 0
#define NIC 0
#define LEAD 0
#define FIN16 1
#define VXG 0
#define NRING 20
#define EXB 0
#define EXD 0
#define EXB2 8192
#define HDLY 0
#define F10 1
#define NPROBE 2
#define QM 0
#define N5 (EXB ? 256 : 224)
#define KP(i) (((i) >> 1) + 4 * ((i) & 1))
#define SPIN_LIMIT (1 << 14)
#define XP 0

__device__ __align__(1024) bf16 g_Ocat[S_LEN * KCAT];
__device__ __align__(1024) unsigned char g_red_raw[2 * 262144];
constexpr int HINT_OFF = 2048;
__device__ __align__(16) float g_gate[S_LEN];
__device__ __align__(128) uint4 g_stats[96 * 2];
__device__ unsigned g_epoch;
__device__ unsigned g_epoch2;
__device__ unsigned g_ocnt[NSEG * 32];
__device__ unsigned g_abar[3 * 32];
__device__ unsigned g_scnt[NSEG * 32 * 8];
__device__ __align__(1024) unsigned char g_seg[NRING * 96 * 10240];
__device__ unsigned g_used[NH * 32];
__device__ __align__(1024) uint4 g_part[4 * 36 * 4 * 128];
__device__ int g_err;
#define TSTAMP(i)
#define PROF(idx)
#define PROFP(idx)
#define RSTAMP(k)
#define STAMP(idx)
#define ASTAMP(idx)
#define SSTAMP(k, seg)
#define WSTAMP(idx)

#define DI __device__ __forceinline__
DI uint32_t smem_u32(const void* p) { return (uint32_t)__cvta_generic_to_shared(p); }
DI uint32_t clock32() { uint32_t c; asm volatile("mov.u32 %0, %%clock;" : "=r"(c) :: "memory"); return c; }
DI uint32_t gtime() { uint32_t c; asm volatile("mov.u32 %0, %%globaltimer_lo;" : "=r"(c) :: "memory"); return c; }
DI uint32_t ldg_relaxed32(const void* p) { uint32_t v; asm volatile("ld.relaxed.gpu.global.b32 %0, [%1];" : "=r"(v) : "l"(p) : "memory"); return v; }
DI uint32_t ldg_acquire32(const void* p) { uint32_t v; asm volatile("ld.acquire.gpu.global.b32 %0, [%1];" : "=r"(v) : "l"(p) : "memory"); return v; }
DI void stg_relaxed32(void* p, uint32_t v) { asm volatile("st.relaxed.gpu.global.b32 [%0], %1;" :: "l"(p), "r"(v) : "memory"); }
DI int head_id() { int c; asm volatile("mov.u32 %0, %%clusterid.x;" : "=r"(c)); return c; }
DI uint32_t mapa(uint32_t a, uint32_t r) { uint32_t o; asm("mapa.shared::cluster.u32 %0, %1, %2;" : "=r"(o) : "r"(a), "r"(r)); return o; }
DI void cluster_arrive() { asm volatile("barrier.cluster.arrive.relaxed.aligned;" ::: "memory"); }
DI void cluster_wait() { asm volatile("barrier.cluster.wait.aligned;" ::: "memory"); }
DI void cluster_sync() { asm volatile("barrier.cluster.arrive.release.aligned;\nbarrier.cluster.wait.acquire.aligned;" ::: "memory"); }
DI void mbar_init(uint32_t b, uint32_t c) { asm volatile("mbarrier.init.shared::cta.b64 [%0], %1;" :: "r"(b), "r"(c) : "memory"); }
DI void mbar_expect(uint32_t b, uint32_t tx) { asm volatile("mbarrier.arrive.expect_tx.shared::cta.b64 _, [%0], %1;" :: "r"(b), "r"(tx) : "memory"); }
DI void mbar_arrive(uint32_t b) { asm volatile("mbarrier.arrive.shared::cta.b64 _, [%0];" :: "r"(b) : "memory"); }
DI void mbar_wait(uint32_t b, uint32_t par) {
  asm volatile("{\n.reg .pred p;\n.reg .u32 n, q;\nmov.u32 n, 0;\n"
               "WL: add.u32 n, n, 1;\nshr.u32 q, n, 12;\nxor.b32 q, q, %1;\n"
               "mbarrier.try_wait.parity.shared::cta.b64 p, [%0], q;\n@!p bra.uni WL;\n}"
               :: "r"(b), "r"(par) : "memory");
}
DI void wait_until(uint32_t t) {
  const uint32_t now = gtime();
  t = min(t, now + 8192);
  asm volatile("{\n.reg .pred p;\n.reg .u32 c;\nTL: mov.u32 c, %%globaltimer_lo;\nsetp.lt.u32 p, c, %0;\n@p bra.uni TL;\n}" :: "r"(t) : "memory");
}
#define PIN(v) v = __shfl_xor_sync(0xffffffffu, v, 0)
#define SCHED_FENCE(k) asm volatile("{\n.reg .pred p;\nsetp.eq.u32 p, %0, %1;\n@p exit;\n}" :: "r"(fence_reg), "r"(k) : "memory")
#define MEM_ORDER(k) asm volatile("{\n.reg .pred p;\nsetp.eq.u32 p, %0, %1;\n@p st.shared.u32 [%0], %0;\n}" :: "r"(fence_reg), "r"(k + 64) : "memory")
DI void bar_sync(int id, int n) { asm volatile("bar.sync %0, %1;" :: "r"(id), "r"(n) : "memory"); }
DI void bar_arrive(int id, int n) { asm volatile("bar.arrive %0, %1;" :: "r"(id), "r"(n) : "memory"); }
DI void fence_async() { asm volatile("fence.proxy.async.shared::cta;" ::: "memory"); }
DI void st_async4(uint32_t a, uint32_t x, uint32_t y, uint32_t z, uint32_t w, uint32_t mb) {
  asm volatile("st.async.weak.shared::cluster.mbarrier::complete_tx::bytes.v4.b32 [%0], {%1,%2,%3,%4}, [%5];"
               :: "r"(a), "r"(x), "r"(y), "r"(z), "r"(w), "r"(mb) : "memory");
}
DI void st_async2(uint32_t a, uint32_t x, uint32_t y, uint32_t mb) {
  asm volatile("st.async.weak.shared::cluster.mbarrier::complete_tx::bytes.v2.b32 [%0], {%1,%2}, [%3];"
               :: "r"(a), "r"(x), "r"(y), "r"(mb) : "memory");
}
DI void sts32(uint32_t a, uint32_t x) { asm volatile("st.shared.b32 [%0], %1;" :: "r"(a), "r"(x) : "memory"); }
DI void sts64(uint32_t a, uint32_t x, uint32_t y) { asm volatile("st.shared.v2.b32 [%0], {%1,%2};" :: "r"(a), "r"(x), "r"(y) : "memory"); }
DI void sts128(uint32_t a, uint32_t x, uint32_t y, uint32_t z, uint32_t w) {
  asm volatile("st.shared.v4.b32 [%0], {%1,%2,%3,%4};" :: "r"(a), "r"(x), "r"(y), "r"(z), "r"(w) : "memory");
}
DI uint32_t lds32(uint32_t a) { uint32_t x; asm volatile("ld.shared.b32 %0, [%1];" : "=r"(x) : "r"(a) : "memory"); return x; }
DI void lds64(uint32_t a, uint32_t& x, uint32_t& y) { asm volatile("ld.shared.v2.b32 {%0,%1}, [%2];" : "=r"(x), "=r"(y) : "r"(a) : "memory"); }
DI void lds128(uint32_t a, uint32_t* r) {
  asm volatile("ld.shared.v4.b32 {%0,%1,%2,%3}, [%4];" : "=r"(r[0]), "=r"(r[1]), "=r"(r[2]), "=r"(r[3]) : "r"(a) : "memory");
}
DI void lds128f(uint32_t a, float* r) {
  asm volatile("ld.shared.v4.f32 {%0,%1,%2,%3}, [%4];" : "=f"(r[0]), "=f"(r[1]), "=f"(r[2]), "=f"(r[3]) : "r"(a) : "memory");
}
DI void lds64f(uint32_t a, float* r) { asm volatile("ld.shared.v2.f32 {%0,%1}, [%2];" : "=f"(r[0]), "=f"(r[1]) : "r"(a) : "memory"); }
DI void ldsm4t(uint32_t* r, uint32_t a) {
  asm volatile("ldmatrix.sync.aligned.m8n8.x4.trans.shared.b16 {%0,%1,%2,%3}, [%4];"
               : "=r"(r[0]), "=r"(r[1]), "=r"(r[2]), "=r"(r[3]) : "r"(a) : "memory");
}
DI void ldsm4t_in(uint32_t* r, uint32_t a, uint32_t t) {
  asm volatile("{\n.reg .pred p;\nsetp.ne.u32 p, %5, 0;\n@p ldmatrix.sync.aligned.m8n8.x4.trans.shared.b16 {%0,%1,%2,%3}, [%4];\n}"
               : "+r"(r[0]), "+r"(r[1]), "+r"(r[2]), "+r"(r[3]) : "r"(a), "r"(t) : "memory");
}
DI void lds128_in(uint32_t* r, uint32_t a, uint32_t t) {
  asm volatile("{\n.reg .pred p;\nsetp.ne.u32 p, %5, 0;\n@p ld.shared.v4.b32 {%0,%1,%2,%3}, [%4];\n}"
               : "+r"(r[0]), "+r"(r[1]), "+r"(r[2]), "+r"(r[3]) : "r"(a), "r"(t) : "memory");
}
DI void ldsm2t_in(uint32_t* r, uint32_t a, uint32_t t) {
  asm volatile("{\n.reg .pred p;\nsetp.ne.u32 p, %3, 0;\n@p ldmatrix.sync.aligned.m8n8.x2.trans.shared.b16 {%0,%1}, [%2];\n}" : "+r"(r[0]), "+r"(r[1]) : "r"(a), "r"(t) : "memory");
}
DI void reserve2(uint32_t* r) { asm volatile("{\n.reg .u64 t;\nmov.u64 t, %%clock64;\nmov.b64 {%0, %1}, t;\n}" : "=r"(r[0]), "=r"(r[1])); }
DI void scale_sum(float& x, float& y, float s, uint32_t t) {
  asm volatile("{\n.reg .pred p;\nsetp.ne.u32 p, %2, 0;\n@p mul.f32 %0, %0, %1;\n}" : "+f"(y) : "f"(s), "r"(t));
  asm volatile("{\n.reg .pred p;\nsetp.ne.u32 p, %3, 1;\n@p fma.rn.f32 %0, %0, %1, %2;\n}" : "+f"(x) : "f"(s), "f"(y), "r"(t));
}
DI void ldsm4(uint32_t* r, uint32_t a) {
  asm volatile("ldmatrix.sync.aligned.m8n8.x4.shared.b16 {%0,%1,%2,%3}, [%4];"
               : "=r"(r[0]), "=r"(r[1]), "=r"(r[2]), "=r"(r[3]) : "r"(a) : "memory");
}
DI void st_async1(uint32_t a, uint32_t x, uint32_t mb) {
  asm volatile("st.async.weak.shared::cluster.mbarrier::complete_tx::bytes.b32 [%0], %1, [%2];" :: "r"(a), "r"(x), "r"(mb) : "memory");
}
DI void stsm4(uint32_t a, uint32_t x, uint32_t y, uint32_t z, uint32_t w) {
  asm volatile("stmatrix.sync.aligned.m8n8.x4.shared.b16 [%0], {%1,%2,%3,%4};" :: "r"(a), "r"(x), "r"(y), "r"(z), "r"(w) : "memory");
}
DI void stsm4t(uint32_t a, uint32_t x, uint32_t y, uint32_t z, uint32_t w) {
  asm volatile("stmatrix.sync.aligned.m8n8.x4.trans.shared.b16 [%0], {%1,%2,%3,%4};" :: "r"(a), "r"(x), "r"(y), "r"(z), "r"(w) : "memory");
}
DI uint32_t pack_bf16(float lo, float hi) { uint32_t r; asm("cvt.rn.bf16x2.f32 %0, %1, %2;" : "=r"(r) : "f"(hi), "f"(lo)); return r; }
DI uint32_t pack_f16(float lo, float hi) { uint32_t r; asm("cvt.rn.f16x2.f32 %0, %1, %2;" : "=r"(r) : "f"(hi), "f"(lo)); return r; }
DI float ex2(float x) { float y; asm("ex2.approx.ftz.f32 %0, %1;" : "=f"(y) : "f"(x)); return y; }
DI float rcp(float x) { float y; asm("rcp.approx.ftz.f32 %0, %1;" : "=f"(y) : "f"(x)); return y; }
DI float bf_lo(uint32_t x) { return __uint_as_float(x << 16); }
DI float bf_hi(uint32_t x) { return __uint_as_float(x & 0xffff0000u); }
DI void mma16816(float* d, const uint32_t* a, uint32_t b0, uint32_t b1) {
  asm volatile("mma.sync.aligned.m16n8k16.row.col.f32.bf16.bf16.f32 {%0,%1,%2,%3}, {%4,%5,%6,%7}, {%8,%9}, {%0,%1,%2,%3};"
               : "+f"(d[0]), "+f"(d[1]), "+f"(d[2]), "+f"(d[3]) : "r"(a[0]), "r"(a[1]), "r"(a[2]), "r"(a[3]), "r"(b0), "r"(b1));
}
DI void mma16816z(float* d, const uint32_t* a, uint32_t b0, uint32_t b1) {
  asm volatile("mma.sync.aligned.m16n8k16.row.col.f32.bf16.bf16.f32 {%0,%1,%2,%3}, {%4,%5,%6,%7}, {%8,%9}, {%10,%10,%10,%10};"
               : "=f"(d[0]), "=f"(d[1]), "=f"(d[2]), "=f"(d[3]) : "r"(a[0]), "r"(a[1]), "r"(a[2]), "r"(a[3]), "r"(b0), "r"(b1), "f"(0.f));
}
DI void mma1688z(float* d, uint32_t a0, uint32_t a1, uint32_t b0) {
  asm volatile("mma.sync.aligned.m16n8k8.row.col.f32.bf16.bf16.f32 {%0,%1,%2,%3}, {%4,%5}, {%6}, {%7,%7,%7,%7};"
               : "=f"(d[0]), "=f"(d[1]), "=f"(d[2]), "=f"(d[3]) : "r"(a0), "r"(a1), "r"(b0), "f"(0.f));
}
DI void mma1688(float* d, uint32_t a0, uint32_t a1, uint32_t b0) {
  asm volatile("mma.sync.aligned.m16n8k8.row.col.f32.bf16.bf16.f32 {%0,%1,%2,%3}, {%4,%5}, {%6}, {%0,%1,%2,%3};"
               : "+f"(d[0]), "+f"(d[1]), "+f"(d[2]), "+f"(d[3]) : "r"(a0), "r"(a1), "r"(b0));
}
DI void ldsm2t(uint32_t* r, uint32_t a) {
  asm volatile("ldmatrix.sync.aligned.m8n8.x2.trans.shared.b16 {%0,%1}, [%2];" : "=r"(r[0]), "=r"(r[1]) : "r"(a) : "memory");
}
DI uint32_t add_bf16(uint32_t a, uint32_t b) { uint32_t r; asm("add.rn.bf16x2 %0, %1, %2;" : "=r"(r) : "r"(a), "r"(b)); return r; }
DI uint32_t mul_bf16(uint32_t a, uint32_t b) { uint32_t r; asm("mul.rn.bf16x2 %0, %1, %2;" : "=r"(r) : "r"(a), "r"(b)); return r; }
DI uint64_t make_desc(uint32_t addr, uint32_t lbo, uint32_t sbo, uint32_t swz) {
  return (uint64_t)((addr & 0x3FFFF) >> 4) | ((uint64_t)(lbo >> 4) << 16) | ((uint64_t)(sbo >> 4) << 32) | ((uint64_t)swz << 62);
}
DI uint64_t desc_at(uint32_t a16, uint32_t lbo, uint32_t sbo, uint32_t swz) {
  uint64_t d; asm("mov.b64 %0, {%1, %2};" : "=l"(d) : "r"(a16 + ((lbo >> 4) << 16)), "r"((sbo >> 4) | (swz << 30)));
  return d;
}
#define WG_FENCE() asm volatile("wgmma.fence.sync.aligned;" ::: "memory")
#define WG_COMMIT() asm volatile("wgmma.commit_group.sync.aligned;" ::: "memory")
#define WG_WAIT(n) asm volatile("wgmma.wait_group.sync.aligned %0;" :: "n"(n) : "memory")
#define ACC8(d, o) "+f"(d[o]), "+f"(d[o + 1]), "+f"(d[o + 2]), "+f"(d[o + 3]), "+f"(d[o + 4]), "+f"(d[o + 5]), "+f"(d[o + 6]), "+f"(d[o + 7])
DI void wgmma_n32_rs(float* d, uint32_t a0, uint32_t a1, uint32_t a2, uint32_t a3, uint64_t db, int acc) {
  asm volatile("{\n.reg .pred p;\nsetp.ne.b32 p, %21, 0;\n"
               "wgmma.mma_async.sync.aligned.m64n32k16.f32.bf16.bf16 {%0,%1,%2,%3,%4,%5,%6,%7,%8,%9,%10,%11,%12,%13,%14,%15}, "
               "{%16,%17,%18,%19}, %20, p, 1, 1, 0;\n}\n"
               : ACC8(d, 0), ACC8(d, 8) : "r"(a0), "r"(a1), "r"(a2), "r"(a3), "l"(db), "r"(acc));
}
template <int TA>
DI void wgmma_n32_ss(float* d, uint64_t da, uint64_t db, int acc) {
  asm volatile("{\n.reg .pred p;\nsetp.ne.b32 p, %18, 0;\n"
               "wgmma.mma_async.sync.aligned.m64n32k16.f32.bf16.bf16 {%0,%1,%2,%3,%4,%5,%6,%7,%8,%9,%10,%11,%12,%13,%14,%15}, "
               "%16, %17, p, 1, 1, %19, 1;\n}\n"
               : ACC8(d, 0), ACC8(d, 8) : "l"(da), "l"(db), "r"(acc), "n"(TA));
}
DI void tma_load(uint32_t dst, const CUtensorMap* m, int c0, int c1, uint32_t mb) {
  asm volatile("cp.async.bulk.tensor.2d.shared::cluster.global.mbarrier::complete_tx::bytes [%0], [%1, {%3, %4}], [%2];"
               :: "r"(dst), "l"(m), "r"(mb), "r"(c0), "r"(c1) : "memory");
}
DI void tma_load3(uint32_t dst, const CUtensorMap* m, int row, uint32_t mb) {
  asm volatile("cp.async.bulk.tensor.3d.shared::cluster.global.mbarrier::complete_tx::bytes [%0], [%1, {%3, %4, %3}], [%2];"
               :: "r"(dst), "l"(m), "r"(mb), "r"(0), "r"(row) : "memory");
}
DI bool elect_one() {
  uint32_t p;
  asm volatile("{\n.reg .pred p;\nelect.sync _|p, 0xffffffff;\nselp.u32 %0, 1, 0, p;\n}" : "=r"(p));
  return p;
}
DI void bulk_s2s(uint32_t dst, uint32_t src, uint32_t bytes, uint32_t mb) {
  asm volatile("cp.async.bulk.shared::cluster.shared::cta.mbarrier::complete_tx::bytes [%0], [%1], %2, [%3];"
               :: "r"(dst), "r"(src), "r"(bytes), "r"(mb) : "memory");
}
DI void tma_prefetch(const CUtensorMap* m, int c0, int c1) {
  asm volatile("cp.async.bulk.prefetch.tensor.2d.L2.global.tile [%0, {%1, %2}];" :: "l"(m), "r"(c0), "r"(c1) : "memory");
}
DI void tma_store(const CUtensorMap* m, uint32_t src, int c0, int c1) {
  asm volatile("cp.async.bulk.tensor.2d.global.shared::cta.bulk_group [%0, {%2, %3}], [%1];" :: "l"(m), "r"(src), "r"(c0), "r"(c1) : "memory");
}
DI uint4 ldg_relaxed(const void* p) {
  uint4 v;
  asm volatile("ld.relaxed.gpu.global.v4.b32 {%0,%1,%2,%3}, [%4];" : "=r"(v.x), "=r"(v.y), "=r"(v.z), "=r"(v.w) : "l"(p) : "memory");
  return v;
}
DI void stg_relaxed(void* p, uint32_t x, uint32_t y, uint32_t z, uint32_t w) {
  asm volatile("st.relaxed.gpu.global.v4.b32 [%0], {%1,%2,%3,%4};" :: "l"(p), "r"(x), "r"(y), "r"(z), "r"(w) : "memory");
}
DI void red_f16x8(void* p, uint32_t x, uint32_t y, uint32_t z, uint32_t w) {
  asm volatile("red.relaxed.gpu.global.add.noftz.v4.f16x2 [%0], {%1,%2,%3,%4};" :: "l"(p), "r"(x), "r"(y), "r"(z), "r"(w) : "memory");
}
DI void sq_acc(uint32_t& a, uint32_t x) { asm("fma.rn.bf16x2 %0, %1, %1, %0;" : "+r"(a) : "r"(x)); }
DI __half2 amax4(__half2 h, const uint32_t* v) {
  h = __hmax2_nan(__hmax2_nan(h, __habs2(*(const __half2*)&v[0])), __habs2(*(const __half2*)&v[1]));
  return __hmax2_nan(__hmax2_nan(h, __habs2(*(const __half2*)&v[2])), __habs2(*(const __half2*)&v[3]));
}
DI uint32_t wexp(__half2 h) { const uint32_t u = *(const uint32_t*)&h; return __reduce_max_sync(0xffffffffu, max((u >> 16) & 0x7fffu, u & 0x7fffu)) >> 7; }
DI float max10(const float* a) {
  return fmaxf(fmaxf(fmaxf(fmaxf(a[0], a[1]), fmaxf(a[2], a[3])), fmaxf(fmaxf(a[4], a[5]), fmaxf(a[6], a[7]))), fmaxf(a[8], a[9]));
}
DI float quad_max(float m) {
  return fmaxf(fmaxf(m, __shfl_xor_sync(0xffffffffu, m, 1)), fmaxf(__shfl_xor_sync(0xffffffffu, m, 2), __shfl_xor_sync(0xffffffffu, m, 3)));
}
DI float warp_sum(float v) {
#pragma unroll
  for (int o = 16; o; o >>= 1) v += __shfl_xor_sync(0xffffffffu, v, o);
  return v;
}

constexpr int SM_WO3 = 0;
constexpr int SM_X = 16384;
constexpr int XT = 36864;
constexpr int SM_EXP = 126976;
constexpr int SEGB = 10240;
constexpr int SM_BLK = SM_EXP + 8192;
constexpr int SM_VC = SM_BLK + 4 * SEGB;
constexpr int SM_PART = SM_VC + 16384;
constexpr int SM_QM = SM_PART + 4096;
constexpr int SM_E = SM_QM + 1024;
constexpr int SM_VM = SM_E + 1536;
constexpr int SM_OB = SM_VM + 2048;
constexpr int SM_FB = SM_OB + 2048;
constexpr int SM_STAGE = SM_X + XT;
constexpr int SM_MISC = 210944;
constexpr int SM_WOST = 212992;
constexpr int SM_MEM = SM_WOST;
constexpr int SM_MAX = SM_MEM + 11264;
#define MEM_BLK(q) ((q) / 3 * 4096 + (q) % 3 * 1024)
constexpr int SM_TOTAL = 229376;
constexpr int MB_W = SM_MISC;
constexpr int MB_WO = SM_MISC + 24;
constexpr int MB_WO3 = SM_MISC + 32;
constexpr int MB_X = SM_MISC + 40;
constexpr int MB_S = SM_MISC + 64;
constexpr int MB_F = SM_MISC + 72;
constexpr int MB_VX = SM_MISC + 80;
constexpr int SC_FPAR = SM_MISC + 136;
constexpr int SC_DEAD = SM_MISC + 96;
constexpr int SC_UNSC = SM_MISC + 112;
constexpr int SC_EPOCH = SM_MISC + 128;
constexpr int SC_EXPW = SM_MISC + 132;
constexpr int SC_ONES = SM_MISC + 144;
constexpr int SC_SS = SM_MISC + 160;
constexpr int SC_LAT = SM_MISC + 224;
constexpr int SC_XMAX = SM_MISC + 256;
constexpr int SC_PROF = 229376;

constexpr float SM_SCALE = 0.08838834764831845f;
constexpr float LOG2E = 1.4426950408889634f;
constexpr float E_LIM = 20.f;

template <bool B> struct BoolC { static constexpr bool value = B; };
struct RMaps { CUtensorMap x, wq, wk, wv, wo; unsigned char* red; uint32_t poll; };

DI uint32_t latest_hint(uint32_t h, uint32_t d, int s) {
  const uint32_t x = (((h | 0xc0c0c0c0u) - ((d >> 5) & 63) * 0x01010101u) & 0x3f3f3f3fu) | ((h ^ (((s >> 2) + 1) & 3) * 0x40404040u) & 0xc0c0c0c0u);
  const uint32_t y = __vmaxu2(x & 0x00ff00ffu, (x >> 8) & 0x00ff00ffu);
  return __reduce_max_sync(0xffffffffu, max(y & 0xffffu, y >> 16));
}
DI uint32_t near_half(uint32_t sb) {
  uint32_t a, b; lds64(sb + SC_LAT, a, b);
  return a > b;
}

template <int RT, int K0, int K1, bool D32 = false>
DI void xproj(float* acc, const uint32_t (&wa)[2][18][4], uint64_t xd) {
  if (XP & 1) return;
  WG_FENCE();
#pragma unroll
  for (int k = K0; k < ((XP & 128) ? K0 + 1 : K1); k++)
  {
    uint64_t d = xd + (uint64_t)(((k >> 1) * 4096 + (k & 1) * 32) >> 4);
    if (D32) asm("mov.b64 %0, {%1, %2};" : "=l"(d) : "r"((uint32_t)xd + (((k >> 1) * 4096 + (k & 1) * 32) >> 4)), "r"((uint32_t)(xd >> 32)));
    wgmma_n32_rs(acc, wa[RT][k][0], wa[RT][k][1], wa[RT][k][2], wa[RT][k][3], d, k != 0);
  }
  WG_COMMIT();
}

DI void seg_store(int seg, uint32_t sb, uint32_t off, uint32_t bytes) {
  asm volatile("cp.async.bulk.global.shared::cta.bulk_group [%0], [%1], %2;"
               :: "l"(g_seg + ((size_t)(seg % NRING) * 96 + blockIdx.x) * SEGB + off), "r"(sb + SM_BLK + (seg & 3) * SEGB + off), "r"(bytes) : "memory");
  asm volatile("cp.async.bulk.commit_group;" ::: "memory");
}
DI void seg_publish(int seg) {
  asm volatile("cp.async.bulk.wait_group 0;" ::: "memory");
  asm volatile("red.relaxed.gpu.global.add.u32 [%0], 1;" :: "l"(&g_scnt[(seg * 32 + blockIdx.x / 3) * 8]) : "memory");
  SSTAMP(10, seg);
}

#define PACE 1200
#define PORD 0
DI void load_weights(uint32_t sb, const RMaps& tm, uint32_t rank, int c) {
  const int h = blockIdx.x / 3;
  if (c < 3) {
    mbar_expect(sb + MB_W + 8 * c, 49152);
    tma_load(sb + SM_STAGE + c * 49152, rank < 2 ? &tm.wk : &tm.wv, h * DH + (rank == 1 ? 64 : 0), c * 192, sb + MB_W + 8 * c);
    tma_load(sb + SM_STAGE + c * 49152 + 24576, rank < 2 ? &tm.wq : &tm.wv, h * DH + (rank == 0 ? 0 : 64), c * 192, sb + MB_W + 8 * c);
  } else {
    tma_prefetch(&tm.wo, rank * 192, h * DH);
    mbar_expect(sb + MB_WO, 16384);
    mbar_expect(sb + MB_WO3, 32768);
    tma_load(sb + SM_WOST, &tm.wo, rank * 192 + 64, h * DH, sb + MB_WO3);
    tma_load(sb + SM_WO3, &tm.wo, rank * 192 + 128, h * DH, sb + MB_WO3);
  }
}

DI void proj_role(const uint32_t sb, const RMaps& tm, const uint32_t rank, const int wg, const int w, const int lane) {
  const bool qk = rank < 2;
  uint32_t wa[2][18][4];
  {
    const int rr = (lane & 7) + ((lane >> 4) << 3);
    const uint32_t col = ((2 * w + ((lane >> 3) & 1)) ^ (lane & 7)) << 4;
    float ss = 0.f;
#pragma unroll
    for (int c = 0; c < 3; c++) {
      mbar_wait(sb + MB_W + 8 * c, 0);
      if (threadIdx.x == 0) SSTAMP(11, c);
#pragma unroll
      for (int rt = 0; rt < 2; rt++)
#pragma unroll
        for (int k = 0; k < 6; k++)
          ldsm4t(wa[rt][c * 6 + k], sb + SM_STAGE + c * 49152 + (rt ^ wg) * 24576 + (64 * (k >> 1) + 32 * wg + 16 * (k & 1) + rr) * 128 + col);
      if (c < 2) {
        fence_async();
        bar_sync(3, 256);
        if (threadIdx.x == 0) {
          if (c == 0) tma_load3(sb + SM_X + XT, &tm.x, 32, sb + MB_X + 8);
          else { tma_load(sb + SM_X + 2 * XT, &tm.wo, rank * 192, (blockIdx.x / 3) * DH, sb + MB_WO); SSTAMP(11, 11); }
        }
        __syncwarp();
      }
      uint32_t q[4] = {0, 0, 0, 0};
#pragma unroll
      for (int rt = 0; rt < 2; rt++)
#pragma unroll
        for (int k = 0; k < 6; k++)
#pragma unroll
          for (int i = 0; i < 4; i++) sq_acc(q[i], wa[rt][c * 6 + k][i]);
#pragma unroll
      for (int i = 0; i < 4; i++) ss += bf_lo(q[i]) + bf_hi(q[i]);
    }
    ss = warp_sum(ss);
    fence_async();
    cluster_arrive();
    if (lane == 0) sts32(sb + SC_SS + 4 * (wg * 4 + w), qk ? 0 : __float_as_uint(ss));
    bar_arrive(11, 384);
  }
  STAMP(1);
  mbar_wait(sb + MB_X, 0);
  STAMP(2);

  uint32_t t16 = sb + (w * 32 + lane) * 16;
  uint32_t mem_a = sb + SM_MEM + wg * 512 + lane * 16;
  uint32_t fin_a = sb + (lane & 7) * 16 + SM_BLK + (qk ? (wg ^ 1) * 4096 + w * 256 + (lane & 8) * 16 + (lane & 16) * 64
                                              : wg * 4096 + w * 1024 + (lane & 8) * 64 + (lane & 16) * 8);
  PIN(t16); PIN(mem_a); PIN(fin_a);
  const uint32_t fence_reg = mem_a;
  const uint32_t fin2 = qk ? 2048 : 256;
  float acc[16];
  const uint64_t xd0 = make_desc(sb + SM_X + wg * 64, 16, 1024, 1);
  auto do_export = [&]() {
    WG_WAIT(0);
#pragma unroll
    for (int i = 0; i < 2; i++)
      sts128(t16 + SM_EXP + wg * 4096 + i * 2048, pack_bf16(acc[8 * i], acc[8 * i + 1]), pack_bf16(acc[8 * i + 2], acc[8 * i + 3]),
             pack_bf16(acc[8 * i + 4], acc[8 * i + 5]), pack_bf16(acc[8 * i + 6], acc[8 * i + 7]));
  };
  uint32_t o[8];
  auto import = [&]() { lds128(t16 + SM_EXP + (wg ^ 1) * 4096, o); lds128(t16 + SM_EXP + (wg ^ 1) * 4096 + 2048, o + 4); };
  auto finish = [&](int seg) {
    const uint32_t a = fin_a + (seg & 3) * SEGB;
    WG_WAIT(0);
#pragma unroll
    for (int i = 0; i < 8; i++) o[i] = FIN16 ? add_bf16(pack_bf16(acc[2 * i], acc[2 * i + 1]), o[i]) : pack_bf16(acc[2 * i] + bf_lo(o[i]), acc[2 * i + 1] + bf_hi(o[i]));
    stsm4(a, o[0], o[1], o[2], o[3]);
    stsm4(a + fin2, o[4], o[5], o[6], o[7]);
  };
  auto send_v = [&](int seg, int dst) {
    fence_async();
    if (seg < NSEG - 1 && !(XP & 2) && elect_one())
      bulk_s2s(mapa(sb + SM_VC + (seg & 1) * 8192, dst), sb + SM_BLK + (seg & 3) * SEGB, 8192, mapa(sb + MB_VX + (seg & 1) * 8, dst));
    __syncwarp();
  };
  auto wait_v = [&](int seg) {
    if (seg < NSEG - 1 && !(XP & 2)) {
      mbar_wait(sb + MB_VX + (seg & 1) * 8, (seg >> 1) & 1);
      if (elect_one()) mbar_expect(sb + MB_VX + (seg & 1) * 8, 8192);
      __syncwarp();
    }
  };
  bar_sync(3, 256);
  xproj<1, 0, 18>(acc, wa, xd0);
  do_export();
  SCHED_FENCE(11);
  xproj<0, 0, 18>(acc, wa, xd0);
  bar_sync(3, 256);
  if (threadIdx.x == 0) SSTAMP(11, 12);
  cluster_wait();
  if (threadIdx.x == 0) SSTAMP(11, 13);
  mbar_wait(sb + MB_X + 8, 0);
  import();
  finish(0);
  SCHED_FENCE(12);
  bar_sync(3, 256);
  uint64_t dA = xd0 + (XT >> 4);
  xproj<1, 0, 18>(acc, wa, dA);
  if (!qk && wg == 0 && w < 2) send_v(0, w);
  do_export();
  if (qk && wg == 0 && w == 0) wait_v(0);
  bar_arrive(13, 384);
  if (!qk) {
    SCHED_FENCE(15);
    xproj<0, 0, 18>(acc, wa, dA);
    if (threadIdx.x == 0 && !(XP & 8)) { mbar_expect(sb + MB_X, XT); tma_load3(sb + SM_X, &tm.x, 96, sb + MB_X); }
    bar_sync(3, 256);
    mbar_wait(sb + MB_X + 16, 0);
    import();
    finish(1);
    SCHED_FENCE(16);
    bar_sync(3, 256);
    dA += XT >> 4;
    xproj<1, 0, 18>(acc, wa, dA);
    if (wg == 0 && ((w == 0 && VS0) || (w == 1 && VS1))) send_v(1, w);
    do_export();
  }
  if (threadIdx.x == 0) SSTAMP(11, 14);
  bar_sync(0, 384);
  const int ro = __shfl_sync(0xffffffffu, near_half(sb) ^ wg, 0);
  STAMP(5);
  TSTAMP(1);
  const uint32_t always = __shfl_sync(0xffffffffu, lds32(sb + SC_DEAD + 12), 0);
  const int ah = qk ? 1 : 2;
  int b2 = qk ? 2 : 0;
  int s = 0;
  uint32_t hint_lo = (uint32_t)(uint64_t)tm.red + HINT_OFF + blockIdx.x + (lane & 1) * 4096 + (lane >> 1) * 16384;
  PIN(hint_lo);
  auto post_hint = [&]() {
    asm volatile("{\n.reg .pred p;\n.reg .b64 a;\n.reg .u32 t;\nsetp.lt.u32 p, %0, %1;\nmov.b64 a, {%2, %3};\nmov.u32 t, %%globaltimer_lo;\n"
                 "bfe.u32 t, t, 5, 6;\nor.b32 t, t, %4;\n@p st.relaxed.gpu.global.u8 [a], t;\n}"
                 :: "r"(t16), "r"(sb + 128), "r"(hint_lo + RED_SLOT(s)), "r"((uint32_t)((uint64_t)tm.red >> 32)), "r"(((s >> 2) + 1) << 6) : "memory");
  };
  auto memproj = [&](auto second, int id, float u0, float u1, float* r) {
    constexpr bool R1 = decltype(second)::value;
    uint32_t b[NUP][4], b0[4];
    SCHED_FENCE(id);
    bar_sync(R1 ? 2 : 1, 256);
    PROF(0);
    ldsm4t(b0, mem_a);
#pragma unroll
    for (int q = 0; q < NUP; q++) {
      if (R1 && q == 2) {
        bar_sync(11, 256);
        SCHED_FENCE(id + 1);
      }
      ldsm4t(b[q], mem_a + MEM_BLK(q + 1));
    }
    mma16816z(&acc[0], wa[0][0], b0[0], b0[1]);
    mma16816z(&acc[4], wa[1][0], b0[0], b0[1]);
    mma16816z(&acc[8], wa[0][1], b0[2], b0[3]);
    mma16816z(&acc[12], wa[1][1], b0[2], b0[3]);
#pragma unroll
    for (int q = 1; q < 9; q++) {
      uint32_t* const c = b[(q - 1) % NUP];
      mma16816(&acc[0], wa[0][2 * q], c[0], c[1]);
      mma16816(&acc[4], wa[1][2 * q], c[0], c[1]);
      mma16816(&acc[8], wa[0][2 * q + 1], c[2], c[3]);
      mma16816(&acc[12], wa[1][2 * q + 1], c[2], c[3]);
      if (R1 && q + NUP == B3Q) bar_sync(3, 256);
      if (q + NUP < 9) ldsm4t_in(c, mem_a + MEM_BLK(q + NUP), always);
      else if (R1 && q + NUP < 11) lds128_in(c, t16 + SM_PART + (10 - q - NUP) * 2048, always);
      else if (!R1 && GATE && q == GATE) { bar_arrive(11, 256); lds128_in(c, sb + SC_DEAD, always); u0 = u1 = __uint_as_float(c[3]); }
    }
#pragma unroll
    for (int i = 0; i < 8; i++) {
      const float u = i < 4 ? u0 : u1;
      r[i] = R1 ? fmaf(acc[8 + i], u, (acc[i] + __uint_as_float(b[(8 + i / 4) % NUP][i & 3])) * u) : (GATE ? fmaf(acc[i], u, acc[8 + i]) : acc[i] + acc[8 + i]);
    }
  };
  if (ro == 0) {
#pragma unroll 1
    while (true) {
      if (s == 8) STAMP(6);
      float r[8];
      memproj(BoolC<false>(), 30, 0.f, 0.f, r);
      sts128(t16 + SM_PART, __float_as_uint(r[0]), __float_as_uint(r[1]), __float_as_uint(r[2]), __float_as_uint(r[3]));
      sts128(t16 + SM_PART + 2048, __float_as_uint(r[4]), __float_as_uint(r[5]), __float_as_uint(r[6]), __float_as_uint(r[7]));
      bar_arrive(3, 256);
      PROF(1);
      bar_sync(9, 256);
      if (s == NSEG - 1) break;
      post_hint();
      if (w == 1) {
        uint32_t m[8];
        lds128(t16 + SM_MAX - 512, m); lds128(t16 + SM_MAX, m + 4);
        const int em = (wexp(amax4(amax4(*(const __half2*)&m[0], m), m + 4)) >> 3) + (int)(lds32(sb + SC_UNSC + (s & 1) * 8) >> 23) - 15;
        const int ex = max(s ? em : 0, (int)lds32(sb + SC_XMAX + 4 * s)) - 127 + (int)lds32(sb + SC_EXPW);
        sts32(sb + SC_UNSC + (~s & 1) * 8, (127 + min(max(ex, -120), 120)) << 23);
        __syncwarp();
        if (elect_one()) mbar_arrive(sb + MB_S);
      }
      SCHED_FENCE(9);
      bar_sync(5, qk ? N5 : 256);
      PROF(2);
      import();
      xproj<0, 0, NII>(acc, wa, dA);
      if (NII < 18) {
        if (qk) bar_sync(7, 384);
        xproj<0, NII, 18>(acc, wa, dA);
        if (!qk) bar_sync(7, 384);
      } else {
        if (F10) WG_WAIT(0);
        bar_sync(10, 256);
        if (F10) SCHED_FENCE(17);
      }
      dA += (int64_t)(b2 ? XT >> 4 : -(XT >> 3));
      finish(s + ah);
      if (qk || !VLATE(w)) bar_arrive(13, 384);
      PROF(6);
      SCHED_FENCE(14);
      bar_sync(12, 256);
      PROF(7);
      xproj<1, 0, 18, true>(acc, wa, dA);
      bar_arrive(14, 256);
      b2 = b2 == 2 ? 0 : b2 + 1;
      s++;
      if (!qk && VLATE(w)) { bar_sync(13, 384); send_v(s + 1, w); }
      PROFP(8);
      do_export();
      s--; RSTAMP(6); s++;
      PROFP(3);
    }
    if (!qk) bar_arrive(5, 256);
  } else {
#pragma unroll 1
    while (true) {
      if (s == 8) STAMP(6);
      const uint32_t tl = ((t16 >> 8) ^ wg) & 1, am = (t16 & ~256u) - w * 256;
      const float un = __uint_as_float(lds32(sb + SC_UNSC + (s & 1) * 8));
      float r[8];
      if (qk) {
        uint32_t a0 = am + (tl ? SM_QM : SM_BLK + 8192 + (s & 3) * SEGB);
        float u0 = wg ? un * (SM_SCALE * LOG2E) : un, u1 = wg ? un : un * (SM_SCALE * LOG2E);
        PIN(a0); PIN(u0); PIN(u1);
        memproj(BoolC<true>(), 32, u0, u1, r);
        stsm4(a0, pack_bf16(r[0], r[1]), pack_bf16(r[2], r[3]), pack_bf16(r[4], r[5]), pack_bf16(r[6], r[7]));
        bar_arrive(4, 256);
      } else {
        const uint32_t d0 = s < NSEG - 1 ? 0 : 2, d1 = s < NSEG - 1 ? 1 : 2;
        uint32_t r0 = mapa(t16 + SM_VM, d0), r1 = mapa(t16 + SM_VM, d1);
        PIN(r0); PIN(r1);
        memproj(BoolC<true>(), 34, un, un, r);
        const uint32_t p0 = pack_bf16(r[0], r[1]), p1 = pack_bf16(r[2], r[3]), p2 = pack_bf16(r[4], r[5]), p3 = pack_bf16(r[6], r[7]);
        const uint32_t v0 = wg ? p2 : p0, v1 = wg ? p3 : p1, v2 = wg ? p0 : p2, v3 = wg ? p1 : p3;
        st_async4(r0, v0, v1, v2, v3, mapa(sb + MB_S, d0));
        st_async4(r1, v0, v1, v2, v3, mapa(sb + MB_S, d1));
        bar_arrive(5, 256);
        if (EXB && s < NSEG - 1) bar_arrive(15, 160);
        sts128(t16 + SM_VM, v0, v1, v2, v3);
        stsm4(am + SM_BLK + 8192 + (s & 3) * SEGB + tl * 1024, p0, p1, p2, p3);
        __syncwarp();
        if (elect_one()) mbar_arrive(sb + MB_S);
      }
      if (s == NSEG - 1) break;
      if (EXPOS >= 5 && (B15 || !qk) && !(XP & 256)) bar_arrive(15, 160);
      PROF(1);
      auto rearm = [&]() { mbar_wait(sb + MB_S, s & 1); if (elect_one()) mbar_expect(sb + MB_S, qk ? 640 + 2048 : 1280); __syncwarp(); };
      if (w == 1) {
        if ((t16 & 384) == 0) stg_relaxed(tm.red + (RED_SLOT(s + 2) + RED_LINE(blockIdx.x)) + (t16 & 112), 0, 0, 0, 0);
      } else if (w == 0) {
        const int tn = s + ah + 1;
        if (RFW) mbar_wait(sb + MB_S, s & 1);
        if (tn + 1 < NSEG && !(XP & 8) && elect_one()) {
          const int b0 = b2 == 2 ? 0 : b2 + 1;
          mbar_expect(sb + MB_X + 8 * b0, XT);
          tma_load3(sb + SM_X + b0 * XT, &tm.x, (tn + 1) * 32, sb + MB_X + 8 * b0);
        }
        if (tn < NSEG && (!(XP & 8) || tn < 3)) mbar_wait(sb + MB_X + 8 * b2, (tn / 3) & 1);
      } else if (w == 2) {
        if (!qk) { if (VS0 == 0) send_v(s + 1, 0); if (VS1 == 0) send_v(s + 1, 1); }
      } else if (qk || !NIC) {
        rearm();
      }
      __syncwarp();
      import();
      PROF(4);
      SCHED_FENCE(10);
      if (NIC) {
        if (qk) bar_sync(7, NII < 18 ? 384 : 256);
        xproj<0, 0, NIC>(acc, wa, dA);
        if (!qk) { if (w == 3) rearm(); bar_sync(7, NII < 18 ? 384 : 256); }
      } else {
        bar_sync(7, NII < 18 ? 384 : 256);
      }
      xproj<0, NIC, 18>(acc, wa, dA);
      bar_arrive(12, 256);
      dA += (int64_t)(b2 ? XT >> 4 : -(XT >> 3));
      finish(s + ah);
      if (qk && w == 0) wait_v(s + 1);
      bar_arrive(13, 384);
      PROF(6);
      SCHED_FENCE(13);
      bar_sync(14, 256);
      PROF(7);
      xproj<1, 0, 18>(acc, wa, dA);
      b2 = b2 == 2 ? 0 : b2 + 1;
      s++;
      PROFP(8);
      do_export();
      s--; RSTAMP(7); s++;
      PROFP(3);
    }
  }
  bar_arrive(0, 384);
  STAMP(3);
  TSTAMP(2);
  cluster_sync();
  STAMP(4);
}

DI void attn_role(const uint32_t sb, unsigned char* smem_raw, const RMaps& tm, const uint32_t RANK, const bf16* __restrict__ x, const bf16* __restrict__ mem0,
                  const int w, const int lane) {
  const int t2 = w * 32 + lane;
  uint32_t wo[8][4], w1[8][4];
  const uint32_t wo_lane = sb + ((lane & 7) + ((lane >> 4) << 3)) * 128 + (((w + 4 * ((lane >> 3) & 1)) ^ (lane & 7)) << 4);
  unsigned char* const g_red = tm.red;
  {
    const uint32_t tag = *(volatile unsigned*)&g_epoch + 1;
    if (w == 0) {
      stg_relaxed(g_red + RED_SLOT(t2 >> 3) + RED_LINE(blockIdx.x) + (t2 & 7) * 16, 0, 0, 0, 0);
      asm volatile("st.relaxed.gpu.global.u8 [%0], 0;" :: "l"(g_red + RED_SLOT(t2) + HINT_OFF + (t2 & 4) * 1024 + (t2 >> 3) * 16384 + blockIdx.x) : "memory");
    }
    uint4 xv[18];
    uint32_t mv[20];
#pragma unroll
    for (int i = 0; i < 20; i++) mv[i] = i < 18 ? ((const uint32_t*)mem0)[(lane >> 2) * (DM / 2) + (w * 18 + i) * 4 + (lane & 3)] : 0;
#pragma unroll
    for (int i = 0; i < 18; i++) xv[i] = blockIdx.x < NSEG ? ((const uint4*)(x + blockIdx.x * 32 * DM))[t2 + 128 * i] : make_uint4(0, 0, 0, 0);
    bar_sync(0, 384);
    cluster_arrive();
    if (PACE && w == 3) {
      const uint32_t t0 = gtime();
#pragma unroll 1
      for (int c = 1; c < 4; c++) {
        wait_until(t0 + c * PACE);
        if (elect_one()) load_weights(sb, tm, RANK, PORD ? (c == 1 ? 3 : c - 1) : c);
        __syncwarp();
      }
    }
    __half2 hx = __float2half2_rn(0.f);
#pragma unroll
    for (int i = 0; i < 18; i++) hx = amax4(hx, &xv[i].x);
    if (blockIdx.x == 0)
#pragma unroll
      for (int i = 0; i < 5; i++) hx = amax4(hx, &mv[4 * i]);
    sts32(sb + SC_SS + 4 * (12 + w), wexp(hx));
    if (t2 == 0) { sts32(sb + SC_EPOCH, (tag - 1) * NSEG + 2 - NRING); sts32(sb + SC_UNSC, __float_as_uint(1.f)); sts128(sb + SC_DEAD, 0, 0, 0, 0x3f800000u); sts64(sb + SC_FPAR, 0, 0); sts128(sb + SC_ONES, 0x3f803f80u, 0x3f803f80u, 0x3f803f80u, 0x3f803f80u); }
    WSTAMP(27);
    if (w == 0) __threadfence();
    uint32_t q[8] = {0, 0, 0, 0, 0, 0, 0, 0};
    mbar_wait(sb + MB_WO3, 0);
    if (t2 == 0) SSTAMP(11, 3);
#pragma unroll
    for (int k = 0; k < 8; k++) {
      ldsm4t(wo[k], wo_lane + SM_WO3 + k * 2048); ldsm4t(w1[k], wo_lane + SM_WOST + k * 2048);
#pragma unroll
      for (int i = 0; i < 4; i++) { sq_acc(q[i], wo[k][i]); sq_acc(q[i], w1[k][i]); }
    }
    bar_sync(6, 128);
    if (t2 == 0) SSTAMP(11, 7);
#pragma unroll
    for (int k = 0; k < 8; k++) sts128(sb + SM_WO3 + t2 * 16 + k * 2048, wo[k][0], wo[k][1], wo[k][2], wo[k][3]);
#pragma unroll
    for (int i = 0; i < 5; i++) {
      const int j = w * 18 + 4 * i + (lane >> 3), c = i < 4 || lane < 16 ? j * 8 + j / 24 * 64 : 192;
      stsm4t(sb + SM_MEM + (c + (lane & 7)) * 16, mv[4 * i], mv[4 * i + 1], mv[4 * i + 2], mv[4 * i + 3]);
    }
    bar_arrive(1, 256); bar_arrive(2, 256); bar_arrive(9, 256);
    if (t2 == 0) SSTAMP(11, 8);
    mbar_wait(sb + MB_WO, 0);
    if (t2 == 0) SSTAMP(11, 4);
#pragma unroll
    for (int k = 0; k < 8; k++) ldsm4t(wo[k], wo_lane + SM_X + 2 * XT + k * 2048);
    fence_async();
    bar_sync(6, 128);
    if (t2 == 32) tma_load3(sb + SM_X + 2 * XT, &tm.x, 64, sb + MB_X + 16);
    __syncwarp();
#pragma unroll
    for (int k = 0; k < 8; k++)
#pragma unroll
      for (int i = 0; i < 4; i++) sq_acc(q[4 + i], wo[k][i]);
    float ss = 0.f;
#pragma unroll
    for (int i = 0; i < 8; i++) ss += bf_lo(q[i]) + bf_hi(q[i]);
    ss = warp_sum(ss);
    if (lane == 0) sts32(sb + SC_SS + 4 * (8 + w), __float_as_uint(ss));
    if (t2 == 0) SSTAMP(11, 9);
    bar_sync(11, 384);
    if (t2 == 0) SSTAMP(11, 10);
    if (t2 == 0) {
      float a[16];
#pragma unroll
      for (int i = 0; i < 4; i++) lds128f(sb + SC_SS + 16 * i, &a[4 * i]);
      stg_relaxed(&g_stats[blockIdx.x * 2], __float_as_uint(((a[0] + a[1]) + (a[2] + a[3])) + ((a[4] + a[5]) + (a[6] + a[7]))),
                  __float_as_uint((a[8] + a[9]) + (a[10] + a[11])),
                  max(max(__float_as_uint(a[12]), __float_as_uint(a[13])), max(__float_as_uint(a[14]), __float_as_uint(a[15]))), tag);
    }
    __syncwarp();
    WSTAMP(24);
    cluster_wait();
    if (w == 0) {
      uint4 v[3];
      int n = 0;
      while (true) {
#pragma unroll
        for (int i = 0; i < 3; i++) v[i] = ldg_relaxed(&g_stats[(i * 32 + lane) * 2]);
        if (__all_sync(0xffffffffu, v[0].w == tag && v[1].w == tag && v[2].w == tag) || ++n > SPIN_LIMIT) break;
        __nanosleep(100);
      }
      WSTAMP(25);
      const float sv = warp_sum(__uint_as_float(v[0].x) + __uint_as_float(v[1].x) + __uint_as_float(v[2].x));
      const float so = warp_sum(__uint_as_float(v[0].y) + __uint_as_float(v[1].y) + __uint_as_float(v[2].y));
      const int expW = ((int)(__float_as_uint(sv) >> 23) + (int)(__float_as_uint(so) >> 23) - 254 + 2 + 10 + 1) >> 1;
      sts32(sb + SC_XMAX + 4 * lane, v[0].z); sts32(sb + SC_XMAX + 128 + 4 * lane, v[1].z);
      sts32(sb + SC_EXPW, expW + 1 - 15);
      if (blockIdx.x == 0 && lane == 0) *(volatile unsigned*)&g_epoch = tag;
      sts32(sb + SC_FPAR + 4, 1);
    } else if (w < 3) {
      const uint32_t u = blockIdx.x >> 4;
      unsigned char* const z = g_red + 98304 + (blockIdx.x & 15) * 128 + (u & 1) * 2048 + (u & 6) * 4096 + (((u >> 1) ^ w) & 1) * 4096 + lane * 4;
      stg_relaxed32(z, 0);
      uint32_t best = 0xffffffffu;
#pragma unroll 1
      for (int i = 0; i < 64; i++) {
        uint32_t last, dt;
        asm volatile("{\n.reg .pred p;\n.reg .u32 c, v;\nld.volatile.shared.u32 %0, [%3];\nmov.u32 c, %%clock;\n"
                     "atom.relaxed.gpu.global.exch.b32 v, [%2], 0;\nsetp.eq.u32 p, v, 0;\nmov.u32 %1, 0;\n@p mov.u32 %1, %%clock;\nsub.u32 %1, %1, c;\n}"
                     : "=r"(last), "=r"(dt) : "l"(z), "r"(sb + SC_FPAR + 4) : "memory");
        best = min(best, dt);
        if (last && i >= NPROBE - 1) break;
      }
      sts32(sb + SC_LAT + (w - 1) * 4, best);
    }
    bar_sync(13, 384);
    bar_arrive(0, 384);
    WSTAMP(26);
  }

  const uint32_t nh = __shfl_sync(0xffffffffu, near_half(sb), 0);
  uint32_t l16 = sb + lane * 16;
  PIN(l16);
#define LV ((l16 >> 4) & 31)
#define fence_reg l16
  const uint32_t red_lo = (uint32_t)(uint64_t)g_red, red_hi = (uint32_t)((uint64_t)g_red >> 32);
  uint32_t lp;
  auto slot = [&](int s, uint32_t c, uint32_t ofs) {
    const uint32_t lo = lp | (red_lo + ((w >> 1) * 4 + (w & 1) * 2 + ((w ^ c) & 1)) * 4096 + RED_SLOT(s) + ofs);
    uint64_t a; asm("mov.b64 %0, {%1, %2};" : "=l"(a) : "r"(lo), "r"(red_hi));
    return (unsigned char*)a;
  };
  const uint32_t always = __shfl_sync(0xffffffffu, lds32(sb + SC_DEAD + 12), 0);
  const int mode0 = RANK < 2 ? w : w | 4;
  auto hint_addr = [&](int s) { return min(LV, 23u) * 4 + (red_lo + HINT_OFF + nh * 4096 + w * 16384 + RED_SLOT(s)); };
  auto load_hints = [&](uint32_t lo) {
    uint64_t a; asm("mov.b64 %0, {%1, %2};" : "=l"(a) : "r"(lo), "r"(red_hi));
    return ldg_relaxed32((const void*)a);
  };
  const uint32_t blk = RANK < 2 ? 9216 : SEGB, exb = RANK < 2 ? EXB : EXB2;
  auto export_rest = [&](int seg) { if (EXB && !(XP & 4) && elect_one()) seg_store(seg, sb, exb, blk - exb); __syncwarp(); };
  auto export_seg = [&](int seg) {
    if (!(XP & 4) && elect_one()) {
      if (seg > 0) seg_publish(seg - 1);
      fence_async();
      seg_store(seg, sb, 0, EXB ? exb : blk);
    }
    __syncwarp();
  };
  auto send_v = [&](int seg, int pos) {
    if (RANK == 2 && ((w == 0 && VS0 == pos) || (w == 1 && VS1 == pos)) && seg > 1 && seg < NSEG - 1 && !(XP & 2)) {
      if (elect_one()) {
        fence_async();
        bulk_s2s(mapa(sb + SM_VC + (seg & 1) * 8192, w), sb + SM_BLK + (seg & 3) * SEGB, 8192, mapa(sb + MB_VX + (seg & 1) * 8, w));
      }
      __syncwarp();
    }
  };
  uint32_t dl = __shfl_sync(0xffffffffu, gtime() - 768, 0);
  int s = 0;
  bool bad = false;
#pragma unroll 1
  while (true) {
    const uint32_t par = s & 1;
    uint32_t vx[4][4], hints;
    auto load_vx = [&]() {
      const uint32_t va = l16 + (RANK < 2 ? SM_VC + par * 8192 : SM_BLK + (s & 3) * SEGB) + w * 1024 + ((LV >> 3) & 1) * 384 - (LV >> 4) * 128;
#pragma unroll
      for (int i = 0; i < 4; i++) ldsm4(vx[i], va + (i & 1) * 4096 + (i >> 1) * 256);
    };
    auto retire = [&](uint32_t x) {
      asm volatile("{\n.reg .pred p;\nsetp.eq.u32 p, %0, 0;\n@p exit;\n}" :: "r"(vx[0][0] | vx[1][0] | vx[2][0] | vx[3][0] | x) : "memory");
    };
    auto scores = [&](auto memkeys, auto first, float* sc) {
      constexpr bool MK = decltype(memkeys)::value, FIRST = decltype(first)::value;
      uint32_t kb[4][4], qb[2][4];
      const uint32_t m = LV >> 3;
      uint32_t kaddr = l16 + SM_BLK + 4096 + (s & 3) * SEGB + w * 2048 + (m & 1) * (MK ? 128 : 896) - (m >> 1) * 128;
      if (MK) { PIN(kaddr); }
      else {
#pragma unroll
        for (int k = 0; k < 4; k++) ldsm4t(kb[k], kaddr + k * 256);
      }
      if (FIRST) { load_vx(); retire(MK ? kaddr : kb[0][0] | kb[1][0] | kb[2][0] | kb[3][0] | l16); bar_sync(4, 256); RSTAMP(4); PROF(4); }
      ldsm4t(qb[0], l16 + SM_QM);
      if (MK) ldsm4t(kb[0], kaddr);
      ldsm4t(qb[1], l16 + SM_QM + 512);
      if (MK) ldsm4t(kb[2], kaddr + 512);
      float c[4][4];
      mma16816z(c[0], kb[0], qb[0][0], qb[0][1]); mma16816z(c[1], kb[MK ? 0 : 1], qb[0][2], qb[0][3]);
      mma16816z(c[2], kb[2], qb[1][0], qb[1][1]); mma16816z(c[3], kb[MK ? 2 : 3], qb[1][2], qb[1][3]);
      if (FIRST && B5POS == 0) bar_arrive(5, N5);
#pragma unroll
      for (int i = 0; i < (MK ? 2 : 4); i++) sc[i] = ((c[0][i] + c[1][MK ? i + 2 : i]) + c[2][i]) + c[3][MK ? i + 2 : i];
    };
    auto send = [&](auto memkeys) {
      constexpr bool MK = decltype(memkeys)::value;
      constexpr int N = MK ? 1 : 2;
      const uint32_t sa = sb + LV * 4 + SM_E + (MK ? 1024 + RANK * 128 : RANK * 512 + w * 256);
      uint32_t ra[N][2], mb[N][2];
#pragma unroll
      for (int i = 0; i < N; i++)
#pragma unroll
        for (int j = 0; j < 2; j++) {
          ra[i][j] = mapa(sa + i * 128, j ? 2 : RANK ^ 1); mb[i][j] = mapa(sb + MB_S, j ? 2 : RANK ^ 1);
          PIN(ra[i][j]);
        }
      float sc[4];
      scores(memkeys, BoolC<true>(), sc);
      uint32_t e[N];
#pragma unroll
      for (int i = 0; i < N; i++) {
        e[i] = pack_bf16(ex2(sc[2 * i]), ex2(sc[2 * i + 1]));
        if (!(fmaxf(fabsf(sc[2 * i]), fabsf(sc[2 * i + 1])) <= E_LIM)) e[i] = 0x7fff7fffu;
        st_async1(ra[i][0], e[i], mb[i][0]);
        st_async1(ra[i][1], e[i], mb[i][1]);
      }
#pragma unroll
      for (int i = 0; i < N; i++) sts32(sa + i * 128, e[i]);
      __syncwarp();
      if (l16 == sb) mbar_arrive(sb + MB_S);
      PROF(5);
    };
    const int mode = bad ? 8 : mode0;
    if (mode < 2) {
      send(BoolC<false>());
    } else if (mode == 2) {
      send(BoolC<true>());
    } else if (mode == 8) {
      load_vx();
      retire(l16);
      const uint32_t fp = lds32(sb + SC_FPAR);
      bar_sync(6, 128);
      if (w == 0 && l16 == sb) { sts32(sb + SC_FPAR, fp ^ 1); mbar_expect(sb + MB_F, 3072); }
      if (RANK < 2 && w < 3) {
        float sc[4] = {0.f, 0.f, 0.f, 0.f};
        if (w < 2) scores(BoolC<false>(), BoolC<false>(), sc); else scores(BoolC<true>(), BoolC<false>(), sc);
#pragma unroll 1
        for (int r = 0; r < 3; r++)
          st_async4(mapa(l16 + SM_FB + RANK * 1536 + w * 512, r), __float_as_uint(sc[0]), __float_as_uint(sc[1]), __float_as_uint(sc[2]), __float_as_uint(sc[3]), mapa(sb + MB_F, r));
      }
      mbar_wait(sb + MB_F, fp);
      float a[12];
#pragma unroll
      for (int j = 0; j < 3; j++) {
        float b[4];
        lds128f(l16 + SM_FB + j * 512, a + 4 * j); lds128f(l16 + SM_FB + 1536 + j * 512, b);
#pragma unroll
        for (int i = 0; i < 4; i++) a[4 * j + i] += b[i];
      }
      float m0 = fmaxf(fmaxf(fmaxf(a[0], a[2]), fmaxf(a[4], a[6])), a[8]), m1 = fmaxf(fmaxf(fmaxf(a[1], a[3]), fmaxf(a[5], a[7])), a[9]);
#pragma unroll
      for (int o = 4; o < 32; o <<= 1) { m0 = fmaxf(m0, __shfl_xor_sync(0xffffffffu, m0, o)); m1 = fmaxf(m1, __shfl_xor_sync(0xffffffffu, m1, o)); }
#pragma unroll
      for (int i = 0; i < 5; i++) {
        const uint32_t ea = sb + SM_E + LV * 4 + (i < 4 ? i * 128 : 1024);
        sts32(ea, pack_bf16(ex2(a[2 * i] - m0), ex2(a[2 * i + 1] - m1)));
        sts32(ea + (i < 4 ? 512 : 128), 0x3f803f80u);
      }
      __syncwarp();
    } else {
      load_vx();
      if (mode == 3 && (EXPOS < 5 || B15 || (XP & 256))) bar_arrive(4, 256);
      retire(l16 + 1);
      if (VS0 == 2 || VS1 == 2) send_v(s + 1, 2);
      if (w == 3) {
        if (EXPOS >= 5) {
          constexpr int EARLY = EXPOS == 6 ? 8192 : 0;
          uint32_t used = ldg_relaxed32(&g_used[blockIdx.x / 3 * 32]);
          if (!(XP & 4) && elect_one()) {
            if (s > 0) seg_publish(s - 1);
            if (EARLY) { fence_async(); seg_store(s, sb, 0, EARLY); }
          }
          __syncwarp();
          if (!(XP & 256)) bar_sync(RANK < 2 && !B15 ? 4 : 15, RANK < 2 && !B15 ? 256 : 160);
          if (!(XP & 260) && elect_one()) { fence_async(); seg_store(s, sb, EARLY, blk - EARLY); }
          __syncwarp();
          if (s >= NRING - 1 && !(XP & 64)) {
            const uint32_t need = lds32(sb + SC_EPOCH) + s;
#pragma unroll 1
            for (int n = 0; (int)(used - need) < 0 && n < SPIN_LIMIT; n++) used = ldg_relaxed32(&g_used[blockIdx.x / 3 * 32]);
          }
        }
        if (EXPOS == 0 && s > 0) export_seg(s - 1);
        if (EXB) { if (RANK < 2) bar_sync(5, N5); else bar_sync(15, 160); if (s > 0) export_rest(s - 1); }
      }
    }
    {
      uint32_t wa[4], wb[4], oc[4];
      constexpr int WS = 2048;
      const uint32_t w3a = l16 + SM_WO3 + w * 512;
      lds128(w3a + KP(0) * WS, wa); lds128(w3a + KP(1) * WS, wb); lds128(sb + SC_ONES, oc);
      if (B5POS == 1 && mode < 3) bar_arrive(5, N5);
      uint32_t e[10], p[5], vm[4], ob[4];
      float o0[4], o1[4], f[3][2][4], rs[4];
      reserve2(vm); reserve2(vm + 2); reserve2(e + 8);
      hints = hint_addr(s);
      PIN(hints);
      if (CLR & 2) asm volatile("{\n.reg .pred p;\nsetp.eq.u32 p, %0, 0;\n@p exit;\n}" :: "r"(wa[0] | wb[0] | oc[0] | hints) : "memory");
      mbar_wait(sb + MB_S, par);
      RSTAMP(5);
      PROF(6);
      ldsm4t(e, l16 + SM_E); ldsm2t_in(e + 8, l16 + SM_E + 1024, always); ldsm4t(e + 4, l16 + SM_E + 512);
      lds128_in(vm, l16 + w * 512 + SM_VM, always);
      const float scl = __uint_as_float(lds32(sb + SC_UNSC + 8 - par * 8));
      hints = load_hints(hints);
      if (GF & 1) SCHED_FENCE(4);
#pragma unroll
      for (int i = 0; i < 4; i++) p[i] = mul_bf16(e[i], e[4 + i]);
      p[4] = mul_bf16(e[8], e[9]);
      mma16816z(o0, vx[0], p[0], p[1]); mma16816z(o1, vx[1], p[0], p[1]); mma16816z(rs, oc, p[0], p[1]);
      mma16816(o0, vx[2], p[2], p[3]); lds128_in(vx[2], w3a + KP(2) * WS, always);
      mma16816(o1, vx[3], p[2], p[3]); lds128_in(vx[3], w3a + KP(3) * WS, always);
      mma16816(rs, oc, p[2], p[3]);
      mma1688(o0, vm[0], vm[1], p[4]); mma1688(o1, vm[2], vm[3], p[4]); mma1688(rs, oc[0], oc[1], p[4]);
      stsm4(l16 + w * 512 + SM_OB, pack_bf16(o0[0], o0[1]), pack_bf16(o0[2], o0[3]), pack_bf16(o1[0], o1[1]), pack_bf16(o1[2], o1[3]));
      bar_sync(6, 128);
      RSTAMP(3);
      PROF(7);
      ldsm4t_in(oc, l16 + SM_OB, always);
      bad = __any_sync(0xffffffffu, !(rs[0] + rs[1] > 0.f) && !bad);
      rs[0] *= scl; rs[1] *= scl;
      asm volatile("{\n.reg .pred p;\nsetp.ne.u32 p, %1, 0;\n@p rcp.approx.ftz.f32 %0, %0;\n}" : "+f"(rs[0]) : "r"(always));
      asm volatile("{\n.reg .pred p;\nsetp.ne.u32 p, %1, 1;\n@p rcp.approx.ftz.f32 %0, %0;\n}" : "+f"(rs[1]) : "r"(always));
      asm volatile("lop3.b32 %0, %1, %2, %3, 0xfe;" : "=r"(lp) : "r"((l16 & 128) * 2), "r"((l16 & 256) * 4), "r"(l16 & 112));
      if (bad) continue;
      ldsm4t(ob, l16 + SM_OB + 512);
      mma16816z(f[2][0], wa, oc[0], oc[1]); mma16816z(f[2][1], wb, oc[2], oc[3]);
      mma16816z(f[0][0], wo[0], oc[0], oc[1]); mma16816z(f[0][1], wo[4], oc[2], oc[3]);
      mma16816z(f[1][0], w1[0], oc[0], oc[1]); mma16816z(f[1][1], w1[4], oc[2], oc[3]);
      ldsm4t_in(oc, l16 + SM_OB + 1024, always);
      mma16816(f[2][0], vx[2], ob[0], ob[1]); lds128_in(vx[2], w3a + KP(4) * WS, always);
      mma16816(f[2][1], vx[3], ob[2], ob[3]); lds128_in(vx[3], w3a + KP(5) * WS, always);
      mma16816(f[0][0], wo[1], ob[0], ob[1]); mma16816(f[0][1], wo[5], ob[2], ob[3]);
      mma16816(f[1][0], w1[1], ob[0], ob[1]); mma16816(f[1][1], w1[5], ob[2], ob[3]);
      ldsm4t_in(ob, l16 + SM_OB + 1536, always);
      mma16816(f[0][0], wo[2], oc[0], oc[1]); mma16816(f[0][1], wo[6], oc[2], oc[3]);
      mma16816(f[2][0], vx[2], oc[0], oc[1]); lds128_in(vx[2], w3a + KP(6) * WS, always);
      mma16816(f[2][1], vx[3], oc[2], oc[3]); lds128_in(vx[3], w3a + KP(7) * WS, always);
      mma16816(f[1][0], w1[2], oc[0], oc[1]); mma16816(f[1][1], w1[6], oc[2], oc[3]);
      mma16816(f[0][0], wo[3], ob[0], ob[1]); mma16816(f[0][1], wo[7], ob[2], ob[3]);
      mma16816(f[1][0], w1[3], ob[0], ob[1]); mma16816(f[1][1], w1[7], ob[2], ob[3]);
      mma16816(f[2][0], vx[2], ob[0], ob[1]); mma16816(f[2][1], vx[3], ob[2], ob[3]);
      bar_arrive(7, NII < 18 ? 384 : 256);
      lds128_in(ob, sb + SC_DEAD, always);
      uint32_t h[3][2];
#pragma unroll
      for (int j = 0; j < 3; j++)
#pragma unroll
        for (int i = 0; i < 2; i++)
        {
          scale_sum(f[j][1][2 * i], f[j][0][2 * i], rs[0], always); scale_sum(f[j][1][2 * i + 1], f[j][0][2 * i + 1], rs[1], always);
          h[j][i] = pack_f16(f[j][1][2 * i], f[j][1][2 * i + 1]);
        }
      const uint32_t rofs = RANK * 32768;
      red_f16x8(slot(s, RANK >> 1, rofs), h[0][0], h[1][0], h[2][0], 0x3c00u);
      red_f16x8(slot(s, (RANK >> 1) ^ 1, rofs), h[0][1], h[1][1], h[2][1], 0x3c00u);
      if (NII == 18) bar_arrive(10, 256);
      SCHED_FENCE(5);
      RSTAMP(0);
      l16 += ob[B7R];
    }
    {
    PROF(8);
    if (VS0 == 3 || VS1 == 3) send_v(s + 1, 3);
    const uint32_t ma0 = l16 + SM_MEM + w * 128 + (LV >> 3) * 896 + nh * 512;
    const unsigned char* const sl[2] = {slot(s, nh, 0), slot(s, nh ^ 1, 0)};
    uint32_t late = latest_hint(hints, dl, s);
    if (late >= 64) {
      int n = 0;
#pragma unroll 1
      do {
        late = latest_hint(load_hints(hint_addr(s)), dl, s);
      } while (late >= 64 && ++n < SPIN_LIMIT);
    }
    dl += late * 32 + tm.poll;
    if ((TL & 1) && s == NSEG - 2 && w == 3 && elect_one()) seg_publish(s);
    if (EXPOS == 2 && w == 3) export_seg(s);
    PROF(9);
    {
      auto wait_until = [&](uint32_t t) {
        asm volatile("{\n.reg .pred p;\n.reg .s32 c;\n.reg .u64 t;\nTL: mov.u64 t, %%globaltimer;\ncvt.u32.u64 c, t;\nsub.s32 c, c, %0;\nsetp.lt.s32 p, c, 0;\n@p bra.uni TL;\n}" :: "r"(t + (l16 & 15)) : "memory");
      };
      uint4 v[2][3];
      auto load = [&](int c) {
#pragma unroll
        for (int r = 0; r < 3; r++) v[c][r] = ldg_relaxed(sl[c ^ (r >> 1)] + r * 32768);
      };
      auto decode = [&](int c, int n) {
        uint32_t q[9];
        __half2 hm;
        const uint32_t ma = ma0 ^ (c * 512);
#pragma unroll
        for (int i = 0; i < 9; i++) {
          const uint32_t h = i % 3 == 0 ? v[c][i / 3].x : (i % 3 == 1 ? v[c][i / 3].y : v[c][i / 3].z);
          const float2 f = __half22float2(*(const __half2*)&h);
          q[i] = pack_bf16(f.x, f.y);
          hm = i ? __hmax2(hm, __habs2(*(const __half2*)&h)) : __habs2(*(const __half2*)&h);
        }
#pragma unroll
        for (int r = 0; r < 3; r++) stsm4(ma + r * 4096, q[3 * r], q[3 * r + 1], q[3 * r + 2], r < 2 ? v[c][r].w : *(const uint32_t*)&hm);
        const bool done = __all_sync(0xffffffffu, v[c][0].w == 0x5000u && v[c][1].w == 0x5000u && v[c][2].w == 0x5000u) || n > SPIN_LIMIT;
        asm volatile("{\n.reg .pred p;\nsetp.ne.u32 p, %0, 0;\n@p bar.arrive %1, 256;\n}" :: "r"((int)done), "r"(1 + c) : "memory");
        return done;
      };
      if (LEAD) { wait_until(dl - LEAD); load(1); }
      wait_until(dl);
      PROF(10);
      int n = 0;
#pragma unroll 1
      do {
        load(0);
        if (!LEAD) load(1);
        asm volatile("{\n.reg .pred p;\nsetp.eq.u32 p, %0, 0;\n@p bar.sync 13, 384;\n}" :: "r"(n) : "memory");
      } while (!decode(0, n++));
      PROF(11);
      RSTAMP(1);
#pragma unroll 1
      while (!decode(1, n++)) load(1);
      bar_arrive(9, 256);
      RSTAMP(2);
      PROF(12);
    }
    if (EXPOS == 3 && w == 3) export_seg(s);
    PROF(13);
    if (++s == NSEG - 1) break;
    }
  }
#undef fence_reg
  if (RANK < 2) bar_arrive(4, 256);
  if (w == 3) { if (EXPOS < 2 || EXPOS == 4) export_seg(NSEG - 2); export_rest(NSEG - 2); if (!(XP & 4) && elect_one()) { if (!(TL & 1)) seg_publish(NSEG - 2); if (EXPOS >= 6) { fence_async(); seg_store(NSEG - 1, sb, 0, 8192); } } }
  __syncwarp();
  bar_sync(0, 384);
  if (w == 3 && !(XP & 4) && elect_one()) {
    fence_async();
    seg_store(NSEG - 1, sb, EXPOS >= 6 ? 8192 : 0, EXPOS >= 6 ? blk - 8192 : blk);
    seg_publish(NSEG - 1);
  }
  __syncwarp();
  cluster_sync();
}

__global__ void __cluster_dims__(3, 1, 1) __launch_bounds__(384, 1)
rec_kernel(const __grid_constant__ RMaps tm, const bf16* __restrict__ x, const bf16* __restrict__ mem0) {
  extern __shared__ __align__(1024) unsigned char smem_raw[];
  const uint32_t sb = smem_u32(smem_raw);
  const int tid = threadIdx.x, lane = tid & 31;
  const int wg = __shfl_sync(0xffffffffu, tid >> 7, 0);
  const int w = __shfl_sync(0xffffffffu, (tid >> 5) & 3, 0);
  uint32_t rank; asm("mov.u32 %0, %%cluster_ctarank;" : "=r"(rank));
  STAMP(0);
  TSTAMP(0);
  asm volatile("griddepcontrol.launch_dependents;" ::: "memory");

#define PFT 1
  if (PFT && wg == 1 && lane == 0) asm volatile("prefetch.tensormap [%0];" :: "l"(w == 0 ? (rank < 2 ? &tm.wk : &tm.wv) : w == 1 ? &tm.wq : w == 2 ? &tm.x : &tm.wo) : "memory");
  if (wg < 2) {
    asm volatile("setmaxnreg.inc.sync.aligned.u32 192;");
    if (tid == 0) {
      for (int i = 0; i < 3; i++) { mbar_init(sb + MB_W + 8 * i, 1); mbar_init(sb + MB_X + 8 * i, 1); }
      mbar_init(sb + MB_WO, 1); mbar_init(sb + MB_WO3, 1);
      mbar_init(sb + MB_S, rank < 2 ? 5 : 6);
      mbar_init(sb + MB_F, 1);
      mbar_init(sb + MB_VX, 1); mbar_init(sb + MB_VX + 8, 1);
      asm volatile("fence.mbarrier_init.release.cluster;" ::: "memory");
      fence_async();
      SSTAMP(11, 6);
      load_weights(sb, tm, rank, 0);
      for (int i = 0; i < 3; i++) mbar_expect(sb + MB_X + 8 * i, XT);
      tma_load3(sb + SM_X, &tm.x, 0, sb + MB_X);
      if (!PACE) for (int c = 1; c < 4; c++) load_weights(sb, tm, rank, c);
      mbar_expect(sb + MB_S, rank < 2 ? 640 + 2048 : 1280);
      mbar_expect(sb + MB_VX, 8192); mbar_expect(sb + MB_VX + 8, 8192);
      SSTAMP(11, 5);
    }
    __syncwarp();
    bar_sync(0, 384);
    proj_role(sb, tm, rank, wg, w, lane);
  } else {
    asm volatile("setmaxnreg.dec.sync.aligned.u32 120;");
    attn_role(sb, smem_raw, tm, rank, x, mem0, w, lane);
  }
}

constexpr int NAUX = 36;
constexpr int A_XH = 73728;
constexpr int A_NS = 9, A_WM = 6144, A_WT = 768;
constexpr int A_RING = 2 * A_XH, A_TAIL = A_RING + A_NS * A_WM, A_GW = A_TAIL + A_NS * A_WT;
constexpr int A_EPI = 212864, A_EPW = 9344;
constexpr int A_XT = 4 * XT, A_XW = A_XT + 8192, A_EX = A_XW + 8192, A_NR = 4;
constexpr int A_IN = A_EX + 16384, A_OST = A_IN + 3 * SEGB;
constexpr int A_GATE = A_EPI + 2 * A_EPW, A_BAR = A_GATE + 512;
constexpr int A_TOTAL = A_BAR + 384;
struct AMaps { CUtensorMap x, wa, wt, oa, o, o3, wob, woa; };

DI void wgmma_n192_ss_nt(float* d, uint64_t da, uint64_t db, int acc) {
  asm volatile("{\n.reg .pred p;\nsetp.ne.b32 p, %98, 0;\n"
               "wgmma.mma_async.sync.aligned.m64n192k16.f32.bf16.bf16 {"
               "%0,%1,%2,%3,%4,%5,%6,%7,%8,%9,%10,%11,%12,%13,%14,%15,%16,%17,%18,%19,%20,%21,%22,%23,%24,%25,%26,%27,%28,%29,%30,%31,"
               "%32,%33,%34,%35,%36,%37,%38,%39,%40,%41,%42,%43,%44,%45,%46,%47,%48,%49,%50,%51,%52,%53,%54,%55,%56,%57,%58,%59,%60,%61,%62,%63,"
               "%64,%65,%66,%67,%68,%69,%70,%71,%72,%73,%74,%75,%76,%77,%78,%79,%80,%81,%82,%83,%84,%85,%86,%87,%88,%89,%90,%91,%92,%93,%94,%95"
               "}, %96, %97, p, 1, 1, 0, 1;\n}\n"
               : ACC8(d, 0), ACC8(d, 8), ACC8(d, 16), ACC8(d, 24), ACC8(d, 32), ACC8(d, 40), ACC8(d, 48), ACC8(d, 56),
                 ACC8(d, 64), ACC8(d, 72), ACC8(d, 80), ACC8(d, 88) : "l"(da), "l"(db), "r"(acc));
}
#define ACC4(d, o) "+f"(d[o]), "+f"(d[o + 1]), "+f"(d[o + 2]), "+f"(d[o + 3])
DI void wgmma_n24_ss_nt(float* d, uint64_t da, uint64_t db, int acc) {
  asm volatile("{\n.reg .pred p;\nsetp.ne.b32 p, %14, 0;\n"
               "wgmma.mma_async.sync.aligned.m64n24k16.f32.bf16.bf16 {%0,%1,%2,%3,%4,%5,%6,%7,%8,%9,%10,%11}, %12, %13, p, 1, 1, 0, 1;\n}\n"
               : ACC8(d, 0), ACC4(d, 8) : "l"(da), "l"(db), "r"(acc));
}
DI void wgmma_n8_ss(float* d, uint64_t da, uint64_t db, int acc) {
  asm volatile("{\n.reg .pred p;\nsetp.ne.b32 p, %6, 0;\n"
               "wgmma.mma_async.sync.aligned.m64n8k16.f32.bf16.bf16 {%0,%1,%2,%3}, %4, %5, p, 1, 1, 0, 0;\n}\n"
               : ACC4(d, 0) : "l"(da), "l"(db), "r"(acc));
}
DI void wgmma_n40_ss_tt(float* d, uint64_t da, uint64_t db, int acc) {
  asm volatile("{\n.reg .pred p;\nsetp.ne.b32 p, %22, 0;\n"
               "wgmma.mma_async.sync.aligned.m64n40k16.f32.bf16.bf16 {%0,%1,%2,%3,%4,%5,%6,%7,%8,%9,%10,%11,%12,%13,%14,%15,%16,%17,%18,%19}, "
               "%20, %21, p, 1, 1, 1, 1;\n}\n"
               : ACC8(d, 0), ACC8(d, 8), ACC4(d, 16) : "l"(da), "l"(db), "r"(acc));
}
DI void wgmma_n64_rs(float* d, const uint32_t* a, uint64_t db, int acc) {
  asm volatile("{\n.reg .pred p;\nsetp.ne.b32 p, %37, 0;\n"
               "wgmma.mma_async.sync.aligned.m64n64k16.f32.bf16.bf16 {"
               "%0,%1,%2,%3,%4,%5,%6,%7,%8,%9,%10,%11,%12,%13,%14,%15,%16,%17,%18,%19,%20,%21,%22,%23,%24,%25,%26,%27,%28,%29,%30,%31"
               "}, {%32,%33,%34,%35}, %36, p, 1, 1, 0;\n}\n"
               : ACC8(d, 0), ACC8(d, 8), ACC8(d, 16), ACC8(d, 24) : "r"(a[0]), "r"(a[1]), "r"(a[2]), "r"(a[3]), "l"(db), "r"(acc));
}
DI void wgmma_n32_ss_tn(float* d, uint64_t da, uint64_t db, int acc) {
  asm volatile("{\n.reg .pred p;\nsetp.ne.b32 p, %18, 0;\n"
               "wgmma.mma_async.sync.aligned.m64n32k16.f32.bf16.bf16 {%0,%1,%2,%3,%4,%5,%6,%7,%8,%9,%10,%11,%12,%13,%14,%15}, "
               "%16, %17, p, 1, 1, 1, 0;\n}\n"
               : ACC8(d, 0), ACC8(d, 8) : "l"(da), "l"(db), "r"(acc));
}
DI void tma_load3c(uint32_t dst, const CUtensorMap* m, int c0, int c1, int c2, uint32_t mb) {
  asm volatile("cp.async.bulk.tensor.3d.shared::cluster.global.mbarrier::complete_tx::bytes [%0], [%1, {%3, %4, %5}], [%2];"
               :: "r"(dst), "l"(m), "r"(mb), "r"(c0), "r"(c1), "r"(c2) : "memory");
}
#define NAP 64
DI uint32_t movm(uint32_t x) { uint32_t r; asm volatile("movmatrix.sync.aligned.m8n8.trans.b16 %0, %1;" : "=r"(r) : "r"(x)); return r; }
DI bool wait_count(const unsigned* p, unsigned target, bool nap = true) {
  int n = 0;
  unsigned v;
  while (true) {
    asm volatile("ld.acquire.gpu.global.b32 %0, [%1];" : "=r"(v) : "l"(p) : "memory");
    if ((int)(v - target) >= 0 || ++n > SPIN_LIMIT) break;
    if (nap) __nanosleep(NAP);
  }
  return n;
}
DI void count_up(unsigned* p) {
  asm volatile("fence.proxy.async;" ::: "memory");
  asm volatile("red.release.gpu.global.add.u32 [%0], 1;" :: "l"(p) : "memory");
}
#define AX 0
#define FDLY 400
#define ORING 63
#define DRY 0
#define FEND 61
#define ADLY 0

__global__ void __launch_bounds__(512, 1)
aux_kernel(const __grid_constant__ AMaps tm, const bf16* __restrict__ wqkv, const bf16* __restrict__ gate_w, bf16* __restrict__ out) {
  extern __shared__ __align__(1024) unsigned char smem_raw[];
  const uint32_t sb = smem_u32(smem_raw);
  const uint32_t fullx = sb + A_BAR, full1 = fullx + 24, empty1 = full1 + 8 * A_NS, fullw = empty1 + 8 * A_NS, full3 = fullw + 8, empty3 = full3 + 8 * A_NR,
                 fullq = empty3 + 8 * A_NR, fullv = fullq + 8, emptyq = fullv + 8, emptyv = emptyq + 8;
  const int tid = threadIdx.x, lane = tid & 31, cta = blockIdx.x;
  const int wg = __shfl_sync(0xffffffffu, tid >> 7, 0), w = __shfl_sync(0xffffffffu, (tid >> 5) & 3, 0);
  ASTAMP(14);
  if (tid == 384) {
    for (int i = 0; i < 3; i++) mbar_init(fullx + 8 * i, 1);
    for (int i = 0; i < A_NS; i++) { mbar_init(full1 + 8 * i, 1); mbar_init(empty1 + 8 * i, 8); }
    mbar_init(fullw, 1); mbar_init(fullq, 1); mbar_init(fullv, 1); mbar_init(emptyq, 4); mbar_init(emptyv, 4);
    for (int i = 0; i < A_NR; i++) { mbar_init(full3 + 8 * i, 1); mbar_init(empty3 + 8 * i, 4); }
    fence_async();
  }
  __syncthreads();
  ASTAMP(0);
  const int tile = cta >> 1, hh = cta & 1;
  const int nsl = cta >> 2, kq = cta & 3;
  if (wg == 3) {
    asm volatile("setmaxnreg.dec.sync.aligned.u32 24;");
    const bool lead = lane == 0;
    if (w < 3) {
      if (ADLY) wait_until(gtime() + ADLY);
      if (elect_one()) {
        mbar_expect(fullx + 8 * w, 49152);
        for (int p = 0; p < 2; p++)
          asm volatile("cp.async.bulk.tensor.4d.shared::cluster.global.mbarrier::complete_tx::bytes [%0], [%1, {%3, %4, %5, %6}], [%2];"
                       :: "r"(sb + p * A_XH + w * 24576), "l"(&tm.x), "r"(fullx + 8 * w), "r"(0), "r"(p), "r"(57 * tile - 7), "r"(3 * w) : "memory");
      }
#pragma unroll 1
      for (int r = 0; r < 17; r++) {
#pragma unroll 1
        for (int st = w; st < A_NS; st += 3) {
          if (r > 0) mbar_wait(empty1 + 8 * st, ~r & 1);
          if (r < 16 && elect_one()) {
            const int col = hh * 288 + (r >> 2) * 72, row = (r & 3) * 144 + st * 16;
            mbar_expect(full1 + 8 * st, A_WM + (AX & 1 ? 0 : A_WT));
            tma_load3c(sb + A_RING + st * A_WM, &tm.wa, col, row, 0, full1 + 8 * st);
            if (!(AX & 1)) tma_load3c(sb + A_TAIL + st * A_WT, &tm.wt, col + 64, row, 0, full1 + 8 * st);
          }
          __syncwarp();
        }
        if (r == 0 && elect_one())
          for (int j = 0; j < 3; j++)
            asm volatile("cp.async.bulk.prefetch.L2.global [%0], %1;" :: "l"((const char*)wqkv + cta * 55296 + (w * 3 + j) * 6144), "r"(6144) : "memory");
        __syncwarp();
      }
      bar_sync(8, 96);
    }
    const unsigned epoch = lds32(sb + A_BAR + 376);
    if (w == 1 && cta < NH) {
#pragma unroll 1
      for (int seg = 0; seg < NSEG; seg++) {
        bar_arrive(5, 160);
        if (seg > 0 && lead) {
          asm volatile("cp.async.bulk.wait_group 0;" ::: "memory");
          asm volatile("red.relaxed.gpu.global.add.u32 [%0], 1;" :: "l"(&g_ocnt[(seg - 1) * 32 + cta / 9 * 8]) : "memory");
          SSTAMP(9, seg - 1);
        }
        __syncwarp();
        bar_sync(4, 160);
        if (lead && !(AX & 32)) {
          tma_store(&tm.o, sb + A_OST, cta * DH, (seg & ORING) * 32);
          tma_store(&tm.o, sb + A_OST + 4096, cta * DH + 64, (seg & ORING) * 32);
          asm volatile("cp.async.bulk.commit_group;" ::: "memory");
          asm volatile("cp.async.bulk.wait_group.read 0;" ::: "memory");
        }
        __syncwarp();
      }
      if (lead) {
        asm volatile("cp.async.bulk.wait_group 0;" ::: "memory");
        asm volatile("red.relaxed.gpu.global.add.u32 [%0], 1;" :: "l"(&g_ocnt[(NSEG - 1) * 32 + cta / 9 * 8]) : "memory");
        SSTAMP(9, NSEG - 1);
      }
    }
    if (w == 2) {
      if (lead && cta < NH) {
#pragma unroll 1
        for (int seg = 0; seg < NSEG; seg++) {
          const unsigned char* const src = g_seg + ((size_t)(AX & 128 ? 0 : seg % NRING) * 96 + cta * 3) * SEGB;
          SSTAMP(0, seg);
          const uint32_t tw = gtime();
          wait_count(&g_scnt[(seg * 32 + cta) * 8], 3 * (epoch + 1), !(TL & 2) || seg < NSEG - 2);
          if (FDLY && seg < FEND && gtime() - tw > 600) wait_until(gtime() + FDLY);
          SSTAMP(1, seg);
          mbar_wait(emptyq, ~seg & 1);
          if (AX & 8) { mbar_arrive(fullq); mbar_wait(emptyv, ~seg & 1); mbar_arrive(fullv); continue; }
          mbar_expect(fullq, 2 * SEGB);
          asm volatile("cp.async.bulk.shared::cluster.global.mbarrier::complete_tx::bytes [%0], [%1], %2, [%3];"
                       :: "r"(sb + A_IN), "l"(src), "r"(2 * SEGB), "r"(fullq) : "memory");
          mbar_wait(emptyv, ~seg & 1);
          stg_relaxed32(&g_used[cta * 32], epoch * NSEG + seg);
          mbar_expect(fullv, SEGB);
          asm volatile("cp.async.bulk.shared::cluster.global.mbarrier::complete_tx::bytes [%0], [%1], %2, [%3];"
                       :: "r"(sb + A_IN + 2 * SEGB), "l"(src + 2 * SEGB), "r"(SEGB), "r"(fullv) : "memory");
        }
      }
    }
    if (w == 3) {
#pragma unroll 1
      for (int c = 0; c < 4; c++) {
        if (lead) asm volatile("cp.async.bulk.wait_group.read 0;" ::: "memory");
        __syncwarp();
        bar_arrive(11, 160); bar_arrive(12, 160);
#pragma unroll 1
        for (int g = 0; g < 2; g++) {
          bar_sync(13 + g, 160);
          if (lead) {
            asm volatile("cp.async.bulk.tensor.3d.global.shared::cta.bulk_group [%0, {%2, %3, %4}], [%1];"
                         :: "l"(&tm.oa), "r"(sb + A_EPI + g * A_EPW + 1024), "r"(4096 + hh * 288 + c * 72), "r"(g), "r"(57 * tile) : "memory");
            asm volatile("cp.async.bulk.commit_group;" ::: "memory");
          }
        }
      }
      if (lead) asm volatile("cp.async.bulk.wait_group.read 0;" ::: "memory");
      __syncwarp();
      bar_arrive(10, 160);
      if (lead) { asm volatile("cp.async.bulk.wait_group 0;" ::: "memory"); count_up(&g_abar[32]); }
    }
    if (w != 0) return;
    if (lead) {
      mbar_expect(fullw, 19 * 8192);
#pragma unroll 1
      for (int k = 0; k < 19; k++) {
        const int kb = k < 18 ? kq * 18 + k : 72;
        const uint32_t dst = sb + (k < 18 ? k * 8192 : A_XW);
        if (kb < 64) tma_load(dst, &tm.wob, nsl * 64, kb * 64, fullw);
        else tma_load(dst, &tm.woa, nsl * 64, (kb - 64) * 64, fullw);
      }
    }
    __syncwarp();
    bar_sync(6, 288);
    if (lead) {
      if (kq == 3) { wait_count(&g_abar[32], NAUX * (epoch + 1)); asm volatile("fence.proxy.async;" ::: "memory"); }
      int avail = 0;
      bool waited = false;
      const unsigned nheads = (kq < 3 ? 9 : 5) * (epoch + 1);
      for (int seg = 0; seg < NSEG; seg++) {
        if (seg >= avail) {
          const int far = min(seg + 3, NSEG - 1);
          if (far > seg && !waited && (int)(ldg_acquire32(&g_ocnt[far * 32 + kq * 8]) - nheads) >= 0) avail = far + 1;
          else { waited = wait_count(&g_ocnt[seg * 32 + kq * 8], nheads, !(TL & 2) || seg < NSEG - 2) && (TL & 4); avail = seg + 1; }
        }
        SSTAMP(5, seg);
        for (int g = 0; g < 2; g++) {
          const int sl = (seg & 1) * 2 + g;
          const bool extra = kq == 3 && g == 0;
          mbar_wait(empty3 + 8 * sl, ((seg >> 1) & 1) ^ 1);
          if (AX & 4) { mbar_arrive(full3 + 8 * sl); continue; }
          mbar_expect(full3 + 8 * sl, XT + (extra ? 4096 : 0));
          tma_load3c(sb + sl * XT, &tm.o3, 0, (kq == 3 && g == 1 ? seg : seg & ORING) * 32, kq * 18 + 9 * g, full3 + 8 * sl);
          if (extra) tma_load(sb + A_XT + (seg & 1) * 4096, &tm.o, 72 * 64, seg * 32, full3 + 8 * sl);
        }
      }
    }
    __syncwarp(); bar_sync(6, 288);
    asm volatile("griddepcontrol.wait;" ::: "memory");
  } else if (wg == 2) {
    asm volatile("setmaxnreg.dec.sync.aligned.u32 88;");
    {
      const unsigned epoch = *(volatile unsigned*)&g_epoch2;
      if ((tid & 127) < 80) { const uint4 g = __ldg((const uint4*)gate_w + min(tid & 127, 71)); sts128(sb + A_GW + (tid & 127) * 16, g.x, g.y, g.z, g.w); }
      fence_async();
      bar_sync(3, 128);
      float gt[2][4];
      const uint32_t d0 = (sb & 0x3FFFF) >> 4;
#pragma unroll 1
      for (int j = 0; j < 3; j++) {
        mbar_wait(fullx + 8 * j, 0);
        WG_FENCE();
#pragma unroll
        for (int k = 0; k < 24; k++)
          wgmma_n8_ss(gt[k & 1], desc_at(d0 + (k & 1) * (A_XH >> 4) + j * 1536 + (k >> 3) * 512 + (k & 6), 16, 1024, 1), desc_at(d0 + (A_GW >> 4) + j * 24 + (k & 30), 16, 128, 0), j | (k >> 1));
        WG_COMMIT();
      }
      WG_WAIT(0);
      if ((lane & 3) == 0)
#pragma unroll
        for (int i = 0; i < 4; i++) {
          const float gv = 1.f / (1.f + __expf(-gt[i >> 1][(i & 1) * 2]));
          const int r = w * 16 + (lane >> 2) + (i & 1) * 8, tok = 2 * (57 * tile - 7 + r) + (i >> 1);
          sts32(sb + A_GATE + ((i >> 1) * 64 + r) * 4, __float_as_uint(gv));
          if (hh == 0 && r >= 7 && tok < S_LEN) g_gate[tok] = gv;
        }
      if (tid == 256) sts32(sb + A_BAR + 376, epoch);
      __syncwarp();
      bar_arrive(7, 384);
      bar_sync(3, 128);
      if (tid == 256) {
        count_up(&g_abar[0]);
        wait_count(&g_abar[0], NAUX * (epoch + 1));
        if (cta == 0) *(volatile unsigned*)&g_epoch2 = epoch + 1;
      }
      __syncwarp();
      bar_sync(10, 160);
    }
    if (cta < NH) {
      const int lim = w * 8 + (lane >> 2) - 2 * (lane & 3);
      const uint32_t oa = sb + A_OST + (w * 8 + (lane & 7)) * 128;
      const uint32_t d0 = ((sb + A_IN) & 0x3FFFF) >> 4;
      uint32_t p[5][4];
#pragma unroll
      for (int n = 0; n < 10; n++) p[n >> 1][1 + (n & 1)] = __shfl_sync(0xffffffffu, lane ^ n, n);
#pragma unroll 1
      for (int seg = 0; seg < NSEG; seg++) {
        const float gt = __ldcg(&g_gate[seg * 32 + w * 8 + (lane >> 2)]);
        float sc[20], d[32];
        mbar_wait(fullq, seg & 1);
        if (tid == 256) SSTAMP(2, seg);
        WG_FENCE();
#pragma unroll
        for (int k = 0; k < 8; k++) {
          const int o = ((k >> 2) * SEGB + (k & 3) * 256) >> 4;
          wgmma_n40_ss_tt(sc, desc_at(d0 + o, 128, 512, 0), desc_at(d0 + o + 256, 128, 1024, 0), k > 0);
        }
        WG_COMMIT();
        WG_WAIT(0);
        if (lane == 0) mbar_arrive(emptyq);
        float a[10];
#pragma unroll
        for (int i = 0; i < 10; i++) {
          a[i] = sc[(i >> 1) * 4 + (i & 1)] * (SM_SCALE * LOG2E);
          if (i < 8 && (i >> 1) * 8 + (i & 1) > lim) a[i] = -1.0e9f * LOG2E;
        }
        float m = max10(a);
        m = fmaxf(m, __shfl_xor_sync(0xffffffffu, m, 1)); m = fmaxf(m, __shfl_xor_sync(0xffffffffu, m, 2));
#pragma unroll
        for (int i = 0; i < 10; i++) a[i] = ex2(a[i] - m);
#pragma unroll
        for (int n = 0; n < 5; n++) {
          p[n][0] = pack_bf16(a[2 * n], a[2 * n + 1]); p[n][3] = p[n][0] | p[n][1];
          asm volatile("" : "+r"(p[n][0]), "+r"(p[n][3]) :: "memory");
        }
        float sum = ((a[0] + a[1]) + (a[2] + a[3])) + ((a[4] + a[5]) + (a[6] + a[7])) + (a[8] + a[9]);
        sum += __shfl_xor_sync(0xffffffffu, sum, 1);
        if (tid == 256) SSTAMP(3, seg);
        mbar_wait(fullv, seg & 1);
        WG_FENCE();
#pragma unroll
        for (int n = 0; n < 5; n++) wgmma_n64_rs(d, p[n], n < 4 ? desc_at(d0 + SEGB / 8 + 8 * n, 4096, 512, 0) : desc_at(d0 + SEGB / 8 + 512, 1024, 128, 0), n);
        WG_COMMIT();
        sum += __shfl_xor_sync(0xffffffffu, sum, 2);
        const float f = (1.f - gt) * rcp(sum);
        bar_sync(5, 160);
        WG_WAIT(0);
        if (lane == 0) mbar_arrive(emptyv);
        if (tid == 256) SSTAMP(4, seg);
#pragma unroll
        for (int q = 0; q < 4; q++) {
          const float* const o = d + (q & 1) * 16 + (q & 2);
          stsm4(oa + (q >> 1) * 4096 + ((((q & 1) * 4 + (lane >> 3)) ^ (lane & 7)) << 4), pack_bf16(o[0] * f, o[1] * f), pack_bf16(o[4] * f, o[5] * f),
                pack_bf16(o[8] * f, o[9] * f), pack_bf16(o[12] * f, o[13] * f));
        }
        fence_async();
        bar_sync(4, 160);
      }
    }
  } else {
    asm volatile("setmaxnreg.inc.sync.aligned.u32 200;");
    {
      const int g = lane >> 2, t = lane & 3;
      const uint32_t eb = sb + A_EPI + wg * A_EPW, d0 = (sb & 0x3FFFF) >> 4;
      const uint32_t own = (2 * t <= g ? 0xffffu : 0u) | (2 * t < g ? 0xffff0000u : 0u);
      const int kmin = 7 - 57 * tile - 16 * w;
#pragma unroll 1
      for (int c = -DRY; c < 4; c++) {
        float acc[96], tl[12];
#pragma unroll 1
        for (int r = c < 0 ? 4 : 0; r < 4; r++) {
#pragma unroll
          for (int st = 0; st < A_NS; st++) {
            const int ks = r * 9 + st;
            if (c == 0 && st % 3 == 0 && ks % 12 == 0) mbar_wait(fullx + 8 * (ks / 12), 0);
            mbar_wait(full1 + 8 * st, r & 1);
            const uint64_t da = desc_at(d0 + wg * (A_XH >> 4) + (ks >> 2) * 512 + (ks & 3) * 2, 16, 1024, 1);
            WG_FENCE();
            wgmma_n192_ss_nt(acc, da, desc_at(d0 + ((A_RING + st * A_WM) >> 4), 2048, 1024, 1), ks);
            if (!(AX & 2)) wgmma_n24_ss_nt(tl, da, desc_at(d0 + ((A_TAIL + st * A_WT) >> 4), 128, 256, 0), ks);
            WG_COMMIT();
            if (st == 0 && r == 2) bar_sync(11 + wg, 160);
            WG_WAIT(1);
            if (ks > 0 && lane == 0) mbar_arrive(empty1 + 8 * ((st + A_NS - 1) % A_NS));
          }
        }
        WG_WAIT(0);
        if (lane == 0 && c >= 0) mbar_arrive(empty1 + 8 * (A_NS - 1));
        ASTAMP(16 + (c & 3));
        uint32_t ql[9], qh[9], kl[9], kh[9], kx[10], vl[9], vh[9], vx[10];
#pragma unroll
        for (int j = 0; j < 9; j++) {
          const float* const q = j < 8 ? acc + 4 * j : tl, * const k = j < 8 ? acc + 32 + 4 * j : tl + 4, * const v = j < 8 ? acc + 64 + 4 * j : tl + 8;
          kh[j] = pack_bf16(k[2], k[3]); vh[j] = pack_bf16(v[2], v[3]);
          ql[j] = pack_bf16(q[0], q[1]); qh[j] = pack_bf16(q[2], q[3]); kl[j] = pack_bf16(k[0], k[1]); vl[j] = pack_bf16(v[0], v[1]);
        }
        if (w < 3) {
          const uint32_t ha = eb + 1024 + w * 2304 + lane * 16;
          stsm4(ha, kh[0], kh[1], kh[2], kh[3]); stsm4(ha + 512, kh[4], kh[5], kh[6], kh[7]);
          stsm4(ha + 1024, vh[0], vh[1], vh[2], vh[3]); stsm4(ha + 1536, vh[4], vh[5], vh[6], vh[7]);
          asm volatile("stmatrix.sync.aligned.m8n8.x2.shared.b16 [%0], {%1,%2};" :: "r"(ha + 2048), "r"(kh[8]), "r"(vh[8]) : "memory");
        }
        if (c == 0) bar_sync(7, 384); else bar_sync(1 + wg, 128);
        {
          const uint32_t ha = eb + 1024 + max(w - 1, 0) * 2304 + lane * 16;
          ldsm4(kx, ha); ldsm4(kx + 4, ha + 512); ldsm4t(vx, ha + 1024); ldsm4t(vx + 4, ha + 1536);
          asm volatile("ldmatrix.sync.aligned.m8n8.x1.shared.b16 {%0}, [%1];" : "=r"(kx[8]) : "r"(ha + 2048) : "memory");
          asm volatile("ldmatrix.sync.aligned.m8n8.x1.trans.shared.b16 {%0}, [%1];" : "=r"(vx[8]) : "r"(ha + 2176) : "memory");
        }
        const float gl = __uint_as_float(lds32(sb + A_GATE + (wg * 64 + w * 16 + g) * 4)), gh = __uint_as_float(lds32(sb + A_GATE + (wg * 64 + w * 16 + g + 8) * 4));
#pragma unroll
        for (int j = 0; j < 9; j++) { vl[j] = movm(vl[j]); vh[j] = movm(vh[j]); }
        bar_sync(1 + wg, 128);
        uint32_t ol[9], oh[9];
#pragma unroll
        for (int i = 0; i < 4; i++) {
          const int b = 2 * i;
          const uint32_t a[4] = {t >= i ? ql[b] : 0u, t >= i ? qh[b] : 0u, ql[b + 1], qh[b + 1]}, a4 = t <= i ? ql[b + 2] : 0u, a5 = t <= i ? qh[b + 2] : 0u;
          float sx[4], sl[4], sh[4];
          mma16816z(sx, a, kx[b], kx[b + 1]); mma16816z(sl, a, kl[b], kl[b + 1]); mma16816z(sh, a, kh[b], kh[b + 1]);
          mma1688(sx, a4, a5, kx[b + 2]); mma1688(sl, a4, a5, kl[b + 2]); mma1688(sh, a4, a5, kh[b + 2]);
          float e[4];
#pragma unroll
          for (int u = 0; u < 4; u++) {
            const int cc = 2 * t + (u & 1);
            e[u] = (cc <= g ? (u < 2 ? sl[u] : sh[u]) : (u < 2 ? sx[u] : sl[u])) * (0.23570226039551584f * LOG2E);
            if ((cc <= g ? cc : cc - 8) + (u & 2) * 4 < kmin) e[u] = -1.0e9f * LOG2E;
          }
          float m0 = fmaxf(e[0], e[1]), m1 = fmaxf(e[2], e[3]);
#pragma unroll
          for (int o = 1; o < 4; o <<= 1) { m0 = fmaxf(m0, __shfl_xor_sync(0xffffffffu, m0, o)); m1 = fmaxf(m1, __shfl_xor_sync(0xffffffffu, m1, o)); }
          e[0] = ex2(e[0] - m0); e[1] = ex2(e[1] - m0); e[2] = ex2(e[2] - m1); e[3] = ex2(e[3] - m1);
          const uint32_t p0 = pack_bf16(e[0], e[1]), p1 = pack_bf16(e[2], e[3]);
          const uint32_t p[4] = {p0 & ~own, 0u, p0 & own, p1 & ~own};
          float s0 = e[0] + e[1], s1 = e[2] + e[3];
#pragma unroll
          for (int o = 1; o < 4; o <<= 1) { s0 += __shfl_xor_sync(0xffffffffu, s0, o); s1 += __shfl_xor_sync(0xffffffffu, s1, o); }
          const float f0 = gl * rcp(s0), f1 = gh * rcp(s1);
#pragma unroll
          for (int j = b; j < b + 3; j++) {
            float o[4];
            mma16816z(o, p, vx[j], vl[j]);
            mma1688(o, 0u, p1 & own, vh[j]);
            const uint32_t lo = pack_bf16(o[0] * f0, o[1] * f0), hi = pack_bf16(o[2] * f1, o[3] * f1);
            if (j > b || i == 0) { ol[j] = lo; oh[j] = hi; }
            else { ol[j] = t >= i ? lo : ol[j]; oh[j] = t >= i ? hi : oh[j]; }
          }
        }
        const uint32_t sa = eb + 16 + (w * 16 + (lane & 15)) * 144 + (lane >> 4) * 16;
#pragma unroll
        for (int j = 0; j < 8; j += 2) stsm4(sa + j * 16, ol[j], oh[j], ol[j + 1], oh[j + 1]);
        asm volatile("stmatrix.sync.aligned.m8n8.x2.shared.b16 [%0], {%1,%2};" :: "r"(sa + 128), "r"(ol[8]), "r"(oh[8]) : "memory");
        fence_async();
        if (c >= 0) bar_arrive(13 + wg, 160); else bar_sync(1 + wg, 128);
        ASTAMP(20 + (c & 3));
      }
    }
    ASTAMP(3);
    uint32_t wa[36][4];
    mbar_wait(fullw, 0);
    const uint32_t la = sb + wg * 73728 + ((lane & 7) + ((lane >> 4) << 3)) * 128 + (((2 * w + ((lane >> 3) & 1)) ^ (lane & 7)) << 4);
#pragma unroll
    for (int k = 0; k < 36; k++) ldsm4t(wa[k], la + k * 2048);
    fence_async();
    bar_sync(6, 288);
    ASTAMP(4);
    float own[4] = {0.f, 0.f, 0.f, 0.f};
    uint4 v[3];
    auto fetch = [&](int seg) {
      const uint4* src = g_part + (((seg & 3) * 36 + cta) * 4) * 128 + (tid & 127);
#pragma unroll
      for (int j = 0; j < 3; j++) v[j] = AX & 16 ? make_uint4(0, 0, 0, 0) : ldg_relaxed(src + ((kq + 1 + j) & 3) * 128);
    };
    auto finish = [&](int seg) {
      const uint32_t tagv = ((seg >> 2) + 1) & 3;
      int n = 0;
#pragma unroll 1
      while (!(AX & 16) && __any_sync(0xffffffffu, (v[0].x & 3) != tagv || (v[1].x & 3) != tagv || (v[2].x & 3) != tagv) && ++n < SPIN_LIMIT) {
        if (seg < NSEG - ((TL & 2) ? 2 : 1)) __nanosleep(200);
        fetch(seg);
      }
#pragma unroll
      for (int j = 0; j < 3; j++) {
        own[0] += __uint_as_float(v[j].x & ~3u); own[1] += __uint_as_float(v[j].y); own[2] += __uint_as_float(v[j].z); own[3] += __uint_as_float(v[j].w);
      }
      uint32_t p0 = pack_bf16(own[0], own[1]), p1 = pack_bf16(own[2], own[3]);
      asm volatile("movmatrix.sync.aligned.m8n8.trans.b16 %0, %0;" : "+r"(p0));
      asm volatile("movmatrix.sync.aligned.m8n8.trans.b16 %0, %0;" : "+r"(p1));
      uint32_t* o = (uint32_t*)(out + (size_t)(seg * 32 + kq * 8 + (lane >> 2)) * DM + nsl * 64 + w * 16) + (lane & 3);
      o[0] = p0; o[4] = p1;
    };
    float acc[16];
    auto stream = [&](int sl, int keep) {
      const uint64_t db = make_desc(sb + sl * XT, 16, 1024, 1);
      WG_FENCE();
#pragma unroll
      for (int k = 0; k < 36; k++) wgmma_n32_rs(acc, wa[k][0], wa[k][1], wa[k][2], wa[k][3], db + (k >> 2) * 256 + (k & 3) * 2, k ? 1 : keep);
      WG_COMMIT();
    };
    const uint32_t ex = sb + A_EX + (tid & 127) * 16;
    if (wg == 0) {
#pragma unroll
      for (int i = 0; i < 16; i++) acc[i] = 0.f;
#pragma unroll 1
      for (int seg = 0; seg < NSEG; seg++) {
        const int sl = (seg & 1) * 2;
        mbar_wait(full3 + 8 * sl, (seg >> 1) & 1);
        if (kq == 3) {
          const uint64_t da = make_desc(sb + A_XW, 8192, 1024, 1), de = make_desc(sb + A_XT + (seg & 1) * 4096, 16, 1024, 1);
          WG_FENCE();
#pragma unroll
          for (int j = 0; j < 4; j++) wgmma_n32_ss_tn(acc, da + j * 128, de + j * 2, j);
          WG_COMMIT();
          WG_WAIT(0);
        }
        if (!(AX & 64)) stream(sl, kq == 3);
        bar_arrive(9, 256);
        WG_WAIT(0);
        if (lane == 0) mbar_arrive(empty3 + 8 * sl);
#pragma unroll
        for (int i = 0; i < 4; i++)
          sts128(ex + (seg & 1) * 8192 + i * 2048, __float_as_uint(acc[4 * i]), __float_as_uint(acc[4 * i + 1]), __float_as_uint(acc[4 * i + 2]), __float_as_uint(acc[4 * i + 3]));
        bar_sync(1, 256);
      }
    } else {
#pragma unroll 1
      for (int seg = 0; seg < NSEG; seg++) {
        const int sl = (seg & 1) * 2 + 1;
        mbar_wait(full3 + 8 * sl, (seg >> 1) & 1);
        if (tid == 128) SSTAMP(6, seg);
        bar_sync(9, 256);
        if (!(AX & 64)) stream(sl, 0);
        bar_sync(1, 256);
        fetch(max(seg - 1, 0));
        WG_WAIT(0);
        if (lane == 0) mbar_arrive(empty3 + 8 * sl);
        float nxt[4] = {0.f, 0.f, 0.f, 0.f};
        uint4* dst = g_part + (((seg & 3) * 36 + nsl * 4) * 4 + kq) * 128 + (tid & 127);
#pragma unroll
        for (int j = 0; j < 4; j++) {
          float o[4];
          lds128f(ex + (seg & 1) * 8192 + j * 2048, o);
#pragma unroll
          for (int i = 0; i < 4; i++) { o[i] += acc[4 * j + i]; if (j == kq) nxt[i] = o[i]; }
          if (j != kq && !(AX & 16)) stg_relaxed(dst + j * 512, (__float_as_uint(o[0]) & ~3u) | (((seg >> 2) + 1) & 3), __float_as_uint(o[1]), __float_as_uint(o[2]), __float_as_uint(o[3]));
        }
        if (tid == 128) SSTAMP(7, seg);
        if (seg > 0) finish(seg - 1);
        if (tid == 128) SSTAMP(8, seg);
#pragma unroll
        for (int i = 0; i < 4; i++) own[i] = nxt[i];
        if ((seg & 7) == 6) ASTAMP(5 + (seg >> 3));
      }
      fetch(NSEG - 1);
      finish(NSEG - 1);
    }
    ASTAMP(13);
    TSTAMP(3);
    bar_sync(6, 288);
  }
}

typedef CUresult (*EncodeFn)(CUtensorMap*, CUtensorMapDataType, cuuint32_t, void*, const cuuint64_t*, const cuuint64_t*,
                             const cuuint32_t*, const cuuint32_t*, CUtensorMapInterleave, CUtensorMapSwizzle,
                             CUtensorMapL2promotion, CUtensorMapFloatOOBfill);
static void make_map(EncodeFn enc, CUtensorMap* m, const void* p, int rows, int cols, int box_rows) {
  cuuint64_t dims[2] = {(cuuint64_t)cols, (cuuint64_t)rows};
  cuuint64_t strides[1] = {(cuuint64_t)cols * 2};
  cuuint32_t box[2] = {64, (cuuint32_t)box_rows};
  cuuint32_t es[2] = {1, 1};
  enc(m, CU_TENSOR_MAP_DATA_TYPE_BFLOAT16, 2, (void*)p, dims, strides, box, es, CU_TENSOR_MAP_INTERLEAVE_NONE,
      CU_TENSOR_MAP_SWIZZLE_128B, CU_TENSOR_MAP_L2_PROMOTION_L2_128B, CU_TENSOR_MAP_FLOAT_OOB_FILL_NONE);
}

constexpr int g_poll = POLL_NS;
extern "C" void kernel_launch(void* const* d_in, const int* in_sizes, int n_in, void* d_out, int out_size) {
  const bf16* x = (const bf16*)d_in[0];
  const bf16* wqkvA = (const bf16*)d_in[1];
  const bf16* woA = (const bf16*)d_in[2];
  const bf16* mem0 = (const bf16*)d_in[4];
  const bf16* Wq = (const bf16*)d_in[5];
  const bf16* Wk = (const bf16*)d_in[6];
  const bf16* Wv = (const bf16*)d_in[7];
  const bf16* Wo = (const bf16*)d_in[8];
  const bf16* gate_w = (const bf16*)d_in[10];
  static EncodeFn enc = nullptr;
  static void *pO = nullptr, *pR = nullptr;
  if (!enc) {
    cudaDriverEntryPointQueryResult qr;
    cudaGetDriverEntryPoint("cuTensorMapEncodeTiled", (void**)&enc, cudaEnableDefault, &qr);
    cudaGetSymbolAddress(&pO, g_Ocat);
    cudaGetSymbolAddress(&pR, g_red_raw);
    cudaFuncSetAttribute(rec_kernel, cudaFuncAttributeMaxDynamicSharedMemorySize, SM_TOTAL);
    cudaFuncSetAttribute(aux_kernel, cudaFuncAttributeMaxDynamicSharedMemorySize, A_TOTAL);
  }
  RMaps rm;
  rm.poll = g_poll;
  rm.red = (unsigned char*)(((uintptr_t)pR + 262143) & ~(uintptr_t)262143);
  {
    cuuint64_t dims[3] = {64, S_LEN, 9}, strides[2] = {DM * 2, 128};
    cuuint32_t box[3] = {64, 32, 9}, es[3] = {1, 1, 1};
    enc(&rm.x, CU_TENSOR_MAP_DATA_TYPE_BFLOAT16, 3, (void*)x, dims, strides, box, es, CU_TENSOR_MAP_INTERLEAVE_NONE,
        CU_TENSOR_MAP_SWIZZLE_128B, CU_TENSOR_MAP_L2_PROMOTION_L2_128B, CU_TENSOR_MAP_FLOAT_OOB_FILL_NONE);
  }
  make_map(enc, &rm.wq, Wq, DM, 4096, 192);
  make_map(enc, &rm.wk, Wk, DM, 4096, 192);
  make_map(enc, &rm.wv, Wv, DM, 4096, 192);
  make_map(enc, &rm.wo, Wo, 4096, DM, 128);
  AMaps am;
  {
    cuuint32_t es[4] = {1, 1, 1, 1};
    cuuint64_t dx[4] = {64, 2, S_LEN / 2, 9}, sx[3] = {DM * 2, DM * 4, 128};
    cuuint32_t bx[4] = {64, 1, 64, 3};
    enc(&am.x, CU_TENSOR_MAP_DATA_TYPE_BFLOAT16, 4, (void*)x, dx, sx, bx, es, CU_TENSOR_MAP_INTERLEAVE_NONE,
        CU_TENSOR_MAP_SWIZZLE_128B, CU_TENSOR_MAP_L2_PROMOTION_L2_128B, CU_TENSOR_MAP_FLOAT_OOB_FILL_NONE);
    cuuint64_t dw[3] = {DM, DM, 3}, sw[2] = {DM * 6, DM * 2};
    cuuint32_t bw[3] = {64, 16, 3}, bt[3] = {8, 16, 3};
    enc(&am.wa, CU_TENSOR_MAP_DATA_TYPE_BFLOAT16, 3, (void*)wqkvA, dw, sw, bw, es, CU_TENSOR_MAP_INTERLEAVE_NONE,
        CU_TENSOR_MAP_SWIZZLE_128B, CU_TENSOR_MAP_L2_PROMOTION_L2_128B, CU_TENSOR_MAP_FLOAT_OOB_FILL_NONE);
    enc(&am.wt, CU_TENSOR_MAP_DATA_TYPE_BFLOAT16, 3, (void*)wqkvA, dw, sw, bt, es, CU_TENSOR_MAP_INTERLEAVE_NONE,
        CU_TENSOR_MAP_SWIZZLE_NONE, CU_TENSOR_MAP_L2_PROMOTION_NONE, CU_TENSOR_MAP_FLOAT_OOB_FILL_NONE);
    cuuint64_t dz[3] = {KCAT, 2, S_LEN / 2}, sz[2] = {KCAT * 2, KCAT * 4};
    cuuint32_t bz[3] = {72, 1, 57};
    enc(&am.oa, CU_TENSOR_MAP_DATA_TYPE_BFLOAT16, 3, pO, dz, sz, bz, es, CU_TENSOR_MAP_INTERLEAVE_NONE,
        CU_TENSOR_MAP_SWIZZLE_NONE, CU_TENSOR_MAP_L2_PROMOTION_NONE, CU_TENSOR_MAP_FLOAT_OOB_FILL_NONE);
  }
  {
    cuuint64_t dims[3] = {64, S_LEN, KCAT / 64}, strides[2] = {KCAT * 2, 128};
    cuuint32_t box[3] = {64, 32, 9}, es[3] = {1, 1, 1};
    make_map(enc, &am.o, pO, S_LEN, KCAT, 32);
    enc(&am.o3, CU_TENSOR_MAP_DATA_TYPE_BFLOAT16, 3, pO, dims, strides, box, es, CU_TENSOR_MAP_INTERLEAVE_NONE,
        CU_TENSOR_MAP_SWIZZLE_128B, CU_TENSOR_MAP_L2_PROMOTION_L2_128B, CU_TENSOR_MAP_FLOAT_OOB_FILL_NONE);
  }
  make_map(enc, &am.wob, Wo, 4096, DM, 64);
  make_map(enc, &am.woa, woA, DM, DM, 64);

  rec_kernel<<<96, 384, SM_TOTAL, cudaStreamPerThread>>>(rm, x, mem0);
  cudaLaunchConfig_t cfg = {};
  cfg.gridDim = dim3(NAUX); cfg.blockDim = dim3(512); cfg.dynamicSmemBytes = A_TOTAL; cfg.stream = cudaStreamPerThread;
  cudaLaunchAttribute at[1];
  at[0].id = cudaLaunchAttributeProgrammaticStreamSerialization; at[0].val.programmaticStreamSerializationAllowed = 1;
  cfg.attrs = at; cfg.numAttrs = 1;
  if (XP & 16) cfg.numAttrs = 0;
  if (!(XP & 64)) cudaLaunchKernelEx(&cfg, aux_kernel, am, wqkvA, gate_w, (bf16*)d_out);
}
```

```cpp
#include <cuda_runtime.h>
#include <cuda_bf16.h>
#include <cuda_fp16.h>
#include <cuda.h>
#include <stdint.h>

typedef __nv_bfloat16 bf16;

constexpr int S_LEN = 2048, DM = 576, NH = 32, DH = 128, NSEG = 64, KCAT = 4096 + 576;
constexpr int NAUXSEG = NSEG - 2;
constexpr int NAUX = 36;
#define RED_LINE(i) (((i) >> 2) * 4096 + ((i) & 1) * 256 + ((i) & 2) * 512)
#define RED_SLOT(s) (((s) & 1) * 128 + ((s) & 2) * 256)

#define POLL_NS 896
#define NII 18
#define W3PRE 4
#define W3MID 4
#define GF 0
#define B5POS 0
#define NUP 4
#define UPF 1
#define B3Q 9
#define B3F 0
#define GATE 7
#define NTL 2
#define B7R 1
#define VS0 1
#define VS1 0
#define VLATE(w) ((w) == 0 ? VS0 == 1 : (w) == 1 ? VS1 == 1 : false)
#define HOIST 1
#define GDW 0
#define RSLOW 0
#define CSY 0
#define DD 2
#define N12 18
#define N14 18
#define HP 0
#define HL 0
#define WL 1
#define RV 3
#define RET 1
#define TL 6
#define CLR 1
#define RFW 0
#define NIC 0
#define LEAD 0
#define FIN16 1
#define VXG 0
#define NRING 20
#define EXD 0
#define HDLY 0
#define F10 1
#define NPROBE 2
#define QM 0
#define N5 224
#define KP(i) (((i) >> 1) + 4 * ((i) & 1))
#define SPIN_LIMIT (1 << 14)
#define XP 0

__device__ __align__(1024) bf16 g_Ocat[S_LEN * KCAT];
__device__ __align__(1024) unsigned char g_red_raw[2 * 262144];
constexpr int HINT_OFF = 2048;
__device__ __align__(16) float g_gate[S_LEN];
__device__ __align__(128) uint4 g_stats[96 * 2];
__device__ unsigned g_epoch;
__device__ unsigned g_epoch2;
__device__ unsigned g_ocnt[NSEG * 32];
__device__ unsigned g_abar[3 * 32];
__device__ unsigned long long g_amax[2 * 16];
__device__ unsigned g_scnt[NSEG * 32 * 8];
__device__ __align__(1024) unsigned char g_seg[NRING * 96 * 10240];
__device__ unsigned g_used[NH * 32];
__device__ __align__(1024) uint4 g_part[4 * 36 * 4 * 128];
__device__ int g_err;
#define TSTAMP(i)
#define PROF(idx)
#define PROFP(idx)
#define RSTAMP(k)
#define STAMP(idx)
#define ASTAMP(idx)
#define SSTAMP(k, seg)
#define WSTAMP(idx)

#define DI __device__ __forceinline__
DI uint32_t smem_u32(const void* p) { return (uint32_t)__cvta_generic_to_shared(p); }
DI uint32_t clock32() { uint32_t c; asm volatile("mov.u32 %0, %%clock;" : "=r"(c) :: "memory"); return c; }
DI uint32_t gtime() { uint32_t c; asm volatile("mov.u32 %0, %%globaltimer_lo;" : "=r"(c) :: "memory"); return c; }
DI uint32_t ldg_relaxed32(const void* p) { uint32_t v; asm volatile("ld.relaxed.gpu.global.b32 %0, [%1];" : "=r"(v) : "l"(p) : "memory"); return v; }
DI uint32_t ldg_acquire32(const void* p) { uint32_t v; asm volatile("ld.acquire.gpu.global.b32 %0, [%1];" : "=r"(v) : "l"(p) : "memory"); return v; }
DI void stg_relaxed32(void* p, uint32_t v) { asm volatile("st.relaxed.gpu.global.b32 [%0], %1;" :: "l"(p), "r"(v) : "memory"); }
DI int head_id() { int c; asm volatile("mov.u32 %0, %%clusterid.x;" : "=r"(c)); return c; }
DI uint32_t mapa(uint32_t a, uint32_t r) { uint32_t o; asm("mapa.shared::cluster.u32 %0, %1, %2;" : "=r"(o) : "r"(a), "r"(r)); return o; }
DI void cluster_arrive() { asm volatile("barrier.cluster.arrive.relaxed.aligned;" ::: "memory"); }
DI void cluster_wait() { asm volatile("barrier.cluster.wait.aligned;" ::: "memory"); }
DI void cluster_sync() { asm volatile("barrier.cluster.arrive.release.aligned;\nbarrier.cluster.wait.acquire.aligned;" ::: "memory"); }
DI void mbar_init(uint32_t b, uint32_t c) { asm volatile("mbarrier.init.shared::cta.b64 [%0], %1;" :: "r"(b), "r"(c) : "memory"); }
DI void mbar_expect(uint32_t b, uint32_t tx) { asm volatile("mbarrier.arrive.expect_tx.shared::cta.b64 _, [%0], %1;" :: "r"(b), "r"(tx) : "memory"); }
DI void mbar_arrive(uint32_t b) { asm volatile("mbarrier.arrive.shared::cta.b64 _, [%0];" :: "r"(b) : "memory"); }
DI void mbar_wait(uint32_t b, uint32_t par) {
  asm volatile("{\n.reg .pred p;\n.reg .u32 n, q;\nmov.u32 n, 0;\n"
               "WL: add.u32 n, n, 1;\nshr.u32 q, n, 12;\nxor.b32 q, q, %1;\n"
               "mbarrier.try_wait.parity.shared::cta.b64 p, [%0], q;\n@!p bra.uni WL;\n}"
               :: "r"(b), "r"(par) : "memory");
}
DI void mbar_wait_fast(uint32_t b, uint32_t par) {
  asm volatile("{\n.reg .pred p;\n.reg .u32 n, q;\nmbarrier.try_wait.parity.shared::cta.b64 p, [%0], %1;\n@p bra.uni WD;\nmov.u32 n, 0;\n"
               "WL: add.u32 n, n, 1;\nshr.u32 q, n, 12;\nxor.b32 q, q, %1;\n"
               "mbarrier.try_wait.parity.shared::cta.b64 p, [%0], q;\n@!p bra.uni WL;\nWD:\n}"
               :: "r"(b), "r"(par) : "memory");
}
DI void wait_until(uint32_t t) {
  const uint32_t now = gtime();
  t = min(t, now + 8192);
  asm volatile("{\n.reg .pred p;\n.reg .u32 c;\nTL: mov.u32 c, %%globaltimer_lo;\nsetp.lt.u32 p, c, %0;\n@p bra.uni TL;\n}" :: "r"(t) : "memory");
}
#define PIN(v) v = __shfl_xor_sync(0xffffffffu, v, 0)
#define SCHED_FENCE(k) asm volatile("{\n.reg .pred p;\nsetp.eq.u32 p, %0, %1;\n@p exit;\n}" :: "r"(fence_reg), "r"(k) : "memory")
#define MEM_ORDER(k) asm volatile("{\n.reg .pred p;\nsetp.eq.u32 p, %0, %1;\n@p st.shared.u32 [%0], %0;\n}" :: "r"(fence_reg), "r"(k + 64) : "memory")
DI void bar_sync(int id, int n) { asm volatile("bar.sync %0, %1;" :: "r"(id), "r"(n) : "memory"); }
DI void bar_arrive(int id, int n) { asm volatile("bar.arrive %0, %1;" :: "r"(id), "r"(n) : "memory"); }
DI void fence_async() { asm volatile("fence.proxy.async.shared::cta;" ::: "memory"); }
DI void st_async4(uint32_t a, uint32_t x, uint32_t y, uint32_t z, uint32_t w, uint32_t mb) {
  asm volatile("st.async.weak.shared::cluster.mbarrier::complete_tx::bytes.v4.b32 [%0], {%1,%2,%3,%4}, [%5];"
               :: "r"(a), "r"(x), "r"(y), "r"(z), "r"(w), "r"(mb) : "memory");
}
DI void st_async2(uint32_t a, uint32_t x, uint32_t y, uint32_t mb) {
  asm volatile("st.async.weak.shared::cluster.mbarrier::complete_tx::bytes.v2.b32 [%0], {%1,%2}, [%3];"
               :: "r"(a), "r"(x), "r"(y), "r"(mb) : "memory");
}
DI void sts32(uint32_t a, uint32_t x) { asm volatile("st.shared.b32 [%0], %1;" :: "r"(a), "r"(x) : "memory"); }
DI void sts64(uint32_t a, uint32_t x, uint32_t y) { asm volatile("st.shared.v2.b32 [%0], {%1,%2};" :: "r"(a), "r"(x), "r"(y) : "memory"); }
DI void sts128(uint32_t a, uint32_t x, uint32_t y, uint32_t z, uint32_t w) {
  asm volatile("st.shared.v4.b32 [%0], {%1,%2,%3,%4};" :: "r"(a), "r"(x), "r"(y), "r"(z), "r"(w) : "memory");
}
DI uint32_t lds32(uint32_t a) { uint32_t x; asm volatile("ld.shared.b32 %0, [%1];" : "=r"(x) : "r"(a) : "memory"); return x; }
DI void lds64(uint32_t a, uint32_t& x, uint32_t& y) { asm volatile("ld.shared.v2.b32 {%0,%1}, [%2];" : "=r"(x), "=r"(y) : "r"(a) : "memory"); }
DI void lds128(uint32_t a, uint32_t* r) {
  asm volatile("ld.shared.v4.b32 {%0,%1,%2,%3}, [%4];" : "=r"(r[0]), "=r"(r[1]), "=r"(r[2]), "=r"(r[3]) : "r"(a) : "memory");
}
DI void lds128f(uint32_t a, float* r) {
  asm volatile("ld.shared.v4.f32 {%0,%1,%2,%3}, [%4];" : "=f"(r[0]), "=f"(r[1]), "=f"(r[2]), "=f"(r[3]) : "r"(a) : "memory");
}
DI void lds64f(uint32_t a, float* r) { asm volatile("ld.shared.v2.f32 {%0,%1}, [%2];" : "=f"(r[0]), "=f"(r[1]) : "r"(a) : "memory"); }
DI void ldsm4t(uint32_t* r, uint32_t a) {
  asm volatile("ldmatrix.sync.aligned.m8n8.x4.trans.shared.b16 {%0,%1,%2,%3}, [%4];"
               : "=r"(r[0]), "=r"(r[1]), "=r"(r[2]), "=r"(r[3]) : "r"(a) : "memory");
}
DI void ldsm4t_in(uint32_t* r, uint32_t a, uint32_t t) {
  asm volatile("{\n.reg .pred p;\nsetp.ne.u32 p, %5, 0;\n@p ldmatrix.sync.aligned.m8n8.x4.trans.shared.b16 {%0,%1,%2,%3}, [%4];\n}"
               : "+r"(r[0]), "+r"(r[1]), "+r"(r[2]), "+r"(r[3]) : "r"(a), "r"(t) : "memory");
}
DI void lds128_in(uint32_t* r, uint32_t a, uint32_t t) {
  asm volatile("{\n.reg .pred p;\nsetp.ne.u32 p, %5, 0;\n@p ld.shared.v4.b32 {%0,%1,%2,%3}, [%4];\n}"
               : "+r"(r[0]), "+r"(r[1]), "+r"(r[2]), "+r"(r[3]) : "r"(a), "r"(t) : "memory");
}
DI void ldsm2t_in(uint32_t* r, uint32_t a, uint32_t t) {
  asm volatile("{\n.reg .pred p;\nsetp.ne.u32 p, %3, 0;\n@p ldmatrix.sync.aligned.m8n8.x2.trans.shared.b16 {%0,%1}, [%2];\n}" : "+r"(r[0]), "+r"(r[1]) : "r"(a), "r"(t) : "memory");
}
DI void reserve2(uint32_t* r) { asm volatile("{\n.reg .u64 t;\nmov.u64 t, %%clock64;\nmov.b64 {%0, %1}, t;\n}" : "=r"(r[0]), "=r"(r[1])); }
DI void scale_sum(float& x, float& y, float s, uint32_t t) {
  asm volatile("{\n.reg .pred p;\nsetp.ne.u32 p, %2, 0;\n@p mul.f32 %0, %0, %1;\n}" : "+f"(y) : "f"(s), "r"(t));
  asm volatile("{\n.reg .pred p;\nsetp.ne.u32 p, %3, 1;\n@p fma.rn.f32 %0, %0, %1, %2;\n}" : "+f"(x) : "f"(s), "f"(y), "r"(t));
}
DI void ldsm4(uint32_t* r, uint32_t a) {
  asm volatile("ldmatrix.sync.aligned.m8n8.x4.shared.b16 {%0,%1,%2,%3}, [%4];"
               : "=r"(r[0]), "=r"(r[1]), "=r"(r[2]), "=r"(r[3]) : "r"(a) : "memory");
}
DI void st_async1(uint32_t a, uint32_t x, uint32_t mb) {
  asm volatile("st.async.weak.shared::cluster.mbarrier::complete_tx::bytes.b32 [%0], %1, [%2];" :: "r"(a), "r"(x), "r"(mb) : "memory");
}
DI void stsm4(uint32_t a, uint32_t x, uint32_t y, uint32_t z, uint32_t w) {
  asm volatile("stmatrix.sync.aligned.m8n8.x4.shared.b16 [%0], {%1,%2,%3,%4};" :: "r"(a), "r"(x), "r"(y), "r"(z), "r"(w) : "memory");
}
DI void stsm4t(uint32_t a, uint32_t x, uint32_t y, uint32_t z, uint32_t w) {
  asm volatile("stmatrix.sync.aligned.m8n8.x4.trans.shared.b16 [%0], {%1,%2,%3,%4};" :: "r"(a), "r"(x), "r"(y), "r"(z), "r"(w) : "memory");
}
DI uint32_t pack_bf16(float lo, float hi) { uint32_t r; asm("cvt.rn.bf16x2.f32 %0, %1, %2;" : "=r"(r) : "f"(hi), "f"(lo)); return r; }
DI uint32_t pack_f16(float lo, float hi) { uint32_t r; asm("cvt.rn.f16x2.f32 %0, %1, %2;" : "=r"(r) : "f"(hi), "f"(lo)); return r; }
DI float ex2(float x) { float y; asm("ex2.approx.ftz.f32 %0, %1;" : "=f"(y) : "f"(x)); return y; }
DI float rcp(float x) { float y; asm("rcp.approx.ftz.f32 %0, %1;" : "=f"(y) : "f"(x)); return y; }
DI float bf_lo(uint32_t x) { return __uint_as_float(x << 16); }
DI float bf_hi(uint32_t x) { return __uint_as_float(x & 0xffff0000u); }
DI void mma16816(float* d, const uint32_t* a, uint32_t b0, uint32_t b1) {
  asm volatile("mma.sync.aligned.m16n8k16.row.col.f32.bf16.bf16.f32 {%0,%1,%2,%3}, {%4,%5,%6,%7}, {%8,%9}, {%0,%1,%2,%3};"
               : "+f"(d[0]), "+f"(d[1]), "+f"(d[2]), "+f"(d[3]) : "r"(a[0]), "r"(a[1]), "r"(a[2]), "r"(a[3]), "r"(b0), "r"(b1));
}
DI void mma16816z(float* d, const uint32_t* a, uint32_t b0, uint32_t b1) {
  asm volatile("mma.sync.aligned.m16n8k16.row.col.f32.bf16.bf16.f32 {%0,%1,%2,%3}, {%4,%5,%6,%7}, {%8,%9}, {%10,%10,%10,%10};"
               : "=f"(d[0]), "=f"(d[1]), "=f"(d[2]), "=f"(d[3]) : "r"(a[0]), "r"(a[1]), "r"(a[2]), "r"(a[3]), "r"(b0), "r"(b1), "f"(0.f));
}
DI void mma1688z(float* d, uint32_t a0, uint32_t a1, uint32_t b0) {
  asm volatile("mma.sync.aligned.m16n8k8.row.col.f32.bf16.bf16.f32 {%0,%1,%2,%3}, {%4,%5}, {%6}, {%7,%7,%7,%7};"
               : "=f"(d[0]), "=f"(d[1]), "=f"(d[2]), "=f"(d[3]) : "r"(a0), "r"(a1), "r"(b0), "f"(0.f));
}
DI void mma1688(float* d, uint32_t a0, uint32_t a1, uint32_t b0) {
  asm volatile("mma.sync.aligned.m16n8k8.row.col.f32.bf16.bf16.f32 {%0,%1,%2,%3}, {%4,%5}, {%6}, {%0,%1,%2,%3};"
               : "+f"(d[0]), "+f"(d[1]), "+f"(d[2]), "+f"(d[3]) : "r"(a0), "r"(a1), "r"(b0));
}
DI void ldsm2t(uint32_t* r, uint32_t a) {
  asm volatile("ldmatrix.sync.aligned.m8n8.x2.trans.shared.b16 {%0,%1}, [%2];" : "=r"(r[0]), "=r"(r[1]) : "r"(a) : "memory");
}
DI uint32_t add_bf16(uint32_t a, uint32_t b) { uint32_t r; asm("add.rn.bf16x2 %0, %1, %2;" : "=r"(r) : "r"(a), "r"(b)); return r; }
DI uint32_t mul_bf16(uint32_t a, uint32_t b) { uint32_t r; asm("mul.rn.bf16x2 %0, %1, %2;" : "=r"(r) : "r"(a), "r"(b)); return r; }
DI uint64_t make_desc(uint32_t addr, uint32_t lbo, uint32_t sbo, uint32_t swz) {
  return (uint64_t)((addr & 0x3FFFF) >> 4) | ((uint64_t)(lbo >> 4) << 16) | ((uint64_t)(sbo >> 4) << 32) | ((uint64_t)swz << 62);
}
DI uint64_t desc_at(uint32_t a16, uint32_t lbo, uint32_t sbo, uint32_t swz) {
  uint64_t d; asm("mov.b64 %0, {%1, %2};" : "=l"(d) : "r"(a16 + ((lbo >> 4) << 16)), "r"((sbo >> 4) | (swz << 30)));
  return d;
}
#define WG_FENCE() asm volatile("wgmma.fence.sync.aligned;" ::: "memory")
#define WG_COMMIT() asm volatile("wgmma.commit_group.sync.aligned;" ::: "memory")
#define WG_WAIT(n) asm volatile("wgmma.wait_group.sync.aligned %0;" :: "n"(n) : "memory")
#define ACC8(d, o) "+f"(d[o]), "+f"(d[o + 1]), "+f"(d[o + 2]), "+f"(d[o + 3]), "+f"(d[o + 4]), "+f"(d[o + 5]), "+f"(d[o + 6]), "+f"(d[o + 7])
DI void wgmma_n32_rs(float* d, uint32_t a0, uint32_t a1, uint32_t a2, uint32_t a3, uint64_t db, int acc) {
  asm volatile("{\n.reg .pred p;\nsetp.ne.b32 p, %21, 0;\n"
               "wgmma.mma_async.sync.aligned.m64n32k16.f32.bf16.bf16 {%0,%1,%2,%3,%4,%5,%6,%7,%8,%9,%10,%11,%12,%13,%14,%15}, "
               "{%16,%17,%18,%19}, %20, p, 1, 1, 0;\n}\n"
               : ACC8(d, 0), ACC8(d, 8) : "r"(a0), "r"(a1), "r"(a2), "r"(a3), "l"(db), "r"(acc));
}
template <int TA>
DI void wgmma_n32_ss(float* d, uint64_t da, uint64_t db, int acc) {
  asm volatile("{\n.reg .pred p;\nsetp.ne.b32 p, %18, 0;\n"
               "wgmma.mma_async.sync.aligned.m64n32k16.f32.bf16.bf16 {%0,%1,%2,%3,%4,%5,%6,%7,%8,%9,%10,%11,%12,%13,%14,%15}, "
               "%16, %17, p, 1, 1, %19, 1;\n}\n"
               : ACC8(d, 0), ACC8(d, 8) : "l"(da), "l"(db), "r"(acc), "n"(TA));
}
DI void tma_load(uint32_t dst, const CUtensorMap* m, int c0, int c1, uint32_t mb) {
  asm volatile("cp.async.bulk.tensor.2d.shared::cluster.global.mbarrier::complete_tx::bytes [%0], [%1, {%3, %4}], [%2];"
               :: "r"(dst), "l"(m), "r"(mb), "r"(c0), "r"(c1) : "memory");
}
DI void tma_load3(uint32_t dst, const CUtensorMap* m, int row, uint32_t mb) {
  asm volatile("cp.async.bulk.tensor.3d.shared::cluster.global.mbarrier::complete_tx::bytes [%0], [%1, {%3, %4, %3}], [%2];"
               :: "r"(dst), "l"(m), "r"(mb), "r"(0), "r"(row) : "memory");
}
DI bool elect_one() {
  uint32_t p;
  asm volatile("{\n.reg .pred p;\nelect.sync _|p, 0xffffffff;\nselp.u32 %0, 1, 0, p;\n}" : "=r"(p));
  return p;
}
DI void bulk_s2s(uint32_t dst, uint32_t src, uint32_t bytes, uint32_t mb) {
  asm volatile("cp.async.bulk.shared::cluster.shared::cta.mbarrier::complete_tx::bytes [%0], [%1], %2, [%3];"
               :: "r"(dst), "r"(src), "r"(bytes), "r"(mb) : "memory");
}
DI void tma_prefetch(const CUtensorMap* m, int c0, int c1) {
  asm volatile("cp.async.bulk.prefetch.tensor.2d.L2.global.tile [%0, {%1, %2}];" :: "l"(m), "r"(c0), "r"(c1) : "memory");
}
DI void tma_store(const CUtensorMap* m, uint32_t src, int c0, int c1) {
  asm volatile("cp.async.bulk.tensor.2d.global.shared::cta.bulk_group [%0, {%2, %3}], [%1];" :: "l"(m), "r"(src), "r"(c0), "r"(c1) : "memory");
}
DI uint4 ldg_relaxed(const void* p) {
  uint4 v;
  asm volatile("ld.relaxed.gpu.global.v4.b32 {%0,%1,%2,%3}, [%4];" : "=r"(v.x), "=r"(v.y), "=r"(v.z), "=r"(v.w) : "l"(p) : "memory");
  return v;
}
DI void stg_relaxed(void* p, uint32_t x, uint32_t y, uint32_t z, uint32_t w) {
  asm volatile("st.relaxed.gpu.global.v4.b32 [%0], {%1,%2,%3,%4};" :: "l"(p), "r"(x), "r"(y), "r"(z), "r"(w) : "memory");
}
DI void red_f16x8(void* p, uint32_t x, uint32_t y, uint32_t z, uint32_t w) {
  asm volatile("red.relaxed.gpu.global.add.noftz.v4.f16x2 [%0], {%1,%2,%3,%4};" :: "l"(p), "r"(x), "r"(y), "r"(z), "r"(w) : "memory");
}
DI void sq_acc(uint32_t& a, uint32_t x) { asm("fma.rn.bf16x2 %0, %1, %1, %0;" : "+r"(a) : "r"(x)); }
DI __half2 amax4(__half2 h, const uint32_t* v) {
  h = __hmax2_nan(__hmax2_nan(h, __habs2(*(const __half2*)&v[0])), __habs2(*(const __half2*)&v[1]));
  return __hmax2_nan(__hmax2_nan(h, __habs2(*(const __half2*)&v[2])), __habs2(*(const __half2*)&v[3]));
}
DI uint32_t wexp(__half2 h) { const uint32_t u = *(const uint32_t*)&h; return __reduce_max_sync(0xffffffffu, max((u >> 16) & 0x7fffu, u & 0x7fffu)) >> 7; }
DI float max10(const float* a) {
  return fmaxf(fmaxf(fmaxf(fmaxf(a[0], a[1]), fmaxf(a[2], a[3])), fmaxf(fmaxf(a[4], a[5]), fmaxf(a[6], a[7]))), fmaxf(a[8], a[9]));
}
DI float quad_max(float m) {
  return fmaxf(fmaxf(m, __shfl_xor_sync(0xffffffffu, m, 1)), fmaxf(__shfl_xor_sync(0xffffffffu, m, 2), __shfl_xor_sync(0xffffffffu, m, 3)));
}
DI float warp_sum(float v) {
#pragma unroll
  for (int o = 16; o; o >>= 1) v += __shfl_xor_sync(0xffffffffu, v, o);
  return v;
}

constexpr int SM_WO3 = 0;
constexpr int SM_X = 16384;
constexpr int XT = 36864;
constexpr int SM_EXP = 126976;
constexpr int SEGB = 10240;
constexpr int SM_BLK = SM_EXP + 8192;
constexpr int SM_VC = SM_BLK + 4 * SEGB;
constexpr int SM_PART = SM_VC + 16384;
constexpr int SM_QM = SM_PART + 4096;
constexpr int SM_E = SM_QM + 1024;
constexpr int SM_VM = SM_E + 1536;
constexpr int SM_OB = SM_VM + 2048;
constexpr int SM_FB = SM_OB + 2048;
constexpr int SM_STAGE = SM_X + XT;
constexpr int SM_MISC = 210944;
constexpr int SM_WOST = 212992;
constexpr int SM_MEM = SM_WOST;
constexpr int SM_MAX = SM_MEM + 11264;
#define MEM_BLK(q) ((q) / 3 * 4096 + (q) % 3 * 1024)
constexpr int SM_TOTAL = 229376;
constexpr int MB_W = SM_MISC;
constexpr int MB_WO = SM_MISC + 24;
constexpr int MB_WO3 = SM_MISC + 32;
constexpr int MB_X = SM_MISC + 40;
constexpr int MB_S = SM_MISC + 64;
constexpr int MB_F = SM_MISC + 72;
constexpr int MB_VX = SM_MISC + 80;
constexpr int SC_FPAR = SM_MISC + 136;
constexpr int SC_DEAD = SM_MISC + 96;
constexpr int SC_UNSC = SM_MISC + 112;
constexpr int SC_EPOCH = SM_MISC + 128;
constexpr int SC_EXPW = SM_MISC + 132;
constexpr int SC_ONES = SM_MISC + 144;
constexpr int SC_SS = SM_MISC + 160;
constexpr int SC_LAT = SM_MISC + 224;
constexpr int MB_T = SM_MISC + 232;
constexpr int T_SX = SM_X + XT;
constexpr int T_OB = SM_X + 2 * XT;
constexpr int T_WA = T_OB + 16384;
constexpr int T_OA = T_WA + 9216;
constexpr int T_G = T_OA + 4096;
constexpr int T_P = T_G + 512;
constexpr int T_UN = T_G + 256;
constexpr int T_RED = 131072;
constexpr int SC_XMAX = SM_MISC + 256;
constexpr int SC_PROF = 229376;

constexpr float SM_SCALE = 0.08838834764831845f;
constexpr float LOG2E = 1.4426950408889634f;
constexpr float E_LIM = 20.f;

template <bool B> struct BoolC { static constexpr bool value = B; };
struct RMaps { CUtensorMap x, wq, wk, wv, wo, woa, oa; unsigned char* red; bf16* out; uint32_t poll; };

DI uint32_t latest_hint(uint32_t h, uint32_t d, int s) {
  const uint32_t x = (((h | 0xc0c0c0c0u) - ((d >> 5) & 63) * 0x01010101u) & 0x3f3f3f3fu) | ((h ^ (((s >> 2) + 1) & 3) * 0x40404040u) & 0xc0c0c0c0u);
  const uint32_t y = __vmaxu2(x & 0x00ff00ffu, (x >> 8) & 0x00ff00ffu);
  return __reduce_max_sync(0xffffffffu, max(y & 0xffffu, y >> 16));
}
DI uint32_t near_half(uint32_t sb) {
  uint32_t a, b; lds64(sb + SC_LAT, a, b);
  return a > b;
}

template <int RT, int K0, int K1, bool D32 = false, int BAR = 0, int KB = 18>
DI void xproj(float* acc, const uint32_t (&wa)[2][18][4], uint64_t xd) {
  if (XP & 1) return;
  WG_FENCE();
#pragma unroll
  for (int k = K0; k < ((XP & 128) ? K0 + 1 : K1); k++)
  {
    uint64_t d = xd + (uint64_t)(((k >> 1) * 4096 + (k & 1) * 32) >> 4);
    if (D32) asm("mov.b64 %0, {%1, %2};" : "=l"(d) : "r"((uint32_t)xd + (((k >> 1) * 4096 + (k & 1) * 32) >> 4)), "r"((uint32_t)(xd >> 32)));
    wgmma_n32_rs(acc, wa[RT][k][0], wa[RT][k][1], wa[RT][k][2], wa[RT][k][3], d, k != 0);
    if (BAR && k == KB - 1 && KB < 18) bar_arrive(BAR, 256);
  }
  WG_COMMIT();
}

DI void seg_store(int seg, uint32_t sb, uint32_t off, uint32_t bytes) {
  asm volatile("cp.async.bulk.global.shared::cta.bulk_group [%0], [%1], %2;"
               :: "l"(g_seg + ((size_t)(seg % NRING) * 96 + blockIdx.x) * SEGB + off), "r"(sb + SM_BLK + (seg & 3) * SEGB + off), "r"(bytes) : "memory");
  asm volatile("cp.async.bulk.commit_group;" ::: "memory");
}
DI void seg_publish(int seg) {
  asm volatile("cp.async.bulk.wait_group 0;" ::: "memory");
  asm volatile("red.relaxed.gpu.global.add.u32 [%0], 1;" :: "l"(&g_scnt[(seg * 32 + blockIdx.x / 3) * 8]) : "memory");
  SSTAMP(10, seg);
}

#define NAP 64
DI uint32_t movm(uint32_t x) { uint32_t r; asm volatile("movmatrix.sync.aligned.m8n8.trans.b16 %0, %1;" : "=r"(r) : "r"(x)); return r; }
DI bool wait_count(const unsigned* p, unsigned target, bool nap = true) {
  int n = 0;
  unsigned v;
  while (true) {
    asm volatile("ld.acquire.gpu.global.b32 %0, [%1];" : "=r"(v) : "l"(p) : "memory");
    if ((int)(v - target) >= 0 || ++n > SPIN_LIMIT) break;
    if (nap) __nanosleep(NAP);
  }
  return n;
}
#define PACE 1200
#define PORD 0
DI void load_weights(uint32_t sb, const RMaps& tm, uint32_t rank, int c) {
  const int h = blockIdx.x / 3;
  if (c < 3) {
    mbar_expect(sb + MB_W + 8 * c, 49152);
    tma_load(sb + SM_STAGE + c * 49152, rank < 2 ? &tm.wk : &tm.wv, h * DH + (rank == 1 ? 64 : 0), c * 192, sb + MB_W + 8 * c);
    tma_load(sb + SM_STAGE + c * 49152 + 24576, rank < 2 ? &tm.wq : &tm.wv, h * DH + (rank == 0 ? 0 : 64), c * 192, sb + MB_W + 8 * c);
  } else {
    tma_prefetch(&tm.wo, rank * 192, h * DH);
    mbar_expect(sb + MB_WO, 16384);
    mbar_expect(sb + MB_WO3, 32768);
    tma_load(sb + SM_WOST, &tm.wo, rank * 192 + 64, h * DH, sb + MB_WO3);
    tma_load(sb + SM_WO3, &tm.wo, rank * 192 + 128, h * DH, sb + MB_WO3);
  }
}

DI void tail_attention(const uint32_t sb, const uint32_t rank, const int w, const int lane, const int sg, const int bar) {
  const int m = lane >> 3, g = lane >> 2, t = lane & 3;
  const uint32_t l16 = sb + lane * 16, src = l16 + T_SX + sg * 10240 + w * 1280;
  if (rank < 2) {
    const uint32_t base = l16 + SM_BLK + (2 + sg) * SEGB, dst = src + rank * 5120;
    uint32_t qb[2][4];
    ldsm4t(qb[0], base + w * 1024); ldsm4t(qb[1], base + w * 1024 + 512);
#pragma unroll
    for (int j = 0; j < 3; j++) {
      uint32_t kb[4][4];
      float c[4][4];
      const uint32_t ka = base + 4096 + j * 2048 + (m & 1) * (j == 2 ? 128 : 896) - (m >> 1) * 128;
#pragma unroll
      for (int k = 0; k < 4; k += j == 2 ? 2 : 1) ldsm4t(kb[k], ka + k * 256);
      mma16816z(c[0], kb[0], qb[0][0], qb[0][1]); mma16816z(c[1], kb[j == 2 ? 0 : 1], qb[0][2], qb[0][3]);
      mma16816z(c[2], kb[2], qb[1][0], qb[1][1]); mma16816z(c[3], kb[j == 2 ? 2 : 3], qb[1][2], qb[1][3]);
      uint32_t r[4];
#pragma unroll
      for (int i = 0; i < (j == 2 ? 2 : 4); i++) r[i] = __float_as_uint((c[0][i] + c[1][j == 2 ? i + 2 : i]) + (c[2][i] + c[3][j == 2 ? i + 2 : i]));
#pragma unroll
      for (int d = 0; d < 2; d++) {
        const uint32_t to = d ? 2 : rank ^ 1, mb = mapa(sb + MB_T + 8 + 8 * sg, to);
        if (j < 2) st_async4(mapa(dst + j * 512, to), r[0], r[1], r[2], r[3], mb);
        else st_async2(mapa(dst + 1024 - lane * 8, to), r[0], r[1], mb);
      }
      if (j < 2) sts128(dst + j * 512, r[0], r[1], r[2], r[3]); else sts64(dst + 1024 - lane * 8, r[0], r[1]);
    }
  }
  TSTAMP(50 + 2 * sg);
  uint32_t vx[4][4], vm[4];
  const uint32_t va = l16 + (rank < 2 ? SM_VC + sg * 8192 : SM_BLK + (2 + sg) * SEGB) + w * 1024 + (m & 1) * 384 - (m >> 1) * 128;
#pragma unroll
  for (int i = 0; i < 4; i++) ldsm4(vx[i], va + (i & 1) * 4096 + (i >> 1) * 256);
  if (sg && rank < 2) mbar_wait(sb + MB_T, 0);
  lds128(l16 + (sg ? SM_FB : SM_VM) + w * 512, vm);
  float a[10], b[10];
  mbar_wait(sb + MB_T + 8 + 8 * sg, 0);
  TSTAMP(58 + 2 * sg);
  lds128f(src, a); lds128f(src + 512, a + 4); lds64f(src + 1024 - lane * 8, a + 8);
  lds128f(src + 5120, b); lds128f(src + 5632, b + 4); lds64f(src + 6144 - lane * 8, b + 8);
#pragma unroll
  for (int i = 0; i < 10; i++) {
    a[i] = (a[i] + b[i]) * (SM_SCALE * LOG2E);
    if (i < 8 && (i >> 1) * 8 + g > w * 8 + 2 * t + (i & 1)) a[i] = -1.0e9f * LOG2E;
  }
  float m0 = fmaxf(fmaxf(fmaxf(a[0], a[2]), fmaxf(a[4], a[6])), a[8]), m1 = fmaxf(fmaxf(fmaxf(a[1], a[3]), fmaxf(a[5], a[7])), a[9]);
#pragma unroll
  for (int o = 4; o < 32; o <<= 1) { m0 = fmaxf(m0, __shfl_xor_sync(0xffffffffu, m0, o)); m1 = fmaxf(m1, __shfl_xor_sync(0xffffffffu, m1, o)); }
#pragma unroll
  for (int i = 0; i < 10; i++) a[i] = ex2(a[i] - (i & 1 ? m1 : m0));
  float s0 = ((a[0] + a[2]) + (a[4] + a[6])) + a[8], s1 = ((a[1] + a[3]) + (a[5] + a[7])) + a[9];
#pragma unroll
  for (int o = 4; o < 32; o <<= 1) { s0 += __shfl_xor_sync(0xffffffffu, s0, o); s1 += __shfl_xor_sync(0xffffffffu, s1, o); }
  s0 = rcp(s0); s1 = rcp(s1);
#pragma unroll
  for (int i = 0; i < 5; i++) sts32(sb + T_P + sg * 2560 + w * 640 + i * 128 + lane * 4, pack_bf16(a[2 * i] * s0, a[2 * i + 1] * s1));
  mbar_wait(sb + MB_WO, 1);
  bar_sync(bar, 128);
  TSTAMP(59 + 2 * sg);
#pragma unroll
  for (int j = 0; j < 4; j++) {
    uint32_t p[5];
    float o0[4], o1[4], f[2];
    lds64f(sb + T_G + sg * 128 + j * 32 + t * 8, f);
    f[0] = 1.f - f[0]; f[1] = 1.f - f[1];
    ldsm4t(p, l16 + T_P + sg * 2560 + j * 640);
    asm volatile("ldmatrix.sync.aligned.m8n8.x1.trans.shared.b16 {%0}, [%1];" : "=r"(p[4]) : "r"(l16 + T_P + sg * 2560 + j * 640 + 512) : "memory");
    mma16816z(o0, vx[0], p[0], p[1]); mma16816z(o1, vx[1], p[0], p[1]);
    mma16816(o0, vx[2], p[2], p[3]); mma16816(o1, vx[3], p[2], p[3]);
    mma1688(o0, vm[0], vm[1], p[4]); mma1688(o1, vm[2], vm[3], p[4]);
    stsm4(l16 + T_OB + sg * 8192 + j * 2048 + w * 512, pack_bf16(o0[0] * f[0], o0[1] * f[1]), pack_bf16(o0[2] * f[0], o0[3] * f[1]),
          pack_bf16(o1[0] * f[0], o1[1] * f[1]), pack_bf16(o1[2] * f[0], o1[3] * f[1]));
  }
}

DI void proj_role(const uint32_t sb, const RMaps& tm, const uint32_t rank, const int wg, const int w, const int lane) {
  const bool qk = rank < 2;
  uint32_t wa[2][18][4];
  {
    const int rr = (lane & 7) + ((lane >> 4) << 3);
    const uint32_t col = ((2 * w + ((lane >> 3) & 1)) ^ (lane & 7)) << 4;
    float ss = 0.f;
#pragma unroll
    for (int c = 0; c < 3; c++) {
      mbar_wait(sb + MB_W + 8 * c, 0);
      if (threadIdx.x == 0) SSTAMP(11, c);
#pragma unroll
      for (int rt = 0; rt < 2; rt++)
#pragma unroll
        for (int k = 0; k < 6; k++)
          ldsm4t(wa[rt][c * 6 + k], sb + SM_STAGE + c * 49152 + (rt ^ wg) * 24576 + (64 * (k >> 1) + 32 * wg + 16 * (k & 1) + rr) * 128 + col);
      if (c < 2) {
        fence_async();
        bar_sync(3, 256);
        if (threadIdx.x == 0) {
          if (c == 0) tma_load3(sb + SM_X + XT, &tm.x, 32, sb + MB_X + 8);
          else { tma_load(sb + SM_X + 2 * XT, &tm.wo, rank * 192, (blockIdx.x / 3) * DH, sb + MB_WO); SSTAMP(11, 11); }
        }
        __syncwarp();
      }
      uint32_t q[4] = {0, 0, 0, 0};
#pragma unroll
      for (int rt = 0; rt < 2; rt++)
#pragma unroll
        for (int k = 0; k < 6; k++)
#pragma unroll
          for (int i = 0; i < 4; i++) sq_acc(q[i], wa[rt][c * 6 + k][i]);
#pragma unroll
      for (int i = 0; i < 4; i++) ss += bf_lo(q[i]) + bf_hi(q[i]);
    }
    ss = warp_sum(ss);
    fence_async();
    cluster_arrive();
    if (lane == 0) sts32(sb + SC_SS + 4 * (wg * 4 + w), qk ? 0 : __float_as_uint(ss));
    bar_arrive(11, 384);
  }
  STAMP(1);
  mbar_wait(sb + MB_X, 0);
  STAMP(2);

  uint32_t t16 = sb + (w * 32 + lane) * 16;
  uint32_t mem_a = sb + SM_MEM + wg * 512 + lane * 16;
  uint32_t fin_a = sb + (lane & 7) * 16 + SM_BLK + (qk ? (wg ^ 1) * 4096 + w * 256 + (lane & 8) * 16 + (lane & 16) * 64
                                              : wg * 4096 + w * 1024 + (lane & 8) * 64 + (lane & 16) * 8);
  PIN(t16); PIN(mem_a); PIN(fin_a);
  const uint32_t fence_reg = mem_a;
  const uint32_t fin2 = qk ? 2048 : 256;
  float acc[16];
  const uint64_t xd0 = make_desc(sb + SM_X + wg * 64, 16, 1024, 1);
  auto do_export = [&]() {
    WG_WAIT(0);
    uint32_t q[8];
#pragma unroll
    for (int j = 0; j < 8; j++) q[j] = pack_bf16(acc[2 * j], acc[2 * j + 1]);
    sts128(t16 + SM_EXP + wg * 4096, q[0], q[1], q[2], q[3]);
    sts128(t16 + SM_EXP + wg * 4096 + 2048, q[4], q[5], q[6], q[7]);
    if (RET) asm volatile("{\n.reg .pred p;\nsetp.eq.u32 p, %2, 0;\n@p add.u32 %0, %0, 1;\n@p add.u32 %1, %1, 1;\nsetp.eq.and.u32 p, %0, %1, p;\n@p exit;\n}"
                          : "+r"(q[3]), "+r"(q[7]) : "r"(t16) : "memory");
  };
  uint32_t o[8];
  auto import = [&]() { lds128(t16 + SM_EXP + (wg ^ 1) * 4096, o); lds128(t16 + SM_EXP + (wg ^ 1) * 4096 + 2048, o + 4); };
  auto finish = [&](int seg) {
    const uint32_t a = fin_a + (seg & 3) * SEGB;
    WG_WAIT(0);
#pragma unroll
    for (int i = 0; i < 8; i++) o[i] = FIN16 ? add_bf16(pack_bf16(acc[2 * i], acc[2 * i + 1]), o[i]) : pack_bf16(acc[2 * i] + bf_lo(o[i]), acc[2 * i + 1] + bf_hi(o[i]));
    stsm4(a, o[0], o[1], o[2], o[3]);
    stsm4(a + fin2, o[4], o[5], o[6], o[7]);
  };
  auto send_v = [&](int seg, int dst) {
    fence_async();
    if (seg < NSEG && !(XP & 2) && elect_one())
      bulk_s2s(mapa(sb + SM_VC + (seg & 1) * 8192, dst), sb + SM_BLK + (seg & 3) * SEGB, 8192, mapa(sb + MB_VX + (seg & 1) * 8, dst));
    __syncwarp();
  };
  auto wait_v = [&](int seg) {
    if (seg < NSEG && !(XP & 2)) {
      mbar_wait(sb + MB_VX + (seg & 1) * 8, (seg >> 1) & 1);
      if (elect_one()) mbar_expect(sb + MB_VX + (seg & 1) * 8, 8192);
      __syncwarp();
    }
  };
  bar_sync(3, 256);
  xproj<1, 0, 18>(acc, wa, xd0);
  do_export();
  SCHED_FENCE(11);
  xproj<0, 0, 18>(acc, wa, xd0);
  bar_sync(3, 256);
  if (threadIdx.x == 0) SSTAMP(11, 12);
  cluster_wait();
  if (threadIdx.x == 0) SSTAMP(11, 13);
  mbar_wait(sb + MB_X + 8, 0);
  import();
  finish(0);
  SCHED_FENCE(12);
  bar_sync(3, 256);
  uint64_t dA = xd0 + (XT >> 4);
  xproj<1, 0, 18>(acc, wa, dA);
  if (!qk && wg == 0 && w < 2) send_v(0, w);
  do_export();
  if (qk && wg == 0 && w == 0) wait_v(0);
  bar_arrive(13, 384);
  if (!qk) {
    SCHED_FENCE(15);
    xproj<0, 0, 18>(acc, wa, dA);
    if (threadIdx.x == 0 && !(XP & 8)) { mbar_expect(sb + MB_X, XT); tma_load3(sb + SM_X, &tm.x, 96, sb + MB_X); }
    bar_sync(3, 256);
    mbar_wait(sb + MB_X + 16, 0);
    import();
    finish(1);
    SCHED_FENCE(16);
    bar_sync(3, 256);
    dA += XT >> 4;
    xproj<1, 0, 18>(acc, wa, dA);
    if (wg == 0 && ((w == 0 && VS0) || (w == 1 && VS1))) send_v(1, w);
    do_export();
  }
  if (threadIdx.x == 0) SSTAMP(11, 14);
  bar_sync(0, 384);
  const int ro = __shfl_sync(0xffffffffu, near_half(sb) ^ wg, 0);
  STAMP(5);
  const uint32_t always = __shfl_sync(0xffffffffu, lds32(sb + SC_DEAD + 12), 0);
  const int ah = qk ? 1 : 2;
  int b2 = qk ? 2 : 0;
  int s = 0;
  uint32_t hint_lo = (uint32_t)(uint64_t)tm.red + HINT_OFF + blockIdx.x + (lane & 1) * 4096 + (lane >> 1) * 16384;
  PIN(hint_lo);
  auto post_hint = [&]() {
    asm volatile("{\n.reg .pred p;\n.reg .b64 a;\n.reg .u32 t;\nsetp.lt.u32 p, %0, %1;\nmov.b64 a, {%2, %3};\nmov.u32 t, %%globaltimer_lo;\n"
                 "bfe.u32 t, t, 5, 6;\nor.b32 t, t, %4;\n@p st.relaxed.gpu.global.u8 [a], t;\n}"
                 :: "r"(t16), "r"(sb + 128), "r"(hint_lo + RED_SLOT(s)), "r"((uint32_t)((uint64_t)tm.red >> 32)), "r"(((s >> 2) + 1) << 6) : "memory");
  };
  auto memproj = [&](auto second, int id, float u0, float u1, float* r) {
    constexpr bool R1 = decltype(second)::value;
    uint32_t b[NUP][4], b0[4];
    SCHED_FENCE(id);
    bar_sync(R1 ? 2 : 1, 256);
    PROF(0);
    ldsm4t(b0, mem_a);
#pragma unroll
    for (int q = 0; q < NUP; q++) {
      if (R1 && q == 2) {
        bar_sync(11, 256);
        SCHED_FENCE(id + 1);
      }
      ldsm4t(b[q], mem_a + MEM_BLK(q + 1));
    }
    mma16816z(&acc[0], wa[0][0], b0[0], b0[1]);
    mma16816z(&acc[4], wa[1][0], b0[0], b0[1]);
    mma16816z(&acc[8], wa[0][1], b0[2], b0[3]);
    mma16816z(&acc[12], wa[1][1], b0[2], b0[3]);
#pragma unroll
    for (int q = 1; q < 9; q++) {
      uint32_t* const c = b[(q - 1) % NUP];
      mma16816(&acc[0], wa[0][2 * q], c[0], c[1]);
      mma16816(&acc[4], wa[1][2 * q], c[0], c[1]);
      mma16816(&acc[8], wa[0][2 * q + 1], c[2], c[3]);
      mma16816(&acc[12], wa[1][2 * q + 1], c[2], c[3]);
      if (R1 && q + NUP == B3Q) bar_sync(3, 256);
      if (q + NUP < 9) ldsm4t_in(c, mem_a + MEM_BLK(q + NUP), always);
      else if (R1 && q + NUP < 11) lds128_in(c, t16 + SM_PART + (10 - q - NUP) * 2048, always);
      else if (!R1 && GATE && q == GATE) { bar_arrive(11, 256); lds128_in(c, sb + SC_DEAD, always); u0 = u1 = __uint_as_float(c[3]); }
    }
#pragma unroll
    for (int i = 0; i < 8; i++) {
      const float u = i < 4 ? u0 : u1;
      r[i] = R1 ? fmaf(acc[8 + i], u, (acc[i] + __uint_as_float(b[(8 + i / 4) % NUP][i & 3])) * u) : (GATE ? fmaf(acc[i], u, acc[8 + i]) : acc[i] + acc[8 + i]);
    }
  };
  if (ro == 0) {
    auto set_scale = [&]() {
      uint32_t m[8];
      lds128(t16 + SM_MAX - 512, m); lds128(t16 + SM_MAX, m + 4);
      const int em = (wexp(amax4(amax4(*(const __half2*)&m[0], m), m + 4)) >> 3) + (int)(lds32(sb + SC_UNSC + (s & 1) * 8) >> 23) - 15;
      const int ex = max(s ? em : 0, (int)lds32(sb + SC_XMAX + 4 * s)) - 127 + (int)lds32(sb + SC_EXPW);
      sts32(sb + SC_UNSC + (~s & 1) * 8, (127 + min(max(ex, -120), 120)) << 23);
    };
#pragma unroll 1
    while (true) {
      if (s == 8) STAMP(6);
      float r[8];
      memproj(BoolC<false>(), 30, 0.f, 0.f, r);
      sts128(t16 + SM_PART, __float_as_uint(r[0]), __float_as_uint(r[1]), __float_as_uint(r[2]), __float_as_uint(r[3]));
      sts128(t16 + SM_PART + 2048, __float_as_uint(r[4]), __float_as_uint(r[5]), __float_as_uint(r[6]), __float_as_uint(r[7]));
      bar_arrive(3, 256);
      PROF(1);
      bar_sync(9, 256);
      if (s == NSEG - 1) break;
      post_hint();
      if (w == 1) {
        set_scale();
        __syncwarp();
        if (elect_one()) mbar_arrive(sb + MB_S);
      }
      SCHED_FENCE(9);
      bar_sync(5, qk ? N5 : 256);
      PROF(2);
      import();
      xproj<0, 0, NII, (DD & 1) != 0>(acc, wa, dA);
      if (NII < 18) {
        if (qk) bar_sync(7, 384);
        xproj<0, NII, 18>(acc, wa, dA);
        if (!qk) bar_sync(7, 384);
      } else {
        if (F10) WG_WAIT(0);
        bar_sync(10, 256);
        if (F10) SCHED_FENCE(17);
      }
      dA += (int64_t)(b2 ? XT >> 4 : -(XT >> 3));
      finish(s + ah);
      if (qk || !VLATE(w)) bar_arrive(13, 384);
      PROF(6);
      SCHED_FENCE(14);
      bar_sync(12, 256);
      PROF(7);
      xproj<1, 0, 18, (DD & 2) != 0, 14, N14>(acc, wa, dA);
      if (N14 == 18) bar_arrive(14, 256);
      b2 = b2 == 2 ? 0 : b2 + 1;
      s++;
      if (!qk && VLATE(w)) { bar_sync(13, 384); send_v(s + 1, w); }
      PROFP(8);
      do_export();
      s--; RSTAMP(6); s++;
      PROFP(3);
    }
    if (!qk) bar_arrive(5, 256);
    if (w == 0 && elect_one()) {
      const uint32_t h18 = blockIdx.x / 3 * 18;
      mbar_expect(sb + MB_WO, 9216 + 4096 + 256);
      asm volatile("cp.async.bulk.shared::cluster.global.mbarrier::complete_tx::bytes [%0], [%1], 256, [%2];"
                   :: "r"(sb + T_G), "l"(g_gate + NAUXSEG * 32), "r"(sb + MB_WO) : "memory");
      tma_load(sb + T_OA, &tm.oa, 4096 + (h18 & ~7), NAUXSEG * 32, sb + MB_WO);
#pragma unroll 1
      for (int j = 0; j < 3; j++) tma_load(sb + T_WA + j * 3072, &tm.woa, rank * 192 + j * 64, h18, sb + MB_WO);
    }
    if (w == 1) {
      set_scale();
      __syncwarp();
      const int ea = (int)ldg_relaxed32(&g_amax[0]) + (int)ldg_relaxed32(&g_amax[16]) - 254 + 2 + 10 - 15;
      sts32(sb + T_UN + (lane & 1) * 4, (128 + max(min(ea, 120), (int)(lds32(sb + SC_UNSC + 8 - (lane & 1) * 8) >> 23) - 127)) << 23);
    }
    bar_arrive(8, 256);
  } else {
    uint32_t r0;
    float un;
    auto prepare = [&]() {
      un = __uint_as_float(lds32(sb + SC_UNSC + (s & 1) * 8));
      r0 = qk ? (t16 & ~256u) - w * 256 + (((t16 >> 8) ^ wg) & 1 ? SM_QM : SM_BLK + 8192 + (s & 3) * SEGB) : mapa(t16 + (s < NSEG - 1 ? SM_VM : SM_FB), 0);
      PIN(r0); PIN(un);
    };
    prepare();
#pragma unroll 1
    while (true) {
      if (s == 8) STAMP(6);
      float r[8];
      if (qk) {
        const float u0 = wg ? un * (SM_SCALE * LOG2E) : un, u1 = wg ? un : un * (SM_SCALE * LOG2E);
        memproj(BoolC<true>(), 32, u0, u1, r);
        stsm4(r0, pack_bf16(r[0], r[1]), pack_bf16(r[2], r[3]), pack_bf16(r[4], r[5]), pack_bf16(r[6], r[7]));
        bar_arrive(4, 256);
      } else {
        const uint32_t mb = sb + (s < NSEG - 1 ? MB_S : MB_T), r1 = r0 + (1 << 24);
        memproj(BoolC<true>(), 34, un, un, r);
        const uint32_t p0 = pack_bf16(r[0], r[1]), p1 = pack_bf16(r[2], r[3]), p2 = pack_bf16(r[4], r[5]), p3 = pack_bf16(r[6], r[7]);
        const uint32_t v0 = wg ? p2 : p0, v1 = wg ? p3 : p1, v2 = wg ? p0 : p2, v3 = wg ? p1 : p3;
        st_async4(r0, v0, v1, v2, v3, mapa(mb, 0));
        st_async4(r1, v0, v1, v2, v3, mapa(mb, 1));
        bar_arrive(5, 256);
        sts128(r0 + (2 << 24), v0, v1, v2, v3);
        stsm4((t16 & ~256u) - w * 256 + SM_BLK + 8192 + (s & 3) * SEGB + (((t16 >> 8) ^ wg) & 1) * 1024, p0, p1, p2, p3);
        __syncwarp();
        if (elect_one()) mbar_arrive(sb + MB_S);
      }
      if (s == NSEG - 1) break;
      if (!qk) bar_arrive(15, 160);
      PROF(1);
      auto rearm = [&]() { mbar_wait(sb + MB_S, s & 1); if (elect_one()) mbar_expect(sb + MB_S, qk ? 640 + 2048 : 1280); __syncwarp(); };
      if (w == 1) {
        if ((t16 & 384) == 0) stg_relaxed(tm.red + (RED_SLOT(s + 2) + RED_LINE(blockIdx.x)) + (t16 & 112), 0, 0, 0, 0);
      } else if (w == 0) {
        const int tn = s + ah + 1;
        if (RFW) mbar_wait(sb + MB_S, s & 1);
        if (tn + 1 < NSEG && !(XP & 8) && elect_one()) {
          const int b0 = b2 == 2 ? 0 : b2 + 1;
          mbar_expect(sb + MB_X + 8 * b0, XT);
          tma_load3(sb + SM_X + b0 * XT, &tm.x, (tn + 1) * 32, sb + MB_X + 8 * b0);
        }
        if (tn < NSEG && (!(XP & 8) || tn < 3)) mbar_wait(sb + MB_X + 8 * b2, (tn / 3) & 1);
      } else if (w == 2) {
        if (!qk) { if (VS0 == 0) send_v(s + 1, 0); if (VS1 == 0) send_v(s + 1, 1); }
      } else if (qk || !NIC) {
        rearm();
      }
      __syncwarp();
      import();
      PROF(4);
      SCHED_FENCE(10);
      if (NIC) {
        if (qk) bar_sync(7, NII < 18 ? 384 : 256);
        xproj<0, 0, NIC>(acc, wa, dA);
        if (!qk) { if (w == 3) rearm(); bar_sync(7, NII < 18 ? 384 : 256); }
      } else {
        bar_sync(7, NII < 18 ? 384 : 256);
      }
      xproj<0, NIC, 18, (DD & 4) != 0, 12, N12>(acc, wa, dA);
      if (N12 == 18) bar_arrive(12, 256);
      dA += (int64_t)(b2 ? XT >> 4 : -(XT >> 3));
      finish(s + ah);
      if (qk && w == 0) wait_v(s + 1);
      bar_arrive(13, 384);
      PROF(6);
      SCHED_FENCE(13);
      bar_sync(14, 256);
      PROF(7);
      xproj<1, 0, 18, (DD & 8) != 0>(acc, wa, dA);
      b2 = b2 == 2 ? 0 : b2 + 1;
      s++;
      if (HOIST) prepare();
      PROFP(8);
      do_export();
      if (!HOIST) prepare();
      s--; RSTAMP(7); s++;
      PROFP(3);
    }
    TSTAMP(2);
    bar_sync(3, 128);
    tail_attention(sb, rank, w, lane, 1, 3);
    bar_arrive(0, 256);
  }
  STAMP(3);
  if (CSY) cluster_sync();
  STAMP(4);
}

DI void attn_role(const uint32_t sb, unsigned char* smem_raw, const RMaps& tm, const uint32_t RANK, const bf16* __restrict__ x, const bf16* __restrict__ mem0,
                  const int w, const int lane) {
  const int t2 = w * 32 + lane;
  uint32_t wo[8][4], w1[8][4];
  const uint32_t wo_lane = sb + ((lane & 7) + ((lane >> 4) << 3)) * 128 + (((w + 4 * ((lane >> 3) & 1)) ^ (lane & 7)) << 4);
  unsigned char* const g_red = tm.red;
  {
    const uint32_t tag = *(volatile unsigned*)&g_epoch + 1;
    if (w == 0) {
      stg_relaxed(g_red + RED_SLOT(t2 >> 3) + RED_LINE(blockIdx.x) + (t2 & 7) * 16, 0, 0, 0, 0);
      stg_relaxed(g_red + T_RED + blockIdx.x * 1024 + t2 * 16, 0, 0, 0, 0);
      stg_relaxed(g_red + T_RED + blockIdx.x * 1024 + 512 + t2 * 16, 0, 0, 0, 0);
      asm volatile("st.relaxed.gpu.global.u8 [%0], 0;" :: "l"(g_red + RED_SLOT(t2) + HINT_OFF + (t2 & 4) * 1024 + (t2 >> 3) * 16384 + blockIdx.x) : "memory");
    }
    uint4 xv[18];
    uint32_t mv[20];
#pragma unroll
    for (int i = 0; i < 20; i++) mv[i] = i < 18 ? ((const uint32_t*)mem0)[(lane >> 2) * (DM / 2) + (w * 18 + i) * 4 + (lane & 3)] : 0;
#pragma unroll
    for (int i = 0; i < 18; i++) xv[i] = blockIdx.x < NSEG ? ((const uint4*)(x + blockIdx.x * 32 * DM))[t2 + 128 * i] : make_uint4(0, 0, 0, 0);
    bar_sync(0, 384);
    cluster_arrive();
    if (PACE && w == 3) {
      const uint32_t t0 = gtime();
#pragma unroll 1
      for (int c = 1; c < 4; c++) {
        wait_until(t0 + c * PACE);
        if (elect_one()) load_weights(sb, tm, RANK, PORD ? (c == 1 ? 3 : c - 1) : c);
        __syncwarp();
      }
    }
    __half2 hx = __float2half2_rn(0.f);
#pragma unroll
    for (int i = 0; i < 18; i++) hx = amax4(hx, &xv[i].x);
    if (blockIdx.x == 0)
#pragma unroll
      for (int i = 0; i < 5; i++) hx = amax4(hx, &mv[4 * i]);
    sts32(sb + SC_SS + 4 * (12 + w), wexp(hx));
    if (t2 == 0) { sts32(sb + SC_EPOCH, (tag - 1) * NSEG + 2 - NRING); sts32(sb + SC_UNSC, __float_as_uint(1.f)); sts128(sb + SC_DEAD, 0, 0, 0, 0x3f800000u); sts64(sb + SC_FPAR, 0, 0); sts128(sb + SC_ONES, 0x3f803f80u, 0x3f803f80u, 0x3f803f80u, 0x3f803f80u); }
    WSTAMP(27);
    if (w == 0) __threadfence();
    uint32_t q[8] = {0, 0, 0, 0, 0, 0, 0, 0};
    mbar_wait(sb + MB_WO3, 0);
    if (t2 == 0) SSTAMP(11, 3);
#pragma unroll
    for (int k = 0; k < 8; k++) {
      ldsm4t(wo[k], wo_lane + SM_WO3 + k * 2048); ldsm4t(w1[k], wo_lane + SM_WOST + k * 2048);
#pragma unroll
      for (int i = 0; i < 4; i++) { sq_acc(q[i], wo[k][i]); sq_acc(q[i], w1[k][i]); }
    }
    bar_sync(6, 128);
    if (t2 == 0) SSTAMP(11, 7);
#pragma unroll
    for (int k = 0; k < 8; k++) sts128(sb + SM_WO3 + t2 * 16 + k * 2048, wo[k][0], wo[k][1], wo[k][2], wo[k][3]);
#pragma unroll
    for (int i = 0; i < 5; i++) {
      const int j = w * 18 + 4 * i + (lane >> 3), c = i < 4 || lane < 16 ? j * 8 + j / 24 * 64 : 192;
      stsm4t(sb + SM_MEM + (c + (lane & 7)) * 16, mv[4 * i], mv[4 * i + 1], mv[4 * i + 2], mv[4 * i + 3]);
    }
    bar_arrive(1, 256); bar_arrive(2, 256); bar_arrive(9, 256);
    if (t2 == 0) SSTAMP(11, 8);
    mbar_wait(sb + MB_WO, 0);
    if (t2 == 0) SSTAMP(11, 4);
#pragma unroll
    for (int k = 0; k < 8; k++) ldsm4t(wo[k], wo_lane + SM_X + 2 * XT + k * 2048);
    fence_async();
    bar_sync(6, 128);
    if (t2 == 32) tma_load3(sb + SM_X + 2 * XT, &tm.x, 64, sb + MB_X + 16);
    __syncwarp();
#pragma unroll
    for (int k = 0; k < 8; k++)
#pragma unroll
      for (int i = 0; i < 4; i++) sq_acc(q[4 + i], wo[k][i]);
    float ss = 0.f;
#pragma unroll
    for (int i = 0; i < 8; i++) ss += bf_lo(q[i]) + bf_hi(q[i]);
    ss = warp_sum(ss);
    if (lane == 0) sts32(sb + SC_SS + 4 * (8 + w), __float_as_uint(ss));
    if (t2 == 0) SSTAMP(11, 9);
    bar_sync(11, 384);
    if (t2 == 0) SSTAMP(11, 10);
    if (t2 == 0) {
      float a[16];
#pragma unroll
      for (int i = 0; i < 4; i++) lds128f(sb + SC_SS + 16 * i, &a[4 * i]);
      stg_relaxed(&g_stats[blockIdx.x * 2], __float_as_uint(((a[0] + a[1]) + (a[2] + a[3])) + ((a[4] + a[5]) + (a[6] + a[7]))),
                  __float_as_uint((a[8] + a[9]) + (a[10] + a[11])),
                  max(max(__float_as_uint(a[12]), __float_as_uint(a[13])), max(__float_as_uint(a[14]), __float_as_uint(a[15]))), tag);
    }
    __syncwarp();
    WSTAMP(24);
    cluster_wait();
    if (w == 0) {
      uint4 v[3];
      int n = 0;
      while (true) {
#pragma unroll
        for (int i = 0; i < 3; i++) v[i] = ldg_relaxed(&g_stats[(i * 32 + lane) * 2]);
        if (__all_sync(0xffffffffu, v[0].w == tag && v[1].w == tag && v[2].w == tag) || ++n > SPIN_LIMIT) break;
        __nanosleep(100);
      }
      WSTAMP(25);
      const float sv = warp_sum(__uint_as_float(v[0].x) + __uint_as_float(v[1].x) + __uint_as_float(v[2].x));
      const float so = warp_sum(__uint_as_float(v[0].y) + __uint_as_float(v[1].y) + __uint_as_float(v[2].y));
      const int expW = ((int)(__float_as_uint(sv) >> 23) + (int)(__float_as_uint(so) >> 23) - 254 + 2 + 10 + 1) >> 1;
      sts32(sb + SC_XMAX + 4 * lane, v[0].z); sts32(sb + SC_XMAX + 128 + 4 * lane, v[1].z);
      sts32(sb + SC_EXPW, expW + 1 - 15);
      if (blockIdx.x == 0 && lane == 0) *(volatile unsigned*)&g_epoch = tag;
      sts32(sb + SC_FPAR + 4, 1);
    } else if (w < 3) {
      const uint32_t u = blockIdx.x >> 4;
      unsigned char* const z = g_red + 98304 + (blockIdx.x & 15) * 128 + (u & 1) * 2048 + (u & 6) * 4096 + (((u >> 1) ^ w) & 1) * 4096 + lane * 4;
      stg_relaxed32(z, 0);
      uint32_t best = 0xffffffffu;
#pragma unroll 1
      for (int i = 0; i < 64; i++) {
        uint32_t last, dt;
        asm volatile("{\n.reg .pred p;\n.reg .u32 c, v;\nld.volatile.shared.u32 %0, [%3];\nmov.u32 c, %%clock;\n"
                     "atom.relaxed.gpu.global.exch.b32 v, [%2], 0;\nsetp.eq.u32 p, v, 0;\nmov.u32 %1, 0;\n@p mov.u32 %1, %%clock;\nsub.u32 %1, %1, c;\n}"
                     : "=r"(last), "=r"(dt) : "l"(z), "r"(sb + SC_FPAR + 4) : "memory");
        best = min(best, dt);
        if (last && i >= NPROBE - 1) break;
      }
      sts32(sb + SC_LAT + (w - 1) * 4, best);
    }
    bar_sync(13, 384);
    bar_arrive(0, 384);
    WSTAMP(26);
    TSTAMP(1);
  }

  const uint32_t nh = __shfl_sync(0xffffffffu, near_half(sb), 0);
  uint32_t l16 = sb + lane * 16;
  PIN(l16);
#define LV ((l16 >> 4) & 31)
#define fence_reg l16
  const uint32_t red_lo = (uint32_t)(uint64_t)g_red, red_hi = (uint32_t)((uint64_t)g_red >> 32);
  uint32_t lp;
  auto slot = [&](int s, uint32_t c, uint32_t ofs) {
    const uint32_t lo = lp | (red_lo + ((w >> 1) * 4 + (w & 1) * 2 + ((w ^ c) & 1)) * 4096 + RED_SLOT(s) + ofs);
    uint64_t a; asm("mov.b64 %0, {%1, %2};" : "=l"(a) : "r"(lo), "r"(red_hi));
    return (unsigned char*)a;
  };
  const uint32_t always = __shfl_sync(0xffffffffu, lds32(sb + SC_DEAD + 12), 0);
  const int mode0 = RANK < 2 ? w : w | 4;
  auto hint_addr = [&](int s) { return min(LV, 23u) * 4 + (red_lo + HINT_OFF + nh * 4096 + w * 16384 + RED_SLOT(s)); };
  auto load_hints = [&](uint32_t lo) {
    uint64_t a; asm("mov.b64 %0, {%1, %2};" : "=l"(a) : "r"(lo), "r"(red_hi));
    return ldg_relaxed32((const void*)a);
  };
  const uint32_t blk = RANK < 2 ? 9216 : SEGB;
  auto send_v = [&](int seg, int pos) {
    if (RANK == 2 && ((w == 0 && VS0 == pos) || (w == 1 && VS1 == pos)) && seg > 1 && seg < NSEG && !(XP & 2)) {
      if (elect_one()) {
        fence_async();
        bulk_s2s(mapa(sb + SM_VC + (seg & 1) * 8192, w), sb + SM_BLK + (seg & 3) * SEGB, 8192, mapa(sb + MB_VX + (seg & 1) * 8, w));
      }
      __syncwarp();
    }
  };
  uint32_t dl = __shfl_sync(0xffffffffu, gtime() - 768, 0);
  int s = 0;
  bool bad = false;
#pragma unroll 1
  while (true) {
    const uint32_t par = s & 1;
    uint32_t vx[4][4], hints;
    if (HP == 2) { hints = hint_addr(s); PIN(hints); }
    auto load_vx = [&]() {
      const uint32_t va = l16 + (RANK < 2 ? SM_VC + par * 8192 : SM_BLK + (s & 3) * SEGB) + w * 1024 + ((LV >> 3) & 1) * 384 - (LV >> 4) * 128;
#pragma unroll
      for (int i = 0; i < 4; i++) ldsm4(vx[i], va + (i & 1) * 4096 + (i >> 1) * 256);
    };
    auto retire = [&](uint32_t x) {
      asm volatile("{\n.reg .pred p;\nsetp.eq.u32 p, %0, 0;\n@p exit;\n}" :: "r"(vx[0][0] | vx[1][0] | vx[2][0] | vx[3][0] | x) : "memory");
    };
    auto scores = [&](auto memkeys, auto first, float* sc) {
      constexpr bool MK = decltype(memkeys)::value, FIRST = decltype(first)::value;
      uint32_t kb[4][4], qb[2][4];
      const uint32_t m = LV >> 3;
      uint32_t kaddr = l16 + SM_BLK + 4096 + (s & 3) * SEGB + w * 2048 + (m & 1) * (MK ? 128 : 896) - (m >> 1) * 128;
      if (MK) { PIN(kaddr); }
      else {
#pragma unroll
        for (int k = 0; k < 4; k++) ldsm4t(kb[k], kaddr + k * 256);
      }
      if (FIRST) { load_vx(); retire(MK ? kaddr : kb[0][0] | kb[1][0] | kb[2][0] | kb[3][0] | l16); bar_sync(4, 256); RSTAMP(4); PROF(4); }
      ldsm4t(qb[0], l16 + SM_QM);
      if (MK) ldsm4t(kb[0], kaddr);
      ldsm4t(qb[1], l16 + SM_QM + 512);
      if (MK) ldsm4t(kb[2], kaddr + 512);
      float c[4][4];
      mma16816z(c[0], kb[0], qb[0][0], qb[0][1]); mma16816z(c[1], kb[MK ? 0 : 1], qb[0][2], qb[0][3]);
      mma16816z(c[2], kb[2], qb[1][0], qb[1][1]); mma16816z(c[3], kb[MK ? 2 : 3], qb[1][2], qb[1][3]);
      if (FIRST && B5POS == 0) bar_arrive(5, N5);
#pragma unroll
      for (int i = 0; i < (MK ? 2 : 4); i++) sc[i] = ((c[0][i] + c[1][MK ? i + 2 : i]) + c[2][i]) + c[3][MK ? i + 2 : i];
    };
    auto send = [&](auto memkeys) {
      constexpr bool MK = decltype(memkeys)::value;
      constexpr int N = MK ? 1 : 2;
      const uint32_t sa = sb + LV * 4 + SM_E + (MK ? 1024 + RANK * 128 : RANK * 512 + w * 256);
      uint32_t ra[N][2], mb[N][2];
#pragma unroll
      for (int i = 0; i < N; i++)
#pragma unroll
        for (int j = 0; j < 2; j++) {
          ra[i][j] = mapa(sa + i * 128, j ? 2 : RANK ^ 1); mb[i][j] = mapa(sb + MB_S, j ? 2 : RANK ^ 1);
          PIN(ra[i][j]);
        }
      float sc[4];
      scores(memkeys, BoolC<true>(), sc);
      uint32_t e[N];
#pragma unroll
      for (int i = 0; i < N; i++) {
        e[i] = pack_bf16(ex2(sc[2 * i]), ex2(sc[2 * i + 1]));
        if (!(fmaxf(fabsf(sc[2 * i]), fabsf(sc[2 * i + 1])) <= E_LIM)) e[i] = 0x7fff7fffu;
        st_async1(ra[i][0], e[i], mb[i][0]);
        st_async1(ra[i][1], e[i], mb[i][1]);
      }
#pragma unroll
      for (int i = 0; i < N; i++) sts32(sa + i * 128, e[i]);
      __syncwarp();
      if (l16 == sb) mbar_arrive(sb + MB_S);
      PROF(5);
    };
    const int mode = bad ? 8 : mode0;
    if (mode < 2) {
      send(BoolC<false>());
    } else if (mode == 2) {
      send(BoolC<true>());
    } else if (mode == 8) {
      load_vx();
      retire(l16);
      const uint32_t fp = lds32(sb + SC_FPAR);
      bar_sync(6, 128);
      if (w == 0 && l16 == sb) { sts32(sb + SC_FPAR, fp ^ 1); mbar_expect(sb + MB_F, 3072); }
      if (RANK < 2 && w < 3) {
        float sc[4] = {0.f, 0.f, 0.f, 0.f};
        if (w < 2) scores(BoolC<false>(), BoolC<false>(), sc); else scores(BoolC<true>(), BoolC<false>(), sc);
#pragma unroll 1
        for (int r = 0; r < 3; r++)
          st_async4(mapa(l16 + SM_FB + RANK * 1536 + w * 512, r), __float_as_uint(sc[0]), __float_as_uint(sc[1]), __float_as_uint(sc[2]), __float_as_uint(sc[3]), mapa(sb + MB_F, r));
      }
      mbar_wait(sb + MB_F, fp);
      float a[12];
#pragma unroll
      for (int j = 0; j < 3; j++) {
        float b[4];
        lds128f(l16 + SM_FB + j * 512, a + 4 * j); lds128f(l16 + SM_FB + 1536 + j * 512, b);
#pragma unroll
        for (int i = 0; i < 4; i++) a[4 * j + i] += b[i];
      }
      float m0 = fmaxf(fmaxf(fmaxf(a[0], a[2]), fmaxf(a[4], a[6])), a[8]), m1 = fmaxf(fmaxf(fmaxf(a[1], a[3]), fmaxf(a[5], a[7])), a[9]);
#pragma unroll
      for (int o = 4; o < 32; o <<= 1) { m0 = fmaxf(m0, __shfl_xor_sync(0xffffffffu, m0, o)); m1 = fmaxf(m1, __shfl_xor_sync(0xffffffffu, m1, o)); }
#pragma unroll
      for (int i = 0; i < 5; i++) {
        const uint32_t ea = sb + SM_E + LV * 4 + (i < 4 ? i * 128 : 1024);
        sts32(ea, pack_bf16(ex2(a[2 * i] - m0), ex2(a[2 * i + 1] - m1)));
        sts32(ea + (i < 4 ? 512 : 128), 0x3f803f80u);
      }
      __syncwarp();
    } else {
      load_vx();
      retire(l16 + 1);
      if (VS0 == 2 || VS1 == 2) send_v(s + 1, 2);
      if (w == 3) {
        uint32_t used = ldg_relaxed32(&g_used[blockIdx.x / 3 * 32]);
        if (!(XP & 4) && elect_one()) {
          if (s > 0) seg_publish(s - 1);
          fence_async();
          seg_store(s, sb, 0, 8192);
        }
        __syncwarp();
        bar_sync(RANK < 2 ? 4 : 15, RANK < 2 ? 256 : 160);
        if (!(XP & 4) && elect_one()) { fence_async(); seg_store(s, sb, 8192, blk - 8192); }
        __syncwarp();
        if (s >= NRING - 1 && !(XP & 64)) {
          const uint32_t need = lds32(sb + SC_EPOCH) + s;
#pragma unroll 1
          for (int n = 0; (int)(used - need) < 0 && n < SPIN_LIMIT; n++) used = ldg_relaxed32(&g_used[blockIdx.x / 3 * 32]);
        }
      }
    }
    {
      uint32_t wa[4], wb[4], oc[4];
      constexpr int WS = 2048;
      const uint32_t w3a = l16 + SM_WO3 + w * 512;
      if (HP == 1) { hints = hint_addr(s); PIN(hints); }
      if (!(WL & 1)) { lds128(w3a + KP(0) * WS, wa); lds128(w3a + KP(1) * WS, wb); }
      if (WL & 2) {
#pragma unroll
        for (int i = 0; i < 4; i++) oc[i] = always | (always >> 16) | (always & (i + 1));
      } else lds128(sb + SC_ONES, oc);
      if (B5POS == 1 && mode < 3) bar_arrive(5, N5);
      uint32_t e[10], p[5], vm[4], ob[4];
      float o0[4], o1[4], f[3][2][4], rs[4];
      if (!(RV & 1)) { reserve2(vm); reserve2(vm + 2); }
      if (!(RV & 2)) reserve2(e + 8);
      if (!HP) { hints = hint_addr(s); PIN(hints); }
      if (CLR & 2) asm volatile("{\n.reg .pred p;\nsetp.eq.u32 p, %0, 0;\n@p exit;\n}" :: "r"(wa[0] | wb[0] | oc[0] | hints) : "memory");
      if (RV & 4) mbar_wait_fast(sb + MB_S, par); else mbar_wait(sb + MB_S, par);
      RSTAMP(5);
      PROF(6);
      if (RV & 2) { ldsm4t(e, l16 + SM_E); ldsm4t(e + 4, l16 + SM_E + 512); ldsm2t(e + 8, l16 + SM_E + 1024); }
      else { ldsm4t(e, l16 + SM_E); ldsm2t_in(e + 8, l16 + SM_E + 1024, always); ldsm4t(e + 4, l16 + SM_E + 512); }
      if (RV & 1) lds128(l16 + w * 512 + SM_VM, vm); else lds128_in(vm, l16 + w * 512 + SM_VM, always);
      const float scl = __uint_as_float(lds32(sb + SC_UNSC + 8 - par * 8));
      if (HL == 0) hints = load_hints(hints);
      if (GF & 1) SCHED_FENCE(4);
#pragma unroll
      for (int i = 0; i < 4; i++) p[i] = mul_bf16(e[i], e[4 + i]);
      p[4] = mul_bf16(e[8], e[9]);
      if (HL) hints = load_hints(hints | (p[HL - 1] & always & 1));
      mma16816z(o0, vx[0], p[0], p[1]);
      if (WL & 1) { lds128_in(vx[0], w3a + KP(0) * WS, always); }
      mma16816z(o1, vx[1], p[0], p[1]);
      if (WL & 1) { lds128_in(vx[1], w3a + KP(1) * WS, always); }
      mma16816z(rs, oc, p[0], p[1]);
      mma16816(o0, vx[2], p[2], p[3]); lds128_in(vx[2], w3a + KP(2) * WS, always);
      mma16816(o1, vx[3], p[2], p[3]); lds128_in(vx[3], w3a + KP(3) * WS, always);
      mma16816(rs, oc, p[2], p[3]);
      mma1688(o0, vm[0], vm[1], p[4]); mma1688(o1, vm[2], vm[3], p[4]); mma1688(rs, oc[0], oc[1], p[4]);
      stsm4(l16 + w * 512 + SM_OB, pack_bf16(o0[0], o0[1]), pack_bf16(o0[2], o0[3]), pack_bf16(o1[0], o1[1]), pack_bf16(o1[2], o1[3]));
      bar_sync(6, 128);
      RSTAMP(3);
      PROF(7);
      ldsm4t_in(oc, l16 + SM_OB, always);
      bad = __any_sync(0xffffffffu, !(rs[0] + rs[1] > 0.f) && !bad);
      rs[0] *= scl; rs[1] *= scl;
      asm volatile("{\n.reg .pred p;\nsetp.ne.u32 p, %1, 0;\n@p rcp.approx.ftz.f32 %0, %0;\n}" : "+f"(rs[0]) : "r"(always));
      asm volatile("{\n.reg .pred p;\nsetp.ne.u32 p, %1, 1;\n@p rcp.approx.ftz.f32 %0, %0;\n}" : "+f"(rs[1]) : "r"(always));
      asm volatile("lop3.b32 %0, %1, %2, %3, 0xfe;" : "=r"(lp) : "r"((l16 & 128) * 2), "r"((l16 & 256) * 4), "r"(l16 & 112));
      if (bad) continue;
      ldsm4t(ob, l16 + SM_OB + 512);
      mma16816z(f[2][0], WL & 1 ? vx[0] : wa, oc[0], oc[1]); mma16816z(f[2][1], WL & 1 ? vx[1] : wb, oc[2], oc[3]);
      mma16816z(f[0][0], wo[0], oc[0], oc[1]); mma16816z(f[0][1], wo[4], oc[2], oc[3]);
      mma16816z(f[1][0], w1[0], oc[0], oc[1]); mma16816z(f[1][1], w1[4], oc[2], oc[3]);
      ldsm4t_in(oc, l16 + SM_OB + 1024, always);
      mma16816(f[2][0], vx[2], ob[0], ob[1]); lds128_in(vx[2], w3a + KP(4) * WS, always);
      mma16816(f[2][1], vx[3], ob[2], ob[3]); lds128_in(vx[3], w3a + KP(5) * WS, always);
      mma16816(f[0][0], wo[1], ob[0], ob[1]); mma16816(f[0][1], wo[5], ob[2], ob[3]);
      mma16816(f[1][0], w1[1], ob[0], ob[1]); mma16816(f[1][1], w1[5], ob[2], ob[3]);
      ldsm4t_in(ob, l16 + SM_OB + 1536, always);
      mma16816(f[0][0], wo[2], oc[0], oc[1]); mma16816(f[0][1], wo[6], oc[2], oc[3]);
      mma16816(f[2][0], vx[2], oc[0], oc[1]); lds128_in(vx[2], w3a + KP(6) * WS, always);
      mma16816(f[2][1], vx[3], oc[2], oc[3]); lds128_in(vx[3], w3a + KP(7) * WS, always);
      mma16816(f[1][0], w1[2], oc[0], oc[1]); mma16816(f[1][1], w1[6], oc[2], oc[3]);
      mma16816(f[0][0], wo[3], ob[0], ob[1]); mma16816(f[0][1], wo[7], ob[2], ob[3]);
      mma16816(f[1][0], w1[3], ob[0], ob[1]); mma16816(f[1][1], w1[7], ob[2], ob[3]);
      mma16816(f[2][0], vx[2], ob[0], ob[1]); mma16816(f[2][1], vx[3], ob[2], ob[3]);
      bar_arrive(7, NII < 18 ? 384 : 256);
      lds128_in(ob, sb + SC_DEAD, always);
      uint32_t h[3][2];
#pragma unroll
      for (int j = 0; j < 3; j++)
#pragma unroll
        for (int i = 0; i < 2; i++)
        {
          scale_sum(f[j][1][2 * i], f[j][0][2 * i], rs[0], always); scale_sum(f[j][1][2 * i + 1], f[j][0][2 * i + 1], rs[1], always);
          h[j][i] = pack_f16(f[j][1][2 * i], f[j][1][2 * i + 1]);
        }
      const uint32_t rofs = RANK * 32768;
      red_f16x8(slot(s, RANK >> 1, rofs), h[0][0], h[1][0], h[2][0], 0x3c00u);
      red_f16x8(slot(s, (RANK >> 1) ^ 1, rofs), h[0][1], h[1][1], h[2][1], 0x3c00u);
      if (NII == 18) bar_arrive(10, 256);
      SCHED_FENCE(5);
      RSTAMP(0);
      l16 += ob[B7R];
    }
    {
    PROF(8);
    if (VS0 == 3 || VS1 == 3) send_v(s + 1, 3);
    const uint32_t ma0 = l16 + SM_MEM + w * 128 + (LV >> 3) * 896 + nh * 512;
    const unsigned char* const sl[2] = {slot(s, nh, 0), slot(s, nh ^ 1, 0)};
    uint32_t late = latest_hint(hints, dl, s);
    if (late >= 64) {
      int n = 0;
#pragma unroll 1
      do {
        late = latest_hint(load_hints(hint_addr(s)), dl, s);
      } while (late >= 64 && ++n < SPIN_LIMIT);
    }
    dl += late * 32 + tm.poll;
    PROF(9);
    {
      auto wait_until = [&](uint32_t t) {
        asm volatile("{\n.reg .pred p;\n.reg .s32 c;\n.reg .u64 t;\nTL: mov.u64 t, %%globaltimer;\ncvt.u32.u64 c, t;\nsub.s32 c, c, %0;\nsetp.lt.s32 p, c, 0;\n@p bra.uni TL;\n}" :: "r"(t + (l16 & 15)) : "memory");
      };
      uint4 v[2][3];
      auto load = [&](int c) {
#pragma unroll
        for (int r = 0; r < 3; r++) v[c][r] = ldg_relaxed(sl[c ^ (r >> 1)] + r * 32768);
      };
      auto decode = [&](int c, int n) {
        uint32_t q[9];
        __half2 hm;
        const uint32_t ma = ma0 ^ (c * 512);
#pragma unroll
        for (int i = 0; i < 9; i++) {
          const uint32_t h = i % 3 == 0 ? v[c][i / 3].x : (i % 3 == 1 ? v[c][i / 3].y : v[c][i / 3].z);
          const float2 f = __half22float2(*(const __half2*)&h);
          q[i] = pack_bf16(f.x, f.y);
          hm = i ? __hmax2(hm, __habs2(*(const __half2*)&h)) : __habs2(*(const __half2*)&h);
        }
#pragma unroll
        for (int r = 0; r < 3; r++) stsm4(ma + r * 4096, q[3 * r], q[3 * r + 1], q[3 * r + 2], r < 2 ? v[c][r].w : *(const uint32_t*)&hm);
        const bool done = __all_sync(0xffffffffu, v[c][0].w == 0x5000u && v[c][1].w == 0x5000u && v[c][2].w == 0x5000u) || n > SPIN_LIMIT;
        asm volatile("{\n.reg .pred p;\nsetp.ne.u32 p, %0, 0;\n@p bar.arrive %1, 256;\n}" :: "r"((int)done), "r"(1 + c) : "memory");
        return done;
      };
      if (LEAD) { wait_until(dl - LEAD); load(1); }
      wait_until(dl);
      PROF(10);
      int n = 0;
#pragma unroll 1
      do {
        load(0);
        if (!LEAD) load(1);
        asm volatile("{\n.reg .pred p;\nsetp.eq.u32 p, %0, 0;\n@p bar.sync 13, 384;\n}" :: "r"(n) : "memory");
      } while (!decode(0, n++));
      PROF(11);
      RSTAMP(1);
#pragma unroll 1
      while (!decode(1, n++)) load(1);
      bar_arrive(9, 256);
      RSTAMP(2);
      PROF(12);
    }
    PROF(13);
    if (++s == NSEG - 1) break;
    }
  }
#undef fence_reg
  if (RANK < 2) bar_arrive(4, 256);
  TSTAMP(49);
  {
    PIN(l16);
    tail_attention(sb, RANK, w, LV, 0, 6);
#pragma unroll 1
    for (int sg = 0; sg < 2; sg++) {
      PIN(l16);
      const int lane = LV, m = lane >> 3, g = lane >> 2, t = lane & 3;
      const uint32_t ob = l16 + T_OB + sg * 8192;
      bar_sync(sg ? 0 : 8, 256);
      TSTAMP(54 + 2 * sg);
      const float inv = __uint_as_float(0x7f000000u - lds32(sb + T_UN + sg * 4));
#pragma unroll 1
      for (int j = 0; j < 4; j += 2) {
        float c[2][3][4];
        uint32_t x[4], y[4], z[2][4];
#pragma unroll
        for (int e = 0; e < 2; e++) {
          const uint32_t oa = sb + T_OA + ((sg * 4 + j + e) * 8 + g) * 64 + (blockIdx.x / 3 * 36 & 15) + t * 4;
          z[e][0] = lds32(oa); z[e][1] = lds32(oa + 16); z[e][2] = t ? 0u : lds32(oa + 32);
        }
#pragma unroll
        for (int i = 0; i < 3; i++) {
          const uint32_t wa = sb + T_WA + ((lane & 7) + ((lane >> 4) << 3)) * 128 + (((w + 4 * (m & 1)) ^ (lane & 7)) << 4);
          ldsm4t(x, wa + i * 3072); ldsm2t(y, wa + i * 3072 + 2048);
#pragma unroll
          for (int e = 0; e < 2; e++) { mma1688z(c[e][i], y[0], y[1], z[e][2]); mma16816(c[e][i], x, z[e][0], z[e][1]); }
        }
#pragma unroll
        for (int r = 0; r < 4; r++) {
          ldsm4t(z[0], ob + j * 2048 + r * 512); ldsm4t(z[1], ob + j * 2048 + 2048 + r * 512);
          lds128(l16 + SM_WO3 + w * 512 + r * 2048, x); lds128(l16 + SM_WO3 + w * 512 + (r + 4) * 2048, y);
#pragma unroll
          for (int e = 0; e < 2; e++) { mma16816(c[e][0], wo[r], z[e][0], z[e][1]); mma16816(c[e][1], w1[r], z[e][0], z[e][1]); mma16816(c[e][2], x, z[e][0], z[e][1]); }
#pragma unroll
          for (int e = 0; e < 2; e++) { mma16816(c[e][0], wo[r + 4], z[e][2], z[e][3]); mma16816(c[e][1], w1[r + 4], z[e][2], z[e][3]); mma16816(c[e][2], y, z[e][2], z[e][3]); }
        }
#pragma unroll
        for (int i = 0; i < 4; i++) {
          const float (&d)[3][4] = c[i >> 1];
          const int q = (i & 1) * 2;
          red_f16x8(g_red + T_RED + ((((sg * 4 + j + (i >> 1)) * 3 + RANK) * 4 + w) * 2 + (i & 1)) * 512 + lane * 16, pack_f16(d[0][q] * inv, d[0][q + 1] * inv),
                    pack_f16(d[1][q] * inv, d[1][q + 1] * inv), pack_f16(d[2][q] * inv, d[2][q + 1] * inv), 0x3c00u);
        }
      }
      TSTAMP(55 + 2 * sg);
    }
    if (RSLOW) { wait_until(gtime() + 8000); wait_until(gtime() + 8000); wait_until(gtime() + 4000); }
    if (w < 2) {
      const int b = blockIdx.x, lane = LV, g = lane >> 2, t = lane & 3;
      uint4 v;
#pragma unroll 1
      for (int n = 0; n < SPIN_LIMIT; n++) {
        v = ldg_relaxed(g_red + T_RED + (w * 96 + b) * 512 + lane * 16);
        if (__all_sync(0xffffffffu, v.w == 0x5000u)) break;
        __nanosleep(40);
      }
      const float un = __uint_as_float(lds32(sb + T_UN + w * 4));
      uint32_t* const o = (uint32_t*)(tm.out + (size_t)((NAUXSEG + w) * 32 + b / 24 * 8 + g) * DM + (b >> 3) % 3 * 192 + (b & 1) * 32 + (b & 6) * 4) + t;
#pragma unroll
      for (int j = 0; j < 3; j++) {
        const float2 f = __half22float2(*(const __half2*)(&v.x + j));
        o[j * 32] = movm(pack_bf16(f.x * un, f.y * un));
      }
    }
  }
  TSTAMP(3);
  if (CSY) cluster_sync();
}

__global__ void __cluster_dims__(3, 1, 1) __launch_bounds__(384, 1)
rec_kernel(const __grid_constant__ RMaps tm, const bf16* __restrict__ x, const bf16* __restrict__ mem0) {
  extern __shared__ __align__(1024) unsigned char smem_raw[];
  const uint32_t sb = smem_u32(smem_raw);
  const int tid = threadIdx.x, lane = tid & 31;
  const int wg = __shfl_sync(0xffffffffu, tid >> 7, 0);
  const int w = __shfl_sync(0xffffffffu, (tid >> 5) & 3, 0);
  uint32_t rank; asm("mov.u32 %0, %%cluster_ctarank;" : "=r"(rank));
  STAMP(0);
  TSTAMP(0);
  asm volatile("griddepcontrol.launch_dependents;" ::: "memory");

#define PFT 1
  if (PFT && wg == 1 && lane == 0) asm volatile("prefetch.tensormap [%0];\nprefetch.tensormap [%1];" :: "l"(w & 1 ? &tm.woa : &tm.oa), "l"(w == 0 ? (rank < 2 ? &tm.wk : &tm.wv) : w == 1 ? &tm.wq : w == 2 ? &tm.x : &tm.wo) : "memory");
  if (wg < 2) {
    asm volatile("setmaxnreg.inc.sync.aligned.u32 192;");
    if (tid == 0) {
      for (int i = 0; i < 3; i++) { mbar_init(sb + MB_W + 8 * i, 1); mbar_init(sb + MB_X + 8 * i, 1); }
      mbar_init(sb + MB_WO, 1); mbar_init(sb + MB_WO3, 1);
      mbar_init(sb + MB_S, rank < 2 ? 5 : 6);
      mbar_init(sb + MB_F, 1);
      for (int i = 0; i < 3; i++) mbar_init(sb + MB_T + 8 * i, 1);
      mbar_init(sb + MB_VX, 1); mbar_init(sb + MB_VX + 8, 1);
      asm volatile("fence.mbarrier_init.release.cluster;" ::: "memory");
      fence_async();
      SSTAMP(11, 6);
      load_weights(sb, tm, rank, 0);
      for (int i = 0; i < 3; i++) mbar_expect(sb + MB_X + 8 * i, XT);
      tma_load3(sb + SM_X, &tm.x, 0, sb + MB_X);
      if (!PACE) for (int c = 1; c < 4; c++) load_weights(sb, tm, rank, c);
      mbar_expect(sb + MB_S, rank < 2 ? 640 + 2048 : 1280);
      mbar_expect(sb + MB_VX, 8192); mbar_expect(sb + MB_VX + 8, 8192);
      mbar_expect(sb + MB_T, 2048);
      for (int i = 1; i < 3; i++) mbar_expect(sb + MB_T + 8 * i, rank < 2 ? 5120 : 10240);
      SSTAMP(11, 5);
    }
    __syncwarp();
    bar_sync(0, 384);
    proj_role(sb, tm, rank, wg, w, lane);
  } else {
    asm volatile("setmaxnreg.dec.sync.aligned.u32 120;");
    attn_role(sb, smem_raw, tm, rank, x, mem0, w, lane);
  }
}

constexpr int A_XH = 73728;
constexpr int A_NS = 9, A_WM = 6144, A_WT = 768;
constexpr int A_RING = 2 * A_XH, A_TAIL = A_RING + A_NS * A_WM, A_GW = A_TAIL + A_NS * A_WT;
constexpr int A_EPI = 212864, A_EPW = 9344;
constexpr int A_XT = 4 * XT, A_XW = A_XT + 8192, A_EX = A_XW + 8192, A_NR = 4;
constexpr int A_IN = A_EX + 16384, A_OST = A_IN + 3 * SEGB;
constexpr int A_GATE = A_EPI + 2 * A_EPW, A_BAR = A_GATE + 512;
constexpr int A_TOTAL = A_BAR + 384;
struct AMaps { CUtensorMap x, wa, wt, oa, o, o3, wob, woa; };

DI void wgmma_n192_ss_nt(float* d, uint64_t da, uint64_t db, int acc) {
  asm volatile("{\n.reg .pred p;\nsetp.ne.b32 p, %98, 0;\n"
               "wgmma.mma_async.sync.aligned.m64n192k16.f32.bf16.bf16 {"
               "%0,%1,%2,%3,%4,%5,%6,%7,%8,%9,%10,%11,%12,%13,%14,%15,%16,%17,%18,%19,%20,%21,%22,%23,%24,%25,%26,%27,%28,%29,%30,%31,"
               "%32,%33,%34,%35,%36,%37,%38,%39,%40,%41,%42,%43,%44,%45,%46,%47,%48,%49,%50,%51,%52,%53,%54,%55,%56,%57,%58,%59,%60,%61,%62,%63,"
               "%64,%65,%66,%67,%68,%69,%70,%71,%72,%73,%74,%75,%76,%77,%78,%79,%80,%81,%82,%83,%84,%85,%86,%87,%88,%89,%90,%91,%92,%93,%94,%95"
               "}, %96, %97, p, 1, 1, 0, 1;\n}\n"
               : ACC8(d, 0), ACC8(d, 8), ACC8(d, 16), ACC8(d, 24), ACC8(d, 32), ACC8(d, 40), ACC8(d, 48), ACC8(d, 56),
                 ACC8(d, 64), ACC8(d, 72), ACC8(d, 80), ACC8(d, 88) : "l"(da), "l"(db), "r"(acc));
}
#define ACC4(d, o) "+f"(d[o]), "+f"(d[o + 1]), "+f"(d[o + 2]), "+f"(d[o + 3])
DI void wgmma_n24_ss_nt(float* d, uint64_t da, uint64_t db, int acc) {
  asm volatile("{\n.reg .pred p;\nsetp.ne.b32 p, %14, 0;\n"
               "wgmma.mma_async.sync.aligned.m64n24k16.f32.bf16.bf16 {%0,%1,%2,%3,%4,%5,%6,%7,%8,%9,%10,%11}, %12, %13, p, 1, 1, 0, 1;\n}\n"
               : ACC8(d, 0), ACC4(d, 8) : "l"(da), "l"(db), "r"(acc));
}
DI void wgmma_n8_ss(float* d, uint64_t da, uint64_t db, int acc) {
  asm volatile("{\n.reg .pred p;\nsetp.ne.b32 p, %6, 0;\n"
               "wgmma.mma_async.sync.aligned.m64n8k16.f32.bf16.bf16 {%0,%1,%2,%3}, %4, %5, p, 1, 1, 0, 0;\n}\n"
               : ACC4(d, 0) : "l"(da), "l"(db), "r"(acc));
}
DI void wgmma_n40_ss_tt(float* d, uint64_t da, uint64_t db, int acc) {
  asm volatile("{\n.reg .pred p;\nsetp.ne.b32 p, %22, 0;\n"
               "wgmma.mma_async.sync.aligned.m64n40k16.f32.bf16.bf16 {%0,%1,%2,%3,%4,%5,%6,%7,%8,%9,%10,%11,%12,%13,%14,%15,%16,%17,%18,%19}, "
               "%20, %21, p, 1, 1, 1, 1;\n}\n"
               : ACC8(d, 0), ACC8(d, 8), ACC4(d, 16) : "l"(da), "l"(db), "r"(acc));
}
DI void wgmma_n64_rs(float* d, const uint32_t* a, uint64_t db, int acc) {
  asm volatile("{\n.reg .pred p;\nsetp.ne.b32 p, %37, 0;\n"
               "wgmma.mma_async.sync.aligned.m64n64k16.f32.bf16.bf16 {"
               "%0,%1,%2,%3,%4,%5,%6,%7,%8,%9,%10,%11,%12,%13,%14,%15,%16,%17,%18,%19,%20,%21,%22,%23,%24,%25,%26,%27,%28,%29,%30,%31"
               "}, {%32,%33,%34,%35}, %36, p, 1, 1, 0;\n}\n"
               : ACC8(d, 0), ACC8(d, 8), ACC8(d, 16), ACC8(d, 24) : "r"(a[0]), "r"(a[1]), "r"(a[2]), "r"(a[3]), "l"(db), "r"(acc));
}
DI void wgmma_n32_ss_tn(float* d, uint64_t da, uint64_t db, int acc) {
  asm volatile("{\n.reg .pred p;\nsetp.ne.b32 p, %18, 0;\n"
               "wgmma.mma_async.sync.aligned.m64n32k16.f32.bf16.bf16 {%0,%1,%2,%3,%4,%5,%6,%7,%8,%9,%10,%11,%12,%13,%14,%15}, "
               "%16, %17, p, 1, 1, 1, 0;\n}\n"
               : ACC8(d, 0), ACC8(d, 8) : "l"(da), "l"(db), "r"(acc));
}
DI void tma_load3c(uint32_t dst, const CUtensorMap* m, int c0, int c1, int c2, uint32_t mb) {
  asm volatile("cp.async.bulk.tensor.3d.shared::cluster.global.mbarrier::complete_tx::bytes [%0], [%1, {%3, %4, %5}], [%2];"
               :: "r"(dst), "l"(m), "r"(mb), "r"(c0), "r"(c1), "r"(c2) : "memory");
}
DI void count_up(unsigned* p) {
  asm volatile("fence.proxy.async;" ::: "memory");
  asm volatile("red.release.gpu.global.add.u32 [%0], 1;" :: "l"(p) : "memory");
}
#define AX 0
#define FDLY 400
#define ORING 63
#define DRY 0
#define FEND 59
#define ADLY 0

__global__ void __launch_bounds__(512, 1)
aux_kernel(const __grid_constant__ AMaps tm, const bf16* __restrict__ wqkv, const bf16* __restrict__ woa, const bf16* __restrict__ gate_w, bf16* __restrict__ out) {
  extern __shared__ __align__(1024) unsigned char smem_raw[];
  const uint32_t sb = smem_u32(smem_raw);
  const uint32_t fullx = sb + A_BAR, full1 = fullx + 24, empty1 = full1 + 8 * A_NS, fullw = empty1 + 8 * A_NS, full3 = fullw + 8, empty3 = full3 + 8 * A_NR,
                 fullq = empty3 + 8 * A_NR, fullv = fullq + 8, emptyq = fullv + 8, emptyv = emptyq + 8;
  const int tid = threadIdx.x, lane = tid & 31, cta = blockIdx.x;
  const int wg = __shfl_sync(0xffffffffu, tid >> 7, 0), w = __shfl_sync(0xffffffffu, (tid >> 5) & 3, 0);
  ASTAMP(14);
  if (tid == 384) {
    for (int i = 0; i < 3; i++) mbar_init(fullx + 8 * i, 1);
    for (int i = 0; i < A_NS; i++) { mbar_init(full1 + 8 * i, 1); mbar_init(empty1 + 8 * i, 8); }
    mbar_init(fullw, 1); mbar_init(fullq, 1); mbar_init(fullv, 1); mbar_init(emptyq, 4); mbar_init(emptyv, 4);
    for (int i = 0; i < A_NR; i++) { mbar_init(full3 + 8 * i, 1); mbar_init(empty3 + 8 * i, 4); }
    fence_async();
  }
  __syncthreads();
  ASTAMP(0);
  const int tile = cta >> 1, hh = cta & 1;
  const int nsl = cta >> 2, kq = cta & 3;
  if (wg == 3) {
    asm volatile("setmaxnreg.dec.sync.aligned.u32 24;");
    const bool lead = lane == 0;
    if (w < 3) {
      if (ADLY) wait_until(gtime() + ADLY);
      if (elect_one()) {
        mbar_expect(fullx + 8 * w, 49152);
        for (int p = 0; p < 2; p++)
          asm volatile("cp.async.bulk.tensor.4d.shared::cluster.global.mbarrier::complete_tx::bytes [%0], [%1, {%3, %4, %5, %6}], [%2];"
                       :: "r"(sb + p * A_XH + w * 24576), "l"(&tm.x), "r"(fullx + 8 * w), "r"(0), "r"(p), "r"(57 * tile - 7), "r"(3 * w) : "memory");
      }
#pragma unroll 1
      for (int r = 0; r < 17; r++) {
#pragma unroll 1
        for (int st = w; st < A_NS; st += 3) {
          if (r > 0) mbar_wait(empty1 + 8 * st, ~r & 1);
          if (r < 16 && elect_one()) {
            const int col = hh * 288 + (r >> 2) * 72, row = (r & 3) * 144 + st * 16;
            mbar_expect(full1 + 8 * st, A_WM + (AX & 1 ? 0 : A_WT));
            tma_load3c(sb + A_RING + st * A_WM, &tm.wa, col, row, 0, full1 + 8 * st);
            if (!(AX & 1)) tma_load3c(sb + A_TAIL + st * A_WT, &tm.wt, col + 64, row, 0, full1 + 8 * st);
          }
          __syncwarp();
        }
        if (r == 0 && elect_one())
          for (int j = 0; j < 3; j++)
            asm volatile("cp.async.bulk.prefetch.L2.global [%0], %1;" :: "l"((const char*)wqkv + cta * 55296 + (w * 3 + j) * 6144), "r"(6144) : "memory");
        __syncwarp();
      }
      bar_sync(8, 96);
    }
    const unsigned epoch = lds32(sb + A_BAR + 376);
    if (w == 1 && cta < NH) {
#pragma unroll 1
      for (int seg = 0; seg < NAUXSEG; seg++) {
        bar_arrive(5, 160);
        if (seg > 0 && lead) {
          asm volatile("cp.async.bulk.wait_group 0;" ::: "memory");
          asm volatile("red.relaxed.gpu.global.add.u32 [%0], 1;" :: "l"(&g_ocnt[(seg - 1) * 32 + cta / 9 * 8]) : "memory");
          SSTAMP(9, seg - 1);
        }
        __syncwarp();
        bar_sync(4, 160);
        if (lead && !(AX & 32)) {
          tma_store(&tm.o, sb + A_OST, cta * DH, (seg & ORING) * 32);
          tma_store(&tm.o, sb + A_OST + 4096, cta * DH + 64, (seg & ORING) * 32);
          asm volatile("cp.async.bulk.commit_group;" ::: "memory");
          asm volatile("cp.async.bulk.wait_group.read 0;" ::: "memory");
        }
        __syncwarp();
      }
      if (lead) {
        asm volatile("cp.async.bulk.wait_group 0;" ::: "memory");
        asm volatile("red.relaxed.gpu.global.add.u32 [%0], 1;" :: "l"(&g_ocnt[(NAUXSEG - 1) * 32 + cta / 9 * 8]) : "memory");
        SSTAMP(9, NAUXSEG - 1);
      }
    }
    if (w == 2) {
      if (lead && cta < NH) {
#pragma unroll 1
        for (int seg = 0; seg < NAUXSEG; seg++) {
          const unsigned char* const src = g_seg + ((size_t)(AX & 128 ? 0 : seg % NRING) * 96 + cta * 3) * SEGB;
          SSTAMP(0, seg);
          const uint32_t tw = gtime();
          wait_count(&g_scnt[(seg * 32 + cta) * 8], 3 * (epoch + 1), !(TL & 2) || seg < NAUXSEG - 2);
          if (FDLY && seg < FEND && gtime() - tw > 600) wait_until(gtime() + FDLY);
          SSTAMP(1, seg);
          mbar_wait(emptyq, ~seg & 1);
          if (AX & 8) { mbar_arrive(fullq); mbar_wait(emptyv, ~seg & 1); mbar_arrive(fullv); continue; }
          mbar_expect(fullq, 2 * SEGB);
          asm volatile("cp.async.bulk.shared::cluster.global.mbarrier::complete_tx::bytes [%0], [%1], %2, [%3];"
                       :: "r"(sb + A_IN), "l"(src), "r"(2 * SEGB), "r"(fullq) : "memory");
          mbar_wait(emptyv, ~seg & 1);
          if (seg == 1) wait_count(&g_abar[32], NAUX * (epoch + 1));
          stg_relaxed32(&g_used[cta * 32], epoch * NSEG + seg);
          mbar_expect(fullv, SEGB);
          asm volatile("cp.async.bulk.shared::cluster.global.mbarrier::complete_tx::bytes [%0], [%1], %2, [%3];"
                       :: "r"(sb + A_IN + 2 * SEGB), "l"(src + 2 * SEGB), "r"(SEGB), "r"(fullv) : "memory");
        }
      }
    }
    if (w == 3) {
#pragma unroll 1
      for (int c = 0; c < 4; c++) {
        if (lead) asm volatile("cp.async.bulk.wait_group.read 0;" ::: "memory");
        __syncwarp();
        bar_arrive(11, 160); bar_arrive(12, 160);
#pragma unroll 1
        for (int g = 0; g < 2; g++) {
          bar_sync(13 + g, 160);
          if (lead) {
            asm volatile("cp.async.bulk.tensor.3d.global.shared::cta.bulk_group [%0, {%2, %3, %4}], [%1];"
                         :: "l"(&tm.oa), "r"(sb + A_EPI + g * A_EPW + 1024), "r"(4096 + hh * 288 + c * 72), "r"(g), "r"(57 * tile) : "memory");
            asm volatile("cp.async.bulk.commit_group;" ::: "memory");
          }
        }
      }
      if (lead) asm volatile("cp.async.bulk.wait_group.read 0;" ::: "memory");
      __syncwarp();
      bar_arrive(10, 160);
      if (lead) { asm volatile("cp.async.bulk.wait_group 0;" ::: "memory"); count_up(&g_abar[32]); }
    }
    if (w != 0) return;
    if (lead) {
      mbar_expect(fullw, 19 * 8192);
#pragma unroll 1
      for (int k = 0; k < 19; k++) {
        const int kb = k < 18 ? kq * 18 + k : 72;
        const uint32_t dst = sb + (k < 18 ? k * 8192 : A_XW);
        if (kb < 64) tma_load(dst, &tm.wob, nsl * 64, kb * 64, fullw);
        else tma_load(dst, &tm.woa, nsl * 64, (kb - 64) * 64, fullw);
      }
    }
    __syncwarp();
    bar_sync(6, 288);
    if (lead) {
      if (kq == 3) { wait_count(&g_abar[32], NAUX * (epoch + 1)); asm volatile("fence.proxy.async;" ::: "memory"); }
      int avail = 0;
      bool waited = false;
      const unsigned nheads = (kq < 3 ? 9 : 5) * (epoch + 1);
      for (int seg = 0; seg < NAUXSEG; seg++) {
        if (seg >= avail) {
          const int far = min(seg + 3, NAUXSEG - 1);
          if (far > seg && !waited && (int)(ldg_acquire32(&g_ocnt[far * 32 + kq * 8]) - nheads) >= 0) avail = far + 1;
          else { waited = wait_count(&g_ocnt[seg * 32 + kq * 8], nheads, !(TL & 2) || seg < NAUXSEG - 2) && (TL & 4); avail = seg + 1; }
        }
        SSTAMP(5, seg);
        for (int g = 0; g < 2; g++) {
          const int sl = (seg & 1) * 2 + g;
          const bool extra = kq == 3 && g == 0;
          mbar_wait(empty3 + 8 * sl, ((seg >> 1) & 1) ^ 1);
          if (AX & 4) { mbar_arrive(full3 + 8 * sl); continue; }
          mbar_expect(full3 + 8 * sl, XT + (extra ? 4096 : 0));
          tma_load3c(sb + sl * XT, &tm.o3, 0, (kq == 3 && g == 1 ? seg : seg & ORING) * 32, kq * 18 + 9 * g, full3 + 8 * sl);
          if (extra) tma_load(sb + A_XT + (seg & 1) * 4096, &tm.o, 72 * 64, seg * 32, full3 + 8 * sl);
        }
      }
    }
    __syncwarp(); bar_sync(6, 288);
    if (GDW) asm volatile("griddepcontrol.wait;" ::: "memory");
  } else if (wg == 2) {
    asm volatile("setmaxnreg.dec.sync.aligned.u32 88;");
    {
      const unsigned epoch = *(volatile unsigned*)&g_epoch2;
      if ((tid & 127) < 80) { const uint4 g = __ldg((const uint4*)gate_w + min(tid & 127, 71)); sts128(sb + A_GW + (tid & 127) * 16, g.x, g.y, g.z, g.w); }
      fence_async();
      bar_sync(3, 128);
      float gt[2][4];
      const uint32_t d0 = (sb & 0x3FFFF) >> 4;
#pragma unroll 1
      for (int j = 0; j < 3; j++) {
        mbar_wait(fullx + 8 * j, 0);
        WG_FENCE();
#pragma unroll
        for (int k = 0; k < 24; k++)
          wgmma_n8_ss(gt[k & 1], desc_at(d0 + (k & 1) * (A_XH >> 4) + j * 1536 + (k >> 3) * 512 + (k & 6), 16, 1024, 1), desc_at(d0 + (A_GW >> 4) + j * 24 + (k & 30), 16, 128, 0), j | (k >> 1));
        WG_COMMIT();
      }
      WG_WAIT(0);
      if ((lane & 3) == 0)
#pragma unroll
        for (int i = 0; i < 4; i++) {
          const float gv = 1.f / (1.f + __expf(-gt[i >> 1][(i & 1) * 2]));
          const int r = w * 16 + (lane >> 2) + (i & 1) * 8, tok = 2 * (57 * tile - 7 + r) + (i >> 1);
          sts32(sb + A_GATE + ((i >> 1) * 64 + r) * 4, __float_as_uint(gv));
          if (hh == 0 && r >= 7 && tok < S_LEN) g_gate[tok] = gv;
        }
      if (tid == 256) sts32(sb + A_BAR + 376, epoch);
      __syncwarp();
      bar_arrive(7, 384);
      __half2 hw = __float2half2_rn(0.f);
#pragma unroll
      for (int i = 0; i < 9; i++) { const uint4 v = __ldg((const uint4*)woa + cta * 1152 + i * 128 + (tid & 127)); hw = amax4(hw, &v.x); }
      const uint32_t ew = wexp(hw);
      if (lane == 0) atomicMax(&g_amax[0], (unsigned long long)(epoch + 1) << 32 | ew);
      bar_sync(3, 128);
      if (tid == 256) {
        count_up(&g_abar[0]);
        wait_count(&g_abar[0], NAUX * (epoch + 1));
        if (cta == 0) *(volatile unsigned*)&g_epoch2 = epoch + 1;
      }
      __syncwarp();
      bar_sync(10, 160);
    }
    if (cta < NH) {
      const int lim = w * 8 + (lane >> 2) - 2 * (lane & 3);
      const uint32_t oa = sb + A_OST + (w * 8 + (lane & 7)) * 128;
      const uint32_t d0 = ((sb + A_IN) & 0x3FFFF) >> 4;
      uint32_t p[5][4];
#pragma unroll
      for (int n = 0; n < 10; n++) p[n >> 1][1 + (n & 1)] = __shfl_sync(0xffffffffu, lane ^ n, n);
#pragma unroll 1
      for (int seg = 0; seg < NAUXSEG; seg++) {
        const float gt = __ldcg(&g_gate[seg * 32 + w * 8 + (lane >> 2)]);
        float sc[20], d[32];
        mbar_wait(fullq, seg & 1);
        if (tid == 256) SSTAMP(2, seg);
        WG_FENCE();
#pragma unroll
        for (int k = 0; k < 8; k++) {
          const int o = ((k >> 2) * SEGB + (k & 3) * 256) >> 4;
          wgmma_n40_ss_tt(sc, desc_at(d0 + o, 128, 512, 0), desc_at(d0 + o + 256, 128, 1024, 0), k > 0);
        }
        WG_COMMIT();
        WG_WAIT(0);
        if (lane == 0) mbar_arrive(emptyq);
        float a[10];
#pragma unroll
        for (int i = 0; i < 10; i++) {
          a[i] = sc[(i >> 1) * 4 + (i & 1)] * (SM_SCALE * LOG2E);
          if (i < 8 && (i >> 1) * 8 + (i & 1) > lim) a[i] = -1.0e9f * LOG2E;
        }
        float m = max10(a);
        m = fmaxf(m, __shfl_xor_sync(0xffffffffu, m, 1)); m = fmaxf(m, __shfl_xor_sync(0xffffffffu, m, 2));
#pragma unroll
        for (int i = 0; i < 10; i++) a[i] = ex2(a[i] - m);
#pragma unroll
        for (int n = 0; n < 5; n++) {
          p[n][0] = pack_bf16(a[2 * n], a[2 * n + 1]); p[n][3] = p[n][0] | p[n][1];
          asm volatile("" : "+r"(p[n][0]), "+r"(p[n][3]) :: "memory");
        }
        float sum = ((a[0] + a[1]) + (a[2] + a[3])) + ((a[4] + a[5]) + (a[6] + a[7])) + (a[8] + a[9]);
        sum += __shfl_xor_sync(0xffffffffu, sum, 1);
        if (tid == 256) SSTAMP(3, seg);
        mbar_wait(fullv, seg & 1);
        WG_FENCE();
#pragma unroll
        for (int n = 0; n < 5; n++) wgmma_n64_rs(d, p[n], n < 4 ? desc_at(d0 + SEGB / 8 + 8 * n, 4096, 512, 0) : desc_at(d0 + SEGB / 8 + 512, 1024, 128, 0), n);
        WG_COMMIT();
        sum += __shfl_xor_sync(0xffffffffu, sum, 2);
        const float f = (1.f - gt) * rcp(sum);
        bar_sync(5, 160);
        WG_WAIT(0);
        if (lane == 0) mbar_arrive(emptyv);
        if (tid == 256) SSTAMP(4, seg);
#pragma unroll
        for (int q = 0; q < 4; q++) {
          const float* const o = d + (q & 1) * 16 + (q & 2);
          stsm4(oa + (q >> 1) * 4096 + ((((q & 1) * 4 + (lane >> 3)) ^ (lane & 7)) << 4), pack_bf16(o[0] * f, o[1] * f), pack_bf16(o[4] * f, o[5] * f),
                pack_bf16(o[8] * f, o[9] * f), pack_bf16(o[12] * f, o[13] * f));
        }
        fence_async();
        bar_sync(4, 160);
      }
    }
  } else {
    asm volatile("setmaxnreg.inc.sync.aligned.u32 200;");
    {
      const int g = lane >> 2, t = lane & 3;
      const uint32_t eb = sb + A_EPI + wg * A_EPW, d0 = (sb & 0x3FFFF) >> 4;
      const uint32_t own = (2 * t <= g ? 0xffffu : 0u) | (2 * t < g ? 0xffff0000u : 0u);
      const int kmin = 7 - 57 * tile - 16 * w;
      __half2 ho = __float2half2_rn(0.f);
#pragma unroll 1
      for (int c = -DRY; c < 4; c++) {
        float acc[96], tl[12];
#pragma unroll 1
        for (int r = c < 0 ? 4 : 0; r < 4; r++) {
#pragma unroll
          for (int st = 0; st < A_NS; st++) {
            const int ks = r * 9 + st;
            if (c == 0 && st % 3 == 0 && ks % 12 == 0) mbar_wait(fullx + 8 * (ks / 12), 0);
            mbar_wait(full1 + 8 * st, r & 1);
            const uint64_t da = desc_at(d0 + wg * (A_XH >> 4) + (ks >> 2) * 512 + (ks & 3) * 2, 16, 1024, 1);
            WG_FENCE();
            wgmma_n192_ss_nt(acc, da, desc_at(d0 + ((A_RING + st * A_WM) >> 4), 2048, 1024, 1), ks);
            if (!(AX & 2)) wgmma_n24_ss_nt(tl, da, desc_at(d0 + ((A_TAIL + st * A_WT) >> 4), 128, 256, 0), ks);
            WG_COMMIT();
            if (st == 0 && r == 2) bar_sync(11 + wg, 160);
            WG_WAIT(1);
            if (ks > 0 && lane == 0) mbar_arrive(empty1 + 8 * ((st + A_NS - 1) % A_NS));
          }
        }
        WG_WAIT(0);
        if (lane == 0 && c >= 0) mbar_arrive(empty1 + 8 * (A_NS - 1));
        ASTAMP(16 + (c & 3));
        uint32_t ql[9], qh[9], kl[9], kh[9], kx[10], vl[9], vh[9], vx[10];
#pragma unroll
        for (int j = 0; j < 9; j++) {
          const float* const q = j < 8 ? acc + 4 * j : tl, * const k = j < 8 ? acc + 32 + 4 * j : tl + 4, * const v = j < 8 ? acc + 64 + 4 * j : tl + 8;
          kh[j] = pack_bf16(k[2], k[3]); vh[j] = pack_bf16(v[2], v[3]);
          ql[j] = pack_bf16(q[0], q[1]); qh[j] = pack_bf16(q[2], q[3]); kl[j] = pack_bf16(k[0], k[1]); vl[j] = pack_bf16(v[0], v[1]);
        }
        if (w < 3) {
          const uint32_t ha = eb + 1024 + w * 2304 + lane * 16;
          stsm4(ha, kh[0], kh[1], kh[2], kh[3]); stsm4(ha + 512, kh[4], kh[5], kh[6], kh[7]);
          stsm4(ha + 1024, vh[0], vh[1], vh[2], vh[3]); stsm4(ha + 1536, vh[4], vh[5], vh[6], vh[7]);
          asm volatile("stmatrix.sync.aligned.m8n8.x2.shared.b16 [%0], {%1,%2};" :: "r"(ha + 2048), "r"(kh[8]), "r"(vh[8]) : "memory");
        }
        if (c == 0) bar_sync(7, 384); else bar_sync(1 + wg, 128);
        {
          const uint32_t ha = eb + 1024 + max(w - 1, 0) * 2304 + lane * 16;
          ldsm4(kx, ha); ldsm4(kx + 4, ha + 512); ldsm4t(vx, ha + 1024); ldsm4t(vx + 4, ha + 1536);
          asm volatile("ldmatrix.sync.aligned.m8n8.x1.shared.b16 {%0}, [%1];" : "=r"(kx[8]) : "r"(ha + 2048) : "memory");
          asm volatile("ldmatrix.sync.aligned.m8n8.x1.trans.shared.b16 {%0}, [%1];" : "=r"(vx[8]) : "r"(ha + 2176) : "memory");
        }
        const float gl = __uint_as_float(lds32(sb + A_GATE + (wg * 64 + w * 16 + g) * 4)), gh = __uint_as_float(lds32(sb + A_GATE + (wg * 64 + w * 16 + g + 8) * 4));
#pragma unroll
        for (int j = 0; j < 9; j++) { vl[j] = movm(vl[j]); vh[j] = movm(vh[j]); }
        bar_sync(1 + wg, 128);
        uint32_t ol[9], oh[9];
#pragma unroll
        for (int i = 0; i < 4; i++) {
          const int b = 2 * i;
          const uint32_t a[4] = {t >= i ? ql[b] : 0u, t >= i ? qh[b] : 0u, ql[b + 1], qh[b + 1]}, a4 = t <= i ? ql[b + 2] : 0u, a5 = t <= i ? qh[b + 2] : 0u;
          float sx[4], sl[4], sh[4];
          mma16816z(sx, a, kx[b], kx[b + 1]); mma16816z(sl, a, kl[b], kl[b + 1]); mma16816z(sh, a, kh[b], kh[b + 1]);
          mma1688(sx, a4, a5, kx[b + 2]); mma1688(sl, a4, a5, kl[b + 2]); mma1688(sh, a4, a5, kh[b + 2]);
          float e[4];
#pragma unroll
          for (int u = 0; u < 4; u++) {
            const int cc = 2 * t + (u & 1);
            e[u] = (cc <= g ? (u < 2 ? sl[u] : sh[u]) : (u < 2 ? sx[u] : sl[u])) * (0.23570226039551584f * LOG2E);
            if ((cc <= g ? cc : cc - 8) + (u & 2) * 4 < kmin) e[u] = -1.0e9f * LOG2E;
          }
          float m0 = fmaxf(e[0], e[1]), m1 = fmaxf(e[2], e[3]);
#pragma unroll
          for (int o = 1; o < 4; o <<= 1) { m0 = fmaxf(m0, __shfl_xor_sync(0xffffffffu, m0, o)); m1 = fmaxf(m1, __shfl_xor_sync(0xffffffffu, m1, o)); }
          e[0] = ex2(e[0] - m0); e[1] = ex2(e[1] - m0); e[2] = ex2(e[2] - m1); e[3] = ex2(e[3] - m1);
          const uint32_t p0 = pack_bf16(e[0], e[1]), p1 = pack_bf16(e[2], e[3]);
          const uint32_t p[4] = {p0 & ~own, 0u, p0 & own, p1 & ~own};
          float s0 = e[0] + e[1], s1 = e[2] + e[3];
#pragma unroll
          for (int o = 1; o < 4; o <<= 1) { s0 += __shfl_xor_sync(0xffffffffu, s0, o); s1 += __shfl_xor_sync(0xffffffffu, s1, o); }
          const float f0 = gl * rcp(s0), f1 = gh * rcp(s1);
#pragma unroll
          for (int j = b; j < b + 3; j++) {
            float o[4];
            mma16816z(o, p, vx[j], vl[j]);
            mma1688(o, 0u, p1 & own, vh[j]);
            const uint32_t lo = pack_bf16(o[0] * f0, o[1] * f0), hi = pack_bf16(o[2] * f1, o[3] * f1);
            if (j > b || i == 0) { ol[j] = lo; oh[j] = hi; }
            else { ol[j] = t >= i ? lo : ol[j]; oh[j] = t >= i ? hi : oh[j]; }
          }
        }
        const uint32_t sa = eb + 16 + (w * 16 + (lane & 15)) * 144 + (lane >> 4) * 16;
#pragma unroll
        for (int j = 0; j < 8; j += 2) stsm4(sa + j * 16, ol[j], oh[j], ol[j + 1], oh[j + 1]);
        asm volatile("stmatrix.sync.aligned.m8n8.x2.shared.b16 [%0], {%1,%2};" :: "r"(sa + 128), "r"(ol[8]), "r"(oh[8]) : "memory");
        ho = amax4(amax4(amax4(amax4(ho, ol), ol + 4), oh), oh + 4);
        ho = __hmax2_nan(__hmax2_nan(ho, __habs2(*(const __half2*)&ol[8])), __habs2(*(const __half2*)&oh[8]));
        if (c == 3 && tile == 17) {
          const uint32_t eo = wexp(ho);
          if (lane == 0) atomicMax(&g_amax[16], (unsigned long long)(lds32(sb + A_BAR + 376) + 1) << 32 | eo);
        }
        fence_async();
        if (c >= 0) bar_arrive(13 + wg, 160); else bar_sync(1 + wg, 128);
        ASTAMP(20 + (c & 3));
      }
    }
    ASTAMP(3);
    uint32_t wa[36][4];
    mbar_wait(fullw, 0);
    const uint32_t la = sb + wg * 73728 + ((lane & 7) + ((lane >> 4) << 3)) * 128 + (((2 * w + ((lane >> 3) & 1)) ^ (lane & 7)) << 4);
#pragma unroll
    for (int k = 0; k < 36; k++) ldsm4t(wa[k], la + k * 2048);
    fence_async();
    bar_sync(6, 288);
    ASTAMP(4);
    float own[4] = {0.f, 0.f, 0.f, 0.f};
    uint4 v[3];
    auto fetch = [&](int seg) {
      const uint4* src = g_part + (((seg & 3) * 36 + cta) * 4) * 128 + (tid & 127);
#pragma unroll
      for (int j = 0; j < 3; j++) v[j] = AX & 16 ? make_uint4(0, 0, 0, 0) : ldg_relaxed(src + ((kq + 1 + j) & 3) * 128);
    };
    auto finish = [&](int seg) {
      const uint32_t tagv = ((seg >> 2) + 1) & 3;
      int n = 0;
#pragma unroll 1
      while (!(AX & 16) && __any_sync(0xffffffffu, (v[0].x & 3) != tagv || (v[1].x & 3) != tagv || (v[2].x & 3) != tagv) && ++n < SPIN_LIMIT) {
        if (seg < NAUXSEG - ((TL & 2) ? 2 : 1)) __nanosleep(200);
        fetch(seg);
      }
#pragma unroll
      for (int j = 0; j < 3; j++) {
        own[0] += __uint_as_float(v[j].x & ~3u); own[1] += __uint_as_float(v[j].y); own[2] += __uint_as_float(v[j].z); own[3] += __uint_as_float(v[j].w);
      }
      uint32_t p0 = pack_bf16(own[0], own[1]), p1 = pack_bf16(own[2], own[3]);
      asm volatile("movmatrix.sync.aligned.m8n8.trans.b16 %0, %0;" : "+r"(p0));
      asm volatile("movmatrix.sync.aligned.m8n8.trans.b16 %0, %0;" : "+r"(p1));
      uint32_t* o = (uint32_t*)(out + (size_t)(seg * 32 + kq * 8 + (lane >> 2)) * DM + nsl * 64 + w * 16) + (lane & 3);
      o[0] = p0; o[4] = p1;
    };
    float acc[16];
    auto stream = [&](int sl, int keep) {
      const uint64_t db = make_desc(sb + sl * XT, 16, 1024, 1);
      WG_FENCE();
#pragma unroll
      for (int k = 0; k < 36; k++) wgmma_n32_rs(acc, wa[k][0], wa[k][1], wa[k][2], wa[k][3], db + (k >> 2) * 256 + (k & 3) * 2, k ? 1 : keep);
      WG_COMMIT();
    };
    const uint32_t ex = sb + A_EX + (tid & 127) * 16;
    if (wg == 0) {
#pragma unroll
      for (int i = 0; i < 16; i++) acc[i] = 0.f;
#pragma unroll 1
      for (int seg = 0; seg < NAUXSEG; seg++) {
        const int sl = (seg & 1) * 2;
        mbar_wait(full3 + 8 * sl, (seg >> 1) & 1);
        if (kq == 3) {
          const uint64_t da = make_desc(sb + A_XW, 8192, 1024, 1), de = make_desc(sb + A_XT + (seg & 1) * 4096, 16, 1024, 1);
          WG_FENCE();
#pragma unroll
          for (int j = 0; j < 4; j++) wgmma_n32_ss_tn(acc, da + j * 128, de + j * 2, j);
          WG_COMMIT();
          WG_WAIT(0);
        }
        if (!(AX & 64)) stream(sl, kq == 3);
        bar_arrive(9, 256);
        WG_WAIT(0);
        if (lane == 0) mbar_arrive(empty3 + 8 * sl);
#pragma unroll
        for (int i = 0; i < 4; i++)
          sts128(ex + (seg & 1) * 8192 + i * 2048, __float_as_uint(acc[4 * i]), __float_as_uint(acc[4 * i + 1]), __float_as_uint(acc[4 * i + 2]), __float_as_uint(acc[4 * i + 3]));
        bar_sync(1, 256);
      }
    } else {
#pragma unroll 1
      for (int seg = 0; seg < NAUXSEG; seg++) {
        const int sl = (seg & 1) * 2 + 1;
        mbar_wait(full3 + 8 * sl, (seg >> 1) & 1);
        if (tid == 128) SSTAMP(6, seg);
        bar_sync(9, 256);
        if (!(AX & 64)) stream(sl, 0);
        bar_sync(1, 256);
        fetch(max(seg - 1, 0));
        WG_WAIT(0);
        if (lane == 0) mbar_arrive(empty3 + 8 * sl);
        float nxt[4] = {0.f, 0.f, 0.f, 0.f};
        uint4* dst = g_part + (((seg & 3) * 36 + nsl * 4) * 4 + kq) * 128 + (tid & 127);
#pragma unroll
        for (int j = 0; j < 4; j++) {
          float o[4];
          lds128f(ex + (seg & 1) * 8192 + j * 2048, o);
#pragma unroll
          for (int i = 0; i < 4; i++) { o[i] += acc[4 * j + i]; if (j == kq) nxt[i] = o[i]; }
          if (j != kq && !(AX & 16)) stg_relaxed(dst + j * 512, (__float_as_uint(o[0]) & ~3u) | (((seg >> 2) + 1) & 3), __float_as_uint(o[1]), __float_as_uint(o[2]), __float_as_uint(o[3]));
        }
        if (tid == 128) SSTAMP(7, seg);
        if (seg > 0) finish(seg - 1);
        if (tid == 128) SSTAMP(8, seg);
#pragma unroll
        for (int i = 0; i < 4; i++) own[i] = nxt[i];
        if ((seg & 7) == 6) ASTAMP(5 + (seg >> 3));
      }
      fetch(NAUXSEG - 1);
      finish(NAUXSEG - 1);
    }
    ASTAMP(13);
    TSTAMP(48);
    bar_sync(6, 288);
  }
}

typedef CUresult (*EncodeFn)(CUtensorMap*, CUtensorMapDataType, cuuint32_t, void*, const cuuint64_t*, const cuuint64_t*,
                             const cuuint32_t*, const cuuint32_t*, CUtensorMapInterleave, CUtensorMapSwizzle,
                             CUtensorMapL2promotion, CUtensorMapFloatOOBfill);
static void make_map(EncodeFn enc, CUtensorMap* m, const void* p, int rows, int cols, int box_rows) {
  cuuint64_t dims[2] = {(cuuint64_t)cols, (cuuint64_t)rows};
  cuuint64_t strides[1] = {(cuuint64_t)cols * 2};
  cuuint32_t box[2] = {64, (cuuint32_t)box_rows};
  cuuint32_t es[2] = {1, 1};
  enc(m, CU_TENSOR_MAP_DATA_TYPE_BFLOAT16, 2, (void*)p, dims, strides, box, es, CU_TENSOR_MAP_INTERLEAVE_NONE,
      CU_TENSOR_MAP_SWIZZLE_128B, CU_TENSOR_MAP_L2_PROMOTION_L2_128B, CU_TENSOR_MAP_FLOAT_OOB_FILL_NONE);
}

constexpr int g_poll = POLL_NS;
extern "C" void kernel_launch(void* const* d_in, const int* in_sizes, int n_in, void* d_out, int out_size) {
  const bf16* x = (const bf16*)d_in[0];
  const bf16* wqkvA = (const bf16*)d_in[1];
  const bf16* woA = (const bf16*)d_in[2];
  const bf16* mem0 = (const bf16*)d_in[4];
  const bf16* Wq = (const bf16*)d_in[5];
  const bf16* Wk = (const bf16*)d_in[6];
  const bf16* Wv = (const bf16*)d_in[7];
  const bf16* Wo = (const bf16*)d_in[8];
  const bf16* gate_w = (const bf16*)d_in[10];
  static EncodeFn enc = nullptr;
  static void *pO = nullptr, *pR = nullptr;
  if (!enc) {
    cudaDriverEntryPointQueryResult qr;
    cudaGetDriverEntryPoint("cuTensorMapEncodeTiled", (void**)&enc, cudaEnableDefault, &qr);
    cudaGetSymbolAddress(&pO, g_Ocat);
    cudaGetSymbolAddress(&pR, g_red_raw);
    cudaFuncSetAttribute(rec_kernel, cudaFuncAttributeMaxDynamicSharedMemorySize, SM_TOTAL);
    cudaFuncSetAttribute(aux_kernel, cudaFuncAttributeMaxDynamicSharedMemorySize, A_TOTAL);
  }
  RMaps rm;
  rm.poll = g_poll; rm.out = (bf16*)d_out;
  make_map(enc, &rm.woa, woA, DM, DM, 24);
  {
    cuuint64_t dims[2] = {KCAT, S_LEN}, strides[1] = {KCAT * 2};
    cuuint32_t box[2] = {32, 64}, es[2] = {1, 1};
    enc(&rm.oa, CU_TENSOR_MAP_DATA_TYPE_BFLOAT16, 2, pO, dims, strides, box, es, CU_TENSOR_MAP_INTERLEAVE_NONE,
        CU_TENSOR_MAP_SWIZZLE_NONE, CU_TENSOR_MAP_L2_PROMOTION_NONE, CU_TENSOR_MAP_FLOAT_OOB_FILL_NONE);
  }
  rm.red = (unsigned char*)(((uintptr_t)pR + 262143) & ~(uintptr_t)262143);
  {
    cuuint64_t dims[3] = {64, S_LEN, 9}, strides[2] = {DM * 2, 128};
    cuuint32_t box[3] = {64, 32, 9}, es[3] = {1, 1, 1};
    enc(&rm.x, CU_TENSOR_MAP_DATA_TYPE_BFLOAT16, 3, (void*)x, dims, strides, box, es, CU_TENSOR_MAP_INTERLEAVE_NONE,
        CU_TENSOR_MAP_SWIZZLE_128B, CU_TENSOR_MAP_L2_PROMOTION_L2_128B, CU_TENSOR_MAP_FLOAT_OOB_FILL_NONE);
  }
  make_map(enc, &rm.wq, Wq, DM, 4096, 192);
  make_map(enc, &rm.wk, Wk, DM, 4096, 192);
  make_map(enc, &rm.wv, Wv, DM, 4096, 192);
  make_map(enc, &rm.wo, Wo, 4096, DM, 128);
  AMaps am;
  {
    cuuint32_t es[4] = {1, 1, 1, 1};
    cuuint64_t dx[4] = {64, 2, S_LEN / 2, 9}, sx[3] = {DM * 2, DM * 4, 128};
    cuuint32_t bx[4] = {64, 1, 64, 3};
    enc(&am.x, CU_TENSOR_MAP_DATA_TYPE_BFLOAT16, 4, (void*)x, dx, sx, bx, es, CU_TENSOR_MAP_INTERLEAVE_NONE,
        CU_TENSOR_MAP_SWIZZLE_128B, CU_TENSOR_MAP_L2_PROMOTION_L2_128B, CU_TENSOR_MAP_FLOAT_OOB_FILL_NONE);
    cuuint64_t dw[3] = {DM, DM, 3}, sw[2] = {DM * 6, DM * 2};
    cuuint32_t bw[3] = {64, 16, 3}, bt[3] = {8, 16, 3};
    enc(&am.wa, CU_TENSOR_MAP_DATA_TYPE_BFLOAT16, 3, (void*)wqkvA, dw, sw, bw, es, CU_TENSOR_MAP_INTERLEAVE_NONE,
        CU_TENSOR_MAP_SWIZZLE_128B, CU_TENSOR_MAP_L2_PROMOTION_L2_128B, CU_TENSOR_MAP_FLOAT_OOB_FILL_NONE);
    enc(&am.wt, CU_TENSOR_MAP_DATA_TYPE_BFLOAT16, 3, (void*)wqkvA, dw, sw, bt, es, CU_TENSOR_MAP_INTERLEAVE_NONE,
        CU_TENSOR_MAP_SWIZZLE_NONE, CU_TENSOR_MAP_L2_PROMOTION_NONE, CU_TENSOR_MAP_FLOAT_OOB_FILL_NONE);
    cuuint64_t dz[3] = {KCAT, 2, S_LEN / 2}, sz[2] = {KCAT * 2, KCAT * 4};
    cuuint32_t bz[3] = {72, 1, 57};
    enc(&am.oa, CU_TENSOR_MAP_DATA_TYPE_BFLOAT16, 3, pO, dz, sz, bz, es, CU_TENSOR_MAP_INTERLEAVE_NONE,
        CU_TENSOR_MAP_SWIZZLE_NONE, CU_TENSOR_MAP_L2_PROMOTION_NONE, CU_TENSOR_MAP_FLOAT_OOB_FILL_NONE);
  }
  {
    cuuint64_t dims[3] = {64, S_LEN, KCAT / 64}, strides[2] = {KCAT * 2, 128};
    cuuint32_t box[3] = {64, 32, 9}, es[3] = {1, 1, 1};
    make_map(enc, &am.o, pO, S_LEN, KCAT, 32);
    enc(&am.o3, CU_TENSOR_MAP_DATA_TYPE_BFLOAT16, 3, pO, dims, strides, box, es, CU_TENSOR_MAP_INTERLEAVE_NONE,
        CU_TENSOR_MAP_SWIZZLE_128B, CU_TENSOR_MAP_L2_PROMOTION_L2_128B, CU_TENSOR_MAP_FLOAT_OOB_FILL_NONE);
  }
  make_map(enc, &am.wob, Wo, 4096, DM, 64);
  make_map(enc, &am.woa, woA, DM, DM, 64);

  rec_kernel<<<96, 384, SM_TOTAL, cudaStreamPerThread>>>(rm, x, mem0);
  cudaLaunchConfig_t cfg = {};
  cfg.gridDim = dim3(NAUX); cfg.blockDim = dim3(512); cfg.dynamicSmemBytes = A_TOTAL; cfg.stream = cudaStreamPerThread;
  cudaLaunchAttribute at[1];
  at[0].id = cudaLaunchAttributeProgrammaticStreamSerialization; at[0].val.programmaticStreamSerializationAllowed = 1;
  cfg.attrs = at; cfg.numAttrs = 1;
  if (XP & 16) cfg.numAttrs = 0;
  if (!(XP & 64)) cudaLaunchKernelEx(&cfg, aux_kernel, am, wqkvA, woA, gate_w, (bf16*)d_out);
}
```

```cpp
#include <cuda_runtime.h>
#include <cuda_bf16.h>
#include <cuda_fp16.h>
#include <cuda.h>
#include <stdint.h>

typedef __nv_bfloat16 bf16;

constexpr int S_LEN = 2048, DM = 576, NH = 32, DH = 128, NSEG = 64, KCAT = 4096 + 576;
constexpr int NAUXSEG = NSEG - 2;
constexpr int NAUX = 36;
#define RED_LINE(i) (((i) >> 2) * 4096 + ((i) & 1) * 256 + ((i) & 2) * 512)
#define RED_SLOT(s) (((s) & 1) * 128 + ((s) & 2) * 256)

#define POLL_NS 896
#define NII 18
#define W3PRE 4
#define W3MID 4
#define GF 0
#define B5POS 0
#define NUP 4
#define UPF 1
#define B3Q 9
#define B3F 0
#define GATE 7
#define NTL 2
#define B7R 1
#define VS0 1
#define VS1 0
#define VLATE(w) ((w) == 0 ? VS0 == 1 : (w) == 1 ? VS1 == 1 : false)
#define HOIST 1
#define GDW 0
#define RSLOW 0
#define CSY 0
#define DD 2
#define N12 18
#define N14 18
#define HP 0
#define HL 0
#define WL 1
#define RV 3
#define RET 1
#define TL 6
#define CLR 1
#define RFW 0
#define NIC 0
#define LEAD 0
#define FIN16 1
#define VXG 0
#define NRING 20
#define EXD 0
#define HDLY 0
#define F10 1
#define NPROBE 2
#define QM 0
#define N5 224
#define KP(i) (((i) >> 1) + 4 * ((i) & 1))
#define SPIN_LIMIT (1 << 14)
#define XP 0

__device__ __align__(1024) bf16 g_Ocat[S_LEN * KCAT];
__device__ __align__(1024) unsigned char g_red_raw[2 * 262144];
constexpr int HINT_OFF = 2048;
__device__ __align__(16) float g_gate[S_LEN];
__device__ __align__(128) uint4 g_stats[96 * 2];
__device__ unsigned g_epoch;
__device__ unsigned g_epoch2;
__device__ unsigned g_ocnt[NSEG * 32];
__device__ unsigned g_abar[3 * 32];
__device__ unsigned long long g_amax[2 * 16];
__device__ unsigned g_scnt[NSEG * 32 * 8];
__device__ __align__(1024) unsigned char g_seg[NRING * 96 * 10240];
__device__ unsigned g_used[NH * 32];
__device__ __align__(1024) uint4 g_part[4 * 36 * 4 * 128];
__device__ int g_err;
#define TSTAMP(i)
#define PROF(idx)
#define PROFP(idx)
#define RSTAMP(k)
#define STAMP(idx)
#define ASTAMP(idx)
#define SSTAMP(k, seg)
#define WSTAMP(idx)

#define DI __device__ __forceinline__
DI uint32_t smem_u32(const void* p) { return (uint32_t)__cvta_generic_to_shared(p); }
DI uint32_t clock32() { uint32_t c; asm volatile("mov.u32 %0, %%clock;" : "=r"(c) :: "memory"); return c; }
DI uint32_t gtime() { uint32_t c; asm volatile("mov.u32 %0, %%globaltimer_lo;" : "=r"(c) :: "memory"); return c; }
DI uint32_t ldg_relaxed32(const void* p) { uint32_t v; asm volatile("ld.relaxed.gpu.global.b32 %0, [%1];" : "=r"(v) : "l"(p) : "memory"); return v; }
DI uint32_t ldg_acquire32(const void* p) { uint32_t v; asm volatile("ld.acquire.gpu.global.b32 %0, [%1];" : "=r"(v) : "l"(p) : "memory"); return v; }
DI void stg_relaxed32(void* p, uint32_t v) { asm volatile("st.relaxed.gpu.global.b32 [%0], %1;" :: "l"(p), "r"(v) : "memory"); }
DI int head_id() { int c; asm volatile("mov.u32 %0, %%clusterid.x;" : "=r"(c)); return c; }
DI uint32_t mapa(uint32_t a, uint32_t r) { uint32_t o; asm("mapa.shared::cluster.u32 %0, %1, %2;" : "=r"(o) : "r"(a), "r"(r)); return o; }
DI void cluster_arrive() { asm volatile("barrier.cluster.arrive.relaxed.aligned;" ::: "memory"); }
DI void cluster_wait() { asm volatile("barrier.cluster.wait.aligned;" ::: "memory"); }
DI void cluster_sync() { asm volatile("barrier.cluster.arrive.release.aligned;\nbarrier.cluster.wait.acquire.aligned;" ::: "memory"); }
DI void mbar_init(uint32_t b, uint32_t c) { asm volatile("mbarrier.init.shared::cta.b64 [%0], %1;" :: "r"(b), "r"(c) : "memory"); }
DI void mbar_expect(uint32_t b, uint32_t tx) { asm volatile("mbarrier.arrive.expect_tx.shared::cta.b64 _, [%0], %1;" :: "r"(b), "r"(tx) : "memory"); }
DI void mbar_arrive(uint32_t b) { asm volatile("mbarrier.arrive.shared::cta.b64 _, [%0];" :: "r"(b) : "memory"); }
DI void mbar_wait(uint32_t b, uint32_t par) {
  asm volatile("{\n.reg .pred p;\n.reg .u32 n, q;\nmov.u32 n, 0;\n"
               "WL: add.u32 n, n, 1;\nshr.u32 q, n, 12;\nxor.b32 q, q, %1;\n"
               "mbarrier.try_wait.parity.shared::cta.b64 p, [%0], q;\n@!p bra.uni WL;\n}"
               :: "r"(b), "r"(par) : "memory");
}
DI void mbar_wait_fast(uint32_t b, uint32_t par) {
  asm volatile("{\n.reg .pred p;\n.reg .u32 n, q;\nmbarrier.try_wait.parity.shared::cta.b64 p, [%0], %1;\n@p bra.uni WD;\nmov.u32 n, 0;\n"
               "WL: add.u32 n, n, 1;\nshr.u32 q, n, 12;\nxor.b32 q, q, %1;\n"
               "mbarrier.try_wait.parity.shared::cta.b64 p, [%0], q;\n@!p bra.uni WL;\nWD:\n}"
               :: "r"(b), "r"(par) : "memory");
}
DI void wait_until(uint32_t t) {
  const uint32_t now = gtime();
  t = min(t, now + 8192);
  asm volatile("{\n.reg .pred p;\n.reg .u32 c;\nTL: mov.u32 c, %%globaltimer_lo;\nsetp.lt.u32 p, c, %0;\n@p bra.uni TL;\n}" :: "r"(t) : "memory");
}
#define PIN(v) v = __shfl_xor_sync(0xffffffffu, v, 0)
#define SCHED_FENCE(k) asm volatile("{\n.reg .pred p;\nsetp.eq.u32 p, %0, %1;\n@p exit;\n}" :: "r"(fence_reg), "r"(k) : "memory")
#define MEM_ORDER(k) asm volatile("{\n.reg .pred p;\nsetp.eq.u32 p, %0, %1;\n@p st.shared.u32 [%0], %0;\n}" :: "r"(fence_reg), "r"(k + 64) : "memory")
DI void bar_sync(int id, int n) { asm volatile("bar.sync %0, %1;" :: "r"(id), "r"(n) : "memory"); }
DI void bar_arrive(int id, int n) { asm volatile("bar.arrive %0, %1;" :: "r"(id), "r"(n) : "memory"); }
DI void fence_async() { asm volatile("fence.proxy.async.shared::cta;" ::: "memory"); }
DI void st_async4(uint32_t a, uint32_t x, uint32_t y, uint32_t z, uint32_t w, uint32_t mb) {
  asm volatile("st.async.weak.shared::cluster.mbarrier::complete_tx::bytes.v4.b32 [%0], {%1,%2,%3,%4}, [%5];"
               :: "r"(a), "r"(x), "r"(y), "r"(z), "r"(w), "r"(mb) : "memory");
}
DI void st_async2(uint32_t a, uint32_t x, uint32_t y, uint32_t mb) {
  asm volatile("st.async.weak.shared::cluster.mbarrier::complete_tx::bytes.v2.b32 [%0], {%1,%2}, [%3];"
               :: "r"(a), "r"(x), "r"(y), "r"(mb) : "memory");
}
DI void sts32(uint32_t a, uint32_t x) { asm volatile("st.shared.b32 [%0], %1;" :: "r"(a), "r"(x) : "memory"); }
DI void sts64(uint32_t a, uint32_t x, uint32_t y) { asm volatile("st.shared.v2.b32 [%0], {%1,%2};" :: "r"(a), "r"(x), "r"(y) : "memory"); }
DI void sts128(uint32_t a, uint32_t x, uint32_t y, uint32_t z, uint32_t w) {
  asm volatile("st.shared.v4.b32 [%0], {%1,%2,%3,%4};" :: "r"(a), "r"(x), "r"(y), "r"(z), "r"(w) : "memory");
}
DI uint32_t lds32(uint32_t a) { uint32_t x; asm volatile("ld.shared.b32 %0, [%1];" : "=r"(x) : "r"(a) : "memory"); return x; }
DI void lds64(uint32_t a, uint32_t& x, uint32_t& y) { asm volatile("ld.shared.v2.b32 {%0,%1}, [%2];" : "=r"(x), "=r"(y) : "r"(a) : "memory"); }
DI void lds128(uint32_t a, uint32_t* r) {
  asm volatile("ld.shared.v4.b32 {%0,%1,%2,%3}, [%4];" : "=r"(r[0]), "=r"(r[1]), "=r"(r[2]), "=r"(r[3]) : "r"(a) : "memory");
}
DI void lds128f(uint32_t a, float* r) {
  asm volatile("ld.shared.v4.f32 {%0,%1,%2,%3}, [%4];" : "=f"(r[0]), "=f"(r[1]), "=f"(r[2]), "=f"(r[3]) : "r"(a) : "memory");
}
DI void lds64f(uint32_t a, float* r) { asm volatile("ld.shared.v2.f32 {%0,%1}, [%2];" : "=f"(r[0]), "=f"(r[1]) : "r"(a) : "memory"); }
DI void ldsm4t(uint32_t* r, uint32_t a) {
  asm volatile("ldmatrix.sync.aligned.m8n8.x4.trans.shared.b16 {%0,%1,%2,%3}, [%4];"
               : "=r"(r[0]), "=r"(r[1]), "=r"(r[2]), "=r"(r[3]) : "r"(a) : "memory");
}
DI void ldsm4t_in(uint32_t* r, uint32_t a, uint32_t t) {
  asm volatile("{\n.reg .pred p;\nsetp.ne.u32 p, %5, 0;\n@p ldmatrix.sync.aligned.m8n8.x4.trans.shared.b16 {%0,%1,%2,%3}, [%4];\n}"
               : "+r"(r[0]), "+r"(r[1]), "+r"(r[2]), "+r"(r[3]) : "r"(a), "r"(t) : "memory");
}
DI void lds128_in(uint32_t* r, uint32_t a, uint32_t t) {
  asm volatile("{\n.reg .pred p;\nsetp.ne.u32 p, %5, 0;\n@p ld.shared.v4.b32 {%0,%1,%2,%3}, [%4];\n}"
               : "+r"(r[0]), "+r"(r[1]), "+r"(r[2]), "+r"(r[3]) : "r"(a), "r"(t) : "memory");
}
DI void ldsm2t_in(uint32_t* r, uint32_t a, uint32_t t) {
  asm volatile("{\n.reg .pred p;\nsetp.ne.u32 p, %3, 0;\n@p ldmatrix.sync.aligned.m8n8.x2.trans.shared.b16 {%0,%1}, [%2];\n}" : "+r"(r[0]), "+r"(r[1]) : "r"(a), "r"(t) : "memory");
}
DI void reserve2(uint32_t* r) { asm volatile("{\n.reg .u64 t;\nmov.u64 t, %%clock64;\nmov.b64 {%0, %1}, t;\n}" : "=r"(r[0]), "=r"(r[1])); }
DI void scale_sum(float& x, float& y, float s, uint32_t t) {
  asm volatile("{\n.reg .pred p;\nsetp.ne.u32 p, %2, 0;\n@p mul.f32 %0, %0, %1;\n}" : "+f"(y) : "f"(s), "r"(t));
  asm volatile("{\n.reg .pred p;\nsetp.ne.u32 p, %3, 1;\n@p fma.rn.f32 %0, %0, %1, %2;\n}" : "+f"(x) : "f"(s), "f"(y), "r"(t));
}
DI void ldsm4(uint32_t* r, uint32_t a) {
  asm volatile("ldmatrix.sync.aligned.m8n8.x4.shared.b16 {%0,%1,%2,%3}, [%4];"
               : "=r"(r[0]), "=r"(r[1]), "=r"(r[2]), "=r"(r[3]) : "r"(a) : "memory");
}
DI void st_async1(uint32_t a, uint32_t x, uint32_t mb) {
  asm volatile("st.async.weak.shared::cluster.mbarrier::complete_tx::bytes.b32 [%0], %1, [%2];" :: "r"(a), "r"(x), "r"(mb) : "memory");
}
DI void stsm4(uint32_t a, uint32_t x, uint32_t y, uint32_t z, uint32_t w) {
  asm volatile("stmatrix.sync.aligned.m8n8.x4.shared.b16 [%0], {%1,%2,%3,%4};" :: "r"(a), "r"(x), "r"(y), "r"(z), "r"(w) : "memory");
}
DI void stsm4t(uint32_t a, uint32_t x, uint32_t y, uint32_t z, uint32_t w) {
  asm volatile("stmatrix.sync.aligned.m8n8.x4.trans.shared.b16 [%0], {%1,%2,%3,%4};" :: "r"(a), "r"(x), "r"(y), "r"(z), "r"(w) : "memory");
}
DI uint32_t pack_bf16(float lo, float hi) { uint32_t r; asm("cvt.rn.bf16x2.f32 %0, %1, %2;" : "=r"(r) : "f"(hi), "f"(lo)); return r; }
DI uint32_t pack_f16(float lo, float hi) { uint32_t r; asm("cvt.rn.f16x2.f32 %0, %1, %2;" : "=r"(r) : "f"(hi), "f"(lo)); return r; }
DI float ex2(float x) { float y; asm("ex2.approx.ftz.f32 %0, %1;" : "=f"(y) : "f"(x)); return y; }
DI float rcp(float x) { float y; asm("rcp.approx.ftz.f32 %0, %1;" : "=f"(y) : "f"(x)); return y; }
DI float bf_lo(uint32_t x) { return __uint_as_float(x << 16); }
DI float bf_hi(uint32_t x) { return __uint_as_float(x & 0xffff0000u); }
DI void mma16816(float* d, const uint32_t* a, uint32_t b0, uint32_t b1) {
  asm volatile("mma.sync.aligned.m16n8k16.row.col.f32.bf16.bf16.f32 {%0,%1,%2,%3}, {%4,%5,%6,%7}, {%8,%9}, {%0,%1,%2,%3};"
               : "+f"(d[0]), "+f"(d[1]), "+f"(d[2]), "+f"(d[3]) : "r"(a[0]), "r"(a[1]), "r"(a[2]), "r"(a[3]), "r"(b0), "r"(b1));
}
DI void mma16816z(float* d, const uint32_t* a, uint32_t b0, uint32_t b1) {
  asm volatile("mma.sync.aligned.m16n8k16.row.col.f32.bf16.bf16.f32 {%0,%1,%2,%3}, {%4,%5,%6,%7}, {%8,%9}, {%10,%10,%10,%10};"
               : "=f"(d[0]), "=f"(d[1]), "=f"(d[2]), "=f"(d[3]) : "r"(a[0]), "r"(a[1]), "r"(a[2]), "r"(a[3]), "r"(b0), "r"(b1), "f"(0.f));
}
DI void mma1688z(float* d, uint32_t a0, uint32_t a1, uint32_t b0) {
  asm volatile("mma.sync.aligned.m16n8k8.row.col.f32.bf16.bf16.f32 {%0,%1,%2,%3}, {%4,%5}, {%6}, {%7,%7,%7,%7};"
               : "=f"(d[0]), "=f"(d[1]), "=f"(d[2]), "=f"(d[3]) : "r"(a0), "r"(a1), "r"(b0), "f"(0.f));
}
DI void mma1688(float* d, uint32_t a0, uint32_t a1, uint32_t b0) {
  asm volatile("mma.sync.aligned.m16n8k8.row.col.f32.bf16.bf16.f32 {%0,%1,%2,%3}, {%4,%5}, {%6}, {%0,%1,%2,%3};"
               : "+f"(d[0]), "+f"(d[1]), "+f"(d[2]), "+f"(d[3]) : "r"(a0), "r"(a1), "r"(b0));
}
DI void ldsm2t(uint32_t* r, uint32_t a) {
  asm volatile("ldmatrix.sync.aligned.m8n8.x2.trans.shared.b16 {%0,%1}, [%2];" : "=r"(r[0]), "=r"(r[1]) : "r"(a) : "memory");
}
DI uint32_t add_bf16(uint32_t a, uint32_t b) { uint32_t r; asm("add.rn.bf16x2 %0, %1, %2;" : "=r"(r) : "r"(a), "r"(b)); return r; }
DI uint32_t mul_bf16(uint32_t a, uint32_t b) { uint32_t r; asm("mul.rn.bf16x2 %0, %1, %2;" : "=r"(r) : "r"(a), "r"(b)); return r; }
DI uint64_t make_desc(uint32_t addr, uint32_t lbo, uint32_t sbo, uint32_t swz) {
  return (uint64_t)((addr & 0x3FFFF) >> 4) | ((uint64_t)(lbo >> 4) << 16) | ((uint64_t)(sbo >> 4) << 32) | ((uint64_t)swz << 62);
}
DI uint64_t desc_at(uint32_t a16, uint32_t lbo, uint32_t sbo, uint32_t swz) {
  uint64_t d; asm("mov.b64 %0, {%1, %2};" : "=l"(d) : "r"(a16 + ((lbo >> 4) << 16)), "r"((sbo >> 4) | (swz << 30)));
  return d;
}
#define WG_FENCE() asm volatile("wgmma.fence.sync.aligned;" ::: "memory")
#define WG_COMMIT() asm volatile("wgmma.commit_group.sync.aligned;" ::: "memory")
#define WG_WAIT(n) asm volatile("wgmma.wait_group.sync.aligned %0;" :: "n"(n) : "memory")
#define ACC8(d, o) "+f"(d[o]), "+f"(d[o + 1]), "+f"(d[o + 2]), "+f"(d[o + 3]), "+f"(d[o + 4]), "+f"(d[o + 5]), "+f"(d[o + 6]), "+f"(d[o + 7])
DI void wgmma_n32_rs(float* d, uint32_t a0, uint32_t a1, uint32_t a2, uint32_t a3, uint64_t db, int acc) {
  asm volatile("{\n.reg .pred p;\nsetp.ne.b32 p, %21, 0;\n"
               "wgmma.mma_async.sync.aligned.m64n32k16.f32.bf16.bf16 {%0,%1,%2,%3,%4,%5,%6,%7,%8,%9,%10,%11,%12,%13,%14,%15}, "
               "{%16,%17,%18,%19}, %20, p, 1, 1, 0;\n}\n"
               : ACC8(d, 0), ACC8(d, 8) : "r"(a0), "r"(a1), "r"(a2), "r"(a3), "l"(db), "r"(acc));
}
template <int TA>
DI void wgmma_n32_ss(float* d, uint64_t da, uint64_t db, int acc) {
  asm volatile("{\n.reg .pred p;\nsetp.ne.b32 p, %18, 0;\n"
               "wgmma.mma_async.sync.aligned.m64n32k16.f32.bf16.bf16 {%0,%1,%2,%3,%4,%5,%6,%7,%8,%9,%10,%11,%12,%13,%14,%15}, "
               "%16, %17, p, 1, 1, %19, 1;\n}\n"
               : ACC8(d, 0), ACC8(d, 8) : "l"(da), "l"(db), "r"(acc), "n"(TA));
}
DI void tma_load(uint32_t dst, const CUtensorMap* m, int c0, int c1, uint32_t mb) {
  asm volatile("cp.async.bulk.tensor.2d.shared::cluster.global.mbarrier::complete_tx::bytes [%0], [%1, {%3, %4}], [%2];"
               :: "r"(dst), "l"(m), "r"(mb), "r"(c0), "r"(c1) : "memory");
}
DI void tma_load3(uint32_t dst, const CUtensorMap* m, int row, uint32_t mb) {
  asm volatile("cp.async.bulk.tensor.3d.shared::cluster.global.mbarrier::complete_tx::bytes [%0], [%1, {%3, %4, %3}], [%2];"
               :: "r"(dst), "l"(m), "r"(mb), "r"(0), "r"(row) : "memory");
}
DI bool elect_one() {
  uint32_t p;
  asm volatile("{\n.reg .pred p;\nelect.sync _|p, 0xffffffff;\nselp.u32 %0, 1, 0, p;\n}" : "=r"(p));
  return p;
}
DI void bulk_s2s(uint32_t dst, uint32_t src, uint32_t bytes, uint32_t mb) {
  asm volatile("cp.async.bulk.shared::cluster.shared::cta.mbarrier::complete_tx::bytes [%0], [%1], %2, [%3];"
               :: "r"(dst), "r"(src), "r"(bytes), "r"(mb) : "memory");
}
DI void tma_prefetch(const CUtensorMap* m, int c0, int c1) {
  asm volatile("cp.async.bulk.prefetch.tensor.2d.L2.global.tile [%0, {%1, %2}];" :: "l"(m), "r"(c0), "r"(c1) : "memory");
}
DI void tma_store(const CUtensorMap* m, uint32_t src, int c0, int c1) {
  asm volatile("cp.async.bulk.tensor.2d.global.shared::cta.bulk_group [%0, {%2, %3}], [%1];" :: "l"(m), "r"(src), "r"(c0), "r"(c1) : "memory");
}
DI uint4 ldg_relaxed(const void* p) {
  uint4 v;
  asm volatile("ld.relaxed.gpu.global.v4.b32 {%0,%1,%2,%3}, [%4];" : "=r"(v.x), "=r"(v.y), "=r"(v.z), "=r"(v.w) : "l"(p) : "memory");
  return v;
}
DI void stg_relaxed(void* p, uint32_t x, uint32_t y, uint32_t z, uint32_t w) {
  asm volatile("st.relaxed.gpu.global.v4.b32 [%0], {%1,%2,%3,%4};" :: "l"(p), "r"(x), "r"(y), "r"(z), "r"(w) : "memory");
}
DI void red_f16x8(void* p, uint32_t x, uint32_t y, uint32_t z, uint32_t w) {
  asm volatile("red.relaxed.gpu.global.add.noftz.v4.f16x2 [%0], {%1,%2,%3,%4};" :: "l"(p), "r"(x), "r"(y), "r"(z), "r"(w) : "memory");
}
DI void sq_acc(uint32_t& a, uint32_t x) { asm("fma.rn.bf16x2 %0, %1, %1, %0;" : "+r"(a) : "r"(x)); }
DI __half2 amax4(__half2 h, const uint32_t* v) {
  h = __hmax2_nan(__hmax2_nan(h, __habs2(*(const __half2*)&v[0])), __habs2(*(const __half2*)&v[1]));
  return __hmax2_nan(__hmax2_nan(h, __habs2(*(const __half2*)&v[2])), __habs2(*(const __half2*)&v[3]));
}
DI uint32_t wexp(__half2 h) { const uint32_t u = *(const uint32_t*)&h; return __reduce_max_sync(0xffffffffu, max((u >> 16) & 0x7fffu, u & 0x7fffu)) >> 7; }
DI float max10(const float* a) {
  return fmaxf(fmaxf(fmaxf(fmaxf(a[0], a[1]), fmaxf(a[2], a[3])), fmaxf(fmaxf(a[4], a[5]), fmaxf(a[6], a[7]))), fmaxf(a[8], a[9]));
}
DI float quad_max(float m) {
  return fmaxf(fmaxf(m, __shfl_xor_sync(0xffffffffu, m, 1)), fmaxf(__shfl_xor_sync(0xffffffffu, m, 2), __shfl_xor_sync(0xffffffffu, m, 3)));
}
DI float warp_sum(float v) {
#pragma unroll
  for (int o = 16; o; o >>= 1) v += __shfl_xor_sync(0xffffffffu, v, o);
  return v;
}

constexpr int SM_WO3 = 0;
constexpr int SM_X = 16384;
constexpr int XT = 36864;
constexpr int SM_EXP = 126976;
constexpr int SEGB = 10240;
constexpr int SM_BLK = SM_EXP + 8192;
constexpr int SM_VC = SM_BLK + 4 * SEGB;
constexpr int SM_PART = SM_VC + 16384;
constexpr int SM_QM = SM_PART + 4096;
constexpr int SM_E = SM_QM + 1024;
constexpr int SM_VM = SM_E + 1536;
constexpr int SM_OB = SM_VM + 2048;
constexpr int SM_FB = SM_OB + 2048;
constexpr int SM_STAGE = SM_X + XT;
constexpr int SM_MISC = 210944;
constexpr int SM_WOST = 212992;
constexpr int SM_MEM = SM_WOST;
constexpr int SM_MAX = SM_MEM + 11264;
#define MEM_BLK(q) ((q) / 3 * 4096 + (q) % 3 * 1024)
constexpr int SM_TOTAL = 229376;
constexpr int MB_W = SM_MISC;
constexpr int MB_WO = SM_MISC + 24;
constexpr int MB_WO3 = SM_MISC + 32;
constexpr int MB_X = SM_MISC + 40;
constexpr int MB_S = SM_MISC + 64;
constexpr int MB_F = SM_MISC + 72;
constexpr int MB_VX = SM_MISC + 80;
constexpr int SC_FPAR = SM_MISC + 136;
constexpr int SC_DEAD = SM_MISC + 96;
constexpr int SC_UNSC = SM_MISC + 112;
constexpr int SC_EPOCH = SM_MISC + 128;
constexpr int SC_EXPW = SM_MISC + 132;
constexpr int SC_ONES = SM_MISC + 144;
constexpr int SC_SS = SM_MISC + 160;
constexpr int SC_LAT = SM_MISC + 224;
constexpr int MB_T = SM_MISC + 232;
constexpr int T_SX = SM_X + XT;
constexpr int T_OB = SM_X + 2 * XT;
constexpr int T_WA = T_OB + 16384;
constexpr int T_OA = T_WA + 9216;
constexpr int T_G = T_OA + 4096;
constexpr int T_P = T_G + 512;
constexpr int T_UN = T_G + 256;
constexpr int T_RED = 131072;
constexpr int SC_XMAX = SM_MISC + 256;
constexpr int SC_PROF = 229376;

constexpr float SM_SCALE = 0.08838834764831845f;
constexpr float LOG2E = 1.4426950408889634f;
constexpr float E_LIM = 20.f;

template <bool B> struct BoolC { static constexpr bool value = B; };
struct RMaps { CUtensorMap x, wq, wk, wv, wo, woa, oa; unsigned char* red; bf16* out; uint32_t poll; };

DI uint32_t latest_hint(uint32_t h, uint32_t d, int s) {
  const uint32_t x = (((h | 0xc0c0c0c0u) - ((d >> 5) & 63) * 0x01010101u) & 0x3f3f3f3fu) | ((h ^ (((s >> 2) + 1) & 3) * 0x40404040u) & 0xc0c0c0c0u);
  const uint32_t y = __vmaxu2(x & 0x00ff00ffu, (x >> 8) & 0x00ff00ffu);
  return __reduce_max_sync(0xffffffffu, max(y & 0xffffu, y >> 16));
}
DI uint32_t near_half(uint32_t sb) {
  uint32_t a, b; lds64(sb + SC_LAT, a, b);
  return a > b;
}

template <int RT, int K0, int K1, bool D32 = false, int BAR = 0, int KB = 18>
DI void xproj(float* acc, const uint32_t (&wa)[2][18][4], uint64_t xd) {
  if (XP & 1) return;
  WG_FENCE();
#pragma unroll
  for (int k = K0; k < ((XP & 128) ? K0 + 1 : K1); k++)
  {
    uint64_t d = xd + (uint64_t)(((k >> 1) * 4096 + (k & 1) * 32) >> 4);
    if (D32) asm("mov.b64 %0, {%1, %2};" : "=l"(d) : "r"((uint32_t)xd + (((k >> 1) * 4096 + (k & 1) * 32) >> 4)), "r"((uint32_t)(xd >> 32)));
    wgmma_n32_rs(acc, wa[RT][k][0], wa[RT][k][1], wa[RT][k][2], wa[RT][k][3], d, k != 0);
    if (BAR && k == KB - 1 && KB < 18) bar_arrive(BAR, 256);
  }
  WG_COMMIT();
}

DI void seg_store(int seg, uint32_t sb, uint32_t off, uint32_t bytes) {
  asm volatile("cp.async.bulk.global.shared::cta.bulk_group [%0], [%1], %2;"
               :: "l"(g_seg + ((size_t)(seg % NRING) * 96 + blockIdx.x) * SEGB + off), "r"(sb + SM_BLK + (seg & 3) * SEGB + off), "r"(bytes) : "memory");
  asm volatile("cp.async.bulk.commit_group;" ::: "memory");
}
DI void seg_publish(int seg) {
  asm volatile("cp.async.bulk.wait_group 0;" ::: "memory");
  asm volatile("red.relaxed.gpu.global.add.u32 [%0], 1;" :: "l"(&g_scnt[(seg * 32 + blockIdx.x / 3) * 8]) : "memory");
  SSTAMP(10, seg);
}

#define NAP 64
DI uint32_t movm(uint32_t x) { uint32_t r; asm volatile("movmatrix.sync.aligned.m8n8.trans.b16 %0, %1;" : "=r"(r) : "r"(x)); return r; }
DI bool wait_count(const unsigned* p, unsigned target, bool nap = true) {
  int n = 0;
  unsigned v;
  while (true) {
    asm volatile("ld.acquire.gpu.global.b32 %0, [%1];" : "=r"(v) : "l"(p) : "memory");
    if ((int)(v - target) >= 0 || ++n > SPIN_LIMIT) break;
    if (nap) __nanosleep(NAP);
  }
  return n;
}
#define PACE 1200
#define PORD 0
DI void load_weights(uint32_t sb, const RMaps& tm, uint32_t rank, int c) {
  const int h = blockIdx.x / 3;
  if (c < 3) {
    mbar_expect(sb + MB_W + 8 * c, 49152);
    tma_load(sb + SM_STAGE + c * 49152, rank < 2 ? &tm.wk : &tm.wv, h * DH + (rank == 1 ? 64 : 0), c * 192, sb + MB_W + 8 * c);
    tma_load(sb + SM_STAGE + c * 49152 + 24576, rank < 2 ? &tm.wq : &tm.wv, h * DH + (rank == 0 ? 0 : 64), c * 192, sb + MB_W + 8 * c);
  } else {
    tma_prefetch(&tm.wo, rank * 192, h * DH);
    mbar_expect(sb + MB_WO, 16384);
    mbar_expect(sb + MB_WO3, 32768);
    tma_load(sb + SM_WOST, &tm.wo, rank * 192 + 64, h * DH, sb + MB_WO3);
    tma_load(sb + SM_WO3, &tm.wo, rank * 192 + 128, h * DH, sb + MB_WO3);
  }
}

DI void tail_attention(const uint32_t sb, const uint32_t rank, const int w, const int lane, const int sg, const int bar) {
  const int m = lane >> 3, g = lane >> 2, t = lane & 3;
  const uint32_t l16 = sb + lane * 16, src = l16 + T_SX + sg * 10240 + w * 1280;
  if (rank < 2) {
    const uint32_t base = l16 + SM_BLK + (2 + sg) * SEGB, dst = src + rank * 5120;
    uint32_t qb[2][4];
    ldsm4t(qb[0], base + w * 1024); ldsm4t(qb[1], base + w * 1024 + 512);
#pragma unroll
    for (int j = 0; j < 3; j++) {
      uint32_t kb[4][4];
      float c[4][4];
      const uint32_t ka = base + 4096 + j * 2048 + (m & 1) * (j == 2 ? 128 : 896) - (m >> 1) * 128;
#pragma unroll
      for (int k = 0; k < 4; k += j == 2 ? 2 : 1) ldsm4t(kb[k], ka + k * 256);
      mma16816z(c[0], kb[0], qb[0][0], qb[0][1]); mma16816z(c[1], kb[j == 2 ? 0 : 1], qb[0][2], qb[0][3]);
      mma16816z(c[2], kb[2], qb[1][0], qb[1][1]); mma16816z(c[3], kb[j == 2 ? 2 : 3], qb[1][2], qb[1][3]);
      uint32_t r[4];
#pragma unroll
      for (int i = 0; i < (j == 2 ? 2 : 4); i++) r[i] = __float_as_uint((c[0][i] + c[1][j == 2 ? i + 2 : i]) + (c[2][i] + c[3][j == 2 ? i + 2 : i]));
#pragma unroll
      for (int d = 0; d < 2; d++) {
        const uint32_t to = d ? 2 : rank ^ 1, mb = mapa(sb + MB_T + 8 + 8 * sg, to);
        if (j < 2) st_async4(mapa(dst + j * 512, to), r[0], r[1], r[2], r[3], mb);
        else st_async2(mapa(dst + 1024 - lane * 8, to), r[0], r[1], mb);
      }
      if (j < 2) sts128(dst + j * 512, r[0], r[1], r[2], r[3]); else sts64(dst + 1024 - lane * 8, r[0], r[1]);
    }
  }
  TSTAMP(50 + 2 * sg);
  uint32_t vx[4][4], vm[4];
  const uint32_t va = l16 + (rank < 2 ? SM_VC + sg * 8192 : SM_BLK + (2 + sg) * SEGB) + w * 1024 + (m & 1) * 384 - (m >> 1) * 128;
#pragma unroll
  for (int i = 0; i < 4; i++) ldsm4(vx[i], va + (i & 1) * 4096 + (i >> 1) * 256);
  if (sg && rank < 2) mbar_wait(sb + MB_T, 0);
  lds128(l16 + (sg ? SM_FB : SM_VM) + w * 512, vm);
  float a[10], b[10];
  mbar_wait(sb + MB_T + 8 + 8 * sg, 0);
  TSTAMP(58 + 2 * sg);
  lds128f(src, a); lds128f(src + 512, a + 4); lds64f(src + 1024 - lane * 8, a + 8);
  lds128f(src + 5120, b); lds128f(src + 5632, b + 4); lds64f(src + 6144 - lane * 8, b + 8);
#pragma unroll
  for (int i = 0; i < 10; i++) {
    a[i] = (a[i] + b[i]) * (SM_SCALE * LOG2E);
    if (i < 8 && (i >> 1) * 8 + g > w * 8 + 2 * t + (i & 1)) a[i] = -1.0e9f * LOG2E;
  }
  float m0 = fmaxf(fmaxf(fmaxf(a[0], a[2]), fmaxf(a[4], a[6])), a[8]), m1 = fmaxf(fmaxf(fmaxf(a[1], a[3]), fmaxf(a[5], a[7])), a[9]);
#pragma unroll
  for (int o = 4; o < 32; o <<= 1) { m0 = fmaxf(m0, __shfl_xor_sync(0xffffffffu, m0, o)); m1 = fmaxf(m1, __shfl_xor_sync(0xffffffffu, m1, o)); }
#pragma unroll
  for (int i = 0; i < 10; i++) a[i] = ex2(a[i] - (i & 1 ? m1 : m0));
  float s0 = ((a[0] + a[2]) + (a[4] + a[6])) + a[8], s1 = ((a[1] + a[3]) + (a[5] + a[7])) + a[9];
#pragma unroll
  for (int o = 4; o < 32; o <<= 1) { s0 += __shfl_xor_sync(0xffffffffu, s0, o); s1 += __shfl_xor_sync(0xffffffffu, s1, o); }
  s0 = rcp(s0); s1 = rcp(s1);
#pragma unroll
  for (int i = 0; i < 5; i++) sts32(sb + T_P + sg * 2560 + w * 640 + i * 128 + lane * 4, pack_bf16(a[2 * i] * s0, a[2 * i + 1] * s1));
  mbar_wait(sb + MB_WO, 1);
  bar_sync(bar, 128);
  TSTAMP(59 + 2 * sg);
#pragma unroll
  for (int j = 0; j < 4; j++) {
    uint32_t p[5];
    float o0[4], o1[4], f[2];
    lds64f(sb + T_G + sg * 128 + j * 32 + t * 8, f);
    f[0] = 1.f - f[0]; f[1] = 1.f - f[1];
    ldsm4t(p, l16 + T_P + sg * 2560 + j * 640);
    asm volatile("ldmatrix.sync.aligned.m8n8.x1.trans.shared.b16 {%0}, [%1];" : "=r"(p[4]) : "r"(l16 + T_P + sg * 2560 + j * 640 + 512) : "memory");
    mma16816z(o0, vx[0], p[0], p[1]); mma16816z(o1, vx[1], p[0], p[1]);
    mma16816(o0, vx[2], p[2], p[3]); mma16816(o1, vx[3], p[2], p[3]);
    mma1688(o0, vm[0], vm[1], p[4]); mma1688(o1, vm[2], vm[3], p[4]);
    stsm4(l16 + T_OB + sg * 8192 + j * 2048 + w * 512, pack_bf16(o0[0] * f[0], o0[1] * f[1]), pack_bf16(o0[2] * f[0], o0[3] * f[1]),
          pack_bf16(o1[0] * f[0], o1[1] * f[1]), pack_bf16(o1[2] * f[0], o1[3] * f[1]));
  }
}

DI void proj_role(const uint32_t sb, const RMaps& tm, const uint32_t rank, const int wg, const int w, const int lane) {
  const bool qk = rank < 2;
  uint32_t wa[2][18][4];
  {
    const int rr = (lane & 7) + ((lane >> 4) << 3);
    const uint32_t col = ((2 * w + ((lane >> 3) & 1)) ^ (lane & 7)) << 4;
    float ss = 0.f;
#pragma unroll
    for (int c = 0; c < 3; c++) {
      mbar_wait(sb + MB_W + 8 * c, 0);
      if (threadIdx.x == 0) SSTAMP(11, c);
#pragma unroll
      for (int rt = 0; rt < 2; rt++)
#pragma unroll
        for (int k = 0; k < 6; k++)
          ldsm4t(wa[rt][c * 6 + k], sb + SM_STAGE + c * 49152 + (rt ^ wg) * 24576 + (64 * (k >> 1) + 32 * wg + 16 * (k & 1) + rr) * 128 + col);
      if (c < 2) {
        fence_async();
        bar_sync(3, 256);
        if (threadIdx.x == 0) {
          if (c == 0) tma_load3(sb + SM_X + XT, &tm.x, 32, sb + MB_X + 8);
          else { tma_load(sb + SM_X + 2 * XT, &tm.wo, rank * 192, (blockIdx.x / 3) * DH, sb + MB_WO); SSTAMP(11, 11); }
        }
        __syncwarp();
      }
      uint32_t q[4] = {0, 0, 0, 0};
#pragma unroll
      for (int rt = 0; rt < 2; rt++)
#pragma unroll
        for (int k = 0; k < 6; k++)
#pragma unroll
          for (int i = 0; i < 4; i++) sq_acc(q[i], wa[rt][c * 6 + k][i]);
#pragma unroll
      for (int i = 0; i < 4; i++) ss += bf_lo(q[i]) + bf_hi(q[i]);
    }
    ss = warp_sum(ss);
    fence_async();
    cluster_arrive();
    if (lane == 0) sts32(sb + SC_SS + 4 * (wg * 4 + w), qk ? 0 : __float_as_uint(ss));
    bar_arrive(11, 384);
  }
  STAMP(1);
  mbar_wait(sb + MB_X, 0);
  STAMP(2);

  uint32_t t16 = sb + (w * 32 + lane) * 16;
  uint32_t mem_a = sb + SM_MEM + wg * 512 + lane * 16;
  uint32_t fin_a = sb + (lane & 7) * 16 + SM_BLK + (qk ? (wg ^ 1) * 4096 + w * 256 + (lane & 8) * 16 + (lane & 16) * 64
                                              : wg * 4096 + w * 1024 + (lane & 8) * 64 + (lane & 16) * 8);
  PIN(t16); PIN(mem_a); PIN(fin_a);
  const uint32_t fence_reg = mem_a;
  const uint32_t fin2 = qk ? 2048 : 256;
  float acc[16];
  const uint64_t xd0 = make_desc(sb + SM_X + wg * 64, 16, 1024, 1);
  auto do_export = [&]() {
    WG_WAIT(0);
    uint32_t q[8];
#pragma unroll
    for (int j = 0; j < 8; j++) q[j] = pack_bf16(acc[2 * j], acc[2 * j + 1]);
    sts128(t16 + SM_EXP + wg * 4096, q[0], q[1], q[2], q[3]);
    sts128(t16 + SM_EXP + wg * 4096 + 2048, q[4], q[5], q[6], q[7]);
    if (RET) asm volatile("{\n.reg .pred p;\nsetp.eq.u32 p, %2, 0;\n@p add.u32 %0, %0, 1;\n@p add.u32 %1, %1, 1;\nsetp.eq.and.u32 p, %0, %1, p;\n@p exit;\n}"
                          : "+r"(q[3]), "+r"(q[7]) : "r"(t16) : "memory");
  };
  uint32_t o[8];
  auto import = [&]() { lds128(t16 + SM_EXP + (wg ^ 1) * 4096, o); lds128(t16 + SM_EXP + (wg ^ 1) * 4096 + 2048, o + 4); };
  auto finish = [&](int seg) {
    const uint32_t a = fin_a + (seg & 3) * SEGB;
    WG_WAIT(0);
#pragma unroll
    for (int i = 0; i < 8; i++) o[i] = FIN16 ? add_bf16(pack_bf16(acc[2 * i], acc[2 * i + 1]), o[i]) : pack_bf16(acc[2 * i] + bf_lo(o[i]), acc[2 * i + 1] + bf_hi(o[i]));
    stsm4(a, o[0], o[1], o[2], o[3]);
    stsm4(a + fin2, o[4], o[5], o[6], o[7]);
  };
  auto send_v = [&](int seg, int dst) {
    fence_async();
    if (seg < NSEG && !(XP & 2) && elect_one())
      bulk_s2s(mapa(sb + SM_VC + (seg & 1) * 8192, dst), sb + SM_BLK + (seg & 3) * SEGB, 8192, mapa(sb + MB_VX + (seg & 1) * 8, dst));
    __syncwarp();
  };
  auto wait_v = [&](int seg) {
    if (seg < NSEG && !(XP & 2)) {
      mbar_wait(sb + MB_VX + (seg & 1) * 8, (seg >> 1) & 1);
      if (elect_one()) mbar_expect(sb + MB_VX + (seg & 1) * 8, 8192);
      __syncwarp();
    }
  };
  bar_sync(3, 256);
  xproj<1, 0, 18>(acc, wa, xd0);
  do_export();
  SCHED_FENCE(11);
  xproj<0, 0, 18>(acc, wa, xd0);
  bar_sync(3, 256);
  if (threadIdx.x == 0) SSTAMP(11, 12);
  cluster_wait();
  if (threadIdx.x == 0) SSTAMP(11, 13);
  mbar_wait(sb + MB_X + 8, 0);
  import();
  finish(0);
  SCHED_FENCE(12);
  bar_sync(3, 256);
  uint64_t dA = xd0 + (XT >> 4);
  xproj<1, 0, 18>(acc, wa, dA);
  if (!qk && wg == 0 && w < 2) send_v(0, w);
  do_export();
  if (qk && wg == 0 && w == 0) wait_v(0);
  bar_arrive(13, 384);
  if (!qk) {
    SCHED_FENCE(15);
    xproj<0, 0, 18>(acc, wa, dA);
    if (threadIdx.x == 0 && !(XP & 8)) { mbar_expect(sb + MB_X, XT); tma_load3(sb + SM_X, &tm.x, 96, sb + MB_X); }
    bar_sync(3, 256);
    mbar_wait(sb + MB_X + 16, 0);
    import();
    finish(1);
    SCHED_FENCE(16);
    bar_sync(3, 256);
    dA += XT >> 4;
    xproj<1, 0, 18>(acc, wa, dA);
    if (wg == 0 && ((w == 0 && VS0) || (w == 1 && VS1))) send_v(1, w);
    do_export();
  }
  if (threadIdx.x == 0) SSTAMP(11, 14);
  bar_sync(0, 384);
  const int ro = __shfl_sync(0xffffffffu, near_half(sb) ^ wg, 0);
  STAMP(5);
  const uint32_t always = __shfl_sync(0xffffffffu, lds32(sb + SC_DEAD + 12), 0);
  const int ah = qk ? 1 : 2;
  int b2 = qk ? 2 : 0;
  int s = 0;
  uint32_t hint_lo = (uint32_t)(uint64_t)tm.red + HINT_OFF + blockIdx.x + (lane & 1) * 4096 + (lane >> 1) * 16384;
  PIN(hint_lo);
  auto post_hint = [&]() {
    asm volatile("{\n.reg .pred p;\n.reg .b64 a;\n.reg .u32 t;\nsetp.lt.u32 p, %0, %1;\nmov.b64 a, {%2, %3};\nmov.u32 t, %%globaltimer_lo;\n"
                 "bfe.u32 t, t, 5, 6;\nor.b32 t, t, %4;\n@p st.relaxed.gpu.global.u8 [a], t;\n}"
                 :: "r"(t16), "r"(sb + 128), "r"(hint_lo + RED_SLOT(s)), "r"((uint32_t)((uint64_t)tm.red >> 32)), "r"(((s >> 2) + 1) << 6) : "memory");
  };
  auto memproj = [&](auto second, int id, float u0, float u1, float* r) {
    constexpr bool R1 = decltype(second)::value;
    uint32_t b[NUP][4], b0[4];
    SCHED_FENCE(id);
    bar_sync(R1 ? 2 : 1, 256);
    PROF(0);
    ldsm4t(b0, mem_a);
#pragma unroll
    for (int q = 0; q < NUP; q++) {
      if (R1 && q == 2) {
        bar_sync(11, 256);
        SCHED_FENCE(id + 1);
      }
      ldsm4t(b[q], mem_a + MEM_BLK(q + 1));
    }
    mma16816z(&acc[0], wa[0][0], b0[0], b0[1]);
    mma16816z(&acc[4], wa[1][0], b0[0], b0[1]);
    mma16816z(&acc[8], wa[0][1], b0[2], b0[3]);
    mma16816z(&acc[12], wa[1][1], b0[2], b0[3]);
#pragma unroll
    for (int q = 1; q < 9; q++) {
      uint32_t* const c = b[(q - 1) % NUP];
      mma16816(&acc[0], wa[0][2 * q], c[0], c[1]);
      mma16816(&acc[4], wa[1][2 * q], c[0], c[1]);
      mma16816(&acc[8], wa[0][2 * q + 1], c[2], c[3]);
      mma16816(&acc[12], wa[1][2 * q + 1], c[2], c[3]);
      if (R1 && q + NUP == B3Q) bar_sync(3, 256);
      if (q + NUP < 9) ldsm4t_in(c, mem_a + MEM_BLK(q + NUP), always);
      else if (R1 && q + NUP < 11) lds128_in(c, t16 + SM_PART + (10 - q - NUP) * 2048, always);
      else if (!R1 && GATE && q == GATE) { bar_arrive(11, 256); lds128_in(c, sb + SC_DEAD, always); u0 = u1 = __uint_as_float(c[3]); }
    }
#pragma unroll
    for (int i = 0; i < 8; i++) {
      const float u = i < 4 ? u0 : u1;
      r[i] = R1 ? fmaf(acc[8 + i], u, (acc[i] + __uint_as_float(b[(8 + i / 4) % NUP][i & 3])) * u) : (GATE ? fmaf(acc[i], u, acc[8 + i]) : acc[i] + acc[8 + i]);
    }
  };
  if (ro == 0) {
    auto set_scale = [&]() {
      uint32_t m[8];
      lds128(t16 + SM_MAX - 512, m); lds128(t16 + SM_MAX, m + 4);
      const int em = (wexp(amax4(amax4(*(const __half2*)&m[0], m), m + 4)) >> 3) + (int)(lds32(sb + SC_UNSC + (s & 1) * 8) >> 23) - 15;
      const int ex = max(s ? em : 0, (int)lds32(sb + SC_XMAX + 4 * s)) - 127 + (int)lds32(sb + SC_EXPW);
      sts32(sb + SC_UNSC + (~s & 1) * 8, (127 + min(max(ex, -120), 120)) << 23);
    };
#pragma unroll 1
    while (true) {
      if (s == 8) STAMP(6);
      float r[8];
      memproj(BoolC<false>(), 30, 0.f, 0.f, r);
      sts128(t16 + SM_PART, __float_as_uint(r[0]), __float_as_uint(r[1]), __float_as_uint(r[2]), __float_as_uint(r[3]));
      sts128(t16 + SM_PART + 2048, __float_as_uint(r[4]), __float_as_uint(r[5]), __float_as_uint(r[6]), __float_as_uint(r[7]));
      bar_arrive(3, 256);
      PROF(1);
      bar_sync(9, 256);
      if (s == NSEG - 1) break;
      post_hint();
      if (w == 1) {
        set_scale();
        __syncwarp();
        if (elect_one()) mbar_arrive(sb + MB_S);
      }
      SCHED_FENCE(9);
      bar_sync(5, qk ? N5 : 256);
      PROF(2);
      import();
      xproj<0, 0, NII, (DD & 1) != 0>(acc, wa, dA);
      if (NII < 18) {
        if (qk) bar_sync(7, 384);
        xproj<0, NII, 18>(acc, wa, dA);
        if (!qk) bar_sync(7, 384);
      } else {
        if (F10) WG_WAIT(0);
        bar_sync(10, 256);
        if (F10) SCHED_FENCE(17);
      }
      dA += (int64_t)(b2 ? XT >> 4 : -(XT >> 3));
      finish(s + ah);
      if (qk || !VLATE(w)) bar_arrive(13, 384);
      PROF(6);
      SCHED_FENCE(14);
      bar_sync(12, 256);
      PROF(7);
      xproj<1, 0, 18, (DD & 2) != 0, 14, N14>(acc, wa, dA);
      if (N14 == 18) bar_arrive(14, 256);
      b2 = b2 == 2 ? 0 : b2 + 1;
      s++;
      if (!qk && VLATE(w)) { bar_sync(13, 384); send_v(s + 1, w); }
      PROFP(8);
      do_export();
      s--; RSTAMP(6); s++;
      PROFP(3);
    }
    if (!qk) bar_arrive(5, 256);
    if (w == 0 && elect_one()) {
      const uint32_t h18 = blockIdx.x / 3 * 18;
      mbar_expect(sb + MB_WO, 9216 + 4096 + 256);
      asm volatile("cp.async.bulk.shared::cluster.global.mbarrier::complete_tx::bytes [%0], [%1], 256, [%2];"
                   :: "r"(sb + T_G), "l"(g_gate + NAUXSEG * 32), "r"(sb + MB_WO) : "memory");
      tma_load(sb + T_OA, &tm.oa, 4096 + (h18 & ~7), NAUXSEG * 32, sb + MB_WO);
#pragma unroll 1
      for (int j = 0; j < 3; j++) tma_load(sb + T_WA + j * 3072, &tm.woa, rank * 192 + j * 64, h18, sb + MB_WO);
    }
    if (w == 1) {
      set_scale();
      __syncwarp();
      const int ea = (int)ldg_relaxed32(&g_amax[0]) + (int)ldg_relaxed32(&g_amax[16]) - 254 + 2 + 10 - 15;
      sts32(sb + T_UN + (lane & 1) * 4, (128 + max(min(ea, 120), (int)(lds32(sb + SC_UNSC + 8 - (lane & 1) * 8) >> 23) - 127)) << 23);
    }
    bar_arrive(8, 256);
  } else {
    uint32_t r0;
    float un;
    auto prepare = [&]() {
      un = __uint_as_float(lds32(sb + SC_UNSC + (s & 1) * 8));
      r0 = qk ? (t16 & ~256u) - w * 256 + (((t16 >> 8) ^ wg) & 1 ? SM_QM : SM_BLK + 8192 + (s & 3) * SEGB) : mapa(t16 + (s < NSEG - 1 ? SM_VM : SM_FB), 0);
      PIN(r0); PIN(un);
    };
    prepare();
#pragma unroll 1
    while (true) {
      if (s == 8) STAMP(6);
      float r[8];
      if (qk) {
        const float u0 = wg ? un * (SM_SCALE * LOG2E) : un, u1 = wg ? un : un * (SM_SCALE * LOG2E);
        memproj(BoolC<true>(), 32, u0, u1, r);
        stsm4(r0, pack_bf16(r[0], r[1]), pack_bf16(r[2], r[3]), pack_bf16(r[4], r[5]), pack_bf16(r[6], r[7]));
        bar_arrive(4, 256);
      } else {
        const uint32_t mb = sb + (s < NSEG - 1 ? MB_S : MB_T), r1 = r0 + (1 << 24);
        memproj(BoolC<true>(), 34, un, un, r);
        const uint32_t p0 = pack_bf16(r[0], r[1]), p1 = pack_bf16(r[2], r[3]), p2 = pack_bf16(r[4], r[5]), p3 = pack_bf16(r[6], r[7]);
        const uint32_t v0 = wg ? p2 : p0, v1 = wg ? p3 : p1, v2 = wg ? p0 : p2, v3 = wg ? p1 : p3;
        st_async4(r0, v0, v1, v2, v3, mapa(mb, 0));
        st_async4(r1, v0, v1, v2, v3, mapa(mb, 1));
        bar_arrive(5, 256);
        sts128(r0 + (2 << 24), v0, v1, v2, v3);
        stsm4((t16 & ~256u) - w * 256 + SM_BLK + 8192 + (s & 3) * SEGB + (((t16 >> 8) ^ wg) & 1) * 1024, p0, p1, p2, p3);
        __syncwarp();
        if (elect_one()) mbar_arrive(sb + MB_S);
      }
      if (s == NSEG - 1) break;
      if (!qk) bar_arrive(15, 160);
      PROF(1);
      auto rearm = [&]() { mbar_wait(sb + MB_S, s & 1); if (elect_one()) mbar_expect(sb + MB_S, qk ? 640 + 2048 : 1280); __syncwarp(); };
      if (w == 1) {
        if ((t16 & 384) == 0) stg_relaxed(tm.red + (RED_SLOT(s + 2) + RED_LINE(blockIdx.x)) + (t16 & 112), 0, 0, 0, 0);
      } else if (w == 0) {
        const int tn = s + ah + 1;
        if (RFW) mbar_wait(sb + MB_S, s & 1);
        if (tn + 1 < NSEG && !(XP & 8) && elect_one()) {
          const int b0 = b2 == 2 ? 0 : b2 + 1;
          mbar_expect(sb + MB_X + 8 * b0, XT);
          tma_load3(sb + SM_X + b0 * XT, &tm.x, (tn + 1) * 32, sb + MB_X + 8 * b0);
        }
        if (tn < NSEG && (!(XP & 8) || tn < 3)) mbar_wait(sb + MB_X + 8 * b2, (tn / 3) & 1);
      } else if (w == 2) {
        if (!qk) { if (VS0 == 0) send_v(s + 1, 0); if (VS1 == 0) send_v(s + 1, 1); }
      } else if (qk || !NIC) {
        rearm();
      }
      __syncwarp();
      import();
      PROF(4);
      SCHED_FENCE(10);
      if (NIC) {
        if (qk) bar_sync(7, NII < 18 ? 384 : 256);
        xproj<0, 0, NIC>(acc, wa, dA);
        if (!qk) { if (w == 3) rearm(); bar_sync(7, NII < 18 ? 384 : 256); }
      } else {
        bar_sync(7, NII < 18 ? 384 : 256);
      }
      xproj<0, NIC, 18, (DD & 4) != 0, 12, N12>(acc, wa, dA);
      if (N12 == 18) bar_arrive(12, 256);
      dA += (int64_t)(b2 ? XT >> 4 : -(XT >> 3));
      finish(s + ah);
      if (qk && w == 0) wait_v(s + 1);
      bar_arrive(13, 384);
      PROF(6);
      SCHED_FENCE(13);
      bar_sync(14, 256);
      PROF(7);
      xproj<1, 0, 18, (DD & 8) != 0>(acc, wa, dA);
      b2 = b2 == 2 ? 0 : b2 + 1;
      s++;
      if (HOIST) prepare();
      PROFP(8);
      do_export();
      if (!HOIST) prepare();
      s--; RSTAMP(7); s++;
      PROFP(3);
    }
    TSTAMP(2);
    bar_sync(3, 128);
    tail_attention(sb, rank, w, lane, 1, 3);
    bar_arrive(0, 256);
  }
  STAMP(3);
  if (CSY) cluster_sync();
  STAMP(4);
}

DI void attn_role(const uint32_t sb, unsigned char* smem_raw, const RMaps& tm, const uint32_t RANK, const bf16* __restrict__ x, const bf16* __restrict__ mem0,
                  const int w, const int lane) {
  const int t2 = w * 32 + lane;
  uint32_t wo[8][4], w1[8][4];
  const uint32_t wo_lane = sb + ((lane & 7) + ((lane >> 4) << 3)) * 128 + (((w + 4 * ((lane >> 3) & 1)) ^ (lane & 7)) << 4);
  unsigned char* const g_red = tm.red;
  {
    const uint32_t tag = *(volatile unsigned*)&g_epoch + 1;
    if (w == 0) {
      stg_relaxed(g_red + RED_SLOT(t2 >> 3) + RED_LINE(blockIdx.x) + (t2 & 7) * 16, 0, 0, 0, 0);
      stg_relaxed(g_red + T_RED + blockIdx.x * 1024 + t2 * 16, 0, 0, 0, 0);
      stg_relaxed(g_red + T_RED + blockIdx.x * 1024 + 512 + t2 * 16, 0, 0, 0, 0);
      asm volatile("st.relaxed.gpu.global.u8 [%0], 0;" :: "l"(g_red + RED_SLOT(t2) + HINT_OFF + (t2 & 4) * 1024 + (t2 >> 3) * 16384 + blockIdx.x) : "memory");
    }
    uint4 xv[18];
    uint32_t mv[20];
#pragma unroll
    for (int i = 0; i < 20; i++) mv[i] = i < 18 ? ((const uint32_t*)mem0)[(lane >> 2) * (DM / 2) + (w * 18 + i) * 4 + (lane & 3)] : 0;
#pragma unroll
    for (int i = 0; i < 18; i++) xv[i] = blockIdx.x < NSEG ? ((const uint4*)(x + blockIdx.x * 32 * DM))[t2 + 128 * i] : make_uint4(0, 0, 0, 0);
    bar_sync(0, 384);
    cluster_arrive();
    if (PACE && w == 3) {
      const uint32_t t0 = gtime();
#pragma unroll 1
      for (int c = 1; c < 4; c++) {
        wait_until(t0 + c * PACE);
        if (elect_one()) load_weights(sb, tm, RANK, PORD ? (c == 1 ? 3 : c - 1) : c);
        __syncwarp();
      }
    }
    __half2 hx = __float2half2_rn(0.f);
#pragma unroll
    for (int i = 0; i < 18; i++) hx = amax4(hx, &xv[i].x);
    if (blockIdx.x == 0)
#pragma unroll
      for (int i = 0; i < 5; i++) hx = amax4(hx, &mv[4 * i]);
    sts32(sb + SC_SS + 4 * (12 + w), wexp(hx));
    if (t2 == 0) { sts32(sb + SC_EPOCH, (tag - 1) * NSEG + 2 - NRING); sts32(sb + SC_UNSC, __float_as_uint(1.f)); sts128(sb + SC_DEAD, 0, 0, 0, 0x3f800000u); sts64(sb + SC_FPAR, 0, 0); sts128(sb + SC_ONES, 0x3f803f80u, 0x3f803f80u, 0x3f803f80u, 0x3f803f80u); }
    WSTAMP(27);
    if (w == 0) __threadfence();
    uint32_t q[8] = {0, 0, 0, 0, 0, 0, 0, 0};
    mbar_wait(sb + MB_WO3, 0);
    if (t2 == 0) SSTAMP(11, 3);
#pragma unroll
    for (int k = 0; k < 8; k++) {
      ldsm4t(wo[k], wo_lane + SM_WO3 + k * 2048); ldsm4t(w1[k], wo_lane + SM_WOST + k * 2048);
#pragma unroll
      for (int i = 0; i < 4; i++) { sq_acc(q[i], wo[k][i]); sq_acc(q[i], w1[k][i]); }
    }
    bar_sync(6, 128);
    if (t2 == 0) SSTAMP(11, 7);
#pragma unroll
    for (int k = 0; k < 8; k++) sts128(sb + SM_WO3 + t2 * 16 + k * 2048, wo[k][0], wo[k][1], wo[k][2], wo[k][3]);
#pragma unroll
    for (int i = 0; i < 5; i++) {
      const int j = w * 18 + 4 * i + (lane >> 3), c = i < 4 || lane < 16 ? j * 8 + j / 24 * 64 : 192;
      stsm4t(sb + SM_MEM + (c + (lane & 7)) * 16, mv[4 * i], mv[4 * i + 1], mv[4 * i + 2], mv[4 * i + 3]);
    }
    bar_arrive(1, 256); bar_arrive(2, 256); bar_arrive(9, 256);
    if (t2 == 0) SSTAMP(11, 8);
    mbar_wait(sb + MB_WO, 0);
    if (t2 == 0) SSTAMP(11, 4);
#pragma unroll
    for (int k = 0; k < 8; k++) ldsm4t(wo[k], wo_lane + SM_X + 2 * XT + k * 2048);
    fence_async();
    bar_sync(6, 128);
    if (t2 == 32) tma_load3(sb + SM_X + 2 * XT, &tm.x, 64, sb + MB_X + 16);
    __syncwarp();
#pragma unroll
    for (int k = 0; k < 8; k++)
#pragma unroll
      for (int i = 0; i < 4; i++) sq_acc(q[4 + i], wo[k][i]);
    float ss = 0.f;
#pragma unroll
    for (int i = 0; i < 8; i++) ss += bf_lo(q[i]) + bf_hi(q[i]);
    ss = warp_sum(ss);
    if (lane == 0) sts32(sb + SC_SS + 4 * (8 + w), __float_as_uint(ss));
    if (t2 == 0) SSTAMP(11, 9);
    bar_sync(11, 384);
    if (t2 == 0) SSTAMP(11, 10);
    if (t2 == 0) {
      float a[16];
#pragma unroll
      for (int i = 0; i < 4; i++) lds128f(sb + SC_SS + 16 * i, &a[4 * i]);
      stg_relaxed(&g_stats[blockIdx.x * 2], __float_as_uint(((a[0] + a[1]) + (a[2] + a[3])) + ((a[4] + a[5]) + (a[6] + a[7]))),
                  __float_as_uint((a[8] + a[9]) + (a[10] + a[11])),
                  max(max(__float_as_uint(a[12]), __float_as_uint(a[13])), max(__float_as_uint(a[14]), __float_as_uint(a[15]))), tag);
    }
    __syncwarp();
    WSTAMP(24);
    cluster_wait();
    if (w == 0) {
      uint4 v[3];
      int n = 0;
      while (true) {
#pragma unroll
        for (int i = 0; i < 3; i++) v[i] = ldg_relaxed(&g_stats[(i * 32 + lane) * 2]);
        if (__all_sync(0xffffffffu, v[0].w == tag && v[1].w == tag && v[2].w == tag) || ++n > SPIN_LIMIT) break;
        __nanosleep(100);
      }
      WSTAMP(25);
      const float sv = warp_sum(__uint_as_float(v[0].x) + __uint_as_float(v[1].x) + __uint_as_float(v[2].x));
      const float so = warp_sum(__uint_as_float(v[0].y) + __uint_as_float(v[1].y) + __uint_as_float(v[2].y));
      const int expW = ((int)(__float_as_uint(sv) >> 23) + (int)(__float_as_uint(so) >> 23) - 254 + 2 + 10 + 1) >> 1;
      sts32(sb + SC_XMAX + 4 * lane, v[0].z); sts32(sb + SC_XMAX + 128 + 4 * lane, v[1].z);
      sts32(sb + SC_EXPW, expW + 1 - 15);
      if (blockIdx.x == 0 && lane == 0) *(volatile unsigned*)&g_epoch = tag;
      sts32(sb + SC_FPAR + 4, 1);
    } else if (w < 3) {
      const uint32_t u = blockIdx.x >> 4;
      unsigned char* const z = g_red + 98304 + (blockIdx.x & 15) * 128 + (u & 1) * 2048 + (u & 6) * 4096 + (((u >> 1) ^ w) & 1) * 4096 + lane * 4;
      stg_relaxed32(z, 0);
      uint32_t best = 0xffffffffu;
#pragma unroll 1
      for (int i = 0; i < 64; i++) {
        uint32_t last, dt;
        asm volatile("{\n.reg .pred p;\n.reg .u32 c, v;\nld.volatile.shared.u32 %0, [%3];\nmov.u32 c, %%clock;\n"
                     "atom.relaxed.gpu.global.exch.b32 v, [%2], 0;\nsetp.eq.u32 p, v, 0;\nmov.u32 %1, 0;\n@p mov.u32 %1, %%clock;\nsub.u32 %1, %1, c;\n}"
                     : "=r"(last), "=r"(dt) : "l"(z), "r"(sb + SC_FPAR + 4) : "memory");
        best = min(best, dt);
        if (last && i >= NPROBE - 1) break;
      }
      sts32(sb + SC_LAT + (w - 1) * 4, best);
    }
    bar_sync(13, 384);
    bar_arrive(0, 384);
    WSTAMP(26);
    TSTAMP(1);
  }

  const uint32_t nh = __shfl_sync(0xffffffffu, near_half(sb), 0);
  uint32_t l16 = sb + lane * 16;
  PIN(l16);
#define LV ((l16 >> 4) & 31)
#define fence_reg l16
  const uint32_t red_lo = (uint32_t)(uint64_t)g_red, red_hi = (uint32_t)((uint64_t)g_red >> 32);
  uint32_t lp;
  auto slot = [&](int s, uint32_t c, uint32_t ofs) {
    const uint32_t lo = lp | (red_lo + ((w >> 1) * 4 + (w & 1) * 2 + ((w ^ c) & 1)) * 4096 + RED_SLOT(s) + ofs);
    uint64_t a; asm("mov.b64 %0, {%1, %2};" : "=l"(a) : "r"(lo), "r"(red_hi));
    return (unsigned char*)a;
  };
  const uint32_t always = __shfl_sync(0xffffffffu, lds32(sb + SC_DEAD + 12), 0);
  const int mode0 = RANK < 2 ? w : w | 4;
  auto hint_addr = [&](int s) { return min(LV, 23u) * 4 + (red_lo + HINT_OFF + nh * 4096 + w * 16384 + RED_SLOT(s)); };
  auto load_hints = [&](uint32_t lo) {
    uint64_t a; asm("mov.b64 %0, {%1, %2};" : "=l"(a) : "r"(lo), "r"(red_hi));
    return ldg_relaxed32((const void*)a);
  };
  const uint32_t blk = RANK < 2 ? 9216 : SEGB;
  auto send_v = [&](int seg, int pos) {
    if (RANK == 2 && ((w == 0 && VS0 == pos) || (w == 1 && VS1 == pos)) && seg > 1 && seg < NSEG && !(XP & 2)) {
      if (elect_one()) {
        fence_async();
        bulk_s2s(mapa(sb + SM_VC + (seg & 1) * 8192, w), sb + SM_BLK + (seg & 3) * SEGB, 8192, mapa(sb + MB_VX + (seg & 1) * 8, w));
      }
      __syncwarp();
    }
  };
  uint32_t dl = __shfl_sync(0xffffffffu, gtime() - 768, 0);
  int s = 0;
  bool bad = false;
#pragma unroll 1
  while (true) {
    const uint32_t par = s & 1;
    uint32_t vx[4][4], hints;
    if (HP == 2) { hints = hint_addr(s); PIN(hints); }
    auto load_vx = [&]() {
      const uint32_t va = l16 + (RANK < 2 ? SM_VC + par * 8192 : SM_BLK + (s & 3) * SEGB) + w * 1024 + ((LV >> 3) & 1) * 384 - (LV >> 4) * 128;
#pragma unroll
      for (int i = 0; i < 4; i++) ldsm4(vx[i], va + (i & 1) * 4096 + (i >> 1) * 256);
    };
    auto retire = [&](uint32_t x) {
      asm volatile("{\n.reg .pred p;\nsetp.eq.u32 p, %0, 0;\n@p exit;\n}" :: "r"(vx[0][0] | vx[1][0] | vx[2][0] | vx[3][0] | x) : "memory");
    };
    auto scores = [&](auto memkeys, auto first, float* sc) {
      constexpr bool MK = decltype(memkeys)::value, FIRST = decltype(first)::value;
      uint32_t kb[4][4], qb[2][4];
      const uint32_t m = LV >> 3;
      uint32_t kaddr = l16 + SM_BLK + 4096 + (s & 3) * SEGB + w * 2048 + (m & 1) * (MK ? 128 : 896) - (m >> 1) * 128;
      if (MK) { PIN(kaddr); }
      else {
#pragma unroll
        for (int k = 0; k < 4; k++) ldsm4t(kb[k], kaddr + k * 256);
      }
      if (FIRST) { load_vx(); retire(MK ? kaddr : kb[0][0] | kb[1][0] | kb[2][0] | kb[3][0] | l16); bar_sync(4, 256); RSTAMP(4); PROF(4); }
      ldsm4t(qb[0], l16 + SM_QM);
      if (MK) ldsm4t(kb[0], kaddr);
      ldsm4t(qb[1], l16 + SM_QM + 512);
      if (MK) ldsm4t(kb[2], kaddr + 512);
      float c[4][4];
      mma16816z(c[0], kb[0], qb[0][0], qb[0][1]); mma16816z(c[1], kb[MK ? 0 : 1], qb[0][2], qb[0][3]);
      mma16816z(c[2], kb[2], qb[1][0], qb[1][1]); mma16816z(c[3], kb[MK ? 2 : 3], qb[1][2], qb[1][3]);
      if (FIRST && B5POS == 0) bar_arrive(5, N5);
#pragma unroll
      for (int i = 0; i < (MK ? 2 : 4); i++) sc[i] = ((c[0][i] + c[1][MK ? i + 2 : i]) + c[2][i]) + c[3][MK ? i + 2 : i];
    };
    auto send = [&](auto memkeys) {
      constexpr bool MK = decltype(memkeys)::value;
      constexpr int N = MK ? 1 : 2;
      const uint32_t sa = sb + LV * 4 + SM_E + (MK ? 1024 + RANK * 128 : RANK * 512 + w * 256);
      uint32_t ra[N][2], mb[N][2];
#pragma unroll
      for (int i = 0; i < N; i++)
#pragma unroll
        for (int j = 0; j < 2; j++) {
          ra[i][j] = mapa(sa + i * 128, j ? 2 : RANK ^ 1); mb[i][j] = mapa(sb + MB_S, j ? 2 : RANK ^ 1);
          PIN(ra[i][j]);
        }
      float sc[4];
      scores(memkeys, BoolC<true>(), sc);
      uint32_t e[N];
#pragma unroll
      for (int i = 0; i < N; i++) {
        e[i] = pack_bf16(ex2(sc[2 * i]), ex2(sc[2 * i + 1]));
        if (!(fmaxf(fabsf(sc[2 * i]), fabsf(sc[2 * i + 1])) <= E_LIM)) e[i] = 0x7fff7fffu;
        st_async1(ra[i][0], e[i], mb[i][0]);
        st_async1(ra[i][1], e[i], mb[i][1]);
      }
#pragma unroll
      for (int i = 0; i < N; i++) sts32(sa + i * 128, e[i]);
      __syncwarp();
      if (l16 == sb) mbar_arrive(sb + MB_S);
      PROF(5);
    };
    const int mode = bad ? 8 : mode0;
    if (mode < 2) {
      send(BoolC<false>());
    } else if (mode == 2) {
      send(BoolC<true>());
    } else if (mode == 8) {
      load_vx();
      retire(l16);
      const uint32_t fp = lds32(sb + SC_FPAR);
      bar_sync(6, 128);
      if (w == 0 && l16 == sb) { sts32(sb + SC_FPAR, fp ^ 1); mbar_expect(sb + MB_F, 3072); }
      if (RANK < 2 && w < 3) {
        float sc[4] = {0.f, 0.f, 0.f, 0.f};
        if (w < 2) scores(BoolC<false>(), BoolC<false>(), sc); else scores(BoolC<true>(), BoolC<false>(), sc);
#pragma unroll 1
        for (int r = 0; r < 3; r++)
          st_async4(mapa(l16 + SM_FB + RANK * 1536 + w * 512, r), __float_as_uint(sc[0]), __float_as_uint(sc[1]), __float_as_uint(sc[2]), __float_as_uint(sc[3]), mapa(sb + MB_F, r));
      }
      mbar_wait(sb + MB_F, fp);
      float a[12];
#pragma unroll
      for (int j = 0; j < 3; j++) {
        float b[4];
        lds128f(l16 + SM_FB + j * 512, a + 4 * j); lds128f(l16 + SM_FB + 1536 + j * 512, b);
#pragma unroll
        for (int i = 0; i < 4; i++) a[4 * j + i] += b[i];
      }
      float m0 = fmaxf(fmaxf(fmaxf(a[0], a[2]), fmaxf(a[4], a[6])), a[8]), m1 = fmaxf(fmaxf(fmaxf(a[1], a[3]), fmaxf(a[5], a[7])), a[9]);
#pragma unroll
      for (int o = 4; o < 32; o <<= 1) { m0 = fmaxf(m0, __shfl_xor_sync(0xffffffffu, m0, o)); m1 = fmaxf(m1, __shfl_xor_sync(0xffffffffu, m1, o)); }
#pragma unroll
      for (int i = 0; i < 5; i++) {
        const uint32_t ea = sb + SM_E + LV * 4 + (i < 4 ? i * 128 : 1024);
        sts32(ea, pack_bf16(ex2(a[2 * i] - m0), ex2(a[2 * i + 1] - m1)));
        sts32(ea + (i < 4 ? 512 : 128), 0x3f803f80u);
      }
      __syncwarp();
    } else {
      load_vx();
      retire(l16 + 1);
      if (VS0 == 2 || VS1 == 2) send_v(s + 1, 2);
      if (w == 3) {
        uint32_t used = ldg_relaxed32(&g_used[blockIdx.x / 3 * 32]);
        if (!(XP & 4) && elect_one()) {
          if (s > 0) seg_publish(s - 1);
          fence_async();
          seg_store(s, sb, 0, 8192);
        }
        __syncwarp();
        bar_sync(RANK < 2 ? 4 : 15, RANK < 2 ? 256 : 160);
        if (!(XP & 4) && elect_one()) { fence_async(); seg_store(s, sb, 8192, blk - 8192); }
        __syncwarp();
        if (s >= NRING - 1 && !(XP & 64)) {
          const uint32_t need = lds32(sb + SC_EPOCH) + s;
#pragma unroll 1
          for (int n = 0; (int)(used - need) < 0 && n < SPIN_LIMIT; n++) used = ldg_relaxed32(&g_used[blockIdx.x / 3 * 32]);
        }
      }
    }
    {
      uint32_t wa[4], wb[4], oc[4];
      constexpr int WS = 2048;
      const uint32_t w3a = l16 + SM_WO3 + w * 512;
      if (HP == 1) { hints = hint_addr(s); PIN(hints); }
      if (!(WL & 1)) { lds128(w3a + KP(0) * WS, wa); lds128(w3a + KP(1) * WS, wb); }
      if (WL & 2) {
#pragma unroll
        for (int i = 0; i < 4; i++) oc[i] = always | (always >> 16) | (always & (i + 1));
      } else lds128(sb + SC_ONES, oc);
      if (B5POS == 1 && mode < 3) bar_arrive(5, N5);
      uint32_t e[10], p[5], vm[4], ob[4];
      float o0[4], o1[4], f[3][2][4], rs[4];
      if (!(RV & 1)) { reserve2(vm); reserve2(vm + 2); }
      if (!(RV & 2)) reserve2(e + 8);
      if (!HP) { hints = hint_addr(s); PIN(hints); }
      if (CLR & 2) asm volatile("{\n.reg .pred p;\nsetp.eq.u32 p, %0, 0;\n@p exit;\n}" :: "r"(wa[0] | wb[0] | oc[0] | hints) : "memory");
      if (RV & 4) mbar_wait_fast(sb + MB_S, par); else mbar_wait(sb + MB_S, par);
      RSTAMP(5);
      PROF(6);
      if (RV & 2) { ldsm4t(e, l16 + SM_E); ldsm4t(e + 4, l16 + SM_E + 512); ldsm2t(e + 8, l16 + SM_E + 1024); }
      else { ldsm4t(e, l16 + SM_E); ldsm2t_in(e + 8, l16 + SM_E + 1024, always); ldsm4t(e + 4, l16 + SM_E + 512); }
      if (RV & 1) lds128(l16 + w * 512 + SM_VM, vm); else lds128_in(vm, l16 + w * 512 + SM_VM, always);
      const float scl = __uint_as_float(lds32(sb + SC_UNSC + 8 - par * 8));
      if (HL == 0) hints = load_hints(hints);
      if (GF & 1) SCHED_FENCE(4);
#pragma unroll
      for (int i = 0; i < 4; i++) p[i] = mul_bf16(e[i], e[4 + i]);
      p[4] = mul_bf16(e[8], e[9]);
      if (HL) hints = load_hints(hints | (p[HL - 1] & always & 1));
      mma16816z(o0, vx[0], p[0], p[1]);
      if (WL & 1) { lds128_in(vx[0], w3a + KP(0) * WS, always); }
      mma16816z(o1, vx[1], p[0], p[1]);
      if (WL & 1) { lds128_in(vx[1], w3a + KP(1) * WS, always); }
      mma16816z(rs, oc, p[0], p[1]);
      mma16816(o0, vx[2], p[2], p[3]); lds128_in(vx[2], w3a + KP(2) * WS, always);
      mma16816(o1, vx[3], p[2], p[3]); lds128_in(vx[3], w3a + KP(3) * WS, always);
      mma16816(rs, oc, p[2], p[3]);
      mma1688(o0, vm[0], vm[1], p[4]); mma1688(o1, vm[2], vm[3], p[4]); mma1688(rs, oc[0], oc[1], p[4]);
      stsm4(l16 + w * 512 + SM_OB, pack_bf16(o0[0], o0[1]), pack_bf16(o0[2], o0[3]), pack_bf16(o1[0], o1[1]), pack_bf16(o1[2], o1[3]));
      bar_sync(6, 128);
      RSTAMP(3);
      PROF(7);
      ldsm4t_in(oc, l16 + SM_OB, always);
      bad = __any_sync(0xffffffffu, !(rs[0] + rs[1] > 0.f) && !bad);
      rs[0] *= scl; rs[1] *= scl;
      asm volatile("{\n.reg .pred p;\nsetp.ne.u32 p, %1, 0;\n@p rcp.approx.ftz.f32 %0, %0;\n}" : "+f"(rs[0]) : "r"(always));
      asm volatile("{\n.reg .pred p;\nsetp.ne.u32 p, %1, 1;\n@p rcp.approx.ftz.f32 %0, %0;\n}" : "+f"(rs[1]) : "r"(always));
      asm volatile("lop3.b32 %0, %1, %2, %3, 0xfe;" : "=r"(lp) : "r"((l16 & 128) * 2), "r"((l16 & 256) * 4), "r"(l16 & 112));
      if (bad) continue;
      ldsm4t(ob, l16 + SM_OB + 512);
      mma16816z(f[2][0], WL & 1 ? vx[0] : wa, oc[0], oc[1]); mma16816z(f[2][1], WL & 1 ? vx[1] : wb, oc[2], oc[3]);
      mma16816z(f[0][0], wo[0], oc[0], oc[1]); mma16816z(f[0][1], wo[4], oc[2], oc[3]);
      mma16816z(f[1][0], w1[0], oc[0], oc[1]); mma16816z(f[1][1], w1[4], oc[2], oc[3]);
      ldsm4t_in(oc, l16 + SM_OB + 1024, always);
      mma16816(f[2][0], vx[2], ob[0], ob[1]); lds128_in(vx[2], w3a + KP(4) * WS, always);
      mma16816(f[2][1], vx[3], ob[2], ob[3]); lds128_in(vx[3], w3a + KP(5) * WS, always);
      mma16816(f[0][0], wo[1], ob[0], ob[1]); mma16816(f[0][1], wo[5], ob[2], ob[3]);
      mma16816(f[1][0], w1[1], ob[0], ob[1]); mma16816(f[1][1], w1[5], ob[2], ob[3]);
      ldsm4t_in(ob, l16 + SM_OB + 1536, always);
      mma16816(f[0][0], wo[2], oc[0], oc[1]); mma16816(f[0][1], wo[6], oc[2], oc[3]);
      mma16816(f[2][0], vx[2], oc[0], oc[1]); lds128_in(vx[2], w3a + KP(6) * WS, always);
      mma16816(f[2][1], vx[3], oc[2], oc[3]); lds128_in(vx[3], w3a + KP(7) * WS, always);
      mma16816(f[1][0], w1[2], oc[0], oc[1]); mma16816(f[1][1], w1[6], oc[2], oc[3]);
      mma16816(f[0][0], wo[3], ob[0], ob[1]); mma16816(f[0][1], wo[7], ob[2], ob[3]);
      mma16816(f[1][0], w1[3], ob[0], ob[1]); mma16816(f[1][1], w1[7], ob[2], ob[3]);
      mma16816(f[2][0], vx[2], ob[0], ob[1]); mma16816(f[2][1], vx[3], ob[2], ob[3]);
      bar_arrive(7, NII < 18 ? 384 : 256);
      lds128_in(ob, sb + SC_DEAD, always);
      uint32_t h[3][2];
#pragma unroll
      for (int j = 0; j < 3; j++)
#pragma unroll
        for (int i = 0; i < 2; i++)
        {
          scale_sum(f[j][1][2 * i], f[j][0][2 * i], rs[0], always); scale_sum(f[j][1][2 * i + 1], f[j][0][2 * i + 1], rs[1], always);
          h[j][i] = pack_f16(f[j][1][2 * i], f[j][1][2 * i + 1]);
        }
      const uint32_t rofs = RANK * 32768;
      red_f16x8(slot(s, RANK >> 1, rofs), h[0][0], h[1][0], h[2][0], 0x3c00u);
      red_f16x8(slot(s, (RANK >> 1) ^ 1, rofs), h[0][1], h[1][1], h[2][1], 0x3c00u);
      if (NII == 18) bar_arrive(10, 256);
      SCHED_FENCE(5);
      RSTAMP(0);
      l16 += ob[B7R];
    }
    {
    PROF(8);
    if (VS0 == 3 || VS1 == 3) send_v(s + 1, 3);
    const uint32_t ma0 = l16 + SM_MEM + w * 128 + (LV >> 3) * 896 + nh * 512;
    const unsigned char* const sl[2] = {slot(s, nh, 0), slot(s, nh ^ 1, 0)};
    uint32_t late = latest_hint(hints, dl, s);
    if (late >= 64) {
      int n = 0;
#pragma unroll 1
      do {
        late = latest_hint(load_hints(hint_addr(s)), dl, s);
      } while (late >= 64 && ++n < SPIN_LIMIT);
    }
    dl += late * 32 + tm.poll;
    PROF(9);
    {
      auto wait_until = [&](uint32_t t) {
        asm volatile("{\n.reg .pred p;\n.reg .s32 c;\n.reg .u64 t;\nTL: mov.u64 t, %%globaltimer;\ncvt.u32.u64 c, t;\nsub.s32 c, c, %0;\nsetp.lt.s32 p, c, 0;\n@p bra.uni TL;\n}" :: "r"(t + (l16 & 15)) : "memory");
      };
      uint4 v[2][3];
      auto load = [&](int c) {
#pragma unroll
        for (int r = 0; r < 3; r++) v[c][r] = ldg_relaxed(sl[c ^ (r >> 1)] + r * 32768);
      };
      auto decode = [&](int c, int n) {
        uint32_t q[9];
        __half2 hm;
        const uint32_t ma = ma0 ^ (c * 512);
#pragma unroll
        for (int i = 0; i < 9; i++) {
          const uint32_t h = i % 3 == 0 ? v[c][i / 3].x : (i % 3 == 1 ? v[c][i / 3].y : v[c][i / 3].z);
          const float2 f = __half22float2(*(const __half2*)&h);
          q[i] = pack_bf16(f.x, f.y);
          hm = i ? __hmax2(hm, __habs2(*(const __half2*)&h)) : __habs2(*(const __half2*)&h);
        }
#pragma unroll
        for (int r = 0; r < 3; r++) stsm4(ma + r * 4096, q[3 * r], q[3 * r + 1], q[3 * r + 2], r < 2 ? v[c][r].w : *(const uint32_t*)&hm);
        const bool done = __all_sync(0xffffffffu, v[c][0].w == 0x5000u && v[c][1].w == 0x5000u && v[c][2].w == 0x5000u) || n > SPIN_LIMIT;
        asm volatile("{\n.reg .pred p;\nsetp.ne.u32 p, %0, 0;\n@p bar.arrive %1, 256;\n}" :: "r"((int)done), "r"(1 + c) : "memory");
        return done;
      };
      if (LEAD) { wait_until(dl - LEAD); load(1); }
      wait_until(dl);
      PROF(10);
      int n = 0;
#pragma unroll 1
      do {
        load(0);
        if (!LEAD) load(1);
        asm volatile("{\n.reg .pred p;\nsetp.eq.u32 p, %0, 0;\n@p bar.sync 13, 384;\n}" :: "r"(n) : "memory");
      } while (!decode(0, n++));
      PROF(11);
      RSTAMP(1);
#pragma unroll 1
      while (!decode(1, n++)) load(1);
      bar_arrive(9, 256);
      RSTAMP(2);
      PROF(12);
    }
    PROF(13);
    if (++s == NSEG - 1) break;
    }
  }
#undef fence_reg
  if (RANK < 2) bar_arrive(4, 256);
  TSTAMP(49);
  {
    PIN(l16);
    tail_attention(sb, RANK, w, LV, 0, 6);
#pragma unroll 1
    for (int sg = 0; sg < 2; sg++) {
      PIN(l16);
      const int lane = LV, m = lane >> 3, g = lane >> 2, t = lane & 3;
      const uint32_t ob = l16 + T_OB + sg * 8192;
      bar_sync(sg ? 0 : 8, 256);
      TSTAMP(54 + 2 * sg);
      const float inv = __uint_as_float(0x7f000000u - lds32(sb + T_UN + sg * 4));
#pragma unroll 1
      for (int j = 0; j < 4; j += 2) {
        float c[2][3][4];
        uint32_t x[4], y[4], z[2][4];
#pragma unroll
        for (int e = 0; e < 2; e++) {
          const uint32_t oa = sb + T_OA + ((sg * 4 + j + e) * 8 + g) * 64 + (blockIdx.x / 3 * 36 & 15) + t * 4;
          z[e][0] = lds32(oa); z[e][1] = lds32(oa + 16); z[e][2] = t ? 0u : lds32(oa + 32);
        }
#pragma unroll
        for (int i = 0; i < 3; i++) {
          const uint32_t wa = sb + T_WA + ((lane & 7) + ((lane >> 4) << 3)) * 128 + (((w + 4 * (m & 1)) ^ (lane & 7)) << 4);
          ldsm4t(x, wa + i * 3072); ldsm2t(y, wa + i * 3072 + 2048);
#pragma unroll
          for (int e = 0; e < 2; e++) { mma1688z(c[e][i], y[0], y[1], z[e][2]); mma16816(c[e][i], x, z[e][0], z[e][1]); }
        }
#pragma unroll
        for (int r = 0; r < 4; r++) {
          ldsm4t(z[0], ob + j * 2048 + r * 512); ldsm4t(z[1], ob + j * 2048 + 2048 + r * 512);
          lds128(l16 + SM_WO3 + w * 512 + r * 2048, x); lds128(l16 + SM_WO3 + w * 512 + (r + 4) * 2048, y);
#pragma unroll
          for (int e = 0; e < 2; e++) { mma16816(c[e][0], wo[r], z[e][0], z[e][1]); mma16816(c[e][1], w1[r], z[e][0], z[e][1]); mma16816(c[e][2], x, z[e][0], z[e][1]); }
#pragma unroll
          for (int e = 0; e < 2; e++) { mma16816(c[e][0], wo[r + 4], z[e][2], z[e][3]); mma16816(c[e][1], w1[r + 4], z[e][2], z[e][3]); mma16816(c[e][2], y, z[e][2], z[e][3]); }
        }
#pragma unroll
        for (int i = 0; i < 4; i++) {
          const float (&d)[3][4] = c[i >> 1];
          const int q = (i & 1) * 2;
          red_f16x8(g_red + T_RED + ((((sg * 4 + j + (i >> 1)) * 3 + RANK) * 4 + w) * 2 + (i & 1)) * 512 + lane * 16, pack_f16(d[0][q] * inv, d[0][q + 1] * inv),
                    pack_f16(d[1][q] * inv, d[1][q + 1] * inv), pack_f16(d[2][q] * inv, d[2][q + 1] * inv), 0x3c00u);
        }
      }
      TSTAMP(55 + 2 * sg);
    }
    if (RSLOW) { wait_until(gtime() + 8000); wait_until(gtime() + 8000); wait_until(gtime() + 4000); }
    if (w < 2) {
      const int b = blockIdx.x, lane = LV, g = lane >> 2, t = lane & 3;
      uint4 v;
#pragma unroll 1
      for (int n = 0; n < SPIN_LIMIT; n++) {
        v = ldg_relaxed(g_red + T_RED + (w * 96 + b) * 512 + lane * 16);
        if (__all_sync(0xffffffffu, v.w == 0x5000u)) break;
        __nanosleep(40);
      }
      const float un = __uint_as_float(lds32(sb + T_UN + w * 4));
      uint32_t* const o = (uint32_t*)(tm.out + (size_t)((NAUXSEG + w) * 32 + b / 24 * 8 + g) * DM + (b >> 3) % 3 * 192 + (b & 1) * 32 + (b & 6) * 4) + t;
#pragma unroll
      for (int j = 0; j < 3; j++) {
        const float2 f = __half22float2(*(const __half2*)(&v.x + j));
        o[j * 32] = movm(pack_bf16(f.x * un, f.y * un));
      }
    }
  }
  TSTAMP(3);
  if (CSY) cluster_sync();
}

__global__ void __cluster_dims__(3, 1, 1) __launch_bounds__(384, 1)
rec_kernel(const __grid_constant__ RMaps tm, const bf16* __restrict__ x, const bf16* __restrict__ mem0) {
  extern __shared__ __align__(1024) unsigned char smem_raw[];
  const uint32_t sb = smem_u32(smem_raw);
  const int tid = threadIdx.x, lane = tid & 31;
  const int wg = __shfl_sync(0xffffffffu, tid >> 7, 0);
  const int w = __shfl_sync(0xffffffffu, (tid >> 5) & 3, 0);
  uint32_t rank; asm("mov.u32 %0, %%cluster_ctarank;" : "=r"(rank));
  STAMP(0);
  TSTAMP(0);
  asm volatile("griddepcontrol.launch_dependents;" ::: "memory");

#define PFT 1
  if (PFT && wg == 1 && lane == 0) asm volatile("prefetch.tensormap [%0];\nprefetch.tensormap [%1];" :: "l"(w & 1 ? &tm.woa : &tm.oa), "l"(w == 0 ? (rank < 2 ? &tm.wk : &tm.wv) : w == 1 ? &tm.wq : w == 2 ? &tm.x : &tm.wo) : "memory");
  if (wg < 2) {
    asm volatile("setmaxnreg.inc.sync.aligned.u32 192;");
    if (tid == 0) {
      for (int i = 0; i < 3; i++) { mbar_init(sb + MB_W + 8 * i, 1); mbar_init(sb + MB_X + 8 * i, 1); }
      mbar_init(sb + MB_WO, 1); mbar_init(sb + MB_WO3, 1);
      mbar_init(sb + MB_S, rank < 2 ? 5 : 6);
      mbar_init(sb + MB_F, 1);
      for (int i = 0; i < 3; i++) mbar_init(sb + MB_T + 8 * i, 1);
      mbar_init(sb + MB_VX, 1); mbar_init(sb + MB_VX + 8, 1);
      asm volatile("fence.mbarrier_init.release.cluster;" ::: "memory");
      fence_async();
      SSTAMP(11, 6);
      load_weights(sb, tm, rank, 0);
      for (int i = 0; i < 3; i++) mbar_expect(sb + MB_X + 8 * i, XT);
      tma_load3(sb + SM_X, &tm.x, 0, sb + MB_X);
      if (!PACE) for (int c = 1; c < 4; c++) load_weights(sb, tm, rank, c);
      mbar_expect(sb + MB_S, rank < 2 ? 640 + 2048 : 1280);
      mbar_expect(sb + MB_VX, 8192); mbar_expect(sb + MB_VX + 8, 8192);
      mbar_expect(sb + MB_T, 2048);
      for (int i = 1; i < 3; i++) mbar_expect(sb + MB_T + 8 * i, rank < 2 ? 5120 : 10240);
      SSTAMP(11, 5);
    }
    __syncwarp();
    bar_sync(0, 384);
    proj_role(sb, tm, rank, wg, w, lane);
  } else {
    asm volatile("setmaxnreg.dec.sync.aligned.u32 120;");
    attn_role(sb, smem_raw, tm, rank, x, mem0, w, lane);
  }
}

constexpr int A_XH = 73728;
constexpr int A_NS = 9, A_WM = 6144, A_WT = 768;
constexpr int A_RING = 2 * A_XH, A_TAIL = A_RING + A_NS * A_WM, A_GW = A_TAIL + A_NS * A_WT;
constexpr int A_EPI = 212864, A_EPW = 9344;
constexpr int A_XT = 4 * XT, A_XW = A_XT + 8192, A_EX = A_XW + 8192, A_NR = 4;
constexpr int A_IN = A_EX + 16384, A_OST = A_IN + 3 * SEGB;
constexpr int A_GATE = A_EPI + 2 * A_EPW, A_BAR = A_GATE + 512;
constexpr int A_TOTAL = A_BAR + 384;
struct AMaps { CUtensorMap x, wa, wt, oa, o, o3, wob, woa; };

DI void wgmma_n192_ss_nt(float* d, uint64_t da, uint64_t db, int acc) {
  asm volatile("{\n.reg .pred p;\nsetp.ne.b32 p, %98, 0;\n"
               "wgmma.mma_async.sync.aligned.m64n192k16.f32.bf16.bf16 {"
               "%0,%1,%2,%3,%4,%5,%6,%7,%8,%9,%10,%11,%12,%13,%14,%15,%16,%17,%18,%19,%20,%21,%22,%23,%24,%25,%26,%27,%28,%29,%30,%31,"
               "%32,%33,%34,%35,%36,%37,%38,%39,%40,%41,%42,%43,%44,%45,%46,%47,%48,%49,%50,%51,%52,%53,%54,%55,%56,%57,%58,%59,%60,%61,%62,%63,"
               "%64,%65,%66,%67,%68,%69,%70,%71,%72,%73,%74,%75,%76,%77,%78,%79,%80,%81,%82,%83,%84,%85,%86,%87,%88,%89,%90,%91,%92,%93,%94,%95"
               "}, %96, %97, p, 1, 1, 0, 1;\n}\n"
               : ACC8(d, 0), ACC8(d, 8), ACC8(d, 16), ACC8(d, 24), ACC8(d, 32), ACC8(d, 40), ACC8(d, 48), ACC8(d, 56),
                 ACC8(d, 64), ACC8(d, 72), ACC8(d, 80), ACC8(d, 88) : "l"(da), "l"(db), "r"(acc));
}
#define ACC4(d, o) "+f"(d[o]), "+f"(d[o + 1]), "+f"(d[o + 2]), "+f"(d[o + 3])
DI void wgmma_n24_ss_nt(float* d, uint64_t da, uint64_t db, int acc) {
  asm volatile("{\n.reg .pred p;\nsetp.ne.b32 p, %14, 0;\n"
               "wgmma.mma_async.sync.aligned.m64n24k16.f32.bf16.bf16 {%0,%1,%2,%3,%4,%5,%6,%7,%8,%9,%10,%11}, %12, %13, p, 1, 1, 0, 1;\n}\n"
               : ACC8(d, 0), ACC4(d, 8) : "l"(da), "l"(db), "r"(acc));
}
DI void wgmma_n8_ss(float* d, uint64_t da, uint64_t db, int acc) {
  asm volatile("{\n.reg .pred p;\nsetp.ne.b32 p, %6, 0;\n"
               "wgmma.mma_async.sync.aligned.m64n8k16.f32.bf16.bf16 {%0,%1,%2,%3}, %4, %5, p, 1, 1, 0, 0;\n}\n"
               : ACC4(d, 0) : "l"(da), "l"(db), "r"(acc));
}
DI void wgmma_n40_ss_tt(float* d, uint64_t da, uint64_t db, int acc) {
  asm volatile("{\n.reg .pred p;\nsetp.ne.b32 p, %22, 0;\n"
               "wgmma.mma_async.sync.aligned.m64n40k16.f32.bf16.bf16 {%0,%1,%2,%3,%4,%5,%6,%7,%8,%9,%10,%11,%12,%13,%14,%15,%16,%17,%18,%19}, "
               "%20, %21, p, 1, 1, 1, 1;\n}\n"
               : ACC8(d, 0), ACC8(d, 8), ACC4(d, 16) : "l"(da), "l"(db), "r"(acc));
}
DI void wgmma_n64_rs(float* d, const uint32_t* a, uint64_t db, int acc) {
  asm volatile("{\n.reg .pred p;\nsetp.ne.b32 p, %37, 0;\n"
               "wgmma.mma_async.sync.aligned.m64n64k16.f32.bf16.bf16 {"
               "%0,%1,%2,%3,%4,%5,%6,%7,%8,%9,%10,%11,%12,%13,%14,%15,%16,%17,%18,%19,%20,%21,%22,%23,%24,%25,%26,%27,%28,%29,%30,%31"
               "}, {%32,%33,%34,%35}, %36, p, 1, 1, 0;\n}\n"
               : ACC8(d, 0), ACC8(d, 8), ACC8(d, 16), ACC8(d, 24) : "r"(a[0]), "r"(a[1]), "r"(a[2]), "r"(a[3]), "l"(db), "r"(acc));
}
DI void wgmma_n32_ss_tn(float* d, uint64_t da, uint64_t db, int acc) {
  asm volatile("{\n.reg .pred p;\nsetp.ne.b32 p, %18, 0;\n"
               "wgmma.mma_async.sync.aligned.m64n32k16.f32.bf16.bf16 {%0,%1,%2,%3,%4,%5,%6,%7,%8,%9,%10,%11,%12,%13,%14,%15}, "
               "%16, %17, p, 1, 1, 1, 0;\n}\n"
               : ACC8(d, 0), ACC8(d, 8) : "l"(da), "l"(db), "r"(acc));
}
DI void tma_load3c(uint32_t dst, const CUtensorMap* m, int c0, int c1, int c2, uint32_t mb) {
  asm volatile("cp.async.bulk.tensor.3d.shared::cluster.global.mbarrier::complete_tx::bytes [%0], [%1, {%3, %4, %5}], [%2];"
               :: "r"(dst), "l"(m), "r"(mb), "r"(c0), "r"(c1), "r"(c2) : "memory");
}
DI void count_up(unsigned* p) {
  asm volatile("fence.proxy.async;" ::: "memory");
  asm volatile("red.release.gpu.global.add.u32 [%0], 1;" :: "l"(p) : "memory");
}
#define AX 0
#define FDLY 400
#define ORING 63
#define DRY 0
#define FEND 59
DI void publish(unsigned* p) {
  asm volatile("cp.async.bulk.wait_group 0;\nfence.proxy.async;" ::: "memory");
  asm volatile("red.relaxed.gpu.global.add.u32 [%0], 1;" :: "l"(p) : "memory");
}
#define ADLY 0

__global__ void __launch_bounds__(512, 1)
aux_kernel(const __grid_constant__ AMaps tm, const bf16* __restrict__ wqkv, const bf16* __restrict__ woa, const bf16* __restrict__ gate_w, bf16* __restrict__ out) {
  extern __shared__ __align__(1024) unsigned char smem_raw[];
  const uint32_t sb = smem_u32(smem_raw);
  const uint32_t fullx = sb + A_BAR, full1 = fullx + 24, empty1 = full1 + 8 * A_NS, fullw = empty1 + 8 * A_NS, full3 = fullw + 8, empty3 = full3 + 8 * A_NR,
                 fullq = empty3 + 8 * A_NR, fullv = fullq + 8, emptyq = fullv + 8, emptyv = emptyq + 8;
  const int tid = threadIdx.x, lane = tid & 31, cta = blockIdx.x;
  const int wg = __shfl_sync(0xffffffffu, tid >> 7, 0), w = __shfl_sync(0xffffffffu, (tid >> 5) & 3, 0);
  ASTAMP(14);
  if (tid == 384) {
    for (int i = 0; i < 3; i++) mbar_init(fullx + 8 * i, 1);
    for (int i = 0; i < A_NS; i++) { mbar_init(full1 + 8 * i, 1); mbar_init(empty1 + 8 * i, 8); }
    mbar_init(fullw, 1); mbar_init(fullq, 1); mbar_init(fullv, 1); mbar_init(emptyq, 4); mbar_init(emptyv, 4);
    for (int i = 0; i < A_NR; i++) { mbar_init(full3 + 8 * i, 1); mbar_init(empty3 + 8 * i, 4); }
    fence_async();
  }
  __syncthreads();
  ASTAMP(0);
  const int tile = cta >> 1, hh = cta & 1;
  const int nsl = cta >> 2, kq = cta & 3;
  if (wg == 3) {
    asm volatile("setmaxnreg.dec.sync.aligned.u32 24;");
    const bool lead = lane == 0;
    if (w < 3) {
      if (ADLY) wait_until(gtime() + ADLY);
      if (elect_one()) {
        mbar_expect(fullx + 8 * w, 49152);
        for (int p = 0; p < 2; p++)
          asm volatile("cp.async.bulk.tensor.4d.shared::cluster.global.mbarrier::complete_tx::bytes [%0], [%1, {%3, %4, %5, %6}], [%2];"
                       :: "r"(sb + p * A_XH + w * 24576), "l"(&tm.x), "r"(fullx + 8 * w), "r"(0), "r"(p), "r"(57 * tile - 7), "r"(3 * w) : "memory");
      }
#pragma unroll 1
      for (int r = 0; r < 17; r++) {
#pragma unroll 1
        for (int st = w; st < A_NS; st += 3) {
          if (r > 0) mbar_wait(empty1 + 8 * st, ~r & 1);
          if (r < 16 && elect_one()) {
            const int col = hh * 288 + (r >> 2) * 72, row = (r & 3) * 144 + st * 16;
            mbar_expect(full1 + 8 * st, A_WM + (AX & 1 ? 0 : A_WT));
            tma_load3c(sb + A_RING + st * A_WM, &tm.wa, col, row, 0, full1 + 8 * st);
            if (!(AX & 1)) tma_load3c(sb + A_TAIL + st * A_WT, &tm.wt, col + 64, row, 0, full1 + 8 * st);
          }
          __syncwarp();
        }
        if (r == 0 && elect_one())
          for (int j = 0; j < 3; j++)
            asm volatile("cp.async.bulk.prefetch.L2.global [%0], %1;" :: "l"((const char*)wqkv + cta * 55296 + (w * 3 + j) * 6144), "r"(6144) : "memory");
        __syncwarp();
      }
      bar_sync(8, 96);
    }
    const unsigned epoch = lds32(sb + A_BAR + 376);
    if (w == 1 && cta < NH) {
#pragma unroll 1
      for (int seg = 0; seg < NAUXSEG; seg++) {
        bar_arrive(5, 160);
        if (seg > 0 && lead) {
          publish(&g_ocnt[(seg - 1) * 32 + cta / 9 * 8]);
          SSTAMP(9, seg - 1);
        }
        __syncwarp();
        bar_sync(4, 160);
        if (lead && !(AX & 32)) {
          tma_store(&tm.o, sb + A_OST, cta * DH, (seg & ORING) * 32);
          tma_store(&tm.o, sb + A_OST + 4096, cta * DH + 64, (seg & ORING) * 32);
          asm volatile("cp.async.bulk.commit_group;" ::: "memory");
          asm volatile("cp.async.bulk.wait_group.read 0;" ::: "memory");
        }
        __syncwarp();
      }
      if (lead) {
        publish(&g_ocnt[(NAUXSEG - 1) * 32 + cta / 9 * 8]);
        SSTAMP(9, NAUXSEG - 1);
      }
    }
    if (w == 2) {
      if (lead && cta < NH) {
#pragma unroll 1
        for (int seg = 0; seg < NAUXSEG; seg++) {
          const unsigned char* const src = g_seg + ((size_t)(AX & 128 ? 0 : seg % NRING) * 96 + cta * 3) * SEGB;
          SSTAMP(0, seg);
          const uint32_t tw = gtime();
          wait_count(&g_scnt[(seg * 32 + cta) * 8], 3 * (epoch + 1), !(TL & 2) || seg < NAUXSEG - 2);
          if (FDLY && seg < FEND && gtime() - tw > 600) wait_until(gtime() + FDLY);
          SSTAMP(1, seg);
          mbar_wait(emptyq, ~seg & 1);
          if (AX & 8) { mbar_arrive(fullq); mbar_wait(emptyv, ~seg & 1); mbar_arrive(fullv); continue; }
          mbar_expect(fullq, 2 * SEGB);
          asm volatile("cp.async.bulk.shared::cluster.global.mbarrier::complete_tx::bytes [%0], [%1], %2, [%3];"
                       :: "r"(sb + A_IN), "l"(src), "r"(2 * SEGB), "r"(fullq) : "memory");
          mbar_wait(emptyv, ~seg & 1);
          if (seg == 1) wait_count(&g_abar[32], NAUX * (epoch + 1));
          stg_relaxed32(&g_used[cta * 32], epoch * NSEG + seg);
          mbar_expect(fullv, SEGB);
          asm volatile("cp.async.bulk.shared::cluster.global.mbarrier::complete_tx::bytes [%0], [%1], %2, [%3];"
                       :: "r"(sb + A_IN + 2 * SEGB), "l"(src + 2 * SEGB), "r"(SEGB), "r"(fullv) : "memory");
        }
      }
    }
    if (w == 3) {
#pragma unroll 1
      for (int c = 0; c < 4; c++) {
        if (lead) asm volatile("cp.async.bulk.wait_group.read 0;" ::: "memory");
        __syncwarp();
        bar_arrive(11, 160); bar_arrive(12, 160);
#pragma unroll 1
        for (int g = 0; g < 2; g++) {
          bar_sync(13 + g, 160);
          if (lead) {
            asm volatile("cp.async.bulk.tensor.3d.global.shared::cta.bulk_group [%0, {%2, %3, %4}], [%1];"
                         :: "l"(&tm.oa), "r"(sb + A_EPI + g * A_EPW + 1024), "r"(4096 + hh * 288 + c * 72), "r"(g), "r"(57 * tile) : "memory");
            asm volatile("cp.async.bulk.commit_group;" ::: "memory");
          }
        }
      }
      if (lead) asm volatile("cp.async.bulk.wait_group.read 0;" ::: "memory");
      __syncwarp();
      bar_arrive(10, 160);
      if (lead) publish(&g_abar[32]);
    }
    if (w != 0) return;
    if (lead) {
      mbar_expect(fullw, 19 * 8192);
#pragma unroll 1
      for (int k = 0; k < 19; k++) {
        const int kb = k < 18 ? kq * 18 + k : 72;
        const uint32_t dst = sb + (k < 18 ? k * 8192 : A_XW);
        if (kb < 64) tma_load(dst, &tm.wob, nsl * 64, kb * 64, fullw);
        else tma_load(dst, &tm.woa, nsl * 64, (kb - 64) * 64, fullw);
      }
    }
    __syncwarp();
    bar_sync(6, 288);
    if (lead) {
      if (kq == 3) { wait_count(&g_abar[32], NAUX * (epoch + 1)); asm volatile("fence.proxy.async;" ::: "memory"); }
      int avail = 0;
      bool waited = false;
      const unsigned nheads = (kq < 3 ? 9 : 5) * (epoch + 1);
      for (int seg = 0; seg < NAUXSEG; seg++) {
        if (seg >= avail) {
          const int far = min(seg + 3, NAUXSEG - 1);
          if (far > seg && !waited && (int)(ldg_acquire32(&g_ocnt[far * 32 + kq * 8]) - nheads) >= 0) avail = far + 1;
          else { waited = wait_count(&g_ocnt[seg * 32 + kq * 8], nheads, !(TL & 2) || seg < NAUXSEG - 2) && (TL & 4); avail = seg + 1; }
        }
        SSTAMP(5, seg);
        for (int g = 0; g < 2; g++) {
          const int sl = (seg & 1) * 2 + g;
          const bool extra = kq == 3 && g == 0;
          mbar_wait(empty3 + 8 * sl, ((seg >> 1) & 1) ^ 1);
          if (AX & 4) { mbar_arrive(full3 + 8 * sl); continue; }
          mbar_expect(full3 + 8 * sl, XT + (extra ? 4096 : 0));
          tma_load3c(sb + sl * XT, &tm.o3, 0, (kq == 3 && g == 1 ? seg : seg & ORING) * 32, kq * 18 + 9 * g, full3 + 8 * sl);
          if (extra) tma_load(sb + A_XT + (seg & 1) * 4096, &tm.o, 72 * 64, seg * 32, full3 + 8 * sl);
        }
      }
    }
    __syncwarp(); bar_sync(6, 288);
    if (GDW) asm volatile("griddepcontrol.wait;" ::: "memory");
  } else if (wg == 2) {
    asm volatile("setmaxnreg.dec.sync.aligned.u32 88;");
    {
      const unsigned epoch = *(volatile unsigned*)&g_epoch2;
      if ((tid & 127) < 80) { const uint4 g = __ldg((const uint4*)gate_w + min(tid & 127, 71)); sts128(sb + A_GW + (tid & 127) * 16, g.x, g.y, g.z, g.w); }
      fence_async();
      bar_sync(3, 128);
      float gt[2][4];
      const uint32_t d0 = (sb & 0x3FFFF) >> 4;
#pragma unroll 1
      for (int j = 0; j < 3; j++) {
        mbar_wait(fullx + 8 * j, 0);
        WG_FENCE();
#pragma unroll
        for (int k = 0; k < 24; k++)
          wgmma_n8_ss(gt[k & 1], desc_at(d0 + (k & 1) * (A_XH >> 4) + j * 1536 + (k >> 3) * 512 + (k & 6), 16, 1024, 1), desc_at(d0 + (A_GW >> 4) + j * 24 + (k & 30), 16, 128, 0), j | (k >> 1));
        WG_COMMIT();
      }
      WG_WAIT(0);
      if ((lane & 3) == 0)
#pragma unroll
        for (int i = 0; i < 4; i++) {
          const float gv = 1.f / (1.f + __expf(-gt[i >> 1][(i & 1) * 2]));
          const int r = w * 16 + (lane >> 2) + (i & 1) * 8, tok = 2 * (57 * tile - 7 + r) + (i >> 1);
          sts32(sb + A_GATE + ((i >> 1) * 64 + r) * 4, __float_as_uint(gv));
          if (hh == 0 && r >= 7 && tok < S_LEN) g_gate[tok] = gv;
        }
      if (tid == 256) sts32(sb + A_BAR + 376, epoch);
      __syncwarp();
      bar_arrive(7, 384);
      __half2 hw = __float2half2_rn(0.f);
#pragma unroll
      for (int i = 0; i < 9; i++) { const uint4 v = __ldg((const uint4*)woa + cta * 1152 + i * 128 + (tid & 127)); hw = amax4(hw, &v.x); }
      const uint32_t ew = wexp(hw);
      if (lane == 0) atomicMax(&g_amax[0], (unsigned long long)(epoch + 1) << 32 | ew);
      bar_sync(3, 128);
      if (tid == 256) {
        count_up(&g_abar[0]);
        wait_count(&g_abar[0], NAUX * (epoch + 1));
        if (cta == 0) *(volatile unsigned*)&g_epoch2 = epoch + 1;
      }
      __syncwarp();
      bar_sync(10, 160);
    }
    if (cta < NH) {
      const int lim = w * 8 + (lane >> 2) - 2 * (lane & 3);
      const uint32_t oa = sb + A_OST + (w * 8 + (lane & 7)) * 128;
      const uint32_t d0 = ((sb + A_IN) & 0x3FFFF) >> 4;
      uint32_t p[5][4];
#pragma unroll
      for (int n = 0; n < 10; n++) p[n >> 1][1 + (n & 1)] = __shfl_sync(0xffffffffu, lane ^ n, n);
#pragma unroll 1
      for (int seg = 0; seg < NAUXSEG; seg++) {
        const float gt = __ldcg(&g_gate[seg * 32 + w * 8 + (lane >> 2)]);
        float sc[20], d[32];
        mbar_wait(fullq, seg & 1);
        if (tid == 256) SSTAMP(2, seg);
        WG_FENCE();
#pragma unroll
        for (int k = 0; k < 8; k++) {
          const int o = ((k >> 2) * SEGB + (k & 3) * 256) >> 4;
          wgmma_n40_ss_tt(sc, desc_at(d0 + o, 128, 512, 0), desc_at(d0 + o + 256, 128, 1024, 0), k > 0);
        }
        WG_COMMIT();
        WG_WAIT(0);
        if (lane == 0) mbar_arrive(emptyq);
        float a[10];
#pragma unroll
        for (int i = 0; i < 10; i++) {
          a[i] = sc[(i >> 1) * 4 + (i & 1)] * (SM_SCALE * LOG2E);
          if (i < 8 && (i >> 1) * 8 + (i & 1) > lim) a[i] = -1.0e9f * LOG2E;
        }
        float m = max10(a);
        m = fmaxf(m, __shfl_xor_sync(0xffffffffu, m, 1)); m = fmaxf(m, __shfl_xor_sync(0xffffffffu, m, 2));
#pragma unroll
        for (int i = 0; i < 10; i++) a[i] = ex2(a[i] - m);
#pragma unroll
        for (int n = 0; n < 5; n++) {
          p[n][0] = pack_bf16(a[2 * n], a[2 * n + 1]); p[n][3] = p[n][0] | p[n][1];
          asm volatile("" : "+r"(p[n][0]), "+r"(p[n][3]) :: "memory");
        }
        float sum = ((a[0] + a[1]) + (a[2] + a[3])) + ((a[4] + a[5]) + (a[6] + a[7])) + (a[8] + a[9]);
        sum += __shfl_xor_sync(0xffffffffu, sum, 1);
        mbar_wait(fullv, seg & 1);
        WG_FENCE();
#pragma unroll
        for (int n = 0; n < 5; n++) wgmma_n64_rs(d, p[n], n < 4 ? desc_at(d0 + SEGB / 8 + 8 * n, 4096, 512, 0) : desc_at(d0 + SEGB / 8 + 512, 1024, 128, 0), n);
        WG_COMMIT();
        sum += __shfl_xor_sync(0xffffffffu, sum, 2);
        const float f = (1.f - gt) * rcp(sum);
        bar_sync(5, 160);
        WG_WAIT(0);
        if (lane == 0) mbar_arrive(emptyv);
        if (tid == 256) SSTAMP(4, seg);
#pragma unroll
        for (int q = 0; q < 4; q++) {
          const float* const o = d + (q & 1) * 16 + (q & 2);
          stsm4(oa + (q >> 1) * 4096 + ((((q & 1) * 4 + (lane >> 3)) ^ (lane & 7)) << 4), pack_bf16(o[0] * f, o[1] * f), pack_bf16(o[4] * f, o[5] * f),
                pack_bf16(o[8] * f, o[9] * f), pack_bf16(o[12] * f, o[13] * f));
        }
        fence_async();
        bar_sync(4, 160);
      }
    }
  } else {
    asm volatile("setmaxnreg.inc.sync.aligned.u32 200;");
    {
      const int g = lane >> 2, t = lane & 3;
      const uint32_t eb = sb + A_EPI + wg * A_EPW, d0 = (sb & 0x3FFFF) >> 4;
      const uint32_t own = (2 * t <= g ? 0xffffu : 0u) | (2 * t < g ? 0xffff0000u : 0u);
      const int kmin = 7 - 57 * tile - 16 * w;
      __half2 ho = __float2half2_rn(0.f);
#pragma unroll 1
      for (int c = -DRY; c < 4; c++) {
        float acc[96], tl[12];
#pragma unroll 1
        for (int r = c < 0 ? 4 : 0; r < 4; r++) {
#pragma unroll
          for (int st = 0; st < A_NS; st++) {
            const int ks = r * 9 + st;
            if (c == 0 && st % 3 == 0 && ks % 12 == 0) mbar_wait(fullx + 8 * (ks / 12), 0);
            mbar_wait(full1 + 8 * st, r & 1);
            const uint64_t da = desc_at(d0 + wg * (A_XH >> 4) + (ks >> 2) * 512 + (ks & 3) * 2, 16, 1024, 1);
            WG_FENCE();
            wgmma_n192_ss_nt(acc, da, desc_at(d0 + ((A_RING + st * A_WM) >> 4), 2048, 1024, 1), ks);
            if (!(AX & 2)) wgmma_n24_ss_nt(tl, da, desc_at(d0 + ((A_TAIL + st * A_WT) >> 4), 128, 256, 0), ks);
            WG_COMMIT();
            if (st == 0 && r == 2) bar_sync(11 + wg, 160);
            WG_WAIT(1);
            if (ks > 0 && lane == 0) mbar_arrive(empty1 + 8 * ((st + A_NS - 1) % A_NS));
          }
        }
        WG_WAIT(0);
        if (lane == 0 && c >= 0) mbar_arrive(empty1 + 8 * (A_NS - 1));
        ASTAMP(16 + (c & 3));
        uint32_t ql[9], qh[9], kl[9], kh[9], kx[10], vl[9], vh[9], vx[10];
#pragma unroll
        for (int j = 0; j < 9; j++) {
          const float* const q = j < 8 ? acc + 4 * j : tl, * const k = j < 8 ? acc + 32 + 4 * j : tl + 4, * const v = j < 8 ? acc + 64 + 4 * j : tl + 8;
          kh[j] = pack_bf16(k[2], k[3]); vh[j] = pack_bf16(v[2], v[3]);
          ql[j] = pack_bf16(q[0], q[1]); qh[j] = pack_bf16(q[2], q[3]); kl[j] = pack_bf16(k[0], k[1]); vl[j] = pack_bf16(v[0], v[1]);
        }
        if (w < 3) {
          const uint32_t ha = eb + 1024 + w * 2304 + lane * 16;
          stsm4(ha, kh[0], kh[1], kh[2], kh[3]); stsm4(ha + 512, kh[4], kh[5], kh[6], kh[7]);
          stsm4(ha + 1024, vh[0], vh[1], vh[2], vh[3]); stsm4(ha + 1536, vh[4], vh[5], vh[6], vh[7]);
          asm volatile("stmatrix.sync.aligned.m8n8.x2.shared.b16 [%0], {%1,%2};" :: "r"(ha + 2048), "r"(kh[8]), "r"(vh[8]) : "memory");
        }
        if (c == 0) bar_sync(7, 384); else bar_sync(1 + wg, 128);
        {
          const uint32_t ha = eb + 1024 + max(w - 1, 0) * 2304 + lane * 16;
          ldsm4(kx, ha); ldsm4(kx + 4, ha + 512); ldsm4t(vx, ha + 1024); ldsm4t(vx + 4, ha + 1536);
          asm volatile("ldmatrix.sync.aligned.m8n8.x1.shared.b16 {%0}, [%1];" : "=r"(kx[8]) : "r"(ha + 2048) : "memory");
          asm volatile("ldmatrix.sync.aligned.m8n8.x1.trans.shared.b16 {%0}, [%1];" : "=r"(vx[8]) : "r"(ha + 2176) : "memory");
        }
        const float gl = __uint_as_float(lds32(sb + A_GATE + (wg * 64 + w * 16 + g) * 4)), gh = __uint_as_float(lds32(sb + A_GATE + (wg * 64 + w * 16 + g + 8) * 4));
#pragma unroll
        for (int j = 0; j < 9; j++) { vl[j] = movm(vl[j]); vh[j] = movm(vh[j]); }
        bar_sync(1 + wg, 128);
        uint32_t ol[9], oh[9];
#pragma unroll
        for (int i = 0; i < 4; i++) {
          const int b = 2 * i;
          const uint32_t a[4] = {t >= i ? ql[b] : 0u, t >= i ? qh[b] : 0u, ql[b + 1], qh[b + 1]}, a4 = t <= i ? ql[b + 2] : 0u, a5 = t <= i ? qh[b + 2] : 0u;
          float sx[4], sl[4], sh[4];
          mma16816z(sx, a, kx[b], kx[b + 1]); mma16816z(sl, a, kl[b], kl[b + 1]); mma16816z(sh, a, kh[b], kh[b + 1]);
          mma1688(sx, a4, a5, kx[b + 2]); mma1688(sl, a4, a5, kl[b + 2]); mma1688(sh, a4, a5, kh[b + 2]);
          float e[4];
#pragma unroll
          for (int u = 0; u < 4; u++) {
            const int cc = 2 * t + (u & 1);
            e[u] = (cc <= g ? (u < 2 ? sl[u] : sh[u]) : (u < 2 ? sx[u] : sl[u])) * (0.23570226039551584f * LOG2E);
            if ((cc <= g ? cc : cc - 8) + (u & 2) * 4 < kmin) e[u] = -1.0e9f * LOG2E;
          }
          float m0 = fmaxf(e[0], e[1]), m1 = fmaxf(e[2], e[3]);
#pragma unroll
          for (int o = 1; o < 4; o <<= 1) { m0 = fmaxf(m0, __shfl_xor_sync(0xffffffffu, m0, o)); m1 = fmaxf(m1, __shfl_xor_sync(0xffffffffu, m1, o)); }
          e[0] = ex2(e[0] - m0); e[1] = ex2(e[1] - m0); e[2] = ex2(e[2] - m1); e[3] = ex2(e[3] - m1);
          const uint32_t p0 = pack_bf16(e[0], e[1]), p1 = pack_bf16(e[2], e[3]);
          const uint32_t p[4] = {p0 & ~own, 0u, p0 & own, p1 & ~own};
          float s0 = e[0] + e[1], s1 = e[2] + e[3];
#pragma unroll
          for (int o = 1; o < 4; o <<= 1) { s0 += __shfl_xor_sync(0xffffffffu, s0, o); s1 += __shfl_xor_sync(0xffffffffu, s1, o); }
          const float f0 = gl * rcp(s0), f1 = gh * rcp(s1);
#pragma unroll
          for (int j = b; j < b + 3; j++) {
            float o[4];
            mma16816z(o, p, vx[j], vl[j]);
            mma1688(o, 0u, p1 & own, vh[j]);
            const uint32_t lo = pack_bf16(o[0] * f0, o[1] * f0), hi = pack_bf16(o[2] * f1, o[3] * f1);
            if (j > b || i == 0) { ol[j] = lo; oh[j] = hi; }
            else { ol[j] = t >= i ? lo : ol[j]; oh[j] = t >= i ? hi : oh[j]; }
          }
        }
        const uint32_t sa = eb + 16 + (w * 16 + (lane & 15)) * 144 + (lane >> 4) * 16;
#pragma unroll
        for (int j = 0; j < 8; j += 2) stsm4(sa + j * 16, ol[j], oh[j], ol[j + 1], oh[j + 1]);
        asm volatile("stmatrix.sync.aligned.m8n8.x2.shared.b16 [%0], {%1,%2};" :: "r"(sa + 128), "r"(ol[8]), "r"(oh[8]) : "memory");
        ho = amax4(amax4(amax4(amax4(ho, ol), ol + 4), oh), oh + 4);
        ho = __hmax2_nan(__hmax2_nan(ho, __habs2(*(const __half2*)&ol[8])), __habs2(*(const __half2*)&oh[8]));
        if (c == 3 && tile == 17) {
          const uint32_t eo = wexp(ho);
          if (lane == 0) atomicMax(&g_amax[16], (unsigned long long)(lds32(sb + A_BAR + 376) + 1) << 32 | eo);
        }
        fence_async();
        if (c >= 0) bar_arrive(13 + wg, 160); else bar_sync(1 + wg, 128);
        ASTAMP(20 + (c & 3));
      }
    }
    ASTAMP(3);
    uint32_t wa[36][4];
    mbar_wait(fullw, 0);
    const uint32_t la = sb + wg * 73728 + ((lane & 7) + ((lane >> 4) << 3)) * 128 + (((2 * w + ((lane >> 3) & 1)) ^ (lane & 7)) << 4);
#pragma unroll
    for (int k = 0; k < 36; k++) ldsm4t(wa[k], la + k * 2048);
    fence_async();
    bar_sync(6, 288);
    ASTAMP(4);
    float own[4] = {0.f, 0.f, 0.f, 0.f};
    uint4 v[3];
    auto fetch = [&](int seg) {
      const uint4* src = g_part + (((seg & 3) * 36 + cta) * 4) * 128 + (tid & 127);
#pragma unroll
      for (int j = 0; j < 3; j++) v[j] = AX & 16 ? make_uint4(0, 0, 0, 0) : ldg_relaxed(src + ((kq + 1 + j) & 3) * 128);
    };
    auto finish = [&](int seg) {
      const uint32_t tagv = ((seg >> 2) + 1) & 3;
      int n = 0;
#pragma unroll 1
      while (!(AX & 16) && __any_sync(0xffffffffu, (v[0].x & 3) != tagv || (v[1].x & 3) != tagv || (v[2].x & 3) != tagv) && ++n < SPIN_LIMIT) {
        if (seg < NAUXSEG - ((TL & 2) ? 2 : 1)) __nanosleep(200);
        fetch(seg);
      }
#pragma unroll
      for (int j = 0; j < 3; j++) {
        own[0] += __uint_as_float(v[j].x & ~3u); own[1] += __uint_as_float(v[j].y); own[2] += __uint_as_float(v[j].z); own[3] += __uint_as_float(v[j].w);
      }
      uint32_t p0 = pack_bf16(own[0], own[1]), p1 = pack_bf16(own[2], own[3]);
      asm volatile("movmatrix.sync.aligned.m8n8.trans.b16 %0, %0;" : "+r"(p0));
      asm volatile("movmatrix.sync.aligned.m8n8.trans.b16 %0, %0;" : "+r"(p1));
      uint32_t* o = (uint32_t*)(out + (size_t)(seg * 32 + kq * 8 + (lane >> 2)) * DM + nsl * 64 + w * 16) + (lane & 3);
      o[0] = p0; o[4] = p1;
    };
    float acc[16];
    auto stream = [&](int sl, int keep) {
      const uint64_t db = make_desc(sb + sl * XT, 16, 1024, 1);
      WG_FENCE();
#pragma unroll
      for (int k = 0; k < 36; k++) wgmma_n32_rs(acc, wa[k][0], wa[k][1], wa[k][2], wa[k][3], db + (k >> 2) * 256 + (k & 3) * 2, k ? 1 : keep);
      WG_COMMIT();
    };
    const uint32_t ex = sb + A_EX + (tid & 127) * 16;
    if (wg == 0) {
#pragma unroll
      for (int i = 0; i < 16; i++) acc[i] = 0.f;
#pragma unroll 1
      for (int seg = 0; seg < NAUXSEG; seg++) {
        const int sl = (seg & 1) * 2;
        mbar_wait(full3 + 8 * sl, (seg >> 1) & 1);
        if (kq == 3) {
          const uint64_t da = make_desc(sb + A_XW, 8192, 1024, 1), de = make_desc(sb + A_XT + (seg & 1) * 4096, 16, 1024, 1);
          WG_FENCE();
#pragma unroll
          for (int j = 0; j < 4; j++) wgmma_n32_ss_tn(acc, da + j * 128, de + j * 2, j);
          WG_COMMIT();
          WG_WAIT(0);
        }
        if (!(AX & 64)) stream(sl, kq == 3);
        bar_arrive(9, 256);
        WG_WAIT(0);
        if (lane == 0) mbar_arrive(empty3 + 8 * sl);
#pragma unroll
        for (int i = 0; i < 4; i++)
          sts128(ex + (seg & 1) * 8192 + i * 2048, __float_as_uint(acc[4 * i]), __float_as_uint(acc[4 * i + 1]), __float_as_uint(acc[4 * i + 2]), __float_as_uint(acc[4 * i + 3]));
        bar_sync(1, 256);
      }
    } else {
#pragma unroll 1
      for (int seg = 0; seg < NAUXSEG; seg++) {
        const int sl = (seg & 1) * 2 + 1;
        mbar_wait(full3 + 8 * sl, (seg >> 1) & 1);
        if (tid == 128) SSTAMP(6, seg);
        bar_sync(9, 256);
        if (!(AX & 64)) stream(sl, 0);
        bar_sync(1, 256);
        fetch(max(seg - 1, 0));
        WG_WAIT(0);
        if (lane == 0) mbar_arrive(empty3 + 8 * sl);
        float nxt[4] = {0.f, 0.f, 0.f, 0.f};
        uint4* dst = g_part + (((seg & 3) * 36 + nsl * 4) * 4 + kq) * 128 + (tid & 127);
#pragma unroll
        for (int j = 0; j < 4; j++) {
          float o[4];
          lds128f(ex + (seg & 1) * 8192 + j * 2048, o);
#pragma unroll
          for (int i = 0; i < 4; i++) { o[i] += acc[4 * j + i]; if (j == kq) nxt[i] = o[i]; }
          if (j != kq && !(AX & 16)) stg_relaxed(dst + j * 512, (__float_as_uint(o[0]) & ~3u) | (((seg >> 2) + 1) & 3), __float_as_uint(o[1]), __float_as_uint(o[2]), __float_as_uint(o[3]));
        }
        if (tid == 128) SSTAMP(7, seg);
        if (seg > 0) finish(seg - 1);
        if (tid == 128) SSTAMP(8, seg);
#pragma unroll
        for (int i = 0; i < 4; i++) own[i] = nxt[i];
        if ((seg & 7) == 6) ASTAMP(5 + (seg >> 3));
      }
      fetch(NAUXSEG - 1);
      finish(NAUXSEG - 1);
    }
    ASTAMP(13);
    TSTAMP(48);
    bar_sync(6, 288);
  }
}

typedef CUresult (*EncodeFn)(CUtensorMap*, CUtensorMapDataType, cuuint32_t, void*, const cuuint64_t*, const cuuint64_t*,
                             const cuuint32_t*, const cuuint32_t*, CUtensorMapInterleave, CUtensorMapSwizzle,
                             CUtensorMapL2promotion, CUtensorMapFloatOOBfill);
static void make_map(EncodeFn enc, CUtensorMap* m, const void* p, int rows, int cols, int box_rows) {
  cuuint64_t dims[2] = {(cuuint64_t)cols, (cuuint64_t)rows};
  cuuint64_t strides[1] = {(cuuint64_t)cols * 2};
  cuuint32_t box[2] = {64, (cuuint32_t)box_rows};
  cuuint32_t es[2] = {1, 1};
  enc(m, CU_TENSOR_MAP_DATA_TYPE_BFLOAT16, 2, (void*)p, dims, strides, box, es, CU_TENSOR_MAP_INTERLEAVE_NONE,
      CU_TENSOR_MAP_SWIZZLE_128B, CU_TENSOR_MAP_L2_PROMOTION_L2_128B, CU_TENSOR_MAP_FLOAT_OOB_FILL_NONE);
}

constexpr int g_poll = POLL_NS;
extern "C" void kernel_launch(void* const* d_in, const int* in_sizes, int n_in, void* d_out, int out_size) {
  const bf16* x = (const bf16*)d_in[0];
  const bf16* wqkvA = (const bf16*)d_in[1];
  const bf16* woA = (const bf16*)d_in[2];
  const bf16* mem0 = (const bf16*)d_in[4];
  const bf16* Wq = (const bf16*)d_in[5];
  const bf16* Wk = (const bf16*)d_in[6];
  const bf16* Wv = (const bf16*)d_in[7];
  const bf16* Wo = (const bf16*)d_in[8];
  const bf16* gate_w = (const bf16*)d_in[10];
  static EncodeFn enc = nullptr;
  static void *pO = nullptr, *pR = nullptr;
  if (!enc) {
    cudaDriverEntryPointQueryResult qr;
    cudaGetDriverEntryPoint("cuTensorMapEncodeTiled", (void**)&enc, cudaEnableDefault, &qr);
    cudaGetSymbolAddress(&pO, g_Ocat);
    cudaGetSymbolAddress(&pR, g_red_raw);
    cudaFuncSetAttribute(rec_kernel, cudaFuncAttributeMaxDynamicSharedMemorySize, SM_TOTAL);
    cudaFuncSetAttribute(aux_kernel, cudaFuncAttributeMaxDynamicSharedMemorySize, A_TOTAL);
  }
  RMaps rm;
  rm.poll = g_poll; rm.out = (bf16*)d_out;
  make_map(enc, &rm.woa, woA, DM, DM, 24);
  {
    cuuint64_t dims[2] = {KCAT, S_LEN}, strides[1] = {KCAT * 2};
    cuuint32_t box[2] = {32, 64}, es[2] = {1, 1};
    enc(&rm.oa, CU_TENSOR_MAP_DATA_TYPE_BFLOAT16, 2, pO, dims, strides, box, es, CU_TENSOR_MAP_INTERLEAVE_NONE,
        CU_TENSOR_MAP_SWIZZLE_NONE, CU_TENSOR_MAP_L2_PROMOTION_NONE, CU_TENSOR_MAP_FLOAT_OOB_FILL_NONE);
  }
  rm.red = (unsigned char*)(((uintptr_t)pR + 262143) & ~(uintptr_t)262143);
  {
    cuuint64_t dims[3] = {64, S_LEN, 9}, strides[2] = {DM * 2, 128};
    cuuint32_t box[3] = {64, 32, 9}, es[3] = {1, 1, 1};
    enc(&rm.x, CU_TENSOR_MAP_DATA_TYPE_BFLOAT16, 3, (void*)x, dims, strides, box, es, CU_TENSOR_MAP_INTERLEAVE_NONE,
        CU_TENSOR_MAP_SWIZZLE_128B, CU_TENSOR_MAP_L2_PROMOTION_L2_128B, CU_TENSOR_MAP_FLOAT_OOB_FILL_NONE);
  }
  make_map(enc, &rm.wq, Wq, DM, 4096, 192);
  make_map(enc, &rm.wk, Wk, DM, 4096, 192);
  make_map(enc, &rm.wv, Wv, DM, 4096, 192);
  make_map(enc, &rm.wo, Wo, 4096, DM, 128);
  AMaps am;
  {
    cuuint32_t es[4] = {1, 1, 1, 1};
    cuuint64_t dx[4] = {64, 2, S_LEN / 2, 9}, sx[3] = {DM * 2, DM * 4, 128};
    cuuint32_t bx[4] = {64, 1, 64, 3};
    enc(&am.x, CU_TENSOR_MAP_DATA_TYPE_BFLOAT16, 4, (void*)x, dx, sx, bx, es, CU_TENSOR_MAP_INTERLEAVE_NONE,
        CU_TENSOR_MAP_SWIZZLE_128B, CU_TENSOR_MAP_L2_PROMOTION_L2_128B, CU_TENSOR_MAP_FLOAT_OOB_FILL_NONE);
    cuuint64_t dw[3] = {DM, DM, 3}, sw[2] = {DM * 6, DM * 2};
    cuuint32_t bw[3] = {64, 16, 3}, bt[3] = {8, 16, 3};
    enc(&am.wa, CU_TENSOR_MAP_DATA_TYPE_BFLOAT16, 3, (void*)wqkvA, dw, sw, bw, es, CU_TENSOR_MAP_INTERLEAVE_NONE,
        CU_TENSOR_MAP_SWIZZLE_128B, CU_TENSOR_MAP_L2_PROMOTION_L2_128B, CU_TENSOR_MAP_FLOAT_OOB_FILL_NONE);
    enc(&am.wt, CU_TENSOR_MAP_DATA_TYPE_BFLOAT16, 3, (void*)wqkvA, dw, sw, bt, es, CU_TENSOR_MAP_INTERLEAVE_NONE,
        CU_TENSOR_MAP_SWIZZLE_NONE, CU_TENSOR_MAP_L2_PROMOTION_NONE, CU_TENSOR_MAP_FLOAT_OOB_FILL_NONE);
    cuuint64_t dz[3] = {KCAT, 2, S_LEN / 2}, sz[2] = {KCAT * 2, KCAT * 4};
    cuuint32_t bz[3] = {72, 1, 57};
    enc(&am.oa, CU_TENSOR_MAP_DATA_TYPE_BFLOAT16, 3, pO, dz, sz, bz, es, CU_TENSOR_MAP_INTERLEAVE_NONE,
        CU_TENSOR_MAP_SWIZZLE_NONE, CU_TENSOR_MAP_L2_PROMOTION_NONE, CU_TENSOR_MAP_FLOAT_OOB_FILL_NONE);
  }
  {
    cuuint64_t dims[3] = {64, S_LEN, KCAT / 64}, strides[2] = {KCAT * 2, 128};
    cuuint32_t box[3] = {64, 32, 9}, es[3] = {1, 1, 1};
    make_map(enc, &am.o, pO, S_LEN, KCAT, 32);
    enc(&am.o3, CU_TENSOR_MAP_DATA_TYPE_BFLOAT16, 3, pO, dims, strides, box, es, CU_TENSOR_MAP_INTERLEAVE_NONE,
        CU_TENSOR_MAP_SWIZZLE_128B, CU_TENSOR_MAP_L2_PROMOTION_L2_128B, CU_TENSOR_MAP_FLOAT_OOB_FILL_NONE);
  }
  make_map(enc, &am.wob, Wo, 4096, DM, 64);
  make_map(enc, &am.woa, woA, DM, DM, 64);

  rec_kernel<<<96, 384, SM_TOTAL, cudaStreamPerThread>>>(rm, x, mem0);
  cudaLaunchConfig_t cfg = {};
  cfg.gridDim = dim3(NAUX); cfg.blockDim = dim3(512); cfg.dynamicSmemBytes = A_TOTAL; cfg.stream = cudaStreamPerThread;
  cudaLaunchAttribute at[1];
  at[0].id = cudaLaunchAttributeProgrammaticStreamSerialization; at[0].val.programmaticStreamSerializationAllowed = 1;
  cfg.attrs = at; cfg.numAttrs = 1;
  if (XP & 16) cfg.numAttrs = 0;
  if (!(XP & 64)) cudaLaunchKernelEx(&cfg, aux_kernel, am, wqkvA, woA, gate_w, (bf16*)d_out);
}
```

```cpp
#include <cuda_runtime.h>
#include <cuda_bf16.h>
#include <cuda_fp16.h>
#include <cuda.h>
#include <stdint.h>

typedef __nv_bfloat16 bf16;

constexpr int S_LEN = 2048, DM = 576, NH = 32, DH = 128, NSEG = 64, KCAT = 4096 + 576;
constexpr int NAUXSEG = NSEG - 2;
constexpr int NAUX = 36;
#define RED_LINE(i) (((i) >> 2) * 4096 + ((i) & 1) * 256 + ((i) & 2) * 512)
#define RED_SLOT(s) (((s) & 1) * 128 + ((s) & 2) * 256)

#define POLL_NS 896
#define NII 18
#define W3PRE 4
#define W3MID 4
#define GF 0
#define B5POS 0
#define NUP 4
#define UPF 1
#define B3Q 9
#define B3F 0
#define GATE 7
#define NTL 2
#define B7R 1
#define VS0 1
#define VS1 0
#define VLATE(w) ((w) == 0 ? VS0 == 1 : (w) == 1 ? VS1 == 1 : false)
#define HOIST 1
#define GDW 0
#define RSLOW 0
#define CSY 0
#define DD 2
#define N12 18
#define N14 18
#define HP 0
#define HL 0
#define WL 1
#define RV 3
#define RET 1
#define TL 6
#define CLR 1
#define RFW 0
#define NIC 0
#define LEAD 0
#define FIN16 1
#define VXG 0
#define NRING 20
#define EXD 0
#define HDLY 0
#define F10 1
#define NPROBE 2
#define QM 0
#define N5 224
#define KP(i) (((i) >> 1) + 4 * ((i) & 1))
#define SPIN_LIMIT (1 << 14)
#define XP 0

__device__ __align__(1024) bf16 g_Ocat[S_LEN * KCAT];
__device__ __align__(1024) unsigned char g_red_raw[2 * 262144];
constexpr int HINT_OFF = 2048;
__device__ __align__(16) float g_gate[S_LEN];
__device__ __align__(128) uint4 g_stats[96 * 2];
__device__ unsigned g_epoch;
__device__ unsigned g_epoch2;
__device__ unsigned g_ocnt[NSEG * 32];
__device__ unsigned g_abar[3 * 32];
__device__ unsigned long long g_amax[2 * 16];
__device__ unsigned g_scnt[NSEG * 32 * 8];
__device__ __align__(1024) unsigned char g_seg[NRING * 96 * 10240];
__device__ unsigned g_used[NH * 32];
__device__ __align__(1024) uint4 g_part[4 * 36 * 4 * 128];
__device__ int g_err;
#define TSTAMP(i)
#define PROF(idx)
#define PROFP(idx)
#define RSTAMP(k)
#define STAMP(idx)
#define ASTAMP(idx)
#define SSTAMP(k, seg)
#define WSTAMP(idx)

#define DI __device__ __forceinline__
DI uint32_t smem_u32(const void* p) { return (uint32_t)__cvta_generic_to_shared(p); }
DI uint32_t clock32() { uint32_t c; asm volatile("mov.u32 %0, %%clock;" : "=r"(c) :: "memory"); return c; }
DI uint32_t gtime() { uint32_t c; asm volatile("mov.u32 %0, %%globaltimer_lo;" : "=r"(c) :: "memory"); return c; }
DI uint32_t ldg_relaxed32(const void* p) { uint32_t v; asm volatile("ld.relaxed.gpu.global.b32 %0, [%1];" : "=r"(v) : "l"(p) : "memory"); return v; }
DI uint32_t ldg_acquire32(const void* p) { uint32_t v; asm volatile("ld.acquire.gpu.global.b32 %0, [%1];" : "=r"(v) : "l"(p) : "memory"); return v; }
DI void stg_relaxed32(void* p, uint32_t v) { asm volatile("st.relaxed.gpu.global.b32 [%0], %1;" :: "l"(p), "r"(v) : "memory"); }
DI int head_id() { int c; asm volatile("mov.u32 %0, %%clusterid.x;" : "=r"(c)); return c; }
DI uint32_t mapa(uint32_t a, uint32_t r) { uint32_t o; asm("mapa.shared::cluster.u32 %0, %1, %2;" : "=r"(o) : "r"(a), "r"(r)); return o; }
DI void cluster_arrive() { asm volatile("barrier.cluster.arrive.relaxed.aligned;" ::: "memory"); }
DI void cluster_wait() { asm volatile("barrier.cluster.wait.aligned;" ::: "memory"); }
DI void cluster_sync() { asm volatile("barrier.cluster.arrive.release.aligned;\nbarrier.cluster.wait.acquire.aligned;" ::: "memory"); }
DI void mbar_init(uint32_t b, uint32_t c) { asm volatile("mbarrier.init.shared::cta.b64 [%0], %1;" :: "r"(b), "r"(c) : "memory"); }
DI void mbar_expect(uint32_t b, uint32_t tx) { asm volatile("mbarrier.arrive.expect_tx.shared::cta.b64 _, [%0], %1;" :: "r"(b), "r"(tx) : "memory"); }
DI void mbar_arrive(uint32_t b) { asm volatile("mbarrier.arrive.shared::cta.b64 _, [%0];" :: "r"(b) : "memory"); }
DI void mbar_wait(uint32_t b, uint32_t par) {
  asm volatile("{\n.reg .pred p;\n.reg .u32 n, q;\nmov.u32 n, 0;\n"
               "WL: add.u32 n, n, 1;\nshr.u32 q, n, 12;\nxor.b32 q, q, %1;\n"
               "mbarrier.try_wait.parity.shared::cta.b64 p, [%0], q;\n@!p bra.uni WL;\n}"
               :: "r"(b), "r"(par) : "memory");
}
DI void mbar_wait_fast(uint32_t b, uint32_t par) {
  asm volatile("{\n.reg .pred p;\n.reg .u32 n, q;\nmbarrier.try_wait.parity.shared::cta.b64 p, [%0], %1;\n@p bra.uni WD;\nmov.u32 n, 0;\n"
               "WL: add.u32 n, n, 1;\nshr.u32 q, n, 12;\nxor.b32 q, q, %1;\n"
               "mbarrier.try_wait.parity.shared::cta.b64 p, [%0], q;\n@!p bra.uni WL;\nWD:\n}"
               :: "r"(b), "r"(par) : "memory");
}
DI void wait_until(uint32_t t) {
  const uint32_t now = gtime();
  t = min(t, now + 8192);
  asm volatile("{\n.reg .pred p;\n.reg .u32 c;\nTL: mov.u32 c, %%globaltimer_lo;\nsetp.lt.u32 p, c, %0;\n@p bra.uni TL;\n}" :: "r"(t) : "memory");
}
#define PIN(v) v = __shfl_xor_sync(0xffffffffu, v, 0)
#define SCHED_FENCE(k) asm volatile("{\n.reg .pred p;\nsetp.eq.u32 p, %0, %1;\n@p exit;\n}" :: "r"(fence_reg), "r"(k) : "memory")
#define MEM_ORDER(k) asm volatile("{\n.reg .pred p;\nsetp.eq.u32 p, %0, %1;\n@p st.shared.u32 [%0], %0;\n}" :: "r"(fence_reg), "r"(k + 64) : "memory")
DI void bar_sync(int id, int n) { asm volatile("bar.sync %0, %1;" :: "r"(id), "r"(n) : "memory"); }
DI void bar_arrive(int id, int n) { asm volatile("bar.arrive %0, %1;" :: "r"(id), "r"(n) : "memory"); }
DI void fence_async() { asm volatile("fence.proxy.async.shared::cta;" ::: "memory"); }
DI void st_async4(uint32_t a, uint32_t x, uint32_t y, uint32_t z, uint32_t w, uint32_t mb) {
  asm volatile("st.async.weak.shared::cluster.mbarrier::complete_tx::bytes.v4.b32 [%0], {%1,%2,%3,%4}, [%5];"
               :: "r"(a), "r"(x), "r"(y), "r"(z), "r"(w), "r"(mb) : "memory");
}
DI void st_async2(uint32_t a, uint32_t x, uint32_t y, uint32_t mb) {
  asm volatile("st.async.weak.shared::cluster.mbarrier::complete_tx::bytes.v2.b32 [%0], {%1,%2}, [%3];"
               :: "r"(a), "r"(x), "r"(y), "r"(mb) : "memory");
}
DI void sts32(uint32_t a, uint32_t x) { asm volatile("st.shared.b32 [%0], %1;" :: "r"(a), "r"(x) : "memory"); }
DI void sts64(uint32_t a, uint32_t x, uint32_t y) { asm volatile("st.shared.v2.b32 [%0], {%1,%2};" :: "r"(a), "r"(x), "r"(y) : "memory"); }
DI void sts128(uint32_t a, uint32_t x, uint32_t y, uint32_t z, uint32_t w) {
  asm volatile("st.shared.v4.b32 [%0], {%1,%2,%3,%4};" :: "r"(a), "r"(x), "r"(y), "r"(z), "r"(w) : "memory");
}
DI uint32_t lds32(uint32_t a) { uint32_t x; asm volatile("ld.shared.b32 %0, [%1];" : "=r"(x) : "r"(a) : "memory"); return x; }
DI void lds64(uint32_t a, uint32_t& x, uint32_t& y) { asm volatile("ld.shared.v2.b32 {%0,%1}, [%2];" : "=r"(x), "=r"(y) : "r"(a) : "memory"); }
DI void lds128(uint32_t a, uint32_t* r) {
  asm volatile("ld.shared.v4.b32 {%0,%1,%2,%3}, [%4];" : "=r"(r[0]), "=r"(r[1]), "=r"(r[2]), "=r"(r[3]) : "r"(a) : "memory");
}
DI void lds128f(uint32_t a, float* r) {
  asm volatile("ld.shared.v4.f32 {%0,%1,%2,%3}, [%4];" : "=f"(r[0]), "=f"(r[1]), "=f"(r[2]), "=f"(r[3]) : "r"(a) : "memory");
}
DI void lds64f(uint32_t a, float* r) { asm volatile("ld.shared.v2.f32 {%0,%1}, [%2];" : "=f"(r[0]), "=f"(r[1]) : "r"(a) : "memory"); }
DI void ldsm4t(uint32_t* r, uint32_t a) {
  asm volatile("ldmatrix.sync.aligned.m8n8.x4.trans.shared.b16 {%0,%1,%2,%3}, [%4];"
               : "=r"(r[0]), "=r"(r[1]), "=r"(r[2]), "=r"(r[3]) : "r"(a) : "memory");
}
DI void ldsm4t_in(uint32_t* r, uint32_t a, uint32_t t) {
  asm volatile("{\n.reg .pred p;\nsetp.ne.u32 p, %5, 0;\n@p ldmatrix.sync.aligned.m8n8.x4.trans.shared.b16 {%0,%1,%2,%3}, [%4];\n}"
               : "+r"(r[0]), "+r"(r[1]), "+r"(r[2]), "+r"(r[3]) : "r"(a), "r"(t) : "memory");
}
DI void lds128_in(uint32_t* r, uint32_t a, uint32_t t) {
  asm volatile("{\n.reg .pred p;\nsetp.ne.u32 p, %5, 0;\n@p ld.shared.v4.b32 {%0,%1,%2,%3}, [%4];\n}"
               : "+r"(r[0]), "+r"(r[1]), "+r"(r[2]), "+r"(r[3]) : "r"(a), "r"(t) : "memory");
}
DI void ldsm2t_in(uint32_t* r, uint32_t a, uint32_t t) {
  asm volatile("{\n.reg .pred p;\nsetp.ne.u32 p, %3, 0;\n@p ldmatrix.sync.aligned.m8n8.x2.trans.shared.b16 {%0,%1}, [%2];\n}" : "+r"(r[0]), "+r"(r[1]) : "r"(a), "r"(t) : "memory");
}
DI void reserve2(uint32_t* r) { asm volatile("{\n.reg .u64 t;\nmov.u64 t, %%clock64;\nmov.b64 {%0, %1}, t;\n}" : "=r"(r[0]), "=r"(r[1])); }
DI void scale_sum(float& x, float& y, float s, uint32_t t) {
  asm volatile("{\n.reg .pred p;\nsetp.ne.u32 p, %2, 0;\n@p mul.f32 %0, %0, %1;\n}" : "+f"(y) : "f"(s), "r"(t));
  asm volatile("{\n.reg .pred p;\nsetp.ne.u32 p, %3, 1;\n@p fma.rn.f32 %0, %0, %1, %2;\n}" : "+f"(x) : "f"(s), "f"(y), "r"(t));
}
DI void ldsm4(uint32_t* r, uint32_t a) {
  asm volatile("ldmatrix.sync.aligned.m8n8.x4.shared.b16 {%0,%1,%2,%3}, [%4];"
               : "=r"(r[0]), "=r"(r[1]), "=r"(r[2]), "=r"(r[3]) : "r"(a) : "memory");
}
DI void st_async1(uint32_t a, uint32_t x, uint32_t mb) {
  asm volatile("st.async.weak.shared::cluster.mbarrier::complete_tx::bytes.b32 [%0], %1, [%2];" :: "r"(a), "r"(x), "r"(mb) : "memory");
}
DI void stsm4(uint32_t a, uint32_t x, uint32_t y, uint32_t z, uint32_t w) {
  asm volatile("stmatrix.sync.aligned.m8n8.x4.shared.b16 [%0], {%1,%2,%3,%4};" :: "r"(a), "r"(x), "r"(y), "r"(z), "r"(w) : "memory");
}
DI void stsm4t(uint32_t a, uint32_t x, uint32_t y, uint32_t z, uint32_t w) {
  asm volatile("stmatrix.sync.aligned.m8n8.x4.trans.shared.b16 [%0], {%1,%2,%3,%4};" :: "r"(a), "r"(x), "r"(y), "r"(z), "r"(w) : "memory");
}
DI uint32_t pack_bf16(float lo, float hi) { uint32_t r; asm("cvt.rn.bf16x2.f32 %0, %1, %2;" : "=r"(r) : "f"(hi), "f"(lo)); return r; }
DI uint32_t pack_f16(float lo, float hi) { uint32_t r; asm("cvt.rn.f16x2.f32 %0, %1, %2;" : "=r"(r) : "f"(hi), "f"(lo)); return r; }
DI float ex2(float x) { float y; asm("ex2.approx.ftz.f32 %0, %1;" : "=f"(y) : "f"(x)); return y; }
DI float rcp(float x) { float y; asm("rcp.approx.ftz.f32 %0, %1;" : "=f"(y) : "f"(x)); return y; }
DI float bf_lo(uint32_t x) { return __uint_as_float(x << 16); }
DI float bf_hi(uint32_t x) { return __uint_as_float(x & 0xffff0000u); }
DI void mma16816(float* d, const uint32_t* a, uint32_t b0, uint32_t b1) {
  asm volatile("mma.sync.aligned.m16n8k16.row.col.f32.bf16.bf16.f32 {%0,%1,%2,%3}, {%4,%5,%6,%7}, {%8,%9}, {%0,%1,%2,%3};"
               : "+f"(d[0]), "+f"(d[1]), "+f"(d[2]), "+f"(d[3]) : "r"(a[0]), "r"(a[1]), "r"(a[2]), "r"(a[3]), "r"(b0), "r"(b1));
}
DI void mma16816z(float* d, const uint32_t* a, uint32_t b0, uint32_t b1) {
  asm volatile("mma.sync.aligned.m16n8k16.row.col.f32.bf16.bf16.f32 {%0,%1,%2,%3}, {%4,%5,%6,%7}, {%8,%9}, {%10,%10,%10,%10};"
               : "=f"(d[0]), "=f"(d[1]), "=f"(d[2]), "=f"(d[3]) : "r"(a[0]), "r"(a[1]), "r"(a[2]), "r"(a[3]), "r"(b0), "r"(b1), "f"(0.f));
}
DI void mma1688z(float* d, uint32_t a0, uint32_t a1, uint32_t b0) {
  asm volatile("mma.sync.aligned.m16n8k8.row.col.f32.bf16.bf16.f32 {%0,%1,%2,%3}, {%4,%5}, {%6}, {%7,%7,%7,%7};"
               : "=f"(d[0]), "=f"(d[1]), "=f"(d[2]), "=f"(d[3]) : "r"(a0), "r"(a1), "r"(b0), "f"(0.f));
}
DI void mma1688(float* d, uint32_t a0, uint32_t a1, uint32_t b0) {
  asm volatile("mma.sync.aligned.m16n8k8.row.col.f32.bf16.bf16.f32 {%0,%1,%2,%3}, {%4,%5}, {%6}, {%0,%1,%2,%3};"
               : "+f"(d[0]), "+f"(d[1]), "+f"(d[2]), "+f"(d[3]) : "r"(a0), "r"(a1), "r"(b0));
}
DI void ldsm2t(uint32_t* r, uint32_t a) {
  asm volatile("ldmatrix.sync.aligned.m8n8.x2.trans.shared.b16 {%0,%1}, [%2];" : "=r"(r[0]), "=r"(r[1]) : "r"(a) : "memory");
}
DI uint32_t add_bf16(uint32_t a, uint32_t b) { uint32_t r; asm("add.rn.bf16x2 %0, %1, %2;" : "=r"(r) : "r"(a), "r"(b)); return r; }
DI uint32_t mul_bf16(uint32_t a, uint32_t b) { uint32_t r; asm("mul.rn.bf16x2 %0, %1, %2;" : "=r"(r) : "r"(a), "r"(b)); return r; }
DI uint64_t make_desc(uint32_t addr, uint32_t lbo, uint32_t sbo, uint32_t swz) {
  return (uint64_t)((addr & 0x3FFFF) >> 4) | ((uint64_t)(lbo >> 4) << 16) | ((uint64_t)(sbo >> 4) << 32) | ((uint64_t)swz << 62);
}
DI uint64_t desc_at(uint32_t a16, uint32_t lbo, uint32_t sbo, uint32_t swz) {
  uint64_t d; asm("mov.b64 %0, {%1, %2};" : "=l"(d) : "r"(a16 + ((lbo >> 4) << 16)), "r"((sbo >> 4) | (swz << 30)));
  return d;
}
#define WG_FENCE() asm volatile("wgmma.fence.sync.aligned;" ::: "memory")
#define WG_COMMIT() asm volatile("wgmma.commit_group.sync.aligned;" ::: "memory")
#define WG_WAIT(n) asm volatile("wgmma.wait_group.sync.aligned %0;" :: "n"(n) : "memory")
#define ACC8(d, o) "+f"(d[o]), "+f"(d[o + 1]), "+f"(d[o + 2]), "+f"(d[o + 3]), "+f"(d[o + 4]), "+f"(d[o + 5]), "+f"(d[o + 6]), "+f"(d[o + 7])
DI void wgmma_n32_rs(float* d, uint32_t a0, uint32_t a1, uint32_t a2, uint32_t a3, uint64_t db, int acc) {
  asm volatile("{\n.reg .pred p;\nsetp.ne.b32 p, %21, 0;\n"
               "wgmma.mma_async.sync.aligned.m64n32k16.f32.bf16.bf16 {%0,%1,%2,%3,%4,%5,%6,%7,%8,%9,%10,%11,%12,%13,%14,%15}, "
               "{%16,%17,%18,%19}, %20, p, 1, 1, 0;\n}\n"
               : ACC8(d, 0), ACC8(d, 8) : "r"(a0), "r"(a1), "r"(a2), "r"(a3), "l"(db), "r"(acc));
}
template <int TA>
DI void wgmma_n32_ss(float* d, uint64_t da, uint64_t db, int acc) {
  asm volatile("{\n.reg .pred p;\nsetp.ne.b32 p, %18, 0;\n"
               "wgmma.mma_async.sync.aligned.m64n32k16.f32.bf16.bf16 {%0,%1,%2,%3,%4,%5,%6,%7,%8,%9,%10,%11,%12,%13,%14,%15}, "
               "%16, %17, p, 1, 1, %19, 1;\n}\n"
               : ACC8(d, 0), ACC8(d, 8) : "l"(da), "l"(db), "r"(acc), "n"(TA));
}
DI void tma_load(uint32_t dst, const CUtensorMap* m, int c0, int c1, uint32_t mb) {
  asm volatile("cp.async.bulk.tensor.2d.shared::cluster.global.mbarrier::complete_tx::bytes [%0], [%1, {%3, %4}], [%2];"
               :: "r"(dst), "l"(m), "r"(mb), "r"(c0), "r"(c1) : "memory");
}
DI void tma_load3(uint32_t dst, const CUtensorMap* m, int row, uint32_t mb) {
  asm volatile("cp.async.bulk.tensor.3d.shared::cluster.global.mbarrier::complete_tx::bytes [%0], [%1, {%3, %4, %3}], [%2];"
               :: "r"(dst), "l"(m), "r"(mb), "r"(0), "r"(row) : "memory");
}
DI bool elect_one() {
  uint32_t p;
  asm volatile("{\n.reg .pred p;\nelect.sync _|p, 0xffffffff;\nselp.u32 %0, 1, 0, p;\n}" : "=r"(p));
  return p;
}
DI void bulk_s2s(uint32_t dst, uint32_t src, uint32_t bytes, uint32_t mb) {
  asm volatile("cp.async.bulk.shared::cluster.shared::cta.mbarrier::complete_tx::bytes [%0], [%1], %2, [%3];"
               :: "r"(dst), "r"(src), "r"(bytes), "r"(mb) : "memory");
}
DI void tma_prefetch(const CUtensorMap* m, int c0, int c1) {
  asm volatile("cp.async.bulk.prefetch.tensor.2d.L2.global.tile [%0, {%1, %2}];" :: "l"(m), "r"(c0), "r"(c1) : "memory");
}
DI void tma_store(const CUtensorMap* m, uint32_t src, int c0, int c1) {
  asm volatile("cp.async.bulk.tensor.2d.global.shared::cta.bulk_group [%0, {%2, %3}], [%1];" :: "l"(m), "r"(src), "r"(c0), "r"(c1) : "memory");
}
DI uint4 ldg_relaxed(const void* p) {
  uint4 v;
  asm volatile("ld.relaxed.gpu.global.v4.b32 {%0,%1,%2,%3}, [%4];" : "=r"(v.x), "=r"(v.y), "=r"(v.z), "=r"(v.w) : "l"(p) : "memory");
  return v;
}
DI void stg_relaxed(void* p, uint32_t x, uint32_t y, uint32_t z, uint32_t w) {
  asm volatile("st.relaxed.gpu.global.v4.b32 [%0], {%1,%2,%3,%4};" :: "l"(p), "r"(x), "r"(y), "r"(z), "r"(w) : "memory");
}
DI void red_f16x8(void* p, uint32_t x, uint32_t y, uint32_t z, uint32_t w) {
  asm volatile("red.relaxed.gpu.global.add.noftz.v4.f16x2 [%0], {%1,%2,%3,%4};" :: "l"(p), "r"(x), "r"(y), "r"(z), "r"(w) : "memory");
}
DI void sq_acc(uint32_t& a, uint32_t x) { asm("fma.rn.bf16x2 %0, %1, %1, %0;" : "+r"(a) : "r"(x)); }
DI __half2 amax4(__half2 h, const uint32_t* v) {
  h = __hmax2_nan(__hmax2_nan(h, __habs2(*(const __half2*)&v[0])), __habs2(*(const __half2*)&v[1]));
  return __hmax2_nan(__hmax2_nan(h, __habs2(*(const __half2*)&v[2])), __habs2(*(const __half2*)&v[3]));
}
DI uint32_t wexp(__half2 h) { const uint32_t u = *(const uint32_t*)&h; return __reduce_max_sync(0xffffffffu, max((u >> 16) & 0x7fffu, u & 0x7fffu)) >> 7; }
DI float max10(const float* a) {
  return fmaxf(fmaxf(fmaxf(fmaxf(a[0], a[1]), fmaxf(a[2], a[3])), fmaxf(fmaxf(a[4], a[5]), fmaxf(a[6], a[7]))), fmaxf(a[8], a[9]));
}
DI float quad_max(float m) {
  return fmaxf(fmaxf(m, __shfl_xor_sync(0xffffffffu, m, 1)), fmaxf(__shfl_xor_sync(0xffffffffu, m, 2), __shfl_xor_sync(0xffffffffu, m, 3)));
}
DI float warp_sum(float v) {
#pragma unroll
  for (int o = 16; o; o >>= 1) v += __shfl_xor_sync(0xffffffffu, v, o);
  return v;
}

constexpr int SM_WO3 = 0;
constexpr int SM_X = 16384;
constexpr int XT = 36864;
constexpr int SM_EXP = 126976;
constexpr int SEGB = 10240;
constexpr int SM_BLK = SM_EXP + 8192;
constexpr int SM_VC = SM_BLK + 4 * SEGB;
constexpr int SM_PART = SM_VC + 16384;
constexpr int SM_QM = SM_PART + 4096;
constexpr int SM_E = SM_QM + 1024;
constexpr int SM_VM = SM_E + 1536;
constexpr int SM_OB = SM_VM + 2048;
constexpr int SM_FB = SM_OB + 2048;
constexpr int SM_STAGE = SM_X + XT;
constexpr int SM_MISC = 210944;
constexpr int SM_WOST = 212992;
constexpr int SM_MEM = SM_WOST;
constexpr int SM_MAX = SM_MEM + 11264;
#define MEM_BLK(q) ((q) / 3 * 4096 + (q) % 3 * 1024)
constexpr int SM_TOTAL = 229376;
constexpr int MB_W = SM_MISC;
constexpr int MB_WO = SM_MISC + 24;
constexpr int MB_WO3 = SM_MISC + 32;
constexpr int MB_X = SM_MISC + 40;
constexpr int MB_S = SM_MISC + 64;
constexpr int MB_F = SM_MISC + 72;
constexpr int MB_VX = SM_MISC + 80;
constexpr int SC_FPAR = SM_MISC + 136;
constexpr int SC_DEAD = SM_MISC + 96;
constexpr int SC_UNSC = SM_MISC + 112;
constexpr int SC_EPOCH = SM_MISC + 128;
constexpr int SC_EXPW = SM_MISC + 132;
constexpr int SC_ONES = SM_MISC + 144;
constexpr int SC_SS = SM_MISC + 160;
constexpr int SC_LAT = SM_MISC + 224;
constexpr int MB_T = SM_MISC + 232;
constexpr int T_SX = SM_X + XT;
constexpr int T_OB = SM_X + 2 * XT;
constexpr int T_WA = T_OB + 16384;
constexpr int T_OA = T_WA + 9216;
constexpr int T_G = T_OA + 4096;
constexpr int T_P = T_G + 512;
constexpr int T_UN = T_G + 256;
constexpr int T_RED = 131072;
constexpr int SC_XMAX = SM_MISC + 256;
constexpr int SC_PROF = 229376;

constexpr float SM_SCALE = 0.08838834764831845f;
constexpr float LOG2E = 1.4426950408889634f;
constexpr float E_LIM = 20.f;

template <bool B> struct BoolC { static constexpr bool value = B; };
struct RMaps { CUtensorMap x, wq, wk, wv, wo, woa, oa; unsigned char* red; bf16* out; uint32_t poll; };

DI uint32_t latest_hint(uint32_t h, uint32_t d, int s) {
  const uint32_t x = (((h | 0xc0c0c0c0u) - ((d >> 5) & 63) * 0x01010101u) & 0x3f3f3f3fu) | ((h ^ (((s >> 2) + 1) & 3) * 0x40404040u) & 0xc0c0c0c0u);
  const uint32_t y = __vmaxu2(x & 0x00ff00ffu, (x >> 8) & 0x00ff00ffu);
  return __reduce_max_sync(0xffffffffu, max(y & 0xffffu, y >> 16));
}
DI uint32_t near_half(uint32_t sb) {
  uint32_t a, b; lds64(sb + SC_LAT, a, b);
  return a > b;
}

template <int RT, int K0, int K1, bool D32 = false, int BAR = 0, int KB = 18>
DI void xproj(float* acc, const uint32_t (&wa)[2][18][4], uint64_t xd) {
  if (XP & 1) return;
  WG_FENCE();
#pragma unroll
  for (int k = K0; k < ((XP & 128) ? K0 + 1 : K1); k++)
  {
    uint64_t d = xd + (uint64_t)(((k >> 1) * 4096 + (k & 1) * 32) >> 4);
    if (D32) asm("mov.b64 %0, {%1, %2};" : "=l"(d) : "r"((uint32_t)xd + (((k >> 1) * 4096 + (k & 1) * 32) >> 4)), "r"((uint32_t)(xd >> 32)));
    wgmma_n32_rs(acc, wa[RT][k][0], wa[RT][k][1], wa[RT][k][2], wa[RT][k][3], d, k != 0);
    if (BAR && k == KB - 1 && KB < 18) bar_arrive(BAR, 256);
  }
  WG_COMMIT();
}

DI void seg_store(int seg, uint32_t sb, uint32_t off, uint32_t bytes) {
  asm volatile("cp.async.bulk.global.shared::cta.bulk_group [%0], [%1], %2;"
               :: "l"(g_seg + ((size_t)(seg % NRING) * 96 + blockIdx.x) * SEGB + off), "r"(sb + SM_BLK + (seg & 3) * SEGB + off), "r"(bytes) : "memory");
  asm volatile("cp.async.bulk.commit_group;" ::: "memory");
}
DI void seg_publish(int seg) {
  asm volatile("cp.async.bulk.wait_group 0;" ::: "memory");
  asm volatile("red.relaxed.gpu.global.add.u32 [%0], 1;" :: "l"(&g_scnt[(seg * 32 + blockIdx.x / 3) * 8]) : "memory");
  SSTAMP(10, seg);
}

#define NAP 64
DI uint32_t movm(uint32_t x) { uint32_t r; asm volatile("movmatrix.sync.aligned.m8n8.trans.b16 %0, %1;" : "=r"(r) : "r"(x)); return r; }
DI bool wait_count(const unsigned* p, unsigned target, bool nap = true) {
  int n = 0;
  unsigned v;
  while (true) {
    asm volatile("ld.acquire.gpu.global.b32 %0, [%1];" : "=r"(v) : "l"(p) : "memory");
    if ((int)(v - target) >= 0 || ++n > SPIN_LIMIT) break;
    if (nap) __nanosleep(NAP);
  }
  return n;
}
#define PACE 1200
#define PORD 0
DI void load_weights(uint32_t sb, const RMaps& tm, uint32_t rank, int c) {
  const int h = blockIdx.x / 3;
  if (c < 3) {
    mbar_expect(sb + MB_W + 8 * c, 49152);
    tma_load(sb + SM_STAGE + c * 49152, rank < 2 ? &tm.wk : &tm.wv, h * DH + (rank == 1 ? 64 : 0), c * 192, sb + MB_W + 8 * c);
    tma_load(sb + SM_STAGE + c * 49152 + 24576, rank < 2 ? &tm.wq : &tm.wv, h * DH + (rank == 0 ? 0 : 64), c * 192, sb + MB_W + 8 * c);
  } else {
    tma_prefetch(&tm.wo, rank * 192, h * DH);
    mbar_expect(sb + MB_WO, 16384);
    mbar_expect(sb + MB_WO3, 32768);
    tma_load(sb + SM_WOST, &tm.wo, rank * 192 + 64, h * DH, sb + MB_WO3);
    tma_load(sb + SM_WO3, &tm.wo, rank * 192 + 128, h * DH, sb + MB_WO3);
  }
}

DI void tail_attention(const uint32_t sb, const uint32_t rank, const int w, const int lane, const int sg, const int bar) {
  const int m = lane >> 3, g = lane >> 2, t = lane & 3;
  const uint32_t l16 = sb + lane * 16, src = l16 + T_SX + sg * 10240 + w * 1280;
  if (rank < 2) {
    const uint32_t base = l16 + SM_BLK + (2 + sg) * SEGB, dst = src + rank * 5120;
    uint32_t qb[2][4];
    ldsm4t(qb[0], base + w * 1024); ldsm4t(qb[1], base + w * 1024 + 512);
#pragma unroll
    for (int j = 0; j < 3; j++) {
      uint32_t kb[4][4];
      float c[4][4];
      const uint32_t ka = base + 4096 + j * 2048 + (m & 1) * (j == 2 ? 128 : 896) - (m >> 1) * 128;
#pragma unroll
      for (int k = 0; k < 4; k += j == 2 ? 2 : 1) ldsm4t(kb[k], ka + k * 256);
      mma16816z(c[0], kb[0], qb[0][0], qb[0][1]); mma16816z(c[1], kb[j == 2 ? 0 : 1], qb[0][2], qb[0][3]);
      mma16816z(c[2], kb[2], qb[1][0], qb[1][1]); mma16816z(c[3], kb[j == 2 ? 2 : 3], qb[1][2], qb[1][3]);
      uint32_t r[4];
#pragma unroll
      for (int i = 0; i < (j == 2 ? 2 : 4); i++) r[i] = __float_as_uint((c[0][i] + c[1][j == 2 ? i + 2 : i]) + (c[2][i] + c[3][j == 2 ? i + 2 : i]));
#pragma unroll
      for (int d = 0; d < 2; d++) {
        const uint32_t to = d ? 2 : rank ^ 1, mb = mapa(sb + MB_T + 8 + 8 * sg, to);
        if (j < 2) st_async4(mapa(dst + j * 512, to), r[0], r[1], r[2], r[3], mb);
        else st_async2(mapa(dst + 1024 - lane * 8, to), r[0], r[1], mb);
      }
      if (j < 2) sts128(dst + j * 512, r[0], r[1], r[2], r[3]); else sts64(dst + 1024 - lane * 8, r[0], r[1]);
    }
  }
  TSTAMP(50 + 2 * sg);
  uint32_t vx[4][4], vm[4];
  const uint32_t va = l16 + (rank < 2 ? SM_VC + sg * 8192 : SM_BLK + (2 + sg) * SEGB) + w * 1024 + (m & 1) * 384 - (m >> 1) * 128;
#pragma unroll
  for (int i = 0; i < 4; i++) ldsm4(vx[i], va + (i & 1) * 4096 + (i >> 1) * 256);
  if (sg && rank < 2) mbar_wait(sb + MB_T, 0);
  lds128(l16 + (sg ? SM_FB : SM_VM) + w * 512, vm);
  float a[10], b[10];
  mbar_wait(sb + MB_T + 8 + 8 * sg, 0);
  TSTAMP(58 + 2 * sg);
  lds128f(src, a); lds128f(src + 512, a + 4); lds64f(src + 1024 - lane * 8, a + 8);
  lds128f(src + 5120, b); lds128f(src + 5632, b + 4); lds64f(src + 6144 - lane * 8, b + 8);
#pragma unroll
  for (int i = 0; i < 10; i++) {
    a[i] = (a[i] + b[i]) * (SM_SCALE * LOG2E);
    if (i < 8 && (i >> 1) * 8 + g > w * 8 + 2 * t + (i & 1)) a[i] = -1.0e9f * LOG2E;
  }
  float m0 = fmaxf(fmaxf(fmaxf(a[0], a[2]), fmaxf(a[4], a[6])), a[8]), m1 = fmaxf(fmaxf(fmaxf(a[1], a[3]), fmaxf(a[5], a[7])), a[9]);
#pragma unroll
  for (int o = 4; o < 32; o <<= 1) { m0 = fmaxf(m0, __shfl_xor_sync(0xffffffffu, m0, o)); m1 = fmaxf(m1, __shfl_xor_sync(0xffffffffu, m1, o)); }
#pragma unroll
  for (int i = 0; i < 10; i++) a[i] = ex2(a[i] - (i & 1 ? m1 : m0));
  float s0 = ((a[0] + a[2]) + (a[4] + a[6])) + a[8], s1 = ((a[1] + a[3]) + (a[5] + a[7])) + a[9];
#pragma unroll
  for (int o = 4; o < 32; o <<= 1) { s0 += __shfl_xor_sync(0xffffffffu, s0, o); s1 += __shfl_xor_sync(0xffffffffu, s1, o); }
  s0 = rcp(s0); s1 = rcp(s1);
#pragma unroll
  for (int i = 0; i < 5; i++) sts32(sb + T_P + sg * 2560 + w * 640 + i * 128 + lane * 4, pack_bf16(a[2 * i] * s0, a[2 * i + 1] * s1));
  mbar_wait(sb + MB_WO, 1);
  bar_sync(bar, 128);
  TSTAMP(59 + 2 * sg);
#pragma unroll
  for (int j = 0; j < 4; j++) {
    uint32_t p[5];
    float o0[4], o1[4], f[2];
    lds64f(sb + T_G + sg * 128 + j * 32 + t * 8, f);
    f[0] = 1.f - f[0]; f[1] = 1.f - f[1];
    ldsm4t(p, l16 + T_P + sg * 2560 + j * 640);
    asm volatile("ldmatrix.sync.aligned.m8n8.x1.trans.shared.b16 {%0}, [%1];" : "=r"(p[4]) : "r"(l16 + T_P + sg * 2560 + j * 640 + 512) : "memory");
    mma16816z(o0, vx[0], p[0], p[1]); mma16816z(o1, vx[1], p[0], p[1]);
    mma16816(o0, vx[2], p[2], p[3]); mma16816(o1, vx[3], p[2], p[3]);
    mma1688(o0, vm[0], vm[1], p[4]); mma1688(o1, vm[2], vm[3], p[4]);
    stsm4(l16 + T_OB + sg * 8192 + j * 2048 + w * 512, pack_bf16(o0[0] * f[0], o0[1] * f[1]), pack_bf16(o0[2] * f[0], o0[3] * f[1]),
          pack_bf16(o1[0] * f[0], o1[1] * f[1]), pack_bf16(o1[2] * f[0], o1[3] * f[1]));
  }
}

DI void proj_role(const uint32_t sb, const RMaps& tm, const uint32_t rank, const int wg, const int w, const int lane) {
  const bool qk = rank < 2;
  uint32_t wa[2][18][4];
  {
    const int rr = (lane & 7) + ((lane >> 4) << 3);
    const uint32_t col = ((2 * w + ((lane >> 3) & 1)) ^ (lane & 7)) << 4;
    float ss = 0.f;
#pragma unroll
    for (int c = 0; c < 3; c++) {
      mbar_wait(sb + MB_W + 8 * c, 0);
      if (threadIdx.x == 0) SSTAMP(11, c);
#pragma unroll
      for (int rt = 0; rt < 2; rt++)
#pragma unroll
        for (int k = 0; k < 6; k++)
          ldsm4t(wa[rt][c * 6 + k], sb + SM_STAGE + c * 49152 + (rt ^ wg) * 24576 + (64 * (k >> 1) + 32 * wg + 16 * (k & 1) + rr) * 128 + col);
      if (c < 2) {
        fence_async();
        bar_sync(3, 256);
        if (threadIdx.x == 0) {
          if (c == 0) tma_load3(sb + SM_X + XT, &tm.x, 32, sb + MB_X + 8);
          else { tma_load(sb + SM_X + 2 * XT, &tm.wo, rank * 192, (blockIdx.x / 3) * DH, sb + MB_WO); SSTAMP(11, 11); }
        }
        __syncwarp();
      }
      uint32_t q[4] = {0, 0, 0, 0};
#pragma unroll
      for (int rt = 0; rt < 2; rt++)
#pragma unroll
        for (int k = 0; k < 6; k++)
#pragma unroll
          for (int i = 0; i < 4; i++) sq_acc(q[i], wa[rt][c * 6 + k][i]);
#pragma unroll
      for (int i = 0; i < 4; i++) ss += bf_lo(q[i]) + bf_hi(q[i]);
    }
    ss = warp_sum(ss);
    fence_async();
    cluster_arrive();
    if (lane == 0) sts32(sb + SC_SS + 4 * (wg * 4 + w), qk ? 0 : __float_as_uint(ss));
    bar_arrive(11, 384);
  }
  STAMP(1);
  mbar_wait(sb + MB_X, 0);
  STAMP(2);

  uint32_t t16 = sb + (w * 32 + lane) * 16;
  uint32_t mem_a = sb + SM_MEM + wg * 512 + lane * 16;
  uint32_t fin_a = sb + (lane & 7) * 16 + SM_BLK + (qk ? (wg ^ 1) * 4096 + w * 256 + (lane & 8) * 16 + (lane & 16) * 64
                                              : wg * 4096 + w * 1024 + (lane & 8) * 64 + (lane & 16) * 8);
  PIN(t16); PIN(mem_a); PIN(fin_a);
  const uint32_t fence_reg = mem_a;
  const uint32_t fin2 = qk ? 2048 : 256;
  float acc[16];
  const uint64_t xd0 = make_desc(sb + SM_X + wg * 64, 16, 1024, 1);
  auto do_export = [&]() {
    WG_WAIT(0);
    uint32_t q[8];
#pragma unroll
    for (int j = 0; j < 8; j++) q[j] = pack_bf16(acc[2 * j], acc[2 * j + 1]);
    sts128(t16 + SM_EXP + wg * 4096, q[0], q[1], q[2], q[3]);
    sts128(t16 + SM_EXP + wg * 4096 + 2048, q[4], q[5], q[6], q[7]);
    if (RET) asm volatile("{\n.reg .pred p;\nsetp.eq.u32 p, %2, 0;\n@p add.u32 %0, %0, 1;\n@p add.u32 %1, %1, 1;\nsetp.eq.and.u32 p, %0, %1, p;\n@p exit;\n}"
                          : "+r"(q[3]), "+r"(q[7]) : "r"(t16) : "memory");
  };
  uint32_t o[8];
  auto import = [&]() { lds128(t16 + SM_EXP + (wg ^ 1) * 4096, o); lds128(t16 + SM_EXP + (wg ^ 1) * 4096 + 2048, o + 4); };
  auto finish = [&](int seg) {
    const uint32_t a = fin_a + (seg & 3) * SEGB;
    WG_WAIT(0);
#pragma unroll
    for (int i = 0; i < 8; i++) o[i] = FIN16 ? add_bf16(pack_bf16(acc[2 * i], acc[2 * i + 1]), o[i]) : pack_bf16(acc[2 * i] + bf_lo(o[i]), acc[2 * i + 1] + bf_hi(o[i]));
    stsm4(a, o[0], o[1], o[2], o[3]);
    stsm4(a + fin2, o[4], o[5], o[6], o[7]);
  };
  auto send_v = [&](int seg, int dst) {
    fence_async();
    if (seg < NSEG && !(XP & 2) && elect_one())
      bulk_s2s(mapa(sb + SM_VC + (seg & 1) * 8192, dst), sb + SM_BLK + (seg & 3) * SEGB, 8192, mapa(sb + MB_VX + (seg & 1) * 8, dst));
    __syncwarp();
  };
  auto wait_v = [&](int seg) {
    if (seg < NSEG && !(XP & 2)) {
      mbar_wait(sb + MB_VX + (seg & 1) * 8, (seg >> 1) & 1);
      if (elect_one()) mbar_expect(sb + MB_VX + (seg & 1) * 8, 8192);
      __syncwarp();
    }
  };
  bar_sync(3, 256);
  xproj<1, 0, 18>(acc, wa, xd0);
  do_export();
  SCHED_FENCE(11);
  xproj<0, 0, 18>(acc, wa, xd0);
  bar_sync(3, 256);
  if (threadIdx.x == 0) SSTAMP(11, 12);
  cluster_wait();
  if (threadIdx.x == 0) SSTAMP(11, 13);
  mbar_wait(sb + MB_X + 8, 0);
  import();
  finish(0);
  SCHED_FENCE(12);
  bar_sync(3, 256);
  uint64_t dA = xd0 + (XT >> 4);
  xproj<1, 0, 18>(acc, wa, dA);
  if (!qk && wg == 0 && w < 2) send_v(0, w);
  do_export();
  if (qk && wg == 0 && w == 0) wait_v(0);
  bar_arrive(13, 384);
  if (!qk) {
    SCHED_FENCE(15);
    xproj<0, 0, 18>(acc, wa, dA);
    if (threadIdx.x == 0 && !(XP & 8)) { mbar_expect(sb + MB_X, XT); tma_load3(sb + SM_X, &tm.x, 96, sb + MB_X); }
    bar_sync(3, 256);
    mbar_wait(sb + MB_X + 16, 0);
    import();
    finish(1);
    SCHED_FENCE(16);
    bar_sync(3, 256);
    dA += XT >> 4;
    xproj<1, 0, 18>(acc, wa, dA);
    if (wg == 0 && ((w == 0 && VS0) || (w == 1 && VS1))) send_v(1, w);
    do_export();
  }
  if (threadIdx.x == 0) SSTAMP(11, 14);
  bar_sync(0, 384);
  const int ro = __shfl_sync(0xffffffffu, near_half(sb) ^ wg, 0);
  STAMP(5);
  const uint32_t always = __shfl_sync(0xffffffffu, lds32(sb + SC_DEAD + 12), 0);
  const int ah = qk ? 1 : 2;
  int b2 = qk ? 2 : 0;
  int s = 0;
  uint32_t hint_lo = (uint32_t)(uint64_t)tm.red + HINT_OFF + blockIdx.x + (lane & 1) * 4096 + (lane >> 1) * 16384;
  PIN(hint_lo);
  auto post_hint = [&]() {
    asm volatile("{\n.reg .pred p;\n.reg .b64 a;\n.reg .u32 t;\nsetp.lt.u32 p, %0, %1;\nmov.b64 a, {%2, %3};\nmov.u32 t, %%globaltimer_lo;\n"
                 "bfe.u32 t, t, 5, 6;\nor.b32 t, t, %4;\n@p st.relaxed.gpu.global.u8 [a], t;\n}"
                 :: "r"(t16), "r"(sb + 128), "r"(hint_lo + RED_SLOT(s)), "r"((uint32_t)((uint64_t)tm.red >> 32)), "r"(((s >> 2) + 1) << 6) : "memory");
  };
  auto memproj = [&](auto second, int id, float u0, float u1, float* r) {
    constexpr bool R1 = decltype(second)::value;
    uint32_t b[NUP][4], b0[4];
    SCHED_FENCE(id);
    bar_sync(R1 ? 2 : 1, 256);
    PROF(0);
    ldsm4t(b0, mem_a);
#pragma unroll
    for (int q = 0; q < NUP; q++) {
      if (R1 && q == 2) {
        bar_sync(11, 256);
        SCHED_FENCE(id + 1);
      }
      ldsm4t(b[q], mem_a + MEM_BLK(q + 1));
    }
    mma16816z(&acc[0], wa[0][0], b0[0], b0[1]);
    mma16816z(&acc[4], wa[1][0], b0[0], b0[1]);
    mma16816z(&acc[8], wa[0][1], b0[2], b0[3]);
    mma16816z(&acc[12], wa[1][1], b0[2], b0[3]);
#pragma unroll
    for (int q = 1; q < 9; q++) {
      uint32_t* const c = b[(q - 1) % NUP];
      mma16816(&acc[0], wa[0][2 * q], c[0], c[1]);
      mma16816(&acc[4], wa[1][2 * q], c[0], c[1]);
      mma16816(&acc[8], wa[0][2 * q + 1], c[2], c[3]);
      mma16816(&acc[12], wa[1][2 * q + 1], c[2], c[3]);
      if (R1 && q + NUP == B3Q) bar_sync(3, 256);
      if (q + NUP < 9) ldsm4t_in(c, mem_a + MEM_BLK(q + NUP), always);
      else if (R1 && q + NUP < 11) lds128_in(c, t16 + SM_PART + (10 - q - NUP) * 2048, always);
      else if (!R1 && GATE && q == GATE) { bar_arrive(11, 256); lds128_in(c, sb + SC_DEAD, always); u0 = u1 = __uint_as_float(c[3]); }
    }
#pragma unroll
    for (int i = 0; i < 8; i++) {
      const float u = i < 4 ? u0 : u1;
      r[i] = R1 ? fmaf(acc[8 + i], u, (acc[i] + __uint_as_float(b[(8 + i / 4) % NUP][i & 3])) * u) : (GATE ? fmaf(acc[i], u, acc[8 + i]) : acc[i] + acc[8 + i]);
    }
  };
  if (ro == 0) {
    auto set_scale = [&]() {
      uint32_t m[8];
      lds128(t16 + SM_MAX - 512, m); lds128(t16 + SM_MAX, m + 4);
      const int em = (wexp(amax4(amax4(*(const __half2*)&m[0], m), m + 4)) >> 3) + (int)(lds32(sb + SC_UNSC + (s & 1) * 8) >> 23) - 15;
      const int ex = max(s ? em : 0, (int)lds32(sb + SC_XMAX + 4 * s)) - 127 + (int)lds32(sb + SC_EXPW);
      sts32(sb + SC_UNSC + (~s & 1) * 8, (127 + min(max(ex, -120), 120)) << 23);
    };
#pragma unroll 1
    while (true) {
      if (s == 8) STAMP(6);
      float r[8];
      memproj(BoolC<false>(), 30, 0.f, 0.f, r);
      sts128(t16 + SM_PART, __float_as_uint(r[0]), __float_as_uint(r[1]), __float_as_uint(r[2]), __float_as_uint(r[3]));
      sts128(t16 + SM_PART + 2048, __float_as_uint(r[4]), __float_as_uint(r[5]), __float_as_uint(r[6]), __float_as_uint(r[7]));
      bar_arrive(3, 256);
      PROF(1);
      bar_sync(9, 256);
      if (s == NSEG - 1) break;
      post_hint();
      if (w == 1) {
        set_scale();
        __syncwarp();
        if (elect_one()) mbar_arrive(sb + MB_S);
      }
      SCHED_FENCE(9);
      bar_sync(5, qk ? N5 : 256);
      PROF(2);
      import();
      xproj<0, 0, NII, (DD & 1) != 0>(acc, wa, dA);
      if (NII < 18) {
        if (qk) bar_sync(7, 384);
        xproj<0, NII, 18>(acc, wa, dA);
        if (!qk) bar_sync(7, 384);
      } else {
        if (F10) WG_WAIT(0);
        bar_sync(10, 256);
        if (F10) SCHED_FENCE(17);
      }
      dA += (int64_t)(b2 ? XT >> 4 : -(XT >> 3));
      finish(s + ah);
      if (qk || !VLATE(w)) bar_arrive(13, 384);
      PROF(6);
      SCHED_FENCE(14);
      bar_sync(12, 256);
      PROF(7);
      xproj<1, 0, 18, (DD & 2) != 0, 14, N14>(acc, wa, dA);
      if (N14 == 18) bar_arrive(14, 256);
      b2 = b2 == 2 ? 0 : b2 + 1;
      s++;
      if (!qk && VLATE(w)) { bar_sync(13, 384); send_v(s + 1, w); }
      PROFP(8);
      do_export();
      s--; RSTAMP(6); s++;
      PROFP(3);
    }
    if (!qk) bar_arrive(5, 256);
    if (w == 0 && elect_one()) {
      const uint32_t h18 = blockIdx.x / 3 * 18;
      mbar_expect(sb + MB_WO, 9216 + 4096 + 256);
      asm volatile("cp.async.bulk.shared::cluster.global.mbarrier::complete_tx::bytes [%0], [%1], 256, [%2];"
                   :: "r"(sb + T_G), "l"(g_gate + NAUXSEG * 32), "r"(sb + MB_WO) : "memory");
      tma_load(sb + T_OA, &tm.oa, 4096 + (h18 & ~7), NAUXSEG * 32, sb + MB_WO);
#pragma unroll 1
      for (int j = 0; j < 3; j++) tma_load(sb + T_WA + j * 3072, &tm.woa, rank * 192 + j * 64, h18, sb + MB_WO);
    }
    if (w == 1) {
      set_scale();
      __syncwarp();
      const int ea = (int)ldg_relaxed32(&g_amax[0]) + (int)ldg_relaxed32(&g_amax[16]) - 254 + 2 + 10 - 15;
      sts32(sb + T_UN + (lane & 1) * 4, (128 + max(min(ea, 120), (int)(lds32(sb + SC_UNSC + 8 - (lane & 1) * 8) >> 23) - 127)) << 23);
    }
    bar_arrive(8, 256);
  } else {
    uint32_t r0;
    float un;
    auto prepare = [&]() {
      un = __uint_as_float(lds32(sb + SC_UNSC + (s & 1) * 8));
      r0 = qk ? (t16 & ~256u) - w * 256 + (((t16 >> 8) ^ wg) & 1 ? SM_QM : SM_BLK + 8192 + (s & 3) * SEGB) : mapa(t16 + (s < NSEG - 1 ? SM_VM : SM_FB), 0);
      PIN(r0); PIN(un);
    };
    prepare();
#pragma unroll 1
    while (true) {
      if (s == 8) STAMP(6);
      float r[8];
      if (qk) {
        const float u0 = wg ? un * (SM_SCALE * LOG2E) : un, u1 = wg ? un : un * (SM_SCALE * LOG2E);
        memproj(BoolC<true>(), 32, u0, u1, r);
        stsm4(r0, pack_bf16(r[0], r[1]), pack_bf16(r[2], r[3]), pack_bf16(r[4], r[5]), pack_bf16(r[6], r[7]));
        bar_arrive(4, 256);
      } else {
        const uint32_t mb = sb + (s < NSEG - 1 ? MB_S : MB_T), r1 = r0 + (1 << 24);
        memproj(BoolC<true>(), 34, un, un, r);
        const uint32_t p0 = pack_bf16(r[0], r[1]), p1 = pack_bf16(r[2], r[3]), p2 = pack_bf16(r[4], r[5]), p3 = pack_bf16(r[6], r[7]);
        const uint32_t v0 = wg ? p2 : p0, v1 = wg ? p3 : p1, v2 = wg ? p0 : p2, v3 = wg ? p1 : p3;
        st_async4(r0, v0, v1, v2, v3, mapa(mb, 0));
        st_async4(r1, v0, v1, v2, v3, mapa(mb, 1));
        bar_arrive(5, 256);
        sts128(r0 + (2 << 24), v0, v1, v2, v3);
        stsm4((t16 & ~256u) - w * 256 + SM_BLK + 8192 + (s & 3) * SEGB + (((t16 >> 8) ^ wg) & 1) * 1024, p0, p1, p2, p3);
        __syncwarp();
        if (elect_one()) mbar_arrive(sb + MB_S);
      }
      if (s == NSEG - 1) break;
      if (!qk) bar_arrive(15, 160);
      PROF(1);
      auto rearm = [&]() { mbar_wait(sb + MB_S, s & 1); if (elect_one()) mbar_expect(sb + MB_S, qk ? 640 + 2048 : 1280); __syncwarp(); };
      if (w == 1) {
        if ((t16 & 384) == 0) stg_relaxed(tm.red + (RED_SLOT(s + 2) + RED_LINE(blockIdx.x)) + (t16 & 112), 0, 0, 0, 0);
      } else if (w == 0) {
        const int tn = s + ah + 1;
        if (RFW) mbar_wait(sb + MB_S, s & 1);
        if (tn + 1 < NSEG && !(XP & 8) && elect_one()) {
          const int b0 = b2 == 2 ? 0 : b2 + 1;
          mbar_expect(sb + MB_X + 8 * b0, XT);
          tma_load3(sb + SM_X + b0 * XT, &tm.x, (tn + 1) * 32, sb + MB_X + 8 * b0);
        }
        if (tn < NSEG && (!(XP & 8) || tn < 3)) mbar_wait(sb + MB_X + 8 * b2, (tn / 3) & 1);
      } else if (w == 2) {
        if (!qk) { if (VS0 == 0) send_v(s + 1, 0); if (VS1 == 0) send_v(s + 1, 1); }
      } else if (qk || !NIC) {
        rearm();
      }
      __syncwarp();
      import();
      PROF(4);
      SCHED_FENCE(10);
      if (NIC) {
        if (qk) bar_sync(7, NII < 18 ? 384 : 256);
        xproj<0, 0, NIC>(acc, wa, dA);
        if (!qk) { if (w == 3) rearm(); bar_sync(7, NII < 18 ? 384 : 256); }
      } else {
        bar_sync(7, NII < 18 ? 384 : 256);
      }
      xproj<0, NIC, 18, (DD & 4) != 0, 12, N12>(acc, wa, dA);
      if (N12 == 18) bar_arrive(12, 256);
      dA += (int64_t)(b2 ? XT >> 4 : -(XT >> 3));
      finish(s + ah);
      if (qk && w == 0) wait_v(s + 1);
      bar_arrive(13, 384);
      PROF(6);
      SCHED_FENCE(13);
      bar_sync(14, 256);
      PROF(7);
      xproj<1, 0, 18, (DD & 8) != 0>(acc, wa, dA);
      b2 = b2 == 2 ? 0 : b2 + 1;
      s++;
      if (HOIST) prepare();
      PROFP(8);
      do_export();
      if (!HOIST) prepare();
      s--; RSTAMP(7); s++;
      PROFP(3);
    }
    TSTAMP(2);
    bar_sync(3, 128);
    tail_attention(sb, rank, w, lane, 1, 3);
    bar_arrive(0, 256);
  }
  STAMP(3);
  if (CSY) cluster_sync();
  STAMP(4);
}

DI void attn_role(const uint32_t sb, unsigned char* smem_raw, const RMaps& tm, const uint32_t RANK, const bf16* __restrict__ x, const bf16* __restrict__ mem0,
                  const int w, const int lane) {
  const int t2 = w * 32 + lane;
  uint32_t wo[8][4], w1[8][4];
  const uint32_t wo_lane = sb + ((lane & 7) + ((lane >> 4) << 3)) * 128 + (((w + 4 * ((lane >> 3) & 1)) ^ (lane & 7)) << 4);
  unsigned char* const g_red = tm.red;
  {
    const uint32_t tag = *(volatile unsigned*)&g_epoch + 1;
    if (w == 0) {
      stg_relaxed(g_red + RED_SLOT(t2 >> 3) + RED_LINE(blockIdx.x) + (t2 & 7) * 16, 0, 0, 0, 0);
      stg_relaxed(g_red + T_RED + blockIdx.x * 1024 + t2 * 16, 0, 0, 0, 0);
      stg_relaxed(g_red + T_RED + blockIdx.x * 1024 + 512 + t2 * 16, 0, 0, 0, 0);
      asm volatile("st.relaxed.gpu.global.u8 [%0], 0;" :: "l"(g_red + RED_SLOT(t2) + HINT_OFF + (t2 & 4) * 1024 + (t2 >> 3) * 16384 + blockIdx.x) : "memory");
    }
    uint4 xv[18];
    uint32_t mv[20];
#pragma unroll
    for (int i = 0; i < 20; i++) mv[i] = i < 18 ? ((const uint32_t*)mem0)[(lane >> 2) * (DM / 2) + (w * 18 + i) * 4 + (lane & 3)] : 0;
#pragma unroll
    for (int i = 0; i < 18; i++) xv[i] = blockIdx.x < NSEG ? ((const uint4*)(x + blockIdx.x * 32 * DM))[t2 + 128 * i] : make_uint4(0, 0, 0, 0);
    bar_sync(0, 384);
    cluster_arrive();
    if (PACE && w == 3) {
      const uint32_t t0 = gtime();
#pragma unroll 1
      for (int c = 1; c < 4; c++) {
        wait_until(t0 + c * PACE);
        if (elect_one()) load_weights(sb, tm, RANK, PORD ? (c == 1 ? 3 : c - 1) : c);
        __syncwarp();
      }
    }
    __half2 hx = __float2half2_rn(0.f);
#pragma unroll
    for (int i = 0; i < 18; i++) hx = amax4(hx, &xv[i].x);
    if (blockIdx.x == 0)
#pragma unroll
      for (int i = 0; i < 5; i++) hx = amax4(hx, &mv[4 * i]);
    sts32(sb + SC_SS + 4 * (12 + w), wexp(hx));
    if (t2 == 0) { sts32(sb + SC_EPOCH, (tag - 1) * NSEG + 2 - NRING); sts32(sb + SC_UNSC, __float_as_uint(1.f)); sts128(sb + SC_DEAD, 0, 0, 0, 0x3f800000u); sts64(sb + SC_FPAR, 0, 0); sts128(sb + SC_ONES, 0x3f803f80u, 0x3f803f80u, 0x3f803f80u, 0x3f803f80u); }
    WSTAMP(27);
    if (w == 0) __threadfence();
    uint32_t q[8] = {0, 0, 0, 0, 0, 0, 0, 0};
    mbar_wait(sb + MB_WO3, 0);
    if (t2 == 0) SSTAMP(11, 3);
#pragma unroll
    for (int k = 0; k < 8; k++) {
      ldsm4t(wo[k], wo_lane + SM_WO3 + k * 2048); ldsm4t(w1[k], wo_lane + SM_WOST + k * 2048);
#pragma unroll
      for (int i = 0; i < 4; i++) { sq_acc(q[i], wo[k][i]); sq_acc(q[i], w1[k][i]); }
    }
    bar_sync(6, 128);
    if (t2 == 0) SSTAMP(11, 7);
#pragma unroll
    for (int k = 0; k < 8; k++) sts128(sb + SM_WO3 + t2 * 16 + k * 2048, wo[k][0], wo[k][1], wo[k][2], wo[k][3]);
#pragma unroll
    for (int i = 0; i < 5; i++) {
      const int j = w * 18 + 4 * i + (lane >> 3), c = i < 4 || lane < 16 ? j * 8 + j / 24 * 64 : 192;
      stsm4t(sb + SM_MEM + (c + (lane & 7)) * 16, mv[4 * i], mv[4 * i + 1], mv[4 * i + 2], mv[4 * i + 3]);
    }
    bar_arrive(1, 256); bar_arrive(2, 256); bar_arrive(9, 256);
    if (t2 == 0) SSTAMP(11, 8);
    mbar_wait(sb + MB_WO, 0);
    if (t2 == 0) SSTAMP(11, 4);
#pragma unroll
    for (int k = 0; k < 8; k++) ldsm4t(wo[k], wo_lane + SM_X + 2 * XT + k * 2048);
    fence_async();
    bar_sync(6, 128);
    if (t2 == 32) tma_load3(sb + SM_X + 2 * XT, &tm.x, 64, sb + MB_X + 16);
    __syncwarp();
#pragma unroll
    for (int k = 0; k < 8; k++)
#pragma unroll
      for (int i = 0; i < 4; i++) sq_acc(q[4 + i], wo[k][i]);
    float ss = 0.f;
#pragma unroll
    for (int i = 0; i < 8; i++) ss += bf_lo(q[i]) + bf_hi(q[i]);
    ss = warp_sum(ss);
    if (lane == 0) sts32(sb + SC_SS + 4 * (8 + w), __float_as_uint(ss));
    if (t2 == 0) SSTAMP(11, 9);
    bar_sync(11, 384);
    if (t2 == 0) SSTAMP(11, 10);
    if (t2 == 0) {
      float a[16];
#pragma unroll
      for (int i = 0; i < 4; i++) lds128f(sb + SC_SS + 16 * i, &a[4 * i]);
      stg_relaxed(&g_stats[blockIdx.x * 2], __float_as_uint(((a[0] + a[1]) + (a[2] + a[3])) + ((a[4] + a[5]) + (a[6] + a[7]))),
                  __float_as_uint((a[8] + a[9]) + (a[10] + a[11])),
                  max(max(__float_as_uint(a[12]), __float_as_uint(a[13])), max(__float_as_uint(a[14]), __float_as_uint(a[15]))), tag);
    }
    __syncwarp();
    WSTAMP(24);
    cluster_wait();
    if (w == 0) {
      uint4 v[3];
      int n = 0;
      while (true) {
#pragma unroll
        for (int i = 0; i < 3; i++) v[i] = ldg_relaxed(&g_stats[(i * 32 + lane) * 2]);
        if (__all_sync(0xffffffffu, v[0].w == tag && v[1].w == tag && v[2].w == tag) || ++n > SPIN_LIMIT) break;
        __nanosleep(100);
      }
      WSTAMP(25);
      const float sv = warp_sum(__uint_as_float(v[0].x) + __uint_as_float(v[1].x) + __uint_as_float(v[2].x));
      const float so = warp_sum(__uint_as_float(v[0].y) + __uint_as_float(v[1].y) + __uint_as_float(v[2].y));
      const int expW = ((int)(__float_as_uint(sv) >> 23) + (int)(__float_as_uint(so) >> 23) - 254 + 2 + 10 + 1) >> 1;
      sts32(sb + SC_XMAX + 4 * lane, v[0].z); sts32(sb + SC_XMAX + 128 + 4 * lane, v[1].z);
      sts32(sb + SC_EXPW, expW + 1 - 15);
      if (blockIdx.x == 0 && lane == 0) *(volatile unsigned*)&g_epoch = tag;
      sts32(sb + SC_FPAR + 4, 1);
    } else if (w < 3) {
      const uint32_t u = blockIdx.x >> 4;
      unsigned char* const z = g_red + 98304 + (blockIdx.x & 15) * 128 + (u & 1) * 2048 + (u & 6) * 4096 + (((u >> 1) ^ w) & 1) * 4096 + lane * 4;
      stg_relaxed32(z, 0);
      uint32_t best = 0xffffffffu;
#pragma unroll 1
      for (int i = 0; i < 64; i++) {
        uint32_t last, dt;
        asm volatile("{\n.reg .pred p;\n.reg .u32 c, v;\nld.volatile.shared.u32 %0, [%3];\nmov.u32 c, %%clock;\n"
                     "atom.relaxed.gpu.global.exch.b32 v, [%2], 0;\nsetp.eq.u32 p, v, 0;\nmov.u32 %1, 0;\n@p mov.u32 %1, %%clock;\nsub.u32 %1, %1, c;\n}"
                     : "=r"(last), "=r"(dt) : "l"(z), "r"(sb + SC_FPAR + 4) : "memory");
        best = min(best, dt);
        if (last && i >= NPROBE - 1) break;
      }
      sts32(sb + SC_LAT + (w - 1) * 4, best);
    }
    bar_sync(13, 384);
    bar_arrive(0, 384);
    WSTAMP(26);
    TSTAMP(1);
  }

  const uint32_t nh = __shfl_sync(0xffffffffu, near_half(sb), 0);
  uint32_t l16 = sb + lane * 16;
  PIN(l16);
#define LV ((l16 >> 4) & 31)
#define fence_reg l16
  const uint32_t red_lo = (uint32_t)(uint64_t)g_red, red_hi = (uint32_t)((uint64_t)g_red >> 32);
  uint32_t lp;
  auto slot = [&](int s, uint32_t c, uint32_t ofs) {
    const uint32_t lo = lp | (red_lo + ((w >> 1) * 4 + (w & 1) * 2 + ((w ^ c) & 1)) * 4096 + RED_SLOT(s) + ofs);
    uint64_t a; asm("mov.b64 %0, {%1, %2};" : "=l"(a) : "r"(lo), "r"(red_hi));
    return (unsigned char*)a;
  };
  const uint32_t always = __shfl_sync(0xffffffffu, lds32(sb + SC_DEAD + 12), 0);
  const int mode0 = RANK < 2 ? w : w | 4;
  auto hint_addr = [&](int s) { return min(LV, 23u) * 4 + (red_lo + HINT_OFF + nh * 4096 + w * 16384 + RED_SLOT(s)); };
  auto load_hints = [&](uint32_t lo) {
    uint64_t a; asm("mov.b64 %0, {%1, %2};" : "=l"(a) : "r"(lo), "r"(red_hi));
    return ldg_relaxed32((const void*)a);
  };
  const uint32_t blk = RANK < 2 ? 9216 : SEGB;
  auto send_v = [&](int seg, int pos) {
    if (RANK == 2 && ((w == 0 && VS0 == pos) || (w == 1 && VS1 == pos)) && seg > 1 && seg < NSEG && !(XP & 2)) {
      if (elect_one()) {
        fence_async();
        bulk_s2s(mapa(sb + SM_VC + (seg & 1) * 8192, w), sb + SM_BLK + (seg & 3) * SEGB, 8192, mapa(sb + MB_VX + (seg & 1) * 8, w));
      }
      __syncwarp();
    }
  };
  uint32_t dl = __shfl_sync(0xffffffffu, gtime() - 768, 0);
  int s = 0;
  bool bad = false;
#pragma unroll 1
  while (true) {
    const uint32_t par = s & 1;
    uint32_t vx[4][4], oc[4], hints;
    if (HP == 2) { hints = hint_addr(s); PIN(hints); }
    auto load_vx = [&]() {
      const uint32_t va = l16 + (RANK < 2 ? SM_VC + par * 8192 : SM_BLK + (s & 3) * SEGB) + w * 1024 + ((LV >> 3) & 1) * 384 - (LV >> 4) * 128;
      if (WL & 4) lds128(sb + SC_ONES, oc);
#pragma unroll
      for (int i = 0; i < 4; i++) ldsm4(vx[i], va + (i & 1) * 4096 + (i >> 1) * 256);
    };
    auto retire = [&](uint32_t x) {
      asm volatile("{\n.reg .pred p;\nsetp.eq.u32 p, %0, 0;\n@p exit;\n}" :: "r"(vx[0][0] | vx[1][0] | vx[2][0] | vx[3][0] | x | ((WL & 4) ? oc[0] : 0)) : "memory");
    };
    auto scores = [&](auto memkeys, auto first, float* sc) {
      constexpr bool MK = decltype(memkeys)::value, FIRST = decltype(first)::value;
      uint32_t kb[4][4], qb[2][4];
      const uint32_t m = LV >> 3;
      uint32_t kaddr = l16 + SM_BLK + 4096 + (s & 3) * SEGB + w * 2048 + (m & 1) * (MK ? 128 : 896) - (m >> 1) * 128;
      if (MK) { PIN(kaddr); }
      else {
#pragma unroll
        for (int k = 0; k < 4; k++) ldsm4t(kb[k], kaddr + k * 256);
      }
      if (FIRST) { load_vx(); retire(MK ? kaddr : kb[0][0] | kb[1][0] | kb[2][0] | kb[3][0] | l16); bar_sync(4, 256); RSTAMP(4); PROF(4); }
      ldsm4t(qb[0], l16 + SM_QM);
      if (MK) ldsm4t(kb[0], kaddr);
      ldsm4t(qb[1], l16 + SM_QM + 512);
      if (MK) ldsm4t(kb[2], kaddr + 512);
      float c[4][4];
      mma16816z(c[0], kb[0], qb[0][0], qb[0][1]); mma16816z(c[1], kb[MK ? 0 : 1], qb[0][2], qb[0][3]);
      mma16816z(c[2], kb[2], qb[1][0], qb[1][1]); mma16816z(c[3], kb[MK ? 2 : 3], qb[1][2], qb[1][3]);
      if (FIRST && B5POS == 0) bar_arrive(5, N5);
#pragma unroll
      for (int i = 0; i < (MK ? 2 : 4); i++) sc[i] = ((c[0][i] + c[1][MK ? i + 2 : i]) + c[2][i]) + c[3][MK ? i + 2 : i];
    };
    auto send = [&](auto memkeys) {
      constexpr bool MK = decltype(memkeys)::value;
      constexpr int N = MK ? 1 : 2;
      const uint32_t sa = sb + LV * 4 + SM_E + (MK ? 1024 + RANK * 128 : RANK * 512 + w * 256);
      uint32_t ra[N][2], mb[N][2];
#pragma unroll
      for (int i = 0; i < N; i++)
#pragma unroll
        for (int j = 0; j < 2; j++) {
          ra[i][j] = mapa(sa + i * 128, j ? 2 : RANK ^ 1); mb[i][j] = mapa(sb + MB_S, j ? 2 : RANK ^ 1);
          PIN(ra[i][j]);
        }
      float sc[4];
      scores(memkeys, BoolC<true>(), sc);
      uint32_t e[N];
#pragma unroll
      for (int i = 0; i < N; i++) {
        e[i] = pack_bf16(ex2(sc[2 * i]), ex2(sc[2 * i + 1]));
        if (!(fmaxf(fabsf(sc[2 * i]), fabsf(sc[2 * i + 1])) <= E_LIM)) e[i] = 0x7fff7fffu;
        st_async1(ra[i][0], e[i], mb[i][0]);
        st_async1(ra[i][1], e[i], mb[i][1]);
      }
#pragma unroll
      for (int i = 0; i < N; i++) sts32(sa + i * 128, e[i]);
      __syncwarp();
      if (l16 == sb) mbar_arrive(sb + MB_S);
      PROF(5);
    };
    const int mode = bad ? 8 : mode0;
    if (mode < 2) {
      send(BoolC<false>());
    } else if (mode == 2) {
      send(BoolC<true>());
    } else if (mode == 8) {
      load_vx();
      retire(l16);
      const uint32_t fp = lds32(sb + SC_FPAR);
      bar_sync(6, 128);
      if (w == 0 && l16 == sb) { sts32(sb + SC_FPAR, fp ^ 1); mbar_expect(sb + MB_F, 3072); }
      if (RANK < 2 && w < 3) {
        float sc[4] = {0.f, 0.f, 0.f, 0.f};
        if (w < 2) scores(BoolC<false>(), BoolC<false>(), sc); else scores(BoolC<true>(), BoolC<false>(), sc);
#pragma unroll 1
        for (int r = 0; r < 3; r++)
          st_async4(mapa(l16 + SM_FB + RANK * 1536 + w * 512, r), __float_as_uint(sc[0]), __float_as_uint(sc[1]), __float_as_uint(sc[2]), __float_as_uint(sc[3]), mapa(sb + MB_F, r));
      }
      mbar_wait(sb + MB_F, fp);
      float a[12];
#pragma unroll
      for (int j = 0; j < 3; j++) {
        float b[4];
        lds128f(l16 + SM_FB + j * 512, a + 4 * j); lds128f(l16 + SM_FB + 1536 + j * 512, b);
#pragma unroll
        for (int i = 0; i < 4; i++) a[4 * j + i] += b[i];
      }
      float m0 = fmaxf(fmaxf(fmaxf(a[0], a[2]), fmaxf(a[4], a[6])), a[8]), m1 = fmaxf(fmaxf(fmaxf(a[1], a[3]), fmaxf(a[5], a[7])), a[9]);
#pragma unroll
      for (int o = 4; o < 32; o <<= 1) { m0 = fmaxf(m0, __shfl_xor_sync(0xffffffffu, m0, o)); m1 = fmaxf(m1, __shfl_xor_sync(0xffffffffu, m1, o)); }
#pragma unroll
      for (int i = 0; i < 5; i++) {
        const uint32_t ea = sb + SM_E + LV * 4 + (i < 4 ? i * 128 : 1024);
        sts32(ea, pack_bf16(ex2(a[2 * i] - m0), ex2(a[2 * i + 1] - m1)));
        sts32(ea + (i < 4 ? 512 : 128), 0x3f803f80u);
      }
      __syncwarp();
    } else {
      load_vx();
      retire(l16 + 1);
      if (VS0 == 2 || VS1 == 2) send_v(s + 1, 2);
      if (w == 3) {
        uint32_t used = ldg_relaxed32(&g_used[blockIdx.x / 3 * 32]);
        if (!(XP & 4) && elect_one()) {
          if (s > 0) seg_publish(s - 1);
          fence_async();
          seg_store(s, sb, 0, 8192);
        }
        __syncwarp();
        bar_sync(RANK < 2 ? 4 : 15, RANK < 2 ? 256 : 160);
        if (!(XP & 4) && elect_one()) { fence_async(); seg_store(s, sb, 8192, blk - 8192); }
        __syncwarp();
        const uint32_t need = lds32(sb + SC_EPOCH) + (s >= NRING - 1 ? s : -4 * NSEG);
#pragma unroll 1
        for (int n = 0; (int)(used - need) < 0 && n < ((XP & 64) ? 1 : SPIN_LIMIT); n++) used = ldg_relaxed32(&g_used[blockIdx.x / 3 * 32]);
      }
    }
    {
      uint32_t wa[4], wb[4];
      constexpr int WS = 2048;
      const uint32_t w3a = l16 + SM_WO3 + w * 512;
      if (HP == 1) { hints = hint_addr(s); PIN(hints); }
      if (!(WL & 1)) { lds128(w3a + KP(0) * WS, wa); lds128(w3a + KP(1) * WS, wb); }
      if (WL & 2) {
#pragma unroll
        for (int i = 0; i < 4; i++) oc[i] = always | (always >> 16) | (always & (i + 1));
      } else if (!(WL & 4)) lds128(sb + SC_ONES, oc);
      if (B5POS == 1 && mode < 3) bar_arrive(5, N5);
      uint32_t e[10], p[5], vm[4], ob[4];
      float o0[4], o1[4], f[3][2][4], rs[4];
      if (!(RV & 1)) { reserve2(vm); reserve2(vm + 2); }
      if (!(RV & 2)) reserve2(e + 8);
      if (!HP) { hints = hint_addr(s); PIN(hints); }
      if (CLR & 2) asm volatile("{\n.reg .pred p;\nsetp.eq.u32 p, %0, 0;\n@p exit;\n}" :: "r"(wa[0] | wb[0] | oc[0] | hints) : "memory");
      if (RV & 4) mbar_wait_fast(sb + MB_S, par); else mbar_wait(sb + MB_S, par);
      RSTAMP(5);
      PROF(6);
      if (RV & 2) { ldsm4t(e, l16 + SM_E); ldsm4t(e + 4, l16 + SM_E + 512); ldsm2t(e + 8, l16 + SM_E + 1024); }
      else { ldsm4t(e, l16 + SM_E); ldsm2t_in(e + 8, l16 + SM_E + 1024, always); ldsm4t(e + 4, l16 + SM_E + 512); }
      if (RV & 1) lds128(l16 + w * 512 + SM_VM, vm); else lds128_in(vm, l16 + w * 512 + SM_VM, always);
      const float scl = __uint_as_float(lds32(sb + SC_UNSC + 8 - par * 8));
      if (HL == 0) hints = load_hints(hints);
      if (GF & 1) SCHED_FENCE(4);
#pragma unroll
      for (int i = 0; i < 4; i++) p[i] = mul_bf16(e[i], e[4 + i]);
      p[4] = mul_bf16(e[8], e[9]);
      if (HL) hints = load_hints(hints | (p[HL - 1] & always & 1));
      mma16816z(o0, vx[0], p[0], p[1]);
      if (WL & 1) { lds128_in(vx[0], w3a + KP(0) * WS, always); }
      mma16816z(o1, vx[1], p[0], p[1]);
      if (WL & 1) { lds128_in(vx[1], w3a + KP(1) * WS, always); }
      mma16816z(rs, oc, p[0], p[1]);
      mma16816(o0, vx[2], p[2], p[3]); lds128_in(vx[2], w3a + KP(2) * WS, always);
      mma16816(o1, vx[3], p[2], p[3]); lds128_in(vx[3], w3a + KP(3) * WS, always);
      mma16816(rs, oc, p[2], p[3]);
      mma1688(o0, vm[0], vm[1], p[4]); mma1688(o1, vm[2], vm[3], p[4]); mma1688(rs, oc[0], oc[1], p[4]);
      stsm4(l16 + w * 512 + SM_OB, pack_bf16(o0[0], o0[1]), pack_bf16(o0[2], o0[3]), pack_bf16(o1[0], o1[1]), pack_bf16(o1[2], o1[3]));
      bar_sync(6, 128);
      RSTAMP(3);
      PROF(7);
      ldsm4t_in(oc, l16 + SM_OB, always);
      bad = __any_sync(0xffffffffu, !(rs[0] + rs[1] > 0.f) && !bad);
      rs[0] *= scl; rs[1] *= scl;
      asm volatile("{\n.reg .pred p;\nsetp.ne.u32 p, %1, 0;\n@p rcp.approx.ftz.f32 %0, %0;\n}" : "+f"(rs[0]) : "r"(always));
      asm volatile("{\n.reg .pred p;\nsetp.ne.u32 p, %1, 1;\n@p rcp.approx.ftz.f32 %0, %0;\n}" : "+f"(rs[1]) : "r"(always));
      asm volatile("lop3.b32 %0, %1, %2, %3, 0xfe;" : "=r"(lp) : "r"((l16 & 128) * 2), "r"((l16 & 256) * 4), "r"(l16 & 112));
      if (bad) continue;
      ldsm4t(ob, l16 + SM_OB + 512);
      mma16816z(f[2][0], WL & 1 ? vx[0] : wa, oc[0], oc[1]); mma16816z(f[2][1], WL & 1 ? vx[1] : wb, oc[2], oc[3]);
      mma16816z(f[0][0], wo[0], oc[0], oc[1]); mma16816z(f[0][1], wo[4], oc[2], oc[3]);
      mma16816z(f[1][0], w1[0], oc[0], oc[1]); mma16816z(f[1][1], w1[4], oc[2], oc[3]);
      ldsm4t_in(oc, l16 + SM_OB + 1024, always);
      mma16816(f[2][0], vx[2], ob[0], ob[1]); lds128_in(vx[2], w3a + KP(4) * WS, always);
      mma16816(f[2][1], vx[3], ob[2], ob[3]); lds128_in(vx[3], w3a + KP(5) * WS, always);
      mma16816(f[0][0], wo[1], ob[0], ob[1]); mma16816(f[0][1], wo[5], ob[2], ob[3]);
      mma16816(f[1][0], w1[1], ob[0], ob[1]); mma16816(f[1][1], w1[5], ob[2], ob[3]);
      ldsm4t_in(ob, l16 + SM_OB + 1536, always);
      mma16816(f[0][0], wo[2], oc[0], oc[1]); mma16816(f[0][1], wo[6], oc[2], oc[3]);
      mma16816(f[2][0], vx[2], oc[0], oc[1]); lds128_in(vx[2], w3a + KP(6) * WS, always);
      mma16816(f[2][1], vx[3], oc[2], oc[3]); lds128_in(vx[3], w3a + KP(7) * WS, always);
      mma16816(f[1][0], w1[2], oc[0], oc[1]); mma16816(f[1][1], w1[6], oc[2], oc[3]);
      mma16816(f[0][0], wo[3], ob[0], ob[1]); mma16816(f[0][1], wo[7], ob[2], ob[3]);
      mma16816(f[1][0], w1[3], ob[0], ob[1]); mma16816(f[1][1], w1[7], ob[2], ob[3]);
      mma16816(f[2][0], vx[2], ob[0], ob[1]); mma16816(f[2][1], vx[3], ob[2], ob[3]);
      bar_arrive(7, NII < 18 ? 384 : 256);
      lds128_in(ob, sb + SC_DEAD, always);
      uint32_t h[3][2];
#pragma unroll
      for (int j = 0; j < 3; j++)
#pragma unroll
        for (int i = 0; i < 2; i++)
        {
          scale_sum(f[j][1][2 * i], f[j][0][2 * i], rs[0], always); scale_sum(f[j][1][2 * i + 1], f[j][0][2 * i + 1], rs[1], always);
          h[j][i] = pack_f16(f[j][1][2 * i], f[j][1][2 * i + 1]);
        }
      const uint32_t rofs = RANK * 32768;
      red_f16x8(slot(s, RANK >> 1, rofs), h[0][0], h[1][0], h[2][0], 0x3c00u);
      red_f16x8(slot(s, (RANK >> 1) ^ 1, rofs), h[0][1], h[1][1], h[2][1], 0x3c00u);
      if (NII == 18) bar_arrive(10, 256);
      SCHED_FENCE(5);
      RSTAMP(0);
      l16 += ob[B7R];
    }
    {
    PROF(8);
    if (VS0 == 3 || VS1 == 3) send_v(s + 1, 3);
    const uint32_t ma0 = l16 + SM_MEM + w * 128 + (LV >> 3) * 896 + nh * 512;
    const unsigned char* const sl[2] = {slot(s, nh, 0), slot(s, nh ^ 1, 0)};
    uint32_t late = latest_hint(hints, dl, s);
    if (late >= 64) {
      int n = 0;
#pragma unroll 1
      do {
        late = latest_hint(load_hints(hint_addr(s)), dl, s);
      } while (late >= 64 && ++n < SPIN_LIMIT);
    }
    dl += late * 32 + tm.poll;
    PROF(9);
    {
      auto wait_until = [&](uint32_t t) {
        asm volatile("{\n.reg .pred p;\n.reg .s32 c;\n.reg .u64 t;\nTL: mov.u64 t, %%globaltimer;\ncvt.u32.u64 c, t;\nsub.s32 c, c, %0;\nsetp.lt.s32 p, c, 0;\n@p bra.uni TL;\n}" :: "r"(t + (l16 & 15)) : "memory");
      };
      uint4 v[2][3];
      auto load = [&](int c) {
#pragma unroll
        for (int r = 0; r < 3; r++) v[c][r] = ldg_relaxed(sl[c ^ (r >> 1)] + r * 32768);
      };
      auto decode = [&](int c, int n) {
        uint32_t q[9];
        __half2 hm;
        const uint32_t ma = ma0 ^ (c * 512);
#pragma unroll
        for (int i = 0; i < 9; i++) {
          const uint32_t h = i % 3 == 0 ? v[c][i / 3].x : (i % 3 == 1 ? v[c][i / 3].y : v[c][i / 3].z);
          const float2 f = __half22float2(*(const __half2*)&h);
          q[i] = pack_bf16(f.x, f.y);
          hm = i ? __hmax2(hm, __habs2(*(const __half2*)&h)) : __habs2(*(const __half2*)&h);
        }
#pragma unroll
        for (int r = 0; r < 3; r++) stsm4(ma + r * 4096, q[3 * r], q[3 * r + 1], q[3 * r + 2], r < 2 ? v[c][r].w : *(const uint32_t*)&hm);
        const bool done = __all_sync(0xffffffffu, v[c][0].w == 0x5000u && v[c][1].w == 0x5000u && v[c][2].w == 0x5000u) || n > SPIN_LIMIT;
        asm volatile("{\n.reg .pred p;\nsetp.ne.u32 p, %0, 0;\n@p bar.arrive %1, 256;\n}" :: "r"((int)done), "r"(1 + c) : "memory");
        return done;
      };
      if (LEAD) { wait_until(dl - LEAD); load(1); }
      wait_until(dl);
      PROF(10);
      int n = 0;
#pragma unroll 1
      do {
        load(0);
        if (!LEAD) load(1);
        asm volatile("{\n.reg .pred p;\nsetp.eq.u32 p, %0, 0;\n@p bar.sync 13, 384;\n}" :: "r"(n) : "memory");
      } while (!decode(0, n++));
      PROF(11);
      RSTAMP(1);
#pragma unroll 1
      while (!decode(1, n++)) load(1);
      bar_arrive(9, 256);
      RSTAMP(2);
      PROF(12);
    }
    PROF(13);
    if (++s == NSEG - 1) break;
    }
  }
#undef fence_reg
  if (RANK < 2) bar_arrive(4, 256);
  TSTAMP(49);
  {
    PIN(l16);
    tail_attention(sb, RANK, w, LV, 0, 6);
#pragma unroll 1
    for (int sg = 0; sg < 2; sg++) {
      PIN(l16);
      const int lane = LV, m = lane >> 3, g = lane >> 2, t = lane & 3;
      const uint32_t ob = l16 + T_OB + sg * 8192;
      bar_sync(sg ? 0 : 8, 256);
      TSTAMP(54 + 2 * sg);
      const float inv = __uint_as_float(0x7f000000u - lds32(sb + T_UN + sg * 4));
#pragma unroll 1
      for (int j = 0; j < 4; j += 2) {
        float c[2][3][4];
        uint32_t x[4], y[4], z[2][4];
#pragma unroll
        for (int e = 0; e < 2; e++) {
          const uint32_t oa = sb + T_OA + ((sg * 4 + j + e) * 8 + g) * 64 + (blockIdx.x / 3 * 36 & 15) + t * 4;
          z[e][0] = lds32(oa); z[e][1] = lds32(oa + 16); z[e][2] = t ? 0u : lds32(oa + 32);
        }
#pragma unroll
        for (int i = 0; i < 3; i++) {
          const uint32_t wa = sb + T_WA + ((lane & 7) + ((lane >> 4) << 3)) * 128 + (((w + 4 * (m & 1)) ^ (lane & 7)) << 4);
          ldsm4t(x, wa + i * 3072); ldsm2t(y, wa + i * 3072 + 2048);
#pragma unroll
          for (int e = 0; e < 2; e++) { mma1688z(c[e][i], y[0], y[1], z[e][2]); mma16816(c[e][i], x, z[e][0], z[e][1]); }
        }
#pragma unroll
        for (int r = 0; r < 4; r++) {
          ldsm4t(z[0], ob + j * 2048 + r * 512); ldsm4t(z[1], ob + j * 2048 + 2048 + r * 512);
          lds128(l16 + SM_WO3 + w * 512 + r * 2048, x); lds128(l16 + SM_WO3 + w * 512 + (r + 4) * 2048, y);
#pragma unroll
          for (int e = 0; e < 2; e++) { mma16816(c[e][0], wo[r], z[e][0], z[e][1]); mma16816(c[e][1], w1[r], z[e][0], z[e][1]); mma16816(c[e][2], x, z[e][0], z[e][1]); }
#pragma unroll
          for (int e = 0; e < 2; e++) { mma16816(c[e][0], wo[r + 4], z[e][2], z[e][3]); mma16816(c[e][1], w1[r + 4], z[e][2], z[e][3]); mma16816(c[e][2], y, z[e][2], z[e][3]); }
        }
#pragma unroll
        for (int i = 0; i < 4; i++) {
          const float (&d)[3][4] = c[i >> 1];
          const int q = (i & 1) * 2;
          red_f16x8(g_red + T_RED + ((((sg * 4 + j + (i >> 1)) * 3 + RANK) * 4 + w) * 2 + (i & 1)) * 512 + lane * 16, pack_f16(d[0][q] * inv, d[0][q + 1] * inv),
                    pack_f16(d[1][q] * inv, d[1][q + 1] * inv), pack_f16(d[2][q] * inv, d[2][q + 1] * inv), 0x3c00u);
        }
      }
      TSTAMP(55 + 2 * sg);
    }
    if (RSLOW) { wait_until(gtime() + 8000); wait_until(gtime() + 8000); wait_until(gtime() + 4000); }
    if (w < 2) {
      const int b = blockIdx.x, lane = LV, g = lane >> 2, t = lane & 3;
      uint4 v;
#pragma unroll 1
      for (int n = 0; n < SPIN_LIMIT; n++) {
        v = ldg_relaxed(g_red + T_RED + (w * 96 + b) * 512 + lane * 16);
        if (__all_sync(0xffffffffu, v.w == 0x5000u)) break;
        __nanosleep(40);
      }
      const float un = __uint_as_float(lds32(sb + T_UN + w * 4));
      uint32_t* const o = (uint32_t*)(tm.out + (size_t)((NAUXSEG + w) * 32 + b / 24 * 8 + g) * DM + (b >> 3) % 3 * 192 + (b & 1) * 32 + (b & 6) * 4) + t;
#pragma unroll
      for (int j = 0; j < 3; j++) {
        const float2 f = __half22float2(*(const __half2*)(&v.x + j));
        o[j * 32] = movm(pack_bf16(f.x * un, f.y * un));
      }
    }
  }
  TSTAMP(3);
  if (CSY) cluster_sync();
}

__global__ void __cluster_dims__(3, 1, 1) __launch_bounds__(384, 1)
rec_kernel(const __grid_constant__ RMaps tm, const bf16* __restrict__ x, const bf16* __restrict__ mem0) {
  extern __shared__ __align__(1024) unsigned char smem_raw[];
  const uint32_t sb = smem_u32(smem_raw);
  const int tid = threadIdx.x, lane = tid & 31;
  const int wg = __shfl_sync(0xffffffffu, tid >> 7, 0);
  const int w = __shfl_sync(0xffffffffu, (tid >> 5) & 3, 0);
  uint32_t rank; asm("mov.u32 %0, %%cluster_ctarank;" : "=r"(rank));
  STAMP(0);
  TSTAMP(0);
  asm volatile("griddepcontrol.launch_dependents;" ::: "memory");

#define PFT 1
  if (PFT && wg == 1 && lane == 0) asm volatile("prefetch.tensormap [%0];\nprefetch.tensormap [%1];" :: "l"(w & 1 ? &tm.woa : &tm.oa), "l"(w == 0 ? (rank < 2 ? &tm.wk : &tm.wv) : w == 1 ? &tm.wq : w == 2 ? &tm.x : &tm.wo) : "memory");
  if (wg < 2) {
    asm volatile("setmaxnreg.inc.sync.aligned.u32 192;");
    if (tid == 0) {
      for (int i = 0; i < 3; i++) { mbar_init(sb + MB_W + 8 * i, 1); mbar_init(sb + MB_X + 8 * i, 1); }
      mbar_init(sb + MB_WO, 1); mbar_init(sb + MB_WO3, 1);
      mbar_init(sb + MB_S, rank < 2 ? 5 : 6);
      mbar_init(sb + MB_F, 1);
      for (int i = 0; i < 3; i++) mbar_init(sb + MB_T + 8 * i, 1);
      mbar_init(sb + MB_VX, 1); mbar_init(sb + MB_VX + 8, 1);
      asm volatile("fence.mbarrier_init.release.cluster;" ::: "memory");
      fence_async();
      SSTAMP(11, 6);
      load_weights(sb, tm, rank, 0);
      for (int i = 0; i < 3; i++) mbar_expect(sb + MB_X + 8 * i, XT);
      tma_load3(sb + SM_X, &tm.x, 0, sb + MB_X);
      if (!PACE) for (int c = 1; c < 4; c++) load_weights(sb, tm, rank, c);
      mbar_expect(sb + MB_S, rank < 2 ? 640 + 2048 : 1280);
      mbar_expect(sb + MB_VX, 8192); mbar_expect(sb + MB_VX + 8, 8192);
      mbar_expect(sb + MB_T, 2048);
      for (int i = 1; i < 3; i++) mbar_expect(sb + MB_T + 8 * i, rank < 2 ? 5120 : 10240);
      SSTAMP(11, 5);
    }
    __syncwarp();
    bar_sync(0, 384);
    proj_role(sb, tm, rank, wg, w, lane);
  } else {
    asm volatile("setmaxnreg.dec.sync.aligned.u32 120;");
    attn_role(sb, smem_raw, tm, rank, x, mem0, w, lane);
  }
}

constexpr int A_XH = 73728;
constexpr int A_NS = 9, A_WM = 6144, A_WT = 768;
constexpr int A_RING = 2 * A_XH, A_TAIL = A_RING + A_NS * A_WM, A_GW = A_TAIL + A_NS * A_WT;
constexpr int A_EPI = 212864, A_EPW = 9344;
constexpr int A_XT = 4 * XT, A_XW = A_XT + 8192, A_EX = A_XW + 8192, A_NR = 4;
constexpr int A_IN = A_EX + 16384, A_OST = A_IN + 3 * SEGB;
constexpr int A_GATE = A_EPI + 2 * A_EPW, A_BAR = A_GATE + 512;
constexpr int A_TOTAL = A_BAR + 384;
struct AMaps { CUtensorMap x, wa, wt, oa, o, o3, wob, woa; };

DI void wgmma_n192_ss_nt(float* d, uint64_t da, uint64_t db, int acc) {
  asm volatile("{\n.reg .pred p;\nsetp.ne.b32 p, %98, 0;\n"
               "wgmma.mma_async.sync.aligned.m64n192k16.f32.bf16.bf16 {"
               "%0,%1,%2,%3,%4,%5,%6,%7,%8,%9,%10,%11,%12,%13,%14,%15,%16,%17,%18,%19,%20,%21,%22,%23,%24,%25,%26,%27,%28,%29,%30,%31,"
               "%32,%33,%34,%35,%36,%37,%38,%39,%40,%41,%42,%43,%44,%45,%46,%47,%48,%49,%50,%51,%52,%53,%54,%55,%56,%57,%58,%59,%60,%61,%62,%63,"
               "%64,%65,%66,%67,%68,%69,%70,%71,%72,%73,%74,%75,%76,%77,%78,%79,%80,%81,%82,%83,%84,%85,%86,%87,%88,%89,%90,%91,%92,%93,%94,%95"
               "}, %96, %97, p, 1, 1, 0, 1;\n}\n"
               : ACC8(d, 0), ACC8(d, 8), ACC8(d, 16), ACC8(d, 24), ACC8(d, 32), ACC8(d, 40), ACC8(d, 48), ACC8(d, 56),
                 ACC8(d, 64), ACC8(d, 72), ACC8(d, 80), ACC8(d, 88) : "l"(da), "l"(db), "r"(acc));
}
#define ACC4(d, o) "+f"(d[o]), "+f"(d[o + 1]), "+f"(d[o + 2]), "+f"(d[o + 3])
DI void wgmma_n24_ss_nt(float* d, uint64_t da, uint64_t db, int acc) {
  asm volatile("{\n.reg .pred p;\nsetp.ne.b32 p, %14, 0;\n"
               "wgmma.mma_async.sync.aligned.m64n24k16.f32.bf16.bf16 {%0,%1,%2,%3,%4,%5,%6,%7,%8,%9,%10,%11}, %12, %13, p, 1, 1, 0, 1;\n}\n"
               : ACC8(d, 0), ACC4(d, 8) : "l"(da), "l"(db), "r"(acc));
}
DI void wgmma_n8_ss(float* d, uint64_t da, uint64_t db, int acc) {
  asm volatile("{\n.reg .pred p;\nsetp.ne.b32 p, %6, 0;\n"
               "wgmma.mma_async.sync.aligned.m64n8k16.f32.bf16.bf16 {%0,%1,%2,%3}, %4, %5, p, 1, 1, 0, 0;\n}\n"
               : ACC4(d, 0) : "l"(da), "l"(db), "r"(acc));
}
DI void wgmma_n40_ss_tt(float* d, uint64_t da, uint64_t db, int acc) {
  asm volatile("{\n.reg .pred p;\nsetp.ne.b32 p, %22, 0;\n"
               "wgmma.mma_async.sync.aligned.m64n40k16.f32.bf16.bf16 {%0,%1,%2,%3,%4,%5,%6,%7,%8,%9,%10,%11,%12,%13,%14,%15,%16,%17,%18,%19}, "
               "%20, %21, p, 1, 1, 1, 1;\n}\n"
               : ACC8(d, 0), ACC8(d, 8), ACC4(d, 16) : "l"(da), "l"(db), "r"(acc));
}
DI void wgmma_n64_rs(float* d, const uint32_t* a, uint64_t db, int acc) {
  asm volatile("{\n.reg .pred p;\nsetp.ne.b32 p, %37, 0;\n"
               "wgmma.mma_async.sync.aligned.m64n64k16.f32.bf16.bf16 {"
               "%0,%1,%2,%3,%4,%5,%6,%7,%8,%9,%10,%11,%12,%13,%14,%15,%16,%17,%18,%19,%20,%21,%22,%23,%24,%25,%26,%27,%28,%29,%30,%31"
               "}, {%32,%33,%34,%35}, %36, p, 1, 1, 0;\n}\n"
               : ACC8(d, 0), ACC8(d, 8), ACC8(d, 16), ACC8(d, 24) : "r"(a[0]), "r"(a[1]), "r"(a[2]), "r"(a[3]), "l"(db), "r"(acc));
}
DI void wgmma_n32_ss_tn(float* d, uint64_t da, uint64_t db, int acc) {
  asm volatile("{\n.reg .pred p;\nsetp.ne.b32 p, %18, 0;\n"
               "wgmma.mma_async.sync.aligned.m64n32k16.f32.bf16.bf16 {%0,%1,%2,%3,%4,%5,%6,%7,%8,%9,%10,%11,%12,%13,%14,%15}, "
               "%16, %17, p, 1, 1, 1, 0;\n}\n"
               : ACC8(d, 0), ACC8(d, 8) : "l"(da), "l"(db), "r"(acc));
}
DI void tma_load3c(uint32_t dst, const CUtensorMap* m, int c0, int c1, int c2, uint32_t mb) {
  asm volatile("cp.async.bulk.tensor.3d.shared::cluster.global.mbarrier::complete_tx::bytes [%0], [%1, {%3, %4, %5}], [%2];"
               :: "r"(dst), "l"(m), "r"(mb), "r"(c0), "r"(c1), "r"(c2) : "memory");
}
DI void count_up(unsigned* p) {
  asm volatile("fence.proxy.async;" ::: "memory");
  asm volatile("red.release.gpu.global.add.u32 [%0], 1;" :: "l"(p) : "memory");
}
#define AX 0
#define FDLY 400
#define ORING 63
#define DRY 0
#define FEND 59
DI void publish(unsigned* p) {
  asm volatile("cp.async.bulk.wait_group 0;\nfence.proxy.async;" ::: "memory");
  asm volatile("red.relaxed.gpu.global.add.u32 [%0], 1;" :: "l"(p) : "memory");
}
#define G_IDLE 600
#define ADLY 0

__global__ void __launch_bounds__(512, 1)
aux_kernel(const __grid_constant__ AMaps tm, const bf16* __restrict__ wqkv, const bf16* __restrict__ woa, const bf16* __restrict__ gate_w, bf16* __restrict__ out) {
  extern __shared__ __align__(1024) unsigned char smem_raw[];
  const uint32_t sb = smem_u32(smem_raw);
  const uint32_t fullx = sb + A_BAR, full1 = fullx + 24, empty1 = full1 + 8 * A_NS, fullw = empty1 + 8 * A_NS, full3 = fullw + 8, empty3 = full3 + 8 * A_NR,
                 fullq = empty3 + 8 * A_NR, fullv = fullq + 8, emptyq = fullv + 8, emptyv = emptyq + 8;
  const int tid = threadIdx.x, lane = tid & 31, cta = blockIdx.x;
  const int wg = __shfl_sync(0xffffffffu, tid >> 7, 0), w = __shfl_sync(0xffffffffu, (tid >> 5) & 3, 0);
  ASTAMP(14);
  if (tid == 384) {
    for (int i = 0; i < 3; i++) mbar_init(fullx + 8 * i, 1);
    for (int i = 0; i < A_NS; i++) { mbar_init(full1 + 8 * i, 1); mbar_init(empty1 + 8 * i, 8); }
    mbar_init(fullw, 1); mbar_init(fullq, 1); mbar_init(fullv, 1); mbar_init(emptyq, 4); mbar_init(emptyv, 4);
    for (int i = 0; i < A_NR; i++) { mbar_init(full3 + 8 * i, 1); mbar_init(empty3 + 8 * i, 4); }
    fence_async();
  }
  __syncthreads();
  ASTAMP(0);
  const int tile = cta >> 1, hh = cta & 1;
  const int nsl = cta >> 2, kq = cta & 3;
  if (wg == 3) {
    asm volatile("setmaxnreg.dec.sync.aligned.u32 24;");
    const bool lead = lane == 0;
    if (w < 3) {
      if (ADLY) wait_until(gtime() + ADLY);
      if (elect_one()) {
        mbar_expect(fullx + 8 * w, 49152);
        for (int p = 0; p < 2; p++)
          asm volatile("cp.async.bulk.tensor.4d.shared::cluster.global.mbarrier::complete_tx::bytes [%0], [%1, {%3, %4, %5, %6}], [%2];"
                       :: "r"(sb + p * A_XH + w * 24576), "l"(&tm.x), "r"(fullx + 8 * w), "r"(0), "r"(p), "r"(57 * tile - 7), "r"(3 * w) : "memory");
      }
#pragma unroll 1
      for (int r = 0; r < 17; r++) {
#pragma unroll 1
        for (int st = w; st < A_NS; st += 3) {
          if (r > 0) mbar_wait(empty1 + 8 * st, ~r & 1);
          if (r < 16 && elect_one()) {
            const int col = hh * 288 + (r >> 2) * 72, row = (r & 3) * 144 + st * 16;
            mbar_expect(full1 + 8 * st, A_WM + (AX & 1 ? 0 : A_WT));
            tma_load3c(sb + A_RING + st * A_WM, &tm.wa, col, row, 0, full1 + 8 * st);
            if (!(AX & 1)) tma_load3c(sb + A_TAIL + st * A_WT, &tm.wt, col + 64, row, 0, full1 + 8 * st);
          }
          __syncwarp();
        }
        if (r == 0 && elect_one())
          for (int j = 0; j < 3; j++)
            asm volatile("cp.async.bulk.prefetch.L2.global [%0], %1;" :: "l"((const char*)wqkv + cta * 55296 + (w * 3 + j) * 6144), "r"(6144) : "memory");
        __syncwarp();
      }
      bar_sync(8, 96);
    }
    const unsigned epoch = lds32(sb + A_BAR + 376);
    if (w == 2) {
      if (lead && cta < NH) {
#pragma unroll 1
        for (int seg = 0; seg < NAUXSEG; seg++) {
          const unsigned char* const src = g_seg + ((size_t)(AX & 128 ? 0 : seg % NRING) * 96 + cta * 3) * SEGB;
          SSTAMP(0, seg);
          const uint32_t tw = gtime();
          wait_count(&g_scnt[(seg * 32 + cta) * 8], 3 * (epoch + 1), !(TL & 2) || seg < NAUXSEG - 2);
          const bool idle = seg < FEND && gtime() - tw > G_IDLE;
          if (FDLY && idle) wait_until(gtime() + FDLY);
          SSTAMP(1, seg);
          mbar_wait(emptyq, ~seg & 1);
          if (AX & 8) { mbar_arrive(fullq); mbar_wait(emptyv, ~seg & 1); mbar_arrive(fullv); continue; }
          mbar_expect(fullq, 2 * SEGB);
          asm volatile("cp.async.bulk.shared::cluster.global.mbarrier::complete_tx::bytes [%0], [%1], %2, [%3];"
                       :: "r"(sb + A_IN), "l"(src), "r"(2 * SEGB), "r"(fullq) : "memory");
          mbar_wait(emptyv, ~seg & 1);
          mbar_expect(fullv, SEGB);
          asm volatile("cp.async.bulk.shared::cluster.global.mbarrier::complete_tx::bytes [%0], [%1], %2, [%3];"
                       :: "r"(sb + A_IN + 2 * SEGB), "l"(src + 2 * SEGB), "r"(SEGB), "r"(fullv) : "memory");
          if (seg == 1) wait_count(&g_abar[32], NAUX * (epoch + 1));
          stg_relaxed32(&g_used[cta * 32], epoch * NSEG + seg);
        }
      }
    }
    if (w == 3) {
#pragma unroll 1
      for (int c = 0; c < 4; c++) {
        if (lead) asm volatile("cp.async.bulk.wait_group.read 0;" ::: "memory");
        __syncwarp();
        bar_arrive(11, 160); bar_arrive(12, 160);
#pragma unroll 1
        for (int g = 0; g < 2; g++) {
          bar_sync(13 + g, 160);
          if (lead) {
            asm volatile("cp.async.bulk.tensor.3d.global.shared::cta.bulk_group [%0, {%2, %3, %4}], [%1];"
                         :: "l"(&tm.oa), "r"(sb + A_EPI + g * A_EPW + 1024), "r"(4096 + hh * 288 + c * 72), "r"(g), "r"(57 * tile) : "memory");
            asm volatile("cp.async.bulk.commit_group;" ::: "memory");
          }
        }
      }
      if (lead) asm volatile("cp.async.bulk.wait_group.read 0;" ::: "memory");
      __syncwarp();
      bar_arrive(10, 160);
      if (lead) publish(&g_abar[32]);
    }
    if ((w & 1) && cta < NH) {
      if (w == 1) bar_arrive(5, 160);
#pragma unroll 1
      for (int seg = w >> 1; seg < NAUXSEG; seg += 2) {
        bar_sync(w == 1 ? 4 : 15, 160);
        if (lead && !(AX & 32)) {
          tma_store(&tm.o, sb + A_OST, cta * DH, (seg & ORING) * 32);
          tma_store(&tm.o, sb + A_OST + 4096, cta * DH + 64, (seg & ORING) * 32);
          asm volatile("cp.async.bulk.commit_group;" ::: "memory");
          asm volatile("cp.async.bulk.wait_group.read 0;" ::: "memory");
        }
        __syncwarp();
        if (seg < NAUXSEG - 1) bar_arrive(5, 160);
        if (lead) { publish(&g_ocnt[seg * 32 + cta / 9 * 8]); SSTAMP(9, seg); }
        __syncwarp();
      }
    }
    if (w != 0) return;
    if (lead) {
      mbar_expect(fullw, 19 * 8192);
#pragma unroll 1
      for (int k = 0; k < 19; k++) {
        const int kb = k < 18 ? kq * 18 + k : 72;
        const uint32_t dst = sb + (k < 18 ? k * 8192 : A_XW);
        if (kb < 64) tma_load(dst, &tm.wob, nsl * 64, kb * 64, fullw);
        else tma_load(dst, &tm.woa, nsl * 64, (kb - 64) * 64, fullw);
      }
    }
    __syncwarp();
    bar_sync(6, 288);
    if (lead) {
      if (kq == 3) { wait_count(&g_abar[32], NAUX * (epoch + 1)); asm volatile("fence.proxy.async;" ::: "memory"); }
      int avail = 0;
      bool waited = false;
      const unsigned nheads = (kq < 3 ? 9 : 5) * (epoch + 1);
      for (int seg = 0; seg < NAUXSEG; seg++) {
        if (seg >= avail) {
          const int far = min(seg + 3, NAUXSEG - 1);
          if (far > seg && !waited && min((int)(ldg_relaxed32(&g_ocnt[far * 32 - 32 + kq * 8]) - nheads), (int)(ldg_acquire32(&g_ocnt[far * 32 + kq * 8]) - nheads)) >= 0) avail = far + 1;
          else { waited = wait_count(&g_ocnt[seg * 32 + kq * 8], nheads, !(TL & 2) || seg < NAUXSEG - 2) && (TL & 4); avail = seg + 1; }
        }
        const bool pidle = waited && seg > 8 && seg < FEND - 1;
        SSTAMP(5, seg);
        for (int g = 0; g < 2; g++) {
          const int sl = (seg & 1) * 2 + g;
          const bool extra = kq == 3 && g == 0;
          mbar_wait(empty3 + 8 * sl, ((seg >> 1) & 1) ^ 1);
          if (AX & 4) { mbar_arrive(full3 + 8 * sl); continue; }
          mbar_expect(full3 + 8 * sl, XT + (extra ? 4096 : 0));
          tma_load3c(sb + sl * XT, &tm.o3, 0, (kq == 3 && g == 1 ? seg : seg & ORING) * 32, kq * 18 + 9 * g, full3 + 8 * sl);
          if (extra) tma_load(sb + A_XT + (seg & 1) * 4096, &tm.o, 72 * 64, seg * 32, full3 + 8 * sl);
        }
      }
    }
    __syncwarp(); bar_sync(6, 288);
    if (GDW) asm volatile("griddepcontrol.wait;" ::: "memory");
  } else if (wg == 2) {
    asm volatile("setmaxnreg.dec.sync.aligned.u32 88;");
    {
      const unsigned epoch = *(volatile unsigned*)&g_epoch2;
      if ((tid & 127) < 80) { const uint4 g = __ldg((const uint4*)gate_w + min(tid & 127, 71)); sts128(sb + A_GW + (tid & 127) * 16, g.x, g.y, g.z, g.w); }
      fence_async();
      bar_sync(3, 128);
      float gt[2][4];
      const uint32_t d0 = (sb & 0x3FFFF) >> 4;
#pragma unroll 1
      for (int j = 0; j < 3; j++) {
        mbar_wait(fullx + 8 * j, 0);
        WG_FENCE();
#pragma unroll
        for (int k = 0; k < 24; k++)
          wgmma_n8_ss(gt[k & 1], desc_at(d0 + (k & 1) * (A_XH >> 4) + j * 1536 + (k >> 3) * 512 + (k & 6), 16, 1024, 1), desc_at(d0 + (A_GW >> 4) + j * 24 + (k & 30), 16, 128, 0), j | (k >> 1));
        WG_COMMIT();
      }
      WG_WAIT(0);
      if ((lane & 3) == 0)
#pragma unroll
        for (int i = 0; i < 4; i++) {
          const float gv = 1.f / (1.f + __expf(-gt[i >> 1][(i & 1) * 2]));
          const int r = w * 16 + (lane >> 2) + (i & 1) * 8, tok = 2 * (57 * tile - 7 + r) + (i >> 1);
          sts32(sb + A_GATE + ((i >> 1) * 64 + r) * 4, __float_as_uint(gv));
          if (hh == 0 && r >= 7 && tok < S_LEN) g_gate[tok] = gv;
        }
      if (tid == 256) sts32(sb + A_BAR + 376, epoch);
      __syncwarp();
      bar_arrive(7, 384);
      __half2 hw = __float2half2_rn(0.f);
#pragma unroll
      for (int i = 0; i < 9; i++) { const uint4 v = __ldg((const uint4*)woa + cta * 1152 + i * 128 + (tid & 127)); hw = amax4(hw, &v.x); }
      const uint32_t ew = wexp(hw);
      if (lane == 0) atomicMax(&g_amax[0], (unsigned long long)(epoch + 1) << 32 | ew);
      bar_sync(3, 128);
      if (tid == 256) {
        count_up(&g_abar[0]);
        wait_count(&g_abar[0], NAUX * (epoch + 1));
        if (cta == 0) *(volatile unsigned*)&g_epoch2 = epoch + 1;
      }
      __syncwarp();
      bar_sync(10, 160);
    }
    if (cta < NH) {
      const int lim = w * 8 + (lane >> 2) - 2 * (lane & 3);
      const uint32_t oa = sb + A_OST + (w * 8 + (lane & 7)) * 128;
      const uint32_t d0 = ((sb + A_IN) & 0x3FFFF) >> 4;
      uint32_t p[5][4];
#pragma unroll
      for (int n = 0; n < 10; n++) p[n >> 1][1 + (n & 1)] = __shfl_sync(0xffffffffu, lane ^ n, n);
#pragma unroll 1
      for (int seg = 0; seg < NAUXSEG; seg++) {
        const float gt = __ldcg(&g_gate[seg * 32 + w * 8 + (lane >> 2)]);
        float sc[20], d[32];
        mbar_wait(fullq, seg & 1);
        if (tid == 256) SSTAMP(2, seg);
        WG_FENCE();
#pragma unroll
        for (int k = 0; k < 8; k++) {
          const int o = ((k >> 2) * SEGB + (k & 3) * 256) >> 4;
          wgmma_n40_ss_tt(sc, desc_at(d0 + o, 128, 512, 0), desc_at(d0 + o + 256, 128, 1024, 0), k > 0);
        }
        WG_COMMIT();
        WG_WAIT(0);
        if (lane == 0) mbar_arrive(emptyq);
        float a[10];
#pragma unroll
        for (int i = 0; i < 10; i++) {
          a[i] = sc[(i >> 1) * 4 + (i & 1)] * (SM_SCALE * LOG2E);
          if (i < 8 && (i >> 1) * 8 + (i & 1) > lim) a[i] = -1.0e9f * LOG2E;
        }
        float m = max10(a);
        m = fmaxf(m, __shfl_xor_sync(0xffffffffu, m, 1)); m = fmaxf(m, __shfl_xor_sync(0xffffffffu, m, 2));
#pragma unroll
        for (int i = 0; i < 10; i++) a[i] = ex2(a[i] - m);
#pragma unroll
        for (int n = 0; n < 5; n++) {
          p[n][0] = pack_bf16(a[2 * n], a[2 * n + 1]); p[n][3] = p[n][0] | p[n][1];
          asm volatile("" : "+r"(p[n][0]), "+r"(p[n][3]) :: "memory");
        }
        float sum = ((a[0] + a[1]) + (a[2] + a[3])) + ((a[4] + a[5]) + (a[6] + a[7])) + (a[8] + a[9]);
        sum += __shfl_xor_sync(0xffffffffu, sum, 1);
        mbar_wait(fullv, seg & 1);
        WG_FENCE();
#pragma unroll
        for (int n = 0; n < 5; n++) wgmma_n64_rs(d, p[n], n < 4 ? desc_at(d0 + SEGB / 8 + 8 * n, 4096, 512, 0) : desc_at(d0 + SEGB / 8 + 512, 1024, 128, 0), n);
        WG_COMMIT();
        sum += __shfl_xor_sync(0xffffffffu, sum, 2);
        const float f = (1.f - gt) * rcp(sum);
        bar_sync(5, 160);
        WG_WAIT(0);
        if (lane == 0) mbar_arrive(emptyv);
        if (tid == 256) SSTAMP(4, seg);
#pragma unroll
        for (int q = 0; q < 4; q++) {
          const float* const o = d + (q & 1) * 16 + (q & 2);
          stsm4(oa + (q >> 1) * 4096 + ((((q & 1) * 4 + (lane >> 3)) ^ (lane & 7)) << 4), pack_bf16(o[0] * f, o[1] * f), pack_bf16(o[4] * f, o[5] * f),
                pack_bf16(o[8] * f, o[9] * f), pack_bf16(o[12] * f, o[13] * f));
        }
        fence_async();
        bar_arrive(seg & 1 ? 15 : 4, 160);
      }
    }
  } else {
    asm volatile("setmaxnreg.inc.sync.aligned.u32 200;");
    {
      const int g = lane >> 2, t = lane & 3;
      const uint32_t eb = sb + A_EPI + wg * A_EPW, d0 = (sb & 0x3FFFF) >> 4;
      const uint32_t own = (2 * t <= g ? 0xffffu : 0u) | (2 * t < g ? 0xffff0000u : 0u);
      const int kmin = 7 - 57 * tile - 16 * w;
      __half2 ho = __float2half2_rn(0.f);
#pragma unroll 1
      for (int c = -DRY; c < 4; c++) {
        float acc[96], tl[12];
#pragma unroll 1
        for (int r = c < 0 ? 4 : 0; r < 4; r++) {
#pragma unroll
          for (int st = 0; st < A_NS; st++) {
            const int ks = r * 9 + st;
            if (c == 0 && st % 3 == 0 && ks % 12 == 0) mbar_wait(fullx + 8 * (ks / 12), 0);
            mbar_wait(full1 + 8 * st, r & 1);
            const uint64_t da = desc_at(d0 + wg * (A_XH >> 4) + (ks >> 2) * 512 + (ks & 3) * 2, 16, 1024, 1);
            WG_FENCE();
            wgmma_n192_ss_nt(acc, da, desc_at(d0 + ((A_RING + st * A_WM) >> 4), 2048, 1024, 1), ks);
            if (!(AX & 2)) wgmma_n24_ss_nt(tl, da, desc_at(d0 + ((A_TAIL + st * A_WT) >> 4), 128, 256, 0), ks);
            WG_COMMIT();
            if (st == 0 && r == 2) bar_sync(11 + wg, 160);
            WG_WAIT(1);
            if (ks > 0 && lane == 0) mbar_arrive(empty1 + 8 * ((st + A_NS - 1) % A_NS));
          }
        }
        WG_WAIT(0);
        if (lane == 0 && c >= 0) mbar_arrive(empty1 + 8 * (A_NS - 1));
        ASTAMP(16 + (c & 3));
        uint32_t ql[9], qh[9], kl[9], kh[9], kx[10], vl[9], vh[9], vx[10];
#pragma unroll
        for (int j = 0; j < 9; j++) {
          const float* const q = j < 8 ? acc + 4 * j : tl, * const k = j < 8 ? acc + 32 + 4 * j : tl + 4, * const v = j < 8 ? acc + 64 + 4 * j : tl + 8;
          kh[j] = pack_bf16(k[2], k[3]); vh[j] = pack_bf16(v[2], v[3]);
          ql[j] = pack_bf16(q[0], q[1]); qh[j] = pack_bf16(q[2], q[3]); kl[j] = pack_bf16(k[0], k[1]); vl[j] = pack_bf16(v[0], v[1]);
        }
        if (w < 3) {
          const uint32_t ha = eb + 1024 + w * 2304 + lane * 16;
          stsm4(ha, kh[0], kh[1], kh[2], kh[3]); stsm4(ha + 512, kh[4], kh[5], kh[6], kh[7]);
          stsm4(ha + 1024, vh[0], vh[1], vh[2], vh[3]); stsm4(ha + 1536, vh[4], vh[5], vh[6], vh[7]);
          asm volatile("stmatrix.sync.aligned.m8n8.x2.shared.b16 [%0], {%1,%2};" :: "r"(ha + 2048), "r"(kh[8]), "r"(vh[8]) : "memory");
        }
        if (c == 0) bar_sync(7, 384); else bar_sync(1 + wg, 128);
        {
          const uint32_t ha = eb + 1024 + max(w - 1, 0) * 2304 + lane * 16;
          ldsm4(kx, ha); ldsm4(kx + 4, ha + 512); ldsm4t(vx, ha + 1024); ldsm4t(vx + 4, ha + 1536);
          asm volatile("ldmatrix.sync.aligned.m8n8.x1.shared.b16 {%0}, [%1];" : "=r"(kx[8]) : "r"(ha + 2048) : "memory");
          asm volatile("ldmatrix.sync.aligned.m8n8.x1.trans.shared.b16 {%0}, [%1];" : "=r"(vx[8]) : "r"(ha + 2176) : "memory");
        }
        const float gl = __uint_as_float(lds32(sb + A_GATE + (wg * 64 + w * 16 + g) * 4)), gh = __uint_as_float(lds32(sb + A_GATE + (wg * 64 + w * 16 + g + 8) * 4));
#pragma unroll
        for (int j = 0; j < 9; j++) { vl[j] = movm(vl[j]); vh[j] = movm(vh[j]); }
        bar_sync(1 + wg, 128);
        uint32_t ol[9], oh[9];
#pragma unroll
        for (int i = 0; i < 4; i++) {
          const int b = 2 * i;
          const uint32_t a[4] = {t >= i ? ql[b] : 0u, t >= i ? qh[b] : 0u, ql[b + 1], qh[b + 1]}, a4 = t <= i ? ql[b + 2] : 0u, a5 = t <= i ? qh[b + 2] : 0u;
          float sx[4], sl[4], sh[4];
          mma16816z(sx, a, kx[b], kx[b + 1]); mma16816z(sl, a, kl[b], kl[b + 1]); mma16816z(sh, a, kh[b], kh[b + 1]);
          mma1688(sx, a4, a5, kx[b + 2]); mma1688(sl, a4, a5, kl[b + 2]); mma1688(sh, a4, a5, kh[b + 2]);
          float e[4];
#pragma unroll
          for (int u = 0; u < 4; u++) {
            const int cc = 2 * t + (u & 1);
            e[u] = (cc <= g ? (u < 2 ? sl[u] : sh[u]) : (u < 2 ? sx[u] : sl[u])) * (0.23570226039551584f * LOG2E);
            if ((cc <= g ? cc : cc - 8) + (u & 2) * 4 < kmin) e[u] = -1.0e9f * LOG2E;
          }
          float m0 = fmaxf(e[0], e[1]), m1 = fmaxf(e[2], e[3]);
#pragma unroll
          for (int o = 1; o < 4; o <<= 1) { m0 = fmaxf(m0, __shfl_xor_sync(0xffffffffu, m0, o)); m1 = fmaxf(m1, __shfl_xor_sync(0xffffffffu, m1, o)); }
          e[0] = ex2(e[0] - m0); e[1] = ex2(e[1] - m0); e[2] = ex2(e[2] - m1); e[3] = ex2(e[3] - m1);
          const uint32_t p0 = pack_bf16(e[0], e[1]), p1 = pack_bf16(e[2], e[3]);
          const uint32_t p[4] = {p0 & ~own, 0u, p0 & own, p1 & ~own};
          float s0 = e[0] + e[1], s1 = e[2] + e[3];
#pragma unroll
          for (int o = 1; o < 4; o <<= 1) { s0 += __shfl_xor_sync(0xffffffffu, s0, o); s1 += __shfl_xor_sync(0xffffffffu, s1, o); }
          const float f0 = gl * rcp(s0), f1 = gh * rcp(s1);
#pragma unroll
          for (int j = b; j < b + 3; j++) {
            float o[4];
            mma16816z(o, p, vx[j], vl[j]);
            mma1688(o, 0u, p1 & own, vh[j]);
            const uint32_t lo = pack_bf16(o[0] * f0, o[1] * f0), hi = pack_bf16(o[2] * f1, o[3] * f1);
            if (j > b || i == 0) { ol[j] = lo; oh[j] = hi; }
            else { ol[j] = t >= i ? lo : ol[j]; oh[j] = t >= i ? hi : oh[j]; }
          }
        }
        const uint32_t sa = eb + 16 + (w * 16 + (lane & 15)) * 144 + (lane >> 4) * 16;
#pragma unroll
        for (int j = 0; j < 8; j += 2) stsm4(sa + j * 16, ol[j], oh[j], ol[j + 1], oh[j + 1]);
        asm volatile("stmatrix.sync.aligned.m8n8.x2.shared.b16 [%0], {%1,%2};" :: "r"(sa + 128), "r"(ol[8]), "r"(oh[8]) : "memory");
        ho = amax4(amax4(amax4(amax4(ho, ol), ol + 4), oh), oh + 4);
        ho = __hmax2_nan(__hmax2_nan(ho, __habs2(*(const __half2*)&ol[8])), __habs2(*(const __half2*)&oh[8]));
        if (c == 3 && tile == 17) {
          const uint32_t eo = wexp(ho);
          if (lane == 0) atomicMax(&g_amax[16], (unsigned long long)(lds32(sb + A_BAR + 376) + 1) << 32 | eo);
        }
        fence_async();
        if (c >= 0) bar_arrive(13 + wg, 160); else bar_sync(1 + wg, 128);
        ASTAMP(20 + (c & 3));
      }
    }
    ASTAMP(3);
    uint32_t wa[36][4];
    mbar_wait(fullw, 0);
    const uint32_t la = sb + wg * 73728 + ((lane & 7) + ((lane >> 4) << 3)) * 128 + (((2 * w + ((lane >> 3) & 1)) ^ (lane & 7)) << 4);
#pragma unroll
    for (int k = 0; k < 36; k++) ldsm4t(wa[k], la + k * 2048);
    fence_async();
    bar_sync(6, 288);
    ASTAMP(4);
    float own[4] = {0.f, 0.f, 0.f, 0.f};
    uint4 v[3];
    auto fetch = [&](int seg) {
      const uint4* src = g_part + (((seg & 3) * 36 + cta) * 4) * 128 + (tid & 127);
#pragma unroll
      for (int j = 0; j < 3; j++) v[j] = AX & 16 ? make_uint4(0, 0, 0, 0) : ldg_relaxed(src + ((kq + 1 + j) & 3) * 128);
    };
    auto finish = [&](int seg) {
      const uint32_t tagv = ((seg >> 2) + 1) & 3;
      int n = 0;
#pragma unroll 1
      while (!(AX & 16) && __any_sync(0xffffffffu, (v[0].x & 3) != tagv || (v[1].x & 3) != tagv || (v[2].x & 3) != tagv) && ++n < SPIN_LIMIT) {
        if (seg < NAUXSEG - ((TL & 2) ? 2 : 1)) __nanosleep(200);
        fetch(seg);
      }
#pragma unroll
      for (int j = 0; j < 3; j++) {
        own[0] += __uint_as_float(v[j].x & ~3u); own[1] += __uint_as_float(v[j].y); own[2] += __uint_as_float(v[j].z); own[3] += __uint_as_float(v[j].w);
      }
      uint32_t p0 = pack_bf16(own[0], own[1]), p1 = pack_bf16(own[2], own[3]);
      asm volatile("movmatrix.sync.aligned.m8n8.trans.b16 %0, %0;" : "+r"(p0));
      asm volatile("movmatrix.sync.aligned.m8n8.trans.b16 %0, %0;" : "+r"(p1));
      uint32_t* o = (uint32_t*)(out + (size_t)(seg * 32 + kq * 8 + (lane >> 2)) * DM + nsl * 64 + w * 16) + (lane & 3);
      o[0] = p0; o[4] = p1;
    };
    float acc[16];
    auto stream = [&](int sl, int keep) {
      const uint64_t db = make_desc(sb + sl * XT, 16, 1024, 1);
      WG_FENCE();
#pragma unroll
      for (int k = 0; k < 36; k++) wgmma_n32_rs(acc, wa[k][0], wa[k][1], wa[k][2], wa[k][3], db + (k >> 2) * 256 + (k & 3) * 2, k ? 1 : keep);
      WG_COMMIT();
    };
    const uint32_t ex = sb + A_EX + (tid & 127) * 16;
    if (wg == 0) {
#pragma unroll
      for (int i = 0; i < 16; i++) acc[i] = 0.f;
#pragma unroll 1
      for (int seg = 0; seg < NAUXSEG; seg++) {
        const int sl = (seg & 1) * 2;
        mbar_wait(full3 + 8 * sl, (seg >> 1) & 1);
        if (kq == 3) {
          const uint64_t da = make_desc(sb + A_XW, 8192, 1024, 1), de = make_desc(sb + A_XT + (seg & 1) * 4096, 16, 1024, 1);
          WG_FENCE();
#pragma unroll
          for (int j = 0; j < 4; j++) wgmma_n32_ss_tn(acc, da + j * 128, de + j * 2, j);
          WG_COMMIT();
          WG_WAIT(0);
        }
        if (!(AX & 64)) stream(sl, kq == 3);
        bar_arrive(9, 256);
        WG_WAIT(0);
        if (lane == 0) mbar_arrive(empty3 + 8 * sl);
#pragma unroll
        for (int i = 0; i < 4; i++)
          sts128(ex + (seg & 1) * 8192 + i * 2048, __float_as_uint(acc[4 * i]), __float_as_uint(acc[4 * i + 1]), __float_as_uint(acc[4 * i + 2]), __float_as_uint(acc[4 * i + 3]));
        bar_sync(1, 256);
      }
    } else {
#pragma unroll 1
      for (int seg = 0; seg < NAUXSEG; seg++) {
        const int sl = (seg & 1) * 2 + 1;
        mbar_wait(full3 + 8 * sl, (seg >> 1) & 1);
        if (tid == 128) SSTAMP(6, seg);
        bar_sync(9, 256);
        if (!(AX & 64)) stream(sl, 0);
        bar_sync(1, 256);
        fetch(max(seg - 1, 0));
        WG_WAIT(0);
        if (lane == 0) mbar_arrive(empty3 + 8 * sl);
        float nxt[4] = {0.f, 0.f, 0.f, 0.f};
        uint4* dst = g_part + (((seg & 3) * 36 + nsl * 4) * 4 + kq) * 128 + (tid & 127);
#pragma unroll
        for (int j = 0; j < 4; j++) {
          float o[4];
          lds128f(ex + (seg & 1) * 8192 + j * 2048, o);
#pragma unroll
          for (int i = 0; i < 4; i++) { o[i] += acc[4 * j + i]; if (j == kq) nxt[i] = o[i]; }
          if (j != kq && !(AX & 16)) stg_relaxed(dst + j * 512, (__float_as_uint(o[0]) & ~3u) | (((seg >> 2) + 1) & 3), __float_as_uint(o[1]), __float_as_uint(o[2]), __float_as_uint(o[3]));
        }
        if (tid == 128) SSTAMP(7, seg);
        if (seg > 0) finish(seg - 1);
        if (tid == 128) SSTAMP(8, seg);
#pragma unroll
        for (int i = 0; i < 4; i++) own[i] = nxt[i];
        if ((seg & 7) == 6) ASTAMP(5 + (seg >> 3));
      }
      fetch(NAUXSEG - 1);
      finish(NAUXSEG - 1);
    }
    ASTAMP(13);
    TSTAMP(48);
    bar_sync(6, 288);
  }
}

typedef CUresult (*EncodeFn)(CUtensorMap*, CUtensorMapDataType, cuuint32_t, void*, const cuuint64_t*, const cuuint64_t*,
                             const cuuint32_t*, const cuuint32_t*, CUtensorMapInterleave, CUtensorMapSwizzle,
                             CUtensorMapL2promotion, CUtensorMapFloatOOBfill);
static void make_map(EncodeFn enc, CUtensorMap* m, const void* p, int rows, int cols, int box_rows) {
  cuuint64_t dims[2] = {(cuuint64_t)cols, (cuuint64_t)rows};
  cuuint64_t strides[1] = {(cuuint64_t)cols * 2};
  cuuint32_t box[2] = {64, (cuuint32_t)box_rows};
  cuuint32_t es[2] = {1, 1};
  enc(m, CU_TENSOR_MAP_DATA_TYPE_BFLOAT16, 2, (void*)p, dims, strides, box, es, CU_TENSOR_MAP_INTERLEAVE_NONE,
      CU_TENSOR_MAP_SWIZZLE_128B, CU_TENSOR_MAP_L2_PROMOTION_L2_128B, CU_TENSOR_MAP_FLOAT_OOB_FILL_NONE);
}

constexpr int g_poll = POLL_NS;
extern "C" void kernel_launch(void* const* d_in, const int* in_sizes, int n_in, void* d_out, int out_size) {
  const bf16* x = (const bf16*)d_in[0];
  const bf16* wqkvA = (const bf16*)d_in[1];
  const bf16* woA = (const bf16*)d_in[2];
  const bf16* mem0 = (const bf16*)d_in[4];
  const bf16* Wq = (const bf16*)d_in[5];
  const bf16* Wk = (const bf16*)d_in[6];
  const bf16* Wv = (const bf16*)d_in[7];
  const bf16* Wo = (const bf16*)d_in[8];
  const bf16* gate_w = (const bf16*)d_in[10];
  static EncodeFn enc = nullptr;
  static void *pO = nullptr, *pR = nullptr;
  if (!enc) {
    cudaDriverEntryPointQueryResult qr;
    cudaGetDriverEntryPoint("cuTensorMapEncodeTiled", (void**)&enc, cudaEnableDefault, &qr);
    cudaGetSymbolAddress(&pO, g_Ocat);
    cudaGetSymbolAddress(&pR, g_red_raw);
    cudaFuncSetAttribute(rec_kernel, cudaFuncAttributeMaxDynamicSharedMemorySize, SM_TOTAL);
    cudaFuncSetAttribute(aux_kernel, cudaFuncAttributeMaxDynamicSharedMemorySize, A_TOTAL);
  }
  RMaps rm;
  rm.poll = g_poll; rm.out = (bf16*)d_out;
  make_map(enc, &rm.woa, woA, DM, DM, 24);
  {
    cuuint64_t dims[2] = {KCAT, S_LEN}, strides[1] = {KCAT * 2};
    cuuint32_t box[2] = {32, 64}, es[2] = {1, 1};
    enc(&rm.oa, CU_TENSOR_MAP_DATA_TYPE_BFLOAT16, 2, pO, dims, strides, box, es, CU_TENSOR_MAP_INTERLEAVE_NONE,
        CU_TENSOR_MAP_SWIZZLE_NONE, CU_TENSOR_MAP_L2_PROMOTION_NONE, CU_TENSOR_MAP_FLOAT_OOB_FILL_NONE);
  }
  rm.red = (unsigned char*)(((uintptr_t)pR + 262143) & ~(uintptr_t)262143);
  {
    cuuint64_t dims[3] = {64, S_LEN, 9}, strides[2] = {DM * 2, 128};
    cuuint32_t box[3] = {64, 32, 9}, es[3] = {1, 1, 1};
    enc(&rm.x, CU_TENSOR_MAP_DATA_TYPE_BFLOAT16, 3, (void*)x, dims, strides, box, es, CU_TENSOR_MAP_INTERLEAVE_NONE,
        CU_TENSOR_MAP_SWIZZLE_128B, CU_TENSOR_MAP_L2_PROMOTION_L2_128B, CU_TENSOR_MAP_FLOAT_OOB_FILL_NONE);
  }
  make_map(enc, &rm.wq, Wq, DM, 4096, 192);
  make_map(enc, &rm.wk, Wk, DM, 4096, 192);
  make_map(enc, &rm.wv, Wv, DM, 4096, 192);
  make_map(enc, &rm.wo, Wo, 4096, DM, 128);
  AMaps am;
  {
    cuuint32_t es[4] = {1, 1, 1, 1};
    cuuint64_t dx[4] = {64, 2, S_LEN / 2, 9}, sx[3] = {DM * 2, DM * 4, 128};
    cuuint32_t bx[4] = {64, 1, 64, 3};
    enc(&am.x, CU_TENSOR_MAP_DATA_TYPE_BFLOAT16, 4, (void*)x, dx, sx, bx, es, CU_TENSOR_MAP_INTERLEAVE_NONE,
        CU_TENSOR_MAP_SWIZZLE_128B, CU_TENSOR_MAP_L2_PROMOTION_L2_128B, CU_TENSOR_MAP_FLOAT_OOB_FILL_NONE);
    cuuint64_t dw[3] = {DM, DM, 3}, sw[2] = {DM * 6, DM * 2};
    cuuint32_t bw[3] = {64, 16, 3}, bt[3] = {8, 16, 3};
    enc(&am.wa, CU_TENSOR_MAP_DATA_TYPE_BFLOAT16, 3, (void*)wqkvA, dw, sw, bw, es, CU_TENSOR_MAP_INTERLEAVE_NONE,
        CU_TENSOR_MAP_SWIZZLE_128B, CU_TENSOR_MAP_L2_PROMOTION_L2_128B, CU_TENSOR_MAP_FLOAT_OOB_FILL_NONE);
    enc(&am.wt, CU_TENSOR_MAP_DATA_TYPE_BFLOAT16, 3, (void*)wqkvA, dw, sw, bt, es, CU_TENSOR_MAP_INTERLEAVE_NONE,
        CU_TENSOR_MAP_SWIZZLE_NONE, CU_TENSOR_MAP_L2_PROMOTION_NONE, CU_TENSOR_MAP_FLOAT_OOB_FILL_NONE);
    cuuint64_t dz[3] = {KCAT, 2, S_LEN / 2}, sz[2] = {KCAT * 2, KCAT * 4};
    cuuint32_t bz[3] = {72, 1, 57};
    enc(&am.oa, CU_TENSOR_MAP_DATA_TYPE_BFLOAT16, 3, pO, dz, sz, bz, es, CU_TENSOR_MAP_INTERLEAVE_NONE,
        CU_TENSOR_MAP_SWIZZLE_NONE, CU_TENSOR_MAP_L2_PROMOTION_NONE, CU_TENSOR_MAP_FLOAT_OOB_FILL_NONE);
  }
  {
    cuuint64_t dims[3] = {64, S_LEN, KCAT / 64}, strides[2] = {KCAT * 2, 128};
    cuuint32_t box[3] = {64, 32, 9}, es[3] = {1, 1, 1};
    make_map(enc, &am.o, pO, S_LEN, KCAT, 32);
    enc(&am.o3, CU_TENSOR_MAP_DATA_TYPE_BFLOAT16, 3, pO, dims, strides, box, es, CU_TENSOR_MAP_INTERLEAVE_NONE,
        CU_TENSOR_MAP_SWIZZLE_128B, CU_TENSOR_MAP_L2_PROMOTION_L2_128B, CU_TENSOR_MAP_FLOAT_OOB_FILL_NONE);
  }
  make_map(enc, &am.wob, Wo, 4096, DM, 64);
  make_map(enc, &am.woa, woA, DM, DM, 64);

  rec_kernel<<<96, 384, SM_TOTAL, cudaStreamPerThread>>>(rm, x, mem0);
  cudaLaunchConfig_t cfg = {};
  cfg.gridDim = dim3(NAUX); cfg.blockDim = dim3(512); cfg.dynamicSmemBytes = A_TOTAL; cfg.stream = cudaStreamPerThread;
  cudaLaunchAttribute at[1];
  at[0].id = cudaLaunchAttributeProgrammaticStreamSerialization; at[0].val.programmaticStreamSerializationAllowed = 1;
  cfg.attrs = at; cfg.numAttrs = 1;
  if (XP & 16) cfg.numAttrs = 0;
  if (!(XP & 64)) cudaLaunchKernelEx(&cfg, aux_kernel, am, wqkvA, woA, gate_w, (bf16*)d_out);
}
```

```cpp
#include <cuda_runtime.h>
#include <cuda_bf16.h>
#include <cuda_fp16.h>
#include <cuda.h>
#include <stdint.h>

typedef __nv_bfloat16 bf16;

constexpr int S_LEN = 2048, DM = 576, NH = 32, DH = 128, NSEG = 64, KCAT = 4096 + 576;
constexpr int NAUXSEG = NSEG - 2;
constexpr int NAUX = 36;
#define RED_LINE(i) (((i) >> 2) * 4096 + ((i) & 1) * 256 + ((i) & 2) * 512)
#define RED_SLOT(s) (((s) & 1) * 128 + ((s) & 2) * 256)

#define POLL_NS 896
#define NII 18
#define W3PRE 4
#define W3MID 4
#define GF 0
#define B5POS 0
#define NUP 4
#define UPF 1
#define B3Q 9
#define B3F 0
#define GATE 7
#define NTL 2
#define B7R 1
#define VS0 1
#define VS1 0
#define VLATE(w) ((w) == 0 ? VS0 == 1 : (w) == 1 ? VS1 == 1 : false)
#define HOIST 1
#define GDW 0
#define RSLOW 0
#define CSY 0
#define DD 2
#define N12 18
#define N14 18
#define HP 0
#define HL 0
#define WL 1
#define RV 3
#define RET 1
#define TL 6
#define CLR 1
#define RFW 0
#define NIC 0
#define LEAD 0
#define FIN16 1
#define VXG 0
#define NRING 20
#define EXD 0
#define HDLY 0
#define F10 1
#define NPROBE 2
#define QM 0
#define N5 224
#define KP(i) (((i) >> 1) + 4 * ((i) & 1))
#define SPIN_LIMIT (1 << 14)
#define XP 0

__device__ __align__(1024) bf16 g_Ocat[S_LEN * KCAT];
__device__ __align__(1024) unsigned char g_red_raw[2 * 262144];
constexpr int HINT_OFF = 2048;
__device__ __align__(16) float g_gate[S_LEN];
__device__ __align__(128) uint4 g_stats[96 * 2];
__device__ unsigned g_epoch;
__device__ unsigned g_epoch2;
__device__ unsigned g_ocnt[NSEG * 64];
__device__ unsigned g_abar[3 * 32];
__device__ unsigned long long g_amax[2 * 16];
__device__ unsigned g_scnt[NSEG * 32 * 8];
__device__ __align__(1024) unsigned char g_seg[NRING * 96 * 10240];
__device__ unsigned g_used[NH * 32];
__device__ __align__(1024) uint2 g_part[4 * 9 * 64 * 64];
__device__ int g_err;
#define TSTAMP(i)
#define PROF(idx)
#define PROFP(idx)
#define RSTAMP(k)
#define STAMP(idx)
#define ASTAMP(idx)
#define SSTAMP(k, seg)
#define WSTAMP(idx)

#define DI __device__ __forceinline__
DI uint32_t smem_u32(const void* p) { return (uint32_t)__cvta_generic_to_shared(p); }
DI uint32_t clock32() { uint32_t c; asm volatile("mov.u32 %0, %%clock;" : "=r"(c) :: "memory"); return c; }
DI uint32_t gtime() { uint32_t c; asm volatile("mov.u32 %0, %%globaltimer_lo;" : "=r"(c) :: "memory"); return c; }
DI uint32_t ldg_relaxed32(const void* p) { uint32_t v; asm volatile("ld.relaxed.gpu.global.b32 %0, [%1];" : "=r"(v) : "l"(p) : "memory"); return v; }
DI uint32_t ldg_acquire32(const void* p) { uint32_t v; asm volatile("ld.acquire.gpu.global.b32 %0, [%1];" : "=r"(v) : "l"(p) : "memory"); return v; }
DI void stg_relaxed32(void* p, uint32_t v) { asm volatile("st.relaxed.gpu.global.b32 [%0], %1;" :: "l"(p), "r"(v) : "memory"); }
DI int head_id() { int c; asm volatile("mov.u32 %0, %%clusterid.x;" : "=r"(c)); return c; }
DI uint32_t mapa(uint32_t a, uint32_t r) { uint32_t o; asm("mapa.shared::cluster.u32 %0, %1, %2;" : "=r"(o) : "r"(a), "r"(r)); return o; }
DI void cluster_arrive() { asm volatile("barrier.cluster.arrive.relaxed.aligned;" ::: "memory"); }
DI void cluster_wait() { asm volatile("barrier.cluster.wait.aligned;" ::: "memory"); }
DI void cluster_sync() { asm volatile("barrier.cluster.arrive.release.aligned;\nbarrier.cluster.wait.acquire.aligned;" ::: "memory"); }
DI void mbar_init(uint32_t b, uint32_t c) { asm volatile("mbarrier.init.shared::cta.b64 [%0], %1;" :: "r"(b), "r"(c) : "memory"); }
DI void mbar_expect(uint32_t b, uint32_t tx) { asm volatile("mbarrier.arrive.expect_tx.shared::cta.b64 _, [%0], %1;" :: "r"(b), "r"(tx) : "memory"); }
DI void mbar_arrive(uint32_t b) { asm volatile("mbarrier.arrive.shared::cta.b64 _, [%0];" :: "r"(b) : "memory"); }
DI void mbar_wait(uint32_t b, uint32_t par) {
  asm volatile("{\n.reg .pred p;\n.reg .u32 n, q;\nmov.u32 n, 0;\n"
               "WL: add.u32 n, n, 1;\nshr.u32 q, n, 12;\nxor.b32 q, q, %1;\n"
               "mbarrier.try_wait.parity.shared::cta.b64 p, [%0], q;\n@!p bra.uni WL;\n}"
               :: "r"(b), "r"(par) : "memory");
}
DI void mbar_wait_fast(uint32_t b, uint32_t par) {
  asm volatile("{\n.reg .pred p;\n.reg .u32 n, q;\nmbarrier.try_wait.parity.shared::cta.b64 p, [%0], %1;\n@p bra.uni WD;\nmov.u32 n, 0;\n"
               "WL: add.u32 n, n, 1;\nshr.u32 q, n, 12;\nxor.b32 q, q, %1;\n"
               "mbarrier.try_wait.parity.shared::cta.b64 p, [%0], q;\n@!p bra.uni WL;\nWD:\n}"
               :: "r"(b), "r"(par) : "memory");
}
DI void wait_until(uint32_t t) {
  const uint32_t now = gtime();
  t = min(t, now + 8192);
  asm volatile("{\n.reg .pred p;\n.reg .u32 c;\nTL: mov.u32 c, %%globaltimer_lo;\nsetp.lt.u32 p, c, %0;\n@p bra.uni TL;\n}" :: "r"(t) : "memory");
}
#define PIN(v) v = __shfl_xor_sync(0xffffffffu, v, 0)
#define SCHED_FENCE(k) asm volatile("{\n.reg .pred p;\nsetp.eq.u32 p, %0, %1;\n@p exit;\n}" :: "r"(fence_reg), "r"(k) : "memory")
#define MEM_ORDER(k) asm volatile("{\n.reg .pred p;\nsetp.eq.u32 p, %0, %1;\n@p st.shared.u32 [%0], %0;\n}" :: "r"(fence_reg), "r"(k + 64) : "memory")
DI void bar_sync(int id, int n) { asm volatile("bar.sync %0, %1;" :: "r"(id), "r"(n) : "memory"); }
DI void bar_arrive(int id, int n) { asm volatile("bar.arrive %0, %1;" :: "r"(id), "r"(n) : "memory"); }
DI void fence_async() { asm volatile("fence.proxy.async.shared::cta;" ::: "memory"); }
DI void st_async4(uint32_t a, uint32_t x, uint32_t y, uint32_t z, uint32_t w, uint32_t mb) {
  asm volatile("st.async.weak.shared::cluster.mbarrier::complete_tx::bytes.v4.b32 [%0], {%1,%2,%3,%4}, [%5];"
               :: "r"(a), "r"(x), "r"(y), "r"(z), "r"(w), "r"(mb) : "memory");
}
DI void st_async2(uint32_t a, uint32_t x, uint32_t y, uint32_t mb) {
  asm volatile("st.async.weak.shared::cluster.mbarrier::complete_tx::bytes.v2.b32 [%0], {%1,%2}, [%3];"
               :: "r"(a), "r"(x), "r"(y), "r"(mb) : "memory");
}
DI void sts32(uint32_t a, uint32_t x) { asm volatile("st.shared.b32 [%0], %1;" :: "r"(a), "r"(x) : "memory"); }
DI void sts64(uint32_t a, uint32_t x, uint32_t y) { asm volatile("st.shared.v2.b32 [%0], {%1,%2};" :: "r"(a), "r"(x), "r"(y) : "memory"); }
DI void sts128(uint32_t a, uint32_t x, uint32_t y, uint32_t z, uint32_t w) {
  asm volatile("st.shared.v4.b32 [%0], {%1,%2,%3,%4};" :: "r"(a), "r"(x), "r"(y), "r"(z), "r"(w) : "memory");
}
DI uint32_t lds32(uint32_t a) { uint32_t x; asm volatile("ld.shared.b32 %0, [%1];" : "=r"(x) : "r"(a) : "memory"); return x; }
DI void lds64(uint32_t a, uint32_t& x, uint32_t& y) { asm volatile("ld.shared.v2.b32 {%0,%1}, [%2];" : "=r"(x), "=r"(y) : "r"(a) : "memory"); }
DI void lds128(uint32_t a, uint32_t* r) {
  asm volatile("ld.shared.v4.b32 {%0,%1,%2,%3}, [%4];" : "=r"(r[0]), "=r"(r[1]), "=r"(r[2]), "=r"(r[3]) : "r"(a) : "memory");
}
DI void lds128f(uint32_t a, float* r) {
  asm volatile("ld.shared.v4.f32 {%0,%1,%2,%3}, [%4];" : "=f"(r[0]), "=f"(r[1]), "=f"(r[2]), "=f"(r[3]) : "r"(a) : "memory");
}
DI void lds64f(uint32_t a, float* r) { asm volatile("ld.shared.v2.f32 {%0,%1}, [%2];" : "=f"(r[0]), "=f"(r[1]) : "r"(a) : "memory"); }
DI void ldsm4t(uint32_t* r, uint32_t a) {
  asm volatile("ldmatrix.sync.aligned.m8n8.x4.trans.shared.b16 {%0,%1,%2,%3}, [%4];"
               : "=r"(r[0]), "=r"(r[1]), "=r"(r[2]), "=r"(r[3]) : "r"(a) : "memory");
}
DI void ldsm4t_in(uint32_t* r, uint32_t a, uint32_t t) {
  asm volatile("{\n.reg .pred p;\nsetp.ne.u32 p, %5, 0;\n@p ldmatrix.sync.aligned.m8n8.x4.trans.shared.b16 {%0,%1,%2,%3}, [%4];\n}"
               : "+r"(r[0]), "+r"(r[1]), "+r"(r[2]), "+r"(r[3]) : "r"(a), "r"(t) : "memory");
}
DI void lds128_in(uint32_t* r, uint32_t a, uint32_t t) {
  asm volatile("{\n.reg .pred p;\nsetp.ne.u32 p, %5, 0;\n@p ld.shared.v4.b32 {%0,%1,%2,%3}, [%4];\n}"
               : "+r"(r[0]), "+r"(r[1]), "+r"(r[2]), "+r"(r[3]) : "r"(a), "r"(t) : "memory");
}
DI void ldsm2t_in(uint32_t* r, uint32_t a, uint32_t t) {
  asm volatile("{\n.reg .pred p;\nsetp.ne.u32 p, %3, 0;\n@p ldmatrix.sync.aligned.m8n8.x2.trans.shared.b16 {%0,%1}, [%2];\n}" : "+r"(r[0]), "+r"(r[1]) : "r"(a), "r"(t) : "memory");
}
DI void reserve2(uint32_t* r) { asm volatile("{\n.reg .u64 t;\nmov.u64 t, %%clock64;\nmov.b64 {%0, %1}, t;\n}" : "=r"(r[0]), "=r"(r[1])); }
DI void scale_sum(float& x, float& y, float s, uint32_t t) {
  asm volatile("{\n.reg .pred p;\nsetp.ne.u32 p, %2, 0;\n@p mul.f32 %0, %0, %1;\n}" : "+f"(y) : "f"(s), "r"(t));
  asm volatile("{\n.reg .pred p;\nsetp.ne.u32 p, %3, 1;\n@p fma.rn.f32 %0, %0, %1, %2;\n}" : "+f"(x) : "f"(s), "f"(y), "r"(t));
}
DI void ldsm4(uint32_t* r, uint32_t a) {
  asm volatile("ldmatrix.sync.aligned.m8n8.x4.shared.b16 {%0,%1,%2,%3}, [%4];"
               : "=r"(r[0]), "=r"(r[1]), "=r"(r[2]), "=r"(r[3]) : "r"(a) : "memory");
}
DI void st_async1(uint32_t a, uint32_t x, uint32_t mb) {
  asm volatile("st.async.weak.shared::cluster.mbarrier::complete_tx::bytes.b32 [%0], %1, [%2];" :: "r"(a), "r"(x), "r"(mb) : "memory");
}
DI void stsm4(uint32_t a, uint32_t x, uint32_t y, uint32_t z, uint32_t w) {
  asm volatile("stmatrix.sync.aligned.m8n8.x4.shared.b16 [%0], {%1,%2,%3,%4};" :: "r"(a), "r"(x), "r"(y), "r"(z), "r"(w) : "memory");
}
DI void stsm4t(uint32_t a, uint32_t x, uint32_t y, uint32_t z, uint32_t w) {
  asm volatile("stmatrix.sync.aligned.m8n8.x4.trans.shared.b16 [%0], {%1,%2,%3,%4};" :: "r"(a), "r"(x), "r"(y), "r"(z), "r"(w) : "memory");
}
DI uint32_t pack_bf16(float lo, float hi) { uint32_t r; asm("cvt.rn.bf16x2.f32 %0, %1, %2;" : "=r"(r) : "f"(hi), "f"(lo)); return r; }
DI uint32_t pack_f16(float lo, float hi) { uint32_t r; asm("cvt.rn.f16x2.f32 %0, %1, %2;" : "=r"(r) : "f"(hi), "f"(lo)); return r; }
DI float ex2(float x) { float y; asm("ex2.approx.ftz.f32 %0, %1;" : "=f"(y) : "f"(x)); return y; }
DI float rcp(float x) { float y; asm("rcp.approx.ftz.f32 %0, %1;" : "=f"(y) : "f"(x)); return y; }
DI float bf_lo(uint32_t x) { return __uint_as_float(x << 16); }
DI float bf_hi(uint32_t x) { return __uint_as_float(x & 0xffff0000u); }
DI void mma16816(float* d, const uint32_t* a, uint32_t b0, uint32_t b1) {
  asm volatile("mma.sync.aligned.m16n8k16.row.col.f32.bf16.bf16.f32 {%0,%1,%2,%3}, {%4,%5,%6,%7}, {%8,%9}, {%0,%1,%2,%3};"
               : "+f"(d[0]), "+f"(d[1]), "+f"(d[2]), "+f"(d[3]) : "r"(a[0]), "r"(a[1]), "r"(a[2]), "r"(a[3]), "r"(b0), "r"(b1));
}
DI void mma16816z(float* d, const uint32_t* a, uint32_t b0, uint32_t b1) {
  asm volatile("mma.sync.aligned.m16n8k16.row.col.f32.bf16.bf16.f32 {%0,%1,%2,%3}, {%4,%5,%6,%7}, {%8,%9}, {%10,%10,%10,%10};"
               : "=f"(d[0]), "=f"(d[1]), "=f"(d[2]), "=f"(d[3]) : "r"(a[0]), "r"(a[1]), "r"(a[2]), "r"(a[3]), "r"(b0), "r"(b1), "f"(0.f));
}
DI void mma1688z(float* d, uint32_t a0, uint32_t a1, uint32_t b0) {
  asm volatile("mma.sync.aligned.m16n8k8.row.col.f32.bf16.bf16.f32 {%0,%1,%2,%3}, {%4,%5}, {%6}, {%7,%7,%7,%7};"
               : "=f"(d[0]), "=f"(d[1]), "=f"(d[2]), "=f"(d[3]) : "r"(a0), "r"(a1), "r"(b0), "f"(0.f));
}
DI void mma1688(float* d, uint32_t a0, uint32_t a1, uint32_t b0) {
  asm volatile("mma.sync.aligned.m16n8k8.row.col.f32.bf16.bf16.f32 {%0,%1,%2,%3}, {%4,%5}, {%6}, {%0,%1,%2,%3};"
               : "+f"(d[0]), "+f"(d[1]), "+f"(d[2]), "+f"(d[3]) : "r"(a0), "r"(a1), "r"(b0));
}
DI void ldsm2t(uint32_t* r, uint32_t a) {
  asm volatile("ldmatrix.sync.aligned.m8n8.x2.trans.shared.b16 {%0,%1}, [%2];" : "=r"(r[0]), "=r"(r[1]) : "r"(a) : "memory");
}
DI uint32_t add_bf16(uint32_t a, uint32_t b) { uint32_t r; asm("add.rn.bf16x2 %0, %1, %2;" : "=r"(r) : "r"(a), "r"(b)); return r; }
DI uint32_t mul_bf16(uint32_t a, uint32_t b) { uint32_t r; asm("mul.rn.bf16x2 %0, %1, %2;" : "=r"(r) : "r"(a), "r"(b)); return r; }
DI uint64_t make_desc(uint32_t addr, uint32_t lbo, uint32_t sbo, uint32_t swz) {
  return (uint64_t)((addr & 0x3FFFF) >> 4) | ((uint64_t)(lbo >> 4) << 16) | ((uint64_t)(sbo >> 4) << 32) | ((uint64_t)swz << 62);
}
DI uint64_t desc_at(uint32_t a16, uint32_t lbo, uint32_t sbo, uint32_t swz) {
  uint64_t d; asm("mov.b64 %0, {%1, %2};" : "=l"(d) : "r"(a16 + ((lbo >> 4) << 16)), "r"((sbo >> 4) | (swz << 30)));
  return d;
}
#define WG_FENCE() asm volatile("wgmma.fence.sync.aligned;" ::: "memory")
#define WG_COMMIT() asm volatile("wgmma.commit_group.sync.aligned;" ::: "memory")
#define WG_WAIT(n) asm volatile("wgmma.wait_group.sync.aligned %0;" :: "n"(n) : "memory")
#define ACC8(d, o) "+f"(d[o]), "+f"(d[o + 1]), "+f"(d[o + 2]), "+f"(d[o + 3]), "+f"(d[o + 4]), "+f"(d[o + 5]), "+f"(d[o + 6]), "+f"(d[o + 7])
DI void wgmma_n32_rs(float* d, uint32_t a0, uint32_t a1, uint32_t a2, uint32_t a3, uint64_t db, int acc) {
  asm volatile("{\n.reg .pred p;\nsetp.ne.b32 p, %21, 0;\n"
               "wgmma.mma_async.sync.aligned.m64n32k16.f32.bf16.bf16 {%0,%1,%2,%3,%4,%5,%6,%7,%8,%9,%10,%11,%12,%13,%14,%15}, "
               "{%16,%17,%18,%19}, %20, p, 1, 1, 0;\n}\n"
               : ACC8(d, 0), ACC8(d, 8) : "r"(a0), "r"(a1), "r"(a2), "r"(a3), "l"(db), "r"(acc));
}
template <int TA>
DI void wgmma_n32_ss(float* d, uint64_t da, uint64_t db, int acc) {
  asm volatile("{\n.reg .pred p;\nsetp.ne.b32 p, %18, 0;\n"
               "wgmma.mma_async.sync.aligned.m64n32k16.f32.bf16.bf16 {%0,%1,%2,%3,%4,%5,%6,%7,%8,%9,%10,%11,%12,%13,%14,%15}, "
               "%16, %17, p, 1, 1, %19, 1;\n}\n"
               : ACC8(d, 0), ACC8(d, 8) : "l"(da), "l"(db), "r"(acc), "n"(TA));
}
DI void tma_load(uint32_t dst, const CUtensorMap* m, int c0, int c1, uint32_t mb) {
  asm volatile("cp.async.bulk.tensor.2d.shared::cluster.global.mbarrier::complete_tx::bytes [%0], [%1, {%3, %4}], [%2];"
               :: "r"(dst), "l"(m), "r"(mb), "r"(c0), "r"(c1) : "memory");
}
DI void tma_load3(uint32_t dst, const CUtensorMap* m, int row, uint32_t mb) {
  asm volatile("cp.async.bulk.tensor.3d.shared::cluster.global.mbarrier::complete_tx::bytes [%0], [%1, {%3, %4, %3}], [%2];"
               :: "r"(dst), "l"(m), "r"(mb), "r"(0), "r"(row) : "memory");
}
DI bool elect_one() {
  uint32_t p;
  asm volatile("{\n.reg .pred p;\nelect.sync _|p, 0xffffffff;\nselp.u32 %0, 1, 0, p;\n}" : "=r"(p));
  return p;
}
DI void bulk_s2s(uint32_t dst, uint32_t src, uint32_t bytes, uint32_t mb) {
  asm volatile("cp.async.bulk.shared::cluster.shared::cta.mbarrier::complete_tx::bytes [%0], [%1], %2, [%3];"
               :: "r"(dst), "r"(src), "r"(bytes), "r"(mb) : "memory");
}
DI void tma_prefetch(const CUtensorMap* m, int c0, int c1) {
  asm volatile("cp.async.bulk.prefetch.tensor.2d.L2.global.tile [%0, {%1, %2}];" :: "l"(m), "r"(c0), "r"(c1) : "memory");
}
DI void tma_store(const CUtensorMap* m, uint32_t src, int c0, int c1) {
  asm volatile("cp.async.bulk.tensor.2d.global.shared::cta.bulk_group [%0, {%2, %3}], [%1];" :: "l"(m), "r"(src), "r"(c0), "r"(c1) : "memory");
}
DI uint4 ldg_relaxed(const void* p) {
  uint4 v;
  asm volatile("ld.relaxed.gpu.global.v4.b32 {%0,%1,%2,%3}, [%4];" : "=r"(v.x), "=r"(v.y), "=r"(v.z), "=r"(v.w) : "l"(p) : "memory");
  return v;
}
DI void stg_relaxed(void* p, uint32_t x, uint32_t y, uint32_t z, uint32_t w) {
  asm volatile("st.relaxed.gpu.global.v4.b32 [%0], {%1,%2,%3,%4};" :: "l"(p), "r"(x), "r"(y), "r"(z), "r"(w) : "memory");
}
DI void red_f16x8(void* p, uint32_t x, uint32_t y, uint32_t z, uint32_t w) {
  asm volatile("red.relaxed.gpu.global.add.noftz.v4.f16x2 [%0], {%1,%2,%3,%4};" :: "l"(p), "r"(x), "r"(y), "r"(z), "r"(w) : "memory");
}
DI void sq_acc(uint32_t& a, uint32_t x) { asm("fma.rn.bf16x2 %0, %1, %1, %0;" : "+r"(a) : "r"(x)); }
DI __half2 amax4(__half2 h, const uint32_t* v) {
  h = __hmax2_nan(__hmax2_nan(h, __habs2(*(const __half2*)&v[0])), __habs2(*(const __half2*)&v[1]));
  return __hmax2_nan(__hmax2_nan(h, __habs2(*(const __half2*)&v[2])), __habs2(*(const __half2*)&v[3]));
}
DI uint32_t wexp(__half2 h) { const uint32_t u = *(const uint32_t*)&h; return __reduce_max_sync(0xffffffffu, max((u >> 16) & 0x7fffu, u & 0x7fffu)) >> 7; }
DI float max10(const float* a) {
  return fmaxf(fmaxf(fmaxf(fmaxf(a[0], a[1]), fmaxf(a[2], a[3])), fmaxf(fmaxf(a[4], a[5]), fmaxf(a[6], a[7]))), fmaxf(a[8], a[9]));
}
DI float quad_max(float m) {
  return fmaxf(fmaxf(m, __shfl_xor_sync(0xffffffffu, m, 1)), fmaxf(__shfl_xor_sync(0xffffffffu, m, 2), __shfl_xor_sync(0xffffffffu, m, 3)));
}
DI float warp_sum(float v) {
#pragma unroll
  for (int o = 16; o; o >>= 1) v += __shfl_xor_sync(0xffffffffu, v, o);
  return v;
}

constexpr int SM_WO3 = 0;
constexpr int SM_X = 16384;
constexpr int XT = 36864;
constexpr int SM_EXP = 126976;
constexpr int SEGB = 10240;
constexpr int SM_BLK = SM_EXP + 8192;
constexpr int SM_VC = SM_BLK + 4 * SEGB;
constexpr int SM_PART = SM_VC + 16384;
constexpr int SM_QM = SM_PART + 4096;
constexpr int SM_E = SM_QM + 1024;
constexpr int SM_VM = SM_E + 1536;
constexpr int SM_OB = SM_VM + 2048;
constexpr int SM_FB = SM_OB + 2048;
constexpr int SM_STAGE = SM_X + XT;
constexpr int SM_MISC = 210944;
constexpr int SM_WOST = 212992;
constexpr int SM_MEM = SM_WOST;
constexpr int SM_MAX = SM_MEM + 11264;
#define MEM_BLK(q) ((q) / 3 * 4096 + (q) % 3 * 1024)
constexpr int SM_TOTAL = 229376;
constexpr int MB_W = SM_MISC;
constexpr int MB_WO = SM_MISC + 24;
constexpr int MB_WO3 = SM_MISC + 32;
constexpr int MB_X = SM_MISC + 40;
constexpr int MB_S = SM_MISC + 64;
constexpr int MB_F = SM_MISC + 72;
constexpr int MB_VX = SM_MISC + 80;
constexpr int SC_FPAR = SM_MISC + 136;
constexpr int SC_DEAD = SM_MISC + 96;
constexpr int SC_UNSC = SM_MISC + 112;
constexpr int SC_EPOCH = SM_MISC + 128;
constexpr int SC_EXPW = SM_MISC + 132;
constexpr int SC_ONES = SM_MISC + 144;
constexpr int SC_SS = SM_MISC + 160;
constexpr int SC_LAT = SM_MISC + 224;
constexpr int MB_T = SM_MISC + 232;
constexpr int T_SX = SM_X + XT;
constexpr int T_OB = SM_X + 2 * XT;
constexpr int T_WA = T_OB + 16384;
constexpr int T_OA = T_WA + 9216;
constexpr int T_G = T_OA + 4096;
constexpr int T_P = T_G + 512;
constexpr int T_UN = T_G + 256;
constexpr int T_RED = 131072;
constexpr int SC_XMAX = SM_MISC + 256;
constexpr int SC_PROF = 229376;

constexpr float SM_SCALE = 0.08838834764831845f;
constexpr float LOG2E = 1.4426950408889634f;
constexpr float E_LIM = 20.f;

template <bool B> struct BoolC { static constexpr bool value = B; };
struct RMaps { CUtensorMap x, wq, wk, wv, wo, woa, oa; unsigned char* red; bf16* out; uint32_t poll; };

DI uint32_t latest_hint(uint32_t h, uint32_t d, int s) {
  const uint32_t x = (((h | 0xc0c0c0c0u) - ((d >> 5) & 63) * 0x01010101u) & 0x3f3f3f3fu) | ((h ^ (((s >> 2) + 1) & 3) * 0x40404040u) & 0xc0c0c0c0u);
  const uint32_t y = __vmaxu2(x & 0x00ff00ffu, (x >> 8) & 0x00ff00ffu);
  return __reduce_max_sync(0xffffffffu, max(y & 0xffffu, y >> 16));
}
DI uint32_t near_half(uint32_t sb) {
  uint32_t a, b; lds64(sb + SC_LAT, a, b);
  return a > b;
}

template <int RT, int K0, int K1, bool D32 = false, int BAR = 0, int KB = 18>
DI void xproj(float* acc, const uint32_t (&wa)[2][18][4], uint64_t xd) {
  if (XP & 1) return;
  WG_FENCE();
#pragma unroll
  for (int k = K0; k < ((XP & 128) ? K0 + 1 : K1); k++)
  {
    uint64_t d = xd + (uint64_t)(((k >> 1) * 4096 + (k & 1) * 32) >> 4);
    if (D32) asm("mov.b64 %0, {%1, %2};" : "=l"(d) : "r"((uint32_t)xd + (((k >> 1) * 4096 + (k & 1) * 32) >> 4)), "r"((uint32_t)(xd >> 32)));
    wgmma_n32_rs(acc, wa[RT][k][0], wa[RT][k][1], wa[RT][k][2], wa[RT][k][3], d, k != 0);
    if (BAR && k == KB - 1 && KB < 18) bar_arrive(BAR, 256);
  }
  WG_COMMIT();
}

DI void seg_store(int seg, uint32_t sb, uint32_t off, uint32_t bytes) {
  asm volatile("cp.async.bulk.global.shared::cta.bulk_group [%0], [%1], %2;"
               :: "l"(g_seg + ((size_t)(seg % NRING) * 96 + blockIdx.x) * SEGB + off), "r"(sb + SM_BLK + (seg & 3) * SEGB + off), "r"(bytes) : "memory");
  asm volatile("cp.async.bulk.commit_group;" ::: "memory");
}
DI void seg_publish(int seg) {
  asm volatile("cp.async.bulk.wait_group 0;" ::: "memory");
  asm volatile("red.relaxed.gpu.global.add.u32 [%0], 1;" :: "l"(&g_scnt[(seg * 32 + blockIdx.x / 3) * 8]) : "memory");
  SSTAMP(10, seg);
}

#define NAP 64
DI uint32_t movm(uint32_t x) { uint32_t r; asm volatile("movmatrix.sync.aligned.m8n8.trans.b16 %0, %1;" : "=r"(r) : "r"(x)); return r; }
DI bool wait_count(const unsigned* p, unsigned target, bool nap = true) {
  int n = 0;
  unsigned v;
  while (true) {
    asm volatile("ld.acquire.gpu.global.b32 %0, [%1];" : "=r"(v) : "l"(p) : "memory");
    if ((int)(v - target) >= 0 || ++n > SPIN_LIMIT) break;
    if (nap) __nanosleep(NAP);
  }
  return n;
}
#define PACE 1200
#define PORD 0
DI void load_weights(uint32_t sb, const RMaps& tm, uint32_t rank, int c) {
  const int h = blockIdx.x / 3;
  if (c < 3) {
    mbar_expect(sb + MB_W + 8 * c, 49152);
    tma_load(sb + SM_STAGE + c * 49152, rank < 2 ? &tm.wk : &tm.wv, h * DH + (rank == 1 ? 64 : 0), c * 192, sb + MB_W + 8 * c);
    tma_load(sb + SM_STAGE + c * 49152 + 24576, rank < 2 ? &tm.wq : &tm.wv, h * DH + (rank == 0 ? 0 : 64), c * 192, sb + MB_W + 8 * c);
  } else {
    tma_prefetch(&tm.wo, rank * 192, h * DH);
    mbar_expect(sb + MB_WO, 16384);
    mbar_expect(sb + MB_WO3, 32768);
    tma_load(sb + SM_WOST, &tm.wo, rank * 192 + 64, h * DH, sb + MB_WO3);
    tma_load(sb + SM_WO3, &tm.wo, rank * 192 + 128, h * DH, sb + MB_WO3);
  }
}

DI void tail_attention(const uint32_t sb, const uint32_t rank, const int w, const int lane, const int sg, const int bar) {
  const int m = lane >> 3, g = lane >> 2, t = lane & 3;
  const uint32_t l16 = sb + lane * 16, src = l16 + T_SX + sg * 10240 + w * 1280;
  if (rank < 2) {
    const uint32_t base = l16 + SM_BLK + (2 + sg) * SEGB, dst = src + rank * 5120;
    uint32_t qb[2][4];
    ldsm4t(qb[0], base + w * 1024); ldsm4t(qb[1], base + w * 1024 + 512);
#pragma unroll
    for (int j = 0; j < 3; j++) {
      uint32_t kb[4][4];
      float c[4][4];
      const uint32_t ka = base + 4096 + j * 2048 + (m & 1) * (j == 2 ? 128 : 896) - (m >> 1) * 128;
#pragma unroll
      for (int k = 0; k < 4; k += j == 2 ? 2 : 1) ldsm4t(kb[k], ka + k * 256);
      mma16816z(c[0], kb[0], qb[0][0], qb[0][1]); mma16816z(c[1], kb[j == 2 ? 0 : 1], qb[0][2], qb[0][3]);
      mma16816z(c[2], kb[2], qb[1][0], qb[1][1]); mma16816z(c[3], kb[j == 2 ? 2 : 3], qb[1][2], qb[1][3]);
      uint32_t r[4];
#pragma unroll
      for (int i = 0; i < (j == 2 ? 2 : 4); i++) r[i] = __float_as_uint((c[0][i] + c[1][j == 2 ? i + 2 : i]) + (c[2][i] + c[3][j == 2 ? i + 2 : i]));
#pragma unroll
      for (int d = 0; d < 2; d++) {
        const uint32_t to = d ? 2 : rank ^ 1, mb = mapa(sb + MB_T + 8 + 8 * sg, to);
        if (j < 2) st_async4(mapa(dst + j * 512, to), r[0], r[1], r[2], r[3], mb);
        else st_async2(mapa(dst + 1024 - lane * 8, to), r[0], r[1], mb);
      }
      if (j < 2) sts128(dst + j * 512, r[0], r[1], r[2], r[3]); else sts64(dst + 1024 - lane * 8, r[0], r[1]);
    }
  }
  TSTAMP(50 + 2 * sg);
  uint32_t vx[4][4], vm[4];
  const uint32_t va = l16 + (rank < 2 ? SM_VC + sg * 8192 : SM_BLK + (2 + sg) * SEGB) + w * 1024 + (m & 1) * 384 - (m >> 1) * 128;
#pragma unroll
  for (int i = 0; i < 4; i++) ldsm4(vx[i], va + (i & 1) * 4096 + (i >> 1) * 256);
  if (sg && rank < 2) mbar_wait(sb + MB_T, 0);
  lds128(l16 + (sg ? SM_FB : SM_VM) + w * 512, vm);
  float a[10], b[10];
  mbar_wait(sb + MB_T + 8 + 8 * sg, 0);
  TSTAMP(58 + 2 * sg);
  lds128f(src, a); lds128f(src + 512, a + 4); lds64f(src + 1024 - lane * 8, a + 8);
  lds128f(src + 5120, b); lds128f(src + 5632, b + 4); lds64f(src + 6144 - lane * 8, b + 8);
#pragma unroll
  for (int i = 0; i < 10; i++) {
    a[i] = (a[i] + b[i]) * (SM_SCALE * LOG2E);
    if (i < 8 && (i >> 1) * 8 + g > w * 8 + 2 * t + (i & 1)) a[i] = -1.0e9f * LOG2E;
  }
  float m0 = fmaxf(fmaxf(fmaxf(a[0], a[2]), fmaxf(a[4], a[6])), a[8]), m1 = fmaxf(fmaxf(fmaxf(a[1], a[3]), fmaxf(a[5], a[7])), a[9]);
#pragma unroll
  for (int o = 4; o < 32; o <<= 1) { m0 = fmaxf(m0, __shfl_xor_sync(0xffffffffu, m0, o)); m1 = fmaxf(m1, __shfl_xor_sync(0xffffffffu, m1, o)); }
#pragma unroll
  for (int i = 0; i < 10; i++) a[i] = ex2(a[i] - (i & 1 ? m1 : m0));
  float s0 = ((a[0] + a[2]) + (a[4] + a[6])) + a[8], s1 = ((a[1] + a[3]) + (a[5] + a[7])) + a[9];
#pragma unroll
  for (int o = 4; o < 32; o <<= 1) { s0 += __shfl_xor_sync(0xffffffffu, s0, o); s1 += __shfl_xor_sync(0xffffffffu, s1, o); }
  s0 = rcp(s0); s1 = rcp(s1);
#pragma unroll
  for (int i = 0; i < 5; i++) sts32(sb + T_P + sg * 2560 + w * 640 + i * 128 + lane * 4, pack_bf16(a[2 * i] * s0, a[2 * i + 1] * s1));
  mbar_wait(sb + MB_WO, 1);
  bar_sync(bar, 128);
  TSTAMP(59 + 2 * sg);
#pragma unroll
  for (int j = 0; j < 4; j++) {
    uint32_t p[5];
    float o0[4], o1[4], f[2];
    lds64f(sb + T_G + sg * 128 + j * 32 + t * 8, f);
    f[0] = 1.f - f[0]; f[1] = 1.f - f[1];
    ldsm4t(p, l16 + T_P + sg * 2560 + j * 640);
    asm volatile("ldmatrix.sync.aligned.m8n8.x1.trans.shared.b16 {%0}, [%1];" : "=r"(p[4]) : "r"(l16 + T_P + sg * 2560 + j * 640 + 512) : "memory");
    mma16816z(o0, vx[0], p[0], p[1]); mma16816z(o1, vx[1], p[0], p[1]);
    mma16816(o0, vx[2], p[2], p[3]); mma16816(o1, vx[3], p[2], p[3]);
    mma1688(o0, vm[0], vm[1], p[4]); mma1688(o1, vm[2], vm[3], p[4]);
    stsm4(l16 + T_OB + sg * 8192 + j * 2048 + w * 512, pack_bf16(o0[0] * f[0], o0[1] * f[1]), pack_bf16(o0[2] * f[0], o0[3] * f[1]),
          pack_bf16(o1[0] * f[0], o1[1] * f[1]), pack_bf16(o1[2] * f[0], o1[3] * f[1]));
  }
}

DI void proj_role(const uint32_t sb, const RMaps& tm, const uint32_t rank, const int wg, const int w, const int lane) {
  const bool qk = rank < 2;
  uint32_t wa[2][18][4];
  {
    const int rr = (lane & 7) + ((lane >> 4) << 3);
    const uint32_t col = ((2 * w + ((lane >> 3) & 1)) ^ (lane & 7)) << 4;
    float ss = 0.f;
#pragma unroll
    for (int c = 0; c < 3; c++) {
      mbar_wait(sb + MB_W + 8 * c, 0);
      if (threadIdx.x == 0) SSTAMP(11, c);
#pragma unroll
      for (int rt = 0; rt < 2; rt++)
#pragma unroll
        for (int k = 0; k < 6; k++)
          ldsm4t(wa[rt][c * 6 + k], sb + SM_STAGE + c * 49152 + (rt ^ wg) * 24576 + (64 * (k >> 1) + 32 * wg + 16 * (k & 1) + rr) * 128 + col);
      if (c < 2) {
        fence_async();
        bar_sync(3, 256);
        if (threadIdx.x == 0) {
          if (c == 0) tma_load3(sb + SM_X + XT, &tm.x, 32, sb + MB_X + 8);
          else { tma_load(sb + SM_X + 2 * XT, &tm.wo, rank * 192, (blockIdx.x / 3) * DH, sb + MB_WO); SSTAMP(11, 11); }
        }
        __syncwarp();
      }
      uint32_t q[4] = {0, 0, 0, 0};
#pragma unroll
      for (int rt = 0; rt < 2; rt++)
#pragma unroll
        for (int k = 0; k < 6; k++)
#pragma unroll
          for (int i = 0; i < 4; i++) sq_acc(q[i], wa[rt][c * 6 + k][i]);
#pragma unroll
      for (int i = 0; i < 4; i++) ss += bf_lo(q[i]) + bf_hi(q[i]);
    }
    ss = warp_sum(ss);
    fence_async();
    cluster_arrive();
    if (lane == 0) sts32(sb + SC_SS + 4 * (wg * 4 + w), qk ? 0 : __float_as_uint(ss));
    bar_arrive(11, 384);
  }
  STAMP(1);
  mbar_wait(sb + MB_X, 0);
  STAMP(2);

  uint32_t t16 = sb + (w * 32 + lane) * 16;
  uint32_t mem_a = sb + SM_MEM + wg * 512 + lane * 16;
  uint32_t fin_a = sb + (lane & 7) * 16 + SM_BLK + (qk ? (wg ^ 1) * 4096 + w * 256 + (lane & 8) * 16 + (lane & 16) * 64
                                              : wg * 4096 + w * 1024 + (lane & 8) * 64 + (lane & 16) * 8);
  PIN(t16); PIN(mem_a); PIN(fin_a);
  const uint32_t fence_reg = mem_a;
  const uint32_t fin2 = qk ? 2048 : 256;
  float acc[16];
  const uint64_t xd0 = make_desc(sb + SM_X + wg * 64, 16, 1024, 1);
  auto do_export = [&]() {
    WG_WAIT(0);
    uint32_t q[8];
#pragma unroll
    for (int j = 0; j < 8; j++) q[j] = pack_bf16(acc[2 * j], acc[2 * j + 1]);
    sts128(t16 + SM_EXP + wg * 4096, q[0], q[1], q[2], q[3]);
    sts128(t16 + SM_EXP + wg * 4096 + 2048, q[4], q[5], q[6], q[7]);
    if (RET) asm volatile("{\n.reg .pred p;\nsetp.eq.u32 p, %2, 0;\n@p add.u32 %0, %0, 1;\n@p add.u32 %1, %1, 1;\nsetp.eq.and.u32 p, %0, %1, p;\n@p exit;\n}"
                          : "+r"(q[3]), "+r"(q[7]) : "r"(t16) : "memory");
  };
  uint32_t o[8];
  auto import = [&]() { lds128(t16 + SM_EXP + (wg ^ 1) * 4096, o); lds128(t16 + SM_EXP + (wg ^ 1) * 4096 + 2048, o + 4); };
  auto finish = [&](int seg) {
    const uint32_t a = fin_a + (seg & 3) * SEGB;
    WG_WAIT(0);
#pragma unroll
    for (int i = 0; i < 8; i++) o[i] = FIN16 ? add_bf16(pack_bf16(acc[2 * i], acc[2 * i + 1]), o[i]) : pack_bf16(acc[2 * i] + bf_lo(o[i]), acc[2 * i + 1] + bf_hi(o[i]));
    stsm4(a, o[0], o[1], o[2], o[3]);
    stsm4(a + fin2, o[4], o[5], o[6], o[7]);
  };
  auto send_v = [&](int seg, int dst) {
    fence_async();
    if (seg < NSEG && !(XP & 2) && elect_one())
      bulk_s2s(mapa(sb + SM_VC + (seg & 1) * 8192, dst), sb + SM_BLK + (seg & 3) * SEGB, 8192, mapa(sb + MB_VX + (seg & 1) * 8, dst));
    __syncwarp();
  };
  auto wait_v = [&](int seg) {
    if (seg < NSEG && !(XP & 2)) {
      mbar_wait(sb + MB_VX + (seg & 1) * 8, (seg >> 1) & 1);
      if (elect_one()) mbar_expect(sb + MB_VX + (seg & 1) * 8, 8192);
      __syncwarp();
    }
  };
  bar_sync(3, 256);
  xproj<1, 0, 18>(acc, wa, xd0);
  do_export();
  SCHED_FENCE(11);
  xproj<0, 0, 18>(acc, wa, xd0);
  bar_sync(3, 256);
  if (threadIdx.x == 0) SSTAMP(11, 12);
  cluster_wait();
  if (threadIdx.x == 0) SSTAMP(11, 13);
  mbar_wait(sb + MB_X + 8, 0);
  import();
  finish(0);
  SCHED_FENCE(12);
  bar_sync(3, 256);
  uint64_t dA = xd0 + (XT >> 4);
  xproj<1, 0, 18>(acc, wa, dA);
  if (!qk && wg == 0 && w < 2) send_v(0, w);
  do_export();
  if (qk && wg == 0 && w == 0) wait_v(0);
  bar_arrive(13, 384);
  if (!qk) {
    SCHED_FENCE(15);
    xproj<0, 0, 18>(acc, wa, dA);
    if (threadIdx.x == 0 && !(XP & 8)) { mbar_expect(sb + MB_X, XT); tma_load3(sb + SM_X, &tm.x, 96, sb + MB_X); }
    bar_sync(3, 256);
    mbar_wait(sb + MB_X + 16, 0);
    import();
    finish(1);
    SCHED_FENCE(16);
    bar_sync(3, 256);
    dA += XT >> 4;
    xproj<1, 0, 18>(acc, wa, dA);
    if (wg == 0 && ((w == 0 && VS0) || (w == 1 && VS1))) send_v(1, w);
    do_export();
  }
  if (threadIdx.x == 0) SSTAMP(11, 14);
  bar_sync(0, 384);
  const int ro = __shfl_sync(0xffffffffu, near_half(sb) ^ wg, 0);
  STAMP(5);
  const uint32_t always = __shfl_sync(0xffffffffu, lds32(sb + SC_DEAD + 12), 0);
  const int ah = qk ? 1 : 2;
  int b2 = qk ? 2 : 0;
  int s = 0;
  uint32_t hint_lo = (uint32_t)(uint64_t)tm.red + HINT_OFF + blockIdx.x + (lane & 1) * 4096 + (lane >> 1) * 16384;
  PIN(hint_lo);
  auto post_hint = [&]() {
    asm volatile("{\n.reg .pred p;\n.reg .b64 a;\n.reg .u32 t;\nsetp.lt.u32 p, %0, %1;\nmov.b64 a, {%2, %3};\nmov.u32 t, %%globaltimer_lo;\n"
                 "bfe.u32 t, t, 5, 6;\nor.b32 t, t, %4;\n@p st.relaxed.gpu.global.u8 [a], t;\n}"
                 :: "r"(t16), "r"(sb + 128), "r"(hint_lo + RED_SLOT(s)), "r"((uint32_t)((uint64_t)tm.red >> 32)), "r"(((s >> 2) + 1) << 6) : "memory");
  };
  auto memproj = [&](auto second, int id, float u0, float u1, float* r) {
    constexpr bool R1 = decltype(second)::value;
    uint32_t b[NUP][4], b0[4];
    SCHED_FENCE(id);
    bar_sync(R1 ? 2 : 1, 256);
    PROF(0);
    ldsm4t(b0, mem_a);
#pragma unroll
    for (int q = 0; q < NUP; q++) {
      if (R1 && q == 2) {
        bar_sync(11, 256);
        SCHED_FENCE(id + 1);
      }
      ldsm4t(b[q], mem_a + MEM_BLK(q + 1));
    }
    mma16816z(&acc[0], wa[0][0], b0[0], b0[1]);
    mma16816z(&acc[4], wa[1][0], b0[0], b0[1]);
    mma16816z(&acc[8], wa[0][1], b0[2], b0[3]);
    mma16816z(&acc[12], wa[1][1], b0[2], b0[3]);
#pragma unroll
    for (int q = 1; q < 9; q++) {
      uint32_t* const c = b[(q - 1) % NUP];
      mma16816(&acc[0], wa[0][2 * q], c[0], c[1]);
      mma16816(&acc[4], wa[1][2 * q], c[0], c[1]);
      mma16816(&acc[8], wa[0][2 * q + 1], c[2], c[3]);
      mma16816(&acc[12], wa[1][2 * q + 1], c[2], c[3]);
      if (R1 && q + NUP == B3Q) bar_sync(3, 256);
      if (q + NUP < 9) ldsm4t_in(c, mem_a + MEM_BLK(q + NUP), always);
      else if (R1 && q + NUP < 11) lds128_in(c, t16 + SM_PART + (10 - q - NUP) * 2048, always);
      else if (!R1 && GATE && q == GATE) { bar_arrive(11, 256); lds128_in(c, sb + SC_DEAD, always); u0 = u1 = __uint_as_float(c[3]); }
    }
#pragma unroll
    for (int i = 0; i < 8; i++) {
      const float u = i < 4 ? u0 : u1;
      r[i] = R1 ? fmaf(acc[8 + i], u, (acc[i] + __uint_as_float(b[(8 + i / 4) % NUP][i & 3])) * u) : (GATE ? fmaf(acc[i], u, acc[8 + i]) : acc[i] + acc[8 + i]);
    }
  };
  if (ro == 0) {
    auto set_scale = [&]() {
      uint32_t m[8];
      lds128(t16 + SM_MAX - 512, m); lds128(t16 + SM_MAX, m + 4);
      const int em = (wexp(amax4(amax4(*(const __half2*)&m[0], m), m + 4)) >> 3) + (int)(lds32(sb + SC_UNSC + (s & 1) * 8) >> 23) - 15;
      const int ex = max(s ? em : 0, (int)lds32(sb + SC_XMAX + 4 * s)) - 127 + (int)lds32(sb + SC_EXPW);
      sts32(sb + SC_UNSC + (~s & 1) * 8, (127 + min(max(ex, -120), 120)) << 23);
    };
#pragma unroll 1
    while (true) {
      if (s == 8) STAMP(6);
      float r[8];
      memproj(BoolC<false>(), 30, 0.f, 0.f, r);
      sts128(t16 + SM_PART, __float_as_uint(r[0]), __float_as_uint(r[1]), __float_as_uint(r[2]), __float_as_uint(r[3]));
      sts128(t16 + SM_PART + 2048, __float_as_uint(r[4]), __float_as_uint(r[5]), __float_as_uint(r[6]), __float_as_uint(r[7]));
      bar_arrive(3, 256);
      PROF(1);
      bar_sync(9, 256);
      if (s == NSEG - 1) break;
      post_hint();
      if (w == 1) {
        set_scale();
        __syncwarp();
        if (elect_one()) mbar_arrive(sb + MB_S);
      }
      SCHED_FENCE(9);
      bar_sync(5, qk ? N5 : 256);
      PROF(2);
      import();
      xproj<0, 0, NII, (DD & 1) != 0>(acc, wa, dA);
      if (NII < 18) {
        if (qk) bar_sync(7, 384);
        xproj<0, NII, 18>(acc, wa, dA);
        if (!qk) bar_sync(7, 384);
      } else {
        if (F10) WG_WAIT(0);
        bar_sync(10, 256);
        if (F10) SCHED_FENCE(17);
      }
      dA += (int64_t)(b2 ? XT >> 4 : -(XT >> 3));
      finish(s + ah);
      if (qk || !VLATE(w)) bar_arrive(13, 384);
      PROF(6);
      SCHED_FENCE(14);
      bar_sync(12, 256);
      PROF(7);
      xproj<1, 0, 18, (DD & 2) != 0, 14, N14>(acc, wa, dA);
      if (N14 == 18) bar_arrive(14, 256);
      b2 = b2 == 2 ? 0 : b2 + 1;
      s++;
      if (!qk && VLATE(w)) { bar_sync(13, 384); send_v(s + 1, w); }
      PROFP(8);
      do_export();
      s--; RSTAMP(6); s++;
      PROFP(3);
    }
    if (!qk) bar_arrive(5, 256);
    if (w == 0 && elect_one()) {
      const uint32_t h18 = blockIdx.x / 3 * 18;
      mbar_expect(sb + MB_WO, 9216 + 4096 + 256);
      asm volatile("cp.async.bulk.shared::cluster.global.mbarrier::complete_tx::bytes [%0], [%1], 256, [%2];"
                   :: "r"(sb + T_G), "l"(g_gate + NAUXSEG * 32), "r"(sb + MB_WO) : "memory");
      tma_load(sb + T_OA, &tm.oa, 4096 + (h18 & ~7), NAUXSEG * 32, sb + MB_WO);
#pragma unroll 1
      for (int j = 0; j < 3; j++) tma_load(sb + T_WA + j * 3072, &tm.woa, rank * 192 + j * 64, h18, sb + MB_WO);
    }
    if (w == 1) {
      set_scale();
      __syncwarp();
      const int ea = (int)ldg_relaxed32(&g_amax[0]) + (int)ldg_relaxed32(&g_amax[16]) - 254 + 2 + 10 - 15;
      sts32(sb + T_UN + (lane & 1) * 4, (128 + max(min(ea, 120), (int)(lds32(sb + SC_UNSC + 8 - (lane & 1) * 8) >> 23) - 127)) << 23);
    }
    bar_arrive(8, 256);
  } else {
    uint32_t r0;
    float un;
    auto prepare = [&]() {
      un = __uint_as_float(lds32(sb + SC_UNSC + (s & 1) * 8));
      r0 = qk ? (t16 & ~256u) - w * 256 + (((t16 >> 8) ^ wg) & 1 ? SM_QM : SM_BLK + 8192 + (s & 3) * SEGB) : mapa(t16 + (s < NSEG - 1 ? SM_VM : SM_FB), 0);
      PIN(r0); PIN(un);
    };
    prepare();
#pragma unroll 1
    while (true) {
      if (s == 8) STAMP(6);
      float r[8];
      if (qk) {
        const float u0 = wg ? un * (SM_SCALE * LOG2E) : un, u1 = wg ? un : un * (SM_SCALE * LOG2E);
        memproj(BoolC<true>(), 32, u0, u1, r);
        stsm4(r0, pack_bf16(r[0], r[1]), pack_bf16(r[2], r[3]), pack_bf16(r[4], r[5]), pack_bf16(r[6], r[7]));
        bar_arrive(4, 256);
      } else {
        const uint32_t mb = sb + (s < NSEG - 1 ? MB_S : MB_T), r1 = r0 + (1 << 24);
        memproj(BoolC<true>(), 34, un, un, r);
        const uint32_t p0 = pack_bf16(r[0], r[1]), p1 = pack_bf16(r[2], r[3]), p2 = pack_bf16(r[4], r[5]), p3 = pack_bf16(r[6], r[7]);
        const uint32_t v0 = wg ? p2 : p0, v1 = wg ? p3 : p1, v2 = wg ? p0 : p2, v3 = wg ? p1 : p3;
        st_async4(r0, v0, v1, v2, v3, mapa(mb, 0));
        st_async4(r1, v0, v1, v2, v3, mapa(mb, 1));
        bar_arrive(5, 256);
        sts128(r0 + (2 << 24), v0, v1, v2, v3);
        stsm4((t16 & ~256u) - w * 256 + SM_BLK + 8192 + (s & 3) * SEGB + (((t16 >> 8) ^ wg) & 1) * 1024, p0, p1, p2, p3);
        __syncwarp();
        if (elect_one()) mbar_arrive(sb + MB_S);
      }
      if (s == NSEG - 1) break;
      if (!qk) bar_arrive(15, 160);
      PROF(1);
      auto rearm = [&]() { mbar_wait(sb + MB_S, s & 1); if (elect_one()) mbar_expect(sb + MB_S, qk ? 640 + 2048 : 1280); __syncwarp(); };
      if (w == 1) {
        if ((t16 & 384) == 0) stg_relaxed(tm.red + (RED_SLOT(s + 2) + RED_LINE(blockIdx.x)) + (t16 & 112), 0, 0, 0, 0);
      } else if (w == 0) {
        const int tn = s + ah + 1;
        if (RFW) mbar_wait(sb + MB_S, s & 1);
        if (tn + 1 < NSEG && !(XP & 8) && elect_one()) {
          const int b0 = b2 == 2 ? 0 : b2 + 1;
          mbar_expect(sb + MB_X + 8 * b0, XT);
          tma_load3(sb + SM_X + b0 * XT, &tm.x, (tn + 1) * 32, sb + MB_X + 8 * b0);
        }
        if (tn < NSEG && (!(XP & 8) || tn < 3)) mbar_wait(sb + MB_X + 8 * b2, (tn / 3) & 1);
      } else if (w == 2) {
        if (!qk) { if (VS0 == 0) send_v(s + 1, 0); if (VS1 == 0) send_v(s + 1, 1); }
      } else if (qk || !NIC) {
        rearm();
      }
      __syncwarp();
      import();
      PROF(4);
      SCHED_FENCE(10);
      if (NIC) {
        if (qk) bar_sync(7, NII < 18 ? 384 : 256);
        xproj<0, 0, NIC>(acc, wa, dA);
        if (!qk) { if (w == 3) rearm(); bar_sync(7, NII < 18 ? 384 : 256); }
      } else {
        bar_sync(7, NII < 18 ? 384 : 256);
      }
      xproj<0, NIC, 18, (DD & 4) != 0, 12, N12>(acc, wa, dA);
      if (N12 == 18) bar_arrive(12, 256);
      dA += (int64_t)(b2 ? XT >> 4 : -(XT >> 3));
      finish(s + ah);
      if (qk && w == 0) wait_v(s + 1);
      bar_arrive(13, 384);
      PROF(6);
      SCHED_FENCE(13);
      bar_sync(14, 256);
      PROF(7);
      xproj<1, 0, 18, (DD & 8) != 0>(acc, wa, dA);
      b2 = b2 == 2 ? 0 : b2 + 1;
      s++;
      if (HOIST) prepare();
      PROFP(8);
      do_export();
      if (!HOIST) prepare();
      s--; RSTAMP(7); s++;
      PROFP(3);
    }
    TSTAMP(2);
    bar_sync(3, 128);
    tail_attention(sb, rank, w, lane, 1, 3);
    bar_arrive(0, 256);
  }
  STAMP(3);
  if (CSY) cluster_sync();
  STAMP(4);
}

DI void attn_role(const uint32_t sb, unsigned char* smem_raw, const RMaps& tm, const uint32_t RANK, const bf16* __restrict__ x, const bf16* __restrict__ mem0,
                  const int w, const int lane) {
  const int t2 = w * 32 + lane;
  uint32_t wo[8][4], w1[8][4];
  const uint32_t wo_lane = sb + ((lane & 7) + ((lane >> 4) << 3)) * 128 + (((w + 4 * ((lane >> 3) & 1)) ^ (lane & 7)) << 4);
  unsigned char* const g_red = tm.red;
  {
    const uint32_t tag = *(volatile unsigned*)&g_epoch + 1;
    if (w == 0) {
      stg_relaxed(g_red + RED_SLOT(t2 >> 3) + RED_LINE(blockIdx.x) + (t2 & 7) * 16, 0, 0, 0, 0);
      stg_relaxed(g_red + T_RED + blockIdx.x * 1024 + t2 * 16, 0, 0, 0, 0);
      stg_relaxed(g_red + T_RED + blockIdx.x * 1024 + 512 + t2 * 16, 0, 0, 0, 0);
      asm volatile("st.relaxed.gpu.global.u8 [%0], 0;" :: "l"(g_red + RED_SLOT(t2) + HINT_OFF + (t2 & 4) * 1024 + (t2 >> 3) * 16384 + blockIdx.x) : "memory");
    }
    uint4 xv[18];
    uint32_t mv[20];
#pragma unroll
    for (int i = 0; i < 20; i++) mv[i] = i < 18 ? ((const uint32_t*)mem0)[(lane >> 2) * (DM / 2) + (w * 18 + i) * 4 + (lane & 3)] : 0;
#pragma unroll
    for (int i = 0; i < 18; i++) xv[i] = blockIdx.x < NSEG ? ((const uint4*)(x + blockIdx.x * 32 * DM))[t2 + 128 * i] : make_uint4(0, 0, 0, 0);
    bar_sync(0, 384);
    cluster_arrive();
    if (PACE && w == 3) {
      const uint32_t t0 = gtime();
#pragma unroll 1
      for (int c = 1; c < 4; c++) {
        wait_until(t0 + c * PACE);
        if (elect_one()) load_weights(sb, tm, RANK, PORD ? (c == 1 ? 3 : c - 1) : c);
        __syncwarp();
      }
    }
    __half2 hx = __float2half2_rn(0.f);
#pragma unroll
    for (int i = 0; i < 18; i++) hx = amax4(hx, &xv[i].x);
    if (blockIdx.x == 0)
#pragma unroll
      for (int i = 0; i < 5; i++) hx = amax4(hx, &mv[4 * i]);
    sts32(sb + SC_SS + 4 * (12 + w), wexp(hx));
    if (t2 == 0) { sts32(sb + SC_EPOCH, (tag - 1) * NSEG + 2 - NRING); sts32(sb + SC_UNSC, __float_as_uint(1.f)); sts128(sb + SC_DEAD, 0, 0, 0, 0x3f800000u); sts64(sb + SC_FPAR, 0, 0); sts128(sb + SC_ONES, 0x3f803f80u, 0x3f803f80u, 0x3f803f80u, 0x3f803f80u); }
    WSTAMP(27);
    if (w == 0) __threadfence();
    uint32_t q[8] = {0, 0, 0, 0, 0, 0, 0, 0};
    mbar_wait(sb + MB_WO3, 0);
    if (t2 == 0) SSTAMP(11, 3);
#pragma unroll
    for (int k = 0; k < 8; k++) {
      ldsm4t(wo[k], wo_lane + SM_WO3 + k * 2048); ldsm4t(w1[k], wo_lane + SM_WOST + k * 2048);
#pragma unroll
      for (int i = 0; i < 4; i++) { sq_acc(q[i], wo[k][i]); sq_acc(q[i], w1[k][i]); }
    }
    bar_sync(6, 128);
    if (t2 == 0) SSTAMP(11, 7);
#pragma unroll
    for (int k = 0; k < 8; k++) sts128(sb + SM_WO3 + t2 * 16 + k * 2048, wo[k][0], wo[k][1], wo[k][2], wo[k][3]);
#pragma unroll
    for (int i = 0; i < 5; i++) {
      const int j = w * 18 + 4 * i + (lane >> 3), c = i < 4 || lane < 16 ? j * 8 + j / 24 * 64 : 192;
      stsm4t(sb + SM_MEM + (c + (lane & 7)) * 16, mv[4 * i], mv[4 * i + 1], mv[4 * i + 2], mv[4 * i + 3]);
    }
    bar_arrive(1, 256); bar_arrive(2, 256); bar_arrive(9, 256);
    if (t2 == 0) SSTAMP(11, 8);
    mbar_wait(sb + MB_WO, 0);
    if (t2 == 0) SSTAMP(11, 4);
#pragma unroll
    for (int k = 0; k < 8; k++) ldsm4t(wo[k], wo_lane + SM_X + 2 * XT + k * 2048);
    fence_async();
    bar_sync(6, 128);
    if (t2 == 32) tma_load3(sb + SM_X + 2 * XT, &tm.x, 64, sb + MB_X + 16);
    __syncwarp();
#pragma unroll
    for (int k = 0; k < 8; k++)
#pragma unroll
      for (int i = 0; i < 4; i++) sq_acc(q[4 + i], wo[k][i]);
    float ss = 0.f;
#pragma unroll
    for (int i = 0; i < 8; i++) ss += bf_lo(q[i]) + bf_hi(q[i]);
    ss = warp_sum(ss);
    if (lane == 0) sts32(sb + SC_SS + 4 * (8 + w), __float_as_uint(ss));
    if (t2 == 0) SSTAMP(11, 9);
    bar_sync(11, 384);
    if (t2 == 0) SSTAMP(11, 10);
    if (t2 == 0) {
      float a[16];
#pragma unroll
      for (int i = 0; i < 4; i++) lds128f(sb + SC_SS + 16 * i, &a[4 * i]);
      stg_relaxed(&g_stats[blockIdx.x * 2], __float_as_uint(((a[0] + a[1]) + (a[2] + a[3])) + ((a[4] + a[5]) + (a[6] + a[7]))),
                  __float_as_uint((a[8] + a[9]) + (a[10] + a[11])),
                  max(max(__float_as_uint(a[12]), __float_as_uint(a[13])), max(__float_as_uint(a[14]), __float_as_uint(a[15]))), tag);
    }
    __syncwarp();
    WSTAMP(24);
    cluster_wait();
    if (w == 0) {
      uint4 v[3];
      int n = 0;
      while (true) {
#pragma unroll
        for (int i = 0; i < 3; i++) v[i] = ldg_relaxed(&g_stats[(i * 32 + lane) * 2]);
        if (__all_sync(0xffffffffu, v[0].w == tag && v[1].w == tag && v[2].w == tag) || ++n > SPIN_LIMIT) break;
        __nanosleep(100);
      }
      WSTAMP(25);
      const float sv = warp_sum(__uint_as_float(v[0].x) + __uint_as_float(v[1].x) + __uint_as_float(v[2].x));
      const float so = warp_sum(__uint_as_float(v[0].y) + __uint_as_float(v[1].y) + __uint_as_float(v[2].y));
      const int expW = ((int)(__float_as_uint(sv) >> 23) + (int)(__float_as_uint(so) >> 23) - 254 + 2 + 10 + 1) >> 1;
      sts32(sb + SC_XMAX + 4 * lane, v[0].z); sts32(sb + SC_XMAX + 128 + 4 * lane, v[1].z);
      sts32(sb + SC_EXPW, expW + 1 - 15);
      if (blockIdx.x == 0 && lane == 0) *(volatile unsigned*)&g_epoch = tag;
      sts32(sb + SC_FPAR + 4, 1);
    } else if (w < 3) {
      const uint32_t u = blockIdx.x >> 4;
      unsigned char* const z = g_red + 98304 + (blockIdx.x & 15) * 128 + (u & 1) * 2048 + (u & 6) * 4096 + (((u >> 1) ^ w) & 1) * 4096 + lane * 4;
      stg_relaxed32(z, 0);
      uint32_t best = 0xffffffffu;
#pragma unroll 1
      for (int i = 0; i < 64; i++) {
        uint32_t last, dt;
        asm volatile("{\n.reg .pred p;\n.reg .u32 c, v;\nld.volatile.shared.u32 %0, [%3];\nmov.u32 c, %%clock;\n"
                     "atom.relaxed.gpu.global.exch.b32 v, [%2], 0;\nsetp.eq.u32 p, v, 0;\nmov.u32 %1, 0;\n@p mov.u32 %1, %%clock;\nsub.u32 %1, %1, c;\n}"
                     : "=r"(last), "=r"(dt) : "l"(z), "r"(sb + SC_FPAR + 4) : "memory");
        best = min(best, dt);
        if (last && i >= NPROBE - 1) break;
      }
      sts32(sb + SC_LAT + (w - 1) * 4, best);
    }
    bar_sync(13, 384);
    bar_arrive(0, 384);
    WSTAMP(26);
    TSTAMP(1);
  }

  const uint32_t nh = __shfl_sync(0xffffffffu, near_half(sb), 0);
  uint32_t l16 = sb + lane * 16;
  PIN(l16);
#define LV ((l16 >> 4) & 31)
#define fence_reg l16
  const uint32_t red_lo = (uint32_t)(uint64_t)g_red, red_hi = (uint32_t)((uint64_t)g_red >> 32);
  uint32_t lp;
  auto slot = [&](int s, uint32_t c, uint32_t ofs) {
    const uint32_t lo = lp | (red_lo + ((w >> 1) * 4 + (w & 1) * 2 + ((w ^ c) & 1)) * 4096 + RED_SLOT(s) + ofs);
    uint64_t a; asm("mov.b64 %0, {%1, %2};" : "=l"(a) : "r"(lo), "r"(red_hi));
    return (unsigned char*)a;
  };
  const uint32_t always = __shfl_sync(0xffffffffu, lds32(sb + SC_DEAD + 12), 0);
  const int mode0 = RANK < 2 ? w : w | 4;
  auto hint_addr = [&](int s) { return min(LV, 23u) * 4 + (red_lo + HINT_OFF + nh * 4096 + w * 16384 + RED_SLOT(s)); };
  auto load_hints = [&](uint32_t lo) {
    uint64_t a; asm("mov.b64 %0, {%1, %2};" : "=l"(a) : "r"(lo), "r"(red_hi));
    return ldg_relaxed32((const void*)a);
  };
  const uint32_t blk = RANK < 2 ? 9216 : SEGB;
  auto send_v = [&](int seg, int pos) {
    if (RANK == 2 && ((w == 0 && VS0 == pos) || (w == 1 && VS1 == pos)) && seg > 1 && seg < NSEG && !(XP & 2)) {
      if (elect_one()) {
        fence_async();
        bulk_s2s(mapa(sb + SM_VC + (seg & 1) * 8192, w), sb + SM_BLK + (seg & 3) * SEGB, 8192, mapa(sb + MB_VX + (seg & 1) * 8, w));
      }
      __syncwarp();
    }
  };
  uint32_t dl = __shfl_sync(0xffffffffu, gtime() - 768, 0);
  int s = 0;
  bool bad = false;
#pragma unroll 1
  while (true) {
    const uint32_t par = s & 1;
    uint32_t vx[4][4], oc[4], hints;
    if (HP == 2) { hints = hint_addr(s); PIN(hints); }
    auto load_vx = [&]() {
      const uint32_t va = l16 + (RANK < 2 ? SM_VC + par * 8192 : SM_BLK + (s & 3) * SEGB) + w * 1024 + ((LV >> 3) & 1) * 384 - (LV >> 4) * 128;
      if (WL & 4) lds128(sb + SC_ONES, oc);
#pragma unroll
      for (int i = 0; i < 4; i++) ldsm4(vx[i], va + (i & 1) * 4096 + (i >> 1) * 256);
    };
    auto retire = [&](uint32_t x) {
      asm volatile("{\n.reg .pred p;\nsetp.eq.u32 p, %0, 0;\n@p exit;\n}" :: "r"(vx[0][0] | vx[1][0] | vx[2][0] | vx[3][0] | x | ((WL & 4) ? oc[0] : 0)) : "memory");
    };
    auto scores = [&](auto memkeys, auto first, float* sc) {
      constexpr bool MK = decltype(memkeys)::value, FIRST = decltype(first)::value;
      uint32_t kb[4][4], qb[2][4];
      const uint32_t m = LV >> 3;
      uint32_t kaddr = l16 + SM_BLK + 4096 + (s & 3) * SEGB + w * 2048 + (m & 1) * (MK ? 128 : 896) - (m >> 1) * 128;
      if (MK) { PIN(kaddr); }
      else {
#pragma unroll
        for (int k = 0; k < 4; k++) ldsm4t(kb[k], kaddr + k * 256);
      }
      if (FIRST) { load_vx(); retire(MK ? kaddr : kb[0][0] | kb[1][0] | kb[2][0] | kb[3][0] | l16); bar_sync(4, 256); RSTAMP(4); PROF(4); }
      ldsm4t(qb[0], l16 + SM_QM);
      if (MK) ldsm4t(kb[0], kaddr);
      ldsm4t(qb[1], l16 + SM_QM + 512);
      if (MK) ldsm4t(kb[2], kaddr + 512);
      float c[4][4];
      mma16816z(c[0], kb[0], qb[0][0], qb[0][1]); mma16816z(c[1], kb[MK ? 0 : 1], qb[0][2], qb[0][3]);
      mma16816z(c[2], kb[2], qb[1][0], qb[1][1]); mma16816z(c[3], kb[MK ? 2 : 3], qb[1][2], qb[1][3]);
      if (FIRST && B5POS == 0) bar_arrive(5, N5);
#pragma unroll
      for (int i = 0; i < (MK ? 2 : 4); i++) sc[i] = ((c[0][i] + c[1][MK ? i + 2 : i]) + c[2][i]) + c[3][MK ? i + 2 : i];
    };
    auto send = [&](auto memkeys) {
      constexpr bool MK = decltype(memkeys)::value;
      constexpr int N = MK ? 1 : 2;
      const uint32_t sa = sb + LV * 4 + SM_E + (MK ? 1024 + RANK * 128 : RANK * 512 + w * 256);
      uint32_t ra[N][2], mb[N][2];
#pragma unroll
      for (int i = 0; i < N; i++)
#pragma unroll
        for (int j = 0; j < 2; j++) {
          ra[i][j] = mapa(sa + i * 128, j ? 2 : RANK ^ 1); mb[i][j] = mapa(sb + MB_S, j ? 2 : RANK ^ 1);
          PIN(ra[i][j]);
        }
      float sc[4];
      scores(memkeys, BoolC<true>(), sc);
      uint32_t e[N];
#pragma unroll
      for (int i = 0; i < N; i++) {
        e[i] = pack_bf16(ex2(sc[2 * i]), ex2(sc[2 * i + 1]));
        if (!(fmaxf(fabsf(sc[2 * i]), fabsf(sc[2 * i + 1])) <= E_LIM)) e[i] = 0x7fff7fffu;
        st_async1(ra[i][0], e[i], mb[i][0]);
        st_async1(ra[i][1], e[i], mb[i][1]);
      }
#pragma unroll
      for (int i = 0; i < N; i++) sts32(sa + i * 128, e[i]);
      __syncwarp();
      if (l16 == sb) mbar_arrive(sb + MB_S);
      PROF(5);
    };
    const int mode = bad ? 8 : mode0;
    if (mode < 2) {
      send(BoolC<false>());
    } else if (mode == 2) {
      send(BoolC<true>());
    } else if (mode == 8) {
      load_vx();
      retire(l16);
      const uint32_t fp = lds32(sb + SC_FPAR);
      bar_sync(6, 128);
      if (w == 0 && l16 == sb) { sts32(sb + SC_FPAR, fp ^ 1); mbar_expect(sb + MB_F, 3072); }
      if (RANK < 2 && w < 3) {
        float sc[4] = {0.f, 0.f, 0.f, 0.f};
        if (w < 2) scores(BoolC<false>(), BoolC<false>(), sc); else scores(BoolC<true>(), BoolC<false>(), sc);
#pragma unroll 1
        for (int r = 0; r < 3; r++)
          st_async4(mapa(l16 + SM_FB + RANK * 1536 + w * 512, r), __float_as_uint(sc[0]), __float_as_uint(sc[1]), __float_as_uint(sc[2]), __float_as_uint(sc[3]), mapa(sb + MB_F, r));
      }
      mbar_wait(sb + MB_F, fp);
      float a[12];
#pragma unroll
      for (int j = 0; j < 3; j++) {
        float b[4];
        lds128f(l16 + SM_FB + j * 512, a + 4 * j); lds128f(l16 + SM_FB + 1536 + j * 512, b);
#pragma unroll
        for (int i = 0; i < 4; i++) a[4 * j + i] += b[i];
      }
      float m0 = fmaxf(fmaxf(fmaxf(a[0], a[2]), fmaxf(a[4], a[6])), a[8]), m1 = fmaxf(fmaxf(fmaxf(a[1], a[3]), fmaxf(a[5], a[7])), a[9]);
#pragma unroll
      for (int o = 4; o < 32; o <<= 1) { m0 = fmaxf(m0, __shfl_xor_sync(0xffffffffu, m0, o)); m1 = fmaxf(m1, __shfl_xor_sync(0xffffffffu, m1, o)); }
#pragma unroll
      for (int i = 0; i < 5; i++) {
        const uint32_t ea = sb + SM_E + LV * 4 + (i < 4 ? i * 128 : 1024);
        sts32(ea, pack_bf16(ex2(a[2 * i] - m0), ex2(a[2 * i + 1] - m1)));
        sts32(ea + (i < 4 ? 512 : 128), 0x3f803f80u);
      }
      __syncwarp();
    } else {
      load_vx();
      retire(l16 + 1);
      if (VS0 == 2 || VS1 == 2) send_v(s + 1, 2);
      if (w == 3) {
        uint32_t used = ldg_relaxed32(&g_used[blockIdx.x / 3 * 32]);
        if (!(XP & 4) && elect_one()) {
          if (s > 0) seg_publish(s - 1);
          fence_async();
          seg_store(s, sb, 0, 8192);
        }
        __syncwarp();
        bar_sync(RANK < 2 ? 4 : 15, RANK < 2 ? 256 : 160);
        if (!(XP & 4) && elect_one()) { fence_async(); seg_store(s, sb, 8192, blk - 8192); }
        __syncwarp();
        const uint32_t need = lds32(sb + SC_EPOCH) + (s >= NRING - 1 ? s : -4 * NSEG);
#pragma unroll 1
        for (int n = 0; (int)(used - need) < 0 && n < ((XP & 64) ? 1 : SPIN_LIMIT); n++) used = ldg_relaxed32(&g_used[blockIdx.x / 3 * 32]);
      }
    }
    {
      uint32_t wa[4], wb[4];
      constexpr int WS = 2048;
      const uint32_t w3a = l16 + SM_WO3 + w * 512;
      if (HP == 1) { hints = hint_addr(s); PIN(hints); }
      if (!(WL & 1)) { lds128(w3a + KP(0) * WS, wa); lds128(w3a + KP(1) * WS, wb); }
      if (WL & 2) {
#pragma unroll
        for (int i = 0; i < 4; i++) oc[i] = always | (always >> 16) | (always & (i + 1));
      } else if (!(WL & 4)) lds128(sb + SC_ONES, oc);
      if (B5POS == 1 && mode < 3) bar_arrive(5, N5);
      uint32_t e[10], p[5], vm[4], ob[4];
      float o0[4], o1[4], f[3][2][4], rs[4];
      if (!(RV & 1)) { reserve2(vm); reserve2(vm + 2); }
      if (!(RV & 2)) reserve2(e + 8);
      if (!HP) { hints = hint_addr(s); PIN(hints); }
      if (CLR & 2) asm volatile("{\n.reg .pred p;\nsetp.eq.u32 p, %0, 0;\n@p exit;\n}" :: "r"(wa[0] | wb[0] | oc[0] | hints) : "memory");
      if (RV & 4) mbar_wait_fast(sb + MB_S, par); else mbar_wait(sb + MB_S, par);
      RSTAMP(5);
      PROF(6);
      if (RV & 2) { ldsm4t(e, l16 + SM_E); ldsm4t(e + 4, l16 + SM_E + 512); ldsm2t(e + 8, l16 + SM_E + 1024); }
      else { ldsm4t(e, l16 + SM_E); ldsm2t_in(e + 8, l16 + SM_E + 1024, always); ldsm4t(e + 4, l16 + SM_E + 512); }
      if (RV & 1) lds128(l16 + w * 512 + SM_VM, vm); else lds128_in(vm, l16 + w * 512 + SM_VM, always);
      const float scl = __uint_as_float(lds32(sb + SC_UNSC + 8 - par * 8));
      if (HL == 0) hints = load_hints(hints);
      if (GF & 1) SCHED_FENCE(4);
#pragma unroll
      for (int i = 0; i < 4; i++) p[i] = mul_bf16(e[i], e[4 + i]);
      p[4] = mul_bf16(e[8], e[9]);
      if (HL) hints = load_hints(hints | (p[HL - 1] & always & 1));
      mma16816z(o0, vx[0], p[0], p[1]);
      if (WL & 1) { lds128_in(vx[0], w3a + KP(0) * WS, always); }
      mma16816z(o1, vx[1], p[0], p[1]);
      if (WL & 1) { lds128_in(vx[1], w3a + KP(1) * WS, always); }
      mma16816z(rs, oc, p[0], p[1]);
      mma16816(o0, vx[2], p[2], p[3]); lds128_in(vx[2], w3a + KP(2) * WS, always);
      mma16816(o1, vx[3], p[2], p[3]); lds128_in(vx[3], w3a + KP(3) * WS, always);
      mma16816(rs, oc, p[2], p[3]);
      mma1688(o0, vm[0], vm[1], p[4]); mma1688(o1, vm[2], vm[3], p[4]); mma1688(rs, oc[0], oc[1], p[4]);
      stsm4(l16 + w * 512 + SM_OB, pack_bf16(o0[0], o0[1]), pack_bf16(o0[2], o0[3]), pack_bf16(o1[0], o1[1]), pack_bf16(o1[2], o1[3]));
      bar_sync(6, 128);
      RSTAMP(3);
      PROF(7);
      ldsm4t_in(oc, l16 + SM_OB, always);
      bad = __any_sync(0xffffffffu, !(rs[0] + rs[1] > 0.f) && !bad);
      rs[0] *= scl; rs[1] *= scl;
      asm volatile("{\n.reg .pred p;\nsetp.ne.u32 p, %1, 0;\n@p rcp.approx.ftz.f32 %0, %0;\n}" : "+f"(rs[0]) : "r"(always));
      asm volatile("{\n.reg .pred p;\nsetp.ne.u32 p, %1, 1;\n@p rcp.approx.ftz.f32 %0, %0;\n}" : "+f"(rs[1]) : "r"(always));
      asm volatile("lop3.b32 %0, %1, %2, %3, 0xfe;" : "=r"(lp) : "r"((l16 & 128) * 2), "r"((l16 & 256) * 4), "r"(l16 & 112));
      if (bad) continue;
      ldsm4t(ob, l16 + SM_OB + 512);
      mma16816z(f[2][0], WL & 1 ? vx[0] : wa, oc[0], oc[1]); mma16816z(f[2][1], WL & 1 ? vx[1] : wb, oc[2], oc[3]);
      mma16816z(f[0][0], wo[0], oc[0], oc[1]); mma16816z(f[0][1], wo[4], oc[2], oc[3]);
      mma16816z(f[1][0], w1[0], oc[0], oc[1]); mma16816z(f[1][1], w1[4], oc[2], oc[3]);
      ldsm4t_in(oc, l16 + SM_OB + 1024, always);
      mma16816(f[2][0], vx[2], ob[0], ob[1]); lds128_in(vx[2], w3a + KP(4) * WS, always);
      mma16816(f[2][1], vx[3], ob[2], ob[3]); lds128_in(vx[3], w3a + KP(5) * WS, always);
      mma16816(f[0][0], wo[1], ob[0], ob[1]); mma16816(f[0][1], wo[5], ob[2], ob[3]);
      mma16816(f[1][0], w1[1], ob[0], ob[1]); mma16816(f[1][1], w1[5], ob[2], ob[3]);
      ldsm4t_in(ob, l16 + SM_OB + 1536, always);
      mma16816(f[0][0], wo[2], oc[0], oc[1]); mma16816(f[0][1], wo[6], oc[2], oc[3]);
      mma16816(f[2][0], vx[2], oc[0], oc[1]); lds128_in(vx[2], w3a + KP(6) * WS, always);
      mma16816(f[2][1], vx[3], oc[2], oc[3]); lds128_in(vx[3], w3a + KP(7) * WS, always);
      mma16816(f[1][0], w1[2], oc[0], oc[1]); mma16816(f[1][1], w1[6], oc[2], oc[3]);
      mma16816(f[0][0], wo[3], ob[0], ob[1]); mma16816(f[0][1], wo[7], ob[2], ob[3]);
      mma16816(f[1][0], w1[3], ob[0], ob[1]); mma16816(f[1][1], w1[7], ob[2], ob[3]);
      mma16816(f[2][0], vx[2], ob[0], ob[1]); mma16816(f[2][1], vx[3], ob[2], ob[3]);
      bar_arrive(7, NII < 18 ? 384 : 256);
      lds128_in(ob, sb + SC_DEAD, always);
      uint32_t h[3][2];
#pragma unroll
      for (int j = 0; j < 3; j++)
#pragma unroll
        for (int i = 0; i < 2; i++)
        {
          scale_sum(f[j][1][2 * i], f[j][0][2 * i], rs[0], always); scale_sum(f[j][1][2 * i + 1], f[j][0][2 * i + 1], rs[1], always);
          h[j][i] = pack_f16(f[j][1][2 * i], f[j][1][2 * i + 1]);
        }
      const uint32_t rofs = RANK * 32768;
      red_f16x8(slot(s, RANK >> 1, rofs), h[0][0], h[1][0], h[2][0], 0x3c00u);
      red_f16x8(slot(s, (RANK >> 1) ^ 1, rofs), h[0][1], h[1][1], h[2][1], 0x3c00u);
      if (NII == 18) bar_arrive(10, 256);
      SCHED_FENCE(5);
      RSTAMP(0);
      l16 += ob[B7R];
    }
    {
    PROF(8);
    if (VS0 == 3 || VS1 == 3) send_v(s + 1, 3);
    const uint32_t ma0 = l16 + SM_MEM + w * 128 + (LV >> 3) * 896 + nh * 512;
    const unsigned char* const sl[2] = {slot(s, nh, 0), slot(s, nh ^ 1, 0)};
    uint32_t late = latest_hint(hints, dl, s);
    if (late >= 64) {
      int n = 0;
#pragma unroll 1
      do {
        late = latest_hint(load_hints(hint_addr(s)), dl, s);
      } while (late >= 64 && ++n < SPIN_LIMIT);
    }
    dl += late * 32 + tm.poll;
    PROF(9);
    {
      auto wait_until = [&](uint32_t t) {
        asm volatile("{\n.reg .pred p;\n.reg .s32 c;\n.reg .u64 t;\nTL: mov.u64 t, %%globaltimer;\ncvt.u32.u64 c, t;\nsub.s32 c, c, %0;\nsetp.lt.s32 p, c, 0;\n@p bra.uni TL;\n}" :: "r"(t + (l16 & 15)) : "memory");
      };
      uint4 v[2][3];
      auto load = [&](int c) {
#pragma unroll
        for (int r = 0; r < 3; r++) v[c][r] = ldg_relaxed(sl[c ^ (r >> 1)] + r * 32768);
      };
      auto decode = [&](int c, int n) {
        uint32_t q[9];
        __half2 hm;
        const uint32_t ma = ma0 ^ (c * 512);
#pragma unroll
        for (int i = 0; i < 9; i++) {
          const uint32_t h = i % 3 == 0 ? v[c][i / 3].x : (i % 3 == 1 ? v[c][i / 3].y : v[c][i / 3].z);
          const float2 f = __half22float2(*(const __half2*)&h);
          q[i] = pack_bf16(f.x, f.y);
          hm = i ? __hmax2(hm, __habs2(*(const __half2*)&h)) : __habs2(*(const __half2*)&h);
        }
#pragma unroll
        for (int r = 0; r < 3; r++) stsm4(ma + r * 4096, q[3 * r], q[3 * r + 1], q[3 * r + 2], r < 2 ? v[c][r].w : *(const uint32_t*)&hm);
        const bool done = __all_sync(0xffffffffu, v[c][0].w == 0x5000u && v[c][1].w == 0x5000u && v[c][2].w == 0x5000u) || n > SPIN_LIMIT;
        asm volatile("{\n.reg .pred p;\nsetp.ne.u32 p, %0, 0;\n@p bar.arrive %1, 256;\n}" :: "r"((int)done), "r"(1 + c) : "memory");
        return done;
      };
      if (LEAD) { wait_until(dl - LEAD); load(1); }
      wait_until(dl);
      PROF(10);
      int n = 0;
#pragma unroll 1
      do {
        load(0);
        if (!LEAD) load(1);
        asm volatile("{\n.reg .pred p;\nsetp.eq.u32 p, %0, 0;\n@p bar.sync 13, 384;\n}" :: "r"(n) : "memory");
      } while (!decode(0, n++));
      PROF(11);
      RSTAMP(1);
#pragma unroll 1
      while (!decode(1, n++)) load(1);
      bar_arrive(9, 256);
      RSTAMP(2);
      PROF(12);
    }
    PROF(13);
    if (++s == NSEG - 1) break;
    }
  }
#undef fence_reg
  if (RANK < 2) bar_arrive(4, 256);
  TSTAMP(49);
  {
    PIN(l16);
    tail_attention(sb, RANK, w, LV, 0, 6);
#pragma unroll 1
    for (int sg = 0; sg < 2; sg++) {
      PIN(l16);
      const int lane = LV, m = lane >> 3, g = lane >> 2, t = lane & 3;
      const uint32_t ob = l16 + T_OB + sg * 8192;
      bar_sync(sg ? 0 : 8, 256);
      TSTAMP(54 + 2 * sg);
      const float inv = __uint_as_float(0x7f000000u - lds32(sb + T_UN + sg * 4));
#pragma unroll 1
      for (int j = 0; j < 4; j += 2) {
        float c[2][3][4];
        uint32_t x[4], y[4], z[2][4];
#pragma unroll
        for (int e = 0; e < 2; e++) {
          const uint32_t oa = sb + T_OA + ((sg * 4 + j + e) * 8 + g) * 64 + (blockIdx.x / 3 * 36 & 15) + t * 4;
          z[e][0] = lds32(oa); z[e][1] = lds32(oa + 16); z[e][2] = t ? 0u : lds32(oa + 32);
        }
#pragma unroll
        for (int i = 0; i < 3; i++) {
          const uint32_t wa = sb + T_WA + ((lane & 7) + ((lane >> 4) << 3)) * 128 + (((w + 4 * (m & 1)) ^ (lane & 7)) << 4);
          ldsm4t(x, wa + i * 3072); ldsm2t(y, wa + i * 3072 + 2048);
#pragma unroll
          for (int e = 0; e < 2; e++) { mma1688z(c[e][i], y[0], y[1], z[e][2]); mma16816(c[e][i], x, z[e][0], z[e][1]); }
        }
#pragma unroll
        for (int r = 0; r < 4; r++) {
          ldsm4t(z[0], ob + j * 2048 + r * 512); ldsm4t(z[1], ob + j * 2048 + 2048 + r * 512);
          lds128(l16 + SM_WO3 + w * 512 + r * 2048, x); lds128(l16 + SM_WO3 + w * 512 + (r + 4) * 2048, y);
#pragma unroll
          for (int e = 0; e < 2; e++) { mma16816(c[e][0], wo[r], z[e][0], z[e][1]); mma16816(c[e][1], w1[r], z[e][0], z[e][1]); mma16816(c[e][2], x, z[e][0], z[e][1]); }
#pragma unroll
          for (int e = 0; e < 2; e++) { mma16816(c[e][0], wo[r + 4], z[e][2], z[e][3]); mma16816(c[e][1], w1[r + 4], z[e][2], z[e][3]); mma16816(c[e][2], y, z[e][2], z[e][3]); }
        }
#pragma unroll
        for (int i = 0; i < 4; i++) {
          const float (&d)[3][4] = c[i >> 1];
          const int q = (i & 1) * 2;
          red_f16x8(g_red + T_RED + ((((sg * 4 + j + (i >> 1)) * 3 + RANK) * 4 + w) * 2 + (i & 1)) * 512 + lane * 16, pack_f16(d[0][q] * inv, d[0][q + 1] * inv),
                    pack_f16(d[1][q] * inv, d[1][q + 1] * inv), pack_f16(d[2][q] * inv, d[2][q + 1] * inv), 0x3c00u);
        }
      }
      TSTAMP(55 + 2 * sg);
    }
    if (RSLOW) { wait_until(gtime() + 8000); wait_until(gtime() + 8000); wait_until(gtime() + 4000); }
    if (w < 2) {
      const int b = blockIdx.x, lane = LV, g = lane >> 2, t = lane & 3;
      uint4 v;
#pragma unroll 1
      for (int n = 0; n < SPIN_LIMIT; n++) {
        v = ldg_relaxed(g_red + T_RED + (w * 96 + b) * 512 + lane * 16);
        if (__all_sync(0xffffffffu, v.w == 0x5000u)) break;
        __nanosleep(40);
      }
      const float un = __uint_as_float(lds32(sb + T_UN + w * 4));
      uint32_t* const o = (uint32_t*)(tm.out + (size_t)((NAUXSEG + w) * 32 + b / 24 * 8 + g) * DM + (b >> 3) % 3 * 192 + (b & 1) * 32 + (b & 6) * 4) + t;
#pragma unroll
      for (int j = 0; j < 3; j++) {
        const float2 f = __half22float2(*(const __half2*)(&v.x + j));
        o[j * 32] = movm(pack_bf16(f.x * un, f.y * un));
      }
    }
  }
  TSTAMP(3);
  if (CSY) cluster_sync();
}

__global__ void __cluster_dims__(3, 1, 1) __launch_bounds__(384, 1)
rec_kernel(const __grid_constant__ RMaps tm, const bf16* __restrict__ x, const bf16* __restrict__ mem0) {
  extern __shared__ __align__(1024) unsigned char smem_raw[];
  const uint32_t sb = smem_u32(smem_raw);
  const int tid = threadIdx.x, lane = tid & 31;
  const int wg = __shfl_sync(0xffffffffu, tid >> 7, 0);
  const int w = __shfl_sync(0xffffffffu, (tid >> 5) & 3, 0);
  uint32_t rank; asm("mov.u32 %0, %%cluster_ctarank;" : "=r"(rank));
  STAMP(0);
  TSTAMP(0);
  asm volatile("griddepcontrol.launch_dependents;" ::: "memory");

#define PFT 1
  if (PFT && wg == 1 && lane == 0) asm volatile("prefetch.tensormap [%0];\nprefetch.tensormap [%1];" :: "l"(w & 1 ? &tm.woa : &tm.oa), "l"(w == 0 ? (rank < 2 ? &tm.wk : &tm.wv) : w == 1 ? &tm.wq : w == 2 ? &tm.x : &tm.wo) : "memory");
  if (wg < 2) {
    asm volatile("setmaxnreg.inc.sync.aligned.u32 192;");
    if (tid == 0) {
      for (int i = 0; i < 3; i++) { mbar_init(sb + MB_W + 8 * i, 1); mbar_init(sb + MB_X + 8 * i, 1); }
      mbar_init(sb + MB_WO, 1); mbar_init(sb + MB_WO3, 1);
      mbar_init(sb + MB_S, rank < 2 ? 5 : 6);
      mbar_init(sb + MB_F, 1);
      for (int i = 0; i < 3; i++) mbar_init(sb + MB_T + 8 * i, 1);
      mbar_init(sb + MB_VX, 1); mbar_init(sb + MB_VX + 8, 1);
      asm volatile("fence.mbarrier_init.release.cluster;" ::: "memory");
      fence_async();
      SSTAMP(11, 6);
      load_weights(sb, tm, rank, 0);
      for (int i = 0; i < 3; i++) mbar_expect(sb + MB_X + 8 * i, XT);
      tma_load3(sb + SM_X, &tm.x, 0, sb + MB_X);
      if (!PACE) for (int c = 1; c < 4; c++) load_weights(sb, tm, rank, c);
      mbar_expect(sb + MB_S, rank < 2 ? 640 + 2048 : 1280);
      mbar_expect(sb + MB_VX, 8192); mbar_expect(sb + MB_VX + 8, 8192);
      mbar_expect(sb + MB_T, 2048);
      for (int i = 1; i < 3; i++) mbar_expect(sb + MB_T + 8 * i, rank < 2 ? 5120 : 10240);
      SSTAMP(11, 5);
    }
    __syncwarp();
    bar_sync(0, 384);
    proj_role(sb, tm, rank, wg, w, lane);
  } else {
    asm volatile("setmaxnreg.dec.sync.aligned.u32 120;");
    attn_role(sb, smem_raw, tm, rank, x, mem0, w, lane);
  }
}

constexpr int A_XH = 73728;
constexpr int A_NS = 9, A_WM = 6144, A_WT = 768;
constexpr int A_RING = 2 * A_XH, A_TAIL = A_RING + A_NS * A_WM, A_GW = A_TAIL + A_NS * A_WT;
constexpr int A_EPI = 212864, A_EPW = 9344;
constexpr int A_XT = 4 * XT, A_XW = A_XT + 16384, A_NR = 4;
constexpr int A_IN = A_XW + 16384, A_OST = A_IN + 3 * SEGB;
constexpr int A_GATE = A_EPI + 2 * A_EPW, A_BAR = A_GATE + 512;
constexpr int A_TOTAL = A_BAR + 384;
struct AMaps { CUtensorMap x, wa, wt, oa, o, o3, wob, woa; };

DI void wgmma_n192_ss_nt(float* d, uint64_t da, uint64_t db, int acc) {
  asm volatile("{\n.reg .pred p;\nsetp.ne.b32 p, %98, 0;\n"
               "wgmma.mma_async.sync.aligned.m64n192k16.f32.bf16.bf16 {"
               "%0,%1,%2,%3,%4,%5,%6,%7,%8,%9,%10,%11,%12,%13,%14,%15,%16,%17,%18,%19,%20,%21,%22,%23,%24,%25,%26,%27,%28,%29,%30,%31,"
               "%32,%33,%34,%35,%36,%37,%38,%39,%40,%41,%42,%43,%44,%45,%46,%47,%48,%49,%50,%51,%52,%53,%54,%55,%56,%57,%58,%59,%60,%61,%62,%63,"
               "%64,%65,%66,%67,%68,%69,%70,%71,%72,%73,%74,%75,%76,%77,%78,%79,%80,%81,%82,%83,%84,%85,%86,%87,%88,%89,%90,%91,%92,%93,%94,%95"
               "}, %96, %97, p, 1, 1, 0, 1;\n}\n"
               : ACC8(d, 0), ACC8(d, 8), ACC8(d, 16), ACC8(d, 24), ACC8(d, 32), ACC8(d, 40), ACC8(d, 48), ACC8(d, 56),
                 ACC8(d, 64), ACC8(d, 72), ACC8(d, 80), ACC8(d, 88) : "l"(da), "l"(db), "r"(acc));
}
#define ACC4(d, o) "+f"(d[o]), "+f"(d[o + 1]), "+f"(d[o + 2]), "+f"(d[o + 3])
DI void wgmma_n24_ss_nt(float* d, uint64_t da, uint64_t db, int acc) {
  asm volatile("{\n.reg .pred p;\nsetp.ne.b32 p, %14, 0;\n"
               "wgmma.mma_async.sync.aligned.m64n24k16.f32.bf16.bf16 {%0,%1,%2,%3,%4,%5,%6,%7,%8,%9,%10,%11}, %12, %13, p, 1, 1, 0, 1;\n}\n"
               : ACC8(d, 0), ACC4(d, 8) : "l"(da), "l"(db), "r"(acc));
}
DI void wgmma_n8_ss(float* d, uint64_t da, uint64_t db, int acc) {
  asm volatile("{\n.reg .pred p;\nsetp.ne.b32 p, %6, 0;\n"
               "wgmma.mma_async.sync.aligned.m64n8k16.f32.bf16.bf16 {%0,%1,%2,%3}, %4, %5, p, 1, 1, 0, 0;\n}\n"
               : ACC4(d, 0) : "l"(da), "l"(db), "r"(acc));
}
DI void wgmma_n40_ss_tt(float* d, uint64_t da, uint64_t db, int acc) {
  asm volatile("{\n.reg .pred p;\nsetp.ne.b32 p, %22, 0;\n"
               "wgmma.mma_async.sync.aligned.m64n40k16.f32.bf16.bf16 {%0,%1,%2,%3,%4,%5,%6,%7,%8,%9,%10,%11,%12,%13,%14,%15,%16,%17,%18,%19}, "
               "%20, %21, p, 1, 1, 1, 1;\n}\n"
               : ACC8(d, 0), ACC8(d, 8), ACC4(d, 16) : "l"(da), "l"(db), "r"(acc));
}
DI void wgmma_n64_rs(float* d, const uint32_t* a, uint64_t db, int acc) {
  asm volatile("{\n.reg .pred p;\nsetp.ne.b32 p, %37, 0;\n"
               "wgmma.mma_async.sync.aligned.m64n64k16.f32.bf16.bf16 {"
               "%0,%1,%2,%3,%4,%5,%6,%7,%8,%9,%10,%11,%12,%13,%14,%15,%16,%17,%18,%19,%20,%21,%22,%23,%24,%25,%26,%27,%28,%29,%30,%31"
               "}, {%32,%33,%34,%35}, %36, p, 1, 1, 0;\n}\n"
               : ACC8(d, 0), ACC8(d, 8), ACC8(d, 16), ACC8(d, 24) : "r"(a[0]), "r"(a[1]), "r"(a[2]), "r"(a[3]), "l"(db), "r"(acc));
}
DI void wgmma_n32_ss_tn(float* d, uint64_t da, uint64_t db, int acc) {
  asm volatile("{\n.reg .pred p;\nsetp.ne.b32 p, %18, 0;\n"
               "wgmma.mma_async.sync.aligned.m64n32k16.f32.bf16.bf16 {%0,%1,%2,%3,%4,%5,%6,%7,%8,%9,%10,%11,%12,%13,%14,%15}, "
               "%16, %17, p, 1, 1, 1, 0;\n}\n"
               : ACC8(d, 0), ACC8(d, 8) : "l"(da), "l"(db), "r"(acc));
}
DI void tma_load3c(uint32_t dst, const CUtensorMap* m, int c0, int c1, int c2, uint32_t mb) {
  asm volatile("cp.async.bulk.tensor.3d.shared::cluster.global.mbarrier::complete_tx::bytes [%0], [%1, {%3, %4, %5}], [%2];"
               :: "r"(dst), "l"(m), "r"(mb), "r"(c0), "r"(c1), "r"(c2) : "memory");
}
DI void count_up(unsigned* p) {
  asm volatile("fence.proxy.async;" ::: "memory");
  asm volatile("red.release.gpu.global.add.u32 [%0], 1;" :: "l"(p) : "memory");
}
#define AX 0
#define FDLY 400
#define DRY 0
#define FEND 59
DI void publish(unsigned* p) {
  asm volatile("cp.async.bulk.wait_group 0;\nfence.proxy.async;" ::: "memory");
  asm volatile("red.relaxed.gpu.global.add.u32 [%0], 1;" :: "l"(p) : "memory");
}
#define G_IDLE 600
#define PL 2
#define ADLY 0

__global__ void __launch_bounds__(512, 1)
aux_kernel(const __grid_constant__ AMaps tm, const bf16* __restrict__ wqkv, const bf16* __restrict__ woa, const bf16* __restrict__ gate_w, bf16* __restrict__ out) {
  extern __shared__ __align__(1024) unsigned char smem_raw[];
  const uint32_t sb = smem_u32(smem_raw);
  const uint32_t fullx = sb + A_BAR, full1 = fullx + 24, empty1 = full1 + 8 * A_NS, fullw = empty1 + 8 * A_NS, full3 = fullw + 8, empty3 = full3 + 8 * A_NR,
                 fullq = empty3 + 8 * A_NR, fullv = fullq + 8, emptyq = fullv + 8, emptyv = emptyq + 8;
  const int tid = threadIdx.x, lane = tid & 31, cta = blockIdx.x;
  const int wg = __shfl_sync(0xffffffffu, tid >> 7, 0), w = __shfl_sync(0xffffffffu, (tid >> 5) & 3, 0);
  ASTAMP(14);
  if (tid == 384) {
    for (int i = 0; i < 3; i++) mbar_init(fullx + 8 * i, 1);
    for (int i = 0; i < A_NS; i++) { mbar_init(full1 + 8 * i, 1); mbar_init(empty1 + 8 * i, 8); }
    mbar_init(fullw, 1); mbar_init(fullq, 1); mbar_init(fullv, 1); mbar_init(emptyq, 4); mbar_init(emptyv, 4);
    for (int i = 0; i < A_NR; i++) { mbar_init(full3 + 8 * i, 1); mbar_init(empty3 + 8 * i, cta < NH ? 8 : 4); }
    fence_async();
  }
  __syncthreads();
  ASTAMP(0);
  const int tile = cta >> 1, hh = cta & 1;
  auto p3_n = [&](int g) { return cta < NH ? (cta & 3) * 2 + g : 8; };
  auto p3_k = [&](int g) { return cta < NH ? cta >> 2 : (cta & 3) * 2 + g; };
  if (wg == 3) {
    asm volatile("setmaxnreg.dec.sync.aligned.u32 24;");
    const bool lead = lane == 0;
    if (w < 3) {
      if (ADLY) wait_until(gtime() + ADLY);
      if (elect_one()) {
        mbar_expect(fullx + 8 * w, 49152);
        for (int p = 0; p < 2; p++)
          asm volatile("cp.async.bulk.tensor.4d.shared::cluster.global.mbarrier::complete_tx::bytes [%0], [%1, {%3, %4, %5, %6}], [%2];"
                       :: "r"(sb + p * A_XH + w * 24576), "l"(&tm.x), "r"(fullx + 8 * w), "r"(0), "r"(p), "r"(57 * tile - 7), "r"(3 * w) : "memory");
      }
#pragma unroll 1
      for (int r = 0; r < 17; r++) {
#pragma unroll 1
        for (int st = w; st < A_NS; st += 3) {
          if (r > 0) mbar_wait(empty1 + 8 * st, ~r & 1);
          if (r < 16 && elect_one()) {
            const int col = hh * 288 + (r >> 2) * 72, row = (r & 3) * 144 + st * 16;
            mbar_expect(full1 + 8 * st, A_WM + (AX & 1 ? 0 : A_WT));
            tma_load3c(sb + A_RING + st * A_WM, &tm.wa, col, row, 0, full1 + 8 * st);
            if (!(AX & 1)) tma_load3c(sb + A_TAIL + st * A_WT, &tm.wt, col + 64, row, 0, full1 + 8 * st);
          }
          __syncwarp();
        }
        if (r == 0 && elect_one())
          for (int j = 0; j < 3; j++)
            asm volatile("cp.async.bulk.prefetch.L2.global [%0], %1;" :: "l"((const char*)wqkv + cta * 55296 + (w * 3 + j) * 6144), "r"(6144) : "memory");
        __syncwarp();
      }
      bar_sync(8, 96);
    }
    const unsigned epoch = lds32(sb + A_BAR + 376);
    if (w == 2) {
      if (lead && cta < NH) {
#pragma unroll 1
        for (int seg = 0; seg < NAUXSEG; seg++) {
          const unsigned char* const src = g_seg + ((size_t)(AX & 128 ? 0 : seg % NRING) * 96 + cta * 3) * SEGB;
          SSTAMP(0, seg);
          const uint32_t tw = gtime();
          wait_count(&g_scnt[(seg * 32 + cta) * 8], 3 * (epoch + 1), !(TL & 2) || seg < NAUXSEG - 2);
          const bool idle = seg < FEND && gtime() - tw > G_IDLE;
          if (FDLY && idle) wait_until(gtime() + FDLY);
          SSTAMP(1, seg);
          mbar_wait(emptyq, ~seg & 1);
          if (AX & 8) { mbar_arrive(fullq); mbar_wait(emptyv, ~seg & 1); mbar_arrive(fullv); continue; }
          mbar_expect(fullq, 2 * SEGB);
          asm volatile("cp.async.bulk.shared::cluster.global.mbarrier::complete_tx::bytes [%0], [%1], %2, [%3];"
                       :: "r"(sb + A_IN), "l"(src), "r"(2 * SEGB), "r"(fullq) : "memory");
          mbar_wait(emptyv, ~seg & 1);
          mbar_expect(fullv, SEGB);
          asm volatile("cp.async.bulk.shared::cluster.global.mbarrier::complete_tx::bytes [%0], [%1], %2, [%3];"
                       :: "r"(sb + A_IN + 2 * SEGB), "l"(src + 2 * SEGB), "r"(SEGB), "r"(fullv) : "memory");
          if (seg == 1) wait_count(&g_abar[32], NAUX * (epoch + 1));
          stg_relaxed32(&g_used[cta * 32], epoch * NSEG + seg);
        }
      }
    }
    if (w == 3) {
#pragma unroll 1
      for (int c = 0; c < 4; c++) {
        if (lead) asm volatile("cp.async.bulk.wait_group.read 0;" ::: "memory");
        __syncwarp();
        bar_arrive(11, 160); bar_arrive(12, 160);
#pragma unroll 1
        for (int g = 0; g < 2; g++) {
          bar_sync(13 + g, 160);
          if (lead) {
            asm volatile("cp.async.bulk.tensor.3d.global.shared::cta.bulk_group [%0, {%2, %3, %4}], [%1];"
                         :: "l"(&tm.oa), "r"(sb + A_EPI + g * A_EPW + 1024), "r"(4096 + hh * 288 + c * 72), "r"(g), "r"(57 * tile) : "memory");
            asm volatile("cp.async.bulk.commit_group;" ::: "memory");
          }
        }
      }
      if (lead) asm volatile("cp.async.bulk.wait_group.read 0;" ::: "memory");
      __syncwarp();
      bar_arrive(10, 160);
      if (lead) publish(&g_abar[32]);
    }
    if ((w & 1) && cta < NH) {
      if (w == 1) bar_arrive(5, 160);
#pragma unroll 1
      for (int seg = w >> 1; seg < NAUXSEG; seg += 2) {
        bar_sync(w == 1 ? 4 : 15, 160);
        if (lead && !(AX & 32)) {
          tma_store(&tm.o, sb + A_OST, cta * DH, seg * 32);
          tma_store(&tm.o, sb + A_OST + 4096, cta * DH + 64, seg * 32);
          asm volatile("cp.async.bulk.commit_group;" ::: "memory");
          asm volatile("cp.async.bulk.wait_group.read 0;" ::: "memory");
        }
        __syncwarp();
        if (seg < NAUXSEG - 1) bar_arrive(5, 160);
        if (lead) {
          publish(&g_ocnt[seg * 64 + 2 * cta / 9 * 8]);
          if (2 * cta / 9 != (2 * cta + 1) / 9) asm volatile("red.relaxed.gpu.global.add.u32 [%0], 1;" :: "l"(&g_ocnt[seg * 64 + (2 * cta + 1) / 9 * 8]) : "memory");
          SSTAMP(9, seg);
        }
        __syncwarp();
      }
    }
    if (w != 0) return;
    if (lead) {
      mbar_expect(fullw, 20 * 8192);
#pragma unroll 1
      for (int k = 0; k < 20; k++) {
        const int g = k < 18 ? k / 9 : k - 18, kb = k < 18 ? p3_k(g) * 9 + k - 9 * g : 72;
        const uint32_t dst = sb + (k < 18 ? k * 8192 : A_XW + g * 8192);
        if (kb < 64) tma_load(dst, &tm.wob, p3_n(g) * 64, kb * 64, fullw);
        else tma_load(dst, &tm.woa, p3_n(g) * 64, (kb - 64) * 64, fullw);
      }
    }
    __syncwarp();
    bar_sync(6, 288);
    if (lead) {
      if (p3_k(1) == 7) { wait_count(&g_abar[32], NAUX * (epoch + 1)); asm volatile("fence.proxy.async;" ::: "memory"); }
      int avail = 0;
      bool waited = false;
      const int nbox = cta < NH ? NAUXSEG : 2 * NAUXSEG;
#pragma unroll 1
      for (int i = 0; i < nbox; i++) {
        const int seg = cta < NH ? i : i >> 1, ke = p3_k(i & 1), sl = i & 3;
        const unsigned nheads = (ke < 7 ? 5 : 1) * (epoch + 1);
        if (seg >= avail) {
          const int far = min(seg + 3, NAUXSEG - 1);
          if (cta < NH && far > seg && !waited && min((int)(ldg_relaxed32(&g_ocnt[far * 64 - 64 + ke * 8]) - nheads), (int)(ldg_acquire32(&g_ocnt[far * 64 + ke * 8]) - nheads)) >= 0) avail = far + 1;
          else waited = wait_count(&g_ocnt[seg * 64 + ke * 8], nheads, !(TL & 2) || seg < NAUXSEG - 2) && (TL & 4);
        }
        SSTAMP(5, seg);
        mbar_wait(empty3 + 8 * sl, ((i >> 2) & 1) ^ 1);
        if (AX & 4) { mbar_arrive(full3 + 8 * sl); continue; }
        mbar_expect(full3 + 8 * sl, XT + (ke == 7 ? 4096 : 0));
        tma_load3c(sb + sl * XT, &tm.o3, 0, seg * 32, ke * 9, full3 + 8 * sl);
        if (ke == 7) tma_load(sb + A_XT + sl * 4096, &tm.o, 72 * 64, seg * 32, full3 + 8 * sl);
      }
    }
    __syncwarp(); bar_sync(6, 288);
    if (GDW) asm volatile("griddepcontrol.wait;" ::: "memory");
  } else if (wg == 2) {
    asm volatile("setmaxnreg.dec.sync.aligned.u32 88;");
    {
      const unsigned epoch = *(volatile unsigned*)&g_epoch2;
      if ((tid & 127) < 80) { const uint4 g = __ldg((const uint4*)gate_w + min(tid & 127, 71)); sts128(sb + A_GW + (tid & 127) * 16, g.x, g.y, g.z, g.w); }
      fence_async();
      bar_sync(3, 128);
      float gt[2][4];
      const uint32_t d0 = (sb & 0x3FFFF) >> 4;
#pragma unroll 1
      for (int j = 0; j < 3; j++) {
        mbar_wait(fullx + 8 * j, 0);
        WG_FENCE();
#pragma unroll
        for (int k = 0; k < 24; k++)
          wgmma_n8_ss(gt[k & 1], desc_at(d0 + (k & 1) * (A_XH >> 4) + j * 1536 + (k >> 3) * 512 + (k & 6), 16, 1024, 1), desc_at(d0 + (A_GW >> 4) + j * 24 + (k & 30), 16, 128, 0), j | (k >> 1));
        WG_COMMIT();
      }
      WG_WAIT(0);
      if ((lane & 3) == 0)
#pragma unroll
        for (int i = 0; i < 4; i++) {
          const float gv = 1.f / (1.f + __expf(-gt[i >> 1][(i & 1) * 2]));
          const int r = w * 16 + (lane >> 2) + (i & 1) * 8, tok = 2 * (57 * tile - 7 + r) + (i >> 1);
          sts32(sb + A_GATE + ((i >> 1) * 64 + r) * 4, __float_as_uint(gv));
          if (hh == 0 && r >= 7 && tok < S_LEN) g_gate[tok] = gv;
        }
      if (tid == 256) sts32(sb + A_BAR + 376, epoch);
      __syncwarp();
      bar_arrive(7, 384);
      __half2 hw = __float2half2_rn(0.f);
#pragma unroll
      for (int i = 0; i < 9; i++) { const uint4 v = __ldg((const uint4*)woa + cta * 1152 + i * 128 + (tid & 127)); hw = amax4(hw, &v.x); }
      const uint32_t ew = wexp(hw);
      if (lane == 0) atomicMax(&g_amax[0], (unsigned long long)(epoch + 1) << 32 | ew);
      bar_sync(3, 128);
      if (tid == 256) {
        count_up(&g_abar[0]);
        wait_count(&g_abar[0], NAUX * (epoch + 1));
        if (cta == 0) *(volatile unsigned*)&g_epoch2 = epoch + 1;
      }
      __syncwarp();
      bar_sync(10, 160);
    }
    if (cta < NH) {
      const int lim = w * 8 + (lane >> 2) - 2 * (lane & 3);
      const uint32_t oa = sb + A_OST + (w * 8 + (lane & 7)) * 128;
      const uint32_t d0 = ((sb + A_IN) & 0x3FFFF) >> 4;
      uint32_t p[5][4];
#pragma unroll
      for (int n = 0; n < 10; n++) p[n >> 1][1 + (n & 1)] = __shfl_sync(0xffffffffu, lane ^ n, n);
#pragma unroll 1
      for (int seg = 0; seg < NAUXSEG; seg++) {
        const float gt = __ldcg(&g_gate[seg * 32 + w * 8 + (lane >> 2)]);
        float sc[20], d[32];
        mbar_wait(fullq, seg & 1);
        if (tid == 256) SSTAMP(2, seg);
        WG_FENCE();
#pragma unroll
        for (int k = 0; k < 8; k++) {
          const int o = ((k >> 2) * SEGB + (k & 3) * 256) >> 4;
          wgmma_n40_ss_tt(sc, desc_at(d0 + o, 128, 512, 0), desc_at(d0 + o + 256, 128, 1024, 0), k > 0);
        }
        WG_COMMIT();
        WG_WAIT(0);
        if (lane == 0) mbar_arrive(emptyq);
        float a[10];
#pragma unroll
        for (int i = 0; i < 10; i++) {
          a[i] = sc[(i >> 1) * 4 + (i & 1)] * (SM_SCALE * LOG2E);
          if (i < 8 && (i >> 1) * 8 + (i & 1) > lim) a[i] = -1.0e9f * LOG2E;
        }
        float m = max10(a);
        m = fmaxf(m, __shfl_xor_sync(0xffffffffu, m, 1)); m = fmaxf(m, __shfl_xor_sync(0xffffffffu, m, 2));
#pragma unroll
        for (int i = 0; i < 10; i++) a[i] = ex2(a[i] - m);
#pragma unroll
        for (int n = 0; n < 5; n++) {
          p[n][0] = pack_bf16(a[2 * n], a[2 * n + 1]); p[n][3] = p[n][0] | p[n][1];
          asm volatile("" : "+r"(p[n][0]), "+r"(p[n][3]) :: "memory");
        }
        float sum = ((a[0] + a[1]) + (a[2] + a[3])) + ((a[4] + a[5]) + (a[6] + a[7])) + (a[8] + a[9]);
        sum += __shfl_xor_sync(0xffffffffu, sum, 1);
        mbar_wait(fullv, seg & 1);
        WG_FENCE();
#pragma unroll
        for (int n = 0; n < 5; n++) wgmma_n64_rs(d, p[n], n < 4 ? desc_at(d0 + SEGB / 8 + 8 * n, 4096, 512, 0) : desc_at(d0 + SEGB / 8 + 512, 1024, 128, 0), n);
        WG_COMMIT();
        sum += __shfl_xor_sync(0xffffffffu, sum, 2);
        const float f = (1.f - gt) * rcp(sum);
        bar_sync(5, 160);
        WG_WAIT(0);
        if (lane == 0) mbar_arrive(emptyv);
        if (tid == 256) SSTAMP(4, seg);
#pragma unroll
        for (int q = 0; q < 4; q++) {
          const float* const o = d + (q & 1) * 16 + (q & 2);
          stsm4(oa + (q >> 1) * 4096 + ((((q & 1) * 4 + (lane >> 3)) ^ (lane & 7)) << 4), pack_bf16(o[0] * f, o[1] * f), pack_bf16(o[4] * f, o[5] * f),
                pack_bf16(o[8] * f, o[9] * f), pack_bf16(o[12] * f, o[13] * f));
        }
        fence_async();
        bar_arrive(seg & 1 ? 15 : 4, 160);
      }
    }
  } else {
    asm volatile("setmaxnreg.inc.sync.aligned.u32 200;");
    {
      const int g = lane >> 2, t = lane & 3;
      const uint32_t eb = sb + A_EPI + wg * A_EPW, d0 = (sb & 0x3FFFF) >> 4;
      const uint32_t own = (2 * t <= g ? 0xffffu : 0u) | (2 * t < g ? 0xffff0000u : 0u);
      const int kmin = 7 - 57 * tile - 16 * w;
      __half2 ho = __float2half2_rn(0.f);
#pragma unroll 1
      for (int c = -DRY; c < 4; c++) {
        float acc[96], tl[12];
#pragma unroll 1
        for (int r = c < 0 ? 4 : 0; r < 4; r++) {
#pragma unroll
          for (int st = 0; st < A_NS; st++) {
            const int ks = r * 9 + st;
            if (c == 0 && st % 3 == 0 && ks % 12 == 0) mbar_wait(fullx + 8 * (ks / 12), 0);
            mbar_wait(full1 + 8 * st, r & 1);
            const uint64_t da = desc_at(d0 + wg * (A_XH >> 4) + (ks >> 2) * 512 + (ks & 3) * 2, 16, 1024, 1);
            WG_FENCE();
            wgmma_n192_ss_nt(acc, da, desc_at(d0 + ((A_RING + st * A_WM) >> 4), 2048, 1024, 1), ks);
            if (!(AX & 2)) wgmma_n24_ss_nt(tl, da, desc_at(d0 + ((A_TAIL + st * A_WT) >> 4), 128, 256, 0), ks);
            WG_COMMIT();
            if (st == 0 && r == 2) bar_sync(11 + wg, 160);
            WG_WAIT(1);
            if (ks > 0 && lane == 0) mbar_arrive(empty1 + 8 * ((st + A_NS - 1) % A_NS));
          }
        }
        WG_WAIT(0);
        if (lane == 0 && c >= 0) mbar_arrive(empty1 + 8 * (A_NS - 1));
        ASTAMP(16 + (c & 3));
        uint32_t ql[9], qh[9], kl[9], kh[9], kx[10], vl[9], vh[9], vx[10];
#pragma unroll
        for (int j = 0; j < 9; j++) {
          const float* const q = j < 8 ? acc + 4 * j : tl, * const k = j < 8 ? acc + 32 + 4 * j : tl + 4, * const v = j < 8 ? acc + 64 + 4 * j : tl + 8;
          kh[j] = pack_bf16(k[2], k[3]); vh[j] = pack_bf16(v[2], v[3]);
          ql[j] = pack_bf16(q[0], q[1]); qh[j] = pack_bf16(q[2], q[3]); kl[j] = pack_bf16(k[0], k[1]); vl[j] = pack_bf16(v[0], v[1]);
        }
        if (w < 3) {
          const uint32_t ha = eb + 1024 + w * 2304 + lane * 16;
          stsm4(ha, kh[0], kh[1], kh[2], kh[3]); stsm4(ha + 512, kh[4], kh[5], kh[6], kh[7]);
          stsm4(ha + 1024, vh[0], vh[1], vh[2], vh[3]); stsm4(ha + 1536, vh[4], vh[5], vh[6], vh[7]);
          asm volatile("stmatrix.sync.aligned.m8n8.x2.shared.b16 [%0], {%1,%2};" :: "r"(ha + 2048), "r"(kh[8]), "r"(vh[8]) : "memory");
        }
        if (c == 0) bar_sync(7, 384); else bar_sync(1 + wg, 128);
        {
          const uint32_t ha = eb + 1024 + max(w - 1, 0) * 2304 + lane * 16;
          ldsm4(kx, ha); ldsm4(kx + 4, ha + 512); ldsm4t(vx, ha + 1024); ldsm4t(vx + 4, ha + 1536);
          asm volatile("ldmatrix.sync.aligned.m8n8.x1.shared.b16 {%0}, [%1];" : "=r"(kx[8]) : "r"(ha + 2048) : "memory");
          asm volatile("ldmatrix.sync.aligned.m8n8.x1.trans.shared.b16 {%0}, [%1];" : "=r"(vx[8]) : "r"(ha + 2176) : "memory");
        }
        const float gl = __uint_as_float(lds32(sb + A_GATE + (wg * 64 + w * 16 + g) * 4)), gh = __uint_as_float(lds32(sb + A_GATE + (wg * 64 + w * 16 + g + 8) * 4));
#pragma unroll
        for (int j = 0; j < 9; j++) { vl[j] = movm(vl[j]); vh[j] = movm(vh[j]); }
        bar_sync(1 + wg, 128);
        uint32_t ol[9], oh[9];
#pragma unroll
        for (int i = 0; i < 4; i++) {
          const int b = 2 * i;
          const uint32_t a[4] = {t >= i ? ql[b] : 0u, t >= i ? qh[b] : 0u, ql[b + 1], qh[b + 1]}, a4 = t <= i ? ql[b + 2] : 0u, a5 = t <= i ? qh[b + 2] : 0u;
          float sx[4], sl[4], sh[4];
          mma16816z(sx, a, kx[b], kx[b + 1]); mma16816z(sl, a, kl[b], kl[b + 1]); mma16816z(sh, a, kh[b], kh[b + 1]);
          mma1688(sx, a4, a5, kx[b + 2]); mma1688(sl, a4, a5, kl[b + 2]); mma1688(sh, a4, a5, kh[b + 2]);
          float e[4];
#pragma unroll
          for (int u = 0; u < 4; u++) {
            const int cc = 2 * t + (u & 1);
            e[u] = (cc <= g ? (u < 2 ? sl[u] : sh[u]) : (u < 2 ? sx[u] : sl[u])) * (0.23570226039551584f * LOG2E);
            if ((cc <= g ? cc : cc - 8) + (u & 2) * 4 < kmin) e[u] = -1.0e9f * LOG2E;
          }
          float m0 = fmaxf(e[0], e[1]), m1 = fmaxf(e[2], e[3]);
#pragma unroll
          for (int o = 1; o < 4; o <<= 1) { m0 = fmaxf(m0, __shfl_xor_sync(0xffffffffu, m0, o)); m1 = fmaxf(m1, __shfl_xor_sync(0xffffffffu, m1, o)); }
          e[0] = ex2(e[0] - m0); e[1] = ex2(e[1] - m0); e[2] = ex2(e[2] - m1); e[3] = ex2(e[3] - m1);
          const uint32_t p0 = pack_bf16(e[0], e[1]), p1 = pack_bf16(e[2], e[3]);
          const uint32_t p[4] = {p0 & ~own, 0u, p0 & own, p1 & ~own};
          float s0 = e[0] + e[1], s1 = e[2] + e[3];
#pragma unroll
          for (int o = 1; o < 4; o <<= 1) { s0 += __shfl_xor_sync(0xffffffffu, s0, o); s1 += __shfl_xor_sync(0xffffffffu, s1, o); }
          const float f0 = gl * rcp(s0), f1 = gh * rcp(s1);
#pragma unroll
          for (int j = b; j < b + 3; j++) {
            float o[4];
            mma16816z(o, p, vx[j], vl[j]);
            mma1688(o, 0u, p1 & own, vh[j]);
            const uint32_t lo = pack_bf16(o[0] * f0, o[1] * f0), hi = pack_bf16(o[2] * f1, o[3] * f1);
            if (j > b || i == 0) { ol[j] = lo; oh[j] = hi; }
            else { ol[j] = t >= i ? lo : ol[j]; oh[j] = t >= i ? hi : oh[j]; }
          }
        }
        const uint32_t sa = eb + 16 + (w * 16 + (lane & 15)) * 144 + (lane >> 4) * 16;
#pragma unroll
        for (int j = 0; j < 8; j += 2) stsm4(sa + j * 16, ol[j], oh[j], ol[j + 1], oh[j + 1]);
        asm volatile("stmatrix.sync.aligned.m8n8.x2.shared.b16 [%0], {%1,%2};" :: "r"(sa + 128), "r"(ol[8]), "r"(oh[8]) : "memory");
        ho = amax4(amax4(amax4(amax4(ho, ol), ol + 4), oh), oh + 4);
        ho = __hmax2_nan(__hmax2_nan(ho, __habs2(*(const __half2*)&ol[8])), __habs2(*(const __half2*)&oh[8]));
        if (c == 3 && tile == 17) {
          const uint32_t eo = wexp(ho);
          if (lane == 0) atomicMax(&g_amax[16], (unsigned long long)(lds32(sb + A_BAR + 376) + 1) << 32 | eo);
        }
        fence_async();
        if (c >= 0) bar_arrive(13 + wg, 160); else bar_sync(1 + wg, 128);
        ASTAMP(20 + (c & 3));
      }
    }
    ASTAMP(3);
    uint32_t wa[36][4];
    mbar_wait(fullw, 0);
    const uint32_t la = sb + wg * 73728 + ((lane & 7) + ((lane >> 4) << 3)) * 128 + (((2 * w + ((lane >> 3) & 1)) ^ (lane & 7)) << 4);
#pragma unroll
    for (int k = 0; k < 36; k++) ldsm4t(wa[k], la + k * 2048);
    fence_async();
    bar_sync(6, 288);
    ASTAMP(4);
    const int nsl = p3_n(wg), ke = p3_k(wg), t = lane & 3;
    const unsigned epoch = lds32(sb + A_BAR + 376);
    uint2* const part = g_part + nsl * 4096 + w * 16 + (lane >> 2) * 2 + (t & 1);
    auto tag = [&](int seg) { return ((seg >> 2) + 1 + (epoch & (seg >> 1))) & 1; };
    uint2 v[4];
    auto fetch = [&](int seg) {
#pragma unroll
      for (int j = 0; j < 4; j++)
        asm volatile("ld.relaxed.gpu.global.v2.b32 {%0,%1}, [%2];" : "=r"(v[j].x), "=r"(v[j].y) : "l"(part + (seg & 3) * 36864 + ke * 512 + ((t >> 1) * 4 + j) * 64) : "memory");
    };
    auto finish = [&](int seg) {
      int n = 0;
#pragma unroll 1
      while (!(AX & 16) && __any_sync(0xffffffffu, (((v[0].x ^ tag(seg)) | (v[1].x ^ tag(seg)) | (v[2].x ^ tag(seg)) | (v[3].x ^ tag(seg))) & 1) != 0) && ++n < SPIN_LIMIT) {
        if (seg < NAUXSEG - ((TL & 2) ? 2 : 1)) __nanosleep(100);
        fetch(seg);
      }
      const float a0 = (bf_lo(v[0].x) + bf_lo(v[1].x)) + (bf_lo(v[2].x) + bf_lo(v[3].x)), a1 = (bf_hi(v[0].x) + bf_hi(v[1].x)) + (bf_hi(v[2].x) + bf_hi(v[3].x));
      const float b0 = (bf_lo(v[0].y) + bf_lo(v[1].y)) + (bf_lo(v[2].y) + bf_lo(v[3].y)), b1 = (bf_hi(v[0].y) + bf_hi(v[1].y)) + (bf_hi(v[2].y) + bf_hi(v[3].y));
      const float c0 = (t < 2 ? a0 : b0) + __shfl_xor_sync(0xffffffffu, t < 2 ? b0 : a0, 2), c1 = (t < 2 ? a1 : b1) + __shfl_xor_sync(0xffffffffu, t < 2 ? b1 : a1, 2);
      ((uint32_t*)(out + (size_t)(seg * 32 + ke * 4 + ((lane >> 2) & 3)) * DM + nsl * 64 + w * 16 + (lane >> 4) * 8))[t] = movm(pack_bf16(c0, c1));
    };
    float acc[16];
#pragma unroll
    for (int i = 0; i < 16; i++) acc[i] = 0.f;
    const uint32_t d0 = (sb & 0x3FFFF) >> 4;
#pragma unroll 1
    for (int seg = 0; seg < NAUXSEG; seg++) {
      const int i = cta < NH ? seg : 2 * seg + wg, sl = i & 3;
      mbar_wait(full3 + 8 * sl, (i >> 2) & 1);
      if (tid == 128) SSTAMP(6, seg);
      if (!(AX & 16)) fetch(max(seg - PL, 0));
      if (ke == 7) {
        WG_FENCE();
#pragma unroll
        for (int j = 0; j < 4; j++) wgmma_n32_ss_tn(acc, desc_at(d0 + ((A_XW + wg * 8192) >> 4) + j * 128, 8192, 1024, 1), desc_at(d0 + ((A_XT + sl * 4096) >> 4) + j * 2, 16, 1024, 1), j);
        WG_COMMIT();
        WG_WAIT(0);
      }
      if (!(AX & 64)) {
        const uint64_t db = desc_at(d0 + sl * (XT >> 4), 16, 1024, 1);
        WG_FENCE();
#pragma unroll
        for (int k = 0; k < 36; k++) wgmma_n32_rs(acc, wa[k][0], wa[k][1], wa[k][2], wa[k][3], db + (k >> 2) * 256 + (k & 3) * 2, k ? 1 : ke == 7);
        WG_COMMIT();
      }
      if (seg >= PL) finish(seg - PL);
      WG_WAIT(0);
      if (lane == 0) mbar_arrive(empty3 + 8 * sl);
#pragma unroll
      for (int j = 0; j < 4; j++)
        if (!(AX & 16))
          asm volatile("st.relaxed.gpu.global.v2.b32 [%0], {%1,%2};" :: "l"(part + (seg & 3) * 36864 + (2 * j + (t >> 1)) * 512 + ke * 64),
                       "r"((pack_bf16(acc[4 * j], acc[4 * j + 1]) & ~1u) | tag(seg)), "r"(pack_bf16(acc[4 * j + 2], acc[4 * j + 3])) : "memory");
      if (tid == 128) SSTAMP(7, seg);
      if (tid == 128) SSTAMP(8, seg);
      if ((seg & 7) == 6) ASTAMP(5 + (seg >> 3));
    }
#pragma unroll 1
    for (int seg = NAUXSEG - PL; seg < NAUXSEG; seg++) { fetch(seg); finish(seg); }
    ASTAMP(13);
    TSTAMP(48);
    bar_sync(6, 288);
  }
}

typedef CUresult (*EncodeFn)(CUtensorMap*, CUtensorMapDataType, cuuint32_t, void*, const cuuint64_t*, const cuuint64_t*,
                             const cuuint32_t*, const cuuint32_t*, CUtensorMapInterleave, CUtensorMapSwizzle,
                             CUtensorMapL2promotion, CUtensorMapFloatOOBfill);
static void make_map(EncodeFn enc, CUtensorMap* m, const void* p, int rows, int cols, int box_rows) {
  cuuint64_t dims[2] = {(cuuint64_t)cols, (cuuint64_t)rows};
  cuuint64_t strides[1] = {(cuuint64_t)cols * 2};
  cuuint32_t box[2] = {64, (cuuint32_t)box_rows};
  cuuint32_t es[2] = {1, 1};
  enc(m, CU_TENSOR_MAP_DATA_TYPE_BFLOAT16, 2, (void*)p, dims, strides, box, es, CU_TENSOR_MAP_INTERLEAVE_NONE,
      CU_TENSOR_MAP_SWIZZLE_128B, CU_TENSOR_MAP_L2_PROMOTION_L2_128B, CU_TENSOR_MAP_FLOAT_OOB_FILL_NONE);
}

constexpr int g_poll = POLL_NS;
extern "C" void kernel_launch(void* const* d_in, const int* in_sizes, int n_in, void* d_out, int out_size) {
  const bf16* x = (const bf16*)d_in[0];
  const bf16* wqkvA = (const bf16*)d_in[1];
  const bf16* woA = (const bf16*)d_in[2];
  const bf16* mem0 = (const bf16*)d_in[4];
  const bf16* Wq = (const bf16*)d_in[5];
  const bf16* Wk = (const bf16*)d_in[6];
  const bf16* Wv = (const bf16*)d_in[7];
  const bf16* Wo = (const bf16*)d_in[8];
  const bf16* gate_w = (const bf16*)d_in[10];
  static EncodeFn enc = nullptr;
  static void *pO = nullptr, *pR = nullptr;
  if (!enc) {
    cudaDriverEntryPointQueryResult qr;
    cudaGetDriverEntryPoint("cuTensorMapEncodeTiled", (void**)&enc, cudaEnableDefault, &qr);
    cudaGetSymbolAddress(&pO, g_Ocat);
    cudaGetSymbolAddress(&pR, g_red_raw);
    cudaFuncSetAttribute(rec_kernel, cudaFuncAttributeMaxDynamicSharedMemorySize, SM_TOTAL);
    cudaFuncSetAttribute(aux_kernel, cudaFuncAttributeMaxDynamicSharedMemorySize, A_TOTAL);
  }
  RMaps rm;
  rm.poll = g_poll; rm.out = (bf16*)d_out;
  make_map(enc, &rm.woa, woA, DM, DM, 24);
  {
    cuuint64_t dims[2] = {KCAT, S_LEN}, strides[1] = {KCAT * 2};
    cuuint32_t box[2] = {32, 64}, es[2] = {1, 1};
    enc(&rm.oa, CU_TENSOR_MAP_DATA_TYPE_BFLOAT16, 2, pO, dims, strides, box, es, CU_TENSOR_MAP_INTERLEAVE_NONE,
        CU_TENSOR_MAP_SWIZZLE_NONE, CU_TENSOR_MAP_L2_PROMOTION_NONE, CU_TENSOR_MAP_FLOAT_OOB_FILL_NONE);
  }
  rm.red = (unsigned char*)(((uintptr_t)pR + 262143) & ~(uintptr_t)262143);
  {
    cuuint64_t dims[3] = {64, S_LEN, 9}, strides[2] = {DM * 2, 128};
    cuuint32_t box[3] = {64, 32, 9}, es[3] = {1, 1, 1};
    enc(&rm.x, CU_TENSOR_MAP_DATA_TYPE_BFLOAT16, 3, (void*)x, dims, strides, box, es, CU_TENSOR_MAP_INTERLEAVE_NONE,
        CU_TENSOR_MAP_SWIZZLE_128B, CU_TENSOR_MAP_L2_PROMOTION_L2_128B, CU_TENSOR_MAP_FLOAT_OOB_FILL_NONE);
  }
  make_map(enc, &rm.wq, Wq, DM, 4096, 192);
  make_map(enc, &rm.wk, Wk, DM, 4096, 192);
  make_map(enc, &rm.wv, Wv, DM, 4096, 192);
  make_map(enc, &rm.wo, Wo, 4096, DM, 128);
  AMaps am;
  {
    cuuint32_t es[4] = {1, 1, 1, 1};
    cuuint64_t dx[4] = {64, 2, S_LEN / 2, 9}, sx[3] = {DM * 2, DM * 4, 128};
    cuuint32_t bx[4] = {64, 1, 64, 3};
    enc(&am.x, CU_TENSOR_MAP_DATA_TYPE_BFLOAT16, 4, (void*)x, dx, sx, bx, es, CU_TENSOR_MAP_INTERLEAVE_NONE,
        CU_TENSOR_MAP_SWIZZLE_128B, CU_TENSOR_MAP_L2_PROMOTION_L2_128B, CU_TENSOR_MAP_FLOAT_OOB_FILL_NONE);
    cuuint64_t dw[3] = {DM, DM, 3}, sw[2] = {DM * 6, DM * 2};
    cuuint32_t bw[3] = {64, 16, 3}, bt[3] = {8, 16, 3};
    enc(&am.wa, CU_TENSOR_MAP_DATA_TYPE_BFLOAT16, 3, (void*)wqkvA, dw, sw, bw, es, CU_TENSOR_MAP_INTERLEAVE_NONE,
        CU_TENSOR_MAP_SWIZZLE_128B, CU_TENSOR_MAP_L2_PROMOTION_L2_128B, CU_TENSOR_MAP_FLOAT_OOB_FILL_NONE);
    enc(&am.wt, CU_TENSOR_MAP_DATA_TYPE_BFLOAT16, 3, (void*)wqkvA, dw, sw, bt, es, CU_TENSOR_MAP_INTERLEAVE_NONE,
        CU_TENSOR_MAP_SWIZZLE_NONE, CU_TENSOR_MAP_L2_PROMOTION_NONE, CU_TENSOR_MAP_FLOAT_OOB_FILL_NONE);
    cuuint64_t dz[3] = {KCAT, 2, S_LEN / 2}, sz[2] = {KCAT * 2, KCAT * 4};
    cuuint32_t bz[3] = {72, 1, 57};
    enc(&am.oa, CU_TENSOR_MAP_DATA_TYPE_BFLOAT16, 3, pO, dz, sz, bz, es, CU_TENSOR_MAP_INTERLEAVE_NONE,
        CU_TENSOR_MAP_SWIZZLE_NONE, CU_TENSOR_MAP_L2_PROMOTION_NONE, CU_TENSOR_MAP_FLOAT_OOB_FILL_NONE);
  }
  {
    cuuint64_t dims[3] = {64, S_LEN, KCAT / 64}, strides[2] = {KCAT * 2, 128};
    cuuint32_t box[3] = {64, 32, 9}, es[3] = {1, 1, 1};
    make_map(enc, &am.o, pO, S_LEN, KCAT, 32);
    enc(&am.o3, CU_TENSOR_MAP_DATA_TYPE_BFLOAT16, 3, pO, dims, strides, box, es, CU_TENSOR_MAP_INTERLEAVE_NONE,
        CU_TENSOR_MAP_SWIZZLE_128B, CU_TENSOR_MAP_L2_PROMOTION_L2_128B, CU_TENSOR_MAP_FLOAT_OOB_FILL_NONE);
  }
  make_map(enc, &am.wob, Wo, 4096, DM, 64);
  make_map(enc, &am.woa, woA, DM, DM, 64);

  rec_kernel<<<96, 384, SM_TOTAL, cudaStreamPerThread>>>(rm, x, mem0);
  cudaLaunchConfig_t cfg = {};
  cfg.gridDim = dim3(NAUX); cfg.blockDim = dim3(512); cfg.dynamicSmemBytes = A_TOTAL; cfg.stream = cudaStreamPerThread;
  cudaLaunchAttribute at[1];
  at[0].id = cudaLaunchAttributeProgrammaticStreamSerialization; at[0].val.programmaticStreamSerializationAllowed = 1;
  cfg.attrs = at; cfg.numAttrs = 1;
  if (XP & 16) cfg.numAttrs = 0;
  if (!(XP & 64)) cudaLaunchKernelEx(&cfg, aux_kernel, am, wqkvA, woA, gate_w, (bf16*)d_out);
}
```

```cpp
#include <cuda_runtime.h>
#include <cuda_bf16.h>
#include <cuda_fp16.h>
#include <cuda.h>
#include <stdint.h>

typedef __nv_bfloat16 bf16;

constexpr int S_LEN = 2048, DM = 576, NH = 32, DH = 128, NSEG = 64, KCAT = 4096 + 576;
constexpr int NAUXSEG = NSEG - 2;
constexpr int NAUX = 36;
#define RED_LINE(i) (((i) >> 2) * 4096 + ((i) & 1) * 256 + ((i) & 2) * 512)
#define RED_SLOT(s) (((s) & 1) * 128 + ((s) & 2) * 256)

#define POLL_NS 896
#define NII 18
#define W3PRE 4
#define W3MID 4
#define GF 0
#define B5POS 0
#define NUP 4
#define UPF 1
#define B3Q 9
#define B3F 0
#define GATE 7
#define NTL 2
#define B7R 1
#define VS0 1
#define VS1 0
#define VLATE(w) ((w) == 0 ? VS0 == 1 : (w) == 1 ? VS1 == 1 : false)
#define HOIST 1
#define GDW 0
#define RSLOW 0
#define CSY 0
#define DD 2
#define N12 18
#define N14 18
#define HP 0
#define HL 0
#define WL 1
#define RV 3
#define RET 1
#define TL 6
#define CLR 1
#define RFW 0
#define NIC 0
#define LEAD 0
#define FIN16 1
#define VXG 0
#define NRING 20
#define EXD 0
#define HDLY 0
#define F10 1
#define NPROBE 2
#define QM 0
#define N5 224
#define KP(i) (((i) >> 1) + 4 * ((i) & 1))
#define SPIN_LIMIT (1 << 14)
#define XP 0

__device__ __align__(1024) bf16 g_Ocat[S_LEN * KCAT];
__device__ __align__(1024) unsigned char g_red_raw[2 * 262144];
constexpr int HINT_OFF = 2048;
__device__ __align__(16) float g_gate[S_LEN];
__device__ __align__(128) uint4 g_stats[96 * 2];
__device__ unsigned g_epoch;
__device__ unsigned g_epoch2;
__device__ unsigned g_ocnt[NSEG * 64];
__device__ unsigned g_abar[3 * 32];
__device__ unsigned long long g_amax[2 * 16];
__device__ unsigned g_scnt[NSEG * 32 * 8];
__device__ __align__(1024) unsigned char g_seg[NRING * 96 * 10240];
__device__ unsigned g_used[NH * 32];
__device__ __align__(1024) uint2 g_part[4 * 9 * 64 * 64];
__device__ int g_err;
#define TSTAMP(i)
#define PROF(idx)
#define PROFP(idx)
#define RSTAMP(k)
#define STAMP(idx)
#define ASTAMP(idx)
#define SSTAMP(k, seg)
#define WSTAMP(idx)

#define DI __device__ __forceinline__
DI uint32_t smem_u32(const void* p) { return (uint32_t)__cvta_generic_to_shared(p); }
DI uint32_t clock32() { uint32_t c; asm volatile("mov.u32 %0, %%clock;" : "=r"(c) :: "memory"); return c; }
DI uint32_t gtime() { uint32_t c; asm volatile("mov.u32 %0, %%globaltimer_lo;" : "=r"(c) :: "memory"); return c; }
DI uint32_t ldg_relaxed32(const void* p) { uint32_t v; asm volatile("ld.relaxed.gpu.global.b32 %0, [%1];" : "=r"(v) : "l"(p) : "memory"); return v; }
DI uint32_t ldg_acquire32(const void* p) { uint32_t v; asm volatile("ld.acquire.gpu.global.b32 %0, [%1];" : "=r"(v) : "l"(p) : "memory"); return v; }
DI void stg_relaxed32(void* p, uint32_t v) { asm volatile("st.relaxed.gpu.global.b32 [%0], %1;" :: "l"(p), "r"(v) : "memory"); }
DI int head_id() { int c; asm volatile("mov.u32 %0, %%clusterid.x;" : "=r"(c)); return c; }
DI uint32_t mapa(uint32_t a, uint32_t r) { uint32_t o; asm("mapa.shared::cluster.u32 %0, %1, %2;" : "=r"(o) : "r"(a), "r"(r)); return o; }
DI void cluster_arrive() { asm volatile("barrier.cluster.arrive.relaxed.aligned;" ::: "memory"); }
DI void cluster_wait() { asm volatile("barrier.cluster.wait.aligned;" ::: "memory"); }
DI void cluster_sync() { asm volatile("barrier.cluster.arrive.release.aligned;\nbarrier.cluster.wait.acquire.aligned;" ::: "memory"); }
DI void mbar_init(uint32_t b, uint32_t c) { asm volatile("mbarrier.init.shared::cta.b64 [%0], %1;" :: "r"(b), "r"(c) : "memory"); }
DI void mbar_expect(uint32_t b, uint32_t tx) { asm volatile("mbarrier.arrive.expect_tx.shared::cta.b64 _, [%0], %1;" :: "r"(b), "r"(tx) : "memory"); }
DI void mbar_arrive(uint32_t b) { asm volatile("mbarrier.arrive.shared::cta.b64 _, [%0];" :: "r"(b) : "memory"); }
DI void mbar_wait(uint32_t b, uint32_t par) {
  asm volatile("{\n.reg .pred p;\n.reg .u32 n, q;\nmov.u32 n, 0;\n"
               "WL: add.u32 n, n, 1;\nshr.u32 q, n, 12;\nxor.b32 q, q, %1;\n"
               "mbarrier.try_wait.parity.shared::cta.b64 p, [%0], q;\n@!p bra.uni WL;\n}"
               :: "r"(b), "r"(par) : "memory");
}
DI void mbar_wait_fast(uint32_t b, uint32_t par) {
  asm volatile("{\n.reg .pred p;\n.reg .u32 n, q;\nmbarrier.try_wait.parity.shared::cta.b64 p, [%0], %1;\n@p bra.uni WD;\nmov.u32 n, 0;\n"
               "WL: add.u32 n, n, 1;\nshr.u32 q, n, 12;\nxor.b32 q, q, %1;\n"
               "mbarrier.try_wait.parity.shared::cta.b64 p, [%0], q;\n@!p bra.uni WL;\nWD:\n}"
               :: "r"(b), "r"(par) : "memory");
}
DI void wait_until(uint32_t t) {
  const uint32_t now = gtime();
  t = min(t, now + 8192);
  asm volatile("{\n.reg .pred p;\n.reg .u32 c;\nTL: mov.u32 c, %%globaltimer_lo;\nsetp.lt.u32 p, c, %0;\n@p bra.uni TL;\n}" :: "r"(t) : "memory");
}
#define PIN(v) v = __shfl_xor_sync(0xffffffffu, v, 0)
#define SCHED_FENCE(k) asm volatile("{\n.reg .pred p;\nsetp.eq.u32 p, %0, %1;\n@p exit;\n}" :: "r"(fence_reg), "r"(k) : "memory")
#define MEM_ORDER(k) asm volatile("{\n.reg .pred p;\nsetp.eq.u32 p, %0, %1;\n@p st.shared.u32 [%0], %0;\n}" :: "r"(fence_reg), "r"(k + 64) : "memory")
DI void bar_sync(int id, int n) { asm volatile("bar.sync %0, %1;" :: "r"(id), "r"(n) : "memory"); }
DI void bar_arrive(int id, int n) { asm volatile("bar.arrive %0, %1;" :: "r"(id), "r"(n) : "memory"); }
DI void fence_async() { asm volatile("fence.proxy.async.shared::cta;" ::: "memory"); }
DI void st_async4(uint32_t a, uint32_t x, uint32_t y, uint32_t z, uint32_t w, uint32_t mb) {
  asm volatile("st.async.weak.shared::cluster.mbarrier::complete_tx::bytes.v4.b32 [%0], {%1,%2,%3,%4}, [%5];"
               :: "r"(a), "r"(x), "r"(y), "r"(z), "r"(w), "r"(mb) : "memory");
}
DI void st_async2(uint32_t a, uint32_t x, uint32_t y, uint32_t mb) {
  asm volatile("st.async.weak.shared::cluster.mbarrier::complete_tx::bytes.v2.b32 [%0], {%1,%2}, [%3];"
               :: "r"(a), "r"(x), "r"(y), "r"(mb) : "memory");
}
DI void sts32(uint32_t a, uint32_t x) { asm volatile("st.shared.b32 [%0], %1;" :: "r"(a), "r"(x) : "memory"); }
DI void sts64(uint32_t a, uint32_t x, uint32_t y) { asm volatile("st.shared.v2.b32 [%0], {%1,%2};" :: "r"(a), "r"(x), "r"(y) : "memory"); }
DI void sts128(uint32_t a, uint32_t x, uint32_t y, uint32_t z, uint32_t w) {
  asm volatile("st.shared.v4.b32 [%0], {%1,%2,%3,%4};" :: "r"(a), "r"(x), "r"(y), "r"(z), "r"(w) : "memory");
}
DI uint32_t lds32(uint32_t a) { uint32_t x; asm volatile("ld.shared.b32 %0, [%1];" : "=r"(x) : "r"(a) : "memory"); return x; }
DI void lds64(uint32_t a, uint32_t& x, uint32_t& y) { asm volatile("ld.shared.v2.b32 {%0,%1}, [%2];" : "=r"(x), "=r"(y) : "r"(a) : "memory"); }
DI void lds128(uint32_t a, uint32_t* r) {
  asm volatile("ld.shared.v4.b32 {%0,%1,%2,%3}, [%4];" : "=r"(r[0]), "=r"(r[1]), "=r"(r[2]), "=r"(r[3]) : "r"(a) : "memory");
}
DI void lds128f(uint32_t a, float* r) {
  asm volatile("ld.shared.v4.f32 {%0,%1,%2,%3}, [%4];" : "=f"(r[0]), "=f"(r[1]), "=f"(r[2]), "=f"(r[3]) : "r"(a) : "memory");
}
DI void lds64f(uint32_t a, float* r) { asm volatile("ld.shared.v2.f32 {%0,%1}, [%2];" : "=f"(r[0]), "=f"(r[1]) : "r"(a) : "memory"); }
DI void ldsm4t(uint32_t* r, uint32_t a) {
  asm volatile("ldmatrix.sync.aligned.m8n8.x4.trans.shared.b16 {%0,%1,%2,%3}, [%4];"
               : "=r"(r[0]), "=r"(r[1]), "=r"(r[2]), "=r"(r[3]) : "r"(a) : "memory");
}
DI void ldsm4t_in(uint32_t* r, uint32_t a, uint32_t t) {
  asm volatile("{\n.reg .pred p;\nsetp.ne.u32 p, %5, 0;\n@p ldmatrix.sync.aligned.m8n8.x4.trans.shared.b16 {%0,%1,%2,%3}, [%4];\n}"
               : "+r"(r[0]), "+r"(r[1]), "+r"(r[2]), "+r"(r[3]) : "r"(a), "r"(t) : "memory");
}
DI void lds128_in(uint32_t* r, uint32_t a, uint32_t t) {
  asm volatile("{\n.reg .pred p;\nsetp.ne.u32 p, %5, 0;\n@p ld.shared.v4.b32 {%0,%1,%2,%3}, [%4];\n}"
               : "+r"(r[0]), "+r"(r[1]), "+r"(r[2]), "+r"(r[3]) : "r"(a), "r"(t) : "memory");
}
DI void ldsm2t_in(uint32_t* r, uint32_t a, uint32_t t) {
  asm volatile("{\n.reg .pred p;\nsetp.ne.u32 p, %3, 0;\n@p ldmatrix.sync.aligned.m8n8.x2.trans.shared.b16 {%0,%1}, [%2];\n}" : "+r"(r[0]), "+r"(r[1]) : "r"(a), "r"(t) : "memory");
}
DI void reserve2(uint32_t* r) { asm volatile("{\n.reg .u64 t;\nmov.u64 t, %%clock64;\nmov.b64 {%0, %1}, t;\n}" : "=r"(r[0]), "=r"(r[1])); }
DI void scale_sum(float& x, float& y, float s, uint32_t t) {
  asm volatile("{\n.reg .pred p;\nsetp.ne.u32 p, %2, 0;\n@p mul.f32 %0, %0, %1;\n}" : "+f"(y) : "f"(s), "r"(t));
  asm volatile("{\n.reg .pred p;\nsetp.ne.u32 p, %3, 1;\n@p fma.rn.f32 %0, %0, %1, %2;\n}" : "+f"(x) : "f"(s), "f"(y), "r"(t));
}
DI void ldsm4(uint32_t* r, uint32_t a) {
  asm volatile("ldmatrix.sync.aligned.m8n8.x4.shared.b16 {%0,%1,%2,%3}, [%4];"
               : "=r"(r[0]), "=r"(r[1]), "=r"(r[2]), "=r"(r[3]) : "r"(a) : "memory");
}
DI void st_async1(uint32_t a, uint32_t x, uint32_t mb) {
  asm volatile("st.async.weak.shared::cluster.mbarrier::complete_tx::bytes.b32 [%0], %1, [%2];" :: "r"(a), "r"(x), "r"(mb) : "memory");
}
DI void stsm4(uint32_t a, uint32_t x, uint32_t y, uint32_t z, uint32_t w) {
  asm volatile("stmatrix.sync.aligned.m8n8.x4.shared.b16 [%0], {%1,%2,%3,%4};" :: "r"(a), "r"(x), "r"(y), "r"(z), "r"(w) : "memory");
}
DI void stsm4t(uint32_t a, uint32_t x, uint32_t y, uint32_t z, uint32_t w) {
  asm volatile("stmatrix.sync.aligned.m8n8.x4.trans.shared.b16 [%0], {%1,%2,%3,%4};" :: "r"(a), "r"(x), "r"(y), "r"(z), "r"(w) : "memory");
}
DI uint32_t pack_bf16(float lo, float hi) { uint32_t r; asm("cvt.rn.bf16x2.f32 %0, %1, %2;" : "=r"(r) : "f"(hi), "f"(lo)); return r; }
DI uint32_t pack_f16(float lo, float hi) { uint32_t r; asm("cvt.rn.f16x2.f32 %0, %1, %2;" : "=r"(r) : "f"(hi), "f"(lo)); return r; }
DI float ex2(float x) { float y; asm("ex2.approx.ftz.f32 %0, %1;" : "=f"(y) : "f"(x)); return y; }
DI float rcp(float x) { float y; asm("rcp.approx.ftz.f32 %0, %1;" : "=f"(y) : "f"(x)); return y; }
DI float bf_lo(uint32_t x) { return __uint_as_float(x << 16); }
DI float bf_hi(uint32_t x) { return __uint_as_float(x & 0xffff0000u); }
DI void mma16816(float* d, const uint32_t* a, uint32_t b0, uint32_t b1) {
  asm volatile("mma.sync.aligned.m16n8k16.row.col.f32.bf16.bf16.f32 {%0,%1,%2,%3}, {%4,%5,%6,%7}, {%8,%9}, {%0,%1,%2,%3};"
               : "+f"(d[0]), "+f"(d[1]), "+f"(d[2]), "+f"(d[3]) : "r"(a[0]), "r"(a[1]), "r"(a[2]), "r"(a[3]), "r"(b0), "r"(b1));
}
DI void mma16816z(float* d, const uint32_t* a, uint32_t b0, uint32_t b1) {
  asm volatile("mma.sync.aligned.m16n8k16.row.col.f32.bf16.bf16.f32 {%0,%1,%2,%3}, {%4,%5,%6,%7}, {%8,%9}, {%10,%10,%10,%10};"
               : "=f"(d[0]), "=f"(d[1]), "=f"(d[2]), "=f"(d[3]) : "r"(a[0]), "r"(a[1]), "r"(a[2]), "r"(a[3]), "r"(b0), "r"(b1), "f"(0.f));
}
DI void mma1688z(float* d, uint32_t a0, uint32_t a1, uint32_t b0) {
  asm volatile("mma.sync.aligned.m16n8k8.row.col.f32.bf16.bf16.f32 {%0,%1,%2,%3}, {%4,%5}, {%6}, {%7,%7,%7,%7};"
               : "=f"(d[0]), "=f"(d[1]), "=f"(d[2]), "=f"(d[3]) : "r"(a0), "r"(a1), "r"(b0), "f"(0.f));
}
DI void mma1688(float* d, uint32_t a0, uint32_t a1, uint32_t b0) {
  asm volatile("mma.sync.aligned.m16n8k8.row.col.f32.bf16.bf16.f32 {%0,%1,%2,%3}, {%4,%5}, {%6}, {%0,%1,%2,%3};"
               : "+f"(d[0]), "+f"(d[1]), "+f"(d[2]), "+f"(d[3]) : "r"(a0), "r"(a1), "r"(b0));
}
DI void ldsm2t(uint32_t* r, uint32_t a) {
  asm volatile("ldmatrix.sync.aligned.m8n8.x2.trans.shared.b16 {%0,%1}, [%2];" : "=r"(r[0]), "=r"(r[1]) : "r"(a) : "memory");
}
DI uint32_t add_bf16(uint32_t a, uint32_t b) { uint32_t r; asm("add.rn.bf16x2 %0, %1, %2;" : "=r"(r) : "r"(a), "r"(b)); return r; }
DI uint32_t mul_bf16(uint32_t a, uint32_t b) { uint32_t r; asm("mul.rn.bf16x2 %0, %1, %2;" : "=r"(r) : "r"(a), "r"(b)); return r; }
DI uint64_t make_desc(uint32_t addr, uint32_t lbo, uint32_t sbo, uint32_t swz) {
  return (uint64_t)((addr & 0x3FFFF) >> 4) | ((uint64_t)(lbo >> 4) << 16) | ((uint64_t)(sbo >> 4) << 32) | ((uint64_t)swz << 62);
}
DI uint64_t desc_at(uint32_t a16, uint32_t lbo, uint32_t sbo, uint32_t swz) {
  uint64_t d; asm("mov.b64 %0, {%1, %2};" : "=l"(d) : "r"(a16 + ((lbo >> 4) << 16)), "r"((sbo >> 4) | (swz << 30)));
  return d;
}
#define WG_FENCE() asm volatile("wgmma.fence.sync.aligned;" ::: "memory")
#define WG_COMMIT() asm volatile("wgmma.commit_group.sync.aligned;" ::: "memory")
#define WG_WAIT(n) asm volatile("wgmma.wait_group.sync.aligned %0;" :: "n"(n) : "memory")
#define ACC8(d, o) "+f"(d[o]), "+f"(d[o + 1]), "+f"(d[o + 2]), "+f"(d[o + 3]), "+f"(d[o + 4]), "+f"(d[o + 5]), "+f"(d[o + 6]), "+f"(d[o + 7])
DI void wgmma_n32_rs(float* d, uint32_t a0, uint32_t a1, uint32_t a2, uint32_t a3, uint64_t db, int acc) {
  asm volatile("{\n.reg .pred p;\nsetp.ne.b32 p, %21, 0;\n"
               "wgmma.mma_async.sync.aligned.m64n32k16.f32.bf16.bf16 {%0,%1,%2,%3,%4,%5,%6,%7,%8,%9,%10,%11,%12,%13,%14,%15}, "
               "{%16,%17,%18,%19}, %20, p, 1, 1, 0;\n}\n"
               : ACC8(d, 0), ACC8(d, 8) : "r"(a0), "r"(a1), "r"(a2), "r"(a3), "l"(db), "r"(acc));
}
template <int TA>
DI void wgmma_n32_ss(float* d, uint64_t da, uint64_t db, int acc) {
  asm volatile("{\n.reg .pred p;\nsetp.ne.b32 p, %18, 0;\n"
               "wgmma.mma_async.sync.aligned.m64n32k16.f32.bf16.bf16 {%0,%1,%2,%3,%4,%5,%6,%7,%8,%9,%10,%11,%12,%13,%14,%15}, "
               "%16, %17, p, 1, 1, %19, 1;\n}\n"
               : ACC8(d, 0), ACC8(d, 8) : "l"(da), "l"(db), "r"(acc), "n"(TA));
}
DI void tma_load(uint32_t dst, const CUtensorMap* m, int c0, int c1, uint32_t mb) {
  asm volatile("cp.async.bulk.tensor.2d.shared::cluster.global.mbarrier::complete_tx::bytes [%0], [%1, {%3, %4}], [%2];"
               :: "r"(dst), "l"(m), "r"(mb), "r"(c0), "r"(c1) : "memory");
}
DI void tma_load3(uint32_t dst, const CUtensorMap* m, int row, uint32_t mb) {
  asm volatile("cp.async.bulk.tensor.3d.shared::cluster.global.mbarrier::complete_tx::bytes [%0], [%1, {%3, %4, %3}], [%2];"
               :: "r"(dst), "l"(m), "r"(mb), "r"(0), "r"(row) : "memory");
}
DI bool elect_one() {
  uint32_t p;
  asm volatile("{\n.reg .pred p;\nelect.sync _|p, 0xffffffff;\nselp.u32 %0, 1, 0, p;\n}" : "=r"(p));
  return p;
}
DI void bulk_s2s(uint32_t dst, uint32_t src, uint32_t bytes, uint32_t mb) {
  asm volatile("cp.async.bulk.shared::cluster.shared::cta.mbarrier::complete_tx::bytes [%0], [%1], %2, [%3];"
               :: "r"(dst), "r"(src), "r"(bytes), "r"(mb) : "memory");
}
DI void tma_prefetch(const CUtensorMap* m, int c0, int c1) {
  asm volatile("cp.async.bulk.prefetch.tensor.2d.L2.global.tile [%0, {%1, %2}];" :: "l"(m), "r"(c0), "r"(c1) : "memory");
}
DI void tma_store(const CUtensorMap* m, uint32_t src, int c0, int c1) {
  asm volatile("cp.async.bulk.tensor.2d.global.shared::cta.bulk_group [%0, {%2, %3}], [%1];" :: "l"(m), "r"(src), "r"(c0), "r"(c1) : "memory");
}
DI uint4 ldg_relaxed(const void* p) {
  uint4 v;
  asm volatile("ld.relaxed.gpu.global.v4.b32 {%0,%1,%2,%3}, [%4];" : "=r"(v.x), "=r"(v.y), "=r"(v.z), "=r"(v.w) : "l"(p) : "memory");
  return v;
}
DI void stg_relaxed(void* p, uint32_t x, uint32_t y, uint32_t z, uint32_t w) {
  asm volatile("st.relaxed.gpu.global.v4.b32 [%0], {%1,%2,%3,%4};" :: "l"(p), "r"(x), "r"(y), "r"(z), "r"(w) : "memory");
}
DI void red_f16x8(void* p, uint32_t x, uint32_t y, uint32_t z, uint32_t w) {
  asm volatile("red.relaxed.gpu.global.add.noftz.v4.f16x2 [%0], {%1,%2,%3,%4};" :: "l"(p), "r"(x), "r"(y), "r"(z), "r"(w) : "memory");
}
DI void sq_acc(uint32_t& a, uint32_t x) { asm("fma.rn.bf16x2 %0, %1, %1, %0;" : "+r"(a) : "r"(x)); }
DI __half2 amax4(__half2 h, const uint32_t* v) {
  h = __hmax2_nan(__hmax2_nan(h, __habs2(*(const __half2*)&v[0])), __habs2(*(const __half2*)&v[1]));
  return __hmax2_nan(__hmax2_nan(h, __habs2(*(const __half2*)&v[2])), __habs2(*(const __half2*)&v[3]));
}
DI uint32_t wexp(__half2 h) { const uint32_t u = *(const uint32_t*)&h; return __reduce_max_sync(0xffffffffu, max((u >> 16) & 0x7fffu, u & 0x7fffu)) >> 7; }
DI float max10(const float* a) {
  return fmaxf(fmaxf(fmaxf(fmaxf(a[0], a[1]), fmaxf(a[2], a[3])), fmaxf(fmaxf(a[4], a[5]), fmaxf(a[6], a[7]))), fmaxf(a[8], a[9]));
}
DI float quad_max(float m) {
  return fmaxf(fmaxf(m, __shfl_xor_sync(0xffffffffu, m, 1)), fmaxf(__shfl_xor_sync(0xffffffffu, m, 2), __shfl_xor_sync(0xffffffffu, m, 3)));
}
DI float warp_sum(float v) {
#pragma unroll
  for (int o = 16; o; o >>= 1) v += __shfl_xor_sync(0xffffffffu, v, o);
  return v;
}

constexpr int SM_WO3 = 0;
constexpr int SM_X = 16384;
constexpr int XT = 36864;
constexpr int SM_EXP = 126976;
constexpr int SEGB = 10240;
constexpr int SM_BLK = SM_EXP + 8192;
constexpr int SM_VC = SM_BLK + 4 * SEGB;
constexpr int SM_PART = SM_VC + 16384;
constexpr int SM_QM = SM_PART + 4096;
constexpr int SM_E = SM_QM + 1024;
constexpr int SM_VM = SM_E + 1536;
constexpr int SM_OB = SM_VM + 2048;
constexpr int SM_FB = SM_OB + 2048;
constexpr int SM_STAGE = SM_X + XT;
constexpr int SM_MISC = 210944;
constexpr int SM_WOST = 212992;
constexpr int SM_MEM = SM_WOST;
constexpr int SM_MAX = SM_MEM + 11264;
#define MEM_BLK(q) ((q) / 3 * 4096 + (q) % 3 * 1024)
constexpr int SM_TOTAL = 229376;
constexpr int MB_W = SM_MISC;
constexpr int MB_WO = SM_MISC + 24;
constexpr int MB_WO3 = SM_MISC + 32;
constexpr int MB_X = SM_MISC + 40;
constexpr int MB_S = SM_MISC + 64;
constexpr int MB_F = SM_MISC + 72;
constexpr int MB_VX = SM_MISC + 80;
constexpr int SC_FPAR = SM_MISC + 136;
constexpr int SC_DEAD = SM_MISC + 96;
constexpr int SC_UNSC = SM_MISC + 112;
constexpr int SC_EPOCH = SM_MISC + 128;
constexpr int SC_EXPW = SM_MISC + 132;
constexpr int SC_ONES = SM_MISC + 144;
constexpr int SC_SS = SM_MISC + 160;
constexpr int SC_LAT = SM_MISC + 224;
constexpr int MB_T = SM_MISC + 232;
constexpr int T_SX = SM_X + XT;
constexpr int T_OB = SM_X + 2 * XT;
constexpr int T_WA = T_OB + 16384;
constexpr int T_OA = T_WA + 9216;
constexpr int T_G = T_OA + 4096;
constexpr int T_P = T_G + 512;
constexpr int T_UN = T_G + 256;
constexpr int T_RED = 131072;
constexpr int SC_XMAX = SM_MISC + 256;
constexpr int SC_PROF = 229376;

constexpr float SM_SCALE = 0.08838834764831845f;
constexpr float LOG2E = 1.4426950408889634f;
constexpr float E_LIM = 20.f;

template <bool B> struct BoolC { static constexpr bool value = B; };
struct RMaps { CUtensorMap x, wq, wk, wv, wo, woa, oa; unsigned char* red; bf16* out; uint32_t poll; };

DI uint32_t latest_hint(uint32_t h, uint32_t d, int s) {
  const uint32_t x = (((h | 0xc0c0c0c0u) - ((d >> 5) & 63) * 0x01010101u) & 0x3f3f3f3fu) | ((h ^ (((s >> 2) + 1) & 3) * 0x40404040u) & 0xc0c0c0c0u);
  const uint32_t y = __vmaxu2(x & 0x00ff00ffu, (x >> 8) & 0x00ff00ffu);
  return __reduce_max_sync(0xffffffffu, max(y & 0xffffu, y >> 16));
}
DI uint32_t near_half(uint32_t sb) {
  uint32_t a, b; lds64(sb + SC_LAT, a, b);
  return a > b;
}

template <int RT, int K0, int K1, bool D32 = false, int BAR = 0, int KB = 18>
DI void xproj(float* acc, const uint32_t (&wa)[2][18][4], uint64_t xd) {
  if (XP & 1) return;
  WG_FENCE();
#pragma unroll
  for (int k = K0; k < ((XP & 128) ? K0 + 1 : K1); k++)
  {
    uint64_t d = xd + (uint64_t)(((k >> 1) * 4096 + (k & 1) * 32) >> 4);
    if (D32) asm("mov.b64 %0, {%1, %2};" : "=l"(d) : "r"((uint32_t)xd + (((k >> 1) * 4096 + (k & 1) * 32) >> 4)), "r"((uint32_t)(xd >> 32)));
    wgmma_n32_rs(acc, wa[RT][k][0], wa[RT][k][1], wa[RT][k][2], wa[RT][k][3], d, k != 0);
    if (BAR && k == KB - 1 && KB < 18) bar_arrive(BAR, 256);
  }
  WG_COMMIT();
}

DI void seg_store(int seg, uint32_t sb, uint32_t off, uint32_t bytes) {
  asm volatile("cp.async.bulk.global.shared::cta.bulk_group [%0], [%1], %2;"
               :: "l"(g_seg + ((size_t)(seg % NRING) * 96 + blockIdx.x) * SEGB + off), "r"(sb + SM_BLK + (seg & 3) * SEGB + off), "r"(bytes) : "memory");
  asm volatile("cp.async.bulk.commit_group;" ::: "memory");
}
DI void seg_publish(int seg) {
  asm volatile("cp.async.bulk.wait_group 0;" ::: "memory");
  asm volatile("red.relaxed.gpu.global.add.u32 [%0], 1;" :: "l"(&g_scnt[(seg * 32 + blockIdx.x / 3) * 8]) : "memory");
  SSTAMP(10, seg);
}

#define NAP 64
DI uint32_t movm(uint32_t x) { uint32_t r; asm volatile("movmatrix.sync.aligned.m8n8.trans.b16 %0, %1;" : "=r"(r) : "r"(x)); return r; }
DI bool wait_count(const unsigned* p, unsigned target, bool nap = true) {
  int n = 0;
  unsigned v;
  while (true) {
    asm volatile("ld.acquire.gpu.global.b32 %0, [%1];" : "=r"(v) : "l"(p) : "memory");
    if ((int)(v - target) >= 0 || ++n > SPIN_LIMIT) break;
    if (nap) __nanosleep(NAP);
  }
  return n;
}
#define PACE 1200
#define PORD 0
DI void load_weights(uint32_t sb, const RMaps& tm, uint32_t rank, int c) {
  const int h = blockIdx.x / 3;
  if (c < 3) {
    mbar_expect(sb + MB_W + 8 * c, 49152);
    tma_load(sb + SM_STAGE + c * 49152, rank < 2 ? &tm.wk : &tm.wv, h * DH + (rank == 1 ? 64 : 0), c * 192, sb + MB_W + 8 * c);
    tma_load(sb + SM_STAGE + c * 49152 + 24576, rank < 2 ? &tm.wq : &tm.wv, h * DH + (rank == 0 ? 0 : 64), c * 192, sb + MB_W + 8 * c);
  } else {
    tma_prefetch(&tm.wo, rank * 192, h * DH);
    mbar_expect(sb + MB_WO, 16384);
    mbar_expect(sb + MB_WO3, 32768);
    tma_load(sb + SM_WOST, &tm.wo, rank * 192 + 64, h * DH, sb + MB_WO3);
    tma_load(sb + SM_WO3, &tm.wo, rank * 192 + 128, h * DH, sb + MB_WO3);
  }
}

DI void tail_attention(const uint32_t sb, const uint32_t rank, const int w, const int lane, const int sg, const int bar) {
  const int m = lane >> 3, g = lane >> 2, t = lane & 3;
  const uint32_t l16 = sb + lane * 16, src = l16 + T_SX + sg * 10240 + w * 1280;
  if (rank < 2) {
    const uint32_t base = l16 + SM_BLK + (2 + sg) * SEGB, dst = src + rank * 5120;
    uint32_t qb[2][4];
    ldsm4t(qb[0], base + w * 1024); ldsm4t(qb[1], base + w * 1024 + 512);
#pragma unroll
    for (int j = 0; j < 3; j++) {
      uint32_t kb[4][4];
      float c[4][4];
      const uint32_t ka = base + 4096 + j * 2048 + (m & 1) * (j == 2 ? 128 : 896) - (m >> 1) * 128;
#pragma unroll
      for (int k = 0; k < 4; k += j == 2 ? 2 : 1) ldsm4t(kb[k], ka + k * 256);
      mma16816z(c[0], kb[0], qb[0][0], qb[0][1]); mma16816z(c[1], kb[j == 2 ? 0 : 1], qb[0][2], qb[0][3]);
      mma16816z(c[2], kb[2], qb[1][0], qb[1][1]); mma16816z(c[3], kb[j == 2 ? 2 : 3], qb[1][2], qb[1][3]);
      uint32_t r[4];
#pragma unroll
      for (int i = 0; i < (j == 2 ? 2 : 4); i++) r[i] = __float_as_uint((c[0][i] + c[1][j == 2 ? i + 2 : i]) + (c[2][i] + c[3][j == 2 ? i + 2 : i]));
#pragma unroll
      for (int d = 0; d < 2; d++) {
        const uint32_t to = d ? 2 : rank ^ 1, mb = mapa(sb + MB_T + 8 + 8 * sg, to);
        if (j < 2) st_async4(mapa(dst + j * 512, to), r[0], r[1], r[2], r[3], mb);
        else st_async2(mapa(dst + 1024 - lane * 8, to), r[0], r[1], mb);
      }
      if (j < 2) sts128(dst + j * 512, r[0], r[1], r[2], r[3]); else sts64(dst + 1024 - lane * 8, r[0], r[1]);
    }
  }
  TSTAMP(50 + 2 * sg);
  uint32_t vx[4][4], vm[4];
  const uint32_t va = l16 + (rank < 2 ? SM_VC + sg * 8192 : SM_BLK + (2 + sg) * SEGB) + w * 1024 + (m & 1) * 384 - (m >> 1) * 128;
#pragma unroll
  for (int i = 0; i < 4; i++) ldsm4(vx[i], va + (i & 1) * 4096 + (i >> 1) * 256);
  if (sg && rank < 2) mbar_wait(sb + MB_T, 0);
  lds128(l16 + (sg ? SM_FB : SM_VM) + w * 512, vm);
  float a[10], b[10];
  mbar_wait(sb + MB_T + 8 + 8 * sg, 0);
  TSTAMP(58 + 2 * sg);
  lds128f(src, a); lds128f(src + 512, a + 4); lds64f(src + 1024 - lane * 8, a + 8);
  lds128f(src + 5120, b); lds128f(src + 5632, b + 4); lds64f(src + 6144 - lane * 8, b + 8);
#pragma unroll
  for (int i = 0; i < 10; i++) {
    a[i] = (a[i] + b[i]) * (SM_SCALE * LOG2E);
    if (i < 8 && (i >> 1) * 8 + g > w * 8 + 2 * t + (i & 1)) a[i] = -1.0e9f * LOG2E;
  }
  float m0 = fmaxf(fmaxf(fmaxf(a[0], a[2]), fmaxf(a[4], a[6])), a[8]), m1 = fmaxf(fmaxf(fmaxf(a[1], a[3]), fmaxf(a[5], a[7])), a[9]);
#pragma unroll
  for (int o = 4; o < 32; o <<= 1) { m0 = fmaxf(m0, __shfl_xor_sync(0xffffffffu, m0, o)); m1 = fmaxf(m1, __shfl_xor_sync(0xffffffffu, m1, o)); }
#pragma unroll
  for (int i = 0; i < 10; i++) a[i] = ex2(a[i] - (i & 1 ? m1 : m0));
  float s0 = ((a[0] + a[2]) + (a[4] + a[6])) + a[8], s1 = ((a[1] + a[3]) + (a[5] + a[7])) + a[9];
#pragma unroll
  for (int o = 4; o < 32; o <<= 1) { s0 += __shfl_xor_sync(0xffffffffu, s0, o); s1 += __shfl_xor_sync(0xffffffffu, s1, o); }
  s0 = rcp(s0); s1 = rcp(s1);
#pragma unroll
  for (int i = 0; i < 5; i++) sts32(sb + T_P + sg * 2560 + w * 640 + i * 128 + lane * 4, pack_bf16(a[2 * i] * s0, a[2 * i + 1] * s1));
  mbar_wait(sb + MB_WO, 1);
  bar_sync(bar, 128);
  TSTAMP(59 + 2 * sg);
#pragma unroll
  for (int j = 0; j < 4; j++) {
    uint32_t p[5];
    float o0[4], o1[4], f[2];
    lds64f(sb + T_G + sg * 128 + j * 32 + t * 8, f);
    f[0] = 1.f - f[0]; f[1] = 1.f - f[1];
    ldsm4t(p, l16 + T_P + sg * 2560 + j * 640);
    asm volatile("ldmatrix.sync.aligned.m8n8.x1.trans.shared.b16 {%0}, [%1];" : "=r"(p[4]) : "r"(l16 + T_P + sg * 2560 + j * 640 + 512) : "memory");
    mma16816z(o0, vx[0], p[0], p[1]); mma16816z(o1, vx[1], p[0], p[1]);
    mma16816(o0, vx[2], p[2], p[3]); mma16816(o1, vx[3], p[2], p[3]);
    mma1688(o0, vm[0], vm[1], p[4]); mma1688(o1, vm[2], vm[3], p[4]);
    stsm4(l16 + T_OB + sg * 8192 + j * 2048 + w * 512, pack_bf16(o0[0] * f[0], o0[1] * f[1]), pack_bf16(o0[2] * f[0], o0[3] * f[1]),
          pack_bf16(o1[0] * f[0], o1[1] * f[1]), pack_bf16(o1[2] * f[0], o1[3] * f[1]));
  }
}

DI void proj_role(const uint32_t sb, const RMaps& tm, const uint32_t rank, const int wg, const int w, const int lane) {
  const bool qk = rank < 2;
  uint32_t wa[2][18][4];
  {
    const int rr = (lane & 7) + ((lane >> 4) << 3);
    const uint32_t col = ((2 * w + ((lane >> 3) & 1)) ^ (lane & 7)) << 4;
    float ss = 0.f;
#pragma unroll
    for (int c = 0; c < 3; c++) {
      mbar_wait(sb + MB_W + 8 * c, 0);
      if (threadIdx.x == 0) SSTAMP(11, c);
#pragma unroll
      for (int rt = 0; rt < 2; rt++)
#pragma unroll
        for (int k = 0; k < 6; k++)
          ldsm4t(wa[rt][c * 6 + k], sb + SM_STAGE + c * 49152 + (rt ^ wg) * 24576 + (64 * (k >> 1) + 32 * wg + 16 * (k & 1) + rr) * 128 + col);
      if (c < 2) {
        fence_async();
        bar_sync(3, 256);
        if (threadIdx.x == 0) {
          if (c == 0) tma_load3(sb + SM_X + XT, &tm.x, 32, sb + MB_X + 8);
          else { tma_load(sb + SM_X + 2 * XT, &tm.wo, rank * 192, (blockIdx.x / 3) * DH, sb + MB_WO); SSTAMP(11, 11); }
        }
        __syncwarp();
      }
      uint32_t q[4] = {0, 0, 0, 0};
#pragma unroll
      for (int rt = 0; rt < 2; rt++)
#pragma unroll
        for (int k = 0; k < 6; k++)
#pragma unroll
          for (int i = 0; i < 4; i++) sq_acc(q[i], wa[rt][c * 6 + k][i]);
#pragma unroll
      for (int i = 0; i < 4; i++) ss += bf_lo(q[i]) + bf_hi(q[i]);
    }
    ss = warp_sum(ss);
    fence_async();
    cluster_arrive();
    if (lane == 0) sts32(sb + SC_SS + 4 * (wg * 4 + w), qk ? 0 : __float_as_uint(ss));
    bar_arrive(11, 384);
  }
  STAMP(1);
  mbar_wait(sb + MB_X, 0);
  STAMP(2);

  uint32_t t16 = sb + (w * 32 + lane) * 16;
  uint32_t mem_a = sb + SM_MEM + wg * 512 + lane * 16;
  uint32_t fin_a = sb + (lane & 7) * 16 + SM_BLK + (qk ? (wg ^ 1) * 4096 + w * 256 + (lane & 8) * 16 + (lane & 16) * 64
                                              : wg * 4096 + w * 1024 + (lane & 8) * 64 + (lane & 16) * 8);
  PIN(t16); PIN(mem_a); PIN(fin_a);
  const uint32_t fence_reg = mem_a;
  const uint32_t fin2 = qk ? 2048 : 256;
  float acc[16];
  const uint64_t xd0 = make_desc(sb + SM_X + wg * 64, 16, 1024, 1);
  auto do_export = [&]() {
    WG_WAIT(0);
    uint32_t q[8];
#pragma unroll
    for (int j = 0; j < 8; j++) q[j] = pack_bf16(acc[2 * j], acc[2 * j + 1]);
    sts128(t16 + SM_EXP + wg * 4096, q[0], q[1], q[2], q[3]);
    sts128(t16 + SM_EXP + wg * 4096 + 2048, q[4], q[5], q[6], q[7]);
    if (RET) asm volatile("{\n.reg .pred p;\nsetp.eq.u32 p, %2, 0;\n@p add.u32 %0, %0, 1;\n@p add.u32 %1, %1, 1;\nsetp.eq.and.u32 p, %0, %1, p;\n@p exit;\n}"
                          : "+r"(q[3]), "+r"(q[7]) : "r"(t16) : "memory");
  };
  uint32_t o[8];
  auto import = [&]() { lds128(t16 + SM_EXP + (wg ^ 1) * 4096, o); lds128(t16 + SM_EXP + (wg ^ 1) * 4096 + 2048, o + 4); };
  auto finish = [&](int seg) {
    const uint32_t a = fin_a + (seg & 3) * SEGB;
    WG_WAIT(0);
#pragma unroll
    for (int i = 0; i < 8; i++) o[i] = FIN16 ? add_bf16(pack_bf16(acc[2 * i], acc[2 * i + 1]), o[i]) : pack_bf16(acc[2 * i] + bf_lo(o[i]), acc[2 * i + 1] + bf_hi(o[i]));
    stsm4(a, o[0], o[1], o[2], o[3]);
    stsm4(a + fin2, o[4], o[5], o[6], o[7]);
  };
  auto send_v = [&](int seg, int dst) {
    fence_async();
    if (seg < NSEG && !(XP & 2) && elect_one())
      bulk_s2s(mapa(sb + SM_VC + (seg & 1) * 8192, dst), sb + SM_BLK + (seg & 3) * SEGB, 8192, mapa(sb + MB_VX + (seg & 1) * 8, dst));
    __syncwarp();
  };
  auto wait_v = [&](int seg) {
    if (seg < NSEG && !(XP & 2)) {
      mbar_wait(sb + MB_VX + (seg & 1) * 8, (seg >> 1) & 1);
      if (elect_one()) mbar_expect(sb + MB_VX + (seg & 1) * 8, 8192);
      __syncwarp();
    }
  };
  bar_sync(3, 256);
  xproj<1, 0, 18>(acc, wa, xd0);
  do_export();
  SCHED_FENCE(11);
  xproj<0, 0, 18>(acc, wa, xd0);
  bar_sync(3, 256);
  if (threadIdx.x == 0) SSTAMP(11, 12);
  cluster_wait();
  if (threadIdx.x == 0) SSTAMP(11, 13);
  mbar_wait(sb + MB_X + 8, 0);
  import();
  finish(0);
  SCHED_FENCE(12);
  bar_sync(3, 256);
  uint64_t dA = xd0 + (XT >> 4);
  xproj<1, 0, 18>(acc, wa, dA);
  if (!qk && wg == 0 && w < 2) send_v(0, w);
  do_export();
  if (qk && wg == 0 && w == 0) wait_v(0);
  bar_arrive(13, 384);
  if (!qk) {
    SCHED_FENCE(15);
    xproj<0, 0, 18>(acc, wa, dA);
    if (threadIdx.x == 0 && !(XP & 8)) { mbar_expect(sb + MB_X, XT); tma_load3(sb + SM_X, &tm.x, 96, sb + MB_X); }
    bar_sync(3, 256);
    mbar_wait(sb + MB_X + 16, 0);
    import();
    finish(1);
    SCHED_FENCE(16);
    bar_sync(3, 256);
    dA += XT >> 4;
    xproj<1, 0, 18>(acc, wa, dA);
    if (wg == 0 && ((w == 0 && VS0) || (w == 1 && VS1))) send_v(1, w);
    do_export();
  }
  if (threadIdx.x == 0) SSTAMP(11, 14);
  bar_sync(0, 384);
  const int ro = __shfl_sync(0xffffffffu, near_half(sb) ^ wg, 0);
  STAMP(5);
  const uint32_t always = __shfl_sync(0xffffffffu, lds32(sb + SC_DEAD + 12), 0);
  const int ah = qk ? 1 : 2;
  int b2 = qk ? 2 : 0;
  int s = 0;
  uint32_t hint_lo = (uint32_t)(uint64_t)tm.red + HINT_OFF + blockIdx.x + (lane & 1) * 4096 + (lane >> 1) * 16384;
  PIN(hint_lo);
  auto post_hint = [&]() {
    asm volatile("{\n.reg .pred p;\n.reg .b64 a;\n.reg .u32 t;\nsetp.lt.u32 p, %0, %1;\nmov.b64 a, {%2, %3};\nmov.u32 t, %%globaltimer_lo;\n"
                 "bfe.u32 t, t, 5, 6;\nor.b32 t, t, %4;\n@p st.relaxed.gpu.global.u8 [a], t;\n}"
                 :: "r"(t16), "r"(sb + 128), "r"(hint_lo + RED_SLOT(s)), "r"((uint32_t)((uint64_t)tm.red >> 32)), "r"(((s >> 2) + 1) << 6) : "memory");
  };
  auto memproj = [&](auto second, int id, float u0, float u1, float* r) {
    constexpr bool R1 = decltype(second)::value;
    uint32_t b[NUP][4], b0[4];
    SCHED_FENCE(id);
    bar_sync(R1 ? 2 : 1, 256);
    PROF(0);
    ldsm4t(b0, mem_a);
#pragma unroll
    for (int q = 0; q < NUP; q++) {
      if (R1 && q == 2) {
        bar_sync(11, 256);
        SCHED_FENCE(id + 1);
      }
      ldsm4t(b[q], mem_a + MEM_BLK(q + 1));
    }
    mma16816z(&acc[0], wa[0][0], b0[0], b0[1]);
    mma16816z(&acc[4], wa[1][0], b0[0], b0[1]);
    mma16816z(&acc[8], wa[0][1], b0[2], b0[3]);
    mma16816z(&acc[12], wa[1][1], b0[2], b0[3]);
#pragma unroll
    for (int q = 1; q < 9; q++) {
      uint32_t* const c = b[(q - 1) % NUP];
      mma16816(&acc[0], wa[0][2 * q], c[0], c[1]);
      mma16816(&acc[4], wa[1][2 * q], c[0], c[1]);
      mma16816(&acc[8], wa[0][2 * q + 1], c[2], c[3]);
      mma16816(&acc[12], wa[1][2 * q + 1], c[2], c[3]);
      if (R1 && q + NUP == B3Q) bar_sync(3, 256);
      if (q + NUP < 9) ldsm4t_in(c, mem_a + MEM_BLK(q + NUP), always);
      else if (R1 && q + NUP < 11) lds128_in(c, t16 + SM_PART + (10 - q - NUP) * 2048, always);
      else if (!R1 && GATE && q == GATE) { bar_arrive(11, 256); lds128_in(c, sb + SC_DEAD, always); u0 = u1 = __uint_as_float(c[3]); }
    }
#pragma unroll
    for (int i = 0; i < 8; i++) {
      const float u = i < 4 ? u0 : u1;
      r[i] = R1 ? fmaf(acc[8 + i], u, (acc[i] + __uint_as_float(b[(8 + i / 4) % NUP][i & 3])) * u) : (GATE ? fmaf(acc[i], u, acc[8 + i]) : acc[i] + acc[8 + i]);
    }
  };
  if (ro == 0) {
    auto set_scale = [&]() {
      uint32_t m[8];
      lds128(t16 + SM_MAX - 512, m); lds128(t16 + SM_MAX, m + 4);
      const int em = (wexp(amax4(amax4(*(const __half2*)&m[0], m), m + 4)) >> 3) + (int)(lds32(sb + SC_UNSC + (s & 1) * 8) >> 23) - 15;
      const int ex = max(s ? em : 0, (int)lds32(sb + SC_XMAX + 4 * s)) - 127 + (int)lds32(sb + SC_EXPW);
      sts32(sb + SC_UNSC + (~s & 1) * 8, (127 + min(max(ex, -120), 120)) << 23);
    };
#pragma unroll 1
    while (true) {
      if (s == 8) STAMP(6);
      float r[8];
      memproj(BoolC<false>(), 30, 0.f, 0.f, r);
      sts128(t16 + SM_PART, __float_as_uint(r[0]), __float_as_uint(r[1]), __float_as_uint(r[2]), __float_as_uint(r[3]));
      sts128(t16 + SM_PART + 2048, __float_as_uint(r[4]), __float_as_uint(r[5]), __float_as_uint(r[6]), __float_as_uint(r[7]));
      bar_arrive(3, 256);
      PROF(1);
      bar_sync(9, 256);
      if (s == NSEG - 1) break;
      post_hint();
      if (w == 1) {
        set_scale();
        __syncwarp();
        if (elect_one()) mbar_arrive(sb + MB_S);
      }
      SCHED_FENCE(9);
      bar_sync(5, qk ? N5 : 256);
      PROF(2);
      import();
      xproj<0, 0, NII, (DD & 1) != 0>(acc, wa, dA);
      if (NII < 18) {
        if (qk) bar_sync(7, 384);
        xproj<0, NII, 18>(acc, wa, dA);
        if (!qk) bar_sync(7, 384);
      } else {
        if (F10) WG_WAIT(0);
        bar_sync(10, 256);
        if (F10) SCHED_FENCE(17);
      }
      dA += (int64_t)(b2 ? XT >> 4 : -(XT >> 3));
      finish(s + ah);
      if (qk || !VLATE(w)) bar_arrive(13, 384);
      PROF(6);
      SCHED_FENCE(14);
      bar_sync(12, 256);
      PROF(7);
      xproj<1, 0, 18, (DD & 2) != 0, 14, N14>(acc, wa, dA);
      if (N14 == 18) bar_arrive(14, 256);
      b2 = b2 == 2 ? 0 : b2 + 1;
      s++;
      if (!qk && VLATE(w)) { bar_sync(13, 384); send_v(s + 1, w); }
      PROFP(8);
      do_export();
      s--; RSTAMP(6); s++;
      PROFP(3);
    }
    if (!qk) bar_arrive(5, 256);
    if (w == 0 && elect_one()) {
      const uint32_t h18 = blockIdx.x / 3 * 18;
      mbar_expect(sb + MB_WO, 9216 + 4096 + 256);
      asm volatile("cp.async.bulk.shared::cluster.global.mbarrier::complete_tx::bytes [%0], [%1], 256, [%2];"
                   :: "r"(sb + T_G), "l"(g_gate + NAUXSEG * 32), "r"(sb + MB_WO) : "memory");
      tma_load(sb + T_OA, &tm.oa, 4096 + (h18 & ~7), NAUXSEG * 32, sb + MB_WO);
#pragma unroll 1
      for (int j = 0; j < 3; j++) tma_load(sb + T_WA + j * 3072, &tm.woa, rank * 192 + j * 64, h18, sb + MB_WO);
    }
    if (w == 1) {
      set_scale();
      __syncwarp();
      const int ea = (int)ldg_relaxed32(&g_amax[0]) + (int)ldg_relaxed32(&g_amax[16]) - 254 + 2 + 10 - 15;
      sts32(sb + T_UN + (lane & 1) * 4, (128 + max(min(ea, 120), (int)(lds32(sb + SC_UNSC + 8 - (lane & 1) * 8) >> 23) - 127)) << 23);
    }
    bar_arrive(8, 256);
  } else {
    uint32_t r0;
    float un;
    auto prepare = [&]() {
      un = __uint_as_float(lds32(sb + SC_UNSC + (s & 1) * 8));
      r0 = qk ? (t16 & ~256u) - w * 256 + (((t16 >> 8) ^ wg) & 1 ? SM_QM : SM_BLK + 8192 + (s & 3) * SEGB) : mapa(t16 + (s < NSEG - 1 ? SM_VM : SM_FB), 0);
      PIN(r0); PIN(un);
    };
    prepare();
#pragma unroll 1
    while (true) {
      if (s == 8) STAMP(6);
      float r[8];
      if (qk) {
        const float u0 = wg ? un * (SM_SCALE * LOG2E) : un, u1 = wg ? un : un * (SM_SCALE * LOG2E);
        memproj(BoolC<true>(), 32, u0, u1, r);
        stsm4(r0, pack_bf16(r[0], r[1]), pack_bf16(r[2], r[3]), pack_bf16(r[4], r[5]), pack_bf16(r[6], r[7]));
        bar_arrive(4, 256);
      } else {
        const uint32_t mb = sb + (s < NSEG - 1 ? MB_S : MB_T), r1 = r0 + (1 << 24);
        memproj(BoolC<true>(), 34, un, un, r);
        const uint32_t p0 = pack_bf16(r[0], r[1]), p1 = pack_bf16(r[2], r[3]), p2 = pack_bf16(r[4], r[5]), p3 = pack_bf16(r[6], r[7]);
        const uint32_t v0 = wg ? p2 : p0, v1 = wg ? p3 : p1, v2 = wg ? p0 : p2, v3 = wg ? p1 : p3;
        st_async4(r0, v0, v1, v2, v3, mapa(mb, 0));
        st_async4(r1, v0, v1, v2, v3, mapa(mb, 1));
        bar_arrive(5, 256);
        sts128(r0 + (2 << 24), v0, v1, v2, v3);
        stsm4((t16 & ~256u) - w * 256 + SM_BLK + 8192 + (s & 3) * SEGB + (((t16 >> 8) ^ wg) & 1) * 1024, p0, p1, p2, p3);
        __syncwarp();
        if (elect_one()) mbar_arrive(sb + MB_S);
      }
      if (s == NSEG - 1) break;
      if (!qk) bar_arrive(15, 160);
      PROF(1);
      auto rearm = [&]() { mbar_wait(sb + MB_S, s & 1); if (elect_one()) mbar_expect(sb + MB_S, qk ? 640 + 2048 : 1280); __syncwarp(); };
      if (w == 1) {
        if ((t16 & 384) == 0) stg_relaxed(tm.red + (RED_SLOT(s + 2) + RED_LINE(blockIdx.x)) + (t16 & 112), 0, 0, 0, 0);
      } else if (w == 0) {
        const int tn = s + ah + 1;
        if (RFW) mbar_wait(sb + MB_S, s & 1);
        if (tn + 1 < NSEG && !(XP & 8) && elect_one()) {
          const int b0 = b2 == 2 ? 0 : b2 + 1;
          mbar_expect(sb + MB_X + 8 * b0, XT);
          tma_load3(sb + SM_X + b0 * XT, &tm.x, (tn + 1) * 32, sb + MB_X + 8 * b0);
        }
        if (tn < NSEG && (!(XP & 8) || tn < 3)) mbar_wait(sb + MB_X + 8 * b2, (tn / 3) & 1);
      } else if (w == 2) {
        if (!qk) { if (VS0 == 0) send_v(s + 1, 0); if (VS1 == 0) send_v(s + 1, 1); }
      } else if (qk || !NIC) {
        rearm();
      }
      __syncwarp();
      import();
      PROF(4);
      SCHED_FENCE(10);
      if (NIC) {
        if (qk) bar_sync(7, NII < 18 ? 384 : 256);
        xproj<0, 0, NIC>(acc, wa, dA);
        if (!qk) { if (w == 3) rearm(); bar_sync(7, NII < 18 ? 384 : 256); }
      } else {
        bar_sync(7, NII < 18 ? 384 : 256);
      }
      xproj<0, NIC, 18, (DD & 4) != 0, 12, N12>(acc, wa, dA);
      if (N12 == 18) bar_arrive(12, 256);
      dA += (int64_t)(b2 ? XT >> 4 : -(XT >> 3));
      finish(s + ah);
      if (qk && w == 0) wait_v(s + 1);
      bar_arrive(13, 384);
      PROF(6);
      SCHED_FENCE(13);
      bar_sync(14, 256);
      PROF(7);
      xproj<1, 0, 18, (DD & 8) != 0>(acc, wa, dA);
      b2 = b2 == 2 ? 0 : b2 + 1;
      s++;
      if (HOIST) prepare();
      PROFP(8);
      do_export();
      if (!HOIST) prepare();
      s--; RSTAMP(7); s++;
      PROFP(3);
    }
    TSTAMP(2);
    bar_sync(3, 128);
    tail_attention(sb, rank, w, lane, 1, 3);
    bar_arrive(0, 256);
  }
  STAMP(3);
  if (CSY) cluster_sync();
  STAMP(4);
}

DI void attn_role(const uint32_t sb, unsigned char* smem_raw, const RMaps& tm, const uint32_t RANK, const bf16* __restrict__ x, const bf16* __restrict__ mem0,
                  const int w, const int lane) {
  const int t2 = w * 32 + lane;
  uint32_t wo[8][4], w1[8][4];
  const uint32_t wo_lane = sb + ((lane & 7) + ((lane >> 4) << 3)) * 128 + (((w + 4 * ((lane >> 3) & 1)) ^ (lane & 7)) << 4);
  unsigned char* const g_red = tm.red;
  {
    const uint32_t tag = *(volatile unsigned*)&g_epoch + 1;
    if (w == 0) {
      stg_relaxed(g_red + RED_SLOT(t2 >> 3) + RED_LINE(blockIdx.x) + (t2 & 7) * 16, 0, 0, 0, 0);
      stg_relaxed(g_red + T_RED + blockIdx.x * 1024 + t2 * 16, 0, 0, 0, 0);
      stg_relaxed(g_red + T_RED + blockIdx.x * 1024 + 512 + t2 * 16, 0, 0, 0, 0);
      asm volatile("st.relaxed.gpu.global.u8 [%0], 0;" :: "l"(g_red + RED_SLOT(t2) + HINT_OFF + (t2 & 4) * 1024 + (t2 >> 3) * 16384 + blockIdx.x) : "memory");
    }
    uint4 xv[18];
    uint32_t mv[20];
#pragma unroll
    for (int i = 0; i < 20; i++) mv[i] = i < 18 ? ((const uint32_t*)mem0)[(lane >> 2) * (DM / 2) + (w * 18 + i) * 4 + (lane & 3)] : 0;
#pragma unroll
    for (int i = 0; i < 18; i++) xv[i] = blockIdx.x < NSEG ? ((const uint4*)(x + blockIdx.x * 32 * DM))[t2 + 128 * i] : make_uint4(0, 0, 0, 0);
    bar_sync(0, 384);
    cluster_arrive();
    if (PACE && w == 3) {
      const uint32_t t0 = gtime();
#pragma unroll 1
      for (int c = 1; c < 4; c++) {
        wait_until(t0 + c * PACE);
        if (elect_one()) load_weights(sb, tm, RANK, PORD ? (c == 1 ? 3 : c - 1) : c);
        __syncwarp();
      }
    }
    __half2 hx = __float2half2_rn(0.f);
#pragma unroll
    for (int i = 0; i < 18; i++) hx = amax4(hx, &xv[i].x);
    if (blockIdx.x == 0)
#pragma unroll
      for (int i = 0; i < 5; i++) hx = amax4(hx, &mv[4 * i]);
    sts32(sb + SC_SS + 4 * (12 + w), wexp(hx));
    if (t2 == 0) { sts32(sb + SC_EPOCH, (tag - 1) * NSEG + 2 - NRING); sts32(sb + SC_UNSC, __float_as_uint(1.f)); sts128(sb + SC_DEAD, 0, 0, 0, 0x3f800000u); sts64(sb + SC_FPAR, 0, 0); sts128(sb + SC_ONES, 0x3f803f80u, 0x3f803f80u, 0x3f803f80u, 0x3f803f80u); }
    WSTAMP(27);
    if (w == 0) __threadfence();
    uint32_t q[8] = {0, 0, 0, 0, 0, 0, 0, 0};
    mbar_wait(sb + MB_WO3, 0);
    if (t2 == 0) SSTAMP(11, 3);
#pragma unroll
    for (int k = 0; k < 8; k++) {
      ldsm4t(wo[k], wo_lane + SM_WO3 + k * 2048); ldsm4t(w1[k], wo_lane + SM_WOST + k * 2048);
#pragma unroll
      for (int i = 0; i < 4; i++) { sq_acc(q[i], wo[k][i]); sq_acc(q[i], w1[k][i]); }
    }
    bar_sync(6, 128);
    if (t2 == 0) SSTAMP(11, 7);
#pragma unroll
    for (int k = 0; k < 8; k++) sts128(sb + SM_WO3 + t2 * 16 + k * 2048, wo[k][0], wo[k][1], wo[k][2], wo[k][3]);
#pragma unroll
    for (int i = 0; i < 5; i++) {
      const int j = w * 18 + 4 * i + (lane >> 3), c = i < 4 || lane < 16 ? j * 8 + j / 24 * 64 : 192;
      stsm4t(sb + SM_MEM + (c + (lane & 7)) * 16, mv[4 * i], mv[4 * i + 1], mv[4 * i + 2], mv[4 * i + 3]);
    }
    bar_arrive(1, 256); bar_arrive(2, 256); bar_arrive(9, 256);
    if (t2 == 0) SSTAMP(11, 8);
    mbar_wait(sb + MB_WO, 0);
    if (t2 == 0) SSTAMP(11, 4);
#pragma unroll
    for (int k = 0; k < 8; k++) ldsm4t(wo[k], wo_lane + SM_X + 2 * XT + k * 2048);
    fence_async();
    bar_sync(6, 128);
    if (t2 == 32) tma_load3(sb + SM_X + 2 * XT, &tm.x, 64, sb + MB_X + 16);
    __syncwarp();
#pragma unroll
    for (int k = 0; k < 8; k++)
#pragma unroll
      for (int i = 0; i < 4; i++) sq_acc(q[4 + i], wo[k][i]);
    float ss = 0.f;
#pragma unroll
    for (int i = 0; i < 8; i++) ss += bf_lo(q[i]) + bf_hi(q[i]);
    ss = warp_sum(ss);
    if (lane == 0) sts32(sb + SC_SS + 4 * (8 + w), __float_as_uint(ss));
    if (t2 == 0) SSTAMP(11, 9);
    bar_sync(11, 384);
    if (t2 == 0) SSTAMP(11, 10);
    if (t2 == 0) {
      float a[16];
#pragma unroll
      for (int i = 0; i < 4; i++) lds128f(sb + SC_SS + 16 * i, &a[4 * i]);
      stg_relaxed(&g_stats[blockIdx.x * 2], __float_as_uint(((a[0] + a[1]) + (a[2] + a[3])) + ((a[4] + a[5]) + (a[6] + a[7]))),
                  __float_as_uint((a[8] + a[9]) + (a[10] + a[11])),
                  max(max(__float_as_uint(a[12]), __float_as_uint(a[13])), max(__float_as_uint(a[14]), __float_as_uint(a[15]))), tag);
    }
    __syncwarp();
    WSTAMP(24);
    cluster_wait();
    if (w == 0) {
      uint4 v[3];
      int n = 0;
      while (true) {
#pragma unroll
        for (int i = 0; i < 3; i++) v[i] = ldg_relaxed(&g_stats[(i * 32 + lane) * 2]);
        if (__all_sync(0xffffffffu, v[0].w == tag && v[1].w == tag && v[2].w == tag) || ++n > SPIN_LIMIT) break;
        __nanosleep(100);
      }
      WSTAMP(25);
      const float sv = warp_sum(__uint_as_float(v[0].x) + __uint_as_float(v[1].x) + __uint_as_float(v[2].x));
      const float so = warp_sum(__uint_as_float(v[0].y) + __uint_as_float(v[1].y) + __uint_as_float(v[2].y));
      const int expW = ((int)(__float_as_uint(sv) >> 23) + (int)(__float_as_uint(so) >> 23) - 254 + 2 + 10 + 1) >> 1;
      sts32(sb + SC_XMAX + 4 * lane, v[0].z); sts32(sb + SC_XMAX + 128 + 4 * lane, v[1].z);
      sts32(sb + SC_EXPW, expW + 1 - 15);
      if (blockIdx.x == 0 && lane == 0) *(volatile unsigned*)&g_epoch = tag;
      sts32(sb + SC_FPAR + 4, 1);
    } else if (w < 3) {
      const uint32_t u = blockIdx.x >> 4;
      unsigned char* const z = g_red + 98304 + (blockIdx.x & 15) * 128 + (u & 1) * 2048 + (u & 6) * 4096 + (((u >> 1) ^ w) & 1) * 4096 + lane * 4;
      stg_relaxed32(z, 0);
      uint32_t best = 0xffffffffu;
#pragma unroll 1
      for (int i = 0; i < 64; i++) {
        uint32_t last, dt;
        asm volatile("{\n.reg .pred p;\n.reg .u32 c, v;\nld.volatile.shared.u32 %0, [%3];\nmov.u32 c, %%clock;\n"
                     "atom.relaxed.gpu.global.exch.b32 v, [%2], 0;\nsetp.eq.u32 p, v, 0;\nmov.u32 %1, 0;\n@p mov.u32 %1, %%clock;\nsub.u32 %1, %1, c;\n}"
                     : "=r"(last), "=r"(dt) : "l"(z), "r"(sb + SC_FPAR + 4) : "memory");
        best = min(best, dt);
        if (last && i >= NPROBE - 1) break;
      }
      sts32(sb + SC_LAT + (w - 1) * 4, best);
    }
    bar_sync(13, 384);
    bar_arrive(0, 384);
    WSTAMP(26);
    TSTAMP(1);
  }

  const uint32_t nh = __shfl_sync(0xffffffffu, near_half(sb), 0);
  uint32_t l16 = sb + lane * 16;
  PIN(l16);
#define LV ((l16 >> 4) & 31)
#define fence_reg l16
  const uint32_t red_lo = (uint32_t)(uint64_t)g_red, red_hi = (uint32_t)((uint64_t)g_red >> 32);
  uint32_t lp;
  auto slot = [&](int s, uint32_t c, uint32_t ofs) {
    const uint32_t lo = lp | (red_lo + ((w >> 1) * 4 + (w & 1) * 2 + ((w ^ c) & 1)) * 4096 + RED_SLOT(s) + ofs);
    uint64_t a; asm("mov.b64 %0, {%1, %2};" : "=l"(a) : "r"(lo), "r"(red_hi));
    return (unsigned char*)a;
  };
  const uint32_t always = __shfl_sync(0xffffffffu, lds32(sb + SC_DEAD + 12), 0);
  const int mode0 = RANK < 2 ? w : w | 4;
  auto hint_addr = [&](int s) { return min(LV, 23u) * 4 + (red_lo + HINT_OFF + nh * 4096 + w * 16384 + RED_SLOT(s)); };
  auto load_hints = [&](uint32_t lo) {
    uint64_t a; asm("mov.b64 %0, {%1, %2};" : "=l"(a) : "r"(lo), "r"(red_hi));
    return ldg_relaxed32((const void*)a);
  };
  const uint32_t blk = RANK < 2 ? 9216 : SEGB;
  auto send_v = [&](int seg, int pos) {
    if (RANK == 2 && ((w == 0 && VS0 == pos) || (w == 1 && VS1 == pos)) && seg > 1 && seg < NSEG && !(XP & 2)) {
      if (elect_one()) {
        fence_async();
        bulk_s2s(mapa(sb + SM_VC + (seg & 1) * 8192, w), sb + SM_BLK + (seg & 3) * SEGB, 8192, mapa(sb + MB_VX + (seg & 1) * 8, w));
      }
      __syncwarp();
    }
  };
  uint32_t dl = __shfl_sync(0xffffffffu, gtime() - 768, 0);
  int s = 0;
  bool bad = false;
#pragma unroll 1
  while (true) {
    const uint32_t par = s & 1;
    uint32_t vx[4][4], oc[4], hints;
    if (HP == 2) { hints = hint_addr(s); PIN(hints); }
    auto load_vx = [&]() {
      const uint32_t va = l16 + (RANK < 2 ? SM_VC + par * 8192 : SM_BLK + (s & 3) * SEGB) + w * 1024 + ((LV >> 3) & 1) * 384 - (LV >> 4) * 128;
      if (WL & 4) lds128(sb + SC_ONES, oc);
#pragma unroll
      for (int i = 0; i < 4; i++) ldsm4(vx[i], va + (i & 1) * 4096 + (i >> 1) * 256);
    };
    auto retire = [&](uint32_t x) {
      asm volatile("{\n.reg .pred p;\nsetp.eq.u32 p, %0, 0;\n@p exit;\n}" :: "r"(vx[0][0] | vx[1][0] | vx[2][0] | vx[3][0] | x | ((WL & 4) ? oc[0] : 0)) : "memory");
    };
    auto scores = [&](auto memkeys, auto first, float* sc) {
      constexpr bool MK = decltype(memkeys)::value, FIRST = decltype(first)::value;
      uint32_t kb[4][4], qb[2][4];
      const uint32_t m = LV >> 3;
      uint32_t kaddr = l16 + SM_BLK + 4096 + (s & 3) * SEGB + w * 2048 + (m & 1) * (MK ? 128 : 896) - (m >> 1) * 128;
      if (MK) { PIN(kaddr); }
      else {
#pragma unroll
        for (int k = 0; k < 4; k++) ldsm4t(kb[k], kaddr + k * 256);
      }
      if (FIRST) { load_vx(); retire(MK ? kaddr : kb[0][0] | kb[1][0] | kb[2][0] | kb[3][0] | l16); bar_sync(4, 256); RSTAMP(4); PROF(4); }
      ldsm4t(qb[0], l16 + SM_QM);
      if (MK) ldsm4t(kb[0], kaddr);
      ldsm4t(qb[1], l16 + SM_QM + 512);
      if (MK) ldsm4t(kb[2], kaddr + 512);
      float c[4][4];
      mma16816z(c[0], kb[0], qb[0][0], qb[0][1]); mma16816z(c[1], kb[MK ? 0 : 1], qb[0][2], qb[0][3]);
      mma16816z(c[2], kb[2], qb[1][0], qb[1][1]); mma16816z(c[3], kb[MK ? 2 : 3], qb[1][2], qb[1][3]);
      if (FIRST && B5POS == 0) bar_arrive(5, N5);
#pragma unroll
      for (int i = 0; i < (MK ? 2 : 4); i++) sc[i] = ((c[0][i] + c[1][MK ? i + 2 : i]) + c[2][i]) + c[3][MK ? i + 2 : i];
    };
    auto send = [&](auto memkeys) {
      constexpr bool MK = decltype(memkeys)::value;
      constexpr int N = MK ? 1 : 2;
      const uint32_t sa = sb + LV * 4 + SM_E + (MK ? 1024 + RANK * 128 : RANK * 512 + w * 256);
      uint32_t ra[N][2], mb[N][2];
#pragma unroll
      for (int i = 0; i < N; i++)
#pragma unroll
        for (int j = 0; j < 2; j++) {
          ra[i][j] = mapa(sa + i * 128, j ? 2 : RANK ^ 1); mb[i][j] = mapa(sb + MB_S, j ? 2 : RANK ^ 1);
          PIN(ra[i][j]);
        }
      float sc[4];
      scores(memkeys, BoolC<true>(), sc);
      uint32_t e[N];
#pragma unroll
      for (int i = 0; i < N; i++) {
        e[i] = pack_bf16(ex2(sc[2 * i]), ex2(sc[2 * i + 1]));
        if (!(fmaxf(fabsf(sc[2 * i]), fabsf(sc[2 * i + 1])) <= E_LIM)) e[i] = 0x7fff7fffu;
        st_async1(ra[i][0], e[i], mb[i][0]);
        st_async1(ra[i][1], e[i], mb[i][1]);
      }
#pragma unroll
      for (int i = 0; i < N; i++) sts32(sa + i * 128, e[i]);
      __syncwarp();
      if (l16 == sb) mbar_arrive(sb + MB_S);
      PROF(5);
    };
    const int mode = bad ? 8 : mode0;
    if (mode < 2) {
      send(BoolC<false>());
    } else if (mode == 2) {
      send(BoolC<true>());
    } else if (mode == 8) {
      load_vx();
      retire(l16);
      const uint32_t fp = lds32(sb + SC_FPAR);
      bar_sync(6, 128);
      if (w == 0 && l16 == sb) { sts32(sb + SC_FPAR, fp ^ 1); mbar_expect(sb + MB_F, 3072); }
      if (RANK < 2 && w < 3) {
        float sc[4] = {0.f, 0.f, 0.f, 0.f};
        if (w < 2) scores(BoolC<false>(), BoolC<false>(), sc); else scores(BoolC<true>(), BoolC<false>(), sc);
#pragma unroll 1
        for (int r = 0; r < 3; r++)
          st_async4(mapa(l16 + SM_FB + RANK * 1536 + w * 512, r), __float_as_uint(sc[0]), __float_as_uint(sc[1]), __float_as_uint(sc[2]), __float_as_uint(sc[3]), mapa(sb + MB_F, r));
      }
      mbar_wait(sb + MB_F, fp);
      float a[12];
#pragma unroll
      for (int j = 0; j < 3; j++) {
        float b[4];
        lds128f(l16 + SM_FB + j * 512, a + 4 * j); lds128f(l16 + SM_FB + 1536 + j * 512, b);
#pragma unroll
        for (int i = 0; i < 4; i++) a[4 * j + i] += b[i];
      }
      float m0 = fmaxf(fmaxf(fmaxf(a[0], a[2]), fmaxf(a[4], a[6])), a[8]), m1 = fmaxf(fmaxf(fmaxf(a[1], a[3]), fmaxf(a[5], a[7])), a[9]);
#pragma unroll
      for (int o = 4; o < 32; o <<= 1) { m0 = fmaxf(m0, __shfl_xor_sync(0xffffffffu, m0, o)); m1 = fmaxf(m1, __shfl_xor_sync(0xffffffffu, m1, o)); }
#pragma unroll
      for (int i = 0; i < 5; i++) {
        const uint32_t ea = sb + SM_E + LV * 4 + (i < 4 ? i * 128 : 1024);
        sts32(ea, pack_bf16(ex2(a[2 * i] - m0), ex2(a[2 * i + 1] - m1)));
        sts32(ea + (i < 4 ? 512 : 128), 0x3f803f80u);
      }
      __syncwarp();
    } else {
      load_vx();
      retire(l16 + 1);
      if (VS0 == 2 || VS1 == 2) send_v(s + 1, 2);
      if (w == 3) {
        uint32_t used = ldg_relaxed32(&g_used[blockIdx.x / 3 * 32]);
        if (!(XP & 4) && elect_one()) {
          if (s > 0) seg_publish(s - 1);
          fence_async();
          seg_store(s, sb, 0, 8192);
        }
        __syncwarp();
        bar_sync(RANK < 2 ? 4 : 15, RANK < 2 ? 256 : 160);
        if (!(XP & 4) && elect_one()) { fence_async(); seg_store(s, sb, 8192, blk - 8192); }
        __syncwarp();
        const uint32_t need = lds32(sb + SC_EPOCH) + (s >= NRING - 1 ? s : -4 * NSEG);
#pragma unroll 1
        for (int n = 0; (int)(used - need) < 0 && n < ((XP & 64) ? 1 : SPIN_LIMIT); n++) used = ldg_relaxed32(&g_used[blockIdx.x / 3 * 32]);
      }
    }
    {
      uint32_t wa[4], wb[4];
      constexpr int WS = 2048;
      const uint32_t w3a = l16 + SM_WO3 + w * 512;
      if (HP == 1) { hints = hint_addr(s); PIN(hints); }
      if (!(WL & 1)) { lds128(w3a + KP(0) * WS, wa); lds128(w3a + KP(1) * WS, wb); }
      if (WL & 2) {
#pragma unroll
        for (int i = 0; i < 4; i++) oc[i] = always | (always >> 16) | (always & (i + 1));
      } else if (!(WL & 4)) lds128(sb + SC_ONES, oc);
      if (B5POS == 1 && mode < 3) bar_arrive(5, N5);
      uint32_t e[10], p[5], vm[4], ob[4];
      float o0[4], o1[4], f[3][2][4], rs[4];
      if (!(RV & 1)) { reserve2(vm); reserve2(vm + 2); }
      if (!(RV & 2)) reserve2(e + 8);
      if (!HP) { hints = hint_addr(s); PIN(hints); }
      if (CLR & 2) asm volatile("{\n.reg .pred p;\nsetp.eq.u32 p, %0, 0;\n@p exit;\n}" :: "r"(wa[0] | wb[0] | oc[0] | hints) : "memory");
      if (RV & 4) mbar_wait_fast(sb + MB_S, par); else mbar_wait(sb + MB_S, par);
      RSTAMP(5);
      PROF(6);
      if (RV & 2) { ldsm4t(e, l16 + SM_E); ldsm4t(e + 4, l16 + SM_E + 512); ldsm2t(e + 8, l16 + SM_E + 1024); }
      else { ldsm4t(e, l16 + SM_E); ldsm2t_in(e + 8, l16 + SM_E + 1024, always); ldsm4t(e + 4, l16 + SM_E + 512); }
      if (RV & 1) lds128(l16 + w * 512 + SM_VM, vm); else lds128_in(vm, l16 + w * 512 + SM_VM, always);
      const float scl = __uint_as_float(lds32(sb + SC_UNSC + 8 - par * 8));
      if (HL == 0) hints = load_hints(hints);
      if (GF & 1) SCHED_FENCE(4);
#pragma unroll
      for (int i = 0; i < 4; i++) p[i] = mul_bf16(e[i], e[4 + i]);
      p[4] = mul_bf16(e[8], e[9]);
      if (HL) hints = load_hints(hints | (p[HL - 1] & always & 1));
      mma16816z(o0, vx[0], p[0], p[1]);
      if (WL & 1) { lds128_in(vx[0], w3a + KP(0) * WS, always); }
      mma16816z(o1, vx[1], p[0], p[1]);
      if (WL & 1) { lds128_in(vx[1], w3a + KP(1) * WS, always); }
      mma16816z(rs, oc, p[0], p[1]);
      mma16816(o0, vx[2], p[2], p[3]); lds128_in(vx[2], w3a + KP(2) * WS, always);
      mma16816(o1, vx[3], p[2], p[3]); lds128_in(vx[3], w3a + KP(3) * WS, always);
      mma16816(rs, oc, p[2], p[3]);
      mma1688(o0, vm[0], vm[1], p[4]); mma1688(o1, vm[2], vm[3], p[4]); mma1688(rs, oc[0], oc[1], p[4]);
      stsm4(l16 + w * 512 + SM_OB, pack_bf16(o0[0], o0[1]), pack_bf16(o0[2], o0[3]), pack_bf16(o1[0], o1[1]), pack_bf16(o1[2], o1[3]));
      bar_sync(6, 128);
      RSTAMP(3);
      PROF(7);
      ldsm4t_in(oc, l16 + SM_OB, always);
      bad = __any_sync(0xffffffffu, !(rs[0] + rs[1] > 0.f) && !bad);
      rs[0] *= scl; rs[1] *= scl;
      asm volatile("{\n.reg .pred p;\nsetp.ne.u32 p, %1, 0;\n@p rcp.approx.ftz.f32 %0, %0;\n}" : "+f"(rs[0]) : "r"(always));
      asm volatile("{\n.reg .pred p;\nsetp.ne.u32 p, %1, 1;\n@p rcp.approx.ftz.f32 %0, %0;\n}" : "+f"(rs[1]) : "r"(always));
      asm volatile("lop3.b32 %0, %1, %2, %3, 0xfe;" : "=r"(lp) : "r"((l16 & 128) * 2), "r"((l16 & 256) * 4), "r"(l16 & 112));
      if (bad) continue;
      ldsm4t(ob, l16 + SM_OB + 512);
      mma16816z(f[2][0], WL & 1 ? vx[0] : wa, oc[0], oc[1]); mma16816z(f[2][1], WL & 1 ? vx[1] : wb, oc[2], oc[3]);
      mma16816z(f[0][0], wo[0], oc[0], oc[1]); mma16816z(f[0][1], wo[4], oc[2], oc[3]);
      mma16816z(f[1][0], w1[0], oc[0], oc[1]); mma16816z(f[1][1], w1[4], oc[2], oc[3]);
      ldsm4t_in(oc, l16 + SM_OB + 1024, always);
      mma16816(f[2][0], vx[2], ob[0], ob[1]); lds128_in(vx[2], w3a + KP(4) * WS, always);
      mma16816(f[2][1], vx[3], ob[2], ob[3]); lds128_in(vx[3], w3a + KP(5) * WS, always);
      mma16816(f[0][0], wo[1], ob[0], ob[1]); mma16816(f[0][1], wo[5], ob[2], ob[3]);
      mma16816(f[1][0], w1[1], ob[0], ob[1]); mma16816(f[1][1], w1[5], ob[2], ob[3]);
      ldsm4t_in(ob, l16 + SM_OB + 1536, always);
      mma16816(f[0][0], wo[2], oc[0], oc[1]); mma16816(f[0][1], wo[6], oc[2], oc[3]);
      mma16816(f[2][0], vx[2], oc[0], oc[1]); lds128_in(vx[2], w3a + KP(6) * WS, always);
      mma16816(f[2][1], vx[3], oc[2], oc[3]); lds128_in(vx[3], w3a + KP(7) * WS, always);
      mma16816(f[1][0], w1[2], oc[0], oc[1]); mma16816(f[1][1], w1[6], oc[2], oc[3]);
      mma16816(f[0][0], wo[3], ob[0], ob[1]); mma16816(f[0][1], wo[7], ob[2], ob[3]);
      mma16816(f[1][0], w1[3], ob[0], ob[1]); mma16816(f[1][1], w1[7], ob[2], ob[3]);
      mma16816(f[2][0], vx[2], ob[0], ob[1]); mma16816(f[2][1], vx[3], ob[2], ob[3]);
      bar_arrive(7, NII < 18 ? 384 : 256);
      lds128_in(ob, sb + SC_DEAD, always);
      uint32_t h[3][2];
#pragma unroll
      for (int j = 0; j < 3; j++)
#pragma unroll
        for (int i = 0; i < 2; i++)
        {
          scale_sum(f[j][1][2 * i], f[j][0][2 * i], rs[0], always); scale_sum(f[j][1][2 * i + 1], f[j][0][2 * i + 1], rs[1], always);
          h[j][i] = pack_f16(f[j][1][2 * i], f[j][1][2 * i + 1]);
        }
      const uint32_t rofs = RANK * 32768;
      red_f16x8(slot(s, RANK >> 1, rofs), h[0][0], h[1][0], h[2][0], 0x3c00u);
      red_f16x8(slot(s, (RANK >> 1) ^ 1, rofs), h[0][1], h[1][1], h[2][1], 0x3c00u);
      if (NII == 18) bar_arrive(10, 256);
      SCHED_FENCE(5);
      RSTAMP(0);
      l16 += ob[B7R];
    }
    {
    PROF(8);
    if (VS0 == 3 || VS1 == 3) send_v(s + 1, 3);
    const uint32_t ma0 = l16 + SM_MEM + w * 128 + (LV >> 3) * 896 + nh * 512;
    const unsigned char* const sl[2] = {slot(s, nh, 0), slot(s, nh ^ 1, 0)};
    uint32_t late = latest_hint(hints, dl, s);
    if (late >= 64) {
      int n = 0;
#pragma unroll 1
      do {
        late = latest_hint(load_hints(hint_addr(s)), dl, s);
      } while (late >= 64 && ++n < SPIN_LIMIT);
    }
    dl += late * 32 + tm.poll;
    PROF(9);
    {
      auto wait_until = [&](uint32_t t) {
        asm volatile("{\n.reg .pred p;\n.reg .s32 c;\n.reg .u64 t;\nTL: mov.u64 t, %%globaltimer;\ncvt.u32.u64 c, t;\nsub.s32 c, c, %0;\nsetp.lt.s32 p, c, 0;\n@p bra.uni TL;\n}" :: "r"(t + (l16 & 15)) : "memory");
      };
      uint4 v[2][3];
      auto load = [&](int c) {
#pragma unroll
        for (int r = 0; r < 3; r++) v[c][r] = ldg_relaxed(sl[c ^ (r >> 1)] + r * 32768);
      };
      auto decode = [&](int c, int n) {
        uint32_t q[9];
        __half2 hm;
        const uint32_t ma = ma0 ^ (c * 512);
#pragma unroll
        for (int i = 0; i < 9; i++) {
          const uint32_t h = i % 3 == 0 ? v[c][i / 3].x : (i % 3 == 1 ? v[c][i / 3].y : v[c][i / 3].z);
          const float2 f = __half22float2(*(const __half2*)&h);
          q[i] = pack_bf16(f.x, f.y);
          hm = i ? __hmax2(hm, __habs2(*(const __half2*)&h)) : __habs2(*(const __half2*)&h);
        }
#pragma unroll
        for (int r = 0; r < 3; r++) stsm4(ma + r * 4096, q[3 * r], q[3 * r + 1], q[3 * r + 2], r < 2 ? v[c][r].w : *(const uint32_t*)&hm);
        const bool done = __all_sync(0xffffffffu, v[c][0].w == 0x5000u && v[c][1].w == 0x5000u && v[c][2].w == 0x5000u) || n > SPIN_LIMIT;
        asm volatile("{\n.reg .pred p;\nsetp.ne.u32 p, %0, 0;\n@p bar.arrive %1, 256;\n}" :: "r"((int)done), "r"(1 + c) : "memory");
        return done;
      };
      if (LEAD) { wait_until(dl - LEAD); load(1); }
      wait_until(dl);
      PROF(10);
      int n = 0;
#pragma unroll 1
      do {
        load(0);
        if (!LEAD) load(1);
        asm volatile("{\n.reg .pred p;\nsetp.eq.u32 p, %0, 0;\n@p bar.sync 13, 384;\n}" :: "r"(n) : "memory");
      } while (!decode(0, n++));
      PROF(11);
      RSTAMP(1);
#pragma unroll 1
      while (!decode(1, n++)) load(1);
      bar_arrive(9, 256);
      RSTAMP(2);
      PROF(12);
    }
    PROF(13);
    if (++s == NSEG - 1) break;
    }
  }
#undef fence_reg
  if (RANK < 2) bar_arrive(4, 256);
  TSTAMP(49);
  {
    PIN(l16);
    tail_attention(sb, RANK, w, LV, 0, 6);
#pragma unroll 1
    for (int sg = 0; sg < 2; sg++) {
      PIN(l16);
      const int lane = LV, m = lane >> 3, g = lane >> 2, t = lane & 3;
      const uint32_t ob = l16 + T_OB + sg * 8192;
      bar_sync(sg ? 0 : 8, 256);
      TSTAMP(54 + 2 * sg);
      const float inv = __uint_as_float(0x7f000000u - lds32(sb + T_UN + sg * 4));
#pragma unroll 1
      for (int j = 0; j < 4; j += 2) {
        float c[2][3][4];
        uint32_t x[4], y[4], z[2][4];
#pragma unroll
        for (int e = 0; e < 2; e++) {
          const uint32_t oa = sb + T_OA + ((sg * 4 + j + e) * 8 + g) * 64 + (blockIdx.x / 3 * 36 & 15) + t * 4;
          z[e][0] = lds32(oa); z[e][1] = lds32(oa + 16); z[e][2] = t ? 0u : lds32(oa + 32);
        }
#pragma unroll
        for (int i = 0; i < 3; i++) {
          const uint32_t wa = sb + T_WA + ((lane & 7) + ((lane >> 4) << 3)) * 128 + (((w + 4 * (m & 1)) ^ (lane & 7)) << 4);
          ldsm4t(x, wa + i * 3072); ldsm2t(y, wa + i * 3072 + 2048);
#pragma unroll
          for (int e = 0; e < 2; e++) { mma1688z(c[e][i], y[0], y[1], z[e][2]); mma16816(c[e][i], x, z[e][0], z[e][1]); }
        }
#pragma unroll
        for (int r = 0; r < 4; r++) {
          ldsm4t(z[0], ob + j * 2048 + r * 512); ldsm4t(z[1], ob + j * 2048 + 2048 + r * 512);
          lds128(l16 + SM_WO3 + w * 512 + r * 2048, x); lds128(l16 + SM_WO3 + w * 512 + (r + 4) * 2048, y);
#pragma unroll
          for (int e = 0; e < 2; e++) { mma16816(c[e][0], wo[r], z[e][0], z[e][1]); mma16816(c[e][1], w1[r], z[e][0], z[e][1]); mma16816(c[e][2], x, z[e][0], z[e][1]); }
#pragma unroll
          for (int e = 0; e < 2; e++) { mma16816(c[e][0], wo[r + 4], z[e][2], z[e][3]); mma16816(c[e][1], w1[r + 4], z[e][2], z[e][3]); mma16816(c[e][2], y, z[e][2], z[e][3]); }
        }
#pragma unroll
        for (int i = 0; i < 4; i++) {
          const float (&d)[3][4] = c[i >> 1];
          const int q = (i & 1) * 2;
          red_f16x8(g_red + T_RED + ((((sg * 4 + j + (i >> 1)) * 3 + RANK) * 4 + w) * 2 + (i & 1)) * 512 + lane * 16, pack_f16(d[0][q] * inv, d[0][q + 1] * inv),
                    pack_f16(d[1][q] * inv, d[1][q + 1] * inv), pack_f16(d[2][q] * inv, d[2][q + 1] * inv), 0x3c00u);
        }
      }
      TSTAMP(55 + 2 * sg);
    }
    if (RSLOW) { wait_until(gtime() + 8000); wait_until(gtime() + 8000); wait_until(gtime() + 4000); }
    if (w < 2) {
      const int b = blockIdx.x, lane = LV, g = lane >> 2, t = lane & 3;
      uint4 v;
#pragma unroll 1
      for (int n = 0; n < SPIN_LIMIT; n++) {
        v = ldg_relaxed(g_red + T_RED + (w * 96 + b) * 512 + lane * 16);
        if (__all_sync(0xffffffffu, v.w == 0x5000u)) break;
        __nanosleep(40);
      }
      const float un = __uint_as_float(lds32(sb + T_UN + w * 4));
      uint32_t* const o = (uint32_t*)(tm.out + (size_t)((NAUXSEG + w) * 32 + b / 24 * 8 + g) * DM + (b >> 3) % 3 * 192 + (b & 1) * 32 + (b & 6) * 4) + t;
#pragma unroll
      for (int j = 0; j < 3; j++) {
        const float2 f = __half22float2(*(const __half2*)(&v.x + j));
        o[j * 32] = movm(pack_bf16(f.x * un, f.y * un));
      }
    }
  }
  TSTAMP(3);
  if (CSY) cluster_sync();
}

__global__ void __cluster_dims__(3, 1, 1) __launch_bounds__(384, 1)
rec_kernel(const __grid_constant__ RMaps tm, const bf16* __restrict__ x, const bf16* __restrict__ mem0) {
  extern __shared__ __align__(1024) unsigned char smem_raw[];
  const uint32_t sb = smem_u32(smem_raw);
  const int tid = threadIdx.x, lane = tid & 31;
  const int wg = __shfl_sync(0xffffffffu, tid >> 7, 0);
  const int w = __shfl_sync(0xffffffffu, (tid >> 5) & 3, 0);
  uint32_t rank; asm("mov.u32 %0, %%cluster_ctarank;" : "=r"(rank));
  STAMP(0);
  TSTAMP(0);
  asm volatile("griddepcontrol.launch_dependents;" ::: "memory");

#define PFT 1
  if (PFT && wg == 1 && lane == 0) asm volatile("prefetch.tensormap [%0];\nprefetch.tensormap [%1];" :: "l"(w & 1 ? &tm.woa : &tm.oa), "l"(w == 0 ? (rank < 2 ? &tm.wk : &tm.wv) : w == 1 ? &tm.wq : w == 2 ? &tm.x : &tm.wo) : "memory");
  if (wg < 2) {
    asm volatile("setmaxnreg.inc.sync.aligned.u32 192;");
    if (tid == 0) {
      for (int i = 0; i < 3; i++) { mbar_init(sb + MB_W + 8 * i, 1); mbar_init(sb + MB_X + 8 * i, 1); }
      mbar_init(sb + MB_WO, 1); mbar_init(sb + MB_WO3, 1);
      mbar_init(sb + MB_S, rank < 2 ? 5 : 6);
      mbar_init(sb + MB_F, 1);
      for (int i = 0; i < 3; i++) mbar_init(sb + MB_T + 8 * i, 1);
      mbar_init(sb + MB_VX, 1); mbar_init(sb + MB_VX + 8, 1);
      asm volatile("fence.mbarrier_init.release.cluster;" ::: "memory");
      fence_async();
      SSTAMP(11, 6);
      load_weights(sb, tm, rank, 0);
      for (int i = 0; i < 3; i++) mbar_expect(sb + MB_X + 8 * i, XT);
      tma_load3(sb + SM_X, &tm.x, 0, sb + MB_X);
      if (!PACE) for (int c = 1; c < 4; c++) load_weights(sb, tm, rank, c);
      mbar_expect(sb + MB_S, rank < 2 ? 640 + 2048 : 1280);
      mbar_expect(sb + MB_VX, 8192); mbar_expect(sb + MB_VX + 8, 8192);
      mbar_expect(sb + MB_T, 2048);
      for (int i = 1; i < 3; i++) mbar_expect(sb + MB_T + 8 * i, rank < 2 ? 5120 : 10240);
      SSTAMP(11, 5);
    }
    __syncwarp();
    bar_sync(0, 384);
    proj_role(sb, tm, rank, wg, w, lane);
  } else {
    asm volatile("setmaxnreg.dec.sync.aligned.u32 120;");
    attn_role(sb, smem_raw, tm, rank, x, mem0, w, lane);
  }
}

constexpr int A_XH = 73728;
constexpr int A_NS = 9, A_WM = 6144, A_WT = 768;
constexpr int A_RING = 2 * A_XH, A_TAIL = A_RING + A_NS * A_WM, A_GW = A_TAIL + A_NS * A_WT;
constexpr int A_EPI = 212864, A_EPW = 9344;
constexpr int A_XW = 4 * XT, A_XT = A_XW + 4096, A_NR = 4;
constexpr int A_IN = A_XW + 32768, A_OST = A_IN + 3 * SEGB;
constexpr int A_GATE = A_EPI + 2 * A_EPW, A_BAR = A_GATE + 512;
constexpr int A_TOTAL = A_BAR + 384;
struct AMaps { CUtensorMap x, wa, wt, oa, o, o3, o8, wob, woa, wo8; };

DI void wgmma_n192_ss_nt(float* d, uint64_t da, uint64_t db, int acc) {
  asm volatile("{\n.reg .pred p;\nsetp.ne.b32 p, %98, 0;\n"
               "wgmma.mma_async.sync.aligned.m64n192k16.f32.bf16.bf16 {"
               "%0,%1,%2,%3,%4,%5,%6,%7,%8,%9,%10,%11,%12,%13,%14,%15,%16,%17,%18,%19,%20,%21,%22,%23,%24,%25,%26,%27,%28,%29,%30,%31,"
               "%32,%33,%34,%35,%36,%37,%38,%39,%40,%41,%42,%43,%44,%45,%46,%47,%48,%49,%50,%51,%52,%53,%54,%55,%56,%57,%58,%59,%60,%61,%62,%63,"
               "%64,%65,%66,%67,%68,%69,%70,%71,%72,%73,%74,%75,%76,%77,%78,%79,%80,%81,%82,%83,%84,%85,%86,%87,%88,%89,%90,%91,%92,%93,%94,%95"
               "}, %96, %97, p, 1, 1, 0, 1;\n}\n"
               : ACC8(d, 0), ACC8(d, 8), ACC8(d, 16), ACC8(d, 24), ACC8(d, 32), ACC8(d, 40), ACC8(d, 48), ACC8(d, 56),
                 ACC8(d, 64), ACC8(d, 72), ACC8(d, 80), ACC8(d, 88) : "l"(da), "l"(db), "r"(acc));
}
#define ACC4(d, o) "+f"(d[o]), "+f"(d[o + 1]), "+f"(d[o + 2]), "+f"(d[o + 3])
DI void wgmma_n24_ss_nt(float* d, uint64_t da, uint64_t db, int acc) {
  asm volatile("{\n.reg .pred p;\nsetp.ne.b32 p, %14, 0;\n"
               "wgmma.mma_async.sync.aligned.m64n24k16.f32.bf16.bf16 {%0,%1,%2,%3,%4,%5,%6,%7,%8,%9,%10,%11}, %12, %13, p, 1, 1, 0, 1;\n}\n"
               : ACC8(d, 0), ACC4(d, 8) : "l"(da), "l"(db), "r"(acc));
}
DI void wgmma_n8_ss(float* d, uint64_t da, uint64_t db, int acc) {
  asm volatile("{\n.reg .pred p;\nsetp.ne.b32 p, %6, 0;\n"
               "wgmma.mma_async.sync.aligned.m64n8k16.f32.bf16.bf16 {%0,%1,%2,%3}, %4, %5, p, 1, 1, 0, 0;\n}\n"
               : ACC4(d, 0) : "l"(da), "l"(db), "r"(acc));
}
DI void wgmma_n40_ss_tt(float* d, uint64_t da, uint64_t db, int acc) {
  asm volatile("{\n.reg .pred p;\nsetp.ne.b32 p, %22, 0;\n"
               "wgmma.mma_async.sync.aligned.m64n40k16.f32.bf16.bf16 {%0,%1,%2,%3,%4,%5,%6,%7,%8,%9,%10,%11,%12,%13,%14,%15,%16,%17,%18,%19}, "
               "%20, %21, p, 1, 1, 1, 1;\n}\n"
               : ACC8(d, 0), ACC8(d, 8), ACC4(d, 16) : "l"(da), "l"(db), "r"(acc));
}
DI void wgmma_n64_rs(float* d, const uint32_t* a, uint64_t db, int acc) {
  asm volatile("{\n.reg .pred p;\nsetp.ne.b32 p, %37, 0;\n"
               "wgmma.mma_async.sync.aligned.m64n64k16.f32.bf16.bf16 {"
               "%0,%1,%2,%3,%4,%5,%6,%7,%8,%9,%10,%11,%12,%13,%14,%15,%16,%17,%18,%19,%20,%21,%22,%23,%24,%25,%26,%27,%28,%29,%30,%31"
               "}, {%32,%33,%34,%35}, %36, p, 1, 1, 0;\n}\n"
               : ACC8(d, 0), ACC8(d, 8), ACC8(d, 16), ACC8(d, 24) : "r"(a[0]), "r"(a[1]), "r"(a[2]), "r"(a[3]), "l"(db), "r"(acc));
}
DI void wgmma_n32_ss_tn(float* d, uint64_t da, uint64_t db, int acc) {
  asm volatile("{\n.reg .pred p;\nsetp.ne.b32 p, %18, 0;\n"
               "wgmma.mma_async.sync.aligned.m64n32k16.f32.bf16.bf16 {%0,%1,%2,%3,%4,%5,%6,%7,%8,%9,%10,%11,%12,%13,%14,%15}, "
               "%16, %17, p, 1, 1, 1, 0;\n}\n"
               : ACC8(d, 0), ACC8(d, 8) : "l"(da), "l"(db), "r"(acc));
}
DI void tma_load3c(uint32_t dst, const CUtensorMap* m, int c0, int c1, int c2, uint32_t mb) {
  asm volatile("cp.async.bulk.tensor.3d.shared::cluster.global.mbarrier::complete_tx::bytes [%0], [%1, {%3, %4, %5}], [%2];"
               :: "r"(dst), "l"(m), "r"(mb), "r"(c0), "r"(c1), "r"(c2) : "memory");
}
DI void count_up(unsigned* p) {
  asm volatile("fence.proxy.async;" ::: "memory");
  asm volatile("red.release.gpu.global.add.u32 [%0], 1;" :: "l"(p) : "memory");
}
#define AX 0
#define FDLY 400
#define DRY 0
#define FEND 59
DI void publish(unsigned* p) {
  asm volatile("cp.async.bulk.wait_group 0;\nfence.proxy.async;" ::: "memory");
  asm volatile("red.relaxed.gpu.global.add.u32 [%0], 1;" :: "l"(p) : "memory");
}
#define G_IDLE 600
#define PL 2
#define STG 0
#define ADLY 0

__global__ void __launch_bounds__(512, 1)
aux_kernel(const __grid_constant__ AMaps tm, const bf16* __restrict__ wqkv, const bf16* __restrict__ woa, const bf16* __restrict__ gate_w, bf16* __restrict__ out) {
  extern __shared__ __align__(1024) unsigned char smem_raw[];
  const uint32_t sb = smem_u32(smem_raw);
  const uint32_t fullx = sb + A_BAR, full1 = fullx + 24, empty1 = full1 + 8 * A_NS, fullw = empty1 + 8 * A_NS, full3 = fullw + 8, empty3 = full3 + 8 * A_NR,
                 fullq = empty3 + 8 * A_NR, fullv = fullq + 8, emptyq = fullv + 8, emptyv = emptyq + 8;
  const int tid = threadIdx.x, lane = tid & 31, cta = blockIdx.x;
  const int wg = __shfl_sync(0xffffffffu, tid >> 7, 0), w = __shfl_sync(0xffffffffu, (tid >> 5) & 3, 0);
  ASTAMP(14);
  if (tid == 384) {
    for (int i = 0; i < 3; i++) mbar_init(fullx + 8 * i, 1);
    for (int i = 0; i < A_NS; i++) { mbar_init(full1 + 8 * i, 1); mbar_init(empty1 + 8 * i, 8); }
    mbar_init(fullw, 1); mbar_init(fullq, 1); mbar_init(fullv, 1); mbar_init(emptyq, 4); mbar_init(emptyv, 4);
    for (int i = 0; i < A_NR; i++) { mbar_init(full3 + 8 * i, 1); mbar_init(empty3 + 8 * i, cta < NH ? 8 : 4); }
    fence_async();
  }
  __syncthreads();
  ASTAMP(0);
  const int tile = cta >> 1, hh = cta & 1;
  auto p3_n = [&](int g) { return cta < NH ? (cta & 3) * 2 + g : 8; };
  auto p3_k = [&](int g) { return cta < NH ? cta >> 2 : (cta & 3) * 2 + g; };
  if (wg == 3) {
    asm volatile("setmaxnreg.dec.sync.aligned.u32 24;");
    const bool lead = lane == 0;
    if (w < 3) {
      if (ADLY) wait_until(gtime() + ADLY);
      if (elect_one()) {
        mbar_expect(fullx + 8 * w, 49152);
        for (int p = 0; p < 2; p++)
          asm volatile("cp.async.bulk.tensor.4d.shared::cluster.global.mbarrier::complete_tx::bytes [%0], [%1, {%3, %4, %5, %6}], [%2];"
                       :: "r"(sb + p * A_XH + w * 24576), "l"(&tm.x), "r"(fullx + 8 * w), "r"(0), "r"(p), "r"(57 * tile - 7), "r"(3 * w) : "memory");
      }
#pragma unroll 1
      for (int r = 0; r < 17; r++) {
#pragma unroll 1
        for (int st = w; st < A_NS; st += 3) {
          if (r > 0) mbar_wait(empty1 + 8 * st, ~r & 1);
          if (r < 16 && elect_one()) {
            const int col = hh * 288 + (r >> 2) * 72, row = (r & 3) * 144 + st * 16;
            mbar_expect(full1 + 8 * st, A_WM + (AX & 1 ? 0 : A_WT));
            tma_load3c(sb + A_RING + st * A_WM, &tm.wa, col, row, 0, full1 + 8 * st);
            if (!(AX & 1)) tma_load3c(sb + A_TAIL + st * A_WT, &tm.wt, col + 64, row, 0, full1 + 8 * st);
          }
          __syncwarp();
        }
        if (r == 0 && elect_one())
          for (int j = 0; j < 3; j++)
            asm volatile("cp.async.bulk.prefetch.L2.global [%0], %1;" :: "l"((const char*)wqkv + cta * 55296 + (w * 3 + j) * 6144), "r"(6144) : "memory");
        __syncwarp();
      }
      bar_sync(8, 96);
    }
    const unsigned epoch = lds32(sb + A_BAR + 376);
    if (w == 2) {
      if (lead && cta < NH) {
#pragma unroll 1
        for (int seg = 0; seg < NAUXSEG; seg++) {
          const unsigned char* const src = g_seg + ((size_t)(AX & 128 ? 0 : seg % NRING) * 96 + cta * 3) * SEGB;
          SSTAMP(0, seg);
          const uint32_t tw = gtime();
          wait_count(&g_scnt[(seg * 32 + cta) * 8], 3 * (epoch + 1), !(TL & 2) || seg < NAUXSEG - 2);
          const bool idle = seg < FEND && gtime() - tw > G_IDLE;
          if (FDLY && idle) wait_until(gtime() + FDLY);
          SSTAMP(1, seg);
          mbar_wait(emptyq, ~seg & 1);
          if (AX & 8) { mbar_arrive(fullq); mbar_wait(emptyv, ~seg & 1); mbar_arrive(fullv); continue; }
          mbar_expect(fullq, 2 * SEGB);
          asm volatile("cp.async.bulk.shared::cluster.global.mbarrier::complete_tx::bytes [%0], [%1], %2, [%3];"
                       :: "r"(sb + A_IN), "l"(src), "r"(2 * SEGB), "r"(fullq) : "memory");
          mbar_wait(emptyv, ~seg & 1);
          mbar_expect(fullv, SEGB);
          asm volatile("cp.async.bulk.shared::cluster.global.mbarrier::complete_tx::bytes [%0], [%1], %2, [%3];"
                       :: "r"(sb + A_IN + 2 * SEGB), "l"(src + 2 * SEGB), "r"(SEGB), "r"(fullv) : "memory");
          if (seg == 1) wait_count(&g_abar[32], NAUX * (epoch + 1));
          stg_relaxed32(&g_used[cta * 32], epoch * NSEG + seg);
        }
      }
    }
    if (w == 3) {
#pragma unroll 1
      for (int c = 0; c < 4; c++) {
        if (lead) asm volatile("cp.async.bulk.wait_group.read 0;" ::: "memory");
        __syncwarp();
        bar_arrive(11, 160); bar_arrive(12, 160);
#pragma unroll 1
        for (int g = 0; g < 2; g++) {
          bar_sync(13 + g, 160);
          if (lead) {
            asm volatile("cp.async.bulk.tensor.3d.global.shared::cta.bulk_group [%0, {%2, %3, %4}], [%1];"
                         :: "l"(&tm.oa), "r"(sb + A_EPI + g * A_EPW + 1024), "r"(4096 + hh * 288 + c * 72), "r"(g), "r"(57 * tile) : "memory");
            asm volatile("cp.async.bulk.commit_group;" ::: "memory");
          }
        }
      }
      if (lead) asm volatile("cp.async.bulk.wait_group.read 0;" ::: "memory");
      __syncwarp();
      bar_arrive(10, 160);
      if (lead) publish(&g_abar[32]);
    }
    if ((w & 1) && cta < NH) {
      if (w == 1) bar_arrive(5, 160);
#pragma unroll 1
      for (int seg = w >> 1; seg < NAUXSEG; seg += 2) {
        bar_sync(w == 1 ? 4 : 15, 160);
        if (lead && !(AX & 32)) {
          tma_store(&tm.o, sb + A_OST, cta * DH, seg * 32);
          tma_store(&tm.o, sb + A_OST + 4096, cta * DH + 64, seg * 32);
          asm volatile("cp.async.bulk.commit_group;" ::: "memory");
          asm volatile("cp.async.bulk.wait_group.read 0;" ::: "memory");
        }
        __syncwarp();
        if (seg < NAUXSEG - 1) bar_arrive(5, 160);
        if (lead) {
          publish(&g_ocnt[seg * 64 + 2 * cta / 9 * 8]);
          if (2 * cta / 9 != (2 * cta + 1) / 9) asm volatile("red.relaxed.gpu.global.add.u32 [%0], 1;" :: "l"(&g_ocnt[seg * 64 + (2 * cta + 1) / 9 * 8]) : "memory");
          SSTAMP(9, seg);
        }
        __syncwarp();
      }
    }
    if (w != 0) return;
    if (lead) {
      mbar_expect(fullw, 18 * 8192 + 2048);
#pragma unroll 1
      for (int k = 0; k < 18; k++) {
        const int g = k / 9, kb = p3_k(g) * 9 + k - 9 * g;
        if (kb < 64) tma_load(sb + k * 8192, &tm.wob, p3_n(g) * 64, kb * 64, fullw);
        else tma_load(sb + k * 8192, &tm.woa, p3_n(g) * 64, (kb - 64) * 64, fullw);
      }
      for (int g = 0; g < 2; g++) tma_load(sb + A_XW + g * 2048, &tm.wo8, p3_n(g) * 64, 512 + p3_k(g) * 8, fullw);
    }
    __syncwarp();
    bar_sync(6, 288);
    if (lead) {
      wait_count(&g_abar[32], NAUX * (epoch + 1));
      int avail = 0;
      bool waited = false;
      const int nbox = cta < NH ? NAUXSEG : 2 * NAUXSEG;
#pragma unroll 1
      for (int i = 0; i < nbox; i++) {
        const int seg = cta < NH ? i : i >> 1, ke = p3_k(i & 1), sl = i & 3;
        const unsigned nheads = (ke < 7 ? 5 : 1) * (epoch + 1);
        if (seg >= avail) {
          const int far = min(seg + 3, NAUXSEG - 1);
          if (cta < NH && far > seg && !waited && min((int)(ldg_relaxed32(&g_ocnt[far * 64 - 64 + ke * 8]) - nheads), (int)(ldg_acquire32(&g_ocnt[far * 64 + ke * 8]) - nheads)) >= 0) avail = far + 1;
          else waited = wait_count(&g_ocnt[seg * 64 + ke * 8], nheads, !(TL & 2) || seg < NAUXSEG - 2) && (TL & 4);
        }
        SSTAMP(5, seg);
        mbar_wait(empty3 + 8 * sl, ((i >> 2) & 1) ^ 1);
        if (AX & 4) { mbar_arrive(full3 + 8 * sl); continue; }
        mbar_expect(full3 + 8 * sl, XT + 512);
        tma_load3c(sb + sl * XT, &tm.o3, 0, seg * 32, ke * 9, full3 + 8 * sl);
        tma_load(sb + A_XT + sl * 512, &tm.o8, 72 * 64 + ke * 8, seg * 32, full3 + 8 * sl);
      }
    }
    __syncwarp(); bar_sync(6, 288);
    if (GDW) asm volatile("griddepcontrol.wait;" ::: "memory");
  } else if (wg == 2) {
    asm volatile("setmaxnreg.dec.sync.aligned.u32 88;");
    {
      const unsigned epoch = *(volatile unsigned*)&g_epoch2;
      if ((tid & 127) < 80) { const uint4 g = __ldg((const uint4*)gate_w + min(tid & 127, 71)); sts128(sb + A_GW + (tid & 127) * 16, g.x, g.y, g.z, g.w); }
      fence_async();
      bar_sync(3, 128);
      float gt[2][4];
      const uint32_t d0 = (sb & 0x3FFFF) >> 4;
#pragma unroll 1
      for (int j = 0; j < 3; j++) {
        mbar_wait(fullx + 8 * j, 0);
        WG_FENCE();
#pragma unroll
        for (int k = 0; k < 24; k++)
          wgmma_n8_ss(gt[k & 1], desc_at(d0 + (k & 1) * (A_XH >> 4) + j * 1536 + (k >> 3) * 512 + (k & 6), 16, 1024, 1), desc_at(d0 + (A_GW >> 4) + j * 24 + (k & 30), 16, 128, 0), j | (k >> 1));
        WG_COMMIT();
      }
      WG_WAIT(0);
      if ((lane & 3) == 0)
#pragma unroll
        for (int i = 0; i < 4; i++) {
          const float gv = 1.f / (1.f + __expf(-gt[i >> 1][(i & 1) * 2]));
          const int r = w * 16 + (lane >> 2) + (i & 1) * 8, tok = 2 * (57 * tile - 7 + r) + (i >> 1);
          sts32(sb + A_GATE + ((i >> 1) * 64 + r) * 4, __float_as_uint(gv));
          if (hh == 0 && r >= 7 && tok < S_LEN) g_gate[tok] = gv;
        }
      if (tid == 256) sts32(sb + A_BAR + 376, epoch);
      __syncwarp();
      bar_arrive(7, 384);
      __half2 hw = __float2half2_rn(0.f);
#pragma unroll
      for (int i = 0; i < 9; i++) { const uint4 v = __ldg((const uint4*)woa + cta * 1152 + i * 128 + (tid & 127)); hw = amax4(hw, &v.x); }
      const uint32_t ew = wexp(hw);
      if (lane == 0) atomicMax(&g_amax[0], (unsigned long long)(epoch + 1) << 32 | ew);
      bar_sync(3, 128);
      if (tid == 256) {
        count_up(&g_abar[0]);
        wait_count(&g_abar[0], NAUX * (epoch + 1));
        if (cta == 0) *(volatile unsigned*)&g_epoch2 = epoch + 1;
      }
      __syncwarp();
      bar_sync(10, 160);
    }
    if (cta < NH) {
      const int lim = w * 8 + (lane >> 2) - 2 * (lane & 3);
      const uint32_t oa = sb + A_OST + (w * 8 + (lane & 7)) * 128;
      const uint32_t d0 = ((sb + A_IN) & 0x3FFFF) >> 4;
      uint32_t p[5][4];
#pragma unroll
      for (int n = 0; n < 10; n++) p[n >> 1][1 + (n & 1)] = __shfl_sync(0xffffffffu, lane ^ n, n);
#pragma unroll 1
      for (int seg = 0; seg < NAUXSEG; seg++) {
        const float gt = __ldcg(&g_gate[seg * 32 + w * 8 + (lane >> 2)]);
        float sc[20], d[32];
        mbar_wait(fullq, seg & 1);
        if (tid == 256) SSTAMP(2, seg);
        WG_FENCE();
#pragma unroll
        for (int k = 0; k < 8; k++) {
          const int o = ((k >> 2) * SEGB + (k & 3) * 256) >> 4;
          wgmma_n40_ss_tt(sc, desc_at(d0 + o, 128, 512, 0), desc_at(d0 + o + 256, 128, 1024, 0), k > 0);
        }
        WG_COMMIT();
        WG_WAIT(0);
        if (lane == 0) mbar_arrive(emptyq);
        float a[10];
#pragma unroll
        for (int i = 0; i < 10; i++) {
          a[i] = sc[(i >> 1) * 4 + (i & 1)] * (SM_SCALE * LOG2E);
          if (i < 8 && (i >> 1) * 8 + (i & 1) > lim) a[i] = -1.0e9f * LOG2E;
        }
        float m = max10(a);
        m = fmaxf(m, __shfl_xor_sync(0xffffffffu, m, 1)); m = fmaxf(m, __shfl_xor_sync(0xffffffffu, m, 2));
#pragma unroll
        for (int i = 0; i < 10; i++) a[i] = ex2(a[i] - m);
#pragma unroll
        for (int n = 0; n < 5; n++) {
          p[n][0] = pack_bf16(a[2 * n], a[2 * n + 1]); p[n][3] = p[n][0] | p[n][1];
          asm volatile("" : "+r"(p[n][0]), "+r"(p[n][3]) :: "memory");
        }
        float sum = ((a[0] + a[1]) + (a[2] + a[3])) + ((a[4] + a[5]) + (a[6] + a[7])) + (a[8] + a[9]);
        sum += __shfl_xor_sync(0xffffffffu, sum, 1);
        mbar_wait(fullv, seg & 1);
        WG_FENCE();
#pragma unroll
        for (int n = 0; n < 5; n++) wgmma_n64_rs(d, p[n], n < 4 ? desc_at(d0 + SEGB / 8 + 8 * n, 4096, 512, 0) : desc_at(d0 + SEGB / 8 + 512, 1024, 128, 0), n);
        WG_COMMIT();
        sum += __shfl_xor_sync(0xffffffffu, sum, 2);
        const float f = (1.f - gt) * rcp(sum);
        bar_sync(5, 160);
        WG_WAIT(0);
        if (lane == 0) mbar_arrive(emptyv);
        if (tid == 256) SSTAMP(4, seg);
#pragma unroll
        for (int q = 0; q < 4; q++) {
          const float* const o = d + (q & 1) * 16 + (q & 2);
          stsm4(oa + (q >> 1) * 4096 + ((((q & 1) * 4 + (lane >> 3)) ^ (lane & 7)) << 4), pack_bf16(o[0] * f, o[1] * f), pack_bf16(o[4] * f, o[5] * f),
                pack_bf16(o[8] * f, o[9] * f), pack_bf16(o[12] * f, o[13] * f));
        }
        fence_async();
        bar_arrive(seg & 1 ? 15 : 4, 160);
      }
    }
  } else {
    asm volatile("setmaxnreg.inc.sync.aligned.u32 200;");
    {
      const int g = lane >> 2, t = lane & 3;
      const uint32_t eb = sb + A_EPI + wg * A_EPW, d0 = (sb & 0x3FFFF) >> 4;
      const uint32_t own = (2 * t <= g ? 0xffffu : 0u) | (2 * t < g ? 0xffff0000u : 0u);
      const int kmin = 7 - 57 * tile - 16 * w;
      __half2 ho = __float2half2_rn(0.f);
#pragma unroll 1
      for (int c = -DRY; c < 4; c++) {
        float acc[96], tl[12];
#pragma unroll 1
        for (int r = c < 0 ? 4 : 0; r < 4; r++) {
#pragma unroll
          for (int st = 0; st < A_NS; st++) {
            const int ks = r * 9 + st;
            if (c == 0 && st % 3 == 0 && ks % 12 == 0) mbar_wait(fullx + 8 * (ks / 12), 0);
            mbar_wait(full1 + 8 * st, r & 1);
            const uint64_t da = desc_at(d0 + wg * (A_XH >> 4) + (ks >> 2) * 512 + (ks & 3) * 2, 16, 1024, 1);
            WG_FENCE();
            wgmma_n192_ss_nt(acc, da, desc_at(d0 + ((A_RING + st * A_WM) >> 4), 2048, 1024, 1), ks);
            if (!(AX & 2)) wgmma_n24_ss_nt(tl, da, desc_at(d0 + ((A_TAIL + st * A_WT) >> 4), 128, 256, 0), ks);
            WG_COMMIT();
            if (st == 0 && r == 2) bar_sync(11 + wg, 160);
            WG_WAIT(1);
            if (ks > 0 && lane == 0) mbar_arrive(empty1 + 8 * ((st + A_NS - 1) % A_NS));
          }
        }
        WG_WAIT(0);
        if (lane == 0 && c >= 0) mbar_arrive(empty1 + 8 * (A_NS - 1));
        ASTAMP(16 + (c & 3));
        uint32_t ql[9], qh[9], kl[9], kh[9], kx[10], vl[9], vh[9], vx[10];
#pragma unroll
        for (int j = 0; j < 9; j++) {
          const float* const q = j < 8 ? acc + 4 * j : tl, * const k = j < 8 ? acc + 32 + 4 * j : tl + 4, * const v = j < 8 ? acc + 64 + 4 * j : tl + 8;
          kh[j] = pack_bf16(k[2], k[3]); vh[j] = pack_bf16(v[2], v[3]);
          ql[j] = pack_bf16(q[0], q[1]); qh[j] = pack_bf16(q[2], q[3]); kl[j] = pack_bf16(k[0], k[1]); vl[j] = pack_bf16(v[0], v[1]);
        }
        if (w < 3) {
          const uint32_t ha = eb + 1024 + w * 2304 + lane * 16;
          stsm4(ha, kh[0], kh[1], kh[2], kh[3]); stsm4(ha + 512, kh[4], kh[5], kh[6], kh[7]);
          stsm4(ha + 1024, vh[0], vh[1], vh[2], vh[3]); stsm4(ha + 1536, vh[4], vh[5], vh[6], vh[7]);
          asm volatile("stmatrix.sync.aligned.m8n8.x2.shared.b16 [%0], {%1,%2};" :: "r"(ha + 2048), "r"(kh[8]), "r"(vh[8]) : "memory");
        }
        if (c == 0) bar_sync(7, 384); else bar_sync(1 + wg, 128);
        {
          const uint32_t ha = eb + 1024 + max(w - 1, 0) * 2304 + lane * 16;
          ldsm4(kx, ha); ldsm4(kx + 4, ha + 512); ldsm4t(vx, ha + 1024); ldsm4t(vx + 4, ha + 1536);
          asm volatile("ldmatrix.sync.aligned.m8n8.x1.shared.b16 {%0}, [%1];" : "=r"(kx[8]) : "r"(ha + 2048) : "memory");
          asm volatile("ldmatrix.sync.aligned.m8n8.x1.trans.shared.b16 {%0}, [%1];" : "=r"(vx[8]) : "r"(ha + 2176) : "memory");
        }
        const float gl = __uint_as_float(lds32(sb + A_GATE + (wg * 64 + w * 16 + g) * 4)), gh = __uint_as_float(lds32(sb + A_GATE + (wg * 64 + w * 16 + g + 8) * 4));
#pragma unroll
        for (int j = 0; j < 9; j++) { vl[j] = movm(vl[j]); vh[j] = movm(vh[j]); }
        bar_sync(1 + wg, 128);
        uint32_t ol[9], oh[9];
#pragma unroll
        for (int i = 0; i < 4; i++) {
          const int b = 2 * i;
          const uint32_t a[4] = {t >= i ? ql[b] : 0u, t >= i ? qh[b] : 0u, ql[b + 1], qh[b + 1]}, a4 = t <= i ? ql[b + 2] : 0u, a5 = t <= i ? qh[b + 2] : 0u;
          float sx[4], sl[4], sh[4];
          mma16816z(sx, a, kx[b], kx[b + 1]); mma16816z(sl, a, kl[b], kl[b + 1]); mma16816z(sh, a, kh[b], kh[b + 1]);
          mma1688(sx, a4, a5, kx[b + 2]); mma1688(sl, a4, a5, kl[b + 2]); mma1688(sh, a4, a5, kh[b + 2]);
          float e[4];
#pragma unroll
          for (int u = 0; u < 4; u++) {
            const int cc = 2 * t + (u & 1);
            e[u] = (cc <= g ? (u < 2 ? sl[u] : sh[u]) : (u < 2 ? sx[u] : sl[u])) * (0.23570226039551584f * LOG2E);
            if ((cc <= g ? cc : cc - 8) + (u & 2) * 4 < kmin) e[u] = -1.0e9f * LOG2E;
          }
          float m0 = fmaxf(e[0], e[1]), m1 = fmaxf(e[2], e[3]);
#pragma unroll
          for (int o = 1; o < 4; o <<= 1) { m0 = fmaxf(m0, __shfl_xor_sync(0xffffffffu, m0, o)); m1 = fmaxf(m1, __shfl_xor_sync(0xffffffffu, m1, o)); }
          e[0] = ex2(e[0] - m0); e[1] = ex2(e[1] - m0); e[2] = ex2(e[2] - m1); e[3] = ex2(e[3] - m1);
          const uint32_t p0 = pack_bf16(e[0], e[1]), p1 = pack_bf16(e[2], e[3]);
          const uint32_t p[4] = {p0 & ~own, 0u, p0 & own, p1 & ~own};
          float s0 = e[0] + e[1], s1 = e[2] + e[3];
#pragma unroll
          for (int o = 1; o < 4; o <<= 1) { s0 += __shfl_xor_sync(0xffffffffu, s0, o); s1 += __shfl_xor_sync(0xffffffffu, s1, o); }
          const float f0 = gl * rcp(s0), f1 = gh * rcp(s1);
#pragma unroll
          for (int j = b; j < b + 3; j++) {
            float o[4];
            mma16816z(o, p, vx[j], vl[j]);
            mma1688(o, 0u, p1 & own, vh[j]);
            const uint32_t lo = pack_bf16(o[0] * f0, o[1] * f0), hi = pack_bf16(o[2] * f1, o[3] * f1);
            if (j > b || i == 0) { ol[j] = lo; oh[j] = hi; }
            else { ol[j] = t >= i ? lo : ol[j]; oh[j] = t >= i ? hi : oh[j]; }
          }
        }
        const uint32_t sa = eb + 16 + (w * 16 + (lane & 15)) * 144 + (lane >> 4) * 16;
#pragma unroll
        for (int j = 0; j < 8; j += 2) stsm4(sa + j * 16, ol[j], oh[j], ol[j + 1], oh[j + 1]);
        asm volatile("stmatrix.sync.aligned.m8n8.x2.shared.b16 [%0], {%1,%2};" :: "r"(sa + 128), "r"(ol[8]), "r"(oh[8]) : "memory");
        ho = amax4(amax4(amax4(amax4(ho, ol), ol + 4), oh), oh + 4);
        ho = __hmax2_nan(__hmax2_nan(ho, __habs2(*(const __half2*)&ol[8])), __habs2(*(const __half2*)&oh[8]));
        if (c == 3 && tile == 17) {
          const uint32_t eo = wexp(ho);
          if (lane == 0) atomicMax(&g_amax[16], (unsigned long long)(lds32(sb + A_BAR + 376) + 1) << 32 | eo);
        }
        fence_async();
        if (c >= 0) bar_arrive(13 + wg, 160); else bar_sync(1 + wg, 128);
        ASTAMP(20 + (c & 3));
      }
    }
    ASTAMP(3);
    uint32_t wa[36][4];
    mbar_wait(fullw, 0);
    const uint32_t la = sb + wg * 73728 + ((lane & 7) + ((lane >> 4) << 3)) * 128 + (((2 * w + ((lane >> 3) & 1)) ^ (lane & 7)) << 4);
#pragma unroll
    for (int k = 0; k < 36; k++) ldsm4t(wa[k], la + k * 2048);
    sts64(sb + A_XW + wg * 2048 + 1024 + (tid & 127) * 8, 0, 0);
    fence_async();
    bar_sync(6, 288);
    ASTAMP(4);
    const int nsl = p3_n(wg), ke = p3_k(wg), t = lane & 3;
    const unsigned epoch = lds32(sb + A_BAR + 376);
    uint2* const part = g_part + nsl * 4096 + w * 16 + (lane >> 2) * 2 + (t & 1);
    auto tag = [&](int seg) { return ((seg >> 2) + 1 + (epoch & (seg >> 1))) & 1; };
    uint2 v[4];
    auto fetch = [&](int seg) {
#pragma unroll
      for (int j = 0; j < 4; j++)
        asm volatile("ld.relaxed.gpu.global.v2.b32 {%0,%1}, [%2];" : "=r"(v[j].x), "=r"(v[j].y) : "l"(part + (seg & 3) * 36864 + ke * 512 + ((t >> 1) * 4 + j) * 64) : "memory");
    };
    auto finish = [&](int seg) {
      int n = 0;
#pragma unroll 1
      while (!(AX & 16) && __any_sync(0xffffffffu, (((v[0].x ^ tag(seg)) | (v[1].x ^ tag(seg)) | (v[2].x ^ tag(seg)) | (v[3].x ^ tag(seg))) & 1) != 0) && ++n < SPIN_LIMIT) {
        if (seg < NAUXSEG - ((TL & 2) ? 2 : 1)) __nanosleep(100);
        fetch(seg);
      }
      const float a0 = (bf_lo(v[0].x) + bf_lo(v[1].x)) + (bf_lo(v[2].x) + bf_lo(v[3].x)), a1 = (bf_hi(v[0].x) + bf_hi(v[1].x)) + (bf_hi(v[2].x) + bf_hi(v[3].x));
      const float b0 = (bf_lo(v[0].y) + bf_lo(v[1].y)) + (bf_lo(v[2].y) + bf_lo(v[3].y)), b1 = (bf_hi(v[0].y) + bf_hi(v[1].y)) + (bf_hi(v[2].y) + bf_hi(v[3].y));
      const float c0 = (t < 2 ? a0 : b0) + __shfl_xor_sync(0xffffffffu, t < 2 ? b0 : a0, 2), c1 = (t < 2 ? a1 : b1) + __shfl_xor_sync(0xffffffffu, t < 2 ? b1 : a1, 2);
      ((uint32_t*)(out + (size_t)(seg * 32 + ke * 4 + ((lane >> 2) & 3)) * DM + nsl * 64 + w * 16 + (lane >> 4) * 8))[t] = movm(pack_bf16(c0, c1));
    };
    float acc[16];
    const uint32_t d0 = (sb & 0x3FFFF) >> 4;
#pragma unroll 1
    for (int seg = 0; seg < NAUXSEG; seg++) {
      const int i = cta < NH ? seg : 2 * seg + wg, sl = i & 3;
      mbar_wait(full3 + 8 * sl, (i >> 2) & 1);
      if (STG && seg == 0 && wg == 1) bar_sync(9, 256);
      if (tid == 128) SSTAMP(6, seg);
      if (!(AX & 16)) fetch(max(seg - PL, 0));
      if (!(AX & 64)) {
        const uint64_t db = desc_at(d0 + sl * (XT >> 4), 16, 1024, 1);
        WG_FENCE();
        wgmma_n32_ss_tn(acc, desc_at(d0 + ((A_XW + wg * 2048) >> 4), 8192, 1024, 1), desc_at(d0 + (A_XT >> 4) + sl * 32, 0, 128, 0), 0);
#pragma unroll
        for (int k = 0; k < 36; k++) {
          wgmma_n32_rs(acc, wa[k][0], wa[k][1], wa[k][2], wa[k][3], db + (k >> 2) * 256 + (k & 3) * 2, 1);
          if (STG && k == STG && seg == 0 && wg == 0) bar_arrive(9, 256);
        }
        WG_COMMIT();
      }
      if (seg >= PL) finish(seg - PL);
      WG_WAIT(0);
      if (lane == 0) mbar_arrive(empty3 + 8 * sl);
#pragma unroll
      for (int j = 0; j < 4; j++)
        if (!(AX & 16))
          asm volatile("st.relaxed.gpu.global.v2.b32 [%0], {%1,%2};" :: "l"(part + (seg & 3) * 36864 + (2 * j + (t >> 1)) * 512 + ke * 64),
                       "r"((pack_bf16(acc[4 * j], acc[4 * j + 1]) & ~1u) | tag(seg)), "r"(pack_bf16(acc[4 * j + 2], acc[4 * j + 3])) : "memory");
      if (tid == 128) SSTAMP(7, seg);
      if (tid == 128) SSTAMP(8, seg);
      if ((seg & 7) == 6) ASTAMP(5 + (seg >> 3));
    }
#pragma unroll 1
    for (int seg = NAUXSEG - PL; seg < NAUXSEG; seg++) { fetch(seg); finish(seg); }
    ASTAMP(13);
    TSTAMP(48);
    bar_sync(6, 288);
  }
}

typedef CUresult (*EncodeFn)(CUtensorMap*, CUtensorMapDataType, cuuint32_t, void*, const cuuint64_t*, const cuuint64_t*,
                             const cuuint32_t*, const cuuint32_t*, CUtensorMapInterleave, CUtensorMapSwizzle,
                             CUtensorMapL2promotion, CUtensorMapFloatOOBfill);
static void make_map(EncodeFn enc, CUtensorMap* m, const void* p, int rows, int cols, int box_rows) {
  cuuint64_t dims[2] = {(cuuint64_t)cols, (cuuint64_t)rows};
  cuuint64_t strides[1] = {(cuuint64_t)cols * 2};
  cuuint32_t box[2] = {64, (cuuint32_t)box_rows};
  cuuint32_t es[2] = {1, 1};
  enc(m, CU_TENSOR_MAP_DATA_TYPE_BFLOAT16, 2, (void*)p, dims, strides, box, es, CU_TENSOR_MAP_INTERLEAVE_NONE,
      CU_TENSOR_MAP_SWIZZLE_128B, CU_TENSOR_MAP_L2_PROMOTION_L2_128B, CU_TENSOR_MAP_FLOAT_OOB_FILL_NONE);
}

constexpr int g_poll = POLL_NS;
extern "C" void kernel_launch(void* const* d_in, const int* in_sizes, int n_in, void* d_out, int out_size) {
  const bf16* x = (const bf16*)d_in[0];
  const bf16* wqkvA = (const bf16*)d_in[1];
  const bf16* woA = (const bf16*)d_in[2];
  const bf16* mem0 = (const bf16*)d_in[4];
  const bf16* Wq = (const bf16*)d_in[5];
  const bf16* Wk = (const bf16*)d_in[6];
  const bf16* Wv = (const bf16*)d_in[7];
  const bf16* Wo = (const bf16*)d_in[8];
  const bf16* gate_w = (const bf16*)d_in[10];
  static EncodeFn enc = nullptr;
  static void *pO = nullptr, *pR = nullptr;
  if (!enc) {
    cudaDriverEntryPointQueryResult qr;
    cudaGetDriverEntryPoint("cuTensorMapEncodeTiled", (void**)&enc, cudaEnableDefault, &qr);
    cudaGetSymbolAddress(&pO, g_Ocat);
    cudaGetSymbolAddress(&pR, g_red_raw);
    cudaFuncSetAttribute(rec_kernel, cudaFuncAttributeMaxDynamicSharedMemorySize, SM_TOTAL);
    cudaFuncSetAttribute(aux_kernel, cudaFuncAttributeMaxDynamicSharedMemorySize, A_TOTAL);
  }
  RMaps rm;
  rm.poll = g_poll; rm.out = (bf16*)d_out;
  make_map(enc, &rm.woa, woA, DM, DM, 24);
  {
    cuuint64_t dims[2] = {KCAT, S_LEN}, strides[1] = {KCAT * 2};
    cuuint32_t box[2] = {32, 64}, es[2] = {1, 1};
    enc(&rm.oa, CU_TENSOR_MAP_DATA_TYPE_BFLOAT16, 2, pO, dims, strides, box, es, CU_TENSOR_MAP_INTERLEAVE_NONE,
        CU_TENSOR_MAP_SWIZZLE_NONE, CU_TENSOR_MAP_L2_PROMOTION_NONE, CU_TENSOR_MAP_FLOAT_OOB_FILL_NONE);
  }
  rm.red = (unsigned char*)(((uintptr_t)pR + 262143) & ~(uintptr_t)262143);
  {
    cuuint64_t dims[3] = {64, S_LEN, 9}, strides[2] = {DM * 2, 128};
    cuuint32_t box[3] = {64, 32, 9}, es[3] = {1, 1, 1};
    enc(&rm.x, CU_TENSOR_MAP_DATA_TYPE_BFLOAT16, 3, (void*)x, dims, strides, box, es, CU_TENSOR_MAP_INTERLEAVE_NONE,
        CU_TENSOR_MAP_SWIZZLE_128B, CU_TENSOR_MAP_L2_PROMOTION_L2_128B, CU_TENSOR_MAP_FLOAT_OOB_FILL_NONE);
  }
  make_map(enc, &rm.wq, Wq, DM, 4096, 192);
  make_map(enc, &rm.wk, Wk, DM, 4096, 192);
  make_map(enc, &rm.wv, Wv, DM, 4096, 192);
  make_map(enc, &rm.wo, Wo, 4096, DM, 128);
  AMaps am;
  {
    cuuint32_t es[4] = {1, 1, 1, 1};
    cuuint64_t dx[4] = {64, 2, S_LEN / 2, 9}, sx[3] = {DM * 2, DM * 4, 128};
    cuuint32_t bx[4] = {64, 1, 64, 3};
    enc(&am.x, CU_TENSOR_MAP_DATA_TYPE_BFLOAT16, 4, (void*)x, dx, sx, bx, es, CU_TENSOR_MAP_INTERLEAVE_NONE,
        CU_TENSOR_MAP_SWIZZLE_128B, CU_TENSOR_MAP_L2_PROMOTION_L2_128B, CU_TENSOR_MAP_FLOAT_OOB_FILL_NONE);
    cuuint64_t dw[3] = {DM, DM, 3}, sw[2] = {DM * 6, DM * 2};
    cuuint32_t bw[3] = {64, 16, 3}, bt[3] = {8, 16, 3};
    enc(&am.wa, CU_TENSOR_MAP_DATA_TYPE_BFLOAT16, 3, (void*)wqkvA, dw, sw, bw, es, CU_TENSOR_MAP_INTERLEAVE_NONE,
        CU_TENSOR_MAP_SWIZZLE_128B, CU_TENSOR_MAP_L2_PROMOTION_L2_128B, CU_TENSOR_MAP_FLOAT_OOB_FILL_NONE);
    enc(&am.wt, CU_TENSOR_MAP_DATA_TYPE_BFLOAT16, 3, (void*)wqkvA, dw, sw, bt, es, CU_TENSOR_MAP_INTERLEAVE_NONE,
        CU_TENSOR_MAP_SWIZZLE_NONE, CU_TENSOR_MAP_L2_PROMOTION_NONE, CU_TENSOR_MAP_FLOAT_OOB_FILL_NONE);
    cuuint64_t dz[3] = {KCAT, 2, S_LEN / 2}, sz[2] = {KCAT * 2, KCAT * 4};
    cuuint32_t bz[3] = {72, 1, 57};
    enc(&am.oa, CU_TENSOR_MAP_DATA_TYPE_BFLOAT16, 3, pO, dz, sz, bz, es, CU_TENSOR_MAP_INTERLEAVE_NONE,
        CU_TENSOR_MAP_SWIZZLE_NONE, CU_TENSOR_MAP_L2_PROMOTION_NONE, CU_TENSOR_MAP_FLOAT_OOB_FILL_NONE);
  }
  {
    cuuint64_t dims[3] = {64, S_LEN, KCAT / 64}, strides[2] = {KCAT * 2, 128};
    cuuint32_t box[3] = {64, 32, 9}, es[3] = {1, 1, 1};
    make_map(enc, &am.o, pO, S_LEN, KCAT, 32);
    enc(&am.o3, CU_TENSOR_MAP_DATA_TYPE_BFLOAT16, 3, pO, dims, strides, box, es, CU_TENSOR_MAP_INTERLEAVE_NONE,
        CU_TENSOR_MAP_SWIZZLE_128B, CU_TENSOR_MAP_L2_PROMOTION_L2_128B, CU_TENSOR_MAP_FLOAT_OOB_FILL_NONE);
  }
  make_map(enc, &am.wob, Wo, 4096, DM, 64);
  make_map(enc, &am.woa, woA, DM, DM, 64);
  make_map(enc, &am.wo8, woA, DM, DM, 8);
  {
    cuuint64_t dims[2] = {KCAT, S_LEN}, strides[1] = {KCAT * 2};
    cuuint32_t box[2] = {8, 32}, es[2] = {1, 1};
    enc(&am.o8, CU_TENSOR_MAP_DATA_TYPE_BFLOAT16, 2, pO, dims, strides, box, es, CU_TENSOR_MAP_INTERLEAVE_NONE,
        CU_TENSOR_MAP_SWIZZLE_NONE, CU_TENSOR_MAP_L2_PROMOTION_NONE, CU_TENSOR_MAP_FLOAT_OOB_FILL_NONE);
  }

  rec_kernel<<<96, 384, SM_TOTAL, cudaStreamPerThread>>>(rm, x, mem0);
  cudaLaunchConfig_t cfg = {};
  cfg.gridDim = dim3(NAUX); cfg.blockDim = dim3(512); cfg.dynamicSmemBytes = A_TOTAL; cfg.stream = cudaStreamPerThread;
  cudaLaunchAttribute at[1];
  at[0].id = cudaLaunchAttributeProgrammaticStreamSerialization; at[0].val.programmaticStreamSerializationAllowed = 1;
  cfg.attrs = at; cfg.numAttrs = 1;
  if (XP & 16) cfg.numAttrs = 0;
  if (!(XP & 64)) cudaLaunchKernelEx(&cfg, aux_kernel, am, wqkvA, woA, gate_w, (bf16*)d_out);
}
```

```cpp
#include <cuda_runtime.h>
#include <cuda_bf16.h>
#include <cuda_fp16.h>
#include <cuda.h>
#include <stdint.h>

typedef __nv_bfloat16 bf16;

constexpr int S_LEN = 2048, DM = 576, NH = 32, DH = 128, NSEG = 64, KCAT = 4096 + 576;
constexpr int NAUXSEG = NSEG - 2;
constexpr int NAUX = 36;
#define RED_LINE(i) (((i) >> 2) * 4096 + ((i) & 1) * 256 + ((i) & 2) * 512)
#define RED_SLOT(s) (((s) & 1) * 128 + ((s) & 2) * 256)

#define POLL_NS 896
#define NII 18
#define W3PRE 4
#define W3MID 4
#define GF 0
#define B5POS 0
#define NUP 4
#define UPF 1
#define B3Q 9
#define B3F 0
#define GATE 7
#define NTL 2
#define B7R 1
#define VS0 1
#define VS1 0
#define VLATE(w) ((w) == 0 ? VS0 == 1 : (w) == 1 ? VS1 == 1 : false)
#define HOIST 1
#define GDW 0
#define RSLOW 0
#define CSY 0
#define DD 2
#define N12 18
#define N14 18
#define HP 0
#define HL 0
#define WL 1
#define RV 3
#define RET 1
#define TL 6
#define CLR 1
#define RFW 0
#define NIC 0
#define LEAD 0
#define FIN16 1
#define VXG 0
#define NRING 20
#define EXD 0
#define HDLY 0
#define F10 1
#define NPROBE 2
#define QM 0
#define N5 224
#define KP(i) (((i) >> 1) + 4 * ((i) & 1))
#define SPIN_LIMIT (1 << 14)
#define XP 0

__device__ __align__(1024) bf16 g_Ocat[S_LEN * KCAT];
__device__ __align__(1024) unsigned char g_red_raw[2 * 262144];
constexpr int HINT_OFF = 2048;
__device__ __align__(16) float g_gate[S_LEN];
__device__ __align__(128) uint4 g_stats[96 * 2];
__device__ unsigned g_epoch;
__device__ unsigned g_epoch2;
__device__ unsigned g_ocnt[NSEG * 64];
__device__ unsigned g_abar[3 * 32];
__device__ unsigned long long g_amax[2 * 16];
__device__ unsigned g_scnt[NSEG * 32 * 8];
__device__ __align__(1024) unsigned char g_seg[NRING * 96 * 10240];
__device__ unsigned g_used[NH * 32];
__device__ __align__(1024) uint2 g_part[8 * 9 * 64 * 64];
__device__ int g_err;
#define TSTAMP(i)
#define PROF(idx)
#define PROFP(idx)
#define RSTAMP(k)
#define STAMP(idx)
#define ASTAMP(idx)
#define SSTAMP(k, seg)
#define WSTAMP(idx)

#define DI __device__ __forceinline__
DI uint32_t smem_u32(const void* p) { return (uint32_t)__cvta_generic_to_shared(p); }
DI uint32_t clock32() { uint32_t c; asm volatile("mov.u32 %0, %%clock;" : "=r"(c) :: "memory"); return c; }
DI uint32_t gtime() { uint32_t c; asm volatile("mov.u32 %0, %%globaltimer_lo;" : "=r"(c) :: "memory"); return c; }
DI uint32_t ldg_relaxed32(const void* p) { uint32_t v; asm volatile("ld.relaxed.gpu.global.b32 %0, [%1];" : "=r"(v) : "l"(p) : "memory"); return v; }
DI uint32_t ldg_acquire32(const void* p) { uint32_t v; asm volatile("ld.acquire.gpu.global.b32 %0, [%1];" : "=r"(v) : "l"(p) : "memory"); return v; }
DI void stg_relaxed32(void* p, uint32_t v) { asm volatile("st.relaxed.gpu.global.b32 [%0], %1;" :: "l"(p), "r"(v) : "memory"); }
DI int head_id() { int c; asm volatile("mov.u32 %0, %%clusterid.x;" : "=r"(c)); return c; }
DI uint32_t mapa(uint32_t a, uint32_t r) { uint32_t o; asm("mapa.shared::cluster.u32 %0, %1, %2;" : "=r"(o) : "r"(a), "r"(r)); return o; }
DI void cluster_arrive() { asm volatile("barrier.cluster.arrive.relaxed.aligned;" ::: "memory"); }
DI void cluster_wait() { asm volatile("barrier.cluster.wait.aligned;" ::: "memory"); }
DI void cluster_sync() { asm volatile("barrier.cluster.arrive.release.aligned;\nbarrier.cluster.wait.acquire.aligned;" ::: "memory"); }
DI void mbar_init(uint32_t b, uint32_t c) { asm volatile("mbarrier.init.shared::cta.b64 [%0], %1;" :: "r"(b), "r"(c) : "memory"); }
DI void mbar_expect(uint32_t b, uint32_t tx) { asm volatile("mbarrier.arrive.expect_tx.shared::cta.b64 _, [%0], %1;" :: "r"(b), "r"(tx) : "memory"); }
DI void mbar_arrive(uint32_t b) { asm volatile("mbarrier.arrive.shared::cta.b64 _, [%0];" :: "r"(b) : "memory"); }
DI void mbar_wait(uint32_t b, uint32_t par) {
  asm volatile("{\n.reg .pred p;\n.reg .u32 n, q;\nmov.u32 n, 0;\n"
               "WL: add.u32 n, n, 1;\nshr.u32 q, n, 12;\nxor.b32 q, q, %1;\n"
               "mbarrier.try_wait.parity.shared::cta.b64 p, [%0], q;\n@!p bra.uni WL;\n}"
               :: "r"(b), "r"(par) : "memory");
}
DI bool mbar_test(uint32_t b, uint32_t par) {
  uint32_t r;
  asm volatile("{\n.reg .pred p;\nmbarrier.test_wait.parity.shared::cta.b64 p, [%1], %2;\nselp.u32 %0, 1, 0, p;\n}" : "=r"(r) : "r"(b), "r"(par) : "memory");
  return r;
}
DI void mbar_wait_fast(uint32_t b, uint32_t par) {
  asm volatile("{\n.reg .pred p;\n.reg .u32 n, q;\nmbarrier.try_wait.parity.shared::cta.b64 p, [%0], %1;\n@p bra.uni WD;\nmov.u32 n, 0;\n"
               "WL: add.u32 n, n, 1;\nshr.u32 q, n, 12;\nxor.b32 q, q, %1;\n"
               "mbarrier.try_wait.parity.shared::cta.b64 p, [%0], q;\n@!p bra.uni WL;\nWD:\n}"
               :: "r"(b), "r"(par) : "memory");
}
DI void wait_until(uint32_t t) {
  const uint32_t now = gtime();
  t = min(t, now + 8192);
  asm volatile("{\n.reg .pred p;\n.reg .u32 c;\nTL: mov.u32 c, %%globaltimer_lo;\nsetp.lt.u32 p, c, %0;\n@p bra.uni TL;\n}" :: "r"(t) : "memory");
}
#define PIN(v) v = __shfl_xor_sync(0xffffffffu, v, 0)
#define SCHED_FENCE(k) asm volatile("{\n.reg .pred p;\nsetp.eq.u32 p, %0, %1;\n@p exit;\n}" :: "r"(fence_reg), "r"(k) : "memory")
#define MEM_ORDER(k) asm volatile("{\n.reg .pred p;\nsetp.eq.u32 p, %0, %1;\n@p st.shared.u32 [%0], %0;\n}" :: "r"(fence_reg), "r"(k + 64) : "memory")
DI void bar_sync(int id, int n) { asm volatile("bar.sync %0, %1;" :: "r"(id), "r"(n) : "memory"); }
DI void bar_arrive(int id, int n) { asm volatile("bar.arrive %0, %1;" :: "r"(id), "r"(n) : "memory"); }
DI void fence_async() { asm volatile("fence.proxy.async.shared::cta;" ::: "memory"); }
DI void st_async4(uint32_t a, uint32_t x, uint32_t y, uint32_t z, uint32_t w, uint32_t mb) {
  asm volatile("st.async.weak.shared::cluster.mbarrier::complete_tx::bytes.v4.b32 [%0], {%1,%2,%3,%4}, [%5];"
               :: "r"(a), "r"(x), "r"(y), "r"(z), "r"(w), "r"(mb) : "memory");
}
DI void st_async2(uint32_t a, uint32_t x, uint32_t y, uint32_t mb) {
  asm volatile("st.async.weak.shared::cluster.mbarrier::complete_tx::bytes.v2.b32 [%0], {%1,%2}, [%3];"
               :: "r"(a), "r"(x), "r"(y), "r"(mb) : "memory");
}
DI void sts32(uint32_t a, uint32_t x) { asm volatile("st.shared.b32 [%0], %1;" :: "r"(a), "r"(x) : "memory"); }
DI void sts64(uint32_t a, uint32_t x, uint32_t y) { asm volatile("st.shared.v2.b32 [%0], {%1,%2};" :: "r"(a), "r"(x), "r"(y) : "memory"); }
DI void sts128(uint32_t a, uint32_t x, uint32_t y, uint32_t z, uint32_t w) {
  asm volatile("st.shared.v4.b32 [%0], {%1,%2,%3,%4};" :: "r"(a), "r"(x), "r"(y), "r"(z), "r"(w) : "memory");
}
DI uint32_t lds32(uint32_t a) { uint32_t x; asm volatile("ld.shared.b32 %0, [%1];" : "=r"(x) : "r"(a) : "memory"); return x; }
DI void lds64(uint32_t a, uint32_t& x, uint32_t& y) { asm volatile("ld.shared.v2.b32 {%0,%1}, [%2];" : "=r"(x), "=r"(y) : "r"(a) : "memory"); }
DI void lds128(uint32_t a, uint32_t* r) {
  asm volatile("ld.shared.v4.b32 {%0,%1,%2,%3}, [%4];" : "=r"(r[0]), "=r"(r[1]), "=r"(r[2]), "=r"(r[3]) : "r"(a) : "memory");
}
DI void lds128f(uint32_t a, float* r) {
  asm volatile("ld.shared.v4.f32 {%0,%1,%2,%3}, [%4];" : "=f"(r[0]), "=f"(r[1]), "=f"(r[2]), "=f"(r[3]) : "r"(a) : "memory");
}
DI void lds64f(uint32_t a, float* r) { asm volatile("ld.shared.v2.f32 {%0,%1}, [%2];" : "=f"(r[0]), "=f"(r[1]) : "r"(a) : "memory"); }
DI void ldsm4t(uint32_t* r, uint32_t a) {
  asm volatile("ldmatrix.sync.aligned.m8n8.x4.trans.shared.b16 {%0,%1,%2,%3}, [%4];"
               : "=r"(r[0]), "=r"(r[1]), "=r"(r[2]), "=r"(r[3]) : "r"(a) : "memory");
}
DI void ldsm4t_in(uint32_t* r, uint32_t a, uint32_t t) {
  asm volatile("{\n.reg .pred p;\nsetp.ne.u32 p, %5, 0;\n@p ldmatrix.sync.aligned.m8n8.x4.trans.shared.b16 {%0,%1,%2,%3}, [%4];\n}"
               : "+r"(r[0]), "+r"(r[1]), "+r"(r[2]), "+r"(r[3]) : "r"(a), "r"(t) : "memory");
}
DI void lds128_in(uint32_t* r, uint32_t a, uint32_t t) {
  asm volatile("{\n.reg .pred p;\nsetp.ne.u32 p, %5, 0;\n@p ld.shared.v4.b32 {%0,%1,%2,%3}, [%4];\n}"
               : "+r"(r[0]), "+r"(r[1]), "+r"(r[2]), "+r"(r[3]) : "r"(a), "r"(t) : "memory");
}
DI void ldsm2t_in(uint32_t* r, uint32_t a, uint32_t t) {
  asm volatile("{\n.reg .pred p;\nsetp.ne.u32 p, %3, 0;\n@p ldmatrix.sync.aligned.m8n8.x2.trans.shared.b16 {%0,%1}, [%2];\n}" : "+r"(r[0]), "+r"(r[1]) : "r"(a), "r"(t) : "memory");
}
DI void reserve2(uint32_t* r) { asm volatile("{\n.reg .u64 t;\nmov.u64 t, %%clock64;\nmov.b64 {%0, %1}, t;\n}" : "=r"(r[0]), "=r"(r[1])); }
DI void scale_sum(float& x, float& y, float s, uint32_t t) {
  asm volatile("{\n.reg .pred p;\nsetp.ne.u32 p, %2, 0;\n@p mul.f32 %0, %0, %1;\n}" : "+f"(y) : "f"(s), "r"(t));
  asm volatile("{\n.reg .pred p;\nsetp.ne.u32 p, %3, 1;\n@p fma.rn.f32 %0, %0, %1, %2;\n}" : "+f"(x) : "f"(s), "f"(y), "r"(t));
}
DI void ldsm4(uint32_t* r, uint32_t a) {
  asm volatile("ldmatrix.sync.aligned.m8n8.x4.shared.b16 {%0,%1,%2,%3}, [%4];"
               : "=r"(r[0]), "=r"(r[1]), "=r"(r[2]), "=r"(r[3]) : "r"(a) : "memory");
}
DI void st_async1(uint32_t a, uint32_t x, uint32_t mb) {
  asm volatile("st.async.weak.shared::cluster.mbarrier::complete_tx::bytes.b32 [%0], %1, [%2];" :: "r"(a), "r"(x), "r"(mb) : "memory");
}
DI void stsm4(uint32_t a, uint32_t x, uint32_t y, uint32_t z, uint32_t w) {
  asm volatile("stmatrix.sync.aligned.m8n8.x4.shared.b16 [%0], {%1,%2,%3,%4};" :: "r"(a), "r"(x), "r"(y), "r"(z), "r"(w) : "memory");
}
DI void stsm4t(uint32_t a, uint32_t x, uint32_t y, uint32_t z, uint32_t w) {
  asm volatile("stmatrix.sync.aligned.m8n8.x4.trans.shared.b16 [%0], {%1,%2,%3,%4};" :: "r"(a), "r"(x), "r"(y), "r"(z), "r"(w) : "memory");
}
DI uint32_t pack_bf16(float lo, float hi) { uint32_t r; asm("cvt.rn.bf16x2.f32 %0, %1, %2;" : "=r"(r) : "f"(hi), "f"(lo)); return r; }
DI uint32_t pack_f16(float lo, float hi) { uint32_t r; asm("cvt.rn.f16x2.f32 %0, %1, %2;" : "=r"(r) : "f"(hi), "f"(lo)); return r; }
DI float ex2(float x) { float y; asm("ex2.approx.ftz.f32 %0, %1;" : "=f"(y) : "f"(x)); return y; }
DI float rcp(float x) { float y; asm("rcp.approx.ftz.f32 %0, %1;" : "=f"(y) : "f"(x)); return y; }
DI float bf_lo(uint32_t x) { return __uint_as_float(x << 16); }
DI float bf_hi(uint32_t x) { return __uint_as_float(x & 0xffff0000u); }
DI void mma16816(float* d, const uint32_t* a, uint32_t b0, uint32_t b1) {
  asm volatile("mma.sync.aligned.m16n8k16.row.col.f32.bf16.bf16.f32 {%0,%1,%2,%3}, {%4,%5,%6,%7}, {%8,%9}, {%0,%1,%2,%3};"
               : "+f"(d[0]), "+f"(d[1]), "+f"(d[2]), "+f"(d[3]) : "r"(a[0]), "r"(a[1]), "r"(a[2]), "r"(a[3]), "r"(b0), "r"(b1));
}
DI void mma16816z(float* d, const uint32_t* a, uint32_t b0, uint32_t b1) {
  asm volatile("mma.sync.aligned.m16n8k16.row.col.f32.bf16.bf16.f32 {%0,%1,%2,%3}, {%4,%5,%6,%7}, {%8,%9}, {%10,%10,%10,%10};"
               : "=f"(d[0]), "=f"(d[1]), "=f"(d[2]), "=f"(d[3]) : "r"(a[0]), "r"(a[1]), "r"(a[2]), "r"(a[3]), "r"(b0), "r"(b1), "f"(0.f));
}
DI void mma1688z(float* d, uint32_t a0, uint32_t a1, uint32_t b0) {
  asm volatile("mma.sync.aligned.m16n8k8.row.col.f32.bf16.bf16.f32 {%0,%1,%2,%3}, {%4,%5}, {%6}, {%7,%7,%7,%7};"
               : "=f"(d[0]), "=f"(d[1]), "=f"(d[2]), "=f"(d[3]) : "r"(a0), "r"(a1), "r"(b0), "f"(0.f));
}
DI void mma1688(float* d, uint32_t a0, uint32_t a1, uint32_t b0) {
  asm volatile("mma.sync.aligned.m16n8k8.row.col.f32.bf16.bf16.f32 {%0,%1,%2,%3}, {%4,%5}, {%6}, {%0,%1,%2,%3};"
               : "+f"(d[0]), "+f"(d[1]), "+f"(d[2]), "+f"(d[3]) : "r"(a0), "r"(a1), "r"(b0));
}
DI void ldsm2t(uint32_t* r, uint32_t a) {
  asm volatile("ldmatrix.sync.aligned.m8n8.x2.trans.shared.b16 {%0,%1}, [%2];" : "=r"(r[0]), "=r"(r[1]) : "r"(a) : "memory");
}
DI uint32_t add_bf16(uint32_t a, uint32_t b) { uint32_t r; asm("add.rn.bf16x2 %0, %1, %2;" : "=r"(r) : "r"(a), "r"(b)); return r; }
DI uint32_t mul_bf16(uint32_t a, uint32_t b) { uint32_t r; asm("mul.rn.bf16x2 %0, %1, %2;" : "=r"(r) : "r"(a), "r"(b)); return r; }
DI uint64_t make_desc(uint32_t addr, uint32_t lbo, uint32_t sbo, uint32_t swz) {
  return (uint64_t)((addr & 0x3FFFF) >> 4) | ((uint64_t)(lbo >> 4) << 16) | ((uint64_t)(sbo >> 4) << 32) | ((uint64_t)swz << 62);
}
DI uint64_t desc_at(uint32_t a16, uint32_t lbo, uint32_t sbo, uint32_t swz) {
  uint64_t d; asm("mov.b64 %0, {%1, %2};" : "=l"(d) : "r"(a16 + ((lbo >> 4) << 16)), "r"((sbo >> 4) | (swz << 30)));
  return d;
}
#define WG_FENCE() asm volatile("wgmma.fence.sync.aligned;" ::: "memory")
#define WG_COMMIT() asm volatile("wgmma.commit_group.sync.aligned;" ::: "memory")
#define WG_WAIT(n) asm volatile("wgmma.wait_group.sync.aligned %0;" :: "n"(n) : "memory")
#define ACC8(d, o) "+f"(d[o]), "+f"(d[o + 1]), "+f"(d[o + 2]), "+f"(d[o + 3]), "+f"(d[o + 4]), "+f"(d[o + 5]), "+f"(d[o + 6]), "+f"(d[o + 7])
DI void wgmma_n32_rs(float* d, uint32_t a0, uint32_t a1, uint32_t a2, uint32_t a3, uint64_t db, int acc) {
  asm volatile("{\n.reg .pred p;\nsetp.ne.b32 p, %21, 0;\n"
               "wgmma.mma_async.sync.aligned.m64n32k16.f32.bf16.bf16 {%0,%1,%2,%3,%4,%5,%6,%7,%8,%9,%10,%11,%12,%13,%14,%15}, "
               "{%16,%17,%18,%19}, %20, p, 1, 1, 0;\n}\n"
               : ACC8(d, 0), ACC8(d, 8) : "r"(a0), "r"(a1), "r"(a2), "r"(a3), "l"(db), "r"(acc));
}
template <int TA>
DI void wgmma_n32_ss(float* d, uint64_t da, uint64_t db, int acc) {
  asm volatile("{\n.reg .pred p;\nsetp.ne.b32 p, %18, 0;\n"
               "wgmma.mma_async.sync.aligned.m64n32k16.f32.bf16.bf16 {%0,%1,%2,%3,%4,%5,%6,%7,%8,%9,%10,%11,%12,%13,%14,%15}, "
               "%16, %17, p, 1, 1, %19, 1;\n}\n"
               : ACC8(d, 0), ACC8(d, 8) : "l"(da), "l"(db), "r"(acc), "n"(TA));
}
DI void tma_load(uint32_t dst, const CUtensorMap* m, int c0, int c1, uint32_t mb) {
  asm volatile("cp.async.bulk.tensor.2d.shared::cluster.global.mbarrier::complete_tx::bytes [%0], [%1, {%3, %4}], [%2];"
               :: "r"(dst), "l"(m), "r"(mb), "r"(c0), "r"(c1) : "memory");
}
DI void tma_load3(uint32_t dst, const CUtensorMap* m, int row, uint32_t mb) {
  asm volatile("cp.async.bulk.tensor.3d.shared::cluster.global.mbarrier::complete_tx::bytes [%0], [%1, {%3, %4, %3}], [%2];"
               :: "r"(dst), "l"(m), "r"(mb), "r"(0), "r"(row) : "memory");
}
DI bool elect_one() {
  uint32_t p;
  asm volatile("{\n.reg .pred p;\nelect.sync _|p, 0xffffffff;\nselp.u32 %0, 1, 0, p;\n}" : "=r"(p));
  return p;
}
DI void bulk_s2s(uint32_t dst, uint32_t src, uint32_t bytes, uint32_t mb) {
  asm volatile("cp.async.bulk.shared::cluster.shared::cta.mbarrier::complete_tx::bytes [%0], [%1], %2, [%3];"
               :: "r"(dst), "r"(src), "r"(bytes), "r"(mb) : "memory");
}
DI void tma_prefetch(const CUtensorMap* m, int c0, int c1) {
  asm volatile("cp.async.bulk.prefetch.tensor.2d.L2.global.tile [%0, {%1, %2}];" :: "l"(m), "r"(c0), "r"(c1) : "memory");
}
DI void tma_store(const CUtensorMap* m, uint32_t src, int c0, int c1) {
  asm volatile("cp.async.bulk.tensor.2d.global.shared::cta.bulk_group [%0, {%2, %3}], [%1];" :: "l"(m), "r"(src), "r"(c0), "r"(c1) : "memory");
}
DI uint4 ldg_relaxed(const void* p) {
  uint4 v;
  asm volatile("ld.relaxed.gpu.global.v4.b32 {%0,%1,%2,%3}, [%4];" : "=r"(v.x), "=r"(v.y), "=r"(v.z), "=r"(v.w) : "l"(p) : "memory");
  return v;
}
DI void stg_relaxed(void* p, uint32_t x, uint32_t y, uint32_t z, uint32_t w) {
  asm volatile("st.relaxed.gpu.global.v4.b32 [%0], {%1,%2,%3,%4};" :: "l"(p), "r"(x), "r"(y), "r"(z), "r"(w) : "memory");
}
DI void red_f16x8(void* p, uint32_t x, uint32_t y, uint32_t z, uint32_t w) {
  asm volatile("red.relaxed.gpu.global.add.noftz.v4.f16x2 [%0], {%1,%2,%3,%4};" :: "l"(p), "r"(x), "r"(y), "r"(z), "r"(w) : "memory");
}
DI void sq_acc(uint32_t& a, uint32_t x) { asm("fma.rn.bf16x2 %0, %1, %1, %0;" : "+r"(a) : "r"(x)); }
DI __half2 amax4(__half2 h, const uint32_t* v) {
  h = __hmax2_nan(__hmax2_nan(h, __habs2(*(const __half2*)&v[0])), __habs2(*(const __half2*)&v[1]));
  return __hmax2_nan(__hmax2_nan(h, __habs2(*(const __half2*)&v[2])), __habs2(*(const __half2*)&v[3]));
}
DI uint32_t wexp(__half2 h) { const uint32_t u = *(const uint32_t*)&h; return __reduce_max_sync(0xffffffffu, max((u >> 16) & 0x7fffu, u & 0x7fffu)) >> 7; }
DI float max10(const float* a) {
  return fmaxf(fmaxf(fmaxf(fmaxf(a[0], a[1]), fmaxf(a[2], a[3])), fmaxf(fmaxf(a[4], a[5]), fmaxf(a[6], a[7]))), fmaxf(a[8], a[9]));
}
DI float quad_max(float m) {
  return fmaxf(fmaxf(m, __shfl_xor_sync(0xffffffffu, m, 1)), fmaxf(__shfl_xor_sync(0xffffffffu, m, 2), __shfl_xor_sync(0xffffffffu, m, 3)));
}
DI float warp_sum(float v) {
#pragma unroll
  for (int o = 16; o; o >>= 1) v += __shfl_xor_sync(0xffffffffu, v, o);
  return v;
}

constexpr int SM_WO3 = 0;
constexpr int SM_X = 16384;
constexpr int XT = 36864;
constexpr int SM_EXP = 126976;
constexpr int SEGB = 10240;
constexpr int SM_BLK = SM_EXP + 8192;
constexpr int SM_VC = SM_BLK + 4 * SEGB;
constexpr int SM_PART = SM_VC + 16384;
constexpr int SM_QM = SM_PART + 4096;
constexpr int SM_E = SM_QM + 1024;
constexpr int SM_VM = SM_E + 1536;
constexpr int SM_OB = SM_VM + 2048;
constexpr int SM_FB = SM_OB + 2048;
constexpr int SM_STAGE = SM_X + XT;
constexpr int SM_MISC = 210944;
constexpr int SM_WOST = 212992;
constexpr int SM_MEM = SM_WOST;
constexpr int SM_MAX = SM_MEM + 11264;
#define MEM_BLK(q) ((q) / 3 * 4096 + (q) % 3 * 1024)
constexpr int SM_TOTAL = 229376;
constexpr int MB_W = SM_MISC;
constexpr int MB_WO = SM_MISC + 24;
constexpr int MB_WO3 = SM_MISC + 32;
constexpr int MB_X = SM_MISC + 40;
constexpr int MB_S = SM_MISC + 64;
constexpr int MB_F = SM_MISC + 72;
constexpr int MB_VX = SM_MISC + 80;
constexpr int SC_FPAR = SM_MISC + 136;
constexpr int SC_DEAD = SM_MISC + 96;
constexpr int SC_UNSC = SM_MISC + 112;
constexpr int SC_EPOCH = SM_MISC + 128;
constexpr int SC_EXPW = SM_MISC + 132;
constexpr int SC_ONES = SM_MISC + 144;
constexpr int SC_SS = SM_MISC + 160;
constexpr int SC_LAT = SM_MISC + 224;
constexpr int MB_T = SM_MISC + 232;
constexpr int T_SX = SM_X + XT;
constexpr int T_OB = SM_X + 2 * XT;
constexpr int T_WA = T_OB + 16384;
constexpr int T_OA = T_WA + 9216;
constexpr int T_G = T_OA + 4096;
constexpr int T_P = T_G + 512;
constexpr int T_UN = T_G + 256;
constexpr int T_RED = 131072;
constexpr int SC_XMAX = SM_MISC + 256;
constexpr int SC_PROF = 229376;

constexpr float SM_SCALE = 0.08838834764831845f;
constexpr float LOG2E = 1.4426950408889634f;
constexpr float E_LIM = 20.f;

template <bool B> struct BoolC { static constexpr bool value = B; };
struct RMaps { CUtensorMap x, wq, wk, wv, wo, woa, oa; unsigned char* red; bf16* out; uint32_t poll; };

DI uint32_t latest_hint(uint32_t h, uint32_t d, int s) {
  const uint32_t x = (((h | 0xc0c0c0c0u) - ((d >> 5) & 63) * 0x01010101u) & 0x3f3f3f3fu) | ((h ^ (((s >> 2) + 1) & 3) * 0x40404040u) & 0xc0c0c0c0u);
  const uint32_t y = __vmaxu2(x & 0x00ff00ffu, (x >> 8) & 0x00ff00ffu);
  return __reduce_max_sync(0xffffffffu, max(y & 0xffffu, y >> 16));
}
DI uint32_t near_half(uint32_t sb) {
  uint32_t a, b; lds64(sb + SC_LAT, a, b);
  return a > b;
}

template <int RT, int K0, int K1, bool D32 = false, int BAR = 0, int KB = 18>
DI void xproj(float* acc, const uint32_t (&wa)[2][18][4], uint64_t xd) {
  if (XP & 1) return;
  WG_FENCE();
#pragma unroll
  for (int k = K0; k < ((XP & 128) ? K0 + 1 : K1); k++)
  {
    uint64_t d = xd + (uint64_t)(((k >> 1) * 4096 + (k & 1) * 32) >> 4);
    if (D32) asm("mov.b64 %0, {%1, %2};" : "=l"(d) : "r"((uint32_t)xd + (((k >> 1) * 4096 + (k & 1) * 32) >> 4)), "r"((uint32_t)(xd >> 32)));
    wgmma_n32_rs(acc, wa[RT][k][0], wa[RT][k][1], wa[RT][k][2], wa[RT][k][3], d, k != 0);
    if (BAR && k == KB - 1 && KB < 18) bar_arrive(BAR, 256);
  }
  WG_COMMIT();
}

DI void seg_store(int seg, uint32_t sb, uint32_t off, uint32_t bytes) {
  asm volatile("cp.async.bulk.global.shared::cta.bulk_group [%0], [%1], %2;"
               :: "l"(g_seg + ((size_t)(seg % NRING) * 96 + blockIdx.x) * SEGB + off), "r"(sb + SM_BLK + (seg & 3) * SEGB + off), "r"(bytes) : "memory");
  asm volatile("cp.async.bulk.commit_group;" ::: "memory");
}
DI void seg_publish(int seg) {
  asm volatile("cp.async.bulk.wait_group 0;" ::: "memory");
  asm volatile("red.relaxed.gpu.global.add.u32 [%0], 1;" :: "l"(&g_scnt[(seg * 32 + blockIdx.x / 3) * 8]) : "memory");
  SSTAMP(10, seg);
}

#define NAP 64
DI uint32_t movm(uint32_t x) { uint32_t r; asm volatile("movmatrix.sync.aligned.m8n8.trans.b16 %0, %1;" : "=r"(r) : "r"(x)); return r; }
DI bool wait_count(const unsigned* p, unsigned target, bool nap = true) {
  int n = 0;
  unsigned v;
  while (true) {
    asm volatile("ld.acquire.gpu.global.b32 %0, [%1];" : "=r"(v) : "l"(p) : "memory");
    if ((int)(v - target) >= 0 || ++n > SPIN_LIMIT) break;
    if (nap) __nanosleep(NAP);
  }
  return n;
}
#define PACE 1200
#define PORD 0
DI void load_weights(uint32_t sb, const RMaps& tm, uint32_t rank, int c) {
  const int h = blockIdx.x / 3;
  if (c < 3) {
    mbar_expect(sb + MB_W + 8 * c, 49152);
    tma_load(sb + SM_STAGE + c * 49152, rank < 2 ? &tm.wk : &tm.wv, h * DH + (rank == 1 ? 64 : 0), c * 192, sb + MB_W + 8 * c);
    tma_load(sb + SM_STAGE + c * 49152 + 24576, rank < 2 ? &tm.wq : &tm.wv, h * DH + (rank == 0 ? 0 : 64), c * 192, sb + MB_W + 8 * c);
  } else {
    tma_prefetch(&tm.wo, rank * 192, h * DH);
    mbar_expect(sb + MB_WO, 16384);
    mbar_expect(sb + MB_WO3, 32768);
    tma_load(sb + SM_WOST, &tm.wo, rank * 192 + 64, h * DH, sb + MB_WO3);
    tma_load(sb + SM_WO3, &tm.wo, rank * 192 + 128, h * DH, sb + MB_WO3);
  }
}

DI void tail_attention(const uint32_t sb, const uint32_t rank, const int w, const int lane, const int sg, const int bar) {
  const int m = lane >> 3, g = lane >> 2, t = lane & 3;
  const uint32_t l16 = sb + lane * 16, src = l16 + T_SX + sg * 10240 + w * 1280;
  if (rank < 2) {
    const uint32_t base = l16 + SM_BLK + (2 + sg) * SEGB, dst = src + rank * 5120;
    uint32_t qb[2][4];
    ldsm4t(qb[0], base + w * 1024); ldsm4t(qb[1], base + w * 1024 + 512);
#pragma unroll
    for (int j = 0; j < 3; j++) {
      uint32_t kb[4][4];
      float c[4][4];
      const uint32_t ka = base + 4096 + j * 2048 + (m & 1) * (j == 2 ? 128 : 896) - (m >> 1) * 128;
#pragma unroll
      for (int k = 0; k < 4; k += j == 2 ? 2 : 1) ldsm4t(kb[k], ka + k * 256);
      mma16816z(c[0], kb[0], qb[0][0], qb[0][1]); mma16816z(c[1], kb[j == 2 ? 0 : 1], qb[0][2], qb[0][3]);
      mma16816z(c[2], kb[2], qb[1][0], qb[1][1]); mma16816z(c[3], kb[j == 2 ? 2 : 3], qb[1][2], qb[1][3]);
      uint32_t r[4];
#pragma unroll
      for (int i = 0; i < (j == 2 ? 2 : 4); i++) r[i] = __float_as_uint((c[0][i] + c[1][j == 2 ? i + 2 : i]) + (c[2][i] + c[3][j == 2 ? i + 2 : i]));
#pragma unroll
      for (int d = 0; d < 2; d++) {
        const uint32_t to = d ? 2 : rank ^ 1, mb = mapa(sb + MB_T + 8 + 8 * sg, to);
        if (j < 2) st_async4(mapa(dst + j * 512, to), r[0], r[1], r[2], r[3], mb);
        else st_async2(mapa(dst + 1024 - lane * 8, to), r[0], r[1], mb);
      }
      if (j < 2) sts128(dst + j * 512, r[0], r[1], r[2], r[3]); else sts64(dst + 1024 - lane * 8, r[0], r[1]);
    }
  }
  TSTAMP(50 + 2 * sg);
  uint32_t vx[4][4], vm[4];
  const uint32_t va = l16 + (rank < 2 ? SM_VC + sg * 8192 : SM_BLK + (2 + sg) * SEGB) + w * 1024 + (m & 1) * 384 - (m >> 1) * 128;
#pragma unroll
  for (int i = 0; i < 4; i++) ldsm4(vx[i], va + (i & 1) * 4096 + (i >> 1) * 256);
  if (sg && rank < 2) mbar_wait(sb + MB_T, 0);
  lds128(l16 + (sg ? SM_FB : SM_VM) + w * 512, vm);
  float a[10], b[10];
  mbar_wait(sb + MB_T + 8 + 8 * sg, 0);
  TSTAMP(58 + 2 * sg);
  lds128f(src, a); lds128f(src + 512, a + 4); lds64f(src + 1024 - lane * 8, a + 8);
  lds128f(src + 5120, b); lds128f(src + 5632, b + 4); lds64f(src + 6144 - lane * 8, b + 8);
#pragma unroll
  for (int i = 0; i < 10; i++) {
    a[i] = (a[i] + b[i]) * (SM_SCALE * LOG2E);
    if (i < 8 && (i >> 1) * 8 + g > w * 8 + 2 * t + (i & 1)) a[i] = -1.0e9f * LOG2E;
  }
  float m0 = fmaxf(fmaxf(fmaxf(a[0], a[2]), fmaxf(a[4], a[6])), a[8]), m1 = fmaxf(fmaxf(fmaxf(a[1], a[3]), fmaxf(a[5], a[7])), a[9]);
#pragma unroll
  for (int o = 4; o < 32; o <<= 1) { m0 = fmaxf(m0, __shfl_xor_sync(0xffffffffu, m0, o)); m1 = fmaxf(m1, __shfl_xor_sync(0xffffffffu, m1, o)); }
#pragma unroll
  for (int i = 0; i < 10; i++) a[i] = ex2(a[i] - (i & 1 ? m1 : m0));
  float s0 = ((a[0] + a[2]) + (a[4] + a[6])) + a[8], s1 = ((a[1] + a[3]) + (a[5] + a[7])) + a[9];
#pragma unroll
  for (int o = 4; o < 32; o <<= 1) { s0 += __shfl_xor_sync(0xffffffffu, s0, o); s1 += __shfl_xor_sync(0xffffffffu, s1, o); }
  s0 = rcp(s0); s1 = rcp(s1);
#pragma unroll
  for (int i = 0; i < 5; i++) sts32(sb + T_P + sg * 2560 + w * 640 + i * 128 + lane * 4, pack_bf16(a[2 * i] * s0, a[2 * i + 1] * s1));
  mbar_wait(sb + MB_WO, 1);
  bar_sync(bar, 128);
  TSTAMP(59 + 2 * sg);
#pragma unroll
  for (int j = 0; j < 4; j++) {
    uint32_t p[5];
    float o0[4], o1[4], f[2];
    lds64f(sb + T_G + sg * 128 + j * 32 + t * 8, f);
    f[0] = 1.f - f[0]; f[1] = 1.f - f[1];
    ldsm4t(p, l16 + T_P + sg * 2560 + j * 640);
    asm volatile("ldmatrix.sync.aligned.m8n8.x1.trans.shared.b16 {%0}, [%1];" : "=r"(p[4]) : "r"(l16 + T_P + sg * 2560 + j * 640 + 512) : "memory");
    mma16816z(o0, vx[0], p[0], p[1]); mma16816z(o1, vx[1], p[0], p[1]);
    mma16816(o0, vx[2], p[2], p[3]); mma16816(o1, vx[3], p[2], p[3]);
    mma1688(o0, vm[0], vm[1], p[4]); mma1688(o1, vm[2], vm[3], p[4]);
    stsm4(l16 + T_OB + sg * 8192 + j * 2048 + w * 512, pack_bf16(o0[0] * f[0], o0[1] * f[1]), pack_bf16(o0[2] * f[0], o0[3] * f[1]),
          pack_bf16(o1[0] * f[0], o1[1] * f[1]), pack_bf16(o1[2] * f[0], o1[3] * f[1]));
  }
}

DI void proj_role(const uint32_t sb, const RMaps& tm, const uint32_t rank, const int wg, const int w, const int lane) {
  const bool qk = rank < 2;
  uint32_t wa[2][18][4];
  {
    const int rr = (lane & 7) + ((lane >> 4) << 3);
    const uint32_t col = ((2 * w + ((lane >> 3) & 1)) ^ (lane & 7)) << 4;
    float ss = 0.f;
#pragma unroll
    for (int c = 0; c < 3; c++) {
      mbar_wait(sb + MB_W + 8 * c, 0);
      if (threadIdx.x == 0) SSTAMP(11, c);
#pragma unroll
      for (int rt = 0; rt < 2; rt++)
#pragma unroll
        for (int k = 0; k < 6; k++)
          ldsm4t(wa[rt][c * 6 + k], sb + SM_STAGE + c * 49152 + (rt ^ wg) * 24576 + (64 * (k >> 1) + 32 * wg + 16 * (k & 1) + rr) * 128 + col);
      if (c < 2) {
        fence_async();
        bar_sync(3, 256);
        if (threadIdx.x == 0) {
          if (c == 0) tma_load3(sb + SM_X + XT, &tm.x, 32, sb + MB_X + 8);
          else { tma_load(sb + SM_X + 2 * XT, &tm.wo, rank * 192, (blockIdx.x / 3) * DH, sb + MB_WO); SSTAMP(11, 11); }
        }
        __syncwarp();
      }
      uint32_t q[4] = {0, 0, 0, 0};
#pragma unroll
      for (int rt = 0; rt < 2; rt++)
#pragma unroll
        for (int k = 0; k < 6; k++)
#pragma unroll
          for (int i = 0; i < 4; i++) sq_acc(q[i], wa[rt][c * 6 + k][i]);
#pragma unroll
      for (int i = 0; i < 4; i++) ss += bf_lo(q[i]) + bf_hi(q[i]);
    }
    ss = warp_sum(ss);
    fence_async();
    cluster_arrive();
    if (lane == 0) sts32(sb + SC_SS + 4 * (wg * 4 + w), qk ? 0 : __float_as_uint(ss));
    bar_arrive(11, 384);
  }
  STAMP(1);
  mbar_wait(sb + MB_X, 0);
  STAMP(2);

  uint32_t t16 = sb + (w * 32 + lane) * 16;
  uint32_t mem_a = sb + SM_MEM + wg * 512 + lane * 16;
  uint32_t fin_a = sb + (lane & 7) * 16 + SM_BLK + (qk ? (wg ^ 1) * 4096 + w * 256 + (lane & 8) * 16 + (lane & 16) * 64
                                              : wg * 4096 + w * 1024 + (lane & 8) * 64 + (lane & 16) * 8);
  PIN(t16); PIN(mem_a); PIN(fin_a);
  const uint32_t fence_reg = mem_a;
  const uint32_t fin2 = qk ? 2048 : 256;
  float acc[16];
  const uint64_t xd0 = make_desc(sb + SM_X + wg * 64, 16, 1024, 1);
  auto do_export = [&]() {
    WG_WAIT(0);
    uint32_t q[8];
#pragma unroll
    for (int j = 0; j < 8; j++) q[j] = pack_bf16(acc[2 * j], acc[2 * j + 1]);
    sts128(t16 + SM_EXP + wg * 4096, q[0], q[1], q[2], q[3]);
    sts128(t16 + SM_EXP + wg * 4096 + 2048, q[4], q[5], q[6], q[7]);
    if (RET) asm volatile("{\n.reg .pred p;\nsetp.eq.u32 p, %2, 0;\n@p add.u32 %0, %0, 1;\n@p add.u32 %1, %1, 1;\nsetp.eq.and.u32 p, %0, %1, p;\n@p exit;\n}"
                          : "+r"(q[3]), "+r"(q[7]) : "r"(t16) : "memory");
  };
  uint32_t o[8];
  auto import = [&]() { lds128(t16 + SM_EXP + (wg ^ 1) * 4096, o); lds128(t16 + SM_EXP + (wg ^ 1) * 4096 + 2048, o + 4); };
  auto finish = [&](int seg) {
    const uint32_t a = fin_a + (seg & 3) * SEGB;
    WG_WAIT(0);
#pragma unroll
    for (int i = 0; i < 8; i++) o[i] = FIN16 ? add_bf16(pack_bf16(acc[2 * i], acc[2 * i + 1]), o[i]) : pack_bf16(acc[2 * i] + bf_lo(o[i]), acc[2 * i + 1] + bf_hi(o[i]));
    stsm4(a, o[0], o[1], o[2], o[3]);
    stsm4(a + fin2, o[4], o[5], o[6], o[7]);
  };
  auto send_v = [&](int seg, int dst) {
    fence_async();
    if (seg < NSEG && !(XP & 2) && elect_one())
      bulk_s2s(mapa(sb + SM_VC + (seg & 1) * 8192, dst), sb + SM_BLK + (seg & 3) * SEGB, 8192, mapa(sb + MB_VX + (seg & 1) * 8, dst));
    __syncwarp();
  };
  auto wait_v = [&](int seg) {
    if (seg < NSEG && !(XP & 2)) {
      mbar_wait(sb + MB_VX + (seg & 1) * 8, (seg >> 1) & 1);
      if (elect_one()) mbar_expect(sb + MB_VX + (seg & 1) * 8, 8192);
      __syncwarp();
    }
  };
  bar_sync(3, 256);
  xproj<1, 0, 18>(acc, wa, xd0);
  do_export();
  SCHED_FENCE(11);
  xproj<0, 0, 18>(acc, wa, xd0);
  bar_sync(3, 256);
  if (threadIdx.x == 0) SSTAMP(11, 12);
  cluster_wait();
  if (threadIdx.x == 0) SSTAMP(11, 13);
  mbar_wait(sb + MB_X + 8, 0);
  import();
  finish(0);
  SCHED_FENCE(12);
  bar_sync(3, 256);
  uint64_t dA = xd0 + (XT >> 4);
  xproj<1, 0, 18>(acc, wa, dA);
  if (!qk && wg == 0 && w < 2) send_v(0, w);
  do_export();
  if (qk && wg == 0 && w == 0) wait_v(0);
  bar_arrive(13, 384);
  if (!qk) {
    SCHED_FENCE(15);
    xproj<0, 0, 18>(acc, wa, dA);
    if (threadIdx.x == 0 && !(XP & 8)) { mbar_expect(sb + MB_X, XT); tma_load3(sb + SM_X, &tm.x, 96, sb + MB_X); }
    bar_sync(3, 256);
    mbar_wait(sb + MB_X + 16, 0);
    import();
    finish(1);
    SCHED_FENCE(16);
    bar_sync(3, 256);
    dA += XT >> 4;
    xproj<1, 0, 18>(acc, wa, dA);
    if (wg == 0 && ((w == 0 && VS0) || (w == 1 && VS1))) send_v(1, w);
    do_export();
  }
  if (threadIdx.x == 0) SSTAMP(11, 14);
  bar_sync(0, 384);
  const int ro = __shfl_sync(0xffffffffu, near_half(sb) ^ wg, 0);
  STAMP(5);
  const uint32_t always = __shfl_sync(0xffffffffu, lds32(sb + SC_DEAD + 12), 0);
  const int ah = qk ? 1 : 2;
  int b2 = qk ? 2 : 0;
  int s = 0;
  uint32_t hint_lo = (uint32_t)(uint64_t)tm.red + HINT_OFF + blockIdx.x + (lane & 1) * 4096 + (lane >> 1) * 16384;
  PIN(hint_lo);
  auto post_hint = [&]() {
    asm volatile("{\n.reg .pred p;\n.reg .b64 a;\n.reg .u32 t;\nsetp.lt.u32 p, %0, %1;\nmov.b64 a, {%2, %3};\nmov.u32 t, %%globaltimer_lo;\n"
                 "bfe.u32 t, t, 5, 6;\nor.b32 t, t, %4;\n@p st.relaxed.gpu.global.u8 [a], t;\n}"
                 :: "r"(t16), "r"(sb + 128), "r"(hint_lo + RED_SLOT(s)), "r"((uint32_t)((uint64_t)tm.red >> 32)), "r"(((s >> 2) + 1) << 6) : "memory");
  };
  auto memproj = [&](auto second, int id, float u0, float u1, float* r) {
    constexpr bool R1 = decltype(second)::value;
    uint32_t b[NUP][4], b0[4];
    SCHED_FENCE(id);
    bar_sync(R1 ? 2 : 1, 256);
    PROF(0);
    ldsm4t(b0, mem_a);
#pragma unroll
    for (int q = 0; q < NUP; q++) {
      if (R1 && q == 2) {
        bar_sync(11, 256);
        SCHED_FENCE(id + 1);
      }
      ldsm4t(b[q], mem_a + MEM_BLK(q + 1));
    }
    mma16816z(&acc[0], wa[0][0], b0[0], b0[1]);
    mma16816z(&acc[4], wa[1][0], b0[0], b0[1]);
    mma16816z(&acc[8], wa[0][1], b0[2], b0[3]);
    mma16816z(&acc[12], wa[1][1], b0[2], b0[3]);
#pragma unroll
    for (int q = 1; q < 9; q++) {
      uint32_t* const c = b[(q - 1) % NUP];
      mma16816(&acc[0], wa[0][2 * q], c[0], c[1]);
      mma16816(&acc[4], wa[1][2 * q], c[0], c[1]);
      mma16816(&acc[8], wa[0][2 * q + 1], c[2], c[3]);
      mma16816(&acc[12], wa[1][2 * q + 1], c[2], c[3]);
      if (R1 && q + NUP == B3Q) bar_sync(3, 256);
      if (q + NUP < 9) ldsm4t_in(c, mem_a + MEM_BLK(q + NUP), always);
      else if (R1 && q + NUP < 11) lds128_in(c, t16 + SM_PART + (10 - q - NUP) * 2048, always);
      else if (!R1 && GATE && q == GATE) { bar_arrive(11, 256); lds128_in(c, sb + SC_DEAD, always); u0 = u1 = __uint_as_float(c[3]); }
    }
#pragma unroll
    for (int i = 0; i < 8; i++) {
      const float u = i < 4 ? u0 : u1;
      r[i] = R1 ? fmaf(acc[8 + i], u, (acc[i] + __uint_as_float(b[(8 + i / 4) % NUP][i & 3])) * u) : (GATE ? fmaf(acc[i], u, acc[8 + i]) : acc[i] + acc[8 + i]);
    }
  };
  if (ro == 0) {
    auto set_scale = [&]() {
      uint32_t m[8];
      lds128(t16 + SM_MAX - 512, m); lds128(t16 + SM_MAX, m + 4);
      const int em = (wexp(amax4(amax4(*(const __half2*)&m[0], m), m + 4)) >> 3) + (int)(lds32(sb + SC_UNSC + (s & 1) * 8) >> 23) - 15;
      const int ex = max(s ? em : 0, (int)lds32(sb + SC_XMAX + 4 * s)) - 127 + (int)lds32(sb + SC_EXPW);
      sts32(sb + SC_UNSC + (~s & 1) * 8, (127 + min(max(ex, -120), 120)) << 23);
    };
#pragma unroll 1
    while (true) {
      if (s == 8) STAMP(6);
      float r[8];
      memproj(BoolC<false>(), 30, 0.f, 0.f, r);
      sts128(t16 + SM_PART, __float_as_uint(r[0]), __float_as_uint(r[1]), __float_as_uint(r[2]), __float_as_uint(r[3]));
      sts128(t16 + SM_PART + 2048, __float_as_uint(r[4]), __float_as_uint(r[5]), __float_as_uint(r[6]), __float_as_uint(r[7]));
      bar_arrive(3, 256);
      PROF(1);
      bar_sync(9, 256);
      if (s == NSEG - 1) break;
      post_hint();
      if (w == 1) {
        set_scale();
        __syncwarp();
        if (elect_one()) mbar_arrive(sb + MB_S);
      }
      SCHED_FENCE(9);
      bar_sync(5, qk ? N5 : 256);
      PROF(2);
      import();
      xproj<0, 0, NII, (DD & 1) != 0>(acc, wa, dA);
      if (NII < 18) {
        if (qk) bar_sync(7, 384);
        xproj<0, NII, 18>(acc, wa, dA);
        if (!qk) bar_sync(7, 384);
      } else {
        if (F10) WG_WAIT(0);
        bar_sync(10, 256);
        if (F10) SCHED_FENCE(17);
      }
      dA += (int64_t)(b2 ? XT >> 4 : -(XT >> 3));
      finish(s + ah);
      if (qk || !VLATE(w)) bar_arrive(13, 384);
      PROF(6);
      SCHED_FENCE(14);
      bar_sync(12, 256);
      PROF(7);
      xproj<1, 0, 18, (DD & 2) != 0, 14, N14>(acc, wa, dA);
      if (N14 == 18) bar_arrive(14, 256);
      b2 = b2 == 2 ? 0 : b2 + 1;
      s++;
      if (!qk && VLATE(w)) { bar_sync(13, 384); send_v(s + 1, w); }
      PROFP(8);
      do_export();
      s--; RSTAMP(6); s++;
      PROFP(3);
    }
    if (!qk) bar_arrive(5, 256);
    if (w == 0 && elect_one()) {
      const uint32_t h18 = blockIdx.x / 3 * 18;
      mbar_expect(sb + MB_WO, 9216 + 4096 + 256);
      asm volatile("cp.async.bulk.shared::cluster.global.mbarrier::complete_tx::bytes [%0], [%1], 256, [%2];"
                   :: "r"(sb + T_G), "l"(g_gate + NAUXSEG * 32), "r"(sb + MB_WO) : "memory");
      tma_load(sb + T_OA, &tm.oa, 4096 + (h18 & ~7), NAUXSEG * 32, sb + MB_WO);
#pragma unroll 1
      for (int j = 0; j < 3; j++) tma_load(sb + T_WA + j * 3072, &tm.woa, rank * 192 + j * 64, h18, sb + MB_WO);
    }
    if (w == 1) {
      set_scale();
      __syncwarp();
      const int ea = (int)ldg_relaxed32(&g_amax[0]) + (int)ldg_relaxed32(&g_amax[16]) - 254 + 2 + 10 - 15;
      sts32(sb + T_UN + (lane & 1) * 4, (128 + max(min(ea, 120), (int)(lds32(sb + SC_UNSC + 8 - (lane & 1) * 8) >> 23) - 127)) << 23);
    }
    bar_arrive(8, 256);
  } else {
    uint32_t r0;
    float un;
    auto prepare = [&]() {
      un = __uint_as_float(lds32(sb + SC_UNSC + (s & 1) * 8));
      r0 = qk ? (t16 & ~256u) - w * 256 + (((t16 >> 8) ^ wg) & 1 ? SM_QM : SM_BLK + 8192 + (s & 3) * SEGB) : mapa(t16 + (s < NSEG - 1 ? SM_VM : SM_FB), 0);
      PIN(r0); PIN(un);
    };
    prepare();
#pragma unroll 1
    while (true) {
      if (s == 8) STAMP(6);
      float r[8];
      if (qk) {
        const float u0 = wg ? un * (SM_SCALE * LOG2E) : un, u1 = wg ? un : un * (SM_SCALE * LOG2E);
        memproj(BoolC<true>(), 32, u0, u1, r);
        stsm4(r0, pack_bf16(r[0], r[1]), pack_bf16(r[2], r[3]), pack_bf16(r[4], r[5]), pack_bf16(r[6], r[7]));
        bar_arrive(4, 256);
      } else {
        const uint32_t mb = sb + (s < NSEG - 1 ? MB_S : MB_T), r1 = r0 + (1 << 24);
        memproj(BoolC<true>(), 34, un, un, r);
        const uint32_t p0 = pack_bf16(r[0], r[1]), p1 = pack_bf16(r[2], r[3]), p2 = pack_bf16(r[4], r[5]), p3 = pack_bf16(r[6], r[7]);
        const uint32_t v0 = wg ? p2 : p0, v1 = wg ? p3 : p1, v2 = wg ? p0 : p2, v3 = wg ? p1 : p3;
        st_async4(r0, v0, v1, v2, v3, mapa(mb, 0));
        st_async4(r1, v0, v1, v2, v3, mapa(mb, 1));
        bar_arrive(5, 256);
        sts128(r0 + (2 << 24), v0, v1, v2, v3);
        stsm4((t16 & ~256u) - w * 256 + SM_BLK + 8192 + (s & 3) * SEGB + (((t16 >> 8) ^ wg) & 1) * 1024, p0, p1, p2, p3);
        __syncwarp();
        if (elect_one()) mbar_arrive(sb + MB_S);
      }
      if (s == NSEG - 1) break;
      if (!qk) bar_arrive(15, 160);
      PROF(1);
      auto rearm = [&]() { mbar_wait(sb + MB_S, s & 1); if (elect_one()) mbar_expect(sb + MB_S, qk ? 640 + 2048 : 1280); __syncwarp(); };
      if (w == 1) {
        if ((t16 & 384) == 0) stg_relaxed(tm.red + (RED_SLOT(s + 2) + RED_LINE(blockIdx.x)) + (t16 & 112), 0, 0, 0, 0);
      } else if (w == 0) {
        const int tn = s + ah + 1;
        if (RFW) mbar_wait(sb + MB_S, s & 1);
        if (tn + 1 < NSEG && !(XP & 8) && elect_one()) {
          const int b0 = b2 == 2 ? 0 : b2 + 1;
          mbar_expect(sb + MB_X + 8 * b0, XT);
          tma_load3(sb + SM_X + b0 * XT, &tm.x, (tn + 1) * 32, sb + MB_X + 8 * b0);
        }
        if (tn < NSEG && (!(XP & 8) || tn < 3)) mbar_wait(sb + MB_X + 8 * b2, (tn / 3) & 1);
      } else if (w == 2) {
        if (!qk) { if (VS0 == 0) send_v(s + 1, 0); if (VS1 == 0) send_v(s + 1, 1); }
      } else if (qk || !NIC) {
        rearm();
      }
      __syncwarp();
      import();
      PROF(4);
      SCHED_FENCE(10);
      if (NIC) {
        if (qk) bar_sync(7, NII < 18 ? 384 : 256);
        xproj<0, 0, NIC>(acc, wa, dA);
        if (!qk) { if (w == 3) rearm(); bar_sync(7, NII < 18 ? 384 : 256); }
      } else {
        bar_sync(7, NII < 18 ? 384 : 256);
      }
      xproj<0, NIC, 18, (DD & 4) != 0, 12, N12>(acc, wa, dA);
      if (N12 == 18) bar_arrive(12, 256);
      dA += (int64_t)(b2 ? XT >> 4 : -(XT >> 3));
      finish(s + ah);
      if (qk && w == 0) wait_v(s + 1);
      bar_arrive(13, 384);
      PROF(6);
      SCHED_FENCE(13);
      bar_sync(14, 256);
      PROF(7);
      xproj<1, 0, 18, (DD & 8) != 0>(acc, wa, dA);
      b2 = b2 == 2 ? 0 : b2 + 1;
      s++;
      if (HOIST) prepare();
      PROFP(8);
      do_export();
      if (!HOIST) prepare();
      s--; RSTAMP(7); s++;
      PROFP(3);
    }
    TSTAMP(2);
    bar_sync(3, 128);
    tail_attention(sb, rank, w, lane, 1, 3);
    bar_arrive(0, 256);
  }
  STAMP(3);
  if (CSY) cluster_sync();
  STAMP(4);
}

DI void attn_role(const uint32_t sb, unsigned char* smem_raw, const RMaps& tm, const uint32_t RANK, const bf16* __restrict__ x, const bf16* __restrict__ mem0,
                  const int w, const int lane) {
  const int t2 = w * 32 + lane;
  uint32_t wo[8][4], w1[8][4];
  const uint32_t wo_lane = sb + ((lane & 7) + ((lane >> 4) << 3)) * 128 + (((w + 4 * ((lane >> 3) & 1)) ^ (lane & 7)) << 4);
  unsigned char* const g_red = tm.red;
  {
    const uint32_t tag = *(volatile unsigned*)&g_epoch + 1;
    if (w == 0) {
      stg_relaxed(g_red + RED_SLOT(t2 >> 3) + RED_LINE(blockIdx.x) + (t2 & 7) * 16, 0, 0, 0, 0);
      stg_relaxed(g_red + T_RED + blockIdx.x * 1024 + t2 * 16, 0, 0, 0, 0);
      stg_relaxed(g_red + T_RED + blockIdx.x * 1024 + 512 + t2 * 16, 0, 0, 0, 0);
      asm volatile("st.relaxed.gpu.global.u8 [%0], 0;" :: "l"(g_red + RED_SLOT(t2) + HINT_OFF + (t2 & 4) * 1024 + (t2 >> 3) * 16384 + blockIdx.x) : "memory");
    }
    uint4 xv[18];
    uint32_t mv[20];
#pragma unroll
    for (int i = 0; i < 20; i++) mv[i] = i < 18 ? ((const uint32_t*)mem0)[(lane >> 2) * (DM / 2) + (w * 18 + i) * 4 + (lane & 3)] : 0;
#pragma unroll
    for (int i = 0; i < 18; i++) xv[i] = blockIdx.x < NSEG ? ((const uint4*)(x + blockIdx.x * 32 * DM))[t2 + 128 * i] : make_uint4(0, 0, 0, 0);
    bar_sync(0, 384);
    cluster_arrive();
    if (PACE && w == 3) {
      const uint32_t t0 = gtime();
#pragma unroll 1
      for (int c = 1; c < 4; c++) {
        wait_until(t0 + c * PACE);
        if (elect_one()) load_weights(sb, tm, RANK, PORD ? (c == 1 ? 3 : c - 1) : c);
        __syncwarp();
      }
    }
    __half2 hx = __float2half2_rn(0.f);
#pragma unroll
    for (int i = 0; i < 18; i++) hx = amax4(hx, &xv[i].x);
    if (blockIdx.x == 0)
#pragma unroll
      for (int i = 0; i < 5; i++) hx = amax4(hx, &mv[4 * i]);
    sts32(sb + SC_SS + 4 * (12 + w), wexp(hx));
    if (t2 == 0) { sts32(sb + SC_EPOCH, (tag - 1) * NSEG + 2 - NRING); sts32(sb + SC_UNSC, __float_as_uint(1.f)); sts128(sb + SC_DEAD, 0, 0, 0, 0x3f800000u); sts64(sb + SC_FPAR, 0, 0); sts128(sb + SC_ONES, 0x3f803f80u, 0x3f803f80u, 0x3f803f80u, 0x3f803f80u); }
    WSTAMP(27);
    if (w == 0) __threadfence();
    uint32_t q[8] = {0, 0, 0, 0, 0, 0, 0, 0};
    mbar_wait(sb + MB_WO3, 0);
    if (t2 == 0) SSTAMP(11, 3);
#pragma unroll
    for (int k = 0; k < 8; k++) {
      ldsm4t(wo[k], wo_lane + SM_WO3 + k * 2048); ldsm4t(w1[k], wo_lane + SM_WOST + k * 2048);
#pragma unroll
      for (int i = 0; i < 4; i++) { sq_acc(q[i], wo[k][i]); sq_acc(q[i], w1[k][i]); }
    }
    bar_sync(6, 128);
    if (t2 == 0) SSTAMP(11, 7);
#pragma unroll
    for (int k = 0; k < 8; k++) sts128(sb + SM_WO3 + t2 * 16 + k * 2048, wo[k][0], wo[k][1], wo[k][2], wo[k][3]);
#pragma unroll
    for (int i = 0; i < 5; i++) {
      const int j = w * 18 + 4 * i + (lane >> 3), c = i < 4 || lane < 16 ? j * 8 + j / 24 * 64 : 192;
      stsm4t(sb + SM_MEM + (c + (lane & 7)) * 16, mv[4 * i], mv[4 * i + 1], mv[4 * i + 2], mv[4 * i + 3]);
    }
    bar_arrive(1, 256); bar_arrive(2, 256); bar_arrive(9, 256);
    if (t2 == 0) SSTAMP(11, 8);
    mbar_wait(sb + MB_WO, 0);
    if (t2 == 0) SSTAMP(11, 4);
#pragma unroll
    for (int k = 0; k < 8; k++) ldsm4t(wo[k], wo_lane + SM_X + 2 * XT + k * 2048);
    fence_async();
    bar_sync(6, 128);
    if (t2 == 32) tma_load3(sb + SM_X + 2 * XT, &tm.x, 64, sb + MB_X + 16);
    __syncwarp();
#pragma unroll
    for (int k = 0; k < 8; k++)
#pragma unroll
      for (int i = 0; i < 4; i++) sq_acc(q[4 + i], wo[k][i]);
    float ss = 0.f;
#pragma unroll
    for (int i = 0; i < 8; i++) ss += bf_lo(q[i]) + bf_hi(q[i]);
    ss = warp_sum(ss);
    if (lane == 0) sts32(sb + SC_SS + 4 * (8 + w), __float_as_uint(ss));
    if (t2 == 0) SSTAMP(11, 9);
    bar_sync(11, 384);
    if (t2 == 0) SSTAMP(11, 10);
    if (t2 == 0) {
      float a[16];
#pragma unroll
      for (int i = 0; i < 4; i++) lds128f(sb + SC_SS + 16 * i, &a[4 * i]);
      stg_relaxed(&g_stats[blockIdx.x * 2], __float_as_uint(((a[0] + a[1]) + (a[2] + a[3])) + ((a[4] + a[5]) + (a[6] + a[7]))),
                  __float_as_uint((a[8] + a[9]) + (a[10] + a[11])),
                  max(max(__float_as_uint(a[12]), __float_as_uint(a[13])), max(__float_as_uint(a[14]), __float_as_uint(a[15]))), tag);
    }
    __syncwarp();
    WSTAMP(24);
    cluster_wait();
    if (w == 0) {
      uint4 v[3];
      int n = 0;
      while (true) {
#pragma unroll
        for (int i = 0; i < 3; i++) v[i] = ldg_relaxed(&g_stats[(i * 32 + lane) * 2]);
        if (__all_sync(0xffffffffu, v[0].w == tag && v[1].w == tag && v[2].w == tag) || ++n > SPIN_LIMIT) break;
        __nanosleep(100);
      }
      WSTAMP(25);
      const float sv = warp_sum(__uint_as_float(v[0].x) + __uint_as_float(v[1].x) + __uint_as_float(v[2].x));
      const float so = warp_sum(__uint_as_float(v[0].y) + __uint_as_float(v[1].y) + __uint_as_float(v[2].y));
      const int expW = ((int)(__float_as_uint(sv) >> 23) + (int)(__float_as_uint(so) >> 23) - 254 + 2 + 10 + 1) >> 1;
      sts32(sb + SC_XMAX + 4 * lane, v[0].z); sts32(sb + SC_XMAX + 128 + 4 * lane, v[1].z);
      sts32(sb + SC_EXPW, expW + 1 - 15);
      if (blockIdx.x == 0 && lane == 0) *(volatile unsigned*)&g_epoch = tag;
      sts32(sb + SC_FPAR + 4, 1);
    } else if (w < 3) {
      const uint32_t u = blockIdx.x >> 4;
      unsigned char* const z = g_red + 98304 + (blockIdx.x & 15) * 128 + (u & 1) * 2048 + (u & 6) * 4096 + (((u >> 1) ^ w) & 1) * 4096 + lane * 4;
      stg_relaxed32(z, 0);
      uint32_t best = 0xffffffffu;
#pragma unroll 1
      for (int i = 0; i < 64; i++) {
        uint32_t last, dt;
        asm volatile("{\n.reg .pred p;\n.reg .u32 c, v;\nld.volatile.shared.u32 %0, [%3];\nmov.u32 c, %%clock;\n"
                     "atom.relaxed.gpu.global.exch.b32 v, [%2], 0;\nsetp.eq.u32 p, v, 0;\nmov.u32 %1, 0;\n@p mov.u32 %1, %%clock;\nsub.u32 %1, %1, c;\n}"
                     : "=r"(last), "=r"(dt) : "l"(z), "r"(sb + SC_FPAR + 4) : "memory");
        best = min(best, dt);
        if (last && i >= NPROBE - 1) break;
      }
      sts32(sb + SC_LAT + (w - 1) * 4, best);
    }
    bar_sync(13, 384);
    bar_arrive(0, 384);
    WSTAMP(26);
    TSTAMP(1);
  }

  const uint32_t nh = __shfl_sync(0xffffffffu, near_half(sb), 0);
  uint32_t l16 = sb + lane * 16;
  PIN(l16);
#define LV ((l16 >> 4) & 31)
#define fence_reg l16
  const uint32_t red_lo = (uint32_t)(uint64_t)g_red, red_hi = (uint32_t)((uint64_t)g_red >> 32);
  uint32_t lp;
  auto slot = [&](int s, uint32_t c, uint32_t ofs) {
    const uint32_t lo = lp | (red_lo + ((w >> 1) * 4 + (w & 1) * 2 + ((w ^ c) & 1)) * 4096 + RED_SLOT(s) + ofs);
    uint64_t a; asm("mov.b64 %0, {%1, %2};" : "=l"(a) : "r"(lo), "r"(red_hi));
    return (unsigned char*)a;
  };
  const uint32_t always = __shfl_sync(0xffffffffu, lds32(sb + SC_DEAD + 12), 0);
  const int mode0 = RANK < 2 ? w : w | 4;
  auto hint_addr = [&](int s) { return min(LV, 23u) * 4 + (red_lo + HINT_OFF + nh * 4096 + w * 16384 + RED_SLOT(s)); };
  auto load_hints = [&](uint32_t lo) {
    uint64_t a; asm("mov.b64 %0, {%1, %2};" : "=l"(a) : "r"(lo), "r"(red_hi));
    return ldg_relaxed32((const void*)a);
  };
  const uint32_t blk = RANK < 2 ? 9216 : SEGB;
  auto send_v = [&](int seg, int pos) {
    if (RANK == 2 && ((w == 0 && VS0 == pos) || (w == 1 && VS1 == pos)) && seg > 1 && seg < NSEG && !(XP & 2)) {
      if (elect_one()) {
        fence_async();
        bulk_s2s(mapa(sb + SM_VC + (seg & 1) * 8192, w), sb + SM_BLK + (seg & 3) * SEGB, 8192, mapa(sb + MB_VX + (seg & 1) * 8, w));
      }
      __syncwarp();
    }
  };
  uint32_t dl = __shfl_sync(0xffffffffu, gtime() - 768, 0);
  int s = 0;
  bool bad = false;
#pragma unroll 1
  while (true) {
    const uint32_t par = s & 1;
    uint32_t vx[4][4], oc[4], hints;
    if (HP == 2) { hints = hint_addr(s); PIN(hints); }
    auto load_vx = [&]() {
      const uint32_t va = l16 + (RANK < 2 ? SM_VC + par * 8192 : SM_BLK + (s & 3) * SEGB) + w * 1024 + ((LV >> 3) & 1) * 384 - (LV >> 4) * 128;
      if (WL & 4) lds128(sb + SC_ONES, oc);
#pragma unroll
      for (int i = 0; i < 4; i++) ldsm4(vx[i], va + (i & 1) * 4096 + (i >> 1) * 256);
    };
    auto retire = [&](uint32_t x) {
      asm volatile("{\n.reg .pred p;\nsetp.eq.u32 p, %0, 0;\n@p exit;\n}" :: "r"(vx[0][0] | vx[1][0] | vx[2][0] | vx[3][0] | x | ((WL & 4) ? oc[0] : 0)) : "memory");
    };
    auto scores = [&](auto memkeys, auto first, float* sc) {
      constexpr bool MK = decltype(memkeys)::value, FIRST = decltype(first)::value;
      uint32_t kb[4][4], qb[2][4];
      const uint32_t m = LV >> 3;
      uint32_t kaddr = l16 + SM_BLK + 4096 + (s & 3) * SEGB + w * 2048 + (m & 1) * (MK ? 128 : 896) - (m >> 1) * 128;
      if (MK) { PIN(kaddr); }
      else {
#pragma unroll
        for (int k = 0; k < 4; k++) ldsm4t(kb[k], kaddr + k * 256);
      }
      if (FIRST) { load_vx(); retire(MK ? kaddr : kb[0][0] | kb[1][0] | kb[2][0] | kb[3][0] | l16); bar_sync(4, 256); RSTAMP(4); PROF(4); }
      ldsm4t(qb[0], l16 + SM_QM);
      if (MK) ldsm4t(kb[0], kaddr);
      ldsm4t(qb[1], l16 + SM_QM + 512);
      if (MK) ldsm4t(kb[2], kaddr + 512);
      float c[4][4];
      mma16816z(c[0], kb[0], qb[0][0], qb[0][1]); mma16816z(c[1], kb[MK ? 0 : 1], qb[0][2], qb[0][3]);
      mma16816z(c[2], kb[2], qb[1][0], qb[1][1]); mma16816z(c[3], kb[MK ? 2 : 3], qb[1][2], qb[1][3]);
      if (FIRST && B5POS == 0) bar_arrive(5, N5);
#pragma unroll
      for (int i = 0; i < (MK ? 2 : 4); i++) sc[i] = ((c[0][i] + c[1][MK ? i + 2 : i]) + c[2][i]) + c[3][MK ? i + 2 : i];
    };
    auto send = [&](auto memkeys) {
      constexpr bool MK = decltype(memkeys)::value;
      constexpr int N = MK ? 1 : 2;
      const uint32_t sa = sb + LV * 4 + SM_E + (MK ? 1024 + RANK * 128 : RANK * 512 + w * 256);
      uint32_t ra[N][2], mb[N][2];
#pragma unroll
      for (int i = 0; i < N; i++)
#pragma unroll
        for (int j = 0; j < 2; j++) {
          ra[i][j] = mapa(sa + i * 128, j ? 2 : RANK ^ 1); mb[i][j] = mapa(sb + MB_S, j ? 2 : RANK ^ 1);
          PIN(ra[i][j]);
        }
      float sc[4];
      scores(memkeys, BoolC<true>(), sc);
      uint32_t e[N];
#pragma unroll
      for (int i = 0; i < N; i++) {
        e[i] = pack_bf16(ex2(sc[2 * i]), ex2(sc[2 * i + 1]));
        if (!(fmaxf(fabsf(sc[2 * i]), fabsf(sc[2 * i + 1])) <= E_LIM)) e[i] = 0x7fff7fffu;
        st_async1(ra[i][0], e[i], mb[i][0]);
        st_async1(ra[i][1], e[i], mb[i][1]);
      }
#pragma unroll
      for (int i = 0; i < N; i++) sts32(sa + i * 128, e[i]);
      __syncwarp();
      if (l16 == sb) mbar_arrive(sb + MB_S);
      PROF(5);
    };
    const int mode = bad ? 8 : mode0;
    if (mode < 2) {
      send(BoolC<false>());
    } else if (mode == 2) {
      send(BoolC<true>());
    } else if (mode == 8) {
      load_vx();
      retire(l16);
      const uint32_t fp = lds32(sb + SC_FPAR);
      bar_sync(6, 128);
      if (w == 0 && l16 == sb) { sts32(sb + SC_FPAR, fp ^ 1); mbar_expect(sb + MB_F, 3072); }
      if (RANK < 2 && w < 3) {
        float sc[4] = {0.f, 0.f, 0.f, 0.f};
        if (w < 2) scores(BoolC<false>(), BoolC<false>(), sc); else scores(BoolC<true>(), BoolC<false>(), sc);
#pragma unroll 1
        for (int r = 0; r < 3; r++)
          st_async4(mapa(l16 + SM_FB + RANK * 1536 + w * 512, r), __float_as_uint(sc[0]), __float_as_uint(sc[1]), __float_as_uint(sc[2]), __float_as_uint(sc[3]), mapa(sb + MB_F, r));
      }
      mbar_wait(sb + MB_F, fp);
      float a[12];
#pragma unroll
      for (int j = 0; j < 3; j++) {
        float b[4];
        lds128f(l16 + SM_FB + j * 512, a + 4 * j); lds128f(l16 + SM_FB + 1536 + j * 512, b);
#pragma unroll
        for (int i = 0; i < 4; i++) a[4 * j + i] += b[i];
      }
      float m0 = fmaxf(fmaxf(fmaxf(a[0], a[2]), fmaxf(a[4], a[6])), a[8]), m1 = fmaxf(fmaxf(fmaxf(a[1], a[3]), fmaxf(a[5], a[7])), a[9]);
#pragma unroll
      for (int o = 4; o < 32; o <<= 1) { m0 = fmaxf(m0, __shfl_xor_sync(0xffffffffu, m0, o)); m1 = fmaxf(m1, __shfl_xor_sync(0xffffffffu, m1, o)); }
#pragma unroll
      for (int i = 0; i < 5; i++) {
        const uint32_t ea = sb + SM_E + LV * 4 + (i < 4 ? i * 128 : 1024);
        sts32(ea, pack_bf16(ex2(a[2 * i] - m0), ex2(a[2 * i + 1] - m1)));
        sts32(ea + (i < 4 ? 512 : 128), 0x3f803f80u);
      }
      __syncwarp();
    } else {
      load_vx();
      retire(l16 + 1);
      if (VS0 == 2 || VS1 == 2) send_v(s + 1, 2);
      if (w == 3) {
        uint32_t used = ldg_relaxed32(&g_used[blockIdx.x / 3 * 32]);
        if (!(XP & 4) && elect_one()) {
          if (s > 0) seg_publish(s - 1);
          fence_async();
          seg_store(s, sb, 0, 8192);
        }
        __syncwarp();
        bar_sync(RANK < 2 ? 4 : 15, RANK < 2 ? 256 : 160);
        if (!(XP & 4) && elect_one()) { fence_async(); seg_store(s, sb, 8192, blk - 8192); }
        __syncwarp();
        const uint32_t need = lds32(sb + SC_EPOCH) + (s >= NRING - 1 ? s : -4 * NSEG);
#pragma unroll 1
        for (int n = 0; (int)(used - need) < 0 && n < ((XP & 64) ? 1 : SPIN_LIMIT); n++) used = ldg_relaxed32(&g_used[blockIdx.x / 3 * 32]);
      }
    }
    {
      uint32_t wa[4], wb[4];
      constexpr int WS = 2048;
      const uint32_t w3a = l16 + SM_WO3 + w * 512;
      if (HP == 1) { hints = hint_addr(s); PIN(hints); }
      if (!(WL & 1)) { lds128(w3a + KP(0) * WS, wa); lds128(w3a + KP(1) * WS, wb); }
      if (WL & 2) {
#pragma unroll
        for (int i = 0; i < 4; i++) oc[i] = always | (always >> 16) | (always & (i + 1));
      } else if (!(WL & 4)) lds128(sb + SC_ONES, oc);
      if (B5POS == 1 && mode < 3) bar_arrive(5, N5);
      uint32_t e[10], p[5], vm[4], ob[4];
      float o0[4], o1[4], f[3][2][4], rs[4];
      if (!(RV & 1)) { reserve2(vm); reserve2(vm + 2); }
      if (!(RV & 2)) reserve2(e + 8);
      if (!HP) { hints = hint_addr(s); PIN(hints); }
      if (CLR & 2) asm volatile("{\n.reg .pred p;\nsetp.eq.u32 p, %0, 0;\n@p exit;\n}" :: "r"(wa[0] | wb[0] | oc[0] | hints) : "memory");
      if (RV & 4) mbar_wait_fast(sb + MB_S, par); else mbar_wait(sb + MB_S, par);
      RSTAMP(5);
      PROF(6);
      if (RV & 2) { ldsm4t(e, l16 + SM_E); ldsm4t(e + 4, l16 + SM_E + 512); ldsm2t(e + 8, l16 + SM_E + 1024); }
      else { ldsm4t(e, l16 + SM_E); ldsm2t_in(e + 8, l16 + SM_E + 1024, always); ldsm4t(e + 4, l16 + SM_E + 512); }
      if (RV & 1) lds128(l16 + w * 512 + SM_VM, vm); else lds128_in(vm, l16 + w * 512 + SM_VM, always);
      const float scl = __uint_as_float(lds32(sb + SC_UNSC + 8 - par * 8));
      if (HL == 0) hints = load_hints(hints);
      if (GF & 1) SCHED_FENCE(4);
#pragma unroll
      for (int i = 0; i < 4; i++) p[i] = mul_bf16(e[i], e[4 + i]);
      p[4] = mul_bf16(e[8], e[9]);
      if (HL) hints = load_hints(hints | (p[HL - 1] & always & 1));
      mma16816z(o0, vx[0], p[0], p[1]);
      if (WL & 1) { lds128_in(vx[0], w3a + KP(0) * WS, always); }
      mma16816z(o1, vx[1], p[0], p[1]);
      if (WL & 1) { lds128_in(vx[1], w3a + KP(1) * WS, always); }
      mma16816z(rs, oc, p[0], p[1]);
      mma16816(o0, vx[2], p[2], p[3]); lds128_in(vx[2], w3a + KP(2) * WS, always);
      mma16816(o1, vx[3], p[2], p[3]); lds128_in(vx[3], w3a + KP(3) * WS, always);
      mma16816(rs, oc, p[2], p[3]);
      mma1688(o0, vm[0], vm[1], p[4]); mma1688(o1, vm[2], vm[3], p[4]); mma1688(rs, oc[0], oc[1], p[4]);
      stsm4(l16 + w * 512 + SM_OB, pack_bf16(o0[0], o0[1]), pack_bf16(o0[2], o0[3]), pack_bf16(o1[0], o1[1]), pack_bf16(o1[2], o1[3]));
      bar_sync(6, 128);
      RSTAMP(3);
      PROF(7);
      ldsm4t_in(oc, l16 + SM_OB, always);
      bad = __any_sync(0xffffffffu, !(rs[0] + rs[1] > 0.f) && !bad);
      rs[0] *= scl; rs[1] *= scl;
      asm volatile("{\n.reg .pred p;\nsetp.ne.u32 p, %1, 0;\n@p rcp.approx.ftz.f32 %0, %0;\n}" : "+f"(rs[0]) : "r"(always));
      asm volatile("{\n.reg .pred p;\nsetp.ne.u32 p, %1, 1;\n@p rcp.approx.ftz.f32 %0, %0;\n}" : "+f"(rs[1]) : "r"(always));
      asm volatile("lop3.b32 %0, %1, %2, %3, 0xfe;" : "=r"(lp) : "r"((l16 & 128) * 2), "r"((l16 & 256) * 4), "r"(l16 & 112));
      if (bad) continue;
      ldsm4t(ob, l16 + SM_OB + 512);
      mma16816z(f[2][0], WL & 1 ? vx[0] : wa, oc[0], oc[1]); mma16816z(f[2][1], WL & 1 ? vx[1] : wb, oc[2], oc[3]);
      mma16816z(f[0][0], wo[0], oc[0], oc[1]); mma16816z(f[0][1], wo[4], oc[2], oc[3]);
      mma16816z(f[1][0], w1[0], oc[0], oc[1]); mma16816z(f[1][1], w1[4], oc[2], oc[3]);
      ldsm4t_in(oc, l16 + SM_OB + 1024, always);
      mma16816(f[2][0], vx[2], ob[0], ob[1]); lds128_in(vx[2], w3a + KP(4) * WS, always);
      mma16816(f[2][1], vx[3], ob[2], ob[3]); lds128_in(vx[3], w3a + KP(5) * WS, always);
      mma16816(f[0][0], wo[1], ob[0], ob[1]); mma16816(f[0][1], wo[5], ob[2], ob[3]);
      mma16816(f[1][0], w1[1], ob[0], ob[1]); mma16816(f[1][1], w1[5], ob[2], ob[3]);
      ldsm4t_in(ob, l16 + SM_OB + 1536, always);
      mma16816(f[0][0], wo[2], oc[0], oc[1]); mma16816(f[0][1], wo[6], oc[2], oc[3]);
      mma16816(f[2][0], vx[2], oc[0], oc[1]); lds128_in(vx[2], w3a + KP(6) * WS, always);
      mma16816(f[2][1], vx[3], oc[2], oc[3]); lds128_in(vx[3], w3a + KP(7) * WS, always);
      mma16816(f[1][0], w1[2], oc[0], oc[1]); mma16816(f[1][1], w1[6], oc[2], oc[3]);
      mma16816(f[0][0], wo[3], ob[0], ob[1]); mma16816(f[0][1], wo[7], ob[2], ob[3]);
      mma16816(f[1][0], w1[3], ob[0], ob[1]); mma16816(f[1][1], w1[7], ob[2], ob[3]);
      mma16816(f[2][0], vx[2], ob[0], ob[1]); mma16816(f[2][1], vx[3], ob[2], ob[3]);
      bar_arrive(7, NII < 18 ? 384 : 256);
      lds128_in(ob, sb + SC_DEAD, always);
      uint32_t h[3][2];
#pragma unroll
      for (int j = 0; j < 3; j++)
#pragma unroll
        for (int i = 0; i < 2; i++)
        {
          scale_sum(f[j][1][2 * i], f[j][0][2 * i], rs[0], always); scale_sum(f[j][1][2 * i + 1], f[j][0][2 * i + 1], rs[1], always);
          h[j][i] = pack_f16(f[j][1][2 * i], f[j][1][2 * i + 1]);
        }
      const uint32_t rofs = RANK * 32768;
      red_f16x8(slot(s, RANK >> 1, rofs), h[0][0], h[1][0], h[2][0], 0x3c00u);
      red_f16x8(slot(s, (RANK >> 1) ^ 1, rofs), h[0][1], h[1][1], h[2][1], 0x3c00u);
      if (NII == 18) bar_arrive(10, 256);
      SCHED_FENCE(5);
      RSTAMP(0);
      l16 += ob[B7R];
    }
    {
    PROF(8);
    if (VS0 == 3 || VS1 == 3) send_v(s + 1, 3);
    const uint32_t ma0 = l16 + SM_MEM + w * 128 + (LV >> 3) * 896 + nh * 512;
    const unsigned char* const sl[2] = {slot(s, nh, 0), slot(s, nh ^ 1, 0)};
    uint32_t late = latest_hint(hints, dl, s);
    if (late >= 64) {
      int n = 0;
#pragma unroll 1
      do {
        late = latest_hint(load_hints(hint_addr(s)), dl, s);
      } while (late >= 64 && ++n < SPIN_LIMIT);
    }
    dl += late * 32 + tm.poll;
    PROF(9);
    {
      auto wait_until = [&](uint32_t t) {
        asm volatile("{\n.reg .pred p;\n.reg .s32 c;\n.reg .u64 t;\nTL: mov.u64 t, %%globaltimer;\ncvt.u32.u64 c, t;\nsub.s32 c, c, %0;\nsetp.lt.s32 p, c, 0;\n@p bra.uni TL;\n}" :: "r"(t + (l16 & 15)) : "memory");
      };
      uint4 v[2][3];
      auto load = [&](int c) {
#pragma unroll
        for (int r = 0; r < 3; r++) v[c][r] = ldg_relaxed(sl[c ^ (r >> 1)] + r * 32768);
      };
      auto decode = [&](int c, int n) {
        uint32_t q[9];
        __half2 hm;
        const uint32_t ma = ma0 ^ (c * 512);
#pragma unroll
        for (int i = 0; i < 9; i++) {
          const uint32_t h = i % 3 == 0 ? v[c][i / 3].x : (i % 3 == 1 ? v[c][i / 3].y : v[c][i / 3].z);
          const float2 f = __half22float2(*(const __half2*)&h);
          q[i] = pack_bf16(f.x, f.y);
          hm = i ? __hmax2(hm, __habs2(*(const __half2*)&h)) : __habs2(*(const __half2*)&h);
        }
#pragma unroll
        for (int r = 0; r < 3; r++) stsm4(ma + r * 4096, q[3 * r], q[3 * r + 1], q[3 * r + 2], r < 2 ? v[c][r].w : *(const uint32_t*)&hm);
        const bool done = __all_sync(0xffffffffu, v[c][0].w == 0x5000u && v[c][1].w == 0x5000u && v[c][2].w == 0x5000u) || n > SPIN_LIMIT;
        asm volatile("{\n.reg .pred p;\nsetp.ne.u32 p, %0, 0;\n@p bar.arrive %1, 256;\n}" :: "r"((int)done), "r"(1 + c) : "memory");
        return done;
      };
      if (LEAD) { wait_until(dl - LEAD); load(1); }
      wait_until(dl);
      PROF(10);
      int n = 0;
#pragma unroll 1
      do {
        load(0);
        if (!LEAD) load(1);
        asm volatile("{\n.reg .pred p;\nsetp.eq.u32 p, %0, 0;\n@p bar.sync 13, 384;\n}" :: "r"(n) : "memory");
      } while (!decode(0, n++));
      PROF(11);
      RSTAMP(1);
#pragma unroll 1
      while (!decode(1, n++)) load(1);
      bar_arrive(9, 256);
      RSTAMP(2);
      PROF(12);
    }
    PROF(13);
    if (++s == NSEG - 1) break;
    }
  }
#undef fence_reg
  if (RANK < 2) bar_arrive(4, 256);
  TSTAMP(49);
  {
    PIN(l16);
    tail_attention(sb, RANK, w, LV, 0, 6);
#pragma unroll 1
    for (int sg = 0; sg < 2; sg++) {
      PIN(l16);
      const int lane = LV, m = lane >> 3, g = lane >> 2, t = lane & 3;
      const uint32_t ob = l16 + T_OB + sg * 8192;
      bar_sync(sg ? 0 : 8, 256);
      TSTAMP(54 + 2 * sg);
      const float inv = __uint_as_float(0x7f000000u - lds32(sb + T_UN + sg * 4));
#pragma unroll 1
      for (int j = 0; j < 4; j += 2) {
        float c[2][3][4];
        uint32_t x[4], y[4], z[2][4];
#pragma unroll
        for (int e = 0; e < 2; e++) {
          const uint32_t oa = sb + T_OA + ((sg * 4 + j + e) * 8 + g) * 64 + (blockIdx.x / 3 * 36 & 15) + t * 4;
          z[e][0] = lds32(oa); z[e][1] = lds32(oa + 16); z[e][2] = t ? 0u : lds32(oa + 32);
        }
#pragma unroll
        for (int i = 0; i < 3; i++) {
          const uint32_t wa = sb + T_WA + ((lane & 7) + ((lane >> 4) << 3)) * 128 + (((w + 4 * (m & 1)) ^ (lane & 7)) << 4);
          ldsm4t(x, wa + i * 3072); ldsm2t(y, wa + i * 3072 + 2048);
#pragma unroll
          for (int e = 0; e < 2; e++) { mma1688z(c[e][i], y[0], y[1], z[e][2]); mma16816(c[e][i], x, z[e][0], z[e][1]); }
        }
#pragma unroll
        for (int r = 0; r < 4; r++) {
          ldsm4t(z[0], ob + j * 2048 + r * 512); ldsm4t(z[1], ob + j * 2048 + 2048 + r * 512);
          lds128(l16 + SM_WO3 + w * 512 + r * 2048, x); lds128(l16 + SM_WO3 + w * 512 + (r + 4) * 2048, y);
#pragma unroll
          for (int e = 0; e < 2; e++) { mma16816(c[e][0], wo[r], z[e][0], z[e][1]); mma16816(c[e][1], w1[r], z[e][0], z[e][1]); mma16816(c[e][2], x, z[e][0], z[e][1]); }
#pragma unroll
          for (int e = 0; e < 2; e++) { mma16816(c[e][0], wo[r + 4], z[e][2], z[e][3]); mma16816(c[e][1], w1[r + 4], z[e][2], z[e][3]); mma16816(c[e][2], y, z[e][2], z[e][3]); }
        }
#pragma unroll
        for (int i = 0; i < 4; i++) {
          const float (&d)[3][4] = c[i >> 1];
          const int q = (i & 1) * 2;
          red_f16x8(g_red + T_RED + ((((sg * 4 + j + (i >> 1)) * 3 + RANK) * 4 + w) * 2 + (i & 1)) * 512 + lane * 16, pack_f16(d[0][q] * inv, d[0][q + 1] * inv),
                    pack_f16(d[1][q] * inv, d[1][q + 1] * inv), pack_f16(d[2][q] * inv, d[2][q + 1] * inv), 0x3c00u);
        }
      }
      TSTAMP(55 + 2 * sg);
    }
    if (RSLOW) { wait_until(gtime() + 8000); wait_until(gtime() + 8000); wait_until(gtime() + 4000); }
    if (w < 2) {
      const int b = blockIdx.x, lane = LV, g = lane >> 2, t = lane & 3;
      uint4 v;
#pragma unroll 1
      for (int n = 0; n < SPIN_LIMIT; n++) {
        v = ldg_relaxed(g_red + T_RED + (w * 96 + b) * 512 + lane * 16);
        if (__all_sync(0xffffffffu, v.w == 0x5000u)) break;
        __nanosleep(40);
      }
      const float un = __uint_as_float(lds32(sb + T_UN + w * 4));
      uint32_t* const o = (uint32_t*)(tm.out + (size_t)((NAUXSEG + w) * 32 + b / 24 * 8 + g) * DM + (b >> 3) % 3 * 192 + (b & 1) * 32 + (b & 6) * 4) + t;
#pragma unroll
      for (int j = 0; j < 3; j++) {
        const float2 f = __half22float2(*(const __half2*)(&v.x + j));
        o[j * 32] = movm(pack_bf16(f.x * un, f.y * un));
      }
    }
  }
  TSTAMP(3);
  if (CSY) cluster_sync();
}

__global__ void __cluster_dims__(3, 1, 1) __launch_bounds__(384, 1)
rec_kernel(const __grid_constant__ RMaps tm, const bf16* __restrict__ x, const bf16* __restrict__ mem0) {
  extern __shared__ __align__(1024) unsigned char smem_raw[];
  const uint32_t sb = smem_u32(smem_raw);
  const int tid = threadIdx.x, lane = tid & 31;
  const int wg = __shfl_sync(0xffffffffu, tid >> 7, 0);
  const int w = __shfl_sync(0xffffffffu, (tid >> 5) & 3, 0);
  uint32_t rank; asm("mov.u32 %0, %%cluster_ctarank;" : "=r"(rank));
  STAMP(0);
  TSTAMP(0);
  asm volatile("griddepcontrol.launch_dependents;" ::: "memory");

#define PFT 1
  if (PFT && wg == 1 && lane == 0) asm volatile("prefetch.tensormap [%0];\nprefetch.tensormap [%1];" :: "l"(w & 1 ? &tm.woa : &tm.oa), "l"(w == 0 ? (rank < 2 ? &tm.wk : &tm.wv) : w == 1 ? &tm.wq : w == 2 ? &tm.x : &tm.wo) : "memory");
  if (wg < 2) {
    asm volatile("setmaxnreg.inc.sync.aligned.u32 192;");
    if (tid == 0) {
      for (int i = 0; i < 3; i++) { mbar_init(sb + MB_W + 8 * i, 1); mbar_init(sb + MB_X + 8 * i, 1); }
      mbar_init(sb + MB_WO, 1); mbar_init(sb + MB_WO3, 1);
      mbar_init(sb + MB_S, rank < 2 ? 5 : 6);
      mbar_init(sb + MB_F, 1);
      for (int i = 0; i < 3; i++) mbar_init(sb + MB_T + 8 * i, 1);
      mbar_init(sb + MB_VX, 1); mbar_init(sb + MB_VX + 8, 1);
      asm volatile("fence.mbarrier_init.release.cluster;" ::: "memory");
      fence_async();
      SSTAMP(11, 6);
      load_weights(sb, tm, rank, 0);
      for (int i = 0; i < 3; i++) mbar_expect(sb + MB_X + 8 * i, XT);
      tma_load3(sb + SM_X, &tm.x, 0, sb + MB_X);
      if (!PACE) for (int c = 1; c < 4; c++) load_weights(sb, tm, rank, c);
      mbar_expect(sb + MB_S, rank < 2 ? 640 + 2048 : 1280);
      mbar_expect(sb + MB_VX, 8192); mbar_expect(sb + MB_VX + 8, 8192);
      mbar_expect(sb + MB_T, 2048);
      for (int i = 1; i < 3; i++) mbar_expect(sb + MB_T + 8 * i, rank < 2 ? 5120 : 10240);
      SSTAMP(11, 5);
    }
    __syncwarp();
    bar_sync(0, 384);
    proj_role(sb, tm, rank, wg, w, lane);
  } else {
    asm volatile("setmaxnreg.dec.sync.aligned.u32 120;");
    attn_role(sb, smem_raw, tm, rank, x, mem0, w, lane);
  }
}

constexpr int A_XH = 73728;
constexpr int A_NS = 9, A_WM = 6144, A_WT = 768;
constexpr int A_RING = 2 * A_XH, A_TAIL = A_RING + A_NS * A_WM, A_GW = A_TAIL + A_NS * A_WT;
constexpr int A_EPI = 212864, A_EPW = 9344;
constexpr int A_XW = 4 * XT, A_XT = A_XW + 4096, A_NR = 4;
constexpr int A_IN = A_XT + 2048, A_INS = 2 * 9216 + SEGB, A_OST = A_IN + 2 * A_INS;
constexpr int A_GATE = A_EPI + 2 * A_EPW, A_BAR = A_GATE + 512;
constexpr int A_TOTAL = A_BAR + 384;
struct AMaps { CUtensorMap x, wa, wt, oa, o, o3, o8, wob, woa, wo8; };

DI void wgmma_n192_ss_nt(float* d, uint64_t da, uint64_t db, int acc) {
  asm volatile("{\n.reg .pred p;\nsetp.ne.b32 p, %98, 0;\n"
               "wgmma.mma_async.sync.aligned.m64n192k16.f32.bf16.bf16 {"
               "%0,%1,%2,%3,%4,%5,%6,%7,%8,%9,%10,%11,%12,%13,%14,%15,%16,%17,%18,%19,%20,%21,%22,%23,%24,%25,%26,%27,%28,%29,%30,%31,"
               "%32,%33,%34,%35,%36,%37,%38,%39,%40,%41,%42,%43,%44,%45,%46,%47,%48,%49,%50,%51,%52,%53,%54,%55,%56,%57,%58,%59,%60,%61,%62,%63,"
               "%64,%65,%66,%67,%68,%69,%70,%71,%72,%73,%74,%75,%76,%77,%78,%79,%80,%81,%82,%83,%84,%85,%86,%87,%88,%89,%90,%91,%92,%93,%94,%95"
               "}, %96, %97, p, 1, 1, 0, 1;\n}\n"
               : ACC8(d, 0), ACC8(d, 8), ACC8(d, 16), ACC8(d, 24), ACC8(d, 32), ACC8(d, 40), ACC8(d, 48), ACC8(d, 56),
                 ACC8(d, 64), ACC8(d, 72), ACC8(d, 80), ACC8(d, 88) : "l"(da), "l"(db), "r"(acc));
}
#define ACC4(d, o) "+f"(d[o]), "+f"(d[o + 1]), "+f"(d[o + 2]), "+f"(d[o + 3])
DI void wgmma_n24_ss_nt(float* d, uint64_t da, uint64_t db, int acc) {
  asm volatile("{\n.reg .pred p;\nsetp.ne.b32 p, %14, 0;\n"
               "wgmma.mma_async.sync.aligned.m64n24k16.f32.bf16.bf16 {%0,%1,%2,%3,%4,%5,%6,%7,%8,%9,%10,%11}, %12, %13, p, 1, 1, 0, 1;\n}\n"
               : ACC8(d, 0), ACC4(d, 8) : "l"(da), "l"(db), "r"(acc));
}
DI void wgmma_n8_ss(float* d, uint64_t da, uint64_t db, int acc) {
  asm volatile("{\n.reg .pred p;\nsetp.ne.b32 p, %6, 0;\n"
               "wgmma.mma_async.sync.aligned.m64n8k16.f32.bf16.bf16 {%0,%1,%2,%3}, %4, %5, p, 1, 1, 0, 0;\n}\n"
               : ACC4(d, 0) : "l"(da), "l"(db), "r"(acc));
}
DI void wgmma_n40_ss_tt(float* d, uint64_t da, uint64_t db, int acc) {
  asm volatile("{\n.reg .pred p;\nsetp.ne.b32 p, %22, 0;\n"
               "wgmma.mma_async.sync.aligned.m64n40k16.f32.bf16.bf16 {%0,%1,%2,%3,%4,%5,%6,%7,%8,%9,%10,%11,%12,%13,%14,%15,%16,%17,%18,%19}, "
               "%20, %21, p, 1, 1, 1, 1;\n}\n"
               : ACC8(d, 0), ACC8(d, 8), ACC4(d, 16) : "l"(da), "l"(db), "r"(acc));
}
DI void wgmma_n64_rs(float* d, const uint32_t* a, uint64_t db, int acc) {
  asm volatile("{\n.reg .pred p;\nsetp.ne.b32 p, %37, 0;\n"
               "wgmma.mma_async.sync.aligned.m64n64k16.f32.bf16.bf16 {"
               "%0,%1,%2,%3,%4,%5,%6,%7,%8,%9,%10,%11,%12,%13,%14,%15,%16,%17,%18,%19,%20,%21,%22,%23,%24,%25,%26,%27,%28,%29,%30,%31"
               "}, {%32,%33,%34,%35}, %36, p, 1, 1, 0;\n}\n"
               : ACC8(d, 0), ACC8(d, 8), ACC8(d, 16), ACC8(d, 24) : "r"(a[0]), "r"(a[1]), "r"(a[2]), "r"(a[3]), "l"(db), "r"(acc));
}
DI void wgmma_n32_ss_tn(float* d, uint64_t da, uint64_t db, int acc) {
  asm volatile("{\n.reg .pred p;\nsetp.ne.b32 p, %18, 0;\n"
               "wgmma.mma_async.sync.aligned.m64n32k16.f32.bf16.bf16 {%0,%1,%2,%3,%4,%5,%6,%7,%8,%9,%10,%11,%12,%13,%14,%15}, "
               "%16, %17, p, 1, 1, 1, 0;\n}\n"
               : ACC8(d, 0), ACC8(d, 8) : "l"(da), "l"(db), "r"(acc));
}
DI void tma_load3c(uint32_t dst, const CUtensorMap* m, int c0, int c1, int c2, uint32_t mb) {
  asm volatile("cp.async.bulk.tensor.3d.shared::cluster.global.mbarrier::complete_tx::bytes [%0], [%1, {%3, %4, %5}], [%2];"
               :: "r"(dst), "l"(m), "r"(mb), "r"(c0), "r"(c1), "r"(c2) : "memory");
}
DI void count_up(unsigned* p) {
  asm volatile("fence.proxy.async;" ::: "memory");
  asm volatile("red.release.gpu.global.add.u32 [%0], 1;" :: "l"(p) : "memory");
}
#define AX 0
#define FDLY 400
#define DRY 0
#define FEND 59
DI void publish(unsigned* p) {
  asm volatile("cp.async.bulk.wait_group 0;\nfence.proxy.async;" ::: "memory");
  asm volatile("red.relaxed.gpu.global.add.u32 [%0], 1;" :: "l"(p) : "memory");
}
#define G_IDLE 600
#define PL 2
#define STG 0
#define DRAIN 0
#define PR 4
#define ADLY 0

__global__ void __launch_bounds__(512, 1)
aux_kernel(const __grid_constant__ AMaps tm, const bf16* __restrict__ wqkv, const bf16* __restrict__ woa, const bf16* __restrict__ gate_w, bf16* __restrict__ out) {
  extern __shared__ __align__(1024) unsigned char smem_raw[];
  const uint32_t sb = smem_u32(smem_raw);
  const uint32_t fullx = sb + A_BAR, full1 = fullx + 24, empty1 = full1 + 8 * A_NS, fullw = empty1 + 8 * A_NS, full3 = fullw + 8, empty3 = full3 + 8 * A_NR,
                 fullq = empty3 + 8 * A_NR, emptyq = fullq + 16;
  const int tid = threadIdx.x, lane = tid & 31, cta = blockIdx.x;
  const int wg = __shfl_sync(0xffffffffu, tid >> 7, 0), w = __shfl_sync(0xffffffffu, (tid >> 5) & 3, 0);
  ASTAMP(14);
  if (tid == 384) {
    for (int i = 0; i < 3; i++) mbar_init(fullx + 8 * i, 1);
    for (int i = 0; i < A_NS; i++) { mbar_init(full1 + 8 * i, 1); mbar_init(empty1 + 8 * i, 8); }
    mbar_init(fullw, 1); mbar_init(fullq, 1); mbar_init(fullq + 8, 1); mbar_init(emptyq, 4); mbar_init(emptyq + 8, 4);
    for (int i = 0; i < A_NR; i++) { mbar_init(full3 + 8 * i, 1); mbar_init(empty3 + 8 * i, cta < NH ? 8 : 4); }
    fence_async();
  }
  __syncthreads();
  ASTAMP(0);
  const int tile = cta >> 1, hh = cta & 1;
  auto p3_n = [&](int g) { return cta < NH ? (cta & 3) * 2 + g : 8; };
  auto p3_k = [&](int g) { return cta < NH ? cta >> 2 : (cta & 3) * 2 + g; };
  if (wg == 3) {
    asm volatile("setmaxnreg.dec.sync.aligned.u32 24;");
    const bool lead = lane == 0;
    if (w < 3) {
      if (ADLY) wait_until(gtime() + ADLY);
      if (elect_one()) {
        mbar_expect(fullx + 8 * w, 49152);
        for (int p = 0; p < 2; p++)
          asm volatile("cp.async.bulk.tensor.4d.shared::cluster.global.mbarrier::complete_tx::bytes [%0], [%1, {%3, %4, %5, %6}], [%2];"
                       :: "r"(sb + p * A_XH + w * 24576), "l"(&tm.x), "r"(fullx + 8 * w), "r"(0), "r"(p), "r"(57 * tile - 7), "r"(3 * w) : "memory");
      }
#pragma unroll 1
      for (int r = 0; r < 17; r++) {
#pragma unroll 1
        for (int st = w; st < A_NS; st += 3) {
          if (r > 0) mbar_wait(empty1 + 8 * st, ~r & 1);
          if (r < 16 && elect_one()) {
            const int col = hh * 288 + (r >> 2) * 72, row = (r & 3) * 144 + st * 16;
            mbar_expect(full1 + 8 * st, A_WM + (AX & 1 ? 0 : A_WT));
            tma_load3c(sb + A_RING + st * A_WM, &tm.wa, col, row, 0, full1 + 8 * st);
            if (!(AX & 1)) tma_load3c(sb + A_TAIL + st * A_WT, &tm.wt, col + 64, row, 0, full1 + 8 * st);
          }
          __syncwarp();
        }
        if (r == 0 && elect_one())
          for (int j = 0; j < 3; j++)
            asm volatile("cp.async.bulk.prefetch.L2.global [%0], %1;" :: "l"((const char*)wqkv + cta * 55296 + (w * 3 + j) * 6144), "r"(6144) : "memory");
        __syncwarp();
      }
      bar_sync(8, 96);
    }
    const unsigned epoch = lds32(sb + A_BAR + 376);
    if (w == 2) {
      if (lead && cta < NH) {
#pragma unroll 1
        for (int seg = 0; seg < NAUXSEG; seg++) {
          const unsigned char* const src = g_seg + ((size_t)(AX & 128 ? 0 : seg % NRING) * 96 + cta * 3) * SEGB;
          SSTAMP(0, seg);
          const uint32_t tw = gtime();
          wait_count(&g_scnt[(seg * 32 + cta) * 8], 3 * (epoch + 1), !(TL & 2) || seg < NAUXSEG - 2);
          const bool idle = seg < FEND && gtime() - tw > G_IDLE;
          if (FDLY && idle) wait_until(gtime() + FDLY);
          SSTAMP(1, seg);
          const uint32_t mb = fullq + (seg & 1) * 8;
          mbar_wait(emptyq + (seg & 1) * 8, (~seg >> 1) & 1);
          if (AX & 8) mbar_arrive(mb); else mbar_expect(mb, A_INS);
#pragma unroll 1
          for (int r = 0; r < ((AX & 8) ? 0 : 3); r++)
            asm volatile("cp.async.bulk.shared::cluster.global.mbarrier::complete_tx::bytes [%0], [%1], %2, [%3];"
                         :: "r"(sb + A_IN + (seg & 1) * A_INS + r * 9216), "l"(src + r * SEGB), "r"(r < 2 ? 9216 : SEGB), "r"(mb) : "memory");
          if (seg == 1) wait_count(&g_abar[32], NAUX * (epoch + 1));
          stg_relaxed32(&g_used[cta * 32], epoch * NSEG + max(seg - 1, 0));
        }
      }
    }
    if (w == 3) {
#pragma unroll 1
      for (int c = 0; c < 4; c++) {
        if (lead) asm volatile("cp.async.bulk.wait_group.read 0;" ::: "memory");
        __syncwarp();
        bar_arrive(11, 160); bar_arrive(12, 160);
#pragma unroll 1
        for (int g = 0; g < 2; g++) {
          bar_sync(13 + g, 160);
          if (lead) {
            asm volatile("cp.async.bulk.tensor.3d.global.shared::cta.bulk_group [%0, {%2, %3, %4}], [%1];"
                         :: "l"(&tm.oa), "r"(sb + A_EPI + g * A_EPW + 1024), "r"(4096 + hh * 288 + c * 72), "r"(g), "r"(57 * tile) : "memory");
            asm volatile("cp.async.bulk.commit_group;" ::: "memory");
          }
        }
      }
      if (lead) asm volatile("cp.async.bulk.wait_group.read 0;" ::: "memory");
      __syncwarp();
      bar_arrive(10, 160);
      if (lead) publish(&g_abar[32]);
    }
    if ((w & 1) && cta < NH) {
      if (w == 1) bar_arrive(5, 160);
#pragma unroll 1
      for (int seg = w >> 1; seg < NAUXSEG; seg += 2) {
        bar_sync(w == 1 ? 4 : 15, 160);
        if (lead && !(AX & 32)) {
          tma_store(&tm.o, sb + A_OST, cta * DH, seg * 32);
          tma_store(&tm.o, sb + A_OST + 4096, cta * DH + 64, seg * 32);
          asm volatile("cp.async.bulk.commit_group;" ::: "memory");
          asm volatile("cp.async.bulk.wait_group.read 0;" ::: "memory");
        }
        __syncwarp();
        if (seg < NAUXSEG - 1) bar_arrive(5, 160);
        if (lead) {
          publish(&g_ocnt[seg * 64 + 2 * cta / 9 * 8]);
          if (2 * cta / 9 != (2 * cta + 1) / 9) asm volatile("red.relaxed.gpu.global.add.u32 [%0], 1;" :: "l"(&g_ocnt[seg * 64 + (2 * cta + 1) / 9 * 8]) : "memory");
          SSTAMP(9, seg);
        }
        __syncwarp();
      }
    }
    if (w != 0) return;
    if (lead) {
      mbar_expect(fullw, 18 * 8192 + 2048);
#pragma unroll 1
      for (int k = 0; k < 18; k++) {
        const int g = k / 9, kb = p3_k(g) * 9 + k - 9 * g;
        if (kb < 64) tma_load(sb + k * 8192, &tm.wob, p3_n(g) * 64, kb * 64, fullw);
        else tma_load(sb + k * 8192, &tm.woa, p3_n(g) * 64, (kb - 64) * 64, fullw);
      }
      for (int g = 0; g < 2; g++) tma_load(sb + A_XW + g * 2048, &tm.wo8, p3_n(g) * 64, 512 + p3_k(g) * 8, fullw);
    }
    __syncwarp();
    bar_sync(6, 288);
    if (lead) {
      wait_count(&g_abar[32], NAUX * (epoch + 1));
      int avail = 0, avail1 = 0;
      bool waited = false;
      const int nbox = cta < NH ? NAUXSEG : 2 * NAUXSEG;
#pragma unroll 1
      for (int i = 0; i < nbox; i++) {
        const int seg = cta < NH ? i : i >> 1, ke = p3_k(i & 1), sl = i & 3;
        const unsigned nheads = (ke < 7 ? 5 : 1) * (epoch + 1);
        if (seg >= avail) {
          const unsigned* const c = &g_ocnt[seg * 64 + ke * 8];
          const int c2 = ldg_relaxed32(c + 128) - nheads, c1 = ldg_relaxed32(c + 64) - nheads, c0 = ldg_acquire32(c) - nheads;
          waited = c0 < 0;
          if (waited) wait_count(c, nheads, !(TL & 2) || seg < NAUXSEG - 2);
          else if (c1 >= 0) avail = seg + (c2 >= 0 ? 3 : 2);
        }
        if (cta >= NH) { const int a = avail; avail = avail1; avail1 = a; }
        SSTAMP(5, seg);
        mbar_wait(empty3 + 8 * sl, ((i >> 2) & 1) ^ 1);
        if (AX & 4) { mbar_arrive(full3 + 8 * sl); continue; }
        mbar_expect(full3 + 8 * sl, XT + 512);
        tma_load3c(sb + sl * XT, &tm.o3, 0, seg * 32, ke * 9, full3 + 8 * sl);
        tma_load(sb + A_XT + sl * 512, &tm.o8, 72 * 64 + ke * 8, seg * 32, full3 + 8 * sl);
      }
    }
    __syncwarp(); bar_sync(6, 288);
    if (GDW) asm volatile("griddepcontrol.wait;" ::: "memory");
  } else if (wg == 2) {
    asm volatile("setmaxnreg.dec.sync.aligned.u32 88;");
    {
      const unsigned epoch = *(volatile unsigned*)&g_epoch2;
      if ((tid & 127) < 80) { const uint4 g = __ldg((const uint4*)gate_w + min(tid & 127, 71)); sts128(sb + A_GW + (tid & 127) * 16, g.x, g.y, g.z, g.w); }
      fence_async();
      bar_sync(3, 128);
      float gt[2][4];
      const uint32_t d0 = (sb & 0x3FFFF) >> 4;
#pragma unroll 1
      for (int j = 0; j < 3; j++) {
        mbar_wait(fullx + 8 * j, 0);
        WG_FENCE();
#pragma unroll
        for (int k = 0; k < 24; k++)
          wgmma_n8_ss(gt[k & 1], desc_at(d0 + (k & 1) * (A_XH >> 4) + j * 1536 + (k >> 3) * 512 + (k & 6), 16, 1024, 1), desc_at(d0 + (A_GW >> 4) + j * 24 + (k & 30), 16, 128, 0), j | (k >> 1));
        WG_COMMIT();
      }
      WG_WAIT(0);
      if ((lane & 3) == 0)
#pragma unroll
        for (int i = 0; i < 4; i++) {
          const float gv = 1.f / (1.f + __expf(-gt[i >> 1][(i & 1) * 2]));
          const int r = w * 16 + (lane >> 2) + (i & 1) * 8, tok = 2 * (57 * tile - 7 + r) + (i >> 1);
          sts32(sb + A_GATE + ((i >> 1) * 64 + r) * 4, __float_as_uint(gv));
          if (hh == 0 && r >= 7 && tok < S_LEN) g_gate[tok] = gv;
        }
      if (tid == 256) sts32(sb + A_BAR + 376, epoch);
      __syncwarp();
      bar_arrive(7, 384);
      __half2 hw = __float2half2_rn(0.f);
#pragma unroll
      for (int i = 0; i < 9; i++) { const uint4 v = __ldg((const uint4*)woa + cta * 1152 + i * 128 + (tid & 127)); hw = amax4(hw, &v.x); }
      const uint32_t ew = wexp(hw);
      if (lane == 0) atomicMax(&g_amax[0], (unsigned long long)(epoch + 1) << 32 | ew);
      bar_sync(3, 128);
      if (tid == 256) {
        count_up(&g_abar[0]);
        wait_count(&g_abar[0], NAUX * (epoch + 1));
        if (cta == 0) *(volatile unsigned*)&g_epoch2 = epoch + 1;
      }
      __syncwarp();
      bar_sync(10, 160);
    }
    if (cta < NH) {
      const int lim = w * 8 + (lane >> 2) - 2 * (lane & 3);
      const uint32_t oa = sb + A_OST + (w * 8 + (lane & 7)) * 128;
      uint32_t p[5][4];
#pragma unroll
      for (int n = 0; n < 10; n++) p[n >> 1][1 + (n & 1)] = __shfl_sync(0xffffffffu, lane ^ n, n);
#pragma unroll 1
      for (int seg = 0; seg < NAUXSEG; seg++) {
        const float gt = __ldcg(&g_gate[seg * 32 + w * 8 + (lane >> 2)]);
        float sc[20], d[32];
        const uint32_t d0 = (((sb + A_IN) & 0x3FFFF) >> 4) + (seg & 1) * (A_INS >> 4);
        mbar_wait(fullq + (seg & 1) * 8, (seg >> 1) & 1);
        if (tid == 256) SSTAMP(2, seg);
        WG_FENCE();
#pragma unroll
        for (int k = 0; k < 8; k++) {
          const int o = ((k >> 2) * 9216 + (k & 3) * 256) >> 4;
          wgmma_n40_ss_tt(sc, desc_at(d0 + o, 128, 512, 0), desc_at(d0 + o + 256, 128, 1024, 0), k > 0);
        }
        WG_COMMIT();
        WG_WAIT(0);
        float a[10];
#pragma unroll
        for (int i = 0; i < 10; i++) {
          a[i] = sc[(i >> 1) * 4 + (i & 1)] * (SM_SCALE * LOG2E);
          if (i < 8 && (i >> 1) * 8 + (i & 1) > lim) a[i] = -1.0e9f * LOG2E;
        }
        float m = max10(a);
        m = fmaxf(m, __shfl_xor_sync(0xffffffffu, m, 1)); m = fmaxf(m, __shfl_xor_sync(0xffffffffu, m, 2));
#pragma unroll
        for (int i = 0; i < 10; i++) a[i] = ex2(a[i] - m);
#pragma unroll
        for (int n = 0; n < 5; n++) {
          p[n][0] = pack_bf16(a[2 * n], a[2 * n + 1]); p[n][3] = p[n][0] | p[n][1];
          asm volatile("" : "+r"(p[n][0]), "+r"(p[n][3]) :: "memory");
        }
        float sum = ((a[0] + a[1]) + (a[2] + a[3])) + ((a[4] + a[5]) + (a[6] + a[7])) + (a[8] + a[9]);
        sum += __shfl_xor_sync(0xffffffffu, sum, 1);
        WG_FENCE();
#pragma unroll
        for (int n = 0; n < 5; n++) wgmma_n64_rs(d, p[n], n < 4 ? desc_at(d0 + 1152 + 8 * n, 4096, 512, 0) : desc_at(d0 + 1152 + 512, 1024, 128, 0), n);
        WG_COMMIT();
        sum += __shfl_xor_sync(0xffffffffu, sum, 2);
        const float f = (1.f - gt) * rcp(sum);
        bar_sync(5, 160);
        WG_WAIT(0);
        if (lane == 0) mbar_arrive(emptyq + (seg & 1) * 8);
        if (tid == 256) SSTAMP(4, seg);
#pragma unroll
        for (int q = 0; q < 4; q++) {
          const float* const o = d + (q & 1) * 16 + (q & 2);
          stsm4(oa + (q >> 1) * 4096 + ((((q & 1) * 4 + (lane >> 3)) ^ (lane & 7)) << 4), pack_bf16(o[0] * f, o[1] * f), pack_bf16(o[4] * f, o[5] * f),
                pack_bf16(o[8] * f, o[9] * f), pack_bf16(o[12] * f, o[13] * f));
        }
        fence_async();
        bar_arrive(seg & 1 ? 15 : 4, 160);
      }
    }
  } else {
    asm volatile("setmaxnreg.inc.sync.aligned.u32 200;");
    {
      const int g = lane >> 2, t = lane & 3;
      const uint32_t eb = sb + A_EPI + wg * A_EPW, d0 = (sb & 0x3FFFF) >> 4;
      const uint32_t own = (2 * t <= g ? 0xffffu : 0u) | (2 * t < g ? 0xffff0000u : 0u);
      const int kmin = 7 - 57 * tile - 16 * w;
      __half2 ho = __float2half2_rn(0.f);
#pragma unroll 1
      for (int c = -DRY; c < 4; c++) {
        float acc[96], tl[12];
#pragma unroll 1
        for (int r = c < 0 ? 4 : 0; r < 4; r++) {
#pragma unroll
          for (int st = 0; st < A_NS; st++) {
            const int ks = r * 9 + st;
            if (c == 0 && st % 3 == 0 && ks % 12 == 0) mbar_wait(fullx + 8 * (ks / 12), 0);
            mbar_wait(full1 + 8 * st, r & 1);
            const uint64_t da = desc_at(d0 + wg * (A_XH >> 4) + (ks >> 2) * 512 + (ks & 3) * 2, 16, 1024, 1);
            WG_FENCE();
            wgmma_n192_ss_nt(acc, da, desc_at(d0 + ((A_RING + st * A_WM) >> 4), 2048, 1024, 1), ks);
            if (!(AX & 2)) wgmma_n24_ss_nt(tl, da, desc_at(d0 + ((A_TAIL + st * A_WT) >> 4), 128, 256, 0), ks);
            WG_COMMIT();
            if (st == 0 && r == 2) bar_sync(11 + wg, 160);
            WG_WAIT(1);
            if (ks > 0 && lane == 0) mbar_arrive(empty1 + 8 * ((st + A_NS - 1) % A_NS));
          }
        }
        WG_WAIT(0);
        if (lane == 0 && c >= 0) mbar_arrive(empty1 + 8 * (A_NS - 1));
        ASTAMP(16 + (c & 3));
        uint32_t ql[9], qh[9], kl[9], kh[9], kx[10], vl[9], vh[9], vx[10];
#pragma unroll
        for (int j = 0; j < 9; j++) {
          const float* const q = j < 8 ? acc + 4 * j : tl, * const k = j < 8 ? acc + 32 + 4 * j : tl + 4, * const v = j < 8 ? acc + 64 + 4 * j : tl + 8;
          kh[j] = pack_bf16(k[2], k[3]); vh[j] = pack_bf16(v[2], v[3]);
          ql[j] = pack_bf16(q[0], q[1]); qh[j] = pack_bf16(q[2], q[3]); kl[j] = pack_bf16(k[0], k[1]); vl[j] = pack_bf16(v[0], v[1]);
        }
        if (w < 3) {
          const uint32_t ha = eb + 1024 + w * 2304 + lane * 16;
          stsm4(ha, kh[0], kh[1], kh[2], kh[3]); stsm4(ha + 512, kh[4], kh[5], kh[6], kh[7]);
          stsm4(ha + 1024, vh[0], vh[1], vh[2], vh[3]); stsm4(ha + 1536, vh[4], vh[5], vh[6], vh[7]);
          asm volatile("stmatrix.sync.aligned.m8n8.x2.shared.b16 [%0], {%1,%2};" :: "r"(ha + 2048), "r"(kh[8]), "r"(vh[8]) : "memory");
        }
        if (c == 0) bar_sync(7, 384); else bar_sync(1 + wg, 128);
        {
          const uint32_t ha = eb + 1024 + max(w - 1, 0) * 2304 + lane * 16;
          ldsm4(kx, ha); ldsm4(kx + 4, ha + 512); ldsm4t(vx, ha + 1024); ldsm4t(vx + 4, ha + 1536);
          asm volatile("ldmatrix.sync.aligned.m8n8.x1.shared.b16 {%0}, [%1];" : "=r"(kx[8]) : "r"(ha + 2048) : "memory");
          asm volatile("ldmatrix.sync.aligned.m8n8.x1.trans.shared.b16 {%0}, [%1];" : "=r"(vx[8]) : "r"(ha + 2176) : "memory");
        }
        const float gl = __uint_as_float(lds32(sb + A_GATE + (wg * 64 + w * 16 + g) * 4)), gh = __uint_as_float(lds32(sb + A_GATE + (wg * 64 + w * 16 + g + 8) * 4));
#pragma unroll
        for (int j = 0; j < 9; j++) { vl[j] = movm(vl[j]); vh[j] = movm(vh[j]); }
        bar_sync(1 + wg, 128);
        uint32_t ol[9], oh[9];
#pragma unroll
        for (int i = 0; i < 4; i++) {
          const int b = 2 * i;
          const uint32_t a[4] = {t >= i ? ql[b] : 0u, t >= i ? qh[b] : 0u, ql[b + 1], qh[b + 1]}, a4 = t <= i ? ql[b + 2] : 0u, a5 = t <= i ? qh[b + 2] : 0u;
          float sx[4], sl[4], sh[4];
          mma16816z(sx, a, kx[b], kx[b + 1]); mma16816z(sl, a, kl[b], kl[b + 1]); mma16816z(sh, a, kh[b], kh[b + 1]);
          mma1688(sx, a4, a5, kx[b + 2]); mma1688(sl, a4, a5, kl[b + 2]); mma1688(sh, a4, a5, kh[b + 2]);
          float e[4];
#pragma unroll
          for (int u = 0; u < 4; u++) {
            const int cc = 2 * t + (u & 1);
            e[u] = (cc <= g ? (u < 2 ? sl[u] : sh[u]) : (u < 2 ? sx[u] : sl[u])) * (0.23570226039551584f * LOG2E);
            if ((cc <= g ? cc : cc - 8) + (u & 2) * 4 < kmin) e[u] = -1.0e9f * LOG2E;
          }
          float m0 = fmaxf(e[0], e[1]), m1 = fmaxf(e[2], e[3]);
#pragma unroll
          for (int o = 1; o < 4; o <<= 1) { m0 = fmaxf(m0, __shfl_xor_sync(0xffffffffu, m0, o)); m1 = fmaxf(m1, __shfl_xor_sync(0xffffffffu, m1, o)); }
          e[0] = ex2(e[0] - m0); e[1] = ex2(e[1] - m0); e[2] = ex2(e[2] - m1); e[3] = ex2(e[3] - m1);
          const uint32_t p0 = pack_bf16(e[0], e[1]), p1 = pack_bf16(e[2], e[3]);
          const uint32_t p[4] = {p0 & ~own, 0u, p0 & own, p1 & ~own};
          float s0 = e[0] + e[1], s1 = e[2] + e[3];
#pragma unroll
          for (int o = 1; o < 4; o <<= 1) { s0 += __shfl_xor_sync(0xffffffffu, s0, o); s1 += __shfl_xor_sync(0xffffffffu, s1, o); }
          const float f0 = gl * rcp(s0), f1 = gh * rcp(s1);
#pragma unroll
          for (int j = b; j < b + 3; j++) {
            float o[4];
            mma16816z(o, p, vx[j], vl[j]);
            mma1688(o, 0u, p1 & own, vh[j]);
            const uint32_t lo = pack_bf16(o[0] * f0, o[1] * f0), hi = pack_bf16(o[2] * f1, o[3] * f1);
            if (j > b || i == 0) { ol[j] = lo; oh[j] = hi; }
            else { ol[j] = t >= i ? lo : ol[j]; oh[j] = t >= i ? hi : oh[j]; }
          }
        }
        const uint32_t sa = eb + 16 + (w * 16 + (lane & 15)) * 144 + (lane >> 4) * 16;
#pragma unroll
        for (int j = 0; j < 8; j += 2) stsm4(sa + j * 16, ol[j], oh[j], ol[j + 1], oh[j + 1]);
        asm volatile("stmatrix.sync.aligned.m8n8.x2.shared.b16 [%0], {%1,%2};" :: "r"(sa + 128), "r"(ol[8]), "r"(oh[8]) : "memory");
        ho = amax4(amax4(amax4(amax4(ho, ol), ol + 4), oh), oh + 4);
        ho = __hmax2_nan(__hmax2_nan(ho, __habs2(*(const __half2*)&ol[8])), __habs2(*(const __half2*)&oh[8]));
        if (c == 3 && tile == 17) {
          const uint32_t eo = wexp(ho);
          if (lane == 0) atomicMax(&g_amax[16], (unsigned long long)(lds32(sb + A_BAR + 376) + 1) << 32 | eo);
        }
        fence_async();
        if (c >= 0) bar_arrive(13 + wg, 160); else bar_sync(1 + wg, 128);
        ASTAMP(20 + (c & 3));
      }
    }
    ASTAMP(3);
    uint32_t wa[36][4];
    mbar_wait(fullw, 0);
    const uint32_t la = sb + wg * 73728 + ((lane & 7) + ((lane >> 4) << 3)) * 128 + (((2 * w + ((lane >> 3) & 1)) ^ (lane & 7)) << 4);
#pragma unroll
    for (int k = 0; k < 36; k++) ldsm4t(wa[k], la + k * 2048);
    sts64(sb + A_XW + wg * 2048 + 1024 + (tid & 127) * 8, 0, 0);
    fence_async();
    bar_sync(6, 288);
    ASTAMP(4);
    const int nsl = p3_n(wg), ke = p3_k(wg), t = lane & 3;
    const unsigned epoch = lds32(sb + A_BAR + 376);
    uint2* const part = g_part + nsl * 4096 + w * 16 + (lane >> 2) * 2 + (t & 1);
    auto tag = [&](int seg) { return PR == 8 ? ((seg >> 3) + 1 + (epoch & (seg >> 1) & (seg >> 2))) & 1 : ((seg >> 2) + 1 + (epoch & (seg >> 1))) & 1; };
    uint2 v[4];
    auto fetch = [&](int seg) {
#pragma unroll
      for (int j = 0; j < 4; j++)
        asm volatile("ld.relaxed.gpu.global.v2.b32 {%0,%1}, [%2];" : "=r"(v[j].x), "=r"(v[j].y) : "l"(part + (seg & (PR - 1)) * 36864 + ke * 512 + ((t >> 1) * 4 + j) * 64) : "memory");
    };
    auto finish = [&](int seg) {
      int n = 0;
#pragma unroll 1
      while (!(AX & 16) && __any_sync(0xffffffffu, (((v[0].x ^ tag(seg)) | (v[1].x ^ tag(seg)) | (v[2].x ^ tag(seg)) | (v[3].x ^ tag(seg))) & 1) != 0) && ++n < SPIN_LIMIT) {
        if (seg < NAUXSEG - ((TL & 2) ? 2 : 1)) __nanosleep(100);
        fetch(seg);
      }
      const float a0 = (bf_lo(v[0].x) + bf_lo(v[1].x)) + (bf_lo(v[2].x) + bf_lo(v[3].x)), a1 = (bf_hi(v[0].x) + bf_hi(v[1].x)) + (bf_hi(v[2].x) + bf_hi(v[3].x));
      const float b0 = (bf_lo(v[0].y) + bf_lo(v[1].y)) + (bf_lo(v[2].y) + bf_lo(v[3].y)), b1 = (bf_hi(v[0].y) + bf_hi(v[1].y)) + (bf_hi(v[2].y) + bf_hi(v[3].y));
      const float c0 = (t < 2 ? a0 : b0) + __shfl_xor_sync(0xffffffffu, t < 2 ? b0 : a0, 2), c1 = (t < 2 ? a1 : b1) + __shfl_xor_sync(0xffffffffu, t < 2 ? b1 : a1, 2);
      ((uint32_t*)(out + (size_t)(seg * 32 + ke * 4 + ((lane >> 2) & 3)) * DM + nsl * 64 + w * 16 + (lane >> 4) * 8))[t] = movm(pack_bf16(c0, c1));
    };
    float acc[16];
    int done = 0;
    const uint32_t d0 = (sb & 0x3FFFF) >> 4;
#pragma unroll 1
    for (int seg = 0; seg < NAUXSEG; seg++) {
      const int i = cta < NH ? seg : 2 * seg + wg, sl = i & 3;
      if (DRAIN) {
#pragma unroll 1
        while (done < seg && !mbar_test(full3 + 8 * sl, (i >> 2) & 1)) { fetch(done); finish(done); done++; }
      }
      mbar_wait(full3 + 8 * sl, (i >> 2) & 1);
      if (STG && seg == 0 && wg == 1) bar_sync(9, 256);
      if (tid == 128) SSTAMP(6, seg);
      if (!(AX & 16)) fetch(done);
      if (!(AX & 64)) {
        const uint64_t db = desc_at(d0 + sl * (XT >> 4), 16, 1024, 1);
        WG_FENCE();
        wgmma_n32_ss_tn(acc, desc_at(d0 + ((A_XW + wg * 2048) >> 4), 8192, 1024, 1), desc_at(d0 + (A_XT >> 4) + sl * 32, 0, 128, 0), 0);
#pragma unroll
        for (int k = 0; k < 36; k++) {
          wgmma_n32_rs(acc, wa[k][0], wa[k][1], wa[k][2], wa[k][3], db + (k >> 2) * 256 + (k & 3) * 2, 1);
          if (STG && k == STG && seg == 0 && wg == 0) bar_arrive(9, 256);
        }
        WG_COMMIT();
      }
      if (done <= seg - PL) finish(done++);
      WG_WAIT(0);
      if (lane == 0) mbar_arrive(empty3 + 8 * sl);
#pragma unroll
      for (int j = 0; j < 4; j++)
        if (!(AX & 16))
          asm volatile("st.relaxed.gpu.global.v2.b32 [%0], {%1,%2};" :: "l"(part + (seg & (PR - 1)) * 36864 + (2 * j + (t >> 1)) * 512 + ke * 64),
                       "r"((pack_bf16(acc[4 * j], acc[4 * j + 1]) & ~1u) | tag(seg)), "r"(pack_bf16(acc[4 * j + 2], acc[4 * j + 3])) : "memory");
      if (tid == 128) SSTAMP(7, seg);
      if (tid == 128) SSTAMP(8, seg);
      if ((seg & 7) == 6) ASTAMP(5 + (seg >> 3));
    }
#pragma unroll 1
    for (; done < NAUXSEG; done++) { fetch(done); finish(done); }
    ASTAMP(13);
    TSTAMP(48);
    bar_sync(6, 288);
  }
}

typedef CUresult (*EncodeFn)(CUtensorMap*, CUtensorMapDataType, cuuint32_t, void*, const cuuint64_t*, const cuuint64_t*,
                             const cuuint32_t*, const cuuint32_t*, CUtensorMapInterleave, CUtensorMapSwizzle,
                             CUtensorMapL2promotion, CUtensorMapFloatOOBfill);
static void make_map(EncodeFn enc, CUtensorMap* m, const void* p, int rows, int cols, int box_rows) {
  cuuint64_t dims[2] = {(cuuint64_t)cols, (cuuint64_t)rows};
  cuuint64_t strides[1] = {(cuuint64_t)cols * 2};
  cuuint32_t box[2] = {64, (cuuint32_t)box_rows};
  cuuint32_t es[2] = {1, 1};
  enc(m, CU_TENSOR_MAP_DATA_TYPE_BFLOAT16, 2, (void*)p, dims, strides, box, es, CU_TENSOR_MAP_INTERLEAVE_NONE,
      CU_TENSOR_MAP_SWIZZLE_128B, CU_TENSOR_MAP_L2_PROMOTION_L2_128B, CU_TENSOR_MAP_FLOAT_OOB_FILL_NONE);
}

constexpr int g_poll = POLL_NS;
extern "C" void kernel_launch(void* const* d_in, const int* in_sizes, int n_in, void* d_out, int out_size) {
  const bf16* x = (const bf16*)d_in[0];
  const bf16* wqkvA = (const bf16*)d_in[1];
  const bf16* woA = (const bf16*)d_in[2];
  const bf16* mem0 = (const bf16*)d_in[4];
  const bf16* Wq = (const bf16*)d_in[5];
  const bf16* Wk = (const bf16*)d_in[6];
  const bf16* Wv = (const bf16*)d_in[7];
  const bf16* Wo = (const bf16*)d_in[8];
  const bf16* gate_w = (const bf16*)d_in[10];
  static EncodeFn enc = nullptr;
  static void *pO = nullptr, *pR = nullptr;
  if (!enc) {
    cudaDriverEntryPointQueryResult qr;
    cudaGetDriverEntryPoint("cuTensorMapEncodeTiled", (void**)&enc, cudaEnableDefault, &qr);
    cudaGetSymbolAddress(&pO, g_Ocat);
    cudaGetSymbolAddress(&pR, g_red_raw);
    cudaFuncSetAttribute(rec_kernel, cudaFuncAttributeMaxDynamicSharedMemorySize, SM_TOTAL);
    cudaFuncSetAttribute(aux_kernel, cudaFuncAttributeMaxDynamicSharedMemorySize, A_TOTAL);
  }
  RMaps rm;
  rm.poll = g_poll; rm.out = (bf16*)d_out;
  make_map(enc, &rm.woa, woA, DM, DM, 24);
  {
    cuuint64_t dims[2] = {KCAT, S_LEN}, strides[1] = {KCAT * 2};
    cuuint32_t box[2] = {32, 64}, es[2] = {1, 1};
    enc(&rm.oa, CU_TENSOR_MAP_DATA_TYPE_BFLOAT16, 2, pO, dims, strides, box, es, CU_TENSOR_MAP_INTERLEAVE_NONE,
        CU_TENSOR_MAP_SWIZZLE_NONE, CU_TENSOR_MAP_L2_PROMOTION_NONE, CU_TENSOR_MAP_FLOAT_OOB_FILL_NONE);
  }
  rm.red = (unsigned char*)(((uintptr_t)pR + 262143) & ~(uintptr_t)262143);
  {
    cuuint64_t dims[3] = {64, S_LEN, 9}, strides[2] = {DM * 2, 128};
    cuuint32_t box[3] = {64, 32, 9}, es[3] = {1, 1, 1};
    enc(&rm.x, CU_TENSOR_MAP_DATA_TYPE_BFLOAT16, 3, (void*)x, dims, strides, box, es, CU_TENSOR_MAP_INTERLEAVE_NONE,
        CU_TENSOR_MAP_SWIZZLE_128B, CU_TENSOR_MAP_L2_PROMOTION_L2_128B, CU_TENSOR_MAP_FLOAT_OOB_FILL_NONE);
  }
  make_map(enc, &rm.wq, Wq, DM, 4096, 192);
  make_map(enc, &rm.wk, Wk, DM, 4096, 192);
  make_map(enc, &rm.wv, Wv, DM, 4096, 192);
  make_map(enc, &rm.wo, Wo, 4096, DM, 128);
  AMaps am;
  {
    cuuint32_t es[4] = {1, 1, 1, 1};
    cuuint64_t dx[4] = {64, 2, S_LEN / 2, 9}, sx[3] = {DM * 2, DM * 4, 128};
    cuuint32_t bx[4] = {64, 1, 64, 3};
    enc(&am.x, CU_TENSOR_MAP_DATA_TYPE_BFLOAT16, 4, (void*)x, dx, sx, bx, es, CU_TENSOR_MAP_INTERLEAVE_NONE,
        CU_TENSOR_MAP_SWIZZLE_128B, CU_TENSOR_MAP_L2_PROMOTION_L2_128B, CU_TENSOR_MAP_FLOAT_OOB_FILL_NONE);
    cuuint64_t dw[3] = {DM, DM, 3}, sw[2] = {DM * 6, DM * 2};
    cuuint32_t bw[3] = {64, 16, 3}, bt[3] = {8, 16, 3};
    enc(&am.wa, CU_TENSOR_MAP_DATA_TYPE_BFLOAT16, 3, (void*)wqkvA, dw, sw, bw, es, CU_TENSOR_MAP_INTERLEAVE_NONE,
        CU_TENSOR_MAP_SWIZZLE_128B, CU_TENSOR_MAP_L2_PROMOTION_L2_128B, CU_TENSOR_MAP_FLOAT_OOB_FILL_NONE);
    enc(&am.wt, CU_TENSOR_MAP_DATA_TYPE_BFLOAT16, 3, (void*)wqkvA, dw, sw, bt, es, CU_TENSOR_MAP_INTERLEAVE_NONE,
        CU_TENSOR_MAP_SWIZZLE_NONE, CU_TENSOR_MAP_L2_PROMOTION_NONE, CU_TENSOR_MAP_FLOAT_OOB_FILL_NONE);
    cuuint64_t dz[3] = {KCAT, 2, S_LEN / 2}, sz[2] = {KCAT * 2, KCAT * 4};
    cuuint32_t bz[3] = {72, 1, 57};
    enc(&am.oa, CU_TENSOR_MAP_DATA_TYPE_BFLOAT16, 3, pO, dz, sz, bz, es, CU_TENSOR_MAP_INTERLEAVE_NONE,
        CU_TENSOR_MAP_SWIZZLE_NONE, CU_TENSOR_MAP_L2_PROMOTION_NONE, CU_TENSOR_MAP_FLOAT_OOB_FILL_NONE);
  }
  {
    cuuint64_t dims[3] = {64, S_LEN, KCAT / 64}, strides[2] = {KCAT * 2, 128};
    cuuint32_t box[3] = {64, 32, 9}, es[3] = {1, 1, 1};
    make_map(enc, &am.o, pO, S_LEN, KCAT, 32);
    enc(&am.o3, CU_TENSOR_MAP_DATA_TYPE_BFLOAT16, 3, pO, dims, strides, box, es, CU_TENSOR_MAP_INTERLEAVE_NONE,
        CU_TENSOR_MAP_SWIZZLE_128B, CU_TENSOR_MAP_L2_PROMOTION_L2_128B, CU_TENSOR_MAP_FLOAT_OOB_FILL_NONE);
  }
  make_map(enc, &am.wob, Wo, 4096, DM, 64);
  make_map(enc, &am.woa, woA, DM, DM, 64);
  make_map(enc, &am.wo8, woA, DM, DM, 8);
  {
    cuuint64_t dims[2] = {KCAT, S_LEN}, strides[1] = {KCAT * 2};
    cuuint32_t box[2] = {8, 32}, es[2] = {1, 1};
    enc(&am.o8, CU_TENSOR_MAP_DATA_TYPE_BFLOAT16, 2, pO, dims, strides, box, es, CU_TENSOR_MAP_INTERLEAVE_NONE,
        CU_TENSOR_MAP_SWIZZLE_NONE, CU_TENSOR_MAP_L2_PROMOTION_NONE, CU_TENSOR_MAP_FLOAT_OOB_FILL_NONE);
  }

  rec_kernel<<<96, 384, SM_TOTAL, cudaStreamPerThread>>>(rm, x, mem0);
  cudaLaunchConfig_t cfg = {};
  cfg.gridDim = dim3(NAUX); cfg.blockDim = dim3(512); cfg.dynamicSmemBytes = A_TOTAL; cfg.stream = cudaStreamPerThread;
  cudaLaunchAttribute at[1];
  at[0].id = cudaLaunchAttributeProgrammaticStreamSerialization; at[0].val.programmaticStreamSerializationAllowed = 1;
  cfg.attrs = at; cfg.numAttrs = 1;
  if (XP & 16) cfg.numAttrs = 0;
  if (!(XP & 64)) cudaLaunchKernelEx(&cfg, aux_kernel, am, wqkvA, woA, gate_w, (bf16*)d_out);
}
```

```cpp
#include <cuda_runtime.h>
#include <cuda_bf16.h>
#include <cuda_fp16.h>
#include <cuda.h>
#include <stdint.h>

typedef __nv_bfloat16 bf16;

constexpr int S_LEN = 2048, DM = 576, NH = 32, DH = 128, NSEG = 64, KCAT = 4096 + 576;
constexpr int NAUXSEG = NSEG - 2;
constexpr int NAUX = 36;
#define RED_LINE(i) (((i) >> 2) * 4096 + ((i) & 1) * 256 + ((i) & 2) * 512)
#define RED_SLOT(s) (((s) & 1) * 128 + ((s) & 2) * 256)

#define POLL_NS 896
#define NII 18
#define W3PRE 4
#define W3MID 4
#define GF 0
#define B5POS 0
#define NUP 4
#define UPF 1
#define B3Q 9
#define B3F 0
#define GATE 7
#define NTL 2
#define B7R 1
#define VS0 1
#define VS1 0
#define VLATE(w) ((w) == 0 ? VS0 == 1 : (w) == 1 ? VS1 == 1 : false)
#define HOIST 1
#define RSLOW 0
#define CSY 0
#define DD 2
#define N12 18
#define N14 18
#define HP 0
#define HL 0
#define WL 1
#define RV 3
#define RET 1
#define TL 6
#define CLR 1
#define RFW 0
#define NIC 0
#define LEAD 0
#define FIN16 1
#define VXG 0
#define NRING 20
#define EXD 0
#define HDLY 0
#define F10 1
#define NPROBE 2
#define QM 0
#define N5 224
#define KP(i) (((i) >> 1) + 4 * ((i) & 1))
#define SPIN_LIMIT (1 << 14)
#define XP 0

__device__ __align__(1024) bf16 g_Ocat[S_LEN * KCAT];
__device__ __align__(1024) unsigned char g_red_raw[2 * 262144];
constexpr int HINT_OFF = 2048;
__device__ __align__(16) float g_gate[S_LEN];
__device__ __align__(128) uint4 g_stats[96 * 2];
__device__ unsigned g_epoch;
__device__ unsigned g_epoch2;
__device__ unsigned g_ocnt[NSEG * 64];
__device__ unsigned g_abar[3 * 32];
__device__ unsigned long long g_amax[2 * 16];
__device__ unsigned g_scnt[NSEG * 32 * 8];
__device__ __align__(1024) unsigned char g_seg[NRING * 96 * 10240];
__device__ unsigned g_used[NH * 32];
__device__ __align__(1024) uint2 g_part[8 * 9 * 64 * 64];
__device__ int g_err;
#define TSTAMP(i)
#define PROF(idx)
#define PROFP(idx)
#define RSTAMP(k)
#define STAMP(idx)
#define ASTAMP(idx)
#define SSTAMP(k, seg)
#define WSTAMP(idx)

#define DI __device__ __forceinline__
DI uint32_t smem_u32(const void* p) { return (uint32_t)__cvta_generic_to_shared(p); }
DI uint32_t clock32() { uint32_t c; asm volatile("mov.u32 %0, %%clock;" : "=r"(c) :: "memory"); return c; }
DI uint32_t gtime() { uint32_t c; asm volatile("mov.u32 %0, %%globaltimer_lo;" : "=r"(c) :: "memory"); return c; }
DI uint32_t ldg_relaxed32(const void* p) { uint32_t v; asm volatile("ld.relaxed.gpu.global.b32 %0, [%1];" : "=r"(v) : "l"(p) : "memory"); return v; }
DI uint32_t ldg_acquire32(const void* p) { uint32_t v; asm volatile("ld.acquire.gpu.global.b32 %0, [%1];" : "=r"(v) : "l"(p) : "memory"); return v; }
DI void stg_relaxed32(void* p, uint32_t v) { asm volatile("st.relaxed.gpu.global.b32 [%0], %1;" :: "l"(p), "r"(v) : "memory"); }
DI int head_id() { int c; asm volatile("mov.u32 %0, %%clusterid.x;" : "=r"(c)); return c; }
DI uint32_t mapa(uint32_t a, uint32_t r) { uint32_t o; asm("mapa.shared::cluster.u32 %0, %1, %2;" : "=r"(o) : "r"(a), "r"(r)); return o; }
DI void cluster_arrive() { asm volatile("barrier.cluster.arrive.relaxed.aligned;" ::: "memory"); }
DI void cluster_wait() { asm volatile("barrier.cluster.wait.aligned;" ::: "memory"); }
DI void cluster_sync() { asm volatile("barrier.cluster.arrive.release.aligned;\nbarrier.cluster.wait.acquire.aligned;" ::: "memory"); }
DI void mbar_init(uint32_t b, uint32_t c) { asm volatile("mbarrier.init.shared::cta.b64 [%0], %1;" :: "r"(b), "r"(c) : "memory"); }
DI void mbar_expect(uint32_t b, uint32_t tx) { asm volatile("mbarrier.arrive.expect_tx.shared::cta.b64 _, [%0], %1;" :: "r"(b), "r"(tx) : "memory"); }
DI void mbar_arrive(uint32_t b) { asm volatile("mbarrier.arrive.shared::cta.b64 _, [%0];" :: "r"(b) : "memory"); }
DI void mbar_wait(uint32_t b, uint32_t par) {
  asm volatile("{\n.reg .pred p;\n.reg .u32 n, q;\nmov.u32 n, 0;\n"
               "WL: add.u32 n, n, 1;\nshr.u32 q, n, 12;\nxor.b32 q, q, %1;\n"
               "mbarrier.try_wait.parity.shared::cta.b64 p, [%0], q;\n@!p bra.uni WL;\n}"
               :: "r"(b), "r"(par) : "memory");
}
DI bool mbar_test(uint32_t b, uint32_t par) {
  uint32_t r;
  asm volatile("{\n.reg .pred p;\nmbarrier.test_wait.parity.shared::cta.b64 p, [%1], %2;\nselp.u32 %0, 1, 0, p;\n}" : "=r"(r) : "r"(b), "r"(par) : "memory");
  return r;
}
DI void mbar_wait_fast(uint32_t b, uint32_t par) {
  asm volatile("{\n.reg .pred p;\n.reg .u32 n, q;\nmbarrier.try_wait.parity.shared::cta.b64 p, [%0], %1;\n@p bra.uni WD;\nmov.u32 n, 0;\n"
               "WL: add.u32 n, n, 1;\nshr.u32 q, n, 12;\nxor.b32 q, q, %1;\n"
               "mbarrier.try_wait.parity.shared::cta.b64 p, [%0], q;\n@!p bra.uni WL;\nWD:\n}"
               :: "r"(b), "r"(par) : "memory");
}
DI void wait_until(uint32_t t) {
  const uint32_t now = gtime();
  t = min(t, now + 8192);
  asm volatile("{\n.reg .pred p;\n.reg .u32 c;\nTL: mov.u32 c, %%globaltimer_lo;\nsetp.lt.u32 p, c, %0;\n@p bra.uni TL;\n}" :: "r"(t) : "memory");
}
#define PIN(v) v = __shfl_xor_sync(0xffffffffu, v, 0)
#define SCHED_FENCE(k) asm volatile("{\n.reg .pred p;\nsetp.eq.u32 p, %0, %1;\n@p exit;\n}" :: "r"(fence_reg), "r"(k) : "memory")
#define MEM_ORDER(k) asm volatile("{\n.reg .pred p;\nsetp.eq.u32 p, %0, %1;\n@p st.shared.u32 [%0], %0;\n}" :: "r"(fence_reg), "r"(k + 64) : "memory")
DI void bar_sync(int id, int n) { asm volatile("bar.sync %0, %1;" :: "r"(id), "r"(n) : "memory"); }
DI void bar_arrive(int id, int n) { asm volatile("bar.arrive %0, %1;" :: "r"(id), "r"(n) : "memory"); }
DI void fence_async() { asm volatile("fence.proxy.async.shared::cta;" ::: "memory"); }
DI void st_async4(uint32_t a, uint32_t x, uint32_t y, uint32_t z, uint32_t w, uint32_t mb) {
  asm volatile("st.async.weak.shared::cluster.mbarrier::complete_tx::bytes.v4.b32 [%0], {%1,%2,%3,%4}, [%5];"
               :: "r"(a), "r"(x), "r"(y), "r"(z), "r"(w), "r"(mb) : "memory");
}
DI void st_async2(uint32_t a, uint32_t x, uint32_t y, uint32_t mb) {
  asm volatile("st.async.weak.shared::cluster.mbarrier::complete_tx::bytes.v2.b32 [%0], {%1,%2}, [%3];"
               :: "r"(a), "r"(x), "r"(y), "r"(mb) : "memory");
}
DI void sts32(uint32_t a, uint32_t x) { asm volatile("st.shared.b32 [%0], %1;" :: "r"(a), "r"(x) : "memory"); }
DI void sts64(uint32_t a, uint32_t x, uint32_t y) { asm volatile("st.shared.v2.b32 [%0], {%1,%2};" :: "r"(a), "r"(x), "r"(y) : "memory"); }
DI void sts128(uint32_t a, uint32_t x, uint32_t y, uint32_t z, uint32_t w) {
  asm volatile("st.shared.v4.b32 [%0], {%1,%2,%3,%4};" :: "r"(a), "r"(x), "r"(y), "r"(z), "r"(w) : "memory");
}
DI uint32_t lds32(uint32_t a) { uint32_t x; asm volatile("ld.shared.b32 %0, [%1];" : "=r"(x) : "r"(a) : "memory"); return x; }
DI void lds64(uint32_t a, uint32_t& x, uint32_t& y) { asm volatile("ld.shared.v2.b32 {%0,%1}, [%2];" : "=r"(x), "=r"(y) : "r"(a) : "memory"); }
DI void lds128(uint32_t a, uint32_t* r) {
  asm volatile("ld.shared.v4.b32 {%0,%1,%2,%3}, [%4];" : "=r"(r[0]), "=r"(r[1]), "=r"(r[2]), "=r"(r[3]) : "r"(a) : "memory");
}
DI void lds128f(uint32_t a, float* r) {
  asm volatile("ld.shared.v4.f32 {%0,%1,%2,%3}, [%4];" : "=f"(r[0]), "=f"(r[1]), "=f"(r[2]), "=f"(r[3]) : "r"(a) : "memory");
}
DI void lds64f(uint32_t a, float* r) { asm volatile("ld.shared.v2.f32 {%0,%1}, [%2];" : "=f"(r[0]), "=f"(r[1]) : "r"(a) : "memory"); }
DI void ldsm4t(uint32_t* r, uint32_t a) {
  asm volatile("ldmatrix.sync.aligned.m8n8.x4.trans.shared.b16 {%0,%1,%2,%3}, [%4];"
               : "=r"(r[0]), "=r"(r[1]), "=r"(r[2]), "=r"(r[3]) : "r"(a) : "memory");
}
DI void ldsm4t_in(uint32_t* r, uint32_t a, uint32_t t) {
  asm volatile("{\n.reg .pred p;\nsetp.ne.u32 p, %5, 0;\n@p ldmatrix.sync.aligned.m8n8.x4.trans.shared.b16 {%0,%1,%2,%3}, [%4];\n}"
               : "+r"(r[0]), "+r"(r[1]), "+r"(r[2]), "+r"(r[3]) : "r"(a), "r"(t) : "memory");
}
DI void lds128_in(uint32_t* r, uint32_t a, uint32_t t) {
  asm volatile("{\n.reg .pred p;\nsetp.ne.u32 p, %5, 0;\n@p ld.shared.v4.b32 {%0,%1,%2,%3}, [%4];\n}"
               : "+r"(r[0]), "+r"(r[1]), "+r"(r[2]), "+r"(r[3]) : "r"(a), "r"(t) : "memory");
}
DI void ldsm2t_in(uint32_t* r, uint32_t a, uint32_t t) {
  asm volatile("{\n.reg .pred p;\nsetp.ne.u32 p, %3, 0;\n@p ldmatrix.sync.aligned.m8n8.x2.trans.shared.b16 {%0,%1}, [%2];\n}" : "+r"(r[0]), "+r"(r[1]) : "r"(a), "r"(t) : "memory");
}
DI void reserve2(uint32_t* r) { asm volatile("{\n.reg .u64 t;\nmov.u64 t, %%clock64;\nmov.b64 {%0, %1}, t;\n}" : "=r"(r[0]), "=r"(r[1])); }
DI void scale_sum(float& x, float& y, float s, uint32_t t) {
  asm volatile("{\n.reg .pred p;\nsetp.ne.u32 p, %2, 0;\n@p mul.f32 %0, %0, %1;\n}" : "+f"(y) : "f"(s), "r"(t));
  asm volatile("{\n.reg .pred p;\nsetp.ne.u32 p, %3, 1;\n@p fma.rn.f32 %0, %0, %1, %2;\n}" : "+f"(x) : "f"(s), "f"(y), "r"(t));
}
DI void ldsm4(uint32_t* r, uint32_t a) {
  asm volatile("ldmatrix.sync.aligned.m8n8.x4.shared.b16 {%0,%1,%2,%3}, [%4];"
               : "=r"(r[0]), "=r"(r[1]), "=r"(r[2]), "=r"(r[3]) : "r"(a) : "memory");
}
DI void st_async1(uint32_t a, uint32_t x, uint32_t mb) {
  asm volatile("st.async.weak.shared::cluster.mbarrier::complete_tx::bytes.b32 [%0], %1, [%2];" :: "r"(a), "r"(x), "r"(mb) : "memory");
}
DI void stsm4(uint32_t a, uint32_t x, uint32_t y, uint32_t z, uint32_t w) {
  asm volatile("stmatrix.sync.aligned.m8n8.x4.shared.b16 [%0], {%1,%2,%3,%4};" :: "r"(a), "r"(x), "r"(y), "r"(z), "r"(w) : "memory");
}
DI void stsm4t(uint32_t a, uint32_t x, uint32_t y, uint32_t z, uint32_t w) {
  asm volatile("stmatrix.sync.aligned.m8n8.x4.trans.shared.b16 [%0], {%1,%2,%3,%4};" :: "r"(a), "r"(x), "r"(y), "r"(z), "r"(w) : "memory");
}
DI uint32_t pack_bf16(float lo, float hi) { uint32_t r; asm("cvt.rn.bf16x2.f32 %0, %1, %2;" : "=r"(r) : "f"(hi), "f"(lo)); return r; }
DI uint32_t pack_f16(float lo, float hi) { uint32_t r; asm("cvt.rn.f16x2.f32 %0, %1, %2;" : "=r"(r) : "f"(hi), "f"(lo)); return r; }
DI float ex2(float x) { float y; asm("ex2.approx.ftz.f32 %0, %1;" : "=f"(y) : "f"(x)); return y; }
DI float rcp(float x) { float y; asm("rcp.approx.ftz.f32 %0, %1;" : "=f"(y) : "f"(x)); return y; }
DI float bf_lo(uint32_t x) { return __uint_as_float(x << 16); }
DI float bf_hi(uint32_t x) { return __uint_as_float(x & 0xffff0000u); }
DI void mma16816(float* d, const uint32_t* a, uint32_t b0, uint32_t b1) {
  asm volatile("mma.sync.aligned.m16n8k16.row.col.f32.bf16.bf16.f32 {%0,%1,%2,%3}, {%4,%5,%6,%7}, {%8,%9}, {%0,%1,%2,%3};"
               : "+f"(d[0]), "+f"(d[1]), "+f"(d[2]), "+f"(d[3]) : "r"(a[0]), "r"(a[1]), "r"(a[2]), "r"(a[3]), "r"(b0), "r"(b1));
}
DI void mma16816z(float* d, const uint32_t* a, uint32_t b0, uint32_t b1) {
  asm volatile("mma.sync.aligned.m16n8k16.row.col.f32.bf16.bf16.f32 {%0,%1,%2,%3}, {%4,%5,%6,%7}, {%8,%9}, {%10,%10,%10,%10};"
               : "=f"(d[0]), "=f"(d[1]), "=f"(d[2]), "=f"(d[3]) : "r"(a[0]), "r"(a[1]), "r"(a[2]), "r"(a[3]), "r"(b0), "r"(b1), "f"(0.f));
}
DI void mma1688z(float* d, uint32_t a0, uint32_t a1, uint32_t b0) {
  asm volatile("mma.sync.aligned.m16n8k8.row.col.f32.bf16.bf16.f32 {%0,%1,%2,%3}, {%4,%5}, {%6}, {%7,%7,%7,%7};"
               : "=f"(d[0]), "=f"(d[1]), "=f"(d[2]), "=f"(d[3]) : "r"(a0), "r"(a1), "r"(b0), "f"(0.f));
}
DI void mma1688(float* d, uint32_t a0, uint32_t a1, uint32_t b0) {
  asm volatile("mma.sync.aligned.m16n8k8.row.col.f32.bf16.bf16.f32 {%0,%1,%2,%3}, {%4,%5}, {%6}, {%0,%1,%2,%3};"
               : "+f"(d[0]), "+f"(d[1]), "+f"(d[2]), "+f"(d[3]) : "r"(a0), "r"(a1), "r"(b0));
}
DI void ldsm2t(uint32_t* r, uint32_t a) {
  asm volatile("ldmatrix.sync.aligned.m8n8.x2.trans.shared.b16 {%0,%1}, [%2];" : "=r"(r[0]), "=r"(r[1]) : "r"(a) : "memory");
}
DI uint32_t add_bf16(uint32_t a, uint32_t b) { uint32_t r; asm("add.rn.bf16x2 %0, %1, %2;" : "=r"(r) : "r"(a), "r"(b)); return r; }
DI uint32_t mul_bf16(uint32_t a, uint32_t b) { uint32_t r; asm("mul.rn.bf16x2 %0, %1, %2;" : "=r"(r) : "r"(a), "r"(b)); return r; }
DI uint64_t make_desc(uint32_t addr, uint32_t lbo, uint32_t sbo, uint32_t swz) {
  return (uint64_t)((addr & 0x3FFFF) >> 4) | ((uint64_t)(lbo >> 4) << 16) | ((uint64_t)(sbo >> 4) << 32) | ((uint64_t)swz << 62);
}
DI uint64_t desc_at(uint32_t a16, uint32_t lbo, uint32_t sbo, uint32_t swz) {
  uint64_t d; asm("mov.b64 %0, {%1, %2};" : "=l"(d) : "r"(a16 + ((lbo >> 4) << 16)), "r"((sbo >> 4) | (swz << 30)));
  return d;
}
#define WG_FENCE() asm volatile("wgmma.fence.sync.aligned;" ::: "memory")
#define WG_COMMIT() asm volatile("wgmma.commit_group.sync.aligned;" ::: "memory")
#define WG_WAIT(n) asm volatile("wgmma.wait_group.sync.aligned %0;" :: "n"(n) : "memory")
#define ACC8(d, o) "+f"(d[o]), "+f"(d[o + 1]), "+f"(d[o + 2]), "+f"(d[o + 3]), "+f"(d[o + 4]), "+f"(d[o + 5]), "+f"(d[o + 6]), "+f"(d[o + 7])
DI void wgmma_n32_rs(float* d, uint32_t a0, uint32_t a1, uint32_t a2, uint32_t a3, uint64_t db, int acc) {
  asm volatile("{\n.reg .pred p;\nsetp.ne.b32 p, %21, 0;\n"
               "wgmma.mma_async.sync.aligned.m64n32k16.f32.bf16.bf16 {%0,%1,%2,%3,%4,%5,%6,%7,%8,%9,%10,%11,%12,%13,%14,%15}, "
               "{%16,%17,%18,%19}, %20, p, 1, 1, 0;\n}\n"
               : ACC8(d, 0), ACC8(d, 8) : "r"(a0), "r"(a1), "r"(a2), "r"(a3), "l"(db), "r"(acc));
}
template <int TA>
DI void wgmma_n32_ss(float* d, uint64_t da, uint64_t db, int acc) {
  asm volatile("{\n.reg .pred p;\nsetp.ne.b32 p, %18, 0;\n"
               "wgmma.mma_async.sync.aligned.m64n32k16.f32.bf16.bf16 {%0,%1,%2,%3,%4,%5,%6,%7,%8,%9,%10,%11,%12,%13,%14,%15}, "
               "%16, %17, p, 1, 1, %19, 1;\n}\n"
               : ACC8(d, 0), ACC8(d, 8) : "l"(da), "l"(db), "r"(acc), "n"(TA));
}
DI void tma_load(uint32_t dst, const CUtensorMap* m, int c0, int c1, uint32_t mb) {
  asm volatile("cp.async.bulk.tensor.2d.shared::cluster.global.mbarrier::complete_tx::bytes [%0], [%1, {%3, %4}], [%2];"
               :: "r"(dst), "l"(m), "r"(mb), "r"(c0), "r"(c1) : "memory");
}
DI void tma_load3(uint32_t dst, const CUtensorMap* m, int row, uint32_t mb) {
  asm volatile("cp.async.bulk.tensor.3d.shared::cluster.global.mbarrier::complete_tx::bytes [%0], [%1, {%3, %4, %3}], [%2];"
               :: "r"(dst), "l"(m), "r"(mb), "r"(0), "r"(row) : "memory");
}
DI bool elect_one() {
  uint32_t p;
  asm volatile("{\n.reg .pred p;\nelect.sync _|p, 0xffffffff;\nselp.u32 %0, 1, 0, p;\n}" : "=r"(p));
  return p;
}
DI void bulk_s2s(uint32_t dst, uint32_t src, uint32_t bytes, uint32_t mb) {
  asm volatile("cp.async.bulk.shared::cluster.shared::cta.mbarrier::complete_tx::bytes [%0], [%1], %2, [%3];"
               :: "r"(dst), "r"(src), "r"(bytes), "r"(mb) : "memory");
}
DI void tma_prefetch(const CUtensorMap* m, int c0, int c1) {
  asm volatile("cp.async.bulk.prefetch.tensor.2d.L2.global.tile [%0, {%1, %2}];" :: "l"(m), "r"(c0), "r"(c1) : "memory");
}
DI void tma_store(const CUtensorMap* m, uint32_t src, int c0, int c1) {
  asm volatile("cp.async.bulk.tensor.2d.global.shared::cta.bulk_group [%0, {%2, %3}], [%1];" :: "l"(m), "r"(src), "r"(c0), "r"(c1) : "memory");
}
DI uint4 ldg_relaxed(const void* p) {
  uint4 v;
  asm volatile("ld.relaxed.gpu.global.v4.b32 {%0,%1,%2,%3}, [%4];" : "=r"(v.x), "=r"(v.y), "=r"(v.z), "=r"(v.w) : "l"(p) : "memory");
  return v;
}
DI void stg_relaxed(void* p, uint32_t x, uint32_t y, uint32_t z, uint32_t w) {
  asm volatile("st.relaxed.gpu.global.v4.b32 [%0], {%1,%2,%3,%4};" :: "l"(p), "r"(x), "r"(y), "r"(z), "r"(w) : "memory");
}
DI void red_f16x8(void* p, uint32_t x, uint32_t y, uint32_t z, uint32_t w) {
  asm volatile("red.relaxed.gpu.global.add.noftz.v4.f16x2 [%0], {%1,%2,%3,%4};" :: "l"(p), "r"(x), "r"(y), "r"(z), "r"(w) : "memory");
}
DI void sq_acc(uint32_t& a, uint32_t x) { asm("fma.rn.bf16x2 %0, %1, %1, %0;" : "+r"(a) : "r"(x)); }
DI __half2 amax4(__half2 h, const uint32_t* v) {
  h = __hmax2_nan(__hmax2_nan(h, __habs2(*(const __half2*)&v[0])), __habs2(*(const __half2*)&v[1]));
  return __hmax2_nan(__hmax2_nan(h, __habs2(*(const __half2*)&v[2])), __habs2(*(const __half2*)&v[3]));
}
DI uint32_t wexp(__half2 h) { const uint32_t u = *(const uint32_t*)&h; return __reduce_max_sync(0xffffffffu, max((u >> 16) & 0x7fffu, u & 0x7fffu)) >> 7; }
DI float max10(const float* a) {
  return fmaxf(fmaxf(fmaxf(fmaxf(a[0], a[1]), fmaxf(a[2], a[3])), fmaxf(fmaxf(a[4], a[5]), fmaxf(a[6], a[7]))), fmaxf(a[8], a[9]));
}
DI float quad_max(float m) {
  return fmaxf(fmaxf(m, __shfl_xor_sync(0xffffffffu, m, 1)), fmaxf(__shfl_xor_sync(0xffffffffu, m, 2), __shfl_xor_sync(0xffffffffu, m, 3)));
}
DI float warp_sum(float v) {
#pragma unroll
  for (int o = 16; o; o >>= 1) v += __shfl_xor_sync(0xffffffffu, v, o);
  return v;
}

constexpr int SM_WO3 = 0;
constexpr int SM_X = 16384;
constexpr int XT = 36864;
constexpr int SM_EXP = 126976;
constexpr int SEGB = 10240;
constexpr int SM_BLK = SM_EXP + 8192;
constexpr int SM_VC = SM_BLK + 4 * SEGB;
constexpr int SM_PART = SM_VC + 16384;
constexpr int SM_QM = SM_PART + 4096;
constexpr int SM_E = SM_QM + 1024;
constexpr int SM_VM = SM_E + 1536;
constexpr int SM_OB = SM_VM + 2048;
constexpr int SM_FB = SM_OB + 2048;
constexpr int SM_STAGE = SM_X + XT;
constexpr int SM_MISC = 210944;
constexpr int SM_WOST = 212992;
constexpr int SM_MEM = SM_WOST;
constexpr int SM_MAX = SM_MEM + 11264;
#define MEM_BLK(q) ((q) / 3 * 4096 + (q) % 3 * 1024)
constexpr int SM_TOTAL = 229376;
constexpr int MB_W = SM_MISC;
constexpr int MB_WO = SM_MISC + 24;
constexpr int MB_WO3 = SM_MISC + 32;
constexpr int MB_X = SM_MISC + 40;
constexpr int MB_S = SM_MISC + 64;
constexpr int MB_F = SM_MISC + 72;
constexpr int MB_VX = SM_MISC + 80;
constexpr int SC_FPAR = SM_MISC + 136;
constexpr int SC_DEAD = SM_MISC + 96;
constexpr int SC_UNSC = SM_MISC + 112;
constexpr int SC_EPOCH = SM_MISC + 128;
constexpr int SC_EXPW = SM_MISC + 132;
constexpr int SC_ONES = SM_MISC + 144;
constexpr int SC_SS = SM_MISC + 160;
constexpr int SC_LAT = SM_MISC + 224;
constexpr int MB_T = SM_MISC + 232;
constexpr int T_SX = SM_X + XT;
constexpr int T_OB = SM_X + 2 * XT;
constexpr int T_WA = T_OB + 16384;
constexpr int T_OA = T_WA + 9216;
constexpr int T_G = T_OA + 4096;
constexpr int T_P = T_G + 512;
constexpr int T_UN = T_G + 256;
constexpr int T_RED = 131072;
constexpr int SC_XMAX = SM_MISC + 256;
constexpr int SC_PROF = 229376;

constexpr float SM_SCALE = 0.08838834764831845f;
constexpr float LOG2E = 1.4426950408889634f;
constexpr float E_LIM = 20.f;

template <bool B> struct BoolC { static constexpr bool value = B; };
struct RMaps { CUtensorMap x, wq, wk, wv, wo, woa, oa; unsigned char* red; bf16* out; uint32_t poll; };

DI uint32_t latest_hint(uint32_t h, uint32_t d, int s) {
  const uint32_t x = (((h | 0xc0c0c0c0u) - ((d >> 5) & 63) * 0x01010101u) & 0x3f3f3f3fu) | ((h ^ (((s >> 2) + 1) & 3) * 0x40404040u) & 0xc0c0c0c0u);
  const uint32_t y = __vmaxu2(x & 0x00ff00ffu, (x >> 8) & 0x00ff00ffu);
  return __reduce_max_sync(0xffffffffu, max(y & 0xffffu, y >> 16));
}
DI uint32_t near_half(uint32_t sb) {
  uint32_t a, b; lds64(sb + SC_LAT, a, b);
  return a > b;
}

template <int RT, int K0, int K1, bool D32 = false, int BAR = 0, int KB = 18>
DI void xproj(float* acc, const uint32_t (&wa)[2][18][4], uint64_t xd) {
  if (XP & 1) return;
  WG_FENCE();
#pragma unroll
  for (int k = K0; k < ((XP & 128) ? K0 + 1 : K1); k++)
  {
    uint64_t d = xd + (uint64_t)(((k >> 1) * 4096 + (k & 1) * 32) >> 4);
    if (D32) asm("mov.b64 %0, {%1, %2};" : "=l"(d) : "r"((uint32_t)xd + (((k >> 1) * 4096 + (k & 1) * 32) >> 4)), "r"((uint32_t)(xd >> 32)));
    wgmma_n32_rs(acc, wa[RT][k][0], wa[RT][k][1], wa[RT][k][2], wa[RT][k][3], d, k != 0);
    if (BAR && k == KB - 1 && KB < 18) bar_arrive(BAR, 256);
  }
  WG_COMMIT();
}

DI void seg_store(int seg, uint32_t sb, uint32_t off, uint32_t bytes) {
  asm volatile("cp.async.bulk.global.shared::cta.bulk_group [%0], [%1], %2;"
               :: "l"(g_seg + ((size_t)(seg % NRING) * 96 + blockIdx.x) * SEGB + off), "r"(sb + SM_BLK + (seg & 3) * SEGB + off), "r"(bytes) : "memory");
  asm volatile("cp.async.bulk.commit_group;" ::: "memory");
}
DI void seg_publish(int seg) {
  asm volatile("cp.async.bulk.wait_group 0;" ::: "memory");
  asm volatile("red.relaxed.gpu.global.add.u32 [%0], 1;" :: "l"(&g_scnt[(seg * 32 + blockIdx.x / 3) * 8]) : "memory");
  SSTAMP(10, seg);
}

#define NAP 64
DI uint32_t movm(uint32_t x) { uint32_t r; asm volatile("movmatrix.sync.aligned.m8n8.trans.b16 %0, %1;" : "=r"(r) : "r"(x)); return r; }
DI bool wait_count(const unsigned* p, unsigned target, bool nap = true) {
  int n = 0;
  unsigned v;
  while (true) {
    asm volatile("ld.acquire.gpu.global.b32 %0, [%1];" : "=r"(v) : "l"(p) : "memory");
    if ((int)(v - target) >= 0 || ++n > SPIN_LIMIT) break;
    if (nap) __nanosleep(NAP);
  }
  return n;
}
#define PACE 1200
#define PORD 0
DI void load_weights(uint32_t sb, const RMaps& tm, uint32_t rank, int c) {
  const int h = blockIdx.x / 3;
  if (c < 3) {
    mbar_expect(sb + MB_W + 8 * c, 49152);
    tma_load(sb + SM_STAGE + c * 49152, rank < 2 ? &tm.wk : &tm.wv, h * DH + (rank == 1 ? 64 : 0), c * 192, sb + MB_W + 8 * c);
    tma_load(sb + SM_STAGE + c * 49152 + 24576, rank < 2 ? &tm.wq : &tm.wv, h * DH + (rank == 0 ? 0 : 64), c * 192, sb + MB_W + 8 * c);
  } else {
    tma_prefetch(&tm.wo, rank * 192, h * DH);
    mbar_expect(sb + MB_WO, 16384);
    mbar_expect(sb + MB_WO3, 32768);
    tma_load(sb + SM_WOST, &tm.wo, rank * 192 + 64, h * DH, sb + MB_WO3);
    tma_load(sb + SM_WO3, &tm.wo, rank * 192 + 128, h * DH, sb + MB_WO3);
  }
}

DI void tail_attention(const uint32_t sb, const uint32_t rank, const int w, const int lane, const int sg, const int bar) {
  const int m = lane >> 3, g = lane >> 2, t = lane & 3;
  const uint32_t l16 = sb + lane * 16, src = l16 + T_SX + sg * 10240 + w * 1280;
  if (rank < 2) {
    const uint32_t base = l16 + SM_BLK + (2 + sg) * SEGB, dst = src + rank * 5120;
    uint32_t qb[2][4];
    ldsm4t(qb[0], base + w * 1024); ldsm4t(qb[1], base + w * 1024 + 512);
#pragma unroll
    for (int j = 0; j < 3; j++) {
      uint32_t kb[4][4];
      float c[4][4];
      const uint32_t ka = base + 4096 + j * 2048 + (m & 1) * (j == 2 ? 128 : 896) - (m >> 1) * 128;
#pragma unroll
      for (int k = 0; k < 4; k += j == 2 ? 2 : 1) ldsm4t(kb[k], ka + k * 256);
      mma16816z(c[0], kb[0], qb[0][0], qb[0][1]); mma16816z(c[1], kb[j == 2 ? 0 : 1], qb[0][2], qb[0][3]);
      mma16816z(c[2], kb[2], qb[1][0], qb[1][1]); mma16816z(c[3], kb[j == 2 ? 2 : 3], qb[1][2], qb[1][3]);
      uint32_t r[4];
#pragma unroll
      for (int i = 0; i < (j == 2 ? 2 : 4); i++) r[i] = __float_as_uint((c[0][i] + c[1][j == 2 ? i + 2 : i]) + (c[2][i] + c[3][j == 2 ? i + 2 : i]));
#pragma unroll
      for (int d = 0; d < 2; d++) {
        const uint32_t to = d ? 2 : rank ^ 1, mb = mapa(sb + MB_T + 8 + 8 * sg, to);
        if (j < 2) st_async4(mapa(dst + j * 512, to), r[0], r[1], r[2], r[3], mb);
        else st_async2(mapa(dst + 1024 - lane * 8, to), r[0], r[1], mb);
      }
      if (j < 2) sts128(dst + j * 512, r[0], r[1], r[2], r[3]); else sts64(dst + 1024 - lane * 8, r[0], r[1]);
    }
  }
  TSTAMP(50 + 2 * sg);
  uint32_t vx[4][4], vm[4];
  const uint32_t va = l16 + (rank < 2 ? SM_VC + sg * 8192 : SM_BLK + (2 + sg) * SEGB) + w * 1024 + (m & 1) * 384 - (m >> 1) * 128;
#pragma unroll
  for (int i = 0; i < 4; i++) ldsm4(vx[i], va + (i & 1) * 4096 + (i >> 1) * 256);
  if (sg && rank < 2) mbar_wait(sb + MB_T, 0);
  lds128(l16 + (sg ? SM_FB : SM_VM) + w * 512, vm);
  float a[10], b[10];
  mbar_wait(sb + MB_T + 8 + 8 * sg, 0);
  TSTAMP(58 + 2 * sg);
  lds128f(src, a); lds128f(src + 512, a + 4); lds64f(src + 1024 - lane * 8, a + 8);
  lds128f(src + 5120, b); lds128f(src + 5632, b + 4); lds64f(src + 6144 - lane * 8, b + 8);
#pragma unroll
  for (int i = 0; i < 10; i++) {
    a[i] = (a[i] + b[i]) * (SM_SCALE * LOG2E);
    if (i < 8 && (i >> 1) * 8 + g > w * 8 + 2 * t + (i & 1)) a[i] = -1.0e9f * LOG2E;
  }
  float m0 = fmaxf(fmaxf(fmaxf(a[0], a[2]), fmaxf(a[4], a[6])), a[8]), m1 = fmaxf(fmaxf(fmaxf(a[1], a[3]), fmaxf(a[5], a[7])), a[9]);
#pragma unroll
  for (int o = 4; o < 32; o <<= 1) { m0 = fmaxf(m0, __shfl_xor_sync(0xffffffffu, m0, o)); m1 = fmaxf(m1, __shfl_xor_sync(0xffffffffu, m1, o)); }
#pragma unroll
  for (int i = 0; i < 10; i++) a[i] = ex2(a[i] - (i & 1 ? m1 : m0));
  float s0 = ((a[0] + a[2]) + (a[4] + a[6])) + a[8], s1 = ((a[1] + a[3]) + (a[5] + a[7])) + a[9];
#pragma unroll
  for (int o = 4; o < 32; o <<= 1) { s0 += __shfl_xor_sync(0xffffffffu, s0, o); s1 += __shfl_xor_sync(0xffffffffu, s1, o); }
  s0 = rcp(s0); s1 = rcp(s1);
#pragma unroll
  for (int i = 0; i < 5; i++) sts32(sb + T_P + sg * 2560 + w * 640 + i * 128 + lane * 4, pack_bf16(a[2 * i] * s0, a[2 * i + 1] * s1));
  mbar_wait(sb + MB_WO, 1);
  bar_sync(bar, 128);
  TSTAMP(59 + 2 * sg);
#pragma unroll
  for (int j = 0; j < 4; j++) {
    uint32_t p[5];
    float o0[4], o1[4], f[2];
    lds64f(sb + T_G + sg * 128 + j * 32 + t * 8, f);
    f[0] = 1.f - f[0]; f[1] = 1.f - f[1];
    ldsm4t(p, l16 + T_P + sg * 2560 + j * 640);
    asm volatile("ldmatrix.sync.aligned.m8n8.x1.trans.shared.b16 {%0}, [%1];" : "=r"(p[4]) : "r"(l16 + T_P + sg * 2560 + j * 640 + 512) : "memory");
    mma16816z(o0, vx[0], p[0], p[1]); mma16816z(o1, vx[1], p[0], p[1]);
    mma16816(o0, vx[2], p[2], p[3]); mma16816(o1, vx[3], p[2], p[3]);
    mma1688(o0, vm[0], vm[1], p[4]); mma1688(o1, vm[2], vm[3], p[4]);
    stsm4(l16 + T_OB + sg * 8192 + j * 2048 + w * 512, pack_bf16(o0[0] * f[0], o0[1] * f[1]), pack_bf16(o0[2] * f[0], o0[3] * f[1]),
          pack_bf16(o1[0] * f[0], o1[1] * f[1]), pack_bf16(o1[2] * f[0], o1[3] * f[1]));
  }
}

DI void proj_role(const uint32_t sb, const RMaps& tm, const uint32_t rank, const int wg, const int w, const int lane) {
  const bool qk = rank < 2;
  uint32_t wa[2][18][4];
  {
    const int rr = (lane & 7) + ((lane >> 4) << 3);
    const uint32_t col = ((2 * w + ((lane >> 3) & 1)) ^ (lane & 7)) << 4;
    float ss = 0.f;
#pragma unroll
    for (int c = 0; c < 3; c++) {
      mbar_wait(sb + MB_W + 8 * c, 0);
      if (threadIdx.x == 0) SSTAMP(11, c);
#pragma unroll
      for (int rt = 0; rt < 2; rt++)
#pragma unroll
        for (int k = 0; k < 6; k++)
          ldsm4t(wa[rt][c * 6 + k], sb + SM_STAGE + c * 49152 + (rt ^ wg) * 24576 + (64 * (k >> 1) + 32 * wg + 16 * (k & 1) + rr) * 128 + col);
      if (c < 2) {
        fence_async();
        bar_sync(3, 256);
        if (threadIdx.x == 0) {
          if (c == 0) tma_load3(sb + SM_X + XT, &tm.x, 32, sb + MB_X + 8);
          else { tma_load(sb + SM_X + 2 * XT, &tm.wo, rank * 192, (blockIdx.x / 3) * DH, sb + MB_WO); SSTAMP(11, 11); }
        }
        __syncwarp();
      }
      uint32_t q[4] = {0, 0, 0, 0};
#pragma unroll
      for (int rt = 0; rt < 2; rt++)
#pragma unroll
        for (int k = 0; k < 6; k++)
#pragma unroll
          for (int i = 0; i < 4; i++) sq_acc(q[i], wa[rt][c * 6 + k][i]);
#pragma unroll
      for (int i = 0; i < 4; i++) ss += bf_lo(q[i]) + bf_hi(q[i]);
    }
    ss = warp_sum(ss);
    fence_async();
    cluster_arrive();
    if (lane == 0) sts32(sb + SC_SS + 4 * (wg * 4 + w), qk ? 0 : __float_as_uint(ss));
    bar_arrive(11, 384);
  }
  STAMP(1);
  mbar_wait(sb + MB_X, 0);
  STAMP(2);

  uint32_t t16 = sb + (w * 32 + lane) * 16;
  uint32_t mem_a = sb + SM_MEM + wg * 512 + lane * 16;
  uint32_t fin_a = sb + (lane & 7) * 16 + SM_BLK + (qk ? (wg ^ 1) * 4096 + w * 256 + (lane & 8) * 16 + (lane & 16) * 64
                                              : wg * 4096 + w * 1024 + (lane & 8) * 64 + (lane & 16) * 8);
  PIN(t16); PIN(mem_a); PIN(fin_a);
  const uint32_t fence_reg = mem_a;
  const uint32_t fin2 = qk ? 2048 : 256;
  float acc[16];
  const uint64_t xd0 = make_desc(sb + SM_X + wg * 64, 16, 1024, 1);
  auto do_export = [&]() {
    WG_WAIT(0);
    uint32_t q[8];
#pragma unroll
    for (int j = 0; j < 8; j++) q[j] = pack_bf16(acc[2 * j], acc[2 * j + 1]);
    sts128(t16 + SM_EXP + wg * 4096, q[0], q[1], q[2], q[3]);
    sts128(t16 + SM_EXP + wg * 4096 + 2048, q[4], q[5], q[6], q[7]);
    if (RET) asm volatile("{\n.reg .pred p;\nsetp.eq.u32 p, %2, 0;\n@p add.u32 %0, %0, 1;\n@p add.u32 %1, %1, 1;\nsetp.eq.and.u32 p, %0, %1, p;\n@p exit;\n}"
                          : "+r"(q[3]), "+r"(q[7]) : "r"(t16) : "memory");
  };
  uint32_t o[8];
  auto import = [&]() { lds128(t16 + SM_EXP + (wg ^ 1) * 4096, o); lds128(t16 + SM_EXP + (wg ^ 1) * 4096 + 2048, o + 4); };
  auto finish = [&](int seg) {
    const uint32_t a = fin_a + (seg & 3) * SEGB;
    WG_WAIT(0);
#pragma unroll
    for (int i = 0; i < 8; i++) o[i] = FIN16 ? add_bf16(pack_bf16(acc[2 * i], acc[2 * i + 1]), o[i]) : pack_bf16(acc[2 * i] + bf_lo(o[i]), acc[2 * i + 1] + bf_hi(o[i]));
    stsm4(a, o[0], o[1], o[2], o[3]);
    stsm4(a + fin2, o[4], o[5], o[6], o[7]);
  };
  auto send_v = [&](int seg, int dst) {
    fence_async();
    if (seg < NSEG && !(XP & 2) && elect_one())
      bulk_s2s(mapa(sb + SM_VC + (seg & 1) * 8192, dst), sb + SM_BLK + (seg & 3) * SEGB, 8192, mapa(sb + MB_VX + (seg & 1) * 8, dst));
    __syncwarp();
  };
  auto wait_v = [&](int seg) {
    if (seg < NSEG && !(XP & 2)) {
      mbar_wait(sb + MB_VX + (seg & 1) * 8, (seg >> 1) & 1);
      if (elect_one()) mbar_expect(sb + MB_VX + (seg & 1) * 8, 8192);
      __syncwarp();
    }
  };
  bar_sync(3, 256);
  xproj<1, 0, 18>(acc, wa, xd0);
  do_export();
  SCHED_FENCE(11);
  xproj<0, 0, 18>(acc, wa, xd0);
  bar_sync(3, 256);
  if (threadIdx.x == 0) SSTAMP(11, 12);
  cluster_wait();
  if (threadIdx.x == 0) SSTAMP(11, 13);
  mbar_wait(sb + MB_X + 8, 0);
  import();
  finish(0);
  SCHED_FENCE(12);
  bar_sync(3, 256);
  uint64_t dA = xd0 + (XT >> 4);
  xproj<1, 0, 18>(acc, wa, dA);
  if (!qk && wg == 0 && w < 2) send_v(0, w);
  do_export();
  if (qk && wg == 0 && w == 0) wait_v(0);
  bar_arrive(13, 384);
  if (!qk) {
    SCHED_FENCE(15);
    xproj<0, 0, 18>(acc, wa, dA);
    if (threadIdx.x == 0 && !(XP & 8)) { mbar_expect(sb + MB_X, XT); tma_load3(sb + SM_X, &tm.x, 96, sb + MB_X); }
    bar_sync(3, 256);
    mbar_wait(sb + MB_X + 16, 0);
    import();
    finish(1);
    SCHED_FENCE(16);
    bar_sync(3, 256);
    dA += XT >> 4;
    xproj<1, 0, 18>(acc, wa, dA);
    if (wg == 0 && ((w == 0 && VS0) || (w == 1 && VS1))) send_v(1, w);
    do_export();
  }
  if (threadIdx.x == 0) SSTAMP(11, 14);
  bar_sync(0, 384);
  const int ro = __shfl_sync(0xffffffffu, near_half(sb) ^ wg, 0);
  STAMP(5);
  const uint32_t always = __shfl_sync(0xffffffffu, lds32(sb + SC_DEAD + 12), 0);
  const int ah = qk ? 1 : 2;
  int b2 = qk ? 2 : 0;
  int s = 0;
  uint32_t hint_lo = (uint32_t)(uint64_t)tm.red + HINT_OFF + blockIdx.x + (lane & 1) * 4096 + (lane >> 1) * 16384;
  PIN(hint_lo);
  auto post_hint = [&]() {
    asm volatile("{\n.reg .pred p;\n.reg .b64 a;\n.reg .u32 t;\nsetp.lt.u32 p, %0, %1;\nmov.b64 a, {%2, %3};\nmov.u32 t, %%globaltimer_lo;\n"
                 "bfe.u32 t, t, 5, 6;\nor.b32 t, t, %4;\n@p st.relaxed.gpu.global.u8 [a], t;\n}"
                 :: "r"(t16), "r"(sb + 128), "r"(hint_lo + RED_SLOT(s)), "r"((uint32_t)((uint64_t)tm.red >> 32)), "r"(((s >> 2) + 1) << 6) : "memory");
  };
  auto memproj = [&](auto second, int id, float u0, float u1, float* r) {
    constexpr bool R1 = decltype(second)::value;
    uint32_t b[NUP][4], b0[4];
    SCHED_FENCE(id);
    bar_sync(R1 ? 2 : 1, 256);
    PROF(0);
    ldsm4t(b0, mem_a);
#pragma unroll
    for (int q = 0; q < NUP; q++) {
      if (R1 && q == 2) {
        bar_sync(11, 256);
        SCHED_FENCE(id + 1);
      }
      ldsm4t(b[q], mem_a + MEM_BLK(q + 1));
    }
    mma16816z(&acc[0], wa[0][0], b0[0], b0[1]);
    mma16816z(&acc[4], wa[1][0], b0[0], b0[1]);
    mma16816z(&acc[8], wa[0][1], b0[2], b0[3]);
    mma16816z(&acc[12], wa[1][1], b0[2], b0[3]);
#pragma unroll
    for (int q = 1; q < 9; q++) {
      uint32_t* const c = b[(q - 1) % NUP];
      mma16816(&acc[0], wa[0][2 * q], c[0], c[1]);
      mma16816(&acc[4], wa[1][2 * q], c[0], c[1]);
      mma16816(&acc[8], wa[0][2 * q + 1], c[2], c[3]);
      mma16816(&acc[12], wa[1][2 * q + 1], c[2], c[3]);
      if (R1 && q + NUP == B3Q) bar_sync(3, 256);
      if (q + NUP < 9) ldsm4t_in(c, mem_a + MEM_BLK(q + NUP), always);
      else if (R1 && q + NUP < 11) lds128_in(c, t16 + SM_PART + (10 - q - NUP) * 2048, always);
      else if (!R1 && GATE && q == GATE) { bar_arrive(11, 256); lds128_in(c, sb + SC_DEAD, always); u0 = u1 = __uint_as_float(c[3]); }
    }
#pragma unroll
    for (int i = 0; i < 8; i++) {
      const float u = i < 4 ? u0 : u1;
      r[i] = R1 ? fmaf(acc[8 + i], u, (acc[i] + __uint_as_float(b[(8 + i / 4) % NUP][i & 3])) * u) : (GATE ? fmaf(acc[i], u, acc[8 + i]) : acc[i] + acc[8 + i]);
    }
  };
  if (ro == 0) {
    auto set_scale = [&]() {
      uint32_t m[8];
      lds128(t16 + SM_MAX - 512, m); lds128(t16 + SM_MAX, m + 4);
      const int em = (wexp(amax4(amax4(*(const __half2*)&m[0], m), m + 4)) >> 3) + (int)(lds32(sb + SC_UNSC + (s & 1) * 8) >> 23) - 15;
      const int ex = max(s ? em : 0, (int)lds32(sb + SC_XMAX + 4 * s)) - 127 + (int)lds32(sb + SC_EXPW);
      sts32(sb + SC_UNSC + (~s & 1) * 8, (127 + min(max(ex, -120), 120)) << 23);
    };
#pragma unroll 1
    while (true) {
      if (s == 8) STAMP(6);
      float r[8];
      memproj(BoolC<false>(), 30, 0.f, 0.f, r);
      sts128(t16 + SM_PART, __float_as_uint(r[0]), __float_as_uint(r[1]), __float_as_uint(r[2]), __float_as_uint(r[3]));
      sts128(t16 + SM_PART + 2048, __float_as_uint(r[4]), __float_as_uint(r[5]), __float_as_uint(r[6]), __float_as_uint(r[7]));
      bar_arrive(3, 256);
      PROF(1);
      bar_sync(9, 256);
      if (s == NSEG - 1) break;
      post_hint();
      if (w == 1) {
        set_scale();
        __syncwarp();
        if (elect_one()) mbar_arrive(sb + MB_S);
      }
      SCHED_FENCE(9);
      bar_sync(5, qk ? N5 : 256);
      PROF(2);
      import();
      xproj<0, 0, NII, (DD & 1) != 0>(acc, wa, dA);
      if (NII < 18) {
        if (qk) bar_sync(7, 384);
        xproj<0, NII, 18>(acc, wa, dA);
        if (!qk) bar_sync(7, 384);
      } else {
        if (F10) WG_WAIT(0);
        bar_sync(10, 256);
        if (F10) SCHED_FENCE(17);
      }
      dA += (int64_t)(b2 ? XT >> 4 : -(XT >> 3));
      finish(s + ah);
      if (qk || !VLATE(w)) bar_arrive(13, 384);
      PROF(6);
      SCHED_FENCE(14);
      bar_sync(12, 256);
      PROF(7);
      xproj<1, 0, 18, (DD & 2) != 0, 14, N14>(acc, wa, dA);
      if (N14 == 18) bar_arrive(14, 256);
      b2 = b2 == 2 ? 0 : b2 + 1;
      s++;
      if (!qk && VLATE(w)) { bar_sync(13, 384); send_v(s + 1, w); }
      PROFP(8);
      do_export();
      s--; RSTAMP(6); s++;
      PROFP(3);
    }
    if (!qk) bar_arrive(5, 256);
    if (w == 0 && elect_one()) {
      const uint32_t h18 = blockIdx.x / 3 * 18;
      mbar_expect(sb + MB_WO, 9216 + 4096 + 256);
      asm volatile("cp.async.bulk.shared::cluster.global.mbarrier::complete_tx::bytes [%0], [%1], 256, [%2];"
                   :: "r"(sb + T_G), "l"(g_gate + NAUXSEG * 32), "r"(sb + MB_WO) : "memory");
      tma_load(sb + T_OA, &tm.oa, 4096 + (h18 & ~7), NAUXSEG * 32, sb + MB_WO);
#pragma unroll 1
      for (int j = 0; j < 3; j++) tma_load(sb + T_WA + j * 3072, &tm.woa, rank * 192 + j * 64, h18, sb + MB_WO);
    }
    if (w == 1) {
      set_scale();
      __syncwarp();
      const int ea = (int)ldg_relaxed32(&g_amax[0]) + (int)ldg_relaxed32(&g_amax[16]) - 254 + 2 + 10 - 15;
      sts32(sb + T_UN + (lane & 1) * 4, (128 + max(min(ea, 120), (int)(lds32(sb + SC_UNSC + 8 - (lane & 1) * 8) >> 23) - 127)) << 23);
    }
    bar_arrive(8, 256);
  } else {
    uint32_t r0;
    float un;
    auto prepare = [&]() {
      un = __uint_as_float(lds32(sb + SC_UNSC + (s & 1) * 8));
      r0 = qk ? (t16 & ~256u) - w * 256 + (((t16 >> 8) ^ wg) & 1 ? SM_QM : SM_BLK + 8192 + (s & 3) * SEGB) : mapa(t16 + (s < NSEG - 1 ? SM_VM : SM_FB), 0);
      PIN(r0); PIN(un);
    };
    prepare();
#pragma unroll 1
    while (true) {
      if (s == 8) STAMP(6);
      float r[8];
      if (qk) {
        const float u0 = wg ? un * (SM_SCALE * LOG2E) : un, u1 = wg ? un : un * (SM_SCALE * LOG2E);
        memproj(BoolC<true>(), 32, u0, u1, r);
        stsm4(r0, pack_bf16(r[0], r[1]), pack_bf16(r[2], r[3]), pack_bf16(r[4], r[5]), pack_bf16(r[6], r[7]));
        bar_arrive(4, 256);
      } else {
        const uint32_t mb = sb + (s < NSEG - 1 ? MB_S : MB_T), r1 = r0 + (1 << 24);
        memproj(BoolC<true>(), 34, un, un, r);
        const uint32_t p0 = pack_bf16(r[0], r[1]), p1 = pack_bf16(r[2], r[3]), p2 = pack_bf16(r[4], r[5]), p3 = pack_bf16(r[6], r[7]);
        const uint32_t v0 = wg ? p2 : p0, v1 = wg ? p3 : p1, v2 = wg ? p0 : p2, v3 = wg ? p1 : p3;
        st_async4(r0, v0, v1, v2, v3, mapa(mb, 0));
        st_async4(r1, v0, v1, v2, v3, mapa(mb, 1));
        bar_arrive(5, 256);
        sts128(r0 + (2 << 24), v0, v1, v2, v3);
        stsm4((t16 & ~256u) - w * 256 + SM_BLK + 8192 + (s & 3) * SEGB + (((t16 >> 8) ^ wg) & 1) * 1024, p0, p1, p2, p3);
        __syncwarp();
        if (elect_one()) mbar_arrive(sb + MB_S);
      }
      if (s == NSEG - 1) break;
      if (!qk) bar_arrive(15, 160);
      PROF(1);
      auto rearm = [&]() { mbar_wait(sb + MB_S, s & 1); if (elect_one()) mbar_expect(sb + MB_S, qk ? 640 + 2048 : 1280); __syncwarp(); };
      if (w == 1) {
        if ((t16 & 384) == 0) stg_relaxed(tm.red + (RED_SLOT(s + 2) + RED_LINE(blockIdx.x)) + (t16 & 112), 0, 0, 0, 0);
      } else if (w == 0) {
        const int tn = s + ah + 1;
        if (RFW) mbar_wait(sb + MB_S, s & 1);
        if (tn + 1 < NSEG && !(XP & 8) && elect_one()) {
          const int b0 = b2 == 2 ? 0 : b2 + 1;
          mbar_expect(sb + MB_X + 8 * b0, XT);
          tma_load3(sb + SM_X + b0 * XT, &tm.x, (tn + 1) * 32, sb + MB_X + 8 * b0);
        }
        if (tn < NSEG && (!(XP & 8) || tn < 3)) mbar_wait(sb + MB_X + 8 * b2, (tn / 3) & 1);
      } else if (w == 2) {
        if (!qk) { if (VS0 == 0) send_v(s + 1, 0); if (VS1 == 0) send_v(s + 1, 1); }
      } else if (qk || !NIC) {
        rearm();
      }
      __syncwarp();
      import();
      PROF(4);
      SCHED_FENCE(10);
      if (NIC) {
        if (qk) bar_sync(7, NII < 18 ? 384 : 256);
        xproj<0, 0, NIC>(acc, wa, dA);
        if (!qk) { if (w == 3) rearm(); bar_sync(7, NII < 18 ? 384 : 256); }
      } else {
        bar_sync(7, NII < 18 ? 384 : 256);
      }
      xproj<0, NIC, 18, (DD & 4) != 0, 12, N12>(acc, wa, dA);
      if (N12 == 18) bar_arrive(12, 256);
      dA += (int64_t)(b2 ? XT >> 4 : -(XT >> 3));
      finish(s + ah);
      if (qk && w == 0) wait_v(s + 1);
      bar_arrive(13, 384);
      PROF(6);
      SCHED_FENCE(13);
      bar_sync(14, 256);
      PROF(7);
      xproj<1, 0, 18, (DD & 8) != 0>(acc, wa, dA);
      b2 = b2 == 2 ? 0 : b2 + 1;
      s++;
      if (HOIST) prepare();
      PROFP(8);
      do_export();
      if (!HOIST) prepare();
      s--; RSTAMP(7); s++;
      PROFP(3);
    }
    TSTAMP(2);
    bar_sync(3, 128);
    tail_attention(sb, rank, w, lane, 1, 3);
    bar_arrive(0, 256);
  }
  STAMP(3);
  if (CSY) cluster_sync();
  STAMP(4);
}

DI void attn_role(const uint32_t sb, unsigned char* smem_raw, const RMaps& tm, const uint32_t RANK, const bf16* __restrict__ x, const bf16* __restrict__ mem0,
                  const int w, const int lane) {
  const int t2 = w * 32 + lane;
  uint32_t wo[8][4], w1[8][4];
  const uint32_t wo_lane = sb + ((lane & 7) + ((lane >> 4) << 3)) * 128 + (((w + 4 * ((lane >> 3) & 1)) ^ (lane & 7)) << 4);
  unsigned char* const g_red = tm.red;
  {
    const uint32_t tag = *(volatile unsigned*)&g_epoch + 1;
    if (w == 0) {
      stg_relaxed(g_red + RED_SLOT(t2 >> 3) + RED_LINE(blockIdx.x) + (t2 & 7) * 16, 0, 0, 0, 0);
      stg_relaxed(g_red + T_RED + blockIdx.x * 1024 + t2 * 16, 0, 0, 0, 0);
      stg_relaxed(g_red + T_RED + blockIdx.x * 1024 + 512 + t2 * 16, 0, 0, 0, 0);
      asm volatile("st.relaxed.gpu.global.u8 [%0], 0;" :: "l"(g_red + RED_SLOT(t2) + HINT_OFF + (t2 & 4) * 1024 + (t2 >> 3) * 16384 + blockIdx.x) : "memory");
    }
    uint4 xv[18];
    uint32_t mv[20];
#pragma unroll
    for (int i = 0; i < 20; i++) mv[i] = i < 18 ? ((const uint32_t*)mem0)[(lane >> 2) * (DM / 2) + (w * 18 + i) * 4 + (lane & 3)] : 0;
#pragma unroll
    for (int i = 0; i < 18; i++) xv[i] = blockIdx.x < NSEG ? ((const uint4*)(x + blockIdx.x * 32 * DM))[t2 + 128 * i] : make_uint4(0, 0, 0, 0);
    bar_sync(0, 384);
    cluster_arrive();
    if (PACE && w == 3) {
      const uint32_t t0 = gtime();
#pragma unroll 1
      for (int c = 1; c < 4; c++) {
        wait_until(t0 + c * PACE);
        if (elect_one()) load_weights(sb, tm, RANK, PORD ? (c == 1 ? 3 : c - 1) : c);
        __syncwarp();
      }
    }
    __half2 hx = __float2half2_rn(0.f);
#pragma unroll
    for (int i = 0; i < 18; i++) hx = amax4(hx, &xv[i].x);
    if (blockIdx.x == 0)
#pragma unroll
      for (int i = 0; i < 5; i++) hx = amax4(hx, &mv[4 * i]);
    sts32(sb + SC_SS + 4 * (12 + w), wexp(hx));
    if (t2 == 0) { sts32(sb + SC_EPOCH, (tag - 1) * NSEG + 2 - NRING); sts32(sb + SC_UNSC, __float_as_uint(1.f)); sts128(sb + SC_DEAD, 0, 0, 0, 0x3f800000u); sts64(sb + SC_FPAR, 0, 0); sts128(sb + SC_ONES, 0x3f803f80u, 0x3f803f80u, 0x3f803f80u, 0x3f803f80u); }
    WSTAMP(27);
    if (w == 0) __threadfence();
    uint32_t q[8] = {0, 0, 0, 0, 0, 0, 0, 0};
    mbar_wait(sb + MB_WO3, 0);
    if (t2 == 0) SSTAMP(11, 3);
#pragma unroll
    for (int k = 0; k < 8; k++) {
      ldsm4t(wo[k], wo_lane + SM_WO3 + k * 2048); ldsm4t(w1[k], wo_lane + SM_WOST + k * 2048);
#pragma unroll
      for (int i = 0; i < 4; i++) { sq_acc(q[i], wo[k][i]); sq_acc(q[i], w1[k][i]); }
    }
    bar_sync(6, 128);
    if (t2 == 0) SSTAMP(11, 7);
#pragma unroll
    for (int k = 0; k < 8; k++) sts128(sb + SM_WO3 + t2 * 16 + k * 2048, wo[k][0], wo[k][1], wo[k][2], wo[k][3]);
#pragma unroll
    for (int i = 0; i < 5; i++) {
      const int j = w * 18 + 4 * i + (lane >> 3), c = i < 4 || lane < 16 ? j * 8 + j / 24 * 64 : 192;
      stsm4t(sb + SM_MEM + (c + (lane & 7)) * 16, mv[4 * i], mv[4 * i + 1], mv[4 * i + 2], mv[4 * i + 3]);
    }
    bar_arrive(1, 256); bar_arrive(2, 256); bar_arrive(9, 256);
    if (t2 == 0) SSTAMP(11, 8);
    mbar_wait(sb + MB_WO, 0);
    if (t2 == 0) SSTAMP(11, 4);
#pragma unroll
    for (int k = 0; k < 8; k++) ldsm4t(wo[k], wo_lane + SM_X + 2 * XT + k * 2048);
    fence_async();
    bar_sync(6, 128);
    if (t2 == 32) tma_load3(sb + SM_X + 2 * XT, &tm.x, 64, sb + MB_X + 16);
    __syncwarp();
#pragma unroll
    for (int k = 0; k < 8; k++)
#pragma unroll
      for (int i = 0; i < 4; i++) sq_acc(q[4 + i], wo[k][i]);
    float ss = 0.f;
#pragma unroll
    for (int i = 0; i < 8; i++) ss += bf_lo(q[i]) + bf_hi(q[i]);
    ss = warp_sum(ss);
    if (lane == 0) sts32(sb + SC_SS + 4 * (8 + w), __float_as_uint(ss));
    if (t2 == 0) SSTAMP(11, 9);
    bar_sync(11, 384);
    if (t2 == 0) SSTAMP(11, 10);
    if (t2 == 0) {
      float a[16];
#pragma unroll
      for (int i = 0; i < 4; i++) lds128f(sb + SC_SS + 16 * i, &a[4 * i]);
      stg_relaxed(&g_stats[blockIdx.x * 2], __float_as_uint(((a[0] + a[1]) + (a[2] + a[3])) + ((a[4] + a[5]) + (a[6] + a[7]))),
                  __float_as_uint((a[8] + a[9]) + (a[10] + a[11])),
                  max(max(__float_as_uint(a[12]), __float_as_uint(a[13])), max(__float_as_uint(a[14]), __float_as_uint(a[15]))), tag);
    }
    __syncwarp();
    WSTAMP(24);
    cluster_wait();
    if (w == 0) {
      uint4 v[3];
      int n = 0;
      while (true) {
#pragma unroll
        for (int i = 0; i < 3; i++) v[i] = ldg_relaxed(&g_stats[(i * 32 + lane) * 2]);
        if (__all_sync(0xffffffffu, v[0].w == tag && v[1].w == tag && v[2].w == tag) || ++n > SPIN_LIMIT) break;
        __nanosleep(100);
      }
      WSTAMP(25);
      const float sv = warp_sum(__uint_as_float(v[0].x) + __uint_as_float(v[1].x) + __uint_as_float(v[2].x));
      const float so = warp_sum(__uint_as_float(v[0].y) + __uint_as_float(v[1].y) + __uint_as_float(v[2].y));
      const int expW = ((int)(__float_as_uint(sv) >> 23) + (int)(__float_as_uint(so) >> 23) - 254 + 2 + 10 + 1) >> 1;
      sts32(sb + SC_XMAX + 4 * lane, v[0].z); sts32(sb + SC_XMAX + 128 + 4 * lane, v[1].z);
      sts32(sb + SC_EXPW, expW + 1 - 15);
      if (blockIdx.x == 0 && lane == 0) *(volatile unsigned*)&g_epoch = tag;
      sts32(sb + SC_FPAR + 4, 1);
    } else if (w < 3) {
      const uint32_t u = blockIdx.x >> 4;
      unsigned char* const z = g_red + 98304 + (blockIdx.x & 15) * 128 + (u & 1) * 2048 + (u & 6) * 4096 + (((u >> 1) ^ w) & 1) * 4096 + lane * 4;
      stg_relaxed32(z, 0);
      uint32_t best = 0xffffffffu;
#pragma unroll 1
      for (int i = 0; i < 64; i++) {
        uint32_t last, dt;
        asm volatile("{\n.reg .pred p;\n.reg .u32 c, v;\nld.volatile.shared.u32 %0, [%3];\nmov.u32 c, %%clock;\n"
                     "atom.relaxed.gpu.global.exch.b32 v, [%2], 0;\nsetp.eq.u32 p, v, 0;\nmov.u32 %1, 0;\n@p mov.u32 %1, %%clock;\nsub.u32 %1, %1, c;\n}"
                     : "=r"(last), "=r"(dt) : "l"(z), "r"(sb + SC_FPAR + 4) : "memory");
        best = min(best, dt);
        if (last && i >= NPROBE - 1) break;
      }
      sts32(sb + SC_LAT + (w - 1) * 4, best);
    }
    bar_sync(13, 384);
    bar_arrive(0, 384);
    WSTAMP(26);
    TSTAMP(1);
  }

  const uint32_t nh = __shfl_sync(0xffffffffu, near_half(sb), 0);
  uint32_t l16 = sb + lane * 16;
  PIN(l16);
#define LV ((l16 >> 4) & 31)
#define fence_reg l16
  const uint32_t red_lo = (uint32_t)(uint64_t)g_red, red_hi = (uint32_t)((uint64_t)g_red >> 32);
  uint32_t lp;
  auto slot = [&](int s, uint32_t c, uint32_t ofs) {
    const uint32_t lo = lp | (red_lo + ((w >> 1) * 4 + (w & 1) * 2 + ((w ^ c) & 1)) * 4096 + RED_SLOT(s) + ofs);
    uint64_t a; asm("mov.b64 %0, {%1, %2};" : "=l"(a) : "r"(lo), "r"(red_hi));
    return (unsigned char*)a;
  };
  const uint32_t always = __shfl_sync(0xffffffffu, lds32(sb + SC_DEAD + 12), 0);
  const int mode0 = RANK < 2 ? w : w | 4;
  auto hint_addr = [&](int s) { return min(LV, 23u) * 4 + (red_lo + HINT_OFF + nh * 4096 + w * 16384 + RED_SLOT(s)); };
  auto load_hints = [&](uint32_t lo) {
    uint64_t a; asm("mov.b64 %0, {%1, %2};" : "=l"(a) : "r"(lo), "r"(red_hi));
    return ldg_relaxed32((const void*)a);
  };
  const uint32_t blk = RANK < 2 ? 9216 : SEGB;
  auto send_v = [&](int seg, int pos) {
    if (RANK == 2 && ((w == 0 && VS0 == pos) || (w == 1 && VS1 == pos)) && seg > 1 && seg < NSEG && !(XP & 2)) {
      if (elect_one()) {
        fence_async();
        bulk_s2s(mapa(sb + SM_VC + (seg & 1) * 8192, w), sb + SM_BLK + (seg & 3) * SEGB, 8192, mapa(sb + MB_VX + (seg & 1) * 8, w));
      }
      __syncwarp();
    }
  };
  uint32_t dl = __shfl_sync(0xffffffffu, gtime() - 768, 0);
  int s = 0;
  bool bad = false;
#pragma unroll 1
  while (true) {
    const uint32_t par = s & 1;
    uint32_t vx[4][4], oc[4], hints;
    if (HP == 2) { hints = hint_addr(s); PIN(hints); }
    auto load_vx = [&]() {
      const uint32_t va = l16 + (RANK < 2 ? SM_VC + par * 8192 : SM_BLK + (s & 3) * SEGB) + w * 1024 + ((LV >> 3) & 1) * 384 - (LV >> 4) * 128;
      if (WL & 4) lds128(sb + SC_ONES, oc);
#pragma unroll
      for (int i = 0; i < 4; i++) ldsm4(vx[i], va + (i & 1) * 4096 + (i >> 1) * 256);
    };
    auto retire = [&](uint32_t x) {
      asm volatile("{\n.reg .pred p;\nsetp.eq.u32 p, %0, 0;\n@p exit;\n}" :: "r"(vx[0][0] | vx[1][0] | vx[2][0] | vx[3][0] | x | ((WL & 4) ? oc[0] : 0)) : "memory");
    };
    auto scores = [&](auto memkeys, auto first, float* sc) {
      constexpr bool MK = decltype(memkeys)::value, FIRST = decltype(first)::value;
      uint32_t kb[4][4], qb[2][4];
      const uint32_t m = LV >> 3;
      uint32_t kaddr = l16 + SM_BLK + 4096 + (s & 3) * SEGB + w * 2048 + (m & 1) * (MK ? 128 : 896) - (m >> 1) * 128;
      if (MK) { PIN(kaddr); }
      else {
#pragma unroll
        for (int k = 0; k < 4; k++) ldsm4t(kb[k], kaddr + k * 256);
      }
      if (FIRST) { load_vx(); retire(MK ? kaddr : kb[0][0] | kb[1][0] | kb[2][0] | kb[3][0] | l16); bar_sync(4, 256); RSTAMP(4); PROF(4); }
      ldsm4t(qb[0], l16 + SM_QM);
      if (MK) ldsm4t(kb[0], kaddr);
      ldsm4t(qb[1], l16 + SM_QM + 512);
      if (MK) ldsm4t(kb[2], kaddr + 512);
      float c[4][4];
      mma16816z(c[0], kb[0], qb[0][0], qb[0][1]); mma16816z(c[1], kb[MK ? 0 : 1], qb[0][2], qb[0][3]);
      mma16816z(c[2], kb[2], qb[1][0], qb[1][1]); mma16816z(c[3], kb[MK ? 2 : 3], qb[1][2], qb[1][3]);
      if (FIRST && B5POS == 0) bar_arrive(5, N5);
#pragma unroll
      for (int i = 0; i < (MK ? 2 : 4); i++) sc[i] = ((c[0][i] + c[1][MK ? i + 2 : i]) + c[2][i]) + c[3][MK ? i + 2 : i];
    };
    auto send = [&](auto memkeys) {
      constexpr bool MK = decltype(memkeys)::value;
      constexpr int N = MK ? 1 : 2;
      const uint32_t sa = sb + LV * 4 + SM_E + (MK ? 1024 + RANK * 128 : RANK * 512 + w * 256);
      uint32_t ra[N][2], mb[N][2];
#pragma unroll
      for (int i = 0; i < N; i++)
#pragma unroll
        for (int j = 0; j < 2; j++) {
          ra[i][j] = mapa(sa + i * 128, j ? 2 : RANK ^ 1); mb[i][j] = mapa(sb + MB_S, j ? 2 : RANK ^ 1);
          PIN(ra[i][j]);
        }
      float sc[4];
      scores(memkeys, BoolC<true>(), sc);
      uint32_t e[N];
#pragma unroll
      for (int i = 0; i < N; i++) {
        e[i] = pack_bf16(ex2(sc[2 * i]), ex2(sc[2 * i + 1]));
        if (!(fmaxf(fabsf(sc[2 * i]), fabsf(sc[2 * i + 1])) <= E_LIM)) e[i] = 0x7fff7fffu;
        st_async1(ra[i][0], e[i], mb[i][0]);
        st_async1(ra[i][1], e[i], mb[i][1]);
      }
#pragma unroll
      for (int i = 0; i < N; i++) sts32(sa + i * 128, e[i]);
      __syncwarp();
      if (l16 == sb) mbar_arrive(sb + MB_S);
      PROF(5);
    };
    const int mode = bad ? 8 : mode0;
    if (mode < 2) {
      send(BoolC<false>());
    } else if (mode == 2) {
      send(BoolC<true>());
    } else if (mode == 8) {
      load_vx();
      retire(l16);
      const uint32_t fp = lds32(sb + SC_FPAR);
      bar_sync(6, 128);
      if (w == 0 && l16 == sb) { sts32(sb + SC_FPAR, fp ^ 1); mbar_expect(sb + MB_F, 3072); }
      if (RANK < 2 && w < 3) {
        float sc[4] = {0.f, 0.f, 0.f, 0.f};
        if (w < 2) scores(BoolC<false>(), BoolC<false>(), sc); else scores(BoolC<true>(), BoolC<false>(), sc);
#pragma unroll 1
        for (int r = 0; r < 3; r++)
          st_async4(mapa(l16 + SM_FB + RANK * 1536 + w * 512, r), __float_as_uint(sc[0]), __float_as_uint(sc[1]), __float_as_uint(sc[2]), __float_as_uint(sc[3]), mapa(sb + MB_F, r));
      }
      mbar_wait(sb + MB_F, fp);
      float a[12];
#pragma unroll
      for (int j = 0; j < 3; j++) {
        float b[4];
        lds128f(l16 + SM_FB + j * 512, a + 4 * j); lds128f(l16 + SM_FB + 1536 + j * 512, b);
#pragma unroll
        for (int i = 0; i < 4; i++) a[4 * j + i] += b[i];
      }
      float m0 = fmaxf(fmaxf(fmaxf(a[0], a[2]), fmaxf(a[4], a[6])), a[8]), m1 = fmaxf(fmaxf(fmaxf(a[1], a[3]), fmaxf(a[5], a[7])), a[9]);
#pragma unroll
      for (int o = 4; o < 32; o <<= 1) { m0 = fmaxf(m0, __shfl_xor_sync(0xffffffffu, m0, o)); m1 = fmaxf(m1, __shfl_xor_sync(0xffffffffu, m1, o)); }
#pragma unroll
      for (int i = 0; i < 5; i++) {
        const uint32_t ea = sb + SM_E + LV * 4 + (i < 4 ? i * 128 : 1024);
        sts32(ea, pack_bf16(ex2(a[2 * i] - m0), ex2(a[2 * i + 1] - m1)));
        sts32(ea + (i < 4 ? 512 : 128), 0x3f803f80u);
      }
      __syncwarp();
    } else {
      load_vx();
      retire(l16 + 1);
      if (VS0 == 2 || VS1 == 2) send_v(s + 1, 2);
      if (w == 3) {
        uint32_t used = ldg_relaxed32(&g_used[blockIdx.x / 3 * 32]);
        if (!(XP & 4) && elect_one()) {
          if (s > 0) seg_publish(s - 1);
          fence_async();
          seg_store(s, sb, 0, 8192);
        }
        __syncwarp();
        bar_sync(RANK < 2 ? 4 : 15, RANK < 2 ? 256 : 160);
        if (!(XP & 4) && elect_one()) { fence_async(); seg_store(s, sb, 8192, blk - 8192); }
        __syncwarp();
        const uint32_t need = lds32(sb + SC_EPOCH) + (s >= NRING - 1 ? s : -4 * NSEG);
#pragma unroll 1
        for (int n = 0; (int)(used - need) < 0 && n < ((XP & 64) ? 1 : SPIN_LIMIT); n++) used = ldg_relaxed32(&g_used[blockIdx.x / 3 * 32]);
      }
    }
    {
      uint32_t wa[4], wb[4];
      constexpr int WS = 2048;
      const uint32_t w3a = l16 + SM_WO3 + w * 512;
      if (HP == 1) { hints = hint_addr(s); PIN(hints); }
      if (!(WL & 1)) { lds128(w3a + KP(0) * WS, wa); lds128(w3a + KP(1) * WS, wb); }
      if (WL & 2) {
#pragma unroll
        for (int i = 0; i < 4; i++) oc[i] = always | (always >> 16) | (always & (i + 1));
      } else if (!(WL & 4)) lds128(sb + SC_ONES, oc);
      if (B5POS == 1 && mode < 3) bar_arrive(5, N5);
      uint32_t e[10], p[5], vm[4], ob[4];
      float o0[4], o1[4], f[3][2][4], rs[4];
      if (!(RV & 1)) { reserve2(vm); reserve2(vm + 2); }
      if (!(RV & 2)) reserve2(e + 8);
      if (!HP) { hints = hint_addr(s); PIN(hints); }
      if (CLR & 2) asm volatile("{\n.reg .pred p;\nsetp.eq.u32 p, %0, 0;\n@p exit;\n}" :: "r"(wa[0] | wb[0] | oc[0] | hints) : "memory");
      if (RV & 4) mbar_wait_fast(sb + MB_S, par); else mbar_wait(sb + MB_S, par);
      RSTAMP(5);
      PROF(6);
      if (RV & 2) { ldsm4t(e, l16 + SM_E); ldsm4t(e + 4, l16 + SM_E + 512); ldsm2t(e + 8, l16 + SM_E + 1024); }
      else { ldsm4t(e, l16 + SM_E); ldsm2t_in(e + 8, l16 + SM_E + 1024, always); ldsm4t(e + 4, l16 + SM_E + 512); }
      if (RV & 1) lds128(l16 + w * 512 + SM_VM, vm); else lds128_in(vm, l16 + w * 512 + SM_VM, always);
      const float scl = __uint_as_float(lds32(sb + SC_UNSC + 8 - par * 8));
      if (HL == 0) hints = load_hints(hints);
      if (GF & 1) SCHED_FENCE(4);
#pragma unroll
      for (int i = 0; i < 4; i++) p[i] = mul_bf16(e[i], e[4 + i]);
      p[4] = mul_bf16(e[8], e[9]);
      if (HL) hints = load_hints(hints | (p[HL - 1] & always & 1));
      mma16816z(o0, vx[0], p[0], p[1]);
      if (WL & 1) { lds128_in(vx[0], w3a + KP(0) * WS, always); }
      mma16816z(o1, vx[1], p[0], p[1]);
      if (WL & 1) { lds128_in(vx[1], w3a + KP(1) * WS, always); }
      mma16816z(rs, oc, p[0], p[1]);
      mma16816(o0, vx[2], p[2], p[3]); lds128_in(vx[2], w3a + KP(2) * WS, always);
      mma16816(o1, vx[3], p[2], p[3]); lds128_in(vx[3], w3a + KP(3) * WS, always);
      mma16816(rs, oc, p[2], p[3]);
      mma1688(o0, vm[0], vm[1], p[4]); mma1688(o1, vm[2], vm[3], p[4]); mma1688(rs, oc[0], oc[1], p[4]);
      stsm4(l16 + w * 512 + SM_OB, pack_bf16(o0[0], o0[1]), pack_bf16(o0[2], o0[3]), pack_bf16(o1[0], o1[1]), pack_bf16(o1[2], o1[3]));
      bar_sync(6, 128);
      RSTAMP(3);
      PROF(7);
      ldsm4t_in(oc, l16 + SM_OB, always);
      bad = __any_sync(0xffffffffu, !(rs[0] + rs[1] > 0.f) && !bad);
      rs[0] *= scl; rs[1] *= scl;
      asm volatile("{\n.reg .pred p;\nsetp.ne.u32 p, %1, 0;\n@p rcp.approx.ftz.f32 %0, %0;\n}" : "+f"(rs[0]) : "r"(always));
      asm volatile("{\n.reg .pred p;\nsetp.ne.u32 p, %1, 1;\n@p rcp.approx.ftz.f32 %0, %0;\n}" : "+f"(rs[1]) : "r"(always));
      asm volatile("lop3.b32 %0, %1, %2, %3, 0xfe;" : "=r"(lp) : "r"((l16 & 128) * 2), "r"((l16 & 256) * 4), "r"(l16 & 112));
      if (bad) continue;
      ldsm4t(ob, l16 + SM_OB + 512);
      mma16816z(f[2][0], WL & 1 ? vx[0] : wa, oc[0], oc[1]); mma16816z(f[2][1], WL & 1 ? vx[1] : wb, oc[2], oc[3]);
      mma16816z(f[0][0], wo[0], oc[0], oc[1]); mma16816z(f[0][1], wo[4], oc[2], oc[3]);
      mma16816z(f[1][0], w1[0], oc[0], oc[1]); mma16816z(f[1][1], w1[4], oc[2], oc[3]);
      ldsm4t_in(oc, l16 + SM_OB + 1024, always);
      mma16816(f[2][0], vx[2], ob[0], ob[1]); lds128_in(vx[2], w3a + KP(4) * WS, always);
      mma16816(f[2][1], vx[3], ob[2], ob[3]); lds128_in(vx[3], w3a + KP(5) * WS, always);
      mma16816(f[0][0], wo[1], ob[0], ob[1]); mma16816(f[0][1], wo[5], ob[2], ob[3]);
      mma16816(f[1][0], w1[1], ob[0], ob[1]); mma16816(f[1][1], w1[5], ob[2], ob[3]);
      ldsm4t_in(ob, l16 + SM_OB + 1536, always);
      mma16816(f[0][0], wo[2], oc[0], oc[1]); mma16816(f[0][1], wo[6], oc[2], oc[3]);
      mma16816(f[2][0], vx[2], oc[0], oc[1]); lds128_in(vx[2], w3a + KP(6) * WS, always);
      mma16816(f[2][1], vx[3], oc[2], oc[3]); lds128_in(vx[3], w3a + KP(7) * WS, always);
      mma16816(f[1][0], w1[2], oc[0], oc[1]); mma16816(f[1][1], w1[6], oc[2], oc[3]);
      mma16816(f[0][0], wo[3], ob[0], ob[1]); mma16816(f[0][1], wo[7], ob[2], ob[3]);
      mma16816(f[1][0], w1[3], ob[0], ob[1]); mma16816(f[1][1], w1[7], ob[2], ob[3]);
      mma16816(f[2][0], vx[2], ob[0], ob[1]); mma16816(f[2][1], vx[3], ob[2], ob[3]);
      bar_arrive(7, NII < 18 ? 384 : 256);
      lds128_in(ob, sb + SC_DEAD, always);
      uint32_t h[3][2];
#pragma unroll
      for (int j = 0; j < 3; j++)
#pragma unroll
        for (int i = 0; i < 2; i++)
        {
          scale_sum(f[j][1][2 * i], f[j][0][2 * i], rs[0], always); scale_sum(f[j][1][2 * i + 1], f[j][0][2 * i + 1], rs[1], always);
          h[j][i] = pack_f16(f[j][1][2 * i], f[j][1][2 * i + 1]);
        }
      const uint32_t rofs = RANK * 32768;
      red_f16x8(slot(s, RANK >> 1, rofs), h[0][0], h[1][0], h[2][0], 0x3c00u);
      red_f16x8(slot(s, (RANK >> 1) ^ 1, rofs), h[0][1], h[1][1], h[2][1], 0x3c00u);
      if (NII == 18) bar_arrive(10, 256);
      SCHED_FENCE(5);
      RSTAMP(0);
      l16 += ob[B7R];
    }
    {
    PROF(8);
    if (VS0 == 3 || VS1 == 3) send_v(s + 1, 3);
    const uint32_t ma0 = l16 + SM_MEM + w * 128 + (LV >> 3) * 896 + nh * 512;
    const unsigned char* const sl[2] = {slot(s, nh, 0), slot(s, nh ^ 1, 0)};
    uint32_t late = latest_hint(hints, dl, s);
    if (late >= 64) {
      int n = 0;
#pragma unroll 1
      do {
        late = latest_hint(load_hints(hint_addr(s)), dl, s);
      } while (late >= 64 && ++n < SPIN_LIMIT);
    }
    dl += late * 32 + tm.poll;
    PROF(9);
    {
      auto wait_until = [&](uint32_t t) {
        asm volatile("{\n.reg .pred p;\n.reg .s32 c;\n.reg .u64 t;\nTL: mov.u64 t, %%globaltimer;\ncvt.u32.u64 c, t;\nsub.s32 c, c, %0;\nsetp.lt.s32 p, c, 0;\n@p bra.uni TL;\n}" :: "r"(t + (l16 & 15)) : "memory");
      };
      uint4 v[2][3];
      auto load = [&](int c) {
#pragma unroll
        for (int r = 0; r < 3; r++) v[c][r] = ldg_relaxed(sl[c ^ (r >> 1)] + r * 32768);
      };
      auto decode = [&](int c, int n) {
        uint32_t q[9];
        __half2 hm;
        const uint32_t ma = ma0 ^ (c * 512);
#pragma unroll
        for (int i = 0; i < 9; i++) {
          const uint32_t h = i % 3 == 0 ? v[c][i / 3].x : (i % 3 == 1 ? v[c][i / 3].y : v[c][i / 3].z);
          const float2 f = __half22float2(*(const __half2*)&h);
          q[i] = pack_bf16(f.x, f.y);
          hm = i ? __hmax2(hm, __habs2(*(const __half2*)&h)) : __habs2(*(const __half2*)&h);
        }
#pragma unroll
        for (int r = 0; r < 3; r++) stsm4(ma + r * 4096, q[3 * r], q[3 * r + 1], q[3 * r + 2], r < 2 ? v[c][r].w : *(const uint32_t*)&hm);
        const bool done = __all_sync(0xffffffffu, v[c][0].w == 0x5000u && v[c][1].w == 0x5000u && v[c][2].w == 0x5000u) || n > SPIN_LIMIT;
        asm volatile("{\n.reg .pred p;\nsetp.ne.u32 p, %0, 0;\n@p bar.arrive %1, 256;\n}" :: "r"((int)done), "r"(1 + c) : "memory");
        return done;
      };
      if (LEAD) { wait_until(dl - LEAD); load(1); }
      wait_until(dl);
      PROF(10);
      int n = 0;
#pragma unroll 1
      do {
        load(0);
        if (!LEAD) load(1);
        asm volatile("{\n.reg .pred p;\nsetp.eq.u32 p, %0, 0;\n@p bar.sync 13, 384;\n}" :: "r"(n) : "memory");
      } while (!decode(0, n++));
      PROF(11);
      RSTAMP(1);
#pragma unroll 1
      while (!decode(1, n++)) load(1);
      bar_arrive(9, 256);
      RSTAMP(2);
      PROF(12);
    }
    PROF(13);
    if (++s == NSEG - 1) break;
    }
  }
#undef fence_reg
  if (RANK < 2) bar_arrive(4, 256);
  TSTAMP(49);
  {
    PIN(l16);
    tail_attention(sb, RANK, w, LV, 0, 6);
#pragma unroll 1
    for (int sg = 0; sg < 2; sg++) {
      PIN(l16);
      const int lane = LV, m = lane >> 3, g = lane >> 2, t = lane & 3;
      const uint32_t ob = l16 + T_OB + sg * 8192;
      bar_sync(sg ? 0 : 8, 256);
      TSTAMP(54 + 2 * sg);
      const float inv = __uint_as_float(0x7f000000u - lds32(sb + T_UN + sg * 4));
#pragma unroll 1
      for (int j = 0; j < 4; j += 2) {
        float c[2][3][4];
        uint32_t x[4], y[4], z[2][4];
#pragma unroll
        for (int e = 0; e < 2; e++) {
          const uint32_t oa = sb + T_OA + ((sg * 4 + j + e) * 8 + g) * 64 + (blockIdx.x / 3 * 36 & 15) + t * 4;
          z[e][0] = lds32(oa); z[e][1] = lds32(oa + 16); z[e][2] = t ? 0u : lds32(oa + 32);
        }
#pragma unroll
        for (int i = 0; i < 3; i++) {
          const uint32_t wa = sb + T_WA + ((lane & 7) + ((lane >> 4) << 3)) * 128 + (((w + 4 * (m & 1)) ^ (lane & 7)) << 4);
          ldsm4t(x, wa + i * 3072); ldsm2t(y, wa + i * 3072 + 2048);
#pragma unroll
          for (int e = 0; e < 2; e++) { mma1688z(c[e][i], y[0], y[1], z[e][2]); mma16816(c[e][i], x, z[e][0], z[e][1]); }
        }
#pragma unroll
        for (int r = 0; r < 4; r++) {
          ldsm4t(z[0], ob + j * 2048 + r * 512); ldsm4t(z[1], ob + j * 2048 + 2048 + r * 512);
          lds128(l16 + SM_WO3 + w * 512 + r * 2048, x); lds128(l16 + SM_WO3 + w * 512 + (r + 4) * 2048, y);
#pragma unroll
          for (int e = 0; e < 2; e++) { mma16816(c[e][0], wo[r], z[e][0], z[e][1]); mma16816(c[e][1], w1[r], z[e][0], z[e][1]); mma16816(c[e][2], x, z[e][0], z[e][1]); }
#pragma unroll
          for (int e = 0; e < 2; e++) { mma16816(c[e][0], wo[r + 4], z[e][2], z[e][3]); mma16816(c[e][1], w1[r + 4], z[e][2], z[e][3]); mma16816(c[e][2], y, z[e][2], z[e][3]); }
        }
#pragma unroll
        for (int i = 0; i < 4; i++) {
          const float (&d)[3][4] = c[i >> 1];
          const int q = (i & 1) * 2;
          red_f16x8(g_red + T_RED + ((((sg * 4 + j + (i >> 1)) * 3 + RANK) * 4 + w) * 2 + (i & 1)) * 512 + lane * 16, pack_f16(d[0][q] * inv, d[0][q + 1] * inv),
                    pack_f16(d[1][q] * inv, d[1][q + 1] * inv), pack_f16(d[2][q] * inv, d[2][q + 1] * inv), 0x3c00u);
        }
      }
      TSTAMP(55 + 2 * sg);
    }
    if (RSLOW) { wait_until(gtime() + 8000); wait_until(gtime() + 8000); wait_until(gtime() + 4000); }
    if (w < 2) {
      const int b = blockIdx.x, lane = LV, g = lane >> 2, t = lane & 3;
      uint4 v;
#pragma unroll 1
      for (int n = 0; n < SPIN_LIMIT; n++) {
        v = ldg_relaxed(g_red + T_RED + (w * 96 + b) * 512 + lane * 16);
        if (__all_sync(0xffffffffu, v.w == 0x5000u)) break;
        __nanosleep(40);
      }
      const float un = __uint_as_float(lds32(sb + T_UN + w * 4));
      uint32_t* const o = (uint32_t*)(tm.out + (size_t)((NAUXSEG + w) * 32 + b / 24 * 8 + g) * DM + (b >> 3) % 3 * 192 + (b & 1) * 32 + (b & 6) * 4) + t;
#pragma unroll
      for (int j = 0; j < 3; j++) {
        const float2 f = __half22float2(*(const __half2*)(&v.x + j));
        o[j * 32] = movm(pack_bf16(f.x * un, f.y * un));
      }
    }
  }
  TSTAMP(3);
  if (CSY) cluster_sync();
}

__global__ void __cluster_dims__(3, 1, 1) __launch_bounds__(384, 1)
rec_kernel(const __grid_constant__ RMaps tm, const bf16* __restrict__ x, const bf16* __restrict__ mem0) {
  extern __shared__ __align__(1024) unsigned char smem_raw[];
  const uint32_t sb = smem_u32(smem_raw);
  const int tid = threadIdx.x, lane = tid & 31;
  const int wg = __shfl_sync(0xffffffffu, tid >> 7, 0);
  const int w = __shfl_sync(0xffffffffu, (tid >> 5) & 3, 0);
  uint32_t rank; asm("mov.u32 %0, %%cluster_ctarank;" : "=r"(rank));
  STAMP(0);
  TSTAMP(0);
  asm volatile("griddepcontrol.launch_dependents;" ::: "memory");

#define PFT 1
  if (PFT && wg == 1 && lane == 0) asm volatile("prefetch.tensormap [%0];\nprefetch.tensormap [%1];" :: "l"(w & 1 ? &tm.woa : &tm.oa), "l"(w == 0 ? (rank < 2 ? &tm.wk : &tm.wv) : w == 1 ? &tm.wq : w == 2 ? &tm.x : &tm.wo) : "memory");
  if (wg < 2) {
    asm volatile("setmaxnreg.inc.sync.aligned.u32 192;");
    if (tid == 0) {
      for (int i = 0; i < 3; i++) { mbar_init(sb + MB_W + 8 * i, 1); mbar_init(sb + MB_X + 8 * i, 1); }
      mbar_init(sb + MB_WO, 1); mbar_init(sb + MB_WO3, 1);
      mbar_init(sb + MB_S, rank < 2 ? 5 : 6);
      mbar_init(sb + MB_F, 1);
      for (int i = 0; i < 3; i++) mbar_init(sb + MB_T + 8 * i, 1);
      mbar_init(sb + MB_VX, 1); mbar_init(sb + MB_VX + 8, 1);
      asm volatile("fence.mbarrier_init.release.cluster;" ::: "memory");
      fence_async();
      SSTAMP(11, 6);
      load_weights(sb, tm, rank, 0);
      for (int i = 0; i < 3; i++) mbar_expect(sb + MB_X + 8 * i, XT);
      tma_load3(sb + SM_X, &tm.x, 0, sb + MB_X);
      if (!PACE) for (int c = 1; c < 4; c++) load_weights(sb, tm, rank, c);
      mbar_expect(sb + MB_S, rank < 2 ? 640 + 2048 : 1280);
      mbar_expect(sb + MB_VX, 8192); mbar_expect(sb + MB_VX + 8, 8192);
      mbar_expect(sb + MB_T, 2048);
      for (int i = 1; i < 3; i++) mbar_expect(sb + MB_T + 8 * i, rank < 2 ? 5120 : 10240);
      SSTAMP(11, 5);
    }
    __syncwarp();
    bar_sync(0, 384);
    proj_role(sb, tm, rank, wg, w, lane);
  } else {
    asm volatile("setmaxnreg.dec.sync.aligned.u32 120;");
    attn_role(sb, smem_raw, tm, rank, x, mem0, w, lane);
  }
}

constexpr int A_XH = 73728;
constexpr int A_NS = 9, A_WM = 6144, A_WT = 768;
constexpr int A_RING = 2 * A_XH, A_TAIL = A_RING + A_NS * A_WM, A_GW = A_TAIL + A_NS * A_WT;
constexpr int A_EPI = 212864, A_EPW = 9344;
constexpr int A_XW = 4 * XT, A_XT = A_XW + 4096, A_NR = 4;
constexpr int A_IN = A_XT + 2048, A_INS = 2 * 9216 + SEGB;
constexpr int A_GATE = A_EPI + 2 * A_EPW, A_BAR = A_GATE + 512;
constexpr int A_TOTAL = A_BAR + 384;
struct AMaps { CUtensorMap x, wa, wt, oa, o, o3, o8, wob, woa, wo8; };

DI void wgmma_n192_ss_nt(float* d, uint64_t da, uint64_t db, int acc) {
  asm volatile("{\n.reg .pred p;\nsetp.ne.b32 p, %98, 0;\n"
               "wgmma.mma_async.sync.aligned.m64n192k16.f32.bf16.bf16 {"
               "%0,%1,%2,%3,%4,%5,%6,%7,%8,%9,%10,%11,%12,%13,%14,%15,%16,%17,%18,%19,%20,%21,%22,%23,%24,%25,%26,%27,%28,%29,%30,%31,"
               "%32,%33,%34,%35,%36,%37,%38,%39,%40,%41,%42,%43,%44,%45,%46,%47,%48,%49,%50,%51,%52,%53,%54,%55,%56,%57,%58,%59,%60,%61,%62,%63,"
               "%64,%65,%66,%67,%68,%69,%70,%71,%72,%73,%74,%75,%76,%77,%78,%79,%80,%81,%82,%83,%84,%85,%86,%87,%88,%89,%90,%91,%92,%93,%94,%95"
               "}, %96, %97, p, 1, 1, 0, 1;\n}\n"
               : ACC8(d, 0), ACC8(d, 8), ACC8(d, 16), ACC8(d, 24), ACC8(d, 32), ACC8(d, 40), ACC8(d, 48), ACC8(d, 56),
                 ACC8(d, 64), ACC8(d, 72), ACC8(d, 80), ACC8(d, 88) : "l"(da), "l"(db), "r"(acc));
}
#define ACC4(d, o) "+f"(d[o]), "+f"(d[o + 1]), "+f"(d[o + 2]), "+f"(d[o + 3])
DI void wgmma_n24_ss_nt(float* d, uint64_t da, uint64_t db, int acc) {
  asm volatile("{\n.reg .pred p;\nsetp.ne.b32 p, %14, 0;\n"
               "wgmma.mma_async.sync.aligned.m64n24k16.f32.bf16.bf16 {%0,%1,%2,%3,%4,%5,%6,%7,%8,%9,%10,%11}, %12, %13, p, 1, 1, 0, 1;\n}\n"
               : ACC8(d, 0), ACC4(d, 8) : "l"(da), "l"(db), "r"(acc));
}
DI void wgmma_n8_ss(float* d, uint64_t da, uint64_t db, int acc) {
  asm volatile("{\n.reg .pred p;\nsetp.ne.b32 p, %6, 0;\n"
               "wgmma.mma_async.sync.aligned.m64n8k16.f32.bf16.bf16 {%0,%1,%2,%3}, %4, %5, p, 1, 1, 0, 0;\n}\n"
               : ACC4(d, 0) : "l"(da), "l"(db), "r"(acc));
}
DI void wgmma_n40_ss_tt(float* d, uint64_t da, uint64_t db, int acc) {
  asm volatile("{\n.reg .pred p;\nsetp.ne.b32 p, %22, 0;\n"
               "wgmma.mma_async.sync.aligned.m64n40k16.f32.bf16.bf16 {%0,%1,%2,%3,%4,%5,%6,%7,%8,%9,%10,%11,%12,%13,%14,%15,%16,%17,%18,%19}, "
               "%20, %21, p, 1, 1, 1, 1;\n}\n"
               : ACC8(d, 0), ACC8(d, 8), ACC4(d, 16) : "l"(da), "l"(db), "r"(acc));
}
DI void wgmma_n64_rs(float* d, const uint32_t* a, uint64_t db, int acc) {
  asm volatile("{\n.reg .pred p;\nsetp.ne.b32 p, %37, 0;\n"
               "wgmma.mma_async.sync.aligned.m64n64k16.f32.bf16.bf16 {"
               "%0,%1,%2,%3,%4,%5,%6,%7,%8,%9,%10,%11,%12,%13,%14,%15,%16,%17,%18,%19,%20,%21,%22,%23,%24,%25,%26,%27,%28,%29,%30,%31"
               "}, {%32,%33,%34,%35}, %36, p, 1, 1, 0;\n}\n"
               : ACC8(d, 0), ACC8(d, 8), ACC8(d, 16), ACC8(d, 24) : "r"(a[0]), "r"(a[1]), "r"(a[2]), "r"(a[3]), "l"(db), "r"(acc));
}
DI void wgmma_n32_ss_tn(float* d, uint64_t da, uint64_t db, int acc) {
  asm volatile("{\n.reg .pred p;\nsetp.ne.b32 p, %18, 0;\n"
               "wgmma.mma_async.sync.aligned.m64n32k16.f32.bf16.bf16 {%0,%1,%2,%3,%4,%5,%6,%7,%8,%9,%10,%11,%12,%13,%14,%15}, "
               "%16, %17, p, 1, 1, 1, 0;\n}\n"
               : ACC8(d, 0), ACC8(d, 8) : "l"(da), "l"(db), "r"(acc));
}
DI void tma_load3c(uint32_t dst, const CUtensorMap* m, int c0, int c1, int c2, uint32_t mb) {
  asm volatile("cp.async.bulk.tensor.3d.shared::cluster.global.mbarrier::complete_tx::bytes [%0], [%1, {%3, %4, %5}], [%2];"
               :: "r"(dst), "l"(m), "r"(mb), "r"(c0), "r"(c1), "r"(c2) : "memory");
}
DI void count_up(unsigned* p) {
  asm volatile("fence.proxy.async;" ::: "memory");
  asm volatile("red.release.gpu.global.add.u32 [%0], 1;" :: "l"(p) : "memory");
}
#define AX 0
#define FDLY 400
#define FEND 59
DI void publish(unsigned* p) {
  asm volatile("cp.async.bulk.wait_group 0;\nfence.proxy.async;" ::: "memory");
  asm volatile("red.relaxed.gpu.global.add.u32 [%0], 1;" :: "l"(p) : "memory");
}
#define PL 2
#define SER 0
#define DRAIN 0
#define PR 4
#define NQ 3
#define PUB 0
#define LA 1
#define ADLY 0

__global__ void __launch_bounds__(512, 1)
aux_kernel(const __grid_constant__ AMaps tm, const bf16* __restrict__ wqkv, const bf16* __restrict__ woa, const bf16* __restrict__ gate_w, bf16* __restrict__ out) {
  extern __shared__ __align__(1024) unsigned char smem_raw[];
  const uint32_t sb = smem_u32(smem_raw);
  const uint32_t fullx = sb + A_BAR, full1 = fullx + 24, empty1 = full1 + 8 * A_NS, fullw = empty1 + 8 * A_NS, full3 = fullw + 8, empty3 = full3 + 8 * A_NR,
                 fullq = empty3 + 8 * A_NR, emptyq = fullq + 24;
  const int tid = threadIdx.x, lane = tid & 31, cta = blockIdx.x;
  const int wg = __shfl_sync(0xffffffffu, tid >> 7, 0), w = __shfl_sync(0xffffffffu, (tid >> 5) & 3, 0);
  ASTAMP(14);
  if (tid == 384) {
    for (int i = 0; i < 3; i++) mbar_init(fullx + 8 * i, 1);
    for (int i = 0; i < A_NS; i++) { mbar_init(full1 + 8 * i, 1); mbar_init(empty1 + 8 * i, 8); }
    mbar_init(fullw, 1);
    for (int i = 0; i < 3; i++) { mbar_init(fullq + 8 * i, 1); mbar_init(emptyq + 8 * i, 4); }
    for (int i = 0; i < A_NR; i++) { mbar_init(full3 + 8 * i, 1); mbar_init(empty3 + 8 * i, cta < NH ? 8 : 4); }
    fence_async();
  }
  __syncthreads();
  ASTAMP(0);
  const int tile = cta >> 1, hh = cta & 1;
  auto p3_n = [&](int g) { return cta < NH ? (cta & 3) * 2 + g : 8; };
  auto p3_next = [&](int& sl, int& ph) {
    sl += cta < NH ? 1 : 2;
    if (sl >= (cta < NH ? 6 - NQ : 4)) { sl -= cta < NH ? 6 - NQ : 4; ph ^= 1; }
  };
  auto p3_k = [&](int g) { return cta < NH ? cta >> 2 : (cta & 3) * 2 + g; };
  if (wg == 3) {
    asm volatile("setmaxnreg.dec.sync.aligned.u32 24;");
    const bool lead = lane == 0;
    if (w < 3) {
      if (ADLY) wait_until(gtime() + ADLY);
      if (elect_one()) {
        mbar_expect(fullx + 8 * w, 49152);
        for (int p = 0; p < 2; p++)
          asm volatile("cp.async.bulk.tensor.4d.shared::cluster.global.mbarrier::complete_tx::bytes [%0], [%1, {%3, %4, %5, %6}], [%2];"
                       :: "r"(sb + p * A_XH + w * 24576), "l"(&tm.x), "r"(fullx + 8 * w), "r"(0), "r"(p), "r"(57 * tile - 7), "r"(3 * w) : "memory");
      }
#pragma unroll 1
      for (int r = 0; r < 17; r++) {
#pragma unroll 1
        for (int st = w; st < A_NS; st += 3) {
          if (r > 0) mbar_wait(empty1 + 8 * st, ~r & 1);
          if (r < 16 && elect_one()) {
            const int col = hh * 288 + (r >> 2) * 72, row = (r & 3) * 144 + st * 16;
            mbar_expect(full1 + 8 * st, A_WM + (AX & 1 ? 0 : A_WT));
            tma_load3c(sb + A_RING + st * A_WM, &tm.wa, col, row, 0, full1 + 8 * st);
            if (!(AX & 1)) tma_load3c(sb + A_TAIL + st * A_WT, &tm.wt, col + 64, row, 0, full1 + 8 * st);
          }
          __syncwarp();
        }
        if (r == 0 && elect_one())
          for (int j = 0; j < 3; j++)
            asm volatile("cp.async.bulk.prefetch.L2.global [%0], %1;" :: "l"((const char*)wqkv + cta * 55296 + (w * 3 + j) * 6144), "r"(6144) : "memory");
        __syncwarp();
      }
      bar_sync(8, 96);
    }
    const unsigned epoch = lds32(sb + A_BAR + 376);
    if (w == 2 && cta < NH) {
      if (lead) {
        int avail = 0, q = 0, ph = 1;
#pragma unroll 1
        for (int seg = 0; seg < NAUXSEG; seg++) {
          const unsigned char* const src = g_seg + ((size_t)(AX & 128 ? 0 : seg % NRING) * 96 + cta * 3) * SEGB;
          SSTAMP(0, seg);
          if (seg >= avail) {
            const unsigned* const c = &g_scnt[(seg * 32 + cta) * 8];
            const int c2 = ldg_relaxed32(c + 512) - 3 * (epoch + 1), c0 = ldg_acquire32(c) - 3 * (epoch + 1);
            if (c2 >= 0 && LA) avail = seg + 3;
            if (c0 < 0) {
              wait_count(c, 3 * (epoch + 1), !(TL & 2) || seg < NAUXSEG - 2);
              if (FDLY && seg < FEND) wait_until(gtime() + FDLY);
            }
          }
          SSTAMP(1, seg);
          const uint32_t mb = fullq + q * 8;
          mbar_wait(emptyq + q * 8, q == 2 ? ph ^ 1 : ph);
          if (AX & 8) mbar_arrive(mb); else mbar_expect(mb, A_INS);
#pragma unroll 1
          for (int r = 0; r < ((AX & 8) ? 0 : 3); r++)
            asm volatile("cp.async.bulk.shared::cluster.global.mbarrier::complete_tx::bytes [%0], [%1], %2, [%3];"
                         :: "r"(sb + (q < 2 ? A_IN + q * A_INS : 3 * XT) + r * 9216), "l"(src + r * SEGB), "r"(r < 2 ? 9216 : SEGB), "r"(mb) : "memory");
          if (seg == 1) wait_count(&g_abar[32], NAUX * (epoch + 1));
          if (seg > 1) stg_relaxed32(&g_used[cta * 32], epoch * NSEG + seg + 1 - NQ);
          if (++q == NQ) { q = 0; ph ^= 1; }
        }
      }
      return;
    }
    if (w == 3) {
#pragma unroll 1
      for (int c = 0; c < 4; c++) {
        if (lead) asm volatile("cp.async.bulk.wait_group.read 0;" ::: "memory");
        __syncwarp();
        bar_arrive(11, 160); bar_arrive(12, 160);
#pragma unroll 1
        for (int g = 0; g < 2; g++) {
          bar_sync(13 + g, 160);
          if (lead) {
            asm volatile("cp.async.bulk.tensor.3d.global.shared::cta.bulk_group [%0, {%2, %3, %4}], [%1];"
                         :: "l"(&tm.oa), "r"(sb + A_EPI + g * A_EPW + 1024), "r"(4096 + hh * 288 + c * 72), "r"(g), "r"(57 * tile) : "memory");
            asm volatile("cp.async.bulk.commit_group;" ::: "memory");
          }
        }
      }
      if (lead) publish(&g_abar[32]);
      __syncwarp();
    }
    if ((w & 1) && cta < NH) {
#pragma unroll 1
      for (int seg = w >> 1; seg < NAUXSEG; seg += 2) {
        bar_sync(w == 1 ? 4 : 15, 160);
        if (lead) {
          if (PUB == 0 || seg >= NAUXSEG - 2) publish(&g_ocnt[seg * 64 + 2 * cta / 9 * 8]);
          else {
            if (PUB == 1) asm volatile("fence.acq_rel.gpu;" ::: "memory"); else if (PUB > 2) wait_until(gtime() + PUB);
            asm volatile("red.relaxed.gpu.global.add.u32 [%0], 1;" :: "l"(&g_ocnt[seg * 64 + 2 * cta / 9 * 8]) : "memory");
          }
          if (2 * cta / 9 != (2 * cta + 1) / 9) asm volatile("red.relaxed.gpu.global.add.u32 [%0], 1;" :: "l"(&g_ocnt[seg * 64 + (2 * cta + 1) / 9 * 8]) : "memory");
          SSTAMP(9, seg);
        }
        __syncwarp();
      }
    }
    if (w & 1) return;
    if (w == 0) {
      if (lead) {
        mbar_expect(fullw, 18 * 8192 + 2048);
#pragma unroll 1
        for (int k = 0; k < 18; k++) {
          const int g = k / 9, kb = p3_k(g) * 9 + k - 9 * g;
          if (kb < 64) tma_load(sb + k * 8192, &tm.wob, p3_n(g) * 64, kb * 64, fullw);
          else tma_load(sb + k * 8192, &tm.woa, p3_n(g) * 64, (kb - 64) * 64, fullw);
        }
        for (int g = 0; g < 2; g++) tma_load(sb + A_XW + g * 2048, &tm.wo8, p3_n(g) * 64, 512 + p3_k(g) * 8, fullw);
      }
      __syncwarp();
    }
    bar_sync(6, cta >= NH ? 320 : 288);
    if (lead) {
      if (NQ == 3) for (int i = 0; i < 4; i++) mbar_arrive(emptyq + 16);
      wait_count(&g_abar[32], NAUX * (epoch + 1));
      int avail = 0, sl = w >> 1, ph = 1;
      const int ke = p3_k(w >> 1);
      const unsigned nheads = (ke < 7 ? 5 : 1) * (epoch + 1);
#pragma unroll 1
      for (int seg = 0; seg < NAUXSEG; seg++) {
        bool waited = false;
        if (seg >= avail) {
          const unsigned* const c = &g_ocnt[seg * 64 + ke * 8];
          const int c2 = ldg_relaxed32(c + 128) - nheads, c1 = ldg_relaxed32(c + 64) - nheads, c0 = ldg_acquire32(c) - nheads;
          waited = c0 < 0;
          if (waited) wait_count(c, nheads, !(TL & 2) || seg < NAUXSEG - 2);
          else if (c1 >= 0) avail = seg + (c2 >= 0 ? 3 : 2);
        }
        SSTAMP(5, seg);
        mbar_wait(empty3 + 8 * sl, ph);
        if (AX & 4) mbar_arrive(full3 + 8 * sl);
        else {
          mbar_expect(full3 + 8 * sl, XT + 512);
          tma_load3c(sb + sl * XT, &tm.o3, 0, seg * 32, ke * 9, full3 + 8 * sl);
          tma_load(sb + A_XT + sl * 512, &tm.o8, 72 * 64 + ke * 8, seg * 32, full3 + 8 * sl);
        }
        p3_next(sl, ph);
      }
    }
  } else if (wg == 2) {
    asm volatile("setmaxnreg.dec.sync.aligned.u32 88;");
    {
      const unsigned epoch = *(volatile unsigned*)&g_epoch2;
      if ((tid & 127) < 80) { const uint4 g = __ldg((const uint4*)gate_w + min(tid & 127, 71)); sts128(sb + A_GW + (tid & 127) * 16, g.x, g.y, g.z, g.w); }
      fence_async();
      bar_sync(3, 128);
      float gt[2][4];
      const uint32_t d0 = (sb & 0x3FFFF) >> 4;
#pragma unroll 1
      for (int j = 0; j < 3; j++) {
        mbar_wait(fullx + 8 * j, 0);
        WG_FENCE();
#pragma unroll
        for (int k = 0; k < 24; k++)
          wgmma_n8_ss(gt[k & 1], desc_at(d0 + (k & 1) * (A_XH >> 4) + j * 1536 + (k >> 3) * 512 + (k & 6), 16, 1024, 1), desc_at(d0 + (A_GW >> 4) + j * 24 + (k & 30), 16, 128, 0), j | (k >> 1));
        WG_COMMIT();
      }
      WG_WAIT(0);
      if ((lane & 3) == 0)
#pragma unroll
        for (int i = 0; i < 4; i++) {
          const float gv = 1.f / (1.f + __expf(-gt[i >> 1][(i & 1) * 2]));
          const int r = w * 16 + (lane >> 2) + (i & 1) * 8, tok = 2 * (57 * tile - 7 + r) + (i >> 1);
          sts32(sb + A_GATE + ((i >> 1) * 64 + r) * 4, __float_as_uint(gv));
          if (hh == 0 && r >= 7 && tok < S_LEN) g_gate[tok] = gv;
        }
      if (tid == 256) sts32(sb + A_BAR + 376, epoch);
      __syncwarp();
      bar_arrive(7, 384);
      __half2 hw = __float2half2_rn(0.f);
#pragma unroll
      for (int i = 0; i < 9; i++) { const uint4 v = __ldg((const uint4*)woa + cta * 1152 + i * 128 + (tid & 127)); hw = amax4(hw, &v.x); }
      const uint32_t ew = wexp(hw);
      if (lane == 0) atomicMax(&g_amax[0], (unsigned long long)(epoch + 1) << 32 | ew);
      bar_sync(3, 128);
      if (tid == 256) {
        count_up(&g_abar[0]);
        wait_count(&g_abar[0], NAUX * (epoch + 1));
        if (cta == 0) *(volatile unsigned*)&g_epoch2 = epoch + 1;
      }
      __syncwarp();
      bar_sync(3, 128);
    }
    if (cta < NH) {
      const int lim = w * 8 + (lane >> 2) - 2 * (lane & 3);
      int q = 0, ph = 0;
      uint32_t p[5][4];
#pragma unroll
      for (int n = 0; n < 10; n++) p[n >> 1][1 + (n & 1)] = __shfl_sync(0xffffffffu, lane ^ n, n);
#pragma unroll 1
      for (int seg = 0; seg < NAUXSEG; seg++) {
        const float gt = __ldcg(&g_gate[seg * 32 + w * 8 + (lane >> 2)]);
        float sc[20], d[32];
        const uint32_t d0 = ((sb & 0x3FFFF) + (q < 2 ? A_IN + q * A_INS : 3 * XT)) >> 4;
        mbar_wait(fullq + q * 8, ph);
        if (tid == 256) SSTAMP(2, seg);
        WG_FENCE();
#pragma unroll
        for (int k = 0; k < 8; k++) {
          const int o = ((k >> 2) * 9216 + (k & 3) * 256) >> 4;
          wgmma_n40_ss_tt(sc, desc_at(d0 + o, 128, 512, 0), desc_at(d0 + o + 256, 128, 1024, 0), k > 0);
        }
        WG_COMMIT();
        WG_WAIT(0);
        if (tid == 256) SSTAMP(12, seg);
        float a[10];
#pragma unroll
        for (int i = 0; i < 10; i++) {
          a[i] = sc[(i >> 1) * 4 + (i & 1)] * (SM_SCALE * LOG2E);
          if (i < 8 && (i >> 1) * 8 + (i & 1) > lim) a[i] = -1.0e9f * LOG2E;
        }
        float m = max10(a);
        m = fmaxf(m, __shfl_xor_sync(0xffffffffu, m, 1)); m = fmaxf(m, __shfl_xor_sync(0xffffffffu, m, 2));
#pragma unroll
        for (int i = 0; i < 10; i++) a[i] = ex2(a[i] - m);
#pragma unroll
        for (int n = 0; n < 5; n++) {
          p[n][0] = pack_bf16(a[2 * n], a[2 * n + 1]); p[n][3] = p[n][0] | p[n][1];
          asm volatile("" : "+r"(p[n][0]), "+r"(p[n][3]) :: "memory");
        }
        float sum = ((a[0] + a[1]) + (a[2] + a[3])) + ((a[4] + a[5]) + (a[6] + a[7])) + (a[8] + a[9]);
        sum += __shfl_xor_sync(0xffffffffu, sum, 1);
        if (tid == 256) SSTAMP(3, seg);
        WG_FENCE();
#pragma unroll
        for (int n = 0; n < 5; n++) wgmma_n64_rs(d, p[n], n < 4 ? desc_at(d0 + 1152 + 8 * n, 4096, 512, 0) : desc_at(d0 + 1152 + 512, 1024, 128, 0), n);
        WG_COMMIT();
        sum += __shfl_xor_sync(0xffffffffu, sum, 2);
        const float f = (1.f - gt) * rcp(sum);
        WG_WAIT(0);
        if (lane == 0) mbar_arrive(emptyq + q * 8);
        if (++q == NQ) { q = 0; ph ^= 1; }
        if (tid == 256) SSTAMP(4, seg);
        unsigned char* const o = (unsigned char*)(g_Ocat + (size_t)(seg * 32 + w * 8 + (lane >> 2)) * KCAT + cta * DH) + (lane & 1) * 12 + (lane & 3) * 4;
#pragma unroll
        for (int n = 0; n < 8; n++) {
          const float* const v = d + (n & 3) * 8 + (n >> 2) * 2;
          const uint32_t x = pack_bf16(v[0] * f, v[1] * f), y = pack_bf16(v[4] * f, v[5] * f), z = __shfl_xor_sync(0xffffffffu, lane & 1 ? x : y, 1);
          if (!(AX & 32)) asm volatile("st.relaxed.gpu.global.v2.b32 [%0], {%1,%2};" :: "l"(o + n * 32), "r"(lane & 1 ? z : x), "r"(lane & 1 ? y : z) : "memory");
        }
        if (tid == 256) SSTAMP(13, seg);
        bar_sync(seg & 1 ? 15 : 4, 160);
      }
    }
  } else {
    asm volatile("setmaxnreg.inc.sync.aligned.u32 200;");
    {
      const int g = lane >> 2, t = lane & 3;
      const uint32_t eb = sb + A_EPI + wg * A_EPW, d0 = (sb & 0x3FFFF) >> 4;
      const uint32_t own = (2 * t <= g ? 0xffffu : 0u) | (2 * t < g ? 0xffff0000u : 0u);
      const int kmin = 7 - 57 * tile - 16 * w;
      __half2 ho = __float2half2_rn(0.f);
#pragma unroll 1
      for (int c = 0; c < 4; c++) {
        float acc[96], tl[12];
#pragma unroll 1
        for (int r = 0; r < 4; r++) {
#pragma unroll
          for (int st = 0; st < A_NS; st++) {
            const int ks = r * 9 + st;
            if (c == 0 && st % 3 == 0 && ks % 12 == 0) mbar_wait(fullx + 8 * (ks / 12), 0);
            mbar_wait(full1 + 8 * st, r & 1);
            const uint64_t da = desc_at(d0 + wg * (A_XH >> 4) + (ks >> 2) * 512 + (ks & 3) * 2, 16, 1024, 1);
            WG_FENCE();
            wgmma_n192_ss_nt(acc, da, desc_at(d0 + ((A_RING + st * A_WM) >> 4), 2048, 1024, 1), ks);
            if (!(AX & 2)) wgmma_n24_ss_nt(tl, da, desc_at(d0 + ((A_TAIL + st * A_WT) >> 4), 128, 256, 0), ks);
            WG_COMMIT();
            if (st == 0 && r == 2) bar_sync(11 + wg, 160);
            WG_WAIT(1);
            if (ks > 0 && lane == 0) mbar_arrive(empty1 + 8 * ((st + A_NS - 1) % A_NS));
          }
        }
        WG_WAIT(0);
        if (lane == 0) mbar_arrive(empty1 + 8 * (A_NS - 1));
        ASTAMP(16 + (c & 3));
        uint32_t ql[9], qh[9], kl[9], kh[9], kx[10], vl[9], vh[9], vx[10];
#pragma unroll
        for (int j = 0; j < 9; j++) {
          const float* const q = j < 8 ? acc + 4 * j : tl, * const k = j < 8 ? acc + 32 + 4 * j : tl + 4, * const v = j < 8 ? acc + 64 + 4 * j : tl + 8;
          kh[j] = pack_bf16(k[2], k[3]); vh[j] = pack_bf16(v[2], v[3]);
          ql[j] = pack_bf16(q[0], q[1]); qh[j] = pack_bf16(q[2], q[3]); kl[j] = pack_bf16(k[0], k[1]); vl[j] = pack_bf16(v[0], v[1]);
        }
        if (w < 3) {
          const uint32_t ha = eb + 1024 + w * 2304 + lane * 16;
          stsm4(ha, kh[0], kh[1], kh[2], kh[3]); stsm4(ha + 512, kh[4], kh[5], kh[6], kh[7]);
          stsm4(ha + 1024, vh[0], vh[1], vh[2], vh[3]); stsm4(ha + 1536, vh[4], vh[5], vh[6], vh[7]);
          asm volatile("stmatrix.sync.aligned.m8n8.x2.shared.b16 [%0], {%1,%2};" :: "r"(ha + 2048), "r"(kh[8]), "r"(vh[8]) : "memory");
        }
        if (c == 0) bar_sync(7, 384); else bar_sync(1 + wg, 128);
        {
          const uint32_t ha = eb + 1024 + max(w - 1, 0) * 2304 + lane * 16;
          ldsm4(kx, ha); ldsm4(kx + 4, ha + 512); ldsm4t(vx, ha + 1024); ldsm4t(vx + 4, ha + 1536);
          asm volatile("ldmatrix.sync.aligned.m8n8.x1.shared.b16 {%0}, [%1];" : "=r"(kx[8]) : "r"(ha + 2048) : "memory");
          asm volatile("ldmatrix.sync.aligned.m8n8.x1.trans.shared.b16 {%0}, [%1];" : "=r"(vx[8]) : "r"(ha + 2176) : "memory");
        }
        const float gl = __uint_as_float(lds32(sb + A_GATE + (wg * 64 + w * 16 + g) * 4)), gh = __uint_as_float(lds32(sb + A_GATE + (wg * 64 + w * 16 + g + 8) * 4));
#pragma unroll
        for (int j = 0; j < 9; j++) { vl[j] = movm(vl[j]); vh[j] = movm(vh[j]); }
        bar_sync(1 + wg, 128);
        uint32_t ol[9], oh[9];
#pragma unroll
        for (int i = 0; i < 4; i++) {
          const int b = 2 * i;
          const uint32_t a[4] = {t >= i ? ql[b] : 0u, t >= i ? qh[b] : 0u, ql[b + 1], qh[b + 1]}, a4 = t <= i ? ql[b + 2] : 0u, a5 = t <= i ? qh[b + 2] : 0u;
          float sx[4], sl[4], sh[4];
          mma16816z(sx, a, kx[b], kx[b + 1]); mma16816z(sl, a, kl[b], kl[b + 1]); mma16816z(sh, a, kh[b], kh[b + 1]);
          mma1688(sx, a4, a5, kx[b + 2]); mma1688(sl, a4, a5, kl[b + 2]); mma1688(sh, a4, a5, kh[b + 2]);
          float e[4];
#pragma unroll
          for (int u = 0; u < 4; u++) {
            const int cc = 2 * t + (u & 1);
            e[u] = (cc <= g ? (u < 2 ? sl[u] : sh[u]) : (u < 2 ? sx[u] : sl[u])) * (0.23570226039551584f * LOG2E);
            if ((cc <= g ? cc : cc - 8) + (u & 2) * 4 < kmin) e[u] = -1.0e9f * LOG2E;
          }
          float m0 = fmaxf(e[0], e[1]), m1 = fmaxf(e[2], e[3]);
#pragma unroll
          for (int o = 1; o < 4; o <<= 1) { m0 = fmaxf(m0, __shfl_xor_sync(0xffffffffu, m0, o)); m1 = fmaxf(m1, __shfl_xor_sync(0xffffffffu, m1, o)); }
          e[0] = ex2(e[0] - m0); e[1] = ex2(e[1] - m0); e[2] = ex2(e[2] - m1); e[3] = ex2(e[3] - m1);
          const uint32_t p0 = pack_bf16(e[0], e[1]), p1 = pack_bf16(e[2], e[3]);
          const uint32_t p[4] = {p0 & ~own, 0u, p0 & own, p1 & ~own};
          float s0 = e[0] + e[1], s1 = e[2] + e[3];
#pragma unroll
          for (int o = 1; o < 4; o <<= 1) { s0 += __shfl_xor_sync(0xffffffffu, s0, o); s1 += __shfl_xor_sync(0xffffffffu, s1, o); }
          const float f0 = gl * rcp(s0), f1 = gh * rcp(s1);
#pragma unroll
          for (int j = b; j < b + 3; j++) {
            float o[4];
            mma16816z(o, p, vx[j], vl[j]);
            mma1688(o, 0u, p1 & own, vh[j]);
            const uint32_t lo = pack_bf16(o[0] * f0, o[1] * f0), hi = pack_bf16(o[2] * f1, o[3] * f1);
            if (j > b || i == 0) { ol[j] = lo; oh[j] = hi; }
            else { ol[j] = t >= i ? lo : ol[j]; oh[j] = t >= i ? hi : oh[j]; }
          }
        }
        const uint32_t sa = eb + 16 + (w * 16 + (lane & 15)) * 144 + (lane >> 4) * 16;
#pragma unroll
        for (int j = 0; j < 8; j += 2) stsm4(sa + j * 16, ol[j], oh[j], ol[j + 1], oh[j + 1]);
        asm volatile("stmatrix.sync.aligned.m8n8.x2.shared.b16 [%0], {%1,%2};" :: "r"(sa + 128), "r"(ol[8]), "r"(oh[8]) : "memory");
        ho = amax4(amax4(amax4(amax4(ho, ol), ol + 4), oh), oh + 4);
        ho = __hmax2_nan(__hmax2_nan(ho, __habs2(*(const __half2*)&ol[8])), __habs2(*(const __half2*)&oh[8]));
        if (c == 3 && tile == 17) {
          const uint32_t eo = wexp(ho);
          if (lane == 0) atomicMax(&g_amax[16], (unsigned long long)(lds32(sb + A_BAR + 376) + 1) << 32 | eo);
        }
        fence_async();
        bar_arrive(13 + wg, 160);
        ASTAMP(20 + (c & 3));
      }
    }
    ASTAMP(3);
    uint32_t wa[36][4];
    mbar_wait(fullw, 0);
    const uint32_t la = sb + wg * 73728 + ((lane & 7) + ((lane >> 4) << 3)) * 128 + (((2 * w + ((lane >> 3) & 1)) ^ (lane & 7)) << 4);
#pragma unroll
    for (int k = 0; k < 36; k++) ldsm4t(wa[k], la + k * 2048);
    sts64(sb + A_XW + wg * 2048 + 1024 + (tid & 127) * 8, 0, 0);
    fence_async();
    bar_arrive(6, cta >= NH ? 320 : 288);
    bar_sync(1 + wg, 128);
    ASTAMP(4);
    const int nsl = p3_n(wg), ke = p3_k(wg), t = lane & 3;
    const unsigned epoch = lds32(sb + A_BAR + 376);
    uint2* const part = g_part + nsl * 4096 + w * 16 + (lane >> 2) * 2 + (t & 1);
    auto tag = [&](int seg) { return PR == 8 ? ((seg >> 3) + 1 + (epoch & (seg >> 1) & (seg >> 2))) & 1 : ((seg >> 2) + 1 + (epoch & (seg >> 1))) & 1; };
    uint2 v[4];
    auto fetch = [&](int seg) {
#pragma unroll
      for (int j = 0; j < 4; j++)
        asm volatile("ld.relaxed.gpu.global.v2.b32 {%0,%1}, [%2];" : "=r"(v[j].x), "=r"(v[j].y) : "l"(part + (seg & (PR - 1)) * 36864 + ke * 512 + ((t >> 1) * 4 + j) * 64) : "memory");
    };
    auto finish = [&](int seg) {
      int n = 0;
#pragma unroll 1
      while (!(AX & 16) && __any_sync(0xffffffffu, (((v[0].x ^ tag(seg)) | (v[1].x ^ tag(seg)) | (v[2].x ^ tag(seg)) | (v[3].x ^ tag(seg))) & 1) != 0) && ++n < SPIN_LIMIT) {
        if (seg < NAUXSEG - ((TL & 2) ? 2 : 1)) __nanosleep(100);
        fetch(seg);
      }
      const float a0 = (bf_lo(v[0].x) + bf_lo(v[1].x)) + (bf_lo(v[2].x) + bf_lo(v[3].x)), a1 = (bf_hi(v[0].x) + bf_hi(v[1].x)) + (bf_hi(v[2].x) + bf_hi(v[3].x));
      const float b0 = (bf_lo(v[0].y) + bf_lo(v[1].y)) + (bf_lo(v[2].y) + bf_lo(v[3].y)), b1 = (bf_hi(v[0].y) + bf_hi(v[1].y)) + (bf_hi(v[2].y) + bf_hi(v[3].y));
      const float c0 = (t < 2 ? a0 : b0) + __shfl_xor_sync(0xffffffffu, t < 2 ? b0 : a0, 2), c1 = (t < 2 ? a1 : b1) + __shfl_xor_sync(0xffffffffu, t < 2 ? b1 : a1, 2);
      ((uint32_t*)(out + (size_t)(seg * 32 + ke * 4 + ((lane >> 2) & 3)) * DM + nsl * 64 + w * 16 + (lane >> 4) * 8))[t] = movm(pack_bf16(c0, c1));
    };
    float acc[16];
    if (AX & 64) for (int i = 0; i < 16; i++) acc[i] = 0.f;
    int done = 0, sl = cta < NH ? 0 : wg, ph = 0;
    const uint32_t d0 = (sb & 0x3FFFF) >> 4;
#pragma unroll 1
    for (int seg = 0; seg < NAUXSEG; seg++) {
      if (DRAIN) {
#pragma unroll 1
        while (done < seg && !mbar_test(full3 + 8 * sl, ph)) { fetch(done); finish(done); done++; }
      }
      mbar_wait(full3 + 8 * sl, ph);
      if (SER && !(AX & 64) && (wg == 1 || seg > 0)) bar_sync(10 - wg, 256);
      if (tid == 128) SSTAMP(6, seg);
      if (!(AX & 16)) fetch(done);
      if (!(AX & 64)) {
        const uint64_t db = desc_at(d0 + sl * (XT >> 4), 16, 1024, 1);
        WG_FENCE();
        wgmma_n32_ss_tn(acc, desc_at(d0 + ((A_XW + wg * 2048) >> 4), 8192, 1024, 1), desc_at(d0 + (A_XT >> 4) + sl * 32, 0, 128, 0), 0);
#pragma unroll
        for (int k = 0; k < 36; k++) {
          wgmma_n32_rs(acc, wa[k][0], wa[k][1], wa[k][2], wa[k][3], db + (k >> 2) * 256 + (k & 3) * 2, 1);
          if (SER && k == SER && (wg == 0 || seg < NAUXSEG - 1)) bar_arrive(9 + wg, 256);
        }
        WG_COMMIT();
      }
      if (done <= seg - PL) finish(done++);
      WG_WAIT(0);
      if (lane == 0) mbar_arrive(empty3 + 8 * sl);
      p3_next(sl, ph);
#pragma unroll
      for (int j = 0; j < 4; j++)
        if (!(AX & 16) || acc[4 * j] == 1.2345678f)
          asm volatile("st.relaxed.gpu.global.v2.b32 [%0], {%1,%2};" :: "l"(part + (seg & (PR - 1)) * 36864 + (2 * j + (t >> 1)) * 512 + ke * 64),
                       "r"((pack_bf16(acc[4 * j], acc[4 * j + 1]) & ~1u) | tag(seg)), "r"(pack_bf16(acc[4 * j + 2], acc[4 * j + 3])) : "memory");
      if (tid == 128) SSTAMP(7, seg);
      if (tid == 128) SSTAMP(8, seg);
      if ((seg & 7) == 6) ASTAMP(5 + (seg >> 3));
    }
#pragma unroll 1
    for (; done < NAUXSEG; done++) { fetch(done); finish(done); }
    ASTAMP(13);
    TSTAMP(48);
  }
}

typedef CUresult (*EncodeFn)(CUtensorMap*, CUtensorMapDataType, cuuint32_t, void*, const cuuint64_t*, const cuuint64_t*,
                             const cuuint32_t*, const cuuint32_t*, CUtensorMapInterleave, CUtensorMapSwizzle,
                             CUtensorMapL2promotion, CUtensorMapFloatOOBfill);
static void make_map(EncodeFn enc, CUtensorMap* m, const void* p, int rows, int cols, int box_rows) {
  cuuint64_t dims[2] = {(cuuint64_t)cols, (cuuint64_t)rows};
  cuuint64_t strides[1] = {(cuuint64_t)cols * 2};
  cuuint32_t box[2] = {64, (cuuint32_t)box_rows};
  cuuint32_t es[2] = {1, 1};
  enc(m, CU_TENSOR_MAP_DATA_TYPE_BFLOAT16, 2, (void*)p, dims, strides, box, es, CU_TENSOR_MAP_INTERLEAVE_NONE,
      CU_TENSOR_MAP_SWIZZLE_128B, CU_TENSOR_MAP_L2_PROMOTION_L2_128B, CU_TENSOR_MAP_FLOAT_OOB_FILL_NONE);
}

constexpr int g_poll = POLL_NS;
extern "C" void kernel_launch(void* const* d_in, const int* in_sizes, int n_in, void* d_out, int out_size) {
  const bf16* x = (const bf16*)d_in[0];
  const bf16* wqkvA = (const bf16*)d_in[1];
  const bf16* woA = (const bf16*)d_in[2];
  const bf16* mem0 = (const bf16*)d_in[4];
  const bf16* Wq = (const bf16*)d_in[5];
  const bf16* Wk = (const bf16*)d_in[6];
  const bf16* Wv = (const bf16*)d_in[7];
  const bf16* Wo = (const bf16*)d_in[8];
  const bf16* gate_w = (const bf16*)d_in[10];
  static EncodeFn enc = nullptr;
  static void *pO = nullptr, *pR = nullptr;
  if (!enc) {
    cudaDriverEntryPointQueryResult qr;
    cudaGetDriverEntryPoint("cuTensorMapEncodeTiled", (void**)&enc, cudaEnableDefault, &qr);
    cudaGetSymbolAddress(&pO, g_Ocat);
    cudaGetSymbolAddress(&pR, g_red_raw);
    cudaFuncSetAttribute(rec_kernel, cudaFuncAttributeMaxDynamicSharedMemorySize, SM_TOTAL);
    cudaFuncSetAttribute(aux_kernel, cudaFuncAttributeMaxDynamicSharedMemorySize, A_TOTAL);
  }
  RMaps rm;
  rm.poll = g_poll; rm.out = (bf16*)d_out;
  make_map(enc, &rm.woa, woA, DM, DM, 24);
  {
    cuuint64_t dims[2] = {KCAT, S_LEN}, strides[1] = {KCAT * 2};
    cuuint32_t box[2] = {32, 64}, es[2] = {1, 1};
    enc(&rm.oa, CU_TENSOR_MAP_DATA_TYPE_BFLOAT16, 2, pO, dims, strides, box, es, CU_TENSOR_MAP_INTERLEAVE_NONE,
        CU_TENSOR_MAP_SWIZZLE_NONE, CU_TENSOR_MAP_L2_PROMOTION_NONE, CU_TENSOR_MAP_FLOAT_OOB_FILL_NONE);
  }
  rm.red = (unsigned char*)(((uintptr_t)pR + 262143) & ~(uintptr_t)262143);
  {
    cuuint64_t dims[3] = {64, S_LEN, 9}, strides[2] = {DM * 2, 128};
    cuuint32_t box[3] = {64, 32, 9}, es[3] = {1, 1, 1};
    enc(&rm.x, CU_TENSOR_MAP_DATA_TYPE_BFLOAT16, 3, (void*)x, dims, strides, box, es, CU_TENSOR_MAP_INTERLEAVE_NONE,
        CU_TENSOR_MAP_SWIZZLE_128B, CU_TENSOR_MAP_L2_PROMOTION_L2_128B, CU_TENSOR_MAP_FLOAT_OOB_FILL_NONE);
  }
  make_map(enc, &rm.wq, Wq, DM, 4096, 192);
  make_map(enc, &rm.wk, Wk, DM, 4096, 192);
  make_map(enc, &rm.wv, Wv, DM, 4096, 192);
  make_map(enc, &rm.wo, Wo, 4096, DM, 128);
  AMaps am;
  {
    cuuint32_t es[4] = {1, 1, 1, 1};
    cuuint64_t dx[4] = {64, 2, S_LEN / 2, 9}, sx[3] = {DM * 2, DM * 4, 128};
    cuuint32_t bx[4] = {64, 1, 64, 3};
    enc(&am.x, CU_TENSOR_MAP_DATA_TYPE_BFLOAT16, 4, (void*)x, dx, sx, bx, es, CU_TENSOR_MAP_INTERLEAVE_NONE,
        CU_TENSOR_MAP_SWIZZLE_128B, CU_TENSOR_MAP_L2_PROMOTION_L2_128B, CU_TENSOR_MAP_FLOAT_OOB_FILL_NONE);
    cuuint64_t dw[3] = {DM, DM, 3}, sw[2] = {DM * 6, DM * 2};
    cuuint32_t bw[3] = {64, 16, 3}, bt[3] = {8, 16, 3};
    enc(&am.wa, CU_TENSOR_MAP_DATA_TYPE_BFLOAT16, 3, (void*)wqkvA, dw, sw, bw, es, CU_TENSOR_MAP_INTERLEAVE_NONE,
        CU_TENSOR_MAP_SWIZZLE_128B, CU_TENSOR_MAP_L2_PROMOTION_L2_128B, CU_TENSOR_MAP_FLOAT_OOB_FILL_NONE);
    enc(&am.wt, CU_TENSOR_MAP_DATA_TYPE_BFLOAT16, 3, (void*)wqkvA, dw, sw, bt, es, CU_TENSOR_MAP_INTERLEAVE_NONE,
        CU_TENSOR_MAP_SWIZZLE_NONE, CU_TENSOR_MAP_L2_PROMOTION_NONE, CU_TENSOR_MAP_FLOAT_OOB_FILL_NONE);
    cuuint64_t dz[3] = {KCAT, 2, S_LEN / 2}, sz[2] = {KCAT * 2, KCAT * 4};
    cuuint32_t bz[3] = {72, 1, 57};
    enc(&am.oa, CU_TENSOR_MAP_DATA_TYPE_BFLOAT16, 3, pO, dz, sz, bz, es, CU_TENSOR_MAP_INTERLEAVE_NONE,
        CU_TENSOR_MAP_SWIZZLE_NONE, CU_TENSOR_MAP_L2_PROMOTION_NONE, CU_TENSOR_MAP_FLOAT_OOB_FILL_NONE);
  }
  {
    cuuint64_t dims[3] = {64, S_LEN, KCAT / 64}, strides[2] = {KCAT * 2, 128};
    cuuint32_t box[3] = {64, 32, 9}, es[3] = {1, 1, 1};
    make_map(enc, &am.o, pO, S_LEN, KCAT, 32);
    enc(&am.o3, CU_TENSOR_MAP_DATA_TYPE_BFLOAT16, 3, pO, dims, strides, box, es, CU_TENSOR_MAP_INTERLEAVE_NONE,
        CU_TENSOR_MAP_SWIZZLE_128B, CU_TENSOR_MAP_L2_PROMOTION_L2_128B, CU_TENSOR_MAP_FLOAT_OOB_FILL_NONE);
  }
  make_map(enc, &am.wob, Wo, 4096, DM, 64);
  make_map(enc, &am.woa, woA, DM, DM, 64);
  make_map(enc, &am.wo8, woA, DM, DM, 8);
  {
    cuuint64_t dims[2] = {KCAT, S_LEN}, strides[1] = {KCAT * 2};
    cuuint32_t box[2] = {8, 32}, es[2] = {1, 1};
    enc(&am.o8, CU_TENSOR_MAP_DATA_TYPE_BFLOAT16, 2, pO, dims, strides, box, es, CU_TENSOR_MAP_INTERLEAVE_NONE,
        CU_TENSOR_MAP_SWIZZLE_NONE, CU_TENSOR_MAP_L2_PROMOTION_NONE, CU_TENSOR_MAP_FLOAT_OOB_FILL_NONE);
  }

  rec_kernel<<<96, 384, SM_TOTAL, cudaStreamPerThread>>>(rm, x, mem0);
  cudaLaunchConfig_t cfg = {};
  cfg.gridDim = dim3(NAUX); cfg.blockDim = dim3(512); cfg.dynamicSmemBytes = A_TOTAL; cfg.stream = cudaStreamPerThread;
  cudaLaunchAttribute at[1];
  at[0].id = cudaLaunchAttributeProgrammaticStreamSerialization; at[0].val.programmaticStreamSerializationAllowed = 1;
  cfg.attrs = at; cfg.numAttrs = 1;
  if (XP & 16) cfg.numAttrs = 0;
  if (!(XP & 64)) cudaLaunchKernelEx(&cfg, aux_kernel, am, wqkvA, woA, gate_w, (bf16*)d_out);
}
```

```cpp
#include <cuda_runtime.h>
#include <cuda_bf16.h>
#include <cuda_fp16.h>
#include <cuda.h>
#include <stdint.h>

typedef __nv_bfloat16 bf16;

constexpr int S_LEN = 2048, DM = 576, NH = 32, DH = 128, NSEG = 64, KCAT = 4096 + 576;
constexpr int NAUXSEG = NSEG - 2;
constexpr int NAUX = 36;
#define RED_LINE(i) (((i) >> 2) * 4096 + ((i) & 1) * 256 + ((i) & 2) * 512)
#define RED_SLOT(s) (((s) & 1) * 128 + ((s) & 2) * 256)

#define POLL_NS 896
#define NII 18
#define W3PRE 4
#define W3MID 4
#define GF 0
#define B5POS 0
#define NUP 4
#define UPF 1
#define B3Q 9
#define B3F 0
#define GATE 7
#define NTL 2
#define B7R 1
#define VS0 1
#define VS1 0
#define VLATE(w) ((w) == 0 ? VS0 == 1 : (w) == 1 ? VS1 == 1 : false)
#define HOIST 1
#define RSLOW 0
#define CSY 0
#define DD 2
#define N12 18
#define N14 18
#define HP 0
#define HL 0
#define WL 1
#define RV 3
#define RET 1
#define TL 6
#define CLR 1
#define RFW 0
#define NIC 0
#define LEAD 0
#define FIN16 1
#define VXG 0
#define NRING 20
#define EXD 0
#define HDLY 0
#define F10 1
#define NPROBE 2
#define QM 0
#define N5 224
#define KP(i) (((i) >> 1) + 4 * ((i) & 1))
#define SPIN_LIMIT (1 << 14)
#define XP 0

__device__ __align__(1024) bf16 g_Ocat[S_LEN * KCAT];
__device__ __align__(1024) unsigned char g_red_raw[2 * 262144];
constexpr int HINT_OFF = 2048;
__device__ __align__(16) float g_gate[S_LEN];
__device__ __align__(128) uint4 g_stats[96 * 2];
__device__ unsigned g_epoch;
__device__ unsigned g_epoch2;
__device__ unsigned g_ocnt[NSEG * 64];
__device__ unsigned g_abar[3 * 32];
__device__ unsigned long long g_amax[2 * 16];
__device__ unsigned g_scnt[NSEG * 32 * 8];
__device__ __align__(1024) unsigned char g_seg[NRING * 96 * 10240];
__device__ unsigned g_used[NH * 32];
__device__ __align__(1024) uint2 g_part[8 * 9 * 64 * 64];
__device__ int g_err;
#define TSTAMP(i)
#define PROF(idx)
#define PROFP(idx)
#define RSTAMP(k)
#define STAMP(idx)
#define ASTAMP(idx)
#define SSTAMP(k, seg)
#define WSTAMP(idx)

#define DI __device__ __forceinline__
DI uint32_t smem_u32(const void* p) { return (uint32_t)__cvta_generic_to_shared(p); }
DI uint32_t clock32() { uint32_t c; asm volatile("mov.u32 %0, %%clock;" : "=r"(c) :: "memory"); return c; }
DI uint32_t gtime() { uint32_t c; asm volatile("mov.u32 %0, %%globaltimer_lo;" : "=r"(c) :: "memory"); return c; }
DI uint32_t ldg_relaxed32(const void* p) { uint32_t v; asm volatile("ld.relaxed.gpu.global.b32 %0, [%1];" : "=r"(v) : "l"(p) : "memory"); return v; }
DI uint32_t ldg_acquire32(const void* p) { uint32_t v; asm volatile("ld.acquire.gpu.global.b32 %0, [%1];" : "=r"(v) : "l"(p) : "memory"); return v; }
DI void stg_relaxed32(void* p, uint32_t v) { asm volatile("st.relaxed.gpu.global.b32 [%0], %1;" :: "l"(p), "r"(v) : "memory"); }
DI int head_id() { int c; asm volatile("mov.u32 %0, %%clusterid.x;" : "=r"(c)); return c; }
DI uint32_t mapa(uint32_t a, uint32_t r) { uint32_t o; asm("mapa.shared::cluster.u32 %0, %1, %2;" : "=r"(o) : "r"(a), "r"(r)); return o; }
DI void cluster_arrive() { asm volatile("barrier.cluster.arrive.relaxed.aligned;" ::: "memory"); }
DI void cluster_wait() { asm volatile("barrier.cluster.wait.aligned;" ::: "memory"); }
DI void cluster_sync() { asm volatile("barrier.cluster.arrive.release.aligned;\nbarrier.cluster.wait.acquire.aligned;" ::: "memory"); }
DI void mbar_init(uint32_t b, uint32_t c) { asm volatile("mbarrier.init.shared::cta.b64 [%0], %1;" :: "r"(b), "r"(c) : "memory"); }
DI void mbar_expect(uint32_t b, uint32_t tx) { asm volatile("mbarrier.arrive.expect_tx.shared::cta.b64 _, [%0], %1;" :: "r"(b), "r"(tx) : "memory"); }
DI void mbar_arrive(uint32_t b) { asm volatile("mbarrier.arrive.shared::cta.b64 _, [%0];" :: "r"(b) : "memory"); }
DI void mbar_wait(uint32_t b, uint32_t par) {
  asm volatile("{\n.reg .pred p;\n.reg .u32 n, q;\nmov.u32 n, 0;\n"
               "WL: add.u32 n, n, 1;\nshr.u32 q, n, 12;\nxor.b32 q, q, %1;\n"
               "mbarrier.try_wait.parity.shared::cta.b64 p, [%0], q;\n@!p bra.uni WL;\n}"
               :: "r"(b), "r"(par) : "memory");
}
DI bool mbar_test(uint32_t b, uint32_t par) {
  uint32_t r;
  asm volatile("{\n.reg .pred p;\nmbarrier.test_wait.parity.shared::cta.b64 p, [%1], %2;\nselp.u32 %0, 1, 0, p;\n}" : "=r"(r) : "r"(b), "r"(par) : "memory");
  return r;
}
DI void mbar_wait_fast(uint32_t b, uint32_t par) {
  asm volatile("{\n.reg .pred p;\n.reg .u32 n, q;\nmbarrier.try_wait.parity.shared::cta.b64 p, [%0], %1;\n@p bra.uni WD;\nmov.u32 n, 0;\n"
               "WL: add.u32 n, n, 1;\nshr.u32 q, n, 12;\nxor.b32 q, q, %1;\n"
               "mbarrier.try_wait.parity.shared::cta.b64 p, [%0], q;\n@!p bra.uni WL;\nWD:\n}"
               :: "r"(b), "r"(par) : "memory");
}
DI void wait_until(uint32_t t) {
  const uint32_t now = gtime();
  t = min(t, now + 8192);
  asm volatile("{\n.reg .pred p;\n.reg .u32 c;\nTL: mov.u32 c, %%globaltimer_lo;\nsetp.lt.u32 p, c, %0;\n@p bra.uni TL;\n}" :: "r"(t) : "memory");
}
#define PIN(v) v = __shfl_xor_sync(0xffffffffu, v, 0)
#define SCHED_FENCE(k) asm volatile("{\n.reg .pred p;\nsetp.eq.u32 p, %0, %1;\n@p exit;\n}" :: "r"(fence_reg), "r"(k) : "memory")
#define MEM_ORDER(k) asm volatile("{\n.reg .pred p;\nsetp.eq.u32 p, %0, %1;\n@p st.shared.u32 [%0], %0;\n}" :: "r"(fence_reg), "r"(k + 64) : "memory")
DI void bar_sync(int id, int n) { asm volatile("bar.sync %0, %1;" :: "r"(id), "r"(n) : "memory"); }
DI void bar_arrive(int id, int n) { asm volatile("bar.arrive %0, %1;" :: "r"(id), "r"(n) : "memory"); }
DI void fence_async() { asm volatile("fence.proxy.async.shared::cta;" ::: "memory"); }
DI void st_async4(uint32_t a, uint32_t x, uint32_t y, uint32_t z, uint32_t w, uint32_t mb) {
  asm volatile("st.async.weak.shared::cluster.mbarrier::complete_tx::bytes.v4.b32 [%0], {%1,%2,%3,%4}, [%5];"
               :: "r"(a), "r"(x), "r"(y), "r"(z), "r"(w), "r"(mb) : "memory");
}
DI void st_async2(uint32_t a, uint32_t x, uint32_t y, uint32_t mb) {
  asm volatile("st.async.weak.shared::cluster.mbarrier::complete_tx::bytes.v2.b32 [%0], {%1,%2}, [%3];"
               :: "r"(a), "r"(x), "r"(y), "r"(mb) : "memory");
}
DI void sts32(uint32_t a, uint32_t x) { asm volatile("st.shared.b32 [%0], %1;" :: "r"(a), "r"(x) : "memory"); }
DI void sts64(uint32_t a, uint32_t x, uint32_t y) { asm volatile("st.shared.v2.b32 [%0], {%1,%2};" :: "r"(a), "r"(x), "r"(y) : "memory"); }
DI void sts128(uint32_t a, uint32_t x, uint32_t y, uint32_t z, uint32_t w) {
  asm volatile("st.shared.v4.b32 [%0], {%1,%2,%3,%4};" :: "r"(a), "r"(x), "r"(y), "r"(z), "r"(w) : "memory");
}
DI uint32_t lds32(uint32_t a) { uint32_t x; asm volatile("ld.shared.b32 %0, [%1];" : "=r"(x) : "r"(a) : "memory"); return x; }
DI void lds64(uint32_t a, uint32_t& x, uint32_t& y) { asm volatile("ld.shared.v2.b32 {%0,%1}, [%2];" : "=r"(x), "=r"(y) : "r"(a) : "memory"); }
DI void lds128(uint32_t a, uint32_t* r) {
  asm volatile("ld.shared.v4.b32 {%0,%1,%2,%3}, [%4];" : "=r"(r[0]), "=r"(r[1]), "=r"(r[2]), "=r"(r[3]) : "r"(a) : "memory");
}
DI void lds128f(uint32_t a, float* r) {
  asm volatile("ld.shared.v4.f32 {%0,%1,%2,%3}, [%4];" : "=f"(r[0]), "=f"(r[1]), "=f"(r[2]), "=f"(r[3]) : "r"(a) : "memory");
}
DI void lds64f(uint32_t a, float* r) { asm volatile("ld.shared.v2.f32 {%0,%1}, [%2];" : "=f"(r[0]), "=f"(r[1]) : "r"(a) : "memory"); }
DI void ldsm4t(uint32_t* r, uint32_t a) {
  asm volatile("ldmatrix.sync.aligned.m8n8.x4.trans.shared.b16 {%0,%1,%2,%3}, [%4];"
               : "=r"(r[0]), "=r"(r[1]), "=r"(r[2]), "=r"(r[3]) : "r"(a) : "memory");
}
DI void ldsm4t_in(uint32_t* r, uint32_t a, uint32_t t) {
  asm volatile("{\n.reg .pred p;\nsetp.ne.u32 p, %5, 0;\n@p ldmatrix.sync.aligned.m8n8.x4.trans.shared.b16 {%0,%1,%2,%3}, [%4];\n}"
               : "+r"(r[0]), "+r"(r[1]), "+r"(r[2]), "+r"(r[3]) : "r"(a), "r"(t) : "memory");
}
DI void lds128_in(uint32_t* r, uint32_t a, uint32_t t) {
  asm volatile("{\n.reg .pred p;\nsetp.ne.u32 p, %5, 0;\n@p ld.shared.v4.b32 {%0,%1,%2,%3}, [%4];\n}"
               : "+r"(r[0]), "+r"(r[1]), "+r"(r[2]), "+r"(r[3]) : "r"(a), "r"(t) : "memory");
}
DI void ldsm2t_in(uint32_t* r, uint32_t a, uint32_t t) {
  asm volatile("{\n.reg .pred p;\nsetp.ne.u32 p, %3, 0;\n@p ldmatrix.sync.aligned.m8n8.x2.trans.shared.b16 {%0,%1}, [%2];\n}" : "+r"(r[0]), "+r"(r[1]) : "r"(a), "r"(t) : "memory");
}
DI void reserve2(uint32_t* r) { asm volatile("{\n.reg .u64 t;\nmov.u64 t, %%clock64;\nmov.b64 {%0, %1}, t;\n}" : "=r"(r[0]), "=r"(r[1])); }
DI void scale_sum(float& x, float& y, float s, uint32_t t) {
  asm volatile("{\n.reg .pred p;\nsetp.ne.u32 p, %2, 0;\n@p mul.f32 %0, %0, %1;\n}" : "+f"(y) : "f"(s), "r"(t));
  asm volatile("{\n.reg .pred p;\nsetp.ne.u32 p, %3, 1;\n@p fma.rn.f32 %0, %0, %1, %2;\n}" : "+f"(x) : "f"(s), "f"(y), "r"(t));
}
DI void ldsm4(uint32_t* r, uint32_t a) {
  asm volatile("ldmatrix.sync.aligned.m8n8.x4.shared.b16 {%0,%1,%2,%3}, [%4];"
               : "=r"(r[0]), "=r"(r[1]), "=r"(r[2]), "=r"(r[3]) : "r"(a) : "memory");
}
DI void st_async1(uint32_t a, uint32_t x, uint32_t mb) {
  asm volatile("st.async.weak.shared::cluster.mbarrier::complete_tx::bytes.b32 [%0], %1, [%2];" :: "r"(a), "r"(x), "r"(mb) : "memory");
}
DI void stsm4(uint32_t a, uint32_t x, uint32_t y, uint32_t z, uint32_t w) {
  asm volatile("stmatrix.sync.aligned.m8n8.x4.shared.b16 [%0], {%1,%2,%3,%4};" :: "r"(a), "r"(x), "r"(y), "r"(z), "r"(w) : "memory");
}
DI void stsm4t(uint32_t a, uint32_t x, uint32_t y, uint32_t z, uint32_t w) {
  asm volatile("stmatrix.sync.aligned.m8n8.x4.trans.shared.b16 [%0], {%1,%2,%3,%4};" :: "r"(a), "r"(x), "r"(y), "r"(z), "r"(w) : "memory");
}
DI uint32_t pack_bf16(float lo, float hi) { uint32_t r; asm("cvt.rn.bf16x2.f32 %0, %1, %2;" : "=r"(r) : "f"(hi), "f"(lo)); return r; }
DI uint32_t pack_f16(float lo, float hi) { uint32_t r; asm("cvt.rn.f16x2.f32 %0, %1, %2;" : "=r"(r) : "f"(hi), "f"(lo)); return r; }
DI float ex2(float x) { float y; asm("ex2.approx.ftz.f32 %0, %1;" : "=f"(y) : "f"(x)); return y; }
DI float rcp(float x) { float y; asm("rcp.approx.ftz.f32 %0, %1;" : "=f"(y) : "f"(x)); return y; }
DI float bf_lo(uint32_t x) { return __uint_as_float(x << 16); }
DI float bf_hi(uint32_t x) { return __uint_as_float(x & 0xffff0000u); }
DI void mma16816(float* d, const uint32_t* a, uint32_t b0, uint32_t b1) {
  asm volatile("mma.sync.aligned.m16n8k16.row.col.f32.bf16.bf16.f32 {%0,%1,%2,%3}, {%4,%5,%6,%7}, {%8,%9}, {%0,%1,%2,%3};"
               : "+f"(d[0]), "+f"(d[1]), "+f"(d[2]), "+f"(d[3]) : "r"(a[0]), "r"(a[1]), "r"(a[2]), "r"(a[3]), "r"(b0), "r"(b1));
}
DI void mma16816z(float* d, const uint32_t* a, uint32_t b0, uint32_t b1) {
  asm volatile("mma.sync.aligned.m16n8k16.row.col.f32.bf16.bf16.f32 {%0,%1,%2,%3}, {%4,%5,%6,%7}, {%8,%9}, {%10,%10,%10,%10};"
               : "=f"(d[0]), "=f"(d[1]), "=f"(d[2]), "=f"(d[3]) : "r"(a[0]), "r"(a[1]), "r"(a[2]), "r"(a[3]), "r"(b0), "r"(b1), "f"(0.f));
}
DI void mma1688z(float* d, uint32_t a0, uint32_t a1, uint32_t b0) {
  asm volatile("mma.sync.aligned.m16n8k8.row.col.f32.bf16.bf16.f32 {%0,%1,%2,%3}, {%4,%5}, {%6}, {%7,%7,%7,%7};"
               : "=f"(d[0]), "=f"(d[1]), "=f"(d[2]), "=f"(d[3]) : "r"(a0), "r"(a1), "r"(b0), "f"(0.f));
}
DI void mma1688(float* d, uint32_t a0, uint32_t a1, uint32_t b0) {
  asm volatile("mma.sync.aligned.m16n8k8.row.col.f32.bf16.bf16.f32 {%0,%1,%2,%3}, {%4,%5}, {%6}, {%0,%1,%2,%3};"
               : "+f"(d[0]), "+f"(d[1]), "+f"(d[2]), "+f"(d[3]) : "r"(a0), "r"(a1), "r"(b0));
}
DI void ldsm2t(uint32_t* r, uint32_t a) {
  asm volatile("ldmatrix.sync.aligned.m8n8.x2.trans.shared.b16 {%0,%1}, [%2];" : "=r"(r[0]), "=r"(r[1]) : "r"(a) : "memory");
}
DI uint32_t add_bf16(uint32_t a, uint32_t b) { uint32_t r; asm("add.rn.bf16x2 %0, %1, %2;" : "=r"(r) : "r"(a), "r"(b)); return r; }
DI uint32_t mul_bf16(uint32_t a, uint32_t b) { uint32_t r; asm("mul.rn.bf16x2 %0, %1, %2;" : "=r"(r) : "r"(a), "r"(b)); return r; }
DI uint64_t make_desc(uint32_t addr, uint32_t lbo, uint32_t sbo, uint32_t swz) {
  return (uint64_t)((addr & 0x3FFFF) >> 4) | ((uint64_t)(lbo >> 4) << 16) | ((uint64_t)(sbo >> 4) << 32) | ((uint64_t)swz << 62);
}
DI uint64_t desc_at(uint32_t a16, uint32_t lbo, uint32_t sbo, uint32_t swz) {
  uint64_t d; asm("mov.b64 %0, {%1, %2};" : "=l"(d) : "r"(a16 + ((lbo >> 4) << 16)), "r"((sbo >> 4) | (swz << 30)));
  return d;
}
#define WG_FENCE() asm volatile("wgmma.fence.sync.aligned;" ::: "memory")
#define WG_COMMIT() asm volatile("wgmma.commit_group.sync.aligned;" ::: "memory")
#define WG_WAIT(n) asm volatile("wgmma.wait_group.sync.aligned %0;" :: "n"(n) : "memory")
#define ACC8(d, o) "+f"(d[o]), "+f"(d[o + 1]), "+f"(d[o + 2]), "+f"(d[o + 3]), "+f"(d[o + 4]), "+f"(d[o + 5]), "+f"(d[o + 6]), "+f"(d[o + 7])
DI void wgmma_n32_rs(float* d, uint32_t a0, uint32_t a1, uint32_t a2, uint32_t a3, uint64_t db, int acc) {
  asm volatile("{\n.reg .pred p;\nsetp.ne.b32 p, %21, 0;\n"
               "wgmma.mma_async.sync.aligned.m64n32k16.f32.bf16.bf16 {%0,%1,%2,%3,%4,%5,%6,%7,%8,%9,%10,%11,%12,%13,%14,%15}, "
               "{%16,%17,%18,%19}, %20, p, 1, 1, 0;\n}\n"
               : ACC8(d, 0), ACC8(d, 8) : "r"(a0), "r"(a1), "r"(a2), "r"(a3), "l"(db), "r"(acc));
}
template <int TA>
DI void wgmma_n32_ss(float* d, uint64_t da, uint64_t db, int acc) {
  asm volatile("{\n.reg .pred p;\nsetp.ne.b32 p, %18, 0;\n"
               "wgmma.mma_async.sync.aligned.m64n32k16.f32.bf16.bf16 {%0,%1,%2,%3,%4,%5,%6,%7,%8,%9,%10,%11,%12,%13,%14,%15}, "
               "%16, %17, p, 1, 1, %19, 1;\n}\n"
               : ACC8(d, 0), ACC8(d, 8) : "l"(da), "l"(db), "r"(acc), "n"(TA));
}
DI void tma_load(uint32_t dst, const CUtensorMap* m, int c0, int c1, uint32_t mb) {
  asm volatile("cp.async.bulk.tensor.2d.shared::cluster.global.mbarrier::complete_tx::bytes [%0], [%1, {%3, %4}], [%2];"
               :: "r"(dst), "l"(m), "r"(mb), "r"(c0), "r"(c1) : "memory");
}
DI void tma_load3(uint32_t dst, const CUtensorMap* m, int row, uint32_t mb) {
  asm volatile("cp.async.bulk.tensor.3d.shared::cluster.global.mbarrier::complete_tx::bytes [%0], [%1, {%3, %4, %3}], [%2];"
               :: "r"(dst), "l"(m), "r"(mb), "r"(0), "r"(row) : "memory");
}
DI bool elect_one() {
  uint32_t p;
  asm volatile("{\n.reg .pred p;\nelect.sync _|p, 0xffffffff;\nselp.u32 %0, 1, 0, p;\n}" : "=r"(p));
  return p;
}
DI void bulk_s2s(uint32_t dst, uint32_t src, uint32_t bytes, uint32_t mb) {
  asm volatile("cp.async.bulk.shared::cluster.shared::cta.mbarrier::complete_tx::bytes [%0], [%1], %2, [%3];"
               :: "r"(dst), "r"(src), "r"(bytes), "r"(mb) : "memory");
}
DI void tma_prefetch(const CUtensorMap* m, int c0, int c1) {
  asm volatile("cp.async.bulk.prefetch.tensor.2d.L2.global.tile [%0, {%1, %2}];" :: "l"(m), "r"(c0), "r"(c1) : "memory");
}
DI void tma_store(const CUtensorMap* m, uint32_t src, int c0, int c1) {
  asm volatile("cp.async.bulk.tensor.2d.global.shared::cta.bulk_group [%0, {%2, %3}], [%1];" :: "l"(m), "r"(src), "r"(c0), "r"(c1) : "memory");
}
DI uint4 ldg_relaxed(const void* p) {
  uint4 v;
  asm volatile("ld.relaxed.gpu.global.v4.b32 {%0,%1,%2,%3}, [%4];" : "=r"(v.x), "=r"(v.y), "=r"(v.z), "=r"(v.w) : "l"(p) : "memory");
  return v;
}
DI void stg_relaxed(void* p, uint32_t x, uint32_t y, uint32_t z, uint32_t w) {
  asm volatile("st.relaxed.gpu.global.v4.b32 [%0], {%1,%2,%3,%4};" :: "l"(p), "r"(x), "r"(y), "r"(z), "r"(w) : "memory");
}
DI void red_f16x8(void* p, uint32_t x, uint32_t y, uint32_t z, uint32_t w) {
  asm volatile("red.relaxed.gpu.global.add.noftz.v4.f16x2 [%0], {%1,%2,%3,%4};" :: "l"(p), "r"(x), "r"(y), "r"(z), "r"(w) : "memory");
}
DI void sq_acc(uint32_t& a, uint32_t x) { asm("fma.rn.bf16x2 %0, %1, %1, %0;" : "+r"(a) : "r"(x)); }
DI __half2 amax4(__half2 h, const uint32_t* v) {
  h = __hmax2_nan(__hmax2_nan(h, __habs2(*(const __half2*)&v[0])), __habs2(*(const __half2*)&v[1]));
  return __hmax2_nan(__hmax2_nan(h, __habs2(*(const __half2*)&v[2])), __habs2(*(const __half2*)&v[3]));
}
DI uint32_t wexp(__half2 h) { const uint32_t u = *(const uint32_t*)&h; return __reduce_max_sync(0xffffffffu, max((u >> 16) & 0x7fffu, u & 0x7fffu)) >> 7; }
DI float max10(const float* a) {
  return fmaxf(fmaxf(fmaxf(fmaxf(a[0], a[1]), fmaxf(a[2], a[3])), fmaxf(fmaxf(a[4], a[5]), fmaxf(a[6], a[7]))), fmaxf(a[8], a[9]));
}
DI float quad_max(float m) {
  return fmaxf(fmaxf(m, __shfl_xor_sync(0xffffffffu, m, 1)), fmaxf(__shfl_xor_sync(0xffffffffu, m, 2), __shfl_xor_sync(0xffffffffu, m, 3)));
}
DI float warp_sum(float v) {
#pragma unroll
  for (int o = 16; o; o >>= 1) v += __shfl_xor_sync(0xffffffffu, v, o);
  return v;
}

constexpr int SM_WO3 = 0;
constexpr int SM_X = 16384;
constexpr int XT = 36864;
constexpr int SM_EXP = 126976;
constexpr int SEGB = 10240;
constexpr int SM_BLK = SM_EXP + 8192;
constexpr int SM_VC = SM_BLK + 4 * SEGB;
constexpr int SM_PART = SM_VC + 16384;
constexpr int SM_QM = SM_PART + 4096;
constexpr int SM_E = SM_QM + 1024;
constexpr int SM_VM = SM_E + 1536;
constexpr int SM_OB = SM_VM + 2048;
constexpr int SM_FB = SM_OB + 2048;
constexpr int SM_STAGE = SM_X + XT;
constexpr int SM_MISC = 210944;
constexpr int SM_WOST = 212992;
constexpr int SM_MEM = SM_WOST;
constexpr int SM_MAX = SM_MEM + 11264;
#define MEM_BLK(q) ((q) / 3 * 4096 + (q) % 3 * 1024)
constexpr int SM_TOTAL = 229376;
constexpr int MB_W = SM_MISC;
constexpr int MB_WO = SM_MISC + 24;
constexpr int MB_WO3 = SM_MISC + 32;
constexpr int MB_X = SM_MISC + 40;
constexpr int MB_S = SM_MISC + 64;
constexpr int MB_F = SM_MISC + 72;
constexpr int MB_VX = SM_MISC + 80;
constexpr int SC_FPAR = SM_MISC + 136;
constexpr int SC_DEAD = SM_MISC + 96;
constexpr int SC_UNSC = SM_MISC + 112;
constexpr int SC_EPOCH = SM_MISC + 128;
constexpr int SC_EXPW = SM_MISC + 132;
constexpr int SC_ONES = SM_MISC + 144;
constexpr int SC_SS = SM_MISC + 160;
constexpr int SC_LAT = SM_MISC + 224;
constexpr int MB_T = SM_MISC + 232;
constexpr int T_SX = SM_X + XT;
constexpr int T_OB = SM_X + 2 * XT;
constexpr int T_WA = T_OB + 16384;
constexpr int T_OA = T_WA + 9216;
constexpr int T_G = T_OA + 4096;
constexpr int T_P = T_G + 512;
constexpr int T_UN = T_G + 256;
constexpr int T_RED = 131072;
constexpr int SC_XMAX = SM_MISC + 256;
constexpr int SC_PROF = 229376;

constexpr float SM_SCALE = 0.08838834764831845f;
constexpr float LOG2E = 1.4426950408889634f;
constexpr float E_LIM = 20.f;

template <bool B> struct BoolC { static constexpr bool value = B; };
struct RMaps { CUtensorMap x, wq, wk, wv, wo, woa, oa; unsigned char* red; bf16* out; uint32_t poll; };

DI uint32_t latest_hint(uint32_t h, uint32_t d, int s) {
  const uint32_t x = (((h | 0xc0c0c0c0u) - ((d >> 5) & 63) * 0x01010101u) & 0x3f3f3f3fu) | ((h ^ (((s >> 2) + 1) & 3) * 0x40404040u) & 0xc0c0c0c0u);
  const uint32_t y = __vmaxu2(x & 0x00ff00ffu, (x >> 8) & 0x00ff00ffu);
  return __reduce_max_sync(0xffffffffu, max(y & 0xffffu, y >> 16));
}
DI uint32_t near_half(uint32_t sb) {
  uint32_t a, b; lds64(sb + SC_LAT, a, b);
  return a > b;
}

template <int RT, int K0, int K1, bool D32 = false, int BAR = 0, int KB = 18>
DI void xproj(float* acc, const uint32_t (&wa)[2][18][4], uint64_t xd) {
  if (XP & 1) return;
  WG_FENCE();
#pragma unroll
  for (int k = K0; k < ((XP & 128) ? K0 + 1 : K1); k++)
  {
    uint64_t d = xd + (uint64_t)(((k >> 1) * 4096 + (k & 1) * 32) >> 4);
    if (D32) asm("mov.b64 %0, {%1, %2};" : "=l"(d) : "r"((uint32_t)xd + (((k >> 1) * 4096 + (k & 1) * 32) >> 4)), "r"((uint32_t)(xd >> 32)));
    wgmma_n32_rs(acc, wa[RT][k][0], wa[RT][k][1], wa[RT][k][2], wa[RT][k][3], d, k != 0);
    if (BAR && k == KB - 1 && KB < 18) bar_arrive(BAR, 256);
  }
  WG_COMMIT();
}

DI void seg_store(int seg, uint32_t sb, uint32_t off, uint32_t bytes) {
  asm volatile("cp.async.bulk.global.shared::cta.bulk_group [%0], [%1], %2;"
               :: "l"(g_seg + ((size_t)(seg % NRING) * 96 + blockIdx.x) * SEGB + off), "r"(sb + SM_BLK + (seg & 3) * SEGB + off), "r"(bytes) : "memory");
  asm volatile("cp.async.bulk.commit_group;" ::: "memory");
}
DI void seg_publish(int seg) {
  asm volatile("cp.async.bulk.wait_group 0;" ::: "memory");
  asm volatile("red.relaxed.gpu.global.add.u32 [%0], 1;" :: "l"(&g_scnt[(seg * 32 + blockIdx.x / 3) * 8]) : "memory");
  SSTAMP(10, seg);
}

#define NAP 64
DI uint32_t movm(uint32_t x) { uint32_t r; asm volatile("movmatrix.sync.aligned.m8n8.trans.b16 %0, %1;" : "=r"(r) : "r"(x)); return r; }
DI bool wait_count(const unsigned* p, unsigned target, bool nap = true) {
  int n = 0;
  unsigned v;
  while (true) {
    asm volatile("ld.acquire.gpu.global.b32 %0, [%1];" : "=r"(v) : "l"(p) : "memory");
    if ((int)(v - target) >= 0 || ++n > SPIN_LIMIT) break;
    if (nap) __nanosleep(NAP);
  }
  return n;
}
#define PACE 1200
#define PORD 0
DI void load_weights(uint32_t sb, const RMaps& tm, uint32_t rank, int c) {
  const int h = blockIdx.x / 3;
  if (c < 3) {
    mbar_expect(sb + MB_W + 8 * c, 49152);
    tma_load(sb + SM_STAGE + c * 49152, rank < 2 ? &tm.wk : &tm.wv, h * DH + (rank == 1 ? 64 : 0), c * 192, sb + MB_W + 8 * c);
    tma_load(sb + SM_STAGE + c * 49152 + 24576, rank < 2 ? &tm.wq : &tm.wv, h * DH + (rank == 0 ? 0 : 64), c * 192, sb + MB_W + 8 * c);
  } else {
    tma_prefetch(&tm.wo, rank * 192, h * DH);
    mbar_expect(sb + MB_WO, 16384);
    mbar_expect(sb + MB_WO3, 32768);
    tma_load(sb + SM_WOST, &tm.wo, rank * 192 + 64, h * DH, sb + MB_WO3);
    tma_load(sb + SM_WO3, &tm.wo, rank * 192 + 128, h * DH, sb + MB_WO3);
  }
}

DI void tail_attention(const uint32_t sb, const uint32_t rank, const int w, const int lane, const int sg, const int bar) {
  const int m = lane >> 3, g = lane >> 2, t = lane & 3;
  const uint32_t l16 = sb + lane * 16, src = l16 + T_SX + sg * 10240 + w * 1280;
  if (rank < 2) {
    const uint32_t base = l16 + SM_BLK + (2 + sg) * SEGB, dst = src + rank * 5120;
    uint32_t qb[2][4];
    ldsm4t(qb[0], base + w * 1024); ldsm4t(qb[1], base + w * 1024 + 512);
#pragma unroll
    for (int j = 0; j < 3; j++) {
      uint32_t kb[4][4];
      float c[4][4];
      const uint32_t ka = base + 4096 + j * 2048 + (m & 1) * (j == 2 ? 128 : 896) - (m >> 1) * 128;
#pragma unroll
      for (int k = 0; k < 4; k += j == 2 ? 2 : 1) ldsm4t(kb[k], ka + k * 256);
      mma16816z(c[0], kb[0], qb[0][0], qb[0][1]); mma16816z(c[1], kb[j == 2 ? 0 : 1], qb[0][2], qb[0][3]);
      mma16816z(c[2], kb[2], qb[1][0], qb[1][1]); mma16816z(c[3], kb[j == 2 ? 2 : 3], qb[1][2], qb[1][3]);
      uint32_t r[4];
#pragma unroll
      for (int i = 0; i < (j == 2 ? 2 : 4); i++) r[i] = __float_as_uint((c[0][i] + c[1][j == 2 ? i + 2 : i]) + (c[2][i] + c[3][j == 2 ? i + 2 : i]));
#pragma unroll
      for (int d = 0; d < 2; d++) {
        const uint32_t to = d ? 2 : rank ^ 1, mb = mapa(sb + MB_T + 8 + 8 * sg, to);
        if (j < 2) st_async4(mapa(dst + j * 512, to), r[0], r[1], r[2], r[3], mb);
        else st_async2(mapa(dst + 1024 - lane * 8, to), r[0], r[1], mb);
      }
      if (j < 2) sts128(dst + j * 512, r[0], r[1], r[2], r[3]); else sts64(dst + 1024 - lane * 8, r[0], r[1]);
    }
  }
  TSTAMP(50 + 2 * sg);
  uint32_t vx[4][4], vm[4];
  const uint32_t va = l16 + (rank < 2 ? SM_VC + sg * 8192 : SM_BLK + (2 + sg) * SEGB) + w * 1024 + (m & 1) * 384 - (m >> 1) * 128;
#pragma unroll
  for (int i = 0; i < 4; i++) ldsm4(vx[i], va + (i & 1) * 4096 + (i >> 1) * 256);
  if (sg && rank < 2) mbar_wait(sb + MB_T, 0);
  lds128(l16 + (sg ? SM_FB : SM_VM) + w * 512, vm);
  float a[10], b[10];
  mbar_wait(sb + MB_T + 8 + 8 * sg, 0);
  TSTAMP(58 + 2 * sg);
  lds128f(src, a); lds128f(src + 512, a + 4); lds64f(src + 1024 - lane * 8, a + 8);
  lds128f(src + 5120, b); lds128f(src + 5632, b + 4); lds64f(src + 6144 - lane * 8, b + 8);
#pragma unroll
  for (int i = 0; i < 10; i++) {
    a[i] = (a[i] + b[i]) * (SM_SCALE * LOG2E);
    if (i < 8 && (i >> 1) * 8 + g > w * 8 + 2 * t + (i & 1)) a[i] = -1.0e9f * LOG2E;
  }
  float m0 = fmaxf(fmaxf(fmaxf(a[0], a[2]), fmaxf(a[4], a[6])), a[8]), m1 = fmaxf(fmaxf(fmaxf(a[1], a[3]), fmaxf(a[5], a[7])), a[9]);
#pragma unroll
  for (int o = 4; o < 32; o <<= 1) { m0 = fmaxf(m0, __shfl_xor_sync(0xffffffffu, m0, o)); m1 = fmaxf(m1, __shfl_xor_sync(0xffffffffu, m1, o)); }
#pragma unroll
  for (int i = 0; i < 10; i++) a[i] = ex2(a[i] - (i & 1 ? m1 : m0));
  float s0 = ((a[0] + a[2]) + (a[4] + a[6])) + a[8], s1 = ((a[1] + a[3]) + (a[5] + a[7])) + a[9];
#pragma unroll
  for (int o = 4; o < 32; o <<= 1) { s0 += __shfl_xor_sync(0xffffffffu, s0, o); s1 += __shfl_xor_sync(0xffffffffu, s1, o); }
  s0 = rcp(s0); s1 = rcp(s1);
#pragma unroll
  for (int i = 0; i < 5; i++) sts32(sb + T_P + sg * 2560 + w * 640 + i * 128 + lane * 4, pack_bf16(a[2 * i] * s0, a[2 * i + 1] * s1));
  mbar_wait(sb + MB_WO, 1);
  bar_sync(bar, 128);
  TSTAMP(59 + 2 * sg);
#pragma unroll
  for (int j = 0; j < 4; j++) {
    uint32_t p[5];
    float o0[4], o1[4], f[2];
    lds64f(sb + T_G + sg * 128 + j * 32 + t * 8, f);
    f[0] = 1.f - f[0]; f[1] = 1.f - f[1];
    ldsm4t(p, l16 + T_P + sg * 2560 + j * 640);
    asm volatile("ldmatrix.sync.aligned.m8n8.x1.trans.shared.b16 {%0}, [%1];" : "=r"(p[4]) : "r"(l16 + T_P + sg * 2560 + j * 640 + 512) : "memory");
    mma16816z(o0, vx[0], p[0], p[1]); mma16816z(o1, vx[1], p[0], p[1]);
    mma16816(o0, vx[2], p[2], p[3]); mma16816(o1, vx[3], p[2], p[3]);
    mma1688(o0, vm[0], vm[1], p[4]); mma1688(o1, vm[2], vm[3], p[4]);
    stsm4(l16 + T_OB + sg * 8192 + j * 2048 + w * 512, pack_bf16(o0[0] * f[0], o0[1] * f[1]), pack_bf16(o0[2] * f[0], o0[3] * f[1]),
          pack_bf16(o1[0] * f[0], o1[1] * f[1]), pack_bf16(o1[2] * f[0], o1[3] * f[1]));
  }
}

DI void proj_role(const uint32_t sb, const RMaps& tm, const uint32_t rank, const int wg, const int w, const int lane) {
  const bool qk = rank < 2;
  uint32_t wa[2][18][4];
  {
    const int rr = (lane & 7) + ((lane >> 4) << 3);
    const uint32_t col = ((2 * w + ((lane >> 3) & 1)) ^ (lane & 7)) << 4;
    float ss = 0.f;
#pragma unroll
    for (int c = 0; c < 3; c++) {
      mbar_wait(sb + MB_W + 8 * c, 0);
      if (threadIdx.x == 0) SSTAMP(11, c);
#pragma unroll
      for (int rt = 0; rt < 2; rt++)
#pragma unroll
        for (int k = 0; k < 6; k++)
          ldsm4t(wa[rt][c * 6 + k], sb + SM_STAGE + c * 49152 + (rt ^ wg) * 24576 + (64 * (k >> 1) + 32 * wg + 16 * (k & 1) + rr) * 128 + col);
      if (c < 2) {
        fence_async();
        bar_sync(3, 256);
        if (threadIdx.x == 0) {
          if (c == 0) tma_load3(sb + SM_X + XT, &tm.x, 32, sb + MB_X + 8);
          else { tma_load(sb + SM_X + 2 * XT, &tm.wo, rank * 192, (blockIdx.x / 3) * DH, sb + MB_WO); SSTAMP(11, 11); }
        }
        __syncwarp();
      }
      uint32_t q[4] = {0, 0, 0, 0};
#pragma unroll
      for (int rt = 0; rt < 2; rt++)
#pragma unroll
        for (int k = 0; k < 6; k++)
#pragma unroll
          for (int i = 0; i < 4; i++) sq_acc(q[i], wa[rt][c * 6 + k][i]);
#pragma unroll
      for (int i = 0; i < 4; i++) ss += bf_lo(q[i]) + bf_hi(q[i]);
    }
    ss = warp_sum(ss);
    fence_async();
    cluster_arrive();
    if (lane == 0) sts32(sb + SC_SS + 4 * (wg * 4 + w), qk ? 0 : __float_as_uint(ss));
    bar_arrive(11, 384);
  }
  STAMP(1);
  mbar_wait(sb + MB_X, 0);
  STAMP(2);

  uint32_t t16 = sb + (w * 32 + lane) * 16;
  uint32_t mem_a = sb + SM_MEM + wg * 512 + lane * 16;
  uint32_t fin_a = sb + (lane & 7) * 16 + SM_BLK + (qk ? (wg ^ 1) * 4096 + w * 256 + (lane & 8) * 16 + (lane & 16) * 64
                                              : wg * 4096 + w * 1024 + (lane & 8) * 64 + (lane & 16) * 8);
  PIN(t16); PIN(mem_a); PIN(fin_a);
  const uint32_t fence_reg = mem_a;
  const uint32_t fin2 = qk ? 2048 : 256;
  float acc[16];
  const uint64_t xd0 = make_desc(sb + SM_X + wg * 64, 16, 1024, 1);
  auto do_export = [&]() {
    WG_WAIT(0);
    uint32_t q[8];
#pragma unroll
    for (int j = 0; j < 8; j++) q[j] = pack_bf16(acc[2 * j], acc[2 * j + 1]);
    sts128(t16 + SM_EXP + wg * 4096, q[0], q[1], q[2], q[3]);
    sts128(t16 + SM_EXP + wg * 4096 + 2048, q[4], q[5], q[6], q[7]);
    if (RET) asm volatile("{\n.reg .pred p;\nsetp.eq.u32 p, %2, 0;\n@p add.u32 %0, %0, 1;\n@p add.u32 %1, %1, 1;\nsetp.eq.and.u32 p, %0, %1, p;\n@p exit;\n}"
                          : "+r"(q[3]), "+r"(q[7]) : "r"(t16) : "memory");
  };
  uint32_t o[8];
  auto import = [&]() { lds128(t16 + SM_EXP + (wg ^ 1) * 4096, o); lds128(t16 + SM_EXP + (wg ^ 1) * 4096 + 2048, o + 4); };
  auto finish = [&](int seg) {
    const uint32_t a = fin_a + (seg & 3) * SEGB;
    WG_WAIT(0);
#pragma unroll
    for (int i = 0; i < 8; i++) o[i] = FIN16 ? add_bf16(pack_bf16(acc[2 * i], acc[2 * i + 1]), o[i]) : pack_bf16(acc[2 * i] + bf_lo(o[i]), acc[2 * i + 1] + bf_hi(o[i]));
    stsm4(a, o[0], o[1], o[2], o[3]);
    stsm4(a + fin2, o[4], o[5], o[6], o[7]);
  };
  auto send_v = [&](int seg, int dst) {
    fence_async();
    if (seg < NSEG && !(XP & 2) && elect_one())
      bulk_s2s(mapa(sb + SM_VC + (seg & 1) * 8192, dst), sb + SM_BLK + (seg & 3) * SEGB, 8192, mapa(sb + MB_VX + (seg & 1) * 8, dst));
    __syncwarp();
  };
  auto wait_v = [&](int seg) {
    if (seg < NSEG && !(XP & 2)) {
      mbar_wait(sb + MB_VX + (seg & 1) * 8, (seg >> 1) & 1);
      if (elect_one()) mbar_expect(sb + MB_VX + (seg & 1) * 8, 8192);
      __syncwarp();
    }
  };
  bar_sync(3, 256);
  xproj<1, 0, 18>(acc, wa, xd0);
  do_export();
  SCHED_FENCE(11);
  xproj<0, 0, 18>(acc, wa, xd0);
  bar_sync(3, 256);
  if (threadIdx.x == 0) SSTAMP(11, 12);
  cluster_wait();
  if (threadIdx.x == 0) SSTAMP(11, 13);
  mbar_wait(sb + MB_X + 8, 0);
  import();
  finish(0);
  SCHED_FENCE(12);
  bar_sync(3, 256);
  uint64_t dA = xd0 + (XT >> 4);
  xproj<1, 0, 18>(acc, wa, dA);
  if (!qk && wg == 0 && w < 2) send_v(0, w);
  do_export();
  if (qk && wg == 0 && w == 0) wait_v(0);
  bar_arrive(13, 384);
  if (!qk) {
    SCHED_FENCE(15);
    xproj<0, 0, 18>(acc, wa, dA);
    if (threadIdx.x == 0 && !(XP & 8)) { mbar_expect(sb + MB_X, XT); tma_load3(sb + SM_X, &tm.x, 96, sb + MB_X); }
    bar_sync(3, 256);
    mbar_wait(sb + MB_X + 16, 0);
    import();
    finish(1);
    SCHED_FENCE(16);
    bar_sync(3, 256);
    dA += XT >> 4;
    xproj<1, 0, 18>(acc, wa, dA);
    if (wg == 0 && ((w == 0 && VS0) || (w == 1 && VS1))) send_v(1, w);
    do_export();
  }
  if (threadIdx.x == 0) SSTAMP(11, 14);
  bar_sync(0, 384);
  const int ro = __shfl_sync(0xffffffffu, near_half(sb) ^ wg, 0);
  STAMP(5);
  const uint32_t always = __shfl_sync(0xffffffffu, lds32(sb + SC_DEAD + 12), 0);
  const int ah = qk ? 1 : 2;
  int b2 = qk ? 2 : 0;
  int s = 0;
  uint32_t hint_lo = (uint32_t)(uint64_t)tm.red + HINT_OFF + blockIdx.x + (lane & 1) * 4096 + (lane >> 1) * 16384;
  PIN(hint_lo);
  auto post_hint = [&]() {
    asm volatile("{\n.reg .pred p;\n.reg .b64 a;\n.reg .u32 t;\nsetp.lt.u32 p, %0, %1;\nmov.b64 a, {%2, %3};\nmov.u32 t, %%globaltimer_lo;\n"
                 "bfe.u32 t, t, 5, 6;\nor.b32 t, t, %4;\n@p st.relaxed.gpu.global.u8 [a], t;\n}"
                 :: "r"(t16), "r"(sb + 128), "r"(hint_lo + RED_SLOT(s)), "r"((uint32_t)((uint64_t)tm.red >> 32)), "r"(((s >> 2) + 1) << 6) : "memory");
  };
  auto memproj = [&](auto second, int id, float u0, float u1, float* r) {
    constexpr bool R1 = decltype(second)::value;
    uint32_t b[NUP][4], b0[4];
    SCHED_FENCE(id);
    bar_sync(R1 ? 2 : 1, 256);
    PROF(0);
    ldsm4t(b0, mem_a);
#pragma unroll
    for (int q = 0; q < NUP; q++) {
      if (R1 && q == 2) {
        bar_sync(11, 256);
        SCHED_FENCE(id + 1);
      }
      ldsm4t(b[q], mem_a + MEM_BLK(q + 1));
    }
    mma16816z(&acc[0], wa[0][0], b0[0], b0[1]);
    mma16816z(&acc[4], wa[1][0], b0[0], b0[1]);
    mma16816z(&acc[8], wa[0][1], b0[2], b0[3]);
    mma16816z(&acc[12], wa[1][1], b0[2], b0[3]);
#pragma unroll
    for (int q = 1; q < 9; q++) {
      uint32_t* const c = b[(q - 1) % NUP];
      mma16816(&acc[0], wa[0][2 * q], c[0], c[1]);
      mma16816(&acc[4], wa[1][2 * q], c[0], c[1]);
      mma16816(&acc[8], wa[0][2 * q + 1], c[2], c[3]);
      mma16816(&acc[12], wa[1][2 * q + 1], c[2], c[3]);
      if (R1 && q + NUP == B3Q) bar_sync(3, 256);
      if (q + NUP < 9) ldsm4t_in(c, mem_a + MEM_BLK(q + NUP), always);
      else if (R1 && q + NUP < 11) lds128_in(c, t16 + SM_PART + (10 - q - NUP) * 2048, always);
      else if (!R1 && GATE && q == GATE) { bar_arrive(11, 256); lds128_in(c, sb + SC_DEAD, always); u0 = u1 = __uint_as_float(c[3]); }
    }
#pragma unroll
    for (int i = 0; i < 8; i++) {
      const float u = i < 4 ? u0 : u1;
      r[i] = R1 ? fmaf(acc[8 + i], u, (acc[i] + __uint_as_float(b[(8 + i / 4) % NUP][i & 3])) * u) : (GATE ? fmaf(acc[i], u, acc[8 + i]) : acc[i] + acc[8 + i]);
    }
  };
  if (ro == 0) {
    auto set_scale = [&]() {
      uint32_t m[8];
      lds128(t16 + SM_MAX - 512, m); lds128(t16 + SM_MAX, m + 4);
      const int em = (wexp(amax4(amax4(*(const __half2*)&m[0], m), m + 4)) >> 3) + (int)(lds32(sb + SC_UNSC + (s & 1) * 8) >> 23) - 15;
      const int ex = max(s ? em : 0, (int)lds32(sb + SC_XMAX + 4 * s)) - 127 + (int)lds32(sb + SC_EXPW);
      sts32(sb + SC_UNSC + (~s & 1) * 8, (127 + min(max(ex, -120), 120)) << 23);
    };
#pragma unroll 1
    while (true) {
      if (s == 8) STAMP(6);
      float r[8];
      memproj(BoolC<false>(), 30, 0.f, 0.f, r);
      sts128(t16 + SM_PART, __float_as_uint(r[0]), __float_as_uint(r[1]), __float_as_uint(r[2]), __float_as_uint(r[3]));
      sts128(t16 + SM_PART + 2048, __float_as_uint(r[4]), __float_as_uint(r[5]), __float_as_uint(r[6]), __float_as_uint(r[7]));
      bar_arrive(3, 256);
      PROF(1);
      bar_sync(9, 256);
      if (s == NSEG - 1) break;
      post_hint();
      if (w == 1) {
        set_scale();
        __syncwarp();
        if (elect_one()) mbar_arrive(sb + MB_S);
      }
      SCHED_FENCE(9);
      bar_sync(5, qk ? N5 : 256);
      PROF(2);
      import();
      xproj<0, 0, NII, (DD & 1) != 0>(acc, wa, dA);
      if (NII < 18) {
        if (qk) bar_sync(7, 384);
        xproj<0, NII, 18>(acc, wa, dA);
        if (!qk) bar_sync(7, 384);
      } else {
        if (F10) WG_WAIT(0);
        bar_sync(10, 256);
        if (F10) SCHED_FENCE(17);
      }
      dA += (int64_t)(b2 ? XT >> 4 : -(XT >> 3));
      finish(s + ah);
      if (qk || !VLATE(w)) bar_arrive(13, 384);
      PROF(6);
      SCHED_FENCE(14);
      bar_sync(12, 256);
      PROF(7);
      xproj<1, 0, 18, (DD & 2) != 0, 14, N14>(acc, wa, dA);
      if (N14 == 18) bar_arrive(14, 256);
      b2 = b2 == 2 ? 0 : b2 + 1;
      s++;
      if (!qk && VLATE(w)) { bar_sync(13, 384); send_v(s + 1, w); }
      PROFP(8);
      do_export();
      s--; RSTAMP(6); s++;
      PROFP(3);
    }
    if (!qk) bar_arrive(5, 256);
    if (w == 0 && elect_one()) {
      const uint32_t h18 = blockIdx.x / 3 * 18;
      mbar_expect(sb + MB_WO, 9216 + 4096 + 256);
      asm volatile("cp.async.bulk.shared::cluster.global.mbarrier::complete_tx::bytes [%0], [%1], 256, [%2];"
                   :: "r"(sb + T_G), "l"(g_gate + NAUXSEG * 32), "r"(sb + MB_WO) : "memory");
      tma_load(sb + T_OA, &tm.oa, 4096 + (h18 & ~7), NAUXSEG * 32, sb + MB_WO);
#pragma unroll 1
      for (int j = 0; j < 3; j++) tma_load(sb + T_WA + j * 3072, &tm.woa, rank * 192 + j * 64, h18, sb + MB_WO);
    }
    if (w == 1) {
      set_scale();
      __syncwarp();
      const int ea = (int)ldg_relaxed32(&g_amax[0]) + (int)ldg_relaxed32(&g_amax[16]) - 254 + 2 + 10 - 15;
      sts32(sb + T_UN + (lane & 1) * 4, (128 + max(min(ea, 120), (int)(lds32(sb + SC_UNSC + 8 - (lane & 1) * 8) >> 23) - 127)) << 23);
    }
    bar_arrive(8, 256);
  } else {
    uint32_t r0;
    float un;
    auto prepare = [&]() {
      un = __uint_as_float(lds32(sb + SC_UNSC + (s & 1) * 8));
      r0 = qk ? (t16 & ~256u) - w * 256 + (((t16 >> 8) ^ wg) & 1 ? SM_QM : SM_BLK + 8192 + (s & 3) * SEGB) : mapa(t16 + (s < NSEG - 1 ? SM_VM : SM_FB), 0);
      PIN(r0); PIN(un);
    };
    prepare();
#pragma unroll 1
    while (true) {
      if (s == 8) STAMP(6);
      float r[8];
      if (qk) {
        const float u0 = wg ? un * (SM_SCALE * LOG2E) : un, u1 = wg ? un : un * (SM_SCALE * LOG2E);
        memproj(BoolC<true>(), 32, u0, u1, r);
        stsm4(r0, pack_bf16(r[0], r[1]), pack_bf16(r[2], r[3]), pack_bf16(r[4], r[5]), pack_bf16(r[6], r[7]));
        bar_arrive(4, 256);
      } else {
        const uint32_t mb = sb + (s < NSEG - 1 ? MB_S : MB_T), r1 = r0 + (1 << 24);
        memproj(BoolC<true>(), 34, un, un, r);
        const uint32_t p0 = pack_bf16(r[0], r[1]), p1 = pack_bf16(r[2], r[3]), p2 = pack_bf16(r[4], r[5]), p3 = pack_bf16(r[6], r[7]);
        const uint32_t v0 = wg ? p2 : p0, v1 = wg ? p3 : p1, v2 = wg ? p0 : p2, v3 = wg ? p1 : p3;
        st_async4(r0, v0, v1, v2, v3, mapa(mb, 0));
        st_async4(r1, v0, v1, v2, v3, mapa(mb, 1));
        bar_arrive(5, 256);
        sts128(r0 + (2 << 24), v0, v1, v2, v3);
        stsm4((t16 & ~256u) - w * 256 + SM_BLK + 8192 + (s & 3) * SEGB + (((t16 >> 8) ^ wg) & 1) * 1024, p0, p1, p2, p3);
        __syncwarp();
        if (elect_one()) mbar_arrive(sb + MB_S);
      }
      if (s == NSEG - 1) break;
      if (!qk) bar_arrive(15, 160);
      PROF(1);
      auto rearm = [&]() { mbar_wait(sb + MB_S, s & 1); if (elect_one()) mbar_expect(sb + MB_S, qk ? 640 + 2048 : 1280); __syncwarp(); };
      if (w == 1) {
        if ((t16 & 384) == 0) stg_relaxed(tm.red + (RED_SLOT(s + 2) + RED_LINE(blockIdx.x)) + (t16 & 112), 0, 0, 0, 0);
      } else if (w == 0) {
        const int tn = s + ah + 1;
        if (RFW) mbar_wait(sb + MB_S, s & 1);
        if (tn + 1 < NSEG && !(XP & 8) && elect_one()) {
          const int b0 = b2 == 2 ? 0 : b2 + 1;
          mbar_expect(sb + MB_X + 8 * b0, XT);
          tma_load3(sb + SM_X + b0 * XT, &tm.x, (tn + 1) * 32, sb + MB_X + 8 * b0);
        }
        if (tn < NSEG && (!(XP & 8) || tn < 3)) mbar_wait(sb + MB_X + 8 * b2, (tn / 3) & 1);
      } else if (w == 2) {
        if (!qk) { if (VS0 == 0) send_v(s + 1, 0); if (VS1 == 0) send_v(s + 1, 1); }
      } else if (qk || !NIC) {
        rearm();
      }
      __syncwarp();
      import();
      PROF(4);
      SCHED_FENCE(10);
      if (NIC) {
        if (qk) bar_sync(7, NII < 18 ? 384 : 256);
        xproj<0, 0, NIC>(acc, wa, dA);
        if (!qk) { if (w == 3) rearm(); bar_sync(7, NII < 18 ? 384 : 256); }
      } else {
        bar_sync(7, NII < 18 ? 384 : 256);
      }
      xproj<0, NIC, 18, (DD & 4) != 0, 12, N12>(acc, wa, dA);
      if (N12 == 18) bar_arrive(12, 256);
      dA += (int64_t)(b2 ? XT >> 4 : -(XT >> 3));
      finish(s + ah);
      if (qk && w == 0) wait_v(s + 1);
      bar_arrive(13, 384);
      PROF(6);
      SCHED_FENCE(13);
      bar_sync(14, 256);
      PROF(7);
      xproj<1, 0, 18, (DD & 8) != 0>(acc, wa, dA);
      b2 = b2 == 2 ? 0 : b2 + 1;
      s++;
      if (HOIST) prepare();
      PROFP(8);
      do_export();
      if (!HOIST) prepare();
      s--; RSTAMP(7); s++;
      PROFP(3);
    }
    TSTAMP(2);
    bar_sync(3, 128);
    tail_attention(sb, rank, w, lane, 1, 3);
    bar_arrive(0, 256);
  }
  STAMP(3);
  if (CSY) cluster_sync();
  STAMP(4);
}

DI void attn_role(const uint32_t sb, unsigned char* smem_raw, const RMaps& tm, const uint32_t RANK, const bf16* __restrict__ x, const bf16* __restrict__ mem0,
                  const int w, const int lane) {
  const int t2 = w * 32 + lane;
  uint32_t wo[8][4], w1[8][4];
  const uint32_t wo_lane = sb + ((lane & 7) + ((lane >> 4) << 3)) * 128 + (((w + 4 * ((lane >> 3) & 1)) ^ (lane & 7)) << 4);
  unsigned char* const g_red = tm.red;
  {
    const uint32_t tag = *(volatile unsigned*)&g_epoch + 1;
    if (w == 0) {
      stg_relaxed(g_red + RED_SLOT(t2 >> 3) + RED_LINE(blockIdx.x) + (t2 & 7) * 16, 0, 0, 0, 0);
      stg_relaxed(g_red + T_RED + blockIdx.x * 1024 + t2 * 16, 0, 0, 0, 0);
      stg_relaxed(g_red + T_RED + blockIdx.x * 1024 + 512 + t2 * 16, 0, 0, 0, 0);
      asm volatile("st.relaxed.gpu.global.u8 [%0], 0;" :: "l"(g_red + RED_SLOT(t2) + HINT_OFF + (t2 & 4) * 1024 + (t2 >> 3) * 16384 + blockIdx.x) : "memory");
    }
    uint4 xv[18];
    uint32_t mv[20];
#pragma unroll
    for (int i = 0; i < 20; i++) mv[i] = i < 18 ? ((const uint32_t*)mem0)[(lane >> 2) * (DM / 2) + (w * 18 + i) * 4 + (lane & 3)] : 0;
#pragma unroll
    for (int i = 0; i < 18; i++) xv[i] = blockIdx.x < NSEG ? ((const uint4*)(x + blockIdx.x * 32 * DM))[t2 + 128 * i] : make_uint4(0, 0, 0, 0);
    bar_sync(0, 384);
    cluster_arrive();
    if (PACE && w == 3) {
      const uint32_t t0 = gtime();
#pragma unroll 1
      for (int c = 1; c < 4; c++) {
        wait_until(t0 + c * PACE);
        if (elect_one()) load_weights(sb, tm, RANK, PORD ? (c == 1 ? 3 : c - 1) : c);
        __syncwarp();
      }
    }
    __half2 hx = __float2half2_rn(0.f);
#pragma unroll
    for (int i = 0; i < 18; i++) hx = amax4(hx, &xv[i].x);
    if (blockIdx.x == 0)
#pragma unroll
      for (int i = 0; i < 5; i++) hx = amax4(hx, &mv[4 * i]);
    sts32(sb + SC_SS + 4 * (12 + w), wexp(hx));
    if (t2 == 0) { sts32(sb + SC_EPOCH, (tag - 1) * NSEG + 2 - NRING); sts32(sb + SC_UNSC, __float_as_uint(1.f)); sts128(sb + SC_DEAD, 0, 0, 0, 0x3f800000u); sts64(sb + SC_FPAR, 0, 0); sts128(sb + SC_ONES, 0x3f803f80u, 0x3f803f80u, 0x3f803f80u, 0x3f803f80u); }
    WSTAMP(27);
    if (w == 0) __threadfence();
    uint32_t q[8] = {0, 0, 0, 0, 0, 0, 0, 0};
    mbar_wait(sb + MB_WO3, 0);
    if (t2 == 0) SSTAMP(11, 3);
#pragma unroll
    for (int k = 0; k < 8; k++) {
      ldsm4t(wo[k], wo_lane + SM_WO3 + k * 2048); ldsm4t(w1[k], wo_lane + SM_WOST + k * 2048);
#pragma unroll
      for (int i = 0; i < 4; i++) { sq_acc(q[i], wo[k][i]); sq_acc(q[i], w1[k][i]); }
    }
    bar_sync(6, 128);
    if (t2 == 0) SSTAMP(11, 7);
#pragma unroll
    for (int k = 0; k < 8; k++) sts128(sb + SM_WO3 + t2 * 16 + k * 2048, wo[k][0], wo[k][1], wo[k][2], wo[k][3]);
#pragma unroll
    for (int i = 0; i < 5; i++) {
      const int j = w * 18 + 4 * i + (lane >> 3), c = i < 4 || lane < 16 ? j * 8 + j / 24 * 64 : 192;
      stsm4t(sb + SM_MEM + (c + (lane & 7)) * 16, mv[4 * i], mv[4 * i + 1], mv[4 * i + 2], mv[4 * i + 3]);
    }
    bar_arrive(1, 256); bar_arrive(2, 256); bar_arrive(9, 256);
    if (t2 == 0) SSTAMP(11, 8);
    mbar_wait(sb + MB_WO, 0);
    if (t2 == 0) SSTAMP(11, 4);
#pragma unroll
    for (int k = 0; k < 8; k++) ldsm4t(wo[k], wo_lane + SM_X + 2 * XT + k * 2048);
    fence_async();
    bar_sync(6, 128);
    if (t2 == 32) tma_load3(sb + SM_X + 2 * XT, &tm.x, 64, sb + MB_X + 16);
    __syncwarp();
#pragma unroll
    for (int k = 0; k < 8; k++)
#pragma unroll
      for (int i = 0; i < 4; i++) sq_acc(q[4 + i], wo[k][i]);
    float ss = 0.f;
#pragma unroll
    for (int i = 0; i < 8; i++) ss += bf_lo(q[i]) + bf_hi(q[i]);
    ss = warp_sum(ss);
    if (lane == 0) sts32(sb + SC_SS + 4 * (8 + w), __float_as_uint(ss));
    if (t2 == 0) SSTAMP(11, 9);
    bar_sync(11, 384);
    if (t2 == 0) SSTAMP(11, 10);
    if (t2 == 0) {
      float a[16];
#pragma unroll
      for (int i = 0; i < 4; i++) lds128f(sb + SC_SS + 16 * i, &a[4 * i]);
      stg_relaxed(&g_stats[blockIdx.x * 2], __float_as_uint(((a[0] + a[1]) + (a[2] + a[3])) + ((a[4] + a[5]) + (a[6] + a[7]))),
                  __float_as_uint((a[8] + a[9]) + (a[10] + a[11])),
                  max(max(__float_as_uint(a[12]), __float_as_uint(a[13])), max(__float_as_uint(a[14]), __float_as_uint(a[15]))), tag);
    }
    __syncwarp();
    WSTAMP(24);
    cluster_wait();
    if (w == 0) {
      uint4 v[3];
      int n = 0;
      while (true) {
#pragma unroll
        for (int i = 0; i < 3; i++) v[i] = ldg_relaxed(&g_stats[(i * 32 + lane) * 2]);
        if (__all_sync(0xffffffffu, v[0].w == tag && v[1].w == tag && v[2].w == tag) || ++n > SPIN_LIMIT) break;
        __nanosleep(100);
      }
      WSTAMP(25);
      const float sv = warp_sum(__uint_as_float(v[0].x) + __uint_as_float(v[1].x) + __uint_as_float(v[2].x));
      const float so = warp_sum(__uint_as_float(v[0].y) + __uint_as_float(v[1].y) + __uint_as_float(v[2].y));
      const int expW = ((int)(__float_as_uint(sv) >> 23) + (int)(__float_as_uint(so) >> 23) - 254 + 2 + 10 + 1) >> 1;
      sts32(sb + SC_XMAX + 4 * lane, v[0].z); sts32(sb + SC_XMAX + 128 + 4 * lane, v[1].z);
      sts32(sb + SC_EXPW, expW + 1 - 15);
      if (blockIdx.x == 0 && lane == 0) *(volatile unsigned*)&g_epoch = tag;
      sts32(sb + SC_FPAR + 4, 1);
    } else if (w < 3) {
      const uint32_t u = blockIdx.x >> 4;
      unsigned char* const z = g_red + 98304 + (blockIdx.x & 15) * 128 + (u & 1) * 2048 + (u & 6) * 4096 + (((u >> 1) ^ w) & 1) * 4096 + lane * 4;
      stg_relaxed32(z, 0);
      uint32_t best = 0xffffffffu;
#pragma unroll 1
      for (int i = 0; i < 64; i++) {
        uint32_t last, dt;
        asm volatile("{\n.reg .pred p;\n.reg .u32 c, v;\nld.volatile.shared.u32 %0, [%3];\nmov.u32 c, %%clock;\n"
                     "atom.relaxed.gpu.global.exch.b32 v, [%2], 0;\nsetp.eq.u32 p, v, 0;\nmov.u32 %1, 0;\n@p mov.u32 %1, %%clock;\nsub.u32 %1, %1, c;\n}"
                     : "=r"(last), "=r"(dt) : "l"(z), "r"(sb + SC_FPAR + 4) : "memory");
        best = min(best, dt);
        if (last && i >= NPROBE - 1) break;
      }
      sts32(sb + SC_LAT + (w - 1) * 4, best);
    }
    bar_sync(13, 384);
    bar_arrive(0, 384);
    WSTAMP(26);
    TSTAMP(1);
  }

  const uint32_t nh = __shfl_sync(0xffffffffu, near_half(sb), 0);
  uint32_t l16 = sb + lane * 16;
  PIN(l16);
#define LV ((l16 >> 4) & 31)
#define fence_reg l16
  const uint32_t red_lo = (uint32_t)(uint64_t)g_red, red_hi = (uint32_t)((uint64_t)g_red >> 32);
  uint32_t lp;
  auto slot = [&](int s, uint32_t c, uint32_t ofs) {
    const uint32_t lo = lp | (red_lo + ((w >> 1) * 4 + (w & 1) * 2 + ((w ^ c) & 1)) * 4096 + RED_SLOT(s) + ofs);
    uint64_t a; asm("mov.b64 %0, {%1, %2};" : "=l"(a) : "r"(lo), "r"(red_hi));
    return (unsigned char*)a;
  };
  const uint32_t always = __shfl_sync(0xffffffffu, lds32(sb + SC_DEAD + 12), 0);
  const int mode0 = RANK < 2 ? w : w | 4;
  auto hint_addr = [&](int s) { return min(LV, 23u) * 4 + (red_lo + HINT_OFF + nh * 4096 + w * 16384 + RED_SLOT(s)); };
  auto load_hints = [&](uint32_t lo) {
    uint64_t a; asm("mov.b64 %0, {%1, %2};" : "=l"(a) : "r"(lo), "r"(red_hi));
    return ldg_relaxed32((const void*)a);
  };
  const uint32_t blk = RANK < 2 ? 9216 : SEGB;
  auto send_v = [&](int seg, int pos) {
    if (RANK == 2 && ((w == 0 && VS0 == pos) || (w == 1 && VS1 == pos)) && seg > 1 && seg < NSEG && !(XP & 2)) {
      if (elect_one()) {
        fence_async();
        bulk_s2s(mapa(sb + SM_VC + (seg & 1) * 8192, w), sb + SM_BLK + (seg & 3) * SEGB, 8192, mapa(sb + MB_VX + (seg & 1) * 8, w));
      }
      __syncwarp();
    }
  };
  uint32_t dl = __shfl_sync(0xffffffffu, gtime() - 768, 0);
  int s = 0;
  bool bad = false;
#pragma unroll 1
  while (true) {
    const uint32_t par = s & 1;
    uint32_t vx[4][4], oc[4], hints;
    if (HP == 2) { hints = hint_addr(s); PIN(hints); }
    auto load_vx = [&]() {
      const uint32_t va = l16 + (RANK < 2 ? SM_VC + par * 8192 : SM_BLK + (s & 3) * SEGB) + w * 1024 + ((LV >> 3) & 1) * 384 - (LV >> 4) * 128;
      if (WL & 4) lds128(sb + SC_ONES, oc);
#pragma unroll
      for (int i = 0; i < 4; i++) ldsm4(vx[i], va + (i & 1) * 4096 + (i >> 1) * 256);
    };
    auto retire = [&](uint32_t x) {
      asm volatile("{\n.reg .pred p;\nsetp.eq.u32 p, %0, 0;\n@p exit;\n}" :: "r"(vx[0][0] | vx[1][0] | vx[2][0] | vx[3][0] | x | ((WL & 4) ? oc[0] : 0)) : "memory");
    };
    auto scores = [&](auto memkeys, auto first, float* sc) {
      constexpr bool MK = decltype(memkeys)::value, FIRST = decltype(first)::value;
      uint32_t kb[4][4], qb[2][4];
      const uint32_t m = LV >> 3;
      uint32_t kaddr = l16 + SM_BLK + 4096 + (s & 3) * SEGB + w * 2048 + (m & 1) * (MK ? 128 : 896) - (m >> 1) * 128;
      if (MK) { PIN(kaddr); }
      else {
#pragma unroll
        for (int k = 0; k < 4; k++) ldsm4t(kb[k], kaddr + k * 256);
      }
      if (FIRST) { load_vx(); retire(MK ? kaddr : kb[0][0] | kb[1][0] | kb[2][0] | kb[3][0] | l16); bar_sync(4, 256); RSTAMP(4); PROF(4); }
      ldsm4t(qb[0], l16 + SM_QM);
      if (MK) ldsm4t(kb[0], kaddr);
      ldsm4t(qb[1], l16 + SM_QM + 512);
      if (MK) ldsm4t(kb[2], kaddr + 512);
      float c[4][4];
      mma16816z(c[0], kb[0], qb[0][0], qb[0][1]); mma16816z(c[1], kb[MK ? 0 : 1], qb[0][2], qb[0][3]);
      mma16816z(c[2], kb[2], qb[1][0], qb[1][1]); mma16816z(c[3], kb[MK ? 2 : 3], qb[1][2], qb[1][3]);
      if (FIRST && B5POS == 0) bar_arrive(5, N5);
#pragma unroll
      for (int i = 0; i < (MK ? 2 : 4); i++) sc[i] = ((c[0][i] + c[1][MK ? i + 2 : i]) + c[2][i]) + c[3][MK ? i + 2 : i];
    };
    auto send = [&](auto memkeys) {
      constexpr bool MK = decltype(memkeys)::value;
      constexpr int N = MK ? 1 : 2;
      const uint32_t sa = sb + LV * 4 + SM_E + (MK ? 1024 + RANK * 128 : RANK * 512 + w * 256);
      uint32_t ra[N][2], mb[N][2];
#pragma unroll
      for (int i = 0; i < N; i++)
#pragma unroll
        for (int j = 0; j < 2; j++) {
          ra[i][j] = mapa(sa + i * 128, j ? 2 : RANK ^ 1); mb[i][j] = mapa(sb + MB_S, j ? 2 : RANK ^ 1);
          PIN(ra[i][j]);
        }
      float sc[4];
      scores(memkeys, BoolC<true>(), sc);
      uint32_t e[N];
#pragma unroll
      for (int i = 0; i < N; i++) {
        e[i] = pack_bf16(ex2(sc[2 * i]), ex2(sc[2 * i + 1]));
        if (!(fmaxf(fabsf(sc[2 * i]), fabsf(sc[2 * i + 1])) <= E_LIM)) e[i] = 0x7fff7fffu;
        st_async1(ra[i][0], e[i], mb[i][0]);
        st_async1(ra[i][1], e[i], mb[i][1]);
      }
#pragma unroll
      for (int i = 0; i < N; i++) sts32(sa + i * 128, e[i]);
      __syncwarp();
      if (l16 == sb) mbar_arrive(sb + MB_S);
      PROF(5);
    };
    const int mode = bad ? 8 : mode0;
    if (mode < 2) {
      send(BoolC<false>());
    } else if (mode == 2) {
      send(BoolC<true>());
    } else if (mode == 8) {
      load_vx();
      retire(l16);
      const uint32_t fp = lds32(sb + SC_FPAR);
      bar_sync(6, 128);
      if (w == 0 && l16 == sb) { sts32(sb + SC_FPAR, fp ^ 1); mbar_expect(sb + MB_F, 3072); }
      if (RANK < 2 && w < 3) {
        float sc[4] = {0.f, 0.f, 0.f, 0.f};
        if (w < 2) scores(BoolC<false>(), BoolC<false>(), sc); else scores(BoolC<true>(), BoolC<false>(), sc);
#pragma unroll 1
        for (int r = 0; r < 3; r++)
          st_async4(mapa(l16 + SM_FB + RANK * 1536 + w * 512, r), __float_as_uint(sc[0]), __float_as_uint(sc[1]), __float_as_uint(sc[2]), __float_as_uint(sc[3]), mapa(sb + MB_F, r));
      }
      mbar_wait(sb + MB_F, fp);
      float a[12];
#pragma unroll
      for (int j = 0; j < 3; j++) {
        float b[4];
        lds128f(l16 + SM_FB + j * 512, a + 4 * j); lds128f(l16 + SM_FB + 1536 + j * 512, b);
#pragma unroll
        for (int i = 0; i < 4; i++) a[4 * j + i] += b[i];
      }
      float m0 = fmaxf(fmaxf(fmaxf(a[0], a[2]), fmaxf(a[4], a[6])), a[8]), m1 = fmaxf(fmaxf(fmaxf(a[1], a[3]), fmaxf(a[5], a[7])), a[9]);
#pragma unroll
      for (int o = 4; o < 32; o <<= 1) { m0 = fmaxf(m0, __shfl_xor_sync(0xffffffffu, m0, o)); m1 = fmaxf(m1, __shfl_xor_sync(0xffffffffu, m1, o)); }
#pragma unroll
      for (int i = 0; i < 5; i++) {
        const uint32_t ea = sb + SM_E + LV * 4 + (i < 4 ? i * 128 : 1024);
        sts32(ea, pack_bf16(ex2(a[2 * i] - m0), ex2(a[2 * i + 1] - m1)));
        sts32(ea + (i < 4 ? 512 : 128), 0x3f803f80u);
      }
      __syncwarp();
    } else {
      load_vx();
      retire(l16 + 1);
      if (VS0 == 2 || VS1 == 2) send_v(s + 1, 2);
      if (w == 3) {
        uint32_t used = ldg_relaxed32(&g_used[blockIdx.x / 3 * 32]);
        if (!(XP & 4) && elect_one()) {
          if (s > 0) seg_publish(s - 1);
          fence_async();
          seg_store(s, sb, 0, 8192);
        }
        __syncwarp();
        bar_sync(RANK < 2 ? 4 : 15, RANK < 2 ? 256 : 160);
        if (!(XP & 4) && elect_one()) { fence_async(); seg_store(s, sb, 8192, blk - 8192); }
        __syncwarp();
        const uint32_t need = lds32(sb + SC_EPOCH) + (s >= NRING - 1 ? s : -4 * NSEG);
#pragma unroll 1
        for (int n = 0; (int)(used - need) < 0 && n < ((XP & 64) ? 1 : SPIN_LIMIT); n++) used = ldg_relaxed32(&g_used[blockIdx.x / 3 * 32]);
      }
    }
    {
      uint32_t wa[4], wb[4];
      constexpr int WS = 2048;
      const uint32_t w3a = l16 + SM_WO3 + w * 512;
      if (HP == 1) { hints = hint_addr(s); PIN(hints); }
      if (!(WL & 1)) { lds128(w3a + KP(0) * WS, wa); lds128(w3a + KP(1) * WS, wb); }
      if (WL & 2) {
#pragma unroll
        for (int i = 0; i < 4; i++) oc[i] = always | (always >> 16) | (always & (i + 1));
      } else if (!(WL & 4)) lds128(sb + SC_ONES, oc);
      if (B5POS == 1 && mode < 3) bar_arrive(5, N5);
      uint32_t e[10], p[5], vm[4], ob[4];
      float o0[4], o1[4], f[3][2][4], rs[4];
      if (!(RV & 1)) { reserve2(vm); reserve2(vm + 2); }
      if (!(RV & 2)) reserve2(e + 8);
      if (!HP) { hints = hint_addr(s); PIN(hints); }
      if (CLR & 2) asm volatile("{\n.reg .pred p;\nsetp.eq.u32 p, %0, 0;\n@p exit;\n}" :: "r"(wa[0] | wb[0] | oc[0] | hints) : "memory");
      if (RV & 4) mbar_wait_fast(sb + MB_S, par); else mbar_wait(sb + MB_S, par);
      RSTAMP(5);
      PROF(6);
      if (RV & 2) { ldsm4t(e, l16 + SM_E); ldsm4t(e + 4, l16 + SM_E + 512); ldsm2t(e + 8, l16 + SM_E + 1024); }
      else { ldsm4t(e, l16 + SM_E); ldsm2t_in(e + 8, l16 + SM_E + 1024, always); ldsm4t(e + 4, l16 + SM_E + 512); }
      if (RV & 1) lds128(l16 + w * 512 + SM_VM, vm); else lds128_in(vm, l16 + w * 512 + SM_VM, always);
      const float scl = __uint_as_float(lds32(sb + SC_UNSC + 8 - par * 8));
      if (HL == 0) hints = load_hints(hints);
      if (GF & 1) SCHED_FENCE(4);
#pragma unroll
      for (int i = 0; i < 4; i++) p[i] = mul_bf16(e[i], e[4 + i]);
      p[4] = mul_bf16(e[8], e[9]);
      if (HL) hints = load_hints(hints | (p[HL - 1] & always & 1));
      mma16816z(o0, vx[0], p[0], p[1]);
      if (WL & 1) { lds128_in(vx[0], w3a + KP(0) * WS, always); }
      mma16816z(o1, vx[1], p[0], p[1]);
      if (WL & 1) { lds128_in(vx[1], w3a + KP(1) * WS, always); }
      mma16816z(rs, oc, p[0], p[1]);
      mma16816(o0, vx[2], p[2], p[3]); lds128_in(vx[2], w3a + KP(2) * WS, always);
      mma16816(o1, vx[3], p[2], p[3]); lds128_in(vx[3], w3a + KP(3) * WS, always);
      mma16816(rs, oc, p[2], p[3]);
      mma1688(o0, vm[0], vm[1], p[4]); mma1688(o1, vm[2], vm[3], p[4]); mma1688(rs, oc[0], oc[1], p[4]);
      stsm4(l16 + w * 512 + SM_OB, pack_bf16(o0[0], o0[1]), pack_bf16(o0[2], o0[3]), pack_bf16(o1[0], o1[1]), pack_bf16(o1[2], o1[3]));
      bar_sync(6, 128);
      RSTAMP(3);
      PROF(7);
      ldsm4t_in(oc, l16 + SM_OB, always);
      bad = __any_sync(0xffffffffu, !(rs[0] + rs[1] > 0.f) && !bad);
      rs[0] *= scl; rs[1] *= scl;
      asm volatile("{\n.reg .pred p;\nsetp.ne.u32 p, %1, 0;\n@p rcp.approx.ftz.f32 %0, %0;\n}" : "+f"(rs[0]) : "r"(always));
      asm volatile("{\n.reg .pred p;\nsetp.ne.u32 p, %1, 1;\n@p rcp.approx.ftz.f32 %0, %0;\n}" : "+f"(rs[1]) : "r"(always));
      asm volatile("lop3.b32 %0, %1, %2, %3, 0xfe;" : "=r"(lp) : "r"((l16 & 128) * 2), "r"((l16 & 256) * 4), "r"(l16 & 112));
      if (bad) continue;
      ldsm4t(ob, l16 + SM_OB + 512);
      mma16816z(f[2][0], WL & 1 ? vx[0] : wa, oc[0], oc[1]); mma16816z(f[2][1], WL & 1 ? vx[1] : wb, oc[2], oc[3]);
      mma16816z(f[0][0], wo[0], oc[0], oc[1]); mma16816z(f[0][1], wo[4], oc[2], oc[3]);
      mma16816z(f[1][0], w1[0], oc[0], oc[1]); mma16816z(f[1][1], w1[4], oc[2], oc[3]);
      ldsm4t_in(oc, l16 + SM_OB + 1024, always);
      mma16816(f[2][0], vx[2], ob[0], ob[1]); lds128_in(vx[2], w3a + KP(4) * WS, always);
      mma16816(f[2][1], vx[3], ob[2], ob[3]); lds128_in(vx[3], w3a + KP(5) * WS, always);
      mma16816(f[0][0], wo[1], ob[0], ob[1]); mma16816(f[0][1], wo[5], ob[2], ob[3]);
      mma16816(f[1][0], w1[1], ob[0], ob[1]); mma16816(f[1][1], w1[5], ob[2], ob[3]);
      ldsm4t_in(ob, l16 + SM_OB + 1536, always);
      mma16816(f[0][0], wo[2], oc[0], oc[1]); mma16816(f[0][1], wo[6], oc[2], oc[3]);
      mma16816(f[2][0], vx[2], oc[0], oc[1]); lds128_in(vx[2], w3a + KP(6) * WS, always);
      mma16816(f[2][1], vx[3], oc[2], oc[3]); lds128_in(vx[3], w3a + KP(7) * WS, always);
      mma16816(f[1][0], w1[2], oc[0], oc[1]); mma16816(f[1][1], w1[6], oc[2], oc[3]);
      mma16816(f[0][0], wo[3], ob[0], ob[1]); mma16816(f[0][1], wo[7], ob[2], ob[3]);
      mma16816(f[1][0], w1[3], ob[0], ob[1]); mma16816(f[1][1], w1[7], ob[2], ob[3]);
      mma16816(f[2][0], vx[2], ob[0], ob[1]); mma16816(f[2][1], vx[3], ob[2], ob[3]);
      bar_arrive(7, NII < 18 ? 384 : 256);
      lds128_in(ob, sb + SC_DEAD, always);
      uint32_t h[3][2];
#pragma unroll
      for (int j = 0; j < 3; j++)
#pragma unroll
        for (int i = 0; i < 2; i++)
        {
          scale_sum(f[j][1][2 * i], f[j][0][2 * i], rs[0], always); scale_sum(f[j][1][2 * i + 1], f[j][0][2 * i + 1], rs[1], always);
          h[j][i] = pack_f16(f[j][1][2 * i], f[j][1][2 * i + 1]);
        }
      const uint32_t rofs = RANK * 32768;
      red_f16x8(slot(s, RANK >> 1, rofs), h[0][0], h[1][0], h[2][0], 0x3c00u);
      red_f16x8(slot(s, (RANK >> 1) ^ 1, rofs), h[0][1], h[1][1], h[2][1], 0x3c00u);
      if (NII == 18) bar_arrive(10, 256);
      SCHED_FENCE(5);
      RSTAMP(0);
      l16 += ob[B7R];
    }
    {
    PROF(8);
    if (VS0 == 3 || VS1 == 3) send_v(s + 1, 3);
    const uint32_t ma0 = l16 + SM_MEM + w * 128 + (LV >> 3) * 896 + nh * 512;
    const unsigned char* const sl[2] = {slot(s, nh, 0), slot(s, nh ^ 1, 0)};
    uint32_t late = latest_hint(hints, dl, s);
    if (late >= 64) {
      int n = 0;
#pragma unroll 1
      do {
        late = latest_hint(load_hints(hint_addr(s)), dl, s);
      } while (late >= 64 && ++n < SPIN_LIMIT);
    }
    dl += late * 32 + tm.poll;
    PROF(9);
    {
      auto wait_until = [&](uint32_t t) {
        asm volatile("{\n.reg .pred p;\n.reg .s32 c;\n.reg .u64 t;\nTL: mov.u64 t, %%globaltimer;\ncvt.u32.u64 c, t;\nsub.s32 c, c, %0;\nsetp.lt.s32 p, c, 0;\n@p bra.uni TL;\n}" :: "r"(t + (l16 & 15)) : "memory");
      };
      uint4 v[2][3];
      auto load = [&](int c) {
#pragma unroll
        for (int r = 0; r < 3; r++) v[c][r] = ldg_relaxed(sl[c ^ (r >> 1)] + r * 32768);
      };
      auto decode = [&](int c, int n) {
        uint32_t q[9];
        __half2 hm;
        const uint32_t ma = ma0 ^ (c * 512);
#pragma unroll
        for (int i = 0; i < 9; i++) {
          const uint32_t h = i % 3 == 0 ? v[c][i / 3].x : (i % 3 == 1 ? v[c][i / 3].y : v[c][i / 3].z);
          const float2 f = __half22float2(*(const __half2*)&h);
          q[i] = pack_bf16(f.x, f.y);
          hm = i ? __hmax2(hm, __habs2(*(const __half2*)&h)) : __habs2(*(const __half2*)&h);
        }
#pragma unroll
        for (int r = 0; r < 3; r++) stsm4(ma + r * 4096, q[3 * r], q[3 * r + 1], q[3 * r + 2], r < 2 ? v[c][r].w : *(const uint32_t*)&hm);
        const bool done = __all_sync(0xffffffffu, v[c][0].w == 0x5000u && v[c][1].w == 0x5000u && v[c][2].w == 0x5000u) || n > SPIN_LIMIT;
        asm volatile("{\n.reg .pred p;\nsetp.ne.u32 p, %0, 0;\n@p bar.arrive %1, 256;\n}" :: "r"((int)done), "r"(1 + c) : "memory");
        return done;
      };
      if (LEAD) { wait_until(dl - LEAD); load(1); }
      wait_until(dl);
      PROF(10);
      int n = 0;
#pragma unroll 1
      do {
        load(0);
        if (!LEAD) load(1);
        asm volatile("{\n.reg .pred p;\nsetp.eq.u32 p, %0, 0;\n@p bar.sync 13, 384;\n}" :: "r"(n) : "memory");
      } while (!decode(0, n++));
      PROF(11);
      RSTAMP(1);
#pragma unroll 1
      while (!decode(1, n++)) load(1);
      bar_arrive(9, 256);
      RSTAMP(2);
      PROF(12);
    }
    PROF(13);
    if (++s == NSEG - 1) break;
    }
  }
#undef fence_reg
  if (RANK < 2) bar_arrive(4, 256);
  TSTAMP(49);
  {
    PIN(l16);
    tail_attention(sb, RANK, w, LV, 0, 6);
#pragma unroll 1
    for (int sg = 0; sg < 2; sg++) {
      PIN(l16);
      const int lane = LV, m = lane >> 3, g = lane >> 2, t = lane & 3;
      const uint32_t ob = l16 + T_OB + sg * 8192;
      bar_sync(sg ? 0 : 8, 256);
      TSTAMP(54 + 2 * sg);
      const float inv = __uint_as_float(0x7f000000u - lds32(sb + T_UN + sg * 4));
#pragma unroll 1
      for (int j = 0; j < 4; j += 2) {
        float c[2][3][4];
        uint32_t x[4], y[4], z[2][4];
#pragma unroll
        for (int e = 0; e < 2; e++) {
          const uint32_t oa = sb + T_OA + ((sg * 4 + j + e) * 8 + g) * 64 + (blockIdx.x / 3 * 36 & 15) + t * 4;
          z[e][0] = lds32(oa); z[e][1] = lds32(oa + 16); z[e][2] = t ? 0u : lds32(oa + 32);
        }
#pragma unroll
        for (int i = 0; i < 3; i++) {
          const uint32_t wa = sb + T_WA + ((lane & 7) + ((lane >> 4) << 3)) * 128 + (((w + 4 * (m & 1)) ^ (lane & 7)) << 4);
          ldsm4t(x, wa + i * 3072); ldsm2t(y, wa + i * 3072 + 2048);
#pragma unroll
          for (int e = 0; e < 2; e++) { mma1688z(c[e][i], y[0], y[1], z[e][2]); mma16816(c[e][i], x, z[e][0], z[e][1]); }
        }
#pragma unroll
        for (int r = 0; r < 4; r++) {
          ldsm4t(z[0], ob + j * 2048 + r * 512); ldsm4t(z[1], ob + j * 2048 + 2048 + r * 512);
          lds128(l16 + SM_WO3 + w * 512 + r * 2048, x); lds128(l16 + SM_WO3 + w * 512 + (r + 4) * 2048, y);
#pragma unroll
          for (int e = 0; e < 2; e++) { mma16816(c[e][0], wo[r], z[e][0], z[e][1]); mma16816(c[e][1], w1[r], z[e][0], z[e][1]); mma16816(c[e][2], x, z[e][0], z[e][1]); }
#pragma unroll
          for (int e = 0; e < 2; e++) { mma16816(c[e][0], wo[r + 4], z[e][2], z[e][3]); mma16816(c[e][1], w1[r + 4], z[e][2], z[e][3]); mma16816(c[e][2], y, z[e][2], z[e][3]); }
        }
#pragma unroll
        for (int i = 0; i < 4; i++) {
          const float (&d)[3][4] = c[i >> 1];
          const int q = (i & 1) * 2;
          red_f16x8(g_red + T_RED + ((((sg * 4 + j + (i >> 1)) * 3 + RANK) * 4 + w) * 2 + (i & 1)) * 512 + lane * 16, pack_f16(d[0][q] * inv, d[0][q + 1] * inv),
                    pack_f16(d[1][q] * inv, d[1][q + 1] * inv), pack_f16(d[2][q] * inv, d[2][q + 1] * inv), 0x3c00u);
        }
      }
      TSTAMP(55 + 2 * sg);
    }
    if (RSLOW) { wait_until(gtime() + 8000); wait_until(gtime() + 8000); wait_until(gtime() + 4000); }
    if (w < 2) {
      const int b = blockIdx.x, lane = LV, g = lane >> 2, t = lane & 3;
      uint4 v;
#pragma unroll 1
      for (int n = 0; n < SPIN_LIMIT; n++) {
        v = ldg_relaxed(g_red + T_RED + (w * 96 + b) * 512 + lane * 16);
        if (__all_sync(0xffffffffu, v.w == 0x5000u)) break;
        __nanosleep(40);
      }
      const float un = __uint_as_float(lds32(sb + T_UN + w * 4));
      uint32_t* const o = (uint32_t*)(tm.out + (size_t)((NAUXSEG + w) * 32 + b / 24 * 8 + g) * DM + (b >> 3) % 3 * 192 + (b & 1) * 32 + (b & 6) * 4) + t;
#pragma unroll
      for (int j = 0; j < 3; j++) {
        const float2 f = __half22float2(*(const __half2*)(&v.x + j));
        o[j * 32] = movm(pack_bf16(f.x * un, f.y * un));
      }
    }
  }
  TSTAMP(3);
  if (CSY) cluster_sync();
}

__global__ void __cluster_dims__(3, 1, 1) __launch_bounds__(384, 1)
rec_kernel(const __grid_constant__ RMaps tm, const bf16* __restrict__ x, const bf16* __restrict__ mem0) {
  extern __shared__ __align__(1024) unsigned char smem_raw[];
  const uint32_t sb = smem_u32(smem_raw);
  const int tid = threadIdx.x, lane = tid & 31;
  const int wg = __shfl_sync(0xffffffffu, tid >> 7, 0);
  const int w = __shfl_sync(0xffffffffu, (tid >> 5) & 3, 0);
  uint32_t rank; asm("mov.u32 %0, %%cluster_ctarank;" : "=r"(rank));
  STAMP(0);
  TSTAMP(0);
  asm volatile("griddepcontrol.launch_dependents;" ::: "memory");

#define PFT 1
  if (PFT && wg == 1 && lane == 0) asm volatile("prefetch.tensormap [%0];\nprefetch.tensormap [%1];" :: "l"(w & 1 ? &tm.woa : &tm.oa), "l"(w == 0 ? (rank < 2 ? &tm.wk : &tm.wv) : w == 1 ? &tm.wq : w == 2 ? &tm.x : &tm.wo) : "memory");
  if (wg < 2) {
    asm volatile("setmaxnreg.inc.sync.aligned.u32 192;");
    if (tid == 0) {
      for (int i = 0; i < 3; i++) { mbar_init(sb + MB_W + 8 * i, 1); mbar_init(sb + MB_X + 8 * i, 1); }
      mbar_init(sb + MB_WO, 1); mbar_init(sb + MB_WO3, 1);
      mbar_init(sb + MB_S, rank < 2 ? 5 : 6);
      mbar_init(sb + MB_F, 1);
      for (int i = 0; i < 3; i++) mbar_init(sb + MB_T + 8 * i, 1);
      mbar_init(sb + MB_VX, 1); mbar_init(sb + MB_VX + 8, 1);
      asm volatile("fence.mbarrier_init.release.cluster;" ::: "memory");
      fence_async();
      SSTAMP(11, 6);
      load_weights(sb, tm, rank, 0);
      for (int i = 0; i < 3; i++) mbar_expect(sb + MB_X + 8 * i, XT);
      tma_load3(sb + SM_X, &tm.x, 0, sb + MB_X);
      if (!PACE) for (int c = 1; c < 4; c++) load_weights(sb, tm, rank, c);
      mbar_expect(sb + MB_S, rank < 2 ? 640 + 2048 : 1280);
      mbar_expect(sb + MB_VX, 8192); mbar_expect(sb + MB_VX + 8, 8192);
      mbar_expect(sb + MB_T, 2048);
      for (int i = 1; i < 3; i++) mbar_expect(sb + MB_T + 8 * i, rank < 2 ? 5120 : 10240);
      SSTAMP(11, 5);
    }
    __syncwarp();
    bar_sync(0, 384);
    proj_role(sb, tm, rank, wg, w, lane);
  } else {
    asm volatile("setmaxnreg.dec.sync.aligned.u32 120;");
    attn_role(sb, smem_raw, tm, rank, x, mem0, w, lane);
  }
}

constexpr int A_XH = 73728;
constexpr int A_NS = 9, A_WM = 6144, A_WT = 768;
constexpr int A_RING = 2 * A_XH, A_TAIL = A_RING + A_NS * A_WM, A_GW = A_TAIL + A_NS * A_WT;
constexpr int A_EPI = 212864, A_EPW = 9344;
constexpr int A_XW = 4 * XT, A_XT = A_XW + 4096, A_NR = 4;
constexpr int A_IN = A_XT + 2048, A_INS = 2 * 9216 + SEGB;
constexpr int A_GATE = A_EPI + 2 * A_EPW, A_BAR = A_GATE + 512;
constexpr int A_TOTAL = A_BAR + 384;
struct AMaps { CUtensorMap x, wa, wt, oa, o, o3, o8, wob, woa, wo8; };

DI void wgmma_n192_ss_nt(float* d, uint64_t da, uint64_t db, int acc) {
  asm volatile("{\n.reg .pred p;\nsetp.ne.b32 p, %98, 0;\n"
               "wgmma.mma_async.sync.aligned.m64n192k16.f32.bf16.bf16 {"
               "%0,%1,%2,%3,%4,%5,%6,%7,%8,%9,%10,%11,%12,%13,%14,%15,%16,%17,%18,%19,%20,%21,%22,%23,%24,%25,%26,%27,%28,%29,%30,%31,"
               "%32,%33,%34,%35,%36,%37,%38,%39,%40,%41,%42,%43,%44,%45,%46,%47,%48,%49,%50,%51,%52,%53,%54,%55,%56,%57,%58,%59,%60,%61,%62,%63,"
               "%64,%65,%66,%67,%68,%69,%70,%71,%72,%73,%74,%75,%76,%77,%78,%79,%80,%81,%82,%83,%84,%85,%86,%87,%88,%89,%90,%91,%92,%93,%94,%95"
               "}, %96, %97, p, 1, 1, 0, 1;\n}\n"
               : ACC8(d, 0), ACC8(d, 8), ACC8(d, 16), ACC8(d, 24), ACC8(d, 32), ACC8(d, 40), ACC8(d, 48), ACC8(d, 56),
                 ACC8(d, 64), ACC8(d, 72), ACC8(d, 80), ACC8(d, 88) : "l"(da), "l"(db), "r"(acc));
}
#define ACC4(d, o) "+f"(d[o]), "+f"(d[o + 1]), "+f"(d[o + 2]), "+f"(d[o + 3])
DI void wgmma_n24_ss_nt(float* d, uint64_t da, uint64_t db, int acc) {
  asm volatile("{\n.reg .pred p;\nsetp.ne.b32 p, %14, 0;\n"
               "wgmma.mma_async.sync.aligned.m64n24k16.f32.bf16.bf16 {%0,%1,%2,%3,%4,%5,%6,%7,%8,%9,%10,%11}, %12, %13, p, 1, 1, 0, 1;\n}\n"
               : ACC8(d, 0), ACC4(d, 8) : "l"(da), "l"(db), "r"(acc));
}
DI void wgmma_n8_ss(float* d, uint64_t da, uint64_t db, int acc) {
  asm volatile("{\n.reg .pred p;\nsetp.ne.b32 p, %6, 0;\n"
               "wgmma.mma_async.sync.aligned.m64n8k16.f32.bf16.bf16 {%0,%1,%2,%3}, %4, %5, p, 1, 1, 0, 0;\n}\n"
               : ACC4(d, 0) : "l"(da), "l"(db), "r"(acc));
}
DI void wgmma_n40_ss_tt(float* d, uint64_t da, uint64_t db, int acc) {
  asm volatile("{\n.reg .pred p;\nsetp.ne.b32 p, %22, 0;\n"
               "wgmma.mma_async.sync.aligned.m64n40k16.f32.bf16.bf16 {%0,%1,%2,%3,%4,%5,%6,%7,%8,%9,%10,%11,%12,%13,%14,%15,%16,%17,%18,%19}, "
               "%20, %21, p, 1, 1, 1, 1;\n}\n"
               : ACC8(d, 0), ACC8(d, 8), ACC4(d, 16) : "l"(da), "l"(db), "r"(acc));
}
DI void wgmma_n64_rs(float* d, const uint32_t* a, uint64_t db, int acc) {
  asm volatile("{\n.reg .pred p;\nsetp.ne.b32 p, %37, 0;\n"
               "wgmma.mma_async.sync.aligned.m64n64k16.f32.bf16.bf16 {"
               "%0,%1,%2,%3,%4,%5,%6,%7,%8,%9,%10,%11,%12,%13,%14,%15,%16,%17,%18,%19,%20,%21,%22,%23,%24,%25,%26,%27,%28,%29,%30,%31"
               "}, {%32,%33,%34,%35}, %36, p, 1, 1, 0;\n}\n"
               : ACC8(d, 0), ACC8(d, 8), ACC8(d, 16), ACC8(d, 24) : "r"(a[0]), "r"(a[1]), "r"(a[2]), "r"(a[3]), "l"(db), "r"(acc));
}
DI void wgmma_n32_ss_tn(float* d, uint64_t da, uint64_t db, int acc) {
  asm volatile("{\n.reg .pred p;\nsetp.ne.b32 p, %18, 0;\n"
               "wgmma.mma_async.sync.aligned.m64n32k16.f32.bf16.bf16 {%0,%1,%2,%3,%4,%5,%6,%7,%8,%9,%10,%11,%12,%13,%14,%15}, "
               "%16, %17, p, 1, 1, 1, 0;\n}\n"
               : ACC8(d, 0), ACC8(d, 8) : "l"(da), "l"(db), "r"(acc));
}
DI void tma_load3c(uint32_t dst, const CUtensorMap* m, int c0, int c1, int c2, uint32_t mb) {
  asm volatile("cp.async.bulk.tensor.3d.shared::cluster.global.mbarrier::complete_tx::bytes [%0], [%1, {%3, %4, %5}], [%2];"
               :: "r"(dst), "l"(m), "r"(mb), "r"(c0), "r"(c1), "r"(c2) : "memory");
}
DI void count_up(unsigned* p) {
  asm volatile("fence.proxy.async;" ::: "memory");
  asm volatile("red.release.gpu.global.add.u32 [%0], 1;" :: "l"(p) : "memory");
}
#define AX 0
#define FDLY 400
#define FEND 59
DI void publish(unsigned* p) {
  asm volatile("cp.async.bulk.wait_group 0;\nfence.proxy.async;" ::: "memory");
  asm volatile("red.relaxed.gpu.global.add.u32 [%0], 1;" :: "l"(p) : "memory");
}
#define PL 2
#define SER 35
#define DRAIN 0
#define PR 4
#define NQ 3
#define PUB 0
#define LA 1
#define LAG0 10
#define LEND 56
#define PDLY 0
#define ADLY 0

__global__ void __launch_bounds__(512, 1)
aux_kernel(const __grid_constant__ AMaps tm, const bf16* __restrict__ wqkv, const bf16* __restrict__ woa, const bf16* __restrict__ gate_w, bf16* __restrict__ out) {
  extern __shared__ __align__(1024) unsigned char smem_raw[];
  const uint32_t sb = smem_u32(smem_raw);
  const uint32_t fullx = sb + A_BAR, full1 = fullx + 24, empty1 = full1 + 8 * A_NS, fullw = empty1 + 8 * A_NS, full3 = fullw + 8, empty3 = full3 + 8 * A_NR,
                 fullq = empty3 + 8 * A_NR, emptyq = fullq + 24;
  const int tid = threadIdx.x, lane = tid & 31, cta = blockIdx.x;
  const int wg = __shfl_sync(0xffffffffu, tid >> 7, 0), w = __shfl_sync(0xffffffffu, (tid >> 5) & 3, 0);
  ASTAMP(14);
  if (tid == 384) {
    for (int i = 0; i < 3; i++) mbar_init(fullx + 8 * i, 1);
    for (int i = 0; i < A_NS; i++) { mbar_init(full1 + 8 * i, 1); mbar_init(empty1 + 8 * i, 8); }
    mbar_init(fullw, 1);
    for (int i = 0; i < 3; i++) { mbar_init(fullq + 8 * i, 1); mbar_init(emptyq + 8 * i, 4); }
    for (int i = 0; i < A_NR; i++) { mbar_init(full3 + 8 * i, 1); mbar_init(empty3 + 8 * i, cta < NH ? 8 : 4); }
    fence_async();
  }
  __syncthreads();
  ASTAMP(0);
  const int tile = cta >> 1, hh = cta & 1;
  auto p3_n = [&](int g) { return cta < NH ? (cta & 3) * 2 + g : 8; };
  auto p3_next = [&](int& sl, int& ph) {
    sl += cta < NH ? 1 : 2;
    if (sl >= (cta < NH ? 6 - NQ : 4)) { sl -= cta < NH ? 6 - NQ : 4; ph ^= 1; }
  };
  auto p3_k = [&](int g) { return cta < NH ? cta >> 2 : (cta & 3) * 2 + g; };
  if (wg == 3) {
    asm volatile("setmaxnreg.dec.sync.aligned.u32 24;");
    const bool lead = lane == 0;
    if (w < 3) {
      if (ADLY) wait_until(gtime() + ADLY);
      if (elect_one()) {
        mbar_expect(fullx + 8 * w, 49152);
        for (int p = 0; p < 2; p++)
          asm volatile("cp.async.bulk.tensor.4d.shared::cluster.global.mbarrier::complete_tx::bytes [%0], [%1, {%3, %4, %5, %6}], [%2];"
                       :: "r"(sb + p * A_XH + w * 24576), "l"(&tm.x), "r"(fullx + 8 * w), "r"(0), "r"(p), "r"(57 * tile - 7), "r"(3 * w) : "memory");
      }
#pragma unroll 1
      for (int r = 0; r < 17; r++) {
#pragma unroll 1
        for (int st = w; st < A_NS; st += 3) {
          if (r > 0) mbar_wait(empty1 + 8 * st, ~r & 1);
          if (r < 16 && elect_one()) {
            const int col = hh * 288 + (r >> 2) * 72, row = (r & 3) * 144 + st * 16;
            mbar_expect(full1 + 8 * st, A_WM + (AX & 1 ? 0 : A_WT));
            tma_load3c(sb + A_RING + st * A_WM, &tm.wa, col, row, 0, full1 + 8 * st);
            if (!(AX & 1)) tma_load3c(sb + A_TAIL + st * A_WT, &tm.wt, col + 64, row, 0, full1 + 8 * st);
          }
          __syncwarp();
        }
        if (r == 0 && elect_one())
          for (int j = 0; j < 3; j++)
            asm volatile("cp.async.bulk.prefetch.L2.global [%0], %1;" :: "l"((const char*)wqkv + cta * 55296 + (w * 3 + j) * 6144), "r"(6144) : "memory");
        __syncwarp();
      }
      bar_sync(8, 96);
    }
    const unsigned epoch = lds32(sb + A_BAR + 376);
    if (w == 2 && cta < NH) {
      if (lead) {
        int avail = 0, q = 0, ph = 1;
#pragma unroll 1
        for (int seg = 0; seg < NAUXSEG; seg++) {
          const unsigned char* const src = g_seg + ((size_t)(AX & 128 ? 0 : seg % NRING) * 96 + cta * 3) * SEGB;
          SSTAMP(0, seg);
          const int ref = seg + max(LAG0 * (LEND - seg) / LEND, 0);
          if (ref >= avail) {
            const unsigned* const c = &g_scnt[(ref * 32 + cta) * 8];
            const int c2 = ldg_relaxed32(c + 512) - 3 * (epoch + 1), c0 = ldg_acquire32(c) - 3 * (epoch + 1);
            avail = ref + (c2 >= 0 && LA ? 3 : 1);
            if (c0 < 0) {
              wait_count(c, 3 * (epoch + 1), !(TL & 2) || seg < NAUXSEG - 2);
              if (FDLY && seg < FEND) wait_until(gtime() + FDLY);
            }
          }
          SSTAMP(1, seg);
          const uint32_t mb = fullq + q * 8;
          mbar_wait(emptyq + q * 8, q == 2 ? ph ^ 1 : ph);
          if (AX & 8) mbar_arrive(mb); else mbar_expect(mb, A_INS);
#pragma unroll 1
          for (int r = 0; r < ((AX & 8) ? 0 : 3); r++)
            asm volatile("cp.async.bulk.shared::cluster.global.mbarrier::complete_tx::bytes [%0], [%1], %2, [%3];"
                         :: "r"(sb + (q < 2 ? A_IN + q * A_INS : 3 * XT) + r * 9216), "l"(src + r * SEGB), "r"(r < 2 ? 9216 : SEGB), "r"(mb) : "memory");
          if (seg == 1) wait_count(&g_abar[32], NAUX * (epoch + 1));
          if (seg > 1) stg_relaxed32(&g_used[cta * 32], epoch * NSEG + seg + 1 - NQ);
          if (++q == NQ) { q = 0; ph ^= 1; }
        }
      }
      return;
    }
    if (w == 3) {
#pragma unroll 1
      for (int c = 0; c < 4; c++) {
        if (lead) asm volatile("cp.async.bulk.wait_group.read 0;" ::: "memory");
        __syncwarp();
        bar_arrive(11, 160); bar_arrive(12, 160);
#pragma unroll 1
        for (int g = 0; g < 2; g++) {
          bar_sync(13 + g, 160);
          if (lead) {
            asm volatile("cp.async.bulk.tensor.3d.global.shared::cta.bulk_group [%0, {%2, %3, %4}], [%1];"
                         :: "l"(&tm.oa), "r"(sb + A_EPI + g * A_EPW + 1024), "r"(4096 + hh * 288 + c * 72), "r"(g), "r"(57 * tile) : "memory");
            asm volatile("cp.async.bulk.commit_group;" ::: "memory");
          }
        }
      }
      if (lead) publish(&g_abar[32]);
      __syncwarp();
    }
    if ((w & 1) && cta < NH) {
#pragma unroll 1
      for (int seg = w >> 1; seg < NAUXSEG; seg += 2) {
        bar_sync(w == 1 ? 4 : 15, 160);
        if (lead) {
          if (PUB == 0 || seg >= NAUXSEG - 2) publish(&g_ocnt[seg * 64 + 2 * cta / 9 * 8]);
          else {
            if (PUB == 1) asm volatile("fence.acq_rel.gpu;" ::: "memory"); else if (PUB > 2) wait_until(gtime() + PUB);
            asm volatile("red.relaxed.gpu.global.add.u32 [%0], 1;" :: "l"(&g_ocnt[seg * 64 + 2 * cta / 9 * 8]) : "memory");
          }
          if (2 * cta / 9 != (2 * cta + 1) / 9) asm volatile("red.relaxed.gpu.global.add.u32 [%0], 1;" :: "l"(&g_ocnt[seg * 64 + (2 * cta + 1) / 9 * 8]) : "memory");
          SSTAMP(9, seg);
        }
        __syncwarp();
      }
    }
    if (w & 1) return;
    if (w == 0) {
      if (lead) {
        mbar_expect(fullw, 18 * 8192 + 2048);
#pragma unroll 1
        for (int k = 0; k < 18; k++) {
          const int g = k / 9, kb = p3_k(g) * 9 + k - 9 * g;
          if (kb < 64) tma_load(sb + k * 8192, &tm.wob, p3_n(g) * 64, kb * 64, fullw);
          else tma_load(sb + k * 8192, &tm.woa, p3_n(g) * 64, (kb - 64) * 64, fullw);
        }
        for (int g = 0; g < 2; g++) tma_load(sb + A_XW + g * 2048, &tm.wo8, p3_n(g) * 64, 512 + p3_k(g) * 8, fullw);
      }
      __syncwarp();
    }
    bar_sync(6, cta >= NH ? 320 : 288);
    if (lead) {
      if (NQ == 3) for (int i = 0; i < 4; i++) mbar_arrive(emptyq + 16);
      wait_count(&g_abar[32], NAUX * (epoch + 1));
      int avail = 0, sl = w >> 1, ph = 1;
      const int ke = p3_k(w >> 1);
      const unsigned nheads = (ke < 7 ? 5 : 1) * (epoch + 1);
#pragma unroll 1
      for (int seg = 0; seg < NAUXSEG; seg++) {
        bool waited = false;
        if (seg >= avail) {
          const unsigned* const c = &g_ocnt[seg * 64 + ke * 8];
          const int c2 = ldg_relaxed32(c + 128) - nheads, c1 = ldg_relaxed32(c + 64) - nheads, c0 = ldg_acquire32(c) - nheads;
          waited = c0 < 0;
          if (waited) { wait_count(c, nheads, !(TL & 2) || seg < NAUXSEG - 2); if (PDLY && seg < FEND) wait_until(gtime() + PDLY); }
          else if (c1 >= 0) avail = seg + (c2 >= 0 ? 3 : 2);
        }
        SSTAMP(5, seg);
        mbar_wait(empty3 + 8 * sl, ph);
        if (AX & 4) mbar_arrive(full3 + 8 * sl);
        else {
          mbar_expect(full3 + 8 * sl, XT + 512);
          tma_load3c(sb + sl * XT, &tm.o3, 0, seg * 32, ke * 9, full3 + 8 * sl);
          tma_load(sb + A_XT + sl * 512, &tm.o8, 72 * 64 + ke * 8, seg * 32, full3 + 8 * sl);
        }
        p3_next(sl, ph);
      }
    }
  } else if (wg == 2) {
    asm volatile("setmaxnreg.dec.sync.aligned.u32 88;");
    {
      const unsigned epoch = *(volatile unsigned*)&g_epoch2;
      if ((tid & 127) < 80) { const uint4 g = __ldg((const uint4*)gate_w + min(tid & 127, 71)); sts128(sb + A_GW + (tid & 127) * 16, g.x, g.y, g.z, g.w); }
      fence_async();
      bar_sync(3, 128);
      float gt[2][4];
      const uint32_t d0 = (sb & 0x3FFFF) >> 4;
#pragma unroll 1
      for (int j = 0; j < 3; j++) {
        mbar_wait(fullx + 8 * j, 0);
        WG_FENCE();
#pragma unroll
        for (int k = 0; k < 24; k++)
          wgmma_n8_ss(gt[k & 1], desc_at(d0 + (k & 1) * (A_XH >> 4) + j * 1536 + (k >> 3) * 512 + (k & 6), 16, 1024, 1), desc_at(d0 + (A_GW >> 4) + j * 24 + (k & 30), 16, 128, 0), j | (k >> 1));
        WG_COMMIT();
      }
      WG_WAIT(0);
      if ((lane & 3) == 0)
#pragma unroll
        for (int i = 0; i < 4; i++) {
          const float gv = 1.f / (1.f + __expf(-gt[i >> 1][(i & 1) * 2]));
          const int r = w * 16 + (lane >> 2) + (i & 1) * 8, tok = 2 * (57 * tile - 7 + r) + (i >> 1);
          sts32(sb + A_GATE + ((i >> 1) * 64 + r) * 4, __float_as_uint(gv));
          if (hh == 0 && r >= 7 && tok < S_LEN) g_gate[tok] = gv;
        }
      if (tid == 256) sts32(sb + A_BAR + 376, epoch);
      __syncwarp();
      bar_arrive(7, 384);
      __half2 hw = __float2half2_rn(0.f);
#pragma unroll
      for (int i = 0; i < 9; i++) { const uint4 v = __ldg((const uint4*)woa + cta * 1152 + i * 128 + (tid & 127)); hw = amax4(hw, &v.x); }
      const uint32_t ew = wexp(hw);
      if (lane == 0) atomicMax(&g_amax[0], (unsigned long long)(epoch + 1) << 32 | ew);
      bar_sync(3, 128);
      if (tid == 256) {
        count_up(&g_abar[0]);
        wait_count(&g_abar[0], NAUX * (epoch + 1));
        if (cta == 0) *(volatile unsigned*)&g_epoch2 = epoch + 1;
      }
      __syncwarp();
      bar_sync(3, 128);
    }
    if (cta < NH) {
      const int lim = w * 8 + (lane >> 2) - 2 * (lane & 3);
      int q = 0, ph = 0;
      uint32_t p[5][4];
#pragma unroll
      for (int n = 0; n < 10; n++) p[n >> 1][1 + (n & 1)] = __shfl_sync(0xffffffffu, lane ^ n, n);
#pragma unroll 1
      for (int seg = 0; seg < NAUXSEG; seg++) {
        const float gt = __ldcg(&g_gate[seg * 32 + w * 8 + (lane >> 2)]);
        float sc[20], d[32];
        const uint32_t d0 = ((sb & 0x3FFFF) + (q < 2 ? A_IN + q * A_INS : 3 * XT)) >> 4;
        mbar_wait(fullq + q * 8, ph);
        if (tid == 256) SSTAMP(2, seg);
        WG_FENCE();
#pragma unroll
        for (int k = 0; k < 8; k++) {
          const int o = ((k >> 2) * 9216 + (k & 3) * 256) >> 4;
          wgmma_n40_ss_tt(sc, desc_at(d0 + o, 128, 512, 0), desc_at(d0 + o + 256, 128, 1024, 0), k > 0);
        }
        WG_COMMIT();
        WG_WAIT(0);
        if (tid == 256) SSTAMP(12, seg);
        float a[10];
#pragma unroll
        for (int i = 0; i < 10; i++) {
          a[i] = sc[(i >> 1) * 4 + (i & 1)] * (SM_SCALE * LOG2E);
          if (i < 8 && (i >> 1) * 8 + (i & 1) > lim) a[i] = -1.0e9f * LOG2E;
        }
        float m = max10(a);
        m = fmaxf(m, __shfl_xor_sync(0xffffffffu, m, 1)); m = fmaxf(m, __shfl_xor_sync(0xffffffffu, m, 2));
#pragma unroll
        for (int i = 0; i < 10; i++) a[i] = ex2(a[i] - m);
#pragma unroll
        for (int n = 0; n < 5; n++) {
          p[n][0] = pack_bf16(a[2 * n], a[2 * n + 1]); p[n][3] = p[n][0] | p[n][1];
          asm volatile("" : "+r"(p[n][0]), "+r"(p[n][3]) :: "memory");
        }
        float sum = ((a[0] + a[1]) + (a[2] + a[3])) + ((a[4] + a[5]) + (a[6] + a[7])) + (a[8] + a[9]);
        sum += __shfl_xor_sync(0xffffffffu, sum, 1);
        if (tid == 256) SSTAMP(3, seg);
        WG_FENCE();
#pragma unroll
        for (int n = 0; n < 5; n++) wgmma_n64_rs(d, p[n], n < 4 ? desc_at(d0 + 1152 + 8 * n, 4096, 512, 0) : desc_at(d0 + 1152 + 512, 1024, 128, 0), n);
        WG_COMMIT();
        sum += __shfl_xor_sync(0xffffffffu, sum, 2);
        const float f = (1.f - gt) * rcp(sum);
        WG_WAIT(0);
        if (lane == 0) mbar_arrive(emptyq + q * 8);
        if (++q == NQ) { q = 0; ph ^= 1; }
        if (tid == 256) SSTAMP(4, seg);
        unsigned char* const o = (unsigned char*)(g_Ocat + (size_t)(seg * 32 + w * 8 + (lane >> 2)) * KCAT + cta * DH) + (lane & 1) * 12 + (lane & 3) * 4;
#pragma unroll
        for (int n = 0; n < 8; n++) {
          const float* const v = d + (n & 3) * 8 + (n >> 2) * 2;
          const uint32_t x = pack_bf16(v[0] * f, v[1] * f), y = pack_bf16(v[4] * f, v[5] * f), z = __shfl_xor_sync(0xffffffffu, lane & 1 ? x : y, 1);
          if (!(AX & 32)) asm volatile("st.relaxed.gpu.global.v2.b32 [%0], {%1,%2};" :: "l"(o + n * 32), "r"(lane & 1 ? z : x), "r"(lane & 1 ? y : z) : "memory");
        }
        if (tid == 256) SSTAMP(13, seg);
        bar_sync(seg & 1 ? 15 : 4, 160);
      }
    }
  } else {
    asm volatile("setmaxnreg.inc.sync.aligned.u32 200;");
    {
      const int g = lane >> 2, t = lane & 3;
      const uint32_t eb = sb + A_EPI + wg * A_EPW, d0 = (sb & 0x3FFFF) >> 4;
      const uint32_t own = (2 * t <= g ? 0xffffu : 0u) | (2 * t < g ? 0xffff0000u : 0u);
      const int kmin = 7 - 57 * tile - 16 * w;
      __half2 ho = __float2half2_rn(0.f);
#pragma unroll 1
      for (int c = 0; c < 4; c++) {
        float acc[96], tl[12];
#pragma unroll 1
        for (int r = 0; r < 4; r++) {
#pragma unroll
          for (int st = 0; st < A_NS; st++) {
            const int ks = r * 9 + st;
            if (c == 0 && st % 3 == 0 && ks % 12 == 0) mbar_wait(fullx + 8 * (ks / 12), 0);
            mbar_wait(full1 + 8 * st, r & 1);
            const uint64_t da = desc_at(d0 + wg * (A_XH >> 4) + (ks >> 2) * 512 + (ks & 3) * 2, 16, 1024, 1);
            WG_FENCE();
            wgmma_n192_ss_nt(acc, da, desc_at(d0 + ((A_RING + st * A_WM) >> 4), 2048, 1024, 1), ks);
            if (!(AX & 2)) wgmma_n24_ss_nt(tl, da, desc_at(d0 + ((A_TAIL + st * A_WT) >> 4), 128, 256, 0), ks);
            WG_COMMIT();
            if (st == 0 && r == 2) bar_sync(11 + wg, 160);
            WG_WAIT(1);
            if (ks > 0 && lane == 0) mbar_arrive(empty1 + 8 * ((st + A_NS - 1) % A_NS));
          }
        }
        WG_WAIT(0);
        if (lane == 0) mbar_arrive(empty1 + 8 * (A_NS - 1));
        ASTAMP(16 + (c & 3));
        uint32_t ql[9], qh[9], kl[9], kh[9], kx[10], vl[9], vh[9], vx[10];
#pragma unroll
        for (int j = 0; j < 9; j++) {
          const float* const q = j < 8 ? acc + 4 * j : tl, * const k = j < 8 ? acc + 32 + 4 * j : tl + 4, * const v = j < 8 ? acc + 64 + 4 * j : tl + 8;
          kh[j] = pack_bf16(k[2], k[3]); vh[j] = pack_bf16(v[2], v[3]);
          ql[j] = pack_bf16(q[0], q[1]); qh[j] = pack_bf16(q[2], q[3]); kl[j] = pack_bf16(k[0], k[1]); vl[j] = pack_bf16(v[0], v[1]);
        }
        if (w < 3) {
          const uint32_t ha = eb + 1024 + w * 2304 + lane * 16;
          stsm4(ha, kh[0], kh[1], kh[2], kh[3]); stsm4(ha + 512, kh[4], kh[5], kh[6], kh[7]);
          stsm4(ha + 1024, vh[0], vh[1], vh[2], vh[3]); stsm4(ha + 1536, vh[4], vh[5], vh[6], vh[7]);
          asm volatile("stmatrix.sync.aligned.m8n8.x2.shared.b16 [%0], {%1,%2};" :: "r"(ha + 2048), "r"(kh[8]), "r"(vh[8]) : "memory");
        }
        if (c == 0) bar_sync(7, 384); else bar_sync(1 + wg, 128);
        {
          const uint32_t ha = eb + 1024 + max(w - 1, 0) * 2304 + lane * 16;
          ldsm4(kx, ha); ldsm4(kx + 4, ha + 512); ldsm4t(vx, ha + 1024); ldsm4t(vx + 4, ha + 1536);
          asm volatile("ldmatrix.sync.aligned.m8n8.x1.shared.b16 {%0}, [%1];" : "=r"(kx[8]) : "r"(ha + 2048) : "memory");
          asm volatile("ldmatrix.sync.aligned.m8n8.x1.trans.shared.b16 {%0}, [%1];" : "=r"(vx[8]) : "r"(ha + 2176) : "memory");
        }
        const float gl = __uint_as_float(lds32(sb + A_GATE + (wg * 64 + w * 16 + g) * 4)), gh = __uint_as_float(lds32(sb + A_GATE + (wg * 64 + w * 16 + g + 8) * 4));
#pragma unroll
        for (int j = 0; j < 9; j++) { vl[j] = movm(vl[j]); vh[j] = movm(vh[j]); }
        bar_sync(1 + wg, 128);
        uint32_t ol[9], oh[9];
#pragma unroll
        for (int i = 0; i < 4; i++) {
          const int b = 2 * i;
          const uint32_t a[4] = {t >= i ? ql[b] : 0u, t >= i ? qh[b] : 0u, ql[b + 1], qh[b + 1]}, a4 = t <= i ? ql[b + 2] : 0u, a5 = t <= i ? qh[b + 2] : 0u;
          float sx[4], sl[4], sh[4];
          mma16816z(sx, a, kx[b], kx[b + 1]); mma16816z(sl, a, kl[b], kl[b + 1]); mma16816z(sh, a, kh[b], kh[b + 1]);
          mma1688(sx, a4, a5, kx[b + 2]); mma1688(sl, a4, a5, kl[b + 2]); mma1688(sh, a4, a5, kh[b + 2]);
          float e[4];
#pragma unroll
          for (int u = 0; u < 4; u++) {
            const int cc = 2 * t + (u & 1);
            e[u] = (cc <= g ? (u < 2 ? sl[u] : sh[u]) : (u < 2 ? sx[u] : sl[u])) * (0.23570226039551584f * LOG2E);
            if ((cc <= g ? cc : cc - 8) + (u & 2) * 4 < kmin) e[u] = -1.0e9f * LOG2E;
          }
          float m0 = fmaxf(e[0], e[1]), m1 = fmaxf(e[2], e[3]);
#pragma unroll
          for (int o = 1; o < 4; o <<= 1) { m0 = fmaxf(m0, __shfl_xor_sync(0xffffffffu, m0, o)); m1 = fmaxf(m1, __shfl_xor_sync(0xffffffffu, m1, o)); }
          e[0] = ex2(e[0] - m0); e[1] = ex2(e[1] - m0); e[2] = ex2(e[2] - m1); e[3] = ex2(e[3] - m1);
          const uint32_t p0 = pack_bf16(e[0], e[1]), p1 = pack_bf16(e[2], e[3]);
          const uint32_t p[4] = {p0 & ~own, 0u, p0 & own, p1 & ~own};
          float s0 = e[0] + e[1], s1 = e[2] + e[3];
#pragma unroll
          for (int o = 1; o < 4; o <<= 1) { s0 += __shfl_xor_sync(0xffffffffu, s0, o); s1 += __shfl_xor_sync(0xffffffffu, s1, o); }
          const float f0 = gl * rcp(s0), f1 = gh * rcp(s1);
#pragma unroll
          for (int j = b; j < b + 3; j++) {
            float o[4];
            mma16816z(o, p, vx[j], vl[j]);
            mma1688(o, 0u, p1 & own, vh[j]);
            const uint32_t lo = pack_bf16(o[0] * f0, o[1] * f0), hi = pack_bf16(o[2] * f1, o[3] * f1);
            if (j > b || i == 0) { ol[j] = lo; oh[j] = hi; }
            else { ol[j] = t >= i ? lo : ol[j]; oh[j] = t >= i ? hi : oh[j]; }
          }
        }
        const uint32_t sa = eb + 16 + (w * 16 + (lane & 15)) * 144 + (lane >> 4) * 16;
#pragma unroll
        for (int j = 0; j < 8; j += 2) stsm4(sa + j * 16, ol[j], oh[j], ol[j + 1], oh[j + 1]);
        asm volatile("stmatrix.sync.aligned.m8n8.x2.shared.b16 [%0], {%1,%2};" :: "r"(sa + 128), "r"(ol[8]), "r"(oh[8]) : "memory");
        ho = amax4(amax4(amax4(amax4(ho, ol), ol + 4), oh), oh + 4);
        ho = __hmax2_nan(__hmax2_nan(ho, __habs2(*(const __half2*)&ol[8])), __habs2(*(const __half2*)&oh[8]));
        if (c == 3 && tile == 17) {
          const uint32_t eo = wexp(ho);
          if (lane == 0) atomicMax(&g_amax[16], (unsigned long long)(lds32(sb + A_BAR + 376) + 1) << 32 | eo);
        }
        fence_async();
        bar_arrive(13 + wg, 160);
        ASTAMP(20 + (c & 3));
      }
    }
    ASTAMP(3);
    uint32_t wa[36][4];
    mbar_wait(fullw, 0);
    const uint32_t la = sb + wg * 73728 + ((lane & 7) + ((lane >> 4) << 3)) * 128 + (((2 * w + ((lane >> 3) & 1)) ^ (lane & 7)) << 4);
#pragma unroll
    for (int k = 0; k < 36; k++) ldsm4t(wa[k], la + k * 2048);
    sts64(sb + A_XW + wg * 2048 + 1024 + (tid & 127) * 8, 0, 0);
    fence_async();
    bar_arrive(6, cta >= NH ? 320 : 288);
    bar_sync(1 + wg, 128);
    ASTAMP(4);
    const int nsl = p3_n(wg), ke = p3_k(wg), t = lane & 3;
    const unsigned epoch = lds32(sb + A_BAR + 376);
    uint2* const part = g_part + nsl * 4096 + w * 16 + (lane >> 2) * 2 + (t & 1);
    auto tag = [&](int seg) { return PR == 8 ? ((seg >> 3) + 1 + (epoch & (seg >> 1) & (seg >> 2))) & 1 : ((seg >> 2) + 1 + (epoch & (seg >> 1))) & 1; };
    uint2 v[4];
    auto fetch = [&](int seg) {
#pragma unroll
      for (int j = 0; j < 4; j++)
        asm volatile("ld.relaxed.gpu.global.v2.b32 {%0,%1}, [%2];" : "=r"(v[j].x), "=r"(v[j].y) : "l"(part + (seg & (PR - 1)) * 36864 + ke * 512 + ((t >> 1) * 4 + j) * 64) : "memory");
    };
    auto finish = [&](int seg) {
      int n = 0;
#pragma unroll 1
      while (!(AX & 16) && __any_sync(0xffffffffu, (((v[0].x ^ tag(seg)) | (v[1].x ^ tag(seg)) | (v[2].x ^ tag(seg)) | (v[3].x ^ tag(seg))) & 1) != 0) && ++n < SPIN_LIMIT) {
        if (seg < NAUXSEG - ((TL & 2) ? 2 : 1)) __nanosleep(100);
        fetch(seg);
      }
      const float a0 = (bf_lo(v[0].x) + bf_lo(v[1].x)) + (bf_lo(v[2].x) + bf_lo(v[3].x)), a1 = (bf_hi(v[0].x) + bf_hi(v[1].x)) + (bf_hi(v[2].x) + bf_hi(v[3].x));
      const float b0 = (bf_lo(v[0].y) + bf_lo(v[1].y)) + (bf_lo(v[2].y) + bf_lo(v[3].y)), b1 = (bf_hi(v[0].y) + bf_hi(v[1].y)) + (bf_hi(v[2].y) + bf_hi(v[3].y));
      const float c0 = (t < 2 ? a0 : b0) + __shfl_xor_sync(0xffffffffu, t < 2 ? b0 : a0, 2), c1 = (t < 2 ? a1 : b1) + __shfl_xor_sync(0xffffffffu, t < 2 ? b1 : a1, 2);
      ((uint32_t*)(out + (size_t)(seg * 32 + ke * 4 + ((lane >> 2) & 3)) * DM + nsl * 64 + w * 16 + (lane >> 4) * 8))[t] = movm(pack_bf16(c0, c1));
    };
    float acc[16];
    if (AX & 64) for (int i = 0; i < 16; i++) acc[i] = 0.f;
    int done = 0, sl = cta < NH ? 0 : wg, ph = 0;
    const uint32_t d0 = (sb & 0x3FFFF) >> 4;
#pragma unroll 1
    for (int seg = 0; seg < NAUXSEG; seg++) {
      if (DRAIN) {
#pragma unroll 1
        while (done < seg && !mbar_test(full3 + 8 * sl, ph)) { fetch(done); finish(done); done++; }
      }
      mbar_wait(full3 + 8 * sl, ph);
      if (SER && !(AX & 64) && (wg == 1 || seg > 0)) bar_sync(10 - wg, 256);
      if (tid == 128) SSTAMP(6, seg);
      if (!(AX & 16)) fetch(done);
      if (!(AX & 64)) {
        const uint64_t db = desc_at(d0 + sl * (XT >> 4), 16, 1024, 1);
        WG_FENCE();
        wgmma_n32_ss_tn(acc, desc_at(d0 + ((A_XW + wg * 2048) >> 4), 8192, 1024, 1), desc_at(d0 + (A_XT >> 4) + sl * 32, 0, 128, 0), 0);
#pragma unroll
        for (int k = 0; k < 36; k++) {
          wgmma_n32_rs(acc, wa[k][0], wa[k][1], wa[k][2], wa[k][3], db + (k >> 2) * 256 + (k & 3) * 2, 1);
          if (SER && k == SER && (wg == 0 || seg < NAUXSEG - 1)) bar_arrive(9 + wg, 256);
        }
        WG_COMMIT();
      }
      if (done <= seg - PL) finish(done++);
      WG_WAIT(0);
      if (lane == 0) mbar_arrive(empty3 + 8 * sl);
      p3_next(sl, ph);
#pragma unroll
      for (int j = 0; j < 4; j++)
        if (!(AX & 16) || acc[4 * j] == 1.2345678f)
          asm volatile("st.relaxed.gpu.global.v2.b32 [%0], {%1,%2};" :: "l"(part + (seg & (PR - 1)) * 36864 + (2 * j + (t >> 1)) * 512 + ke * 64),
                       "r"((pack_bf16(acc[4 * j], acc[4 * j + 1]) & ~1u) | tag(seg)), "r"(pack_bf16(acc[4 * j + 2], acc[4 * j + 3])) : "memory");
      if (tid == 128) SSTAMP(7, seg);
      if (tid == 128) SSTAMP(8, seg);
      if ((seg & 7) == 6) ASTAMP(5 + (seg >> 3));
    }
#pragma unroll 1
    for (; done < NAUXSEG; done++) { fetch(done); finish(done); }
    ASTAMP(13);
    TSTAMP(48);
  }
}

typedef CUresult (*EncodeFn)(CUtensorMap*, CUtensorMapDataType, cuuint32_t, void*, const cuuint64_t*, const cuuint64_t*,
                             const cuuint32_t*, const cuuint32_t*, CUtensorMapInterleave, CUtensorMapSwizzle,
                             CUtensorMapL2promotion, CUtensorMapFloatOOBfill);
static void make_map(EncodeFn enc, CUtensorMap* m, const void* p, int rows, int cols, int box_rows) {
  cuuint64_t dims[2] = {(cuuint64_t)cols, (cuuint64_t)rows};
  cuuint64_t strides[1] = {(cuuint64_t)cols * 2};
  cuuint32_t box[2] = {64, (cuuint32_t)box_rows};
  cuuint32_t es[2] = {1, 1};
  enc(m, CU_TENSOR_MAP_DATA_TYPE_BFLOAT16, 2, (void*)p, dims, strides, box, es, CU_TENSOR_MAP_INTERLEAVE_NONE,
      CU_TENSOR_MAP_SWIZZLE_128B, CU_TENSOR_MAP_L2_PROMOTION_L2_128B, CU_TENSOR_MAP_FLOAT_OOB_FILL_NONE);
}

constexpr int g_poll = POLL_NS;
extern "C" void kernel_launch(void* const* d_in, const int* in_sizes, int n_in, void* d_out, int out_size) {
  const bf16* x = (const bf16*)d_in[0];
  const bf16* wqkvA = (const bf16*)d_in[1];
  const bf16* woA = (const bf16*)d_in[2];
  const bf16* mem0 = (const bf16*)d_in[4];
  const bf16* Wq = (const bf16*)d_in[5];
  const bf16* Wk = (const bf16*)d_in[6];
  const bf16* Wv = (const bf16*)d_in[7];
  const bf16* Wo = (const bf16*)d_in[8];
  const bf16* gate_w = (const bf16*)d_in[10];
  static EncodeFn enc = nullptr;
  static void *pO = nullptr, *pR = nullptr;
  if (!enc) {
    cudaDriverEntryPointQueryResult qr;
    cudaGetDriverEntryPoint("cuTensorMapEncodeTiled", (void**)&enc, cudaEnableDefault, &qr);
    cudaGetSymbolAddress(&pO, g_Ocat);
    cudaGetSymbolAddress(&pR, g_red_raw);
    cudaFuncSetAttribute(rec_kernel, cudaFuncAttributeMaxDynamicSharedMemorySize, SM_TOTAL);
    cudaFuncSetAttribute(aux_kernel, cudaFuncAttributeMaxDynamicSharedMemorySize, A_TOTAL);
  }
  RMaps rm;
  rm.poll = g_poll; rm.out = (bf16*)d_out;
  make_map(enc, &rm.woa, woA, DM, DM, 24);
  {
    cuuint64_t dims[2] = {KCAT, S_LEN}, strides[1] = {KCAT * 2};
    cuuint32_t box[2] = {32, 64}, es[2] = {1, 1};
    enc(&rm.oa, CU_TENSOR_MAP_DATA_TYPE_BFLOAT16, 2, pO, dims, strides, box, es, CU_TENSOR_MAP_INTERLEAVE_NONE,
        CU_TENSOR_MAP_SWIZZLE_NONE, CU_TENSOR_MAP_L2_PROMOTION_NONE, CU_TENSOR_MAP_FLOAT_OOB_FILL_NONE);
  }
  rm.red = (unsigned char*)(((uintptr_t)pR + 262143) & ~(uintptr_t)262143);
  {
    cuuint64_t dims[3] = {64, S_LEN, 9}, strides[2] = {DM * 2, 128};
    cuuint32_t box[3] = {64, 32, 9}, es[3] = {1, 1, 1};
    enc(&rm.x, CU_TENSOR_MAP_DATA_TYPE_BFLOAT16, 3, (void*)x, dims, strides, box, es, CU_TENSOR_MAP_INTERLEAVE_NONE,
        CU_TENSOR_MAP_SWIZZLE_128B, CU_TENSOR_MAP_L2_PROMOTION_L2_128B, CU_TENSOR_MAP_FLOAT_OOB_FILL_NONE);
  }
  make_map(enc, &rm.wq, Wq, DM, 4096, 192);
  make_map(enc, &rm.wk, Wk, DM, 4096, 192);
  make_map(enc, &rm.wv, Wv, DM, 4096, 192);
  make_map(enc, &rm.wo, Wo, 4096, DM, 128);
  AMaps am;
  {
    cuuint32_t es[4] = {1, 1, 1, 1};
    cuuint64_t dx[4] = {64, 2, S_LEN / 2, 9}, sx[3] = {DM * 2, DM * 4, 128};
    cuuint32_t bx[4] = {64, 1, 64, 3};
    enc(&am.x, CU_TENSOR_MAP_DATA_TYPE_BFLOAT16, 4, (void*)x, dx, sx, bx, es, CU_TENSOR_MAP_INTERLEAVE_NONE,
        CU_TENSOR_MAP_SWIZZLE_128B, CU_TENSOR_MAP_L2_PROMOTION_L2_128B, CU_TENSOR_MAP_FLOAT_OOB_FILL_NONE);
    cuuint64_t dw[3] = {DM, DM, 3}, sw[2] = {DM * 6, DM * 2};
    cuuint32_t bw[3] = {64, 16, 3}, bt[3] = {8, 16, 3};
    enc(&am.wa, CU_TENSOR_MAP_DATA_TYPE_BFLOAT16, 3, (void*)wqkvA, dw, sw, bw, es, CU_TENSOR_MAP_INTERLEAVE_NONE,
        CU_TENSOR_MAP_SWIZZLE_128B, CU_TENSOR_MAP_L2_PROMOTION_L2_128B, CU_TENSOR_MAP_FLOAT_OOB_FILL_NONE);
    enc(&am.wt, CU_TENSOR_MAP_DATA_TYPE_BFLOAT16, 3, (void*)wqkvA, dw, sw, bt, es, CU_TENSOR_MAP_INTERLEAVE_NONE,
        CU_TENSOR_MAP_SWIZZLE_NONE, CU_TENSOR_MAP_L2_PROMOTION_NONE, CU_TENSOR_MAP_FLOAT_OOB_FILL_NONE);
    cuuint64_t dz[3] = {KCAT, 2, S_LEN / 2}, sz[2] = {KCAT * 2, KCAT * 4};
    cuuint32_t bz[3] = {72, 1, 57};
    enc(&am.oa, CU_TENSOR_MAP_DATA_TYPE_BFLOAT16, 3, pO, dz, sz, bz, es, CU_TENSOR_MAP_INTERLEAVE_NONE,
        CU_TENSOR_MAP_SWIZZLE_NONE, CU_TENSOR_MAP_L2_PROMOTION_NONE, CU_TENSOR_MAP_FLOAT_OOB_FILL_NONE);
  }
  {
    cuuint64_t dims[3] = {64, S_LEN, KCAT / 64}, strides[2] = {KCAT * 2, 128};
    cuuint32_t box[3] = {64, 32, 9}, es[3] = {1, 1, 1};
    make_map(enc, &am.o, pO, S_LEN, KCAT, 32);
    enc(&am.o3, CU_TENSOR_MAP_DATA_TYPE_BFLOAT16, 3, pO, dims, strides, box, es, CU_TENSOR_MAP_INTERLEAVE_NONE,
        CU_TENSOR_MAP_SWIZZLE_128B, CU_TENSOR_MAP_L2_PROMOTION_L2_128B, CU_TENSOR_MAP_FLOAT_OOB_FILL_NONE);
  }
  make_map(enc, &am.wob, Wo, 4096, DM, 64);
  make_map(enc, &am.woa, woA, DM, DM, 64);
  make_map(enc, &am.wo8, woA, DM, DM, 8);
  {
    cuuint64_t dims[2] = {KCAT, S_LEN}, strides[1] = {KCAT * 2};
    cuuint32_t box[2] = {8, 32}, es[2] = {1, 1};
    enc(&am.o8, CU_TENSOR_MAP_DATA_TYPE_BFLOAT16, 2, pO, dims, strides, box, es, CU_TENSOR_MAP_INTERLEAVE_NONE,
        CU_TENSOR_MAP_SWIZZLE_NONE, CU_TENSOR_MAP_L2_PROMOTION_NONE, CU_TENSOR_MAP_FLOAT_OOB_FILL_NONE);
  }

  rec_kernel<<<96, 384, SM_TOTAL, cudaStreamPerThread>>>(rm, x, mem0);
  cudaLaunchConfig_t cfg = {};
  cfg.gridDim = dim3(NAUX); cfg.blockDim = dim3(512); cfg.dynamicSmemBytes = A_TOTAL; cfg.stream = cudaStreamPerThread;
  cudaLaunchAttribute at[1];
  at[0].id = cudaLaunchAttributeProgrammaticStreamSerialization; at[0].val.programmaticStreamSerializationAllowed = 1;
  cfg.attrs = at; cfg.numAttrs = 1;
  if (XP & 16) cfg.numAttrs = 0;
  if (!(XP & 64)) cudaLaunchKernelEx(&cfg, aux_kernel, am, wqkvA, woA, gate_w, (bf16*)d_out);
}
```

```cpp
#include <cuda_runtime.h>
#include <cuda_bf16.h>
#include <cuda_fp16.h>
#include <cuda.h>
#include <stdint.h>

typedef __nv_bfloat16 bf16;

constexpr int S_LEN = 2048, DM = 576, NH = 32, DH = 128, NSEG = 64, KCAT = 4096 + 576;
constexpr int NAUXSEG = NSEG - 2;
constexpr int NAUX = 36;
#define RED_LINE(i) (((i) >> 2) * 4096 + ((i) & 1) * 256 + ((i) & 2) * 512)
#define RED_SLOT(s) (((s) & 1) * 128 + ((s) & 2) * 256)

#define POLL_NS 880
#define NII 18
#define W3PRE 4
#define W3MID 4
#define GF 0
#define B5POS 0
#define NUP 4
#define UPF 1
#define B3Q 9
#define B3F 0
#define GATE 7
#define NTL 2
#define B7R 1
#define VS0 1
#define VS1 0
#define VLATE(w) ((w) == 0 ? VS0 == 1 : (w) == 1 ? VS1 == 1 : false)
#define HOIST 0
#define RSLOW 0
#define CSY 0
#define DD 2
#define N12 18
#define N14 18
#define HP 0
#define HL 0
#define WL 1
#define RV 3
#define EXM 1
#define PSTAMP 0
#define PFIX 0
#define RET 1
#define TL 6
#define CLR 1
#define RFW 0
#define NIC 0
#define LEAD 0
#define FIN16 1
#define VXG 0
#define NRING 20
#define EXD 0
#define HDLY 0
#define F10 1
#define NPROBE 2
#define QM 0
#define N5 224
#define KP(i) (((i) >> 1) + 4 * ((i) & 1))
#define SPIN_LIMIT (1 << 14)
#define XP 0

__device__ __align__(1024) bf16 g_Ocat[S_LEN * KCAT];
__device__ __align__(1024) unsigned char g_red_raw[2 * 262144];
constexpr int HINT_OFF = 2048;
__device__ __align__(16) float g_gate[S_LEN];
__device__ __align__(128) uint4 g_stats[96 * 2];
__device__ unsigned g_epoch;
__device__ unsigned g_epoch2;
__device__ unsigned g_ocnt[NSEG * 64];
__device__ unsigned g_abar[3 * 32];
__device__ unsigned long long g_amax[2 * 16];
__device__ unsigned g_scnt[NSEG * 32 * 8];
__device__ __align__(1024) unsigned char g_seg[NRING * 96 * 10240];
__device__ unsigned g_used[NH * 32];
__device__ __align__(1024) uint2 g_part[8 * 9 * 64 * 64];
__device__ int g_err;
#define MSTAMP(i)
#define TSTAMP(i)
#define PROF(idx)
#define PROFP(idx)
#define RSTAMP(k)
#define STAMP(idx)
#define ASTAMP(idx)
#define SSTAMP(k, seg)
#define WSTAMP(idx)

#define DI __device__ __forceinline__
DI uint32_t smem_u32(const void* p) { return (uint32_t)__cvta_generic_to_shared(p); }
DI uint32_t clock32() { uint32_t c; asm volatile("mov.u32 %0, %%clock;" : "=r"(c) :: "memory"); return c; }
DI uint32_t gtime() { uint32_t c; asm volatile("mov.u32 %0, %%globaltimer_lo;" : "=r"(c) :: "memory"); return c; }
DI uint32_t ldg_relaxed32(const void* p) { uint32_t v; asm volatile("ld.relaxed.gpu.global.b32 %0, [%1];" : "=r"(v) : "l"(p) : "memory"); return v; }
DI uint32_t ldg_acquire32(const void* p) { uint32_t v; asm volatile("ld.acquire.gpu.global.b32 %0, [%1];" : "=r"(v) : "l"(p) : "memory"); return v; }
DI void stg_relaxed32(void* p, uint32_t v) { asm volatile("st.relaxed.gpu.global.b32 [%0], %1;" :: "l"(p), "r"(v) : "memory"); }
DI int head_id() { int c; asm volatile("mov.u32 %0, %%clusterid.x;" : "=r"(c)); return c; }
DI uint32_t mapa(uint32_t a, uint32_t r) { uint32_t o; asm("mapa.shared::cluster.u32 %0, %1, %2;" : "=r"(o) : "r"(a), "r"(r)); return o; }
DI void cluster_arrive() { asm volatile("barrier.cluster.arrive.relaxed.aligned;" ::: "memory"); }
DI void cluster_wait() { asm volatile("barrier.cluster.wait.aligned;" ::: "memory"); }
DI void cluster_sync() { asm volatile("barrier.cluster.arrive.release.aligned;\nbarrier.cluster.wait.acquire.aligned;" ::: "memory"); }
DI void mbar_init(uint32_t b, uint32_t c) { asm volatile("mbarrier.init.shared::cta.b64 [%0], %1;" :: "r"(b), "r"(c) : "memory"); }
DI void mbar_expect(uint32_t b, uint32_t tx) { asm volatile("mbarrier.arrive.expect_tx.shared::cta.b64 _, [%0], %1;" :: "r"(b), "r"(tx) : "memory"); }
DI void mbar_arrive(uint32_t b) { asm volatile("mbarrier.arrive.shared::cta.b64 _, [%0];" :: "r"(b) : "memory"); }
DI void mbar_wait(uint32_t b, uint32_t par) {
  asm volatile("{\n.reg .pred p;\n.reg .u32 n, q;\nmov.u32 n, 0;\n"
               "WL: add.u32 n, n, 1;\nshr.u32 q, n, 12;\nxor.b32 q, q, %1;\n"
               "mbarrier.try_wait.parity.shared::cta.b64 p, [%0], q;\n@!p bra.uni WL;\n}"
               :: "r"(b), "r"(par) : "memory");
}
DI bool mbar_test(uint32_t b, uint32_t par) {
  uint32_t r;
  asm volatile("{\n.reg .pred p;\nmbarrier.test_wait.parity.shared::cta.b64 p, [%1], %2;\nselp.u32 %0, 1, 0, p;\n}" : "=r"(r) : "r"(b), "r"(par) : "memory");
  return r;
}
DI void mbar_wait_fast(uint32_t b, uint32_t par) {
  asm volatile("{\n.reg .pred p;\n.reg .u32 n, q;\nmbarrier.try_wait.parity.shared::cta.b64 p, [%0], %1;\n@p bra.uni WD;\nmov.u32 n, 0;\n"
               "WL: add.u32 n, n, 1;\nshr.u32 q, n, 12;\nxor.b32 q, q, %1;\n"
               "mbarrier.try_wait.parity.shared::cta.b64 p, [%0], q;\n@!p bra.uni WL;\nWD:\n}"
               :: "r"(b), "r"(par) : "memory");
}
DI void wait_until(uint32_t t) {
  const uint32_t now = gtime();
  t = min(t, now + 8192);
  asm volatile("{\n.reg .pred p;\n.reg .u32 c;\nTL: mov.u32 c, %%globaltimer_lo;\nsetp.lt.u32 p, c, %0;\n@p bra.uni TL;\n}" :: "r"(t) : "memory");
}
#define PIN(v) v = __shfl_xor_sync(0xffffffffu, v, 0)
#define SCHED_FENCE(k) asm volatile("{\n.reg .pred p;\nsetp.eq.u32 p, %0, %1;\n@p exit;\n}" :: "r"(fence_reg), "r"(k) : "memory")
#define MEM_ORDER(k) asm volatile("{\n.reg .pred p;\nsetp.eq.u32 p, %0, %1;\n@p st.shared.u32 [%0], %0;\n}" :: "r"(fence_reg), "r"(k + 64) : "memory")
DI void bar_sync(int id, int n) { asm volatile("bar.sync %0, %1;" :: "r"(id), "r"(n) : "memory"); }
DI void bar_arrive(int id, int n) { asm volatile("bar.arrive %0, %1;" :: "r"(id), "r"(n) : "memory"); }
DI void fence_async() { asm volatile("fence.proxy.async.shared::cta;" ::: "memory"); }
DI void st_async4(uint32_t a, uint32_t x, uint32_t y, uint32_t z, uint32_t w, uint32_t mb) {
  asm volatile("st.async.weak.shared::cluster.mbarrier::complete_tx::bytes.v4.b32 [%0], {%1,%2,%3,%4}, [%5];"
               :: "r"(a), "r"(x), "r"(y), "r"(z), "r"(w), "r"(mb) : "memory");
}
DI void st_async2(uint32_t a, uint32_t x, uint32_t y, uint32_t mb) {
  asm volatile("st.async.weak.shared::cluster.mbarrier::complete_tx::bytes.v2.b32 [%0], {%1,%2}, [%3];"
               :: "r"(a), "r"(x), "r"(y), "r"(mb) : "memory");
}
DI void sts32(uint32_t a, uint32_t x) { asm volatile("st.shared.b32 [%0], %1;" :: "r"(a), "r"(x) : "memory"); }
DI void sts64(uint32_t a, uint32_t x, uint32_t y) { asm volatile("st.shared.v2.b32 [%0], {%1,%2};" :: "r"(a), "r"(x), "r"(y) : "memory"); }
DI void sts128(uint32_t a, uint32_t x, uint32_t y, uint32_t z, uint32_t w) {
  asm volatile("st.shared.v4.b32 [%0], {%1,%2,%3,%4};" :: "r"(a), "r"(x), "r"(y), "r"(z), "r"(w) : "memory");
}
DI uint32_t lds32(uint32_t a) { uint32_t x; asm volatile("ld.shared.b32 %0, [%1];" : "=r"(x) : "r"(a) : "memory"); return x; }
DI void lds64(uint32_t a, uint32_t& x, uint32_t& y) { asm volatile("ld.shared.v2.b32 {%0,%1}, [%2];" : "=r"(x), "=r"(y) : "r"(a) : "memory"); }
DI void lds128(uint32_t a, uint32_t* r) {
  asm volatile("ld.shared.v4.b32 {%0,%1,%2,%3}, [%4];" : "=r"(r[0]), "=r"(r[1]), "=r"(r[2]), "=r"(r[3]) : "r"(a) : "memory");
}
DI void lds128f(uint32_t a, float* r) {
  asm volatile("ld.shared.v4.f32 {%0,%1,%2,%3}, [%4];" : "=f"(r[0]), "=f"(r[1]), "=f"(r[2]), "=f"(r[3]) : "r"(a) : "memory");
}
DI void lds64f(uint32_t a, float* r) { asm volatile("ld.shared.v2.f32 {%0,%1}, [%2];" : "=f"(r[0]), "=f"(r[1]) : "r"(a) : "memory"); }
DI void ldsm4t(uint32_t* r, uint32_t a) {
  asm volatile("ldmatrix.sync.aligned.m8n8.x4.trans.shared.b16 {%0,%1,%2,%3}, [%4];"
               : "=r"(r[0]), "=r"(r[1]), "=r"(r[2]), "=r"(r[3]) : "r"(a) : "memory");
}
DI void ldsm4t_in(uint32_t* r, uint32_t a, uint32_t t) {
  asm volatile("{\n.reg .pred p;\nsetp.ne.u32 p, %5, 0;\n@p ldmatrix.sync.aligned.m8n8.x4.trans.shared.b16 {%0,%1,%2,%3}, [%4];\n}"
               : "+r"(r[0]), "+r"(r[1]), "+r"(r[2]), "+r"(r[3]) : "r"(a), "r"(t) : "memory");
}
DI void lds128_in(uint32_t* r, uint32_t a, uint32_t t) {
  asm volatile("{\n.reg .pred p;\nsetp.ne.u32 p, %5, 0;\n@p ld.shared.v4.b32 {%0,%1,%2,%3}, [%4];\n}"
               : "+r"(r[0]), "+r"(r[1]), "+r"(r[2]), "+r"(r[3]) : "r"(a), "r"(t) : "memory");
}
DI void ldsm2t_in(uint32_t* r, uint32_t a, uint32_t t) {
  asm volatile("{\n.reg .pred p;\nsetp.ne.u32 p, %3, 0;\n@p ldmatrix.sync.aligned.m8n8.x2.trans.shared.b16 {%0,%1}, [%2];\n}" : "+r"(r[0]), "+r"(r[1]) : "r"(a), "r"(t) : "memory");
}
DI void reserve2(uint32_t* r) { asm volatile("{\n.reg .u64 t;\nmov.u64 t, %%clock64;\nmov.b64 {%0, %1}, t;\n}" : "=r"(r[0]), "=r"(r[1])); }
DI void scale_sum(float& x, float& y, float s, uint32_t t) {
  asm volatile("{\n.reg .pred p;\nsetp.ne.u32 p, %2, 0;\n@p mul.f32 %0, %0, %1;\n}" : "+f"(y) : "f"(s), "r"(t));
  asm volatile("{\n.reg .pred p;\nsetp.ne.u32 p, %3, 1;\n@p fma.rn.f32 %0, %0, %1, %2;\n}" : "+f"(x) : "f"(s), "f"(y), "r"(t));
}
DI void ldsm4(uint32_t* r, uint32_t a) {
  asm volatile("ldmatrix.sync.aligned.m8n8.x4.shared.b16 {%0,%1,%2,%3}, [%4];"
               : "=r"(r[0]), "=r"(r[1]), "=r"(r[2]), "=r"(r[3]) : "r"(a) : "memory");
}
DI void st_async1(uint32_t a, uint32_t x, uint32_t mb) {
  asm volatile("st.async.weak.shared::cluster.mbarrier::complete_tx::bytes.b32 [%0], %1, [%2];" :: "r"(a), "r"(x), "r"(mb) : "memory");
}
DI void stsm4(uint32_t a, uint32_t x, uint32_t y, uint32_t z, uint32_t w) {
  asm volatile("stmatrix.sync.aligned.m8n8.x4.shared.b16 [%0], {%1,%2,%3,%4};" :: "r"(a), "r"(x), "r"(y), "r"(z), "r"(w) : "memory");
}
DI void stsm4t(uint32_t a, uint32_t x, uint32_t y, uint32_t z, uint32_t w) {
  asm volatile("stmatrix.sync.aligned.m8n8.x4.trans.shared.b16 [%0], {%1,%2,%3,%4};" :: "r"(a), "r"(x), "r"(y), "r"(z), "r"(w) : "memory");
}
DI uint32_t pack_bf16(float lo, float hi) { uint32_t r; asm("cvt.rn.bf16x2.f32 %0, %1, %2;" : "=r"(r) : "f"(hi), "f"(lo)); return r; }
DI uint32_t pack_f16(float lo, float hi) { uint32_t r; asm("cvt.rn.f16x2.f32 %0, %1, %2;" : "=r"(r) : "f"(hi), "f"(lo)); return r; }
DI float ex2(float x) { float y; asm("ex2.approx.ftz.f32 %0, %1;" : "=f"(y) : "f"(x)); return y; }
DI float rcp(float x) { float y; asm("rcp.approx.ftz.f32 %0, %1;" : "=f"(y) : "f"(x)); return y; }
DI float bf_lo(uint32_t x) { return __uint_as_float(x << 16); }
DI float bf_hi(uint32_t x) { return __uint_as_float(x & 0xffff0000u); }
DI void mma16816(float* d, const uint32_t* a, uint32_t b0, uint32_t b1) {
  asm volatile("mma.sync.aligned.m16n8k16.row.col.f32.bf16.bf16.f32 {%0,%1,%2,%3}, {%4,%5,%6,%7}, {%8,%9}, {%0,%1,%2,%3};"
               : "+f"(d[0]), "+f"(d[1]), "+f"(d[2]), "+f"(d[3]) : "r"(a[0]), "r"(a[1]), "r"(a[2]), "r"(a[3]), "r"(b0), "r"(b1));
}
DI void mma16816z(float* d, const uint32_t* a, uint32_t b0, uint32_t b1) {
  asm volatile("mma.sync.aligned.m16n8k16.row.col.f32.bf16.bf16.f32 {%0,%1,%2,%3}, {%4,%5,%6,%7}, {%8,%9}, {%10,%10,%10,%10};"
               : "=f"(d[0]), "=f"(d[1]), "=f"(d[2]), "=f"(d[3]) : "r"(a[0]), "r"(a[1]), "r"(a[2]), "r"(a[3]), "r"(b0), "r"(b1), "f"(0.f));
}
DI void mma1688z(float* d, uint32_t a0, uint32_t a1, uint32_t b0) {
  asm volatile("mma.sync.aligned.m16n8k8.row.col.f32.bf16.bf16.f32 {%0,%1,%2,%3}, {%4,%5}, {%6}, {%7,%7,%7,%7};"
               : "=f"(d[0]), "=f"(d[1]), "=f"(d[2]), "=f"(d[3]) : "r"(a0), "r"(a1), "r"(b0), "f"(0.f));
}
DI void mma1688(float* d, uint32_t a0, uint32_t a1, uint32_t b0) {
  asm volatile("mma.sync.aligned.m16n8k8.row.col.f32.bf16.bf16.f32 {%0,%1,%2,%3}, {%4,%5}, {%6}, {%0,%1,%2,%3};"
               : "+f"(d[0]), "+f"(d[1]), "+f"(d[2]), "+f"(d[3]) : "r"(a0), "r"(a1), "r"(b0));
}
DI void ldsm2t(uint32_t* r, uint32_t a) {
  asm volatile("ldmatrix.sync.aligned.m8n8.x2.trans.shared.b16 {%0,%1}, [%2];" : "=r"(r[0]), "=r"(r[1]) : "r"(a) : "memory");
}
DI uint32_t add_bf16(uint32_t a, uint32_t b) { uint32_t r; asm("add.rn.bf16x2 %0, %1, %2;" : "=r"(r) : "r"(a), "r"(b)); return r; }
DI uint32_t mul_bf16(uint32_t a, uint32_t b) { uint32_t r; asm("mul.rn.bf16x2 %0, %1, %2;" : "=r"(r) : "r"(a), "r"(b)); return r; }
DI uint64_t make_desc(uint32_t addr, uint32_t lbo, uint32_t sbo, uint32_t swz) {
  return (uint64_t)((addr & 0x3FFFF) >> 4) | ((uint64_t)(lbo >> 4) << 16) | ((uint64_t)(sbo >> 4) << 32) | ((uint64_t)swz << 62);
}
DI uint64_t desc_at(uint32_t a16, uint32_t lbo, uint32_t sbo, uint32_t swz) {
  uint64_t d; asm("mov.b64 %0, {%1, %2};" : "=l"(d) : "r"(a16 + ((lbo >> 4) << 16)), "r"((sbo >> 4) | (swz << 30)));
  return d;
}
#define WG_FENCE() asm volatile("wgmma.fence.sync.aligned;" ::: "memory")
#define WG_COMMIT() asm volatile("wgmma.commit_group.sync.aligned;" ::: "memory")
#define WG_WAIT(n) asm volatile("wgmma.wait_group.sync.aligned %0;" :: "n"(n) : "memory")
#define ACC8(d, o) "+f"(d[o]), "+f"(d[o + 1]), "+f"(d[o + 2]), "+f"(d[o + 3]), "+f"(d[o + 4]), "+f"(d[o + 5]), "+f"(d[o + 6]), "+f"(d[o + 7])
DI void wgmma_n32_rs(float* d, uint32_t a0, uint32_t a1, uint32_t a2, uint32_t a3, uint64_t db, int acc) {
  asm volatile("{\n.reg .pred p;\nsetp.ne.b32 p, %21, 0;\n"
               "wgmma.mma_async.sync.aligned.m64n32k16.f32.bf16.bf16 {%0,%1,%2,%3,%4,%5,%6,%7,%8,%9,%10,%11,%12,%13,%14,%15}, "
               "{%16,%17,%18,%19}, %20, p, 1, 1, 0;\n}\n"
               : ACC8(d, 0), ACC8(d, 8) : "r"(a0), "r"(a1), "r"(a2), "r"(a3), "l"(db), "r"(acc));
}
template <int TA>
DI void wgmma_n32_ss(float* d, uint64_t da, uint64_t db, int acc) {
  asm volatile("{\n.reg .pred p;\nsetp.ne.b32 p, %18, 0;\n"
               "wgmma.mma_async.sync.aligned.m64n32k16.f32.bf16.bf16 {%0,%1,%2,%3,%4,%5,%6,%7,%8,%9,%10,%11,%12,%13,%14,%15}, "
               "%16, %17, p, 1, 1, %19, 1;\n}\n"
               : ACC8(d, 0), ACC8(d, 8) : "l"(da), "l"(db), "r"(acc), "n"(TA));
}
DI void tma_load(uint32_t dst, const CUtensorMap* m, int c0, int c1, uint32_t mb) {
  asm volatile("cp.async.bulk.tensor.2d.shared::cluster.global.mbarrier::complete_tx::bytes [%0], [%1, {%3, %4}], [%2];"
               :: "r"(dst), "l"(m), "r"(mb), "r"(c0), "r"(c1) : "memory");
}
DI void tma_load3(uint32_t dst, const CUtensorMap* m, int row, uint32_t mb) {
  asm volatile("cp.async.bulk.tensor.3d.shared::cluster.global.mbarrier::complete_tx::bytes [%0], [%1, {%3, %4, %3}], [%2];"
               :: "r"(dst), "l"(m), "r"(mb), "r"(0), "r"(row) : "memory");
}
DI bool elect_one() {
  uint32_t p;
  asm volatile("{\n.reg .pred p;\nelect.sync _|p, 0xffffffff;\nselp.u32 %0, 1, 0, p;\n}" : "=r"(p));
  return p;
}
DI void bulk_s2s(uint32_t dst, uint32_t src, uint32_t bytes, uint32_t mb) {
  asm volatile("cp.async.bulk.shared::cluster.shared::cta.mbarrier::complete_tx::bytes [%0], [%1], %2, [%3];"
               :: "r"(dst), "r"(src), "r"(bytes), "r"(mb) : "memory");
}
DI void tma_prefetch(const CUtensorMap* m, int c0, int c1) {
  asm volatile("cp.async.bulk.prefetch.tensor.2d.L2.global.tile [%0, {%1, %2}];" :: "l"(m), "r"(c0), "r"(c1) : "memory");
}
DI void tma_store(const CUtensorMap* m, uint32_t src, int c0, int c1) {
  asm volatile("cp.async.bulk.tensor.2d.global.shared::cta.bulk_group [%0, {%2, %3}], [%1];" :: "l"(m), "r"(src), "r"(c0), "r"(c1) : "memory");
}
DI uint4 ldg_relaxed(const void* p) {
  uint4 v;
  asm volatile("ld.relaxed.gpu.global.v4.b32 {%0,%1,%2,%3}, [%4];" : "=r"(v.x), "=r"(v.y), "=r"(v.z), "=r"(v.w) : "l"(p) : "memory");
  return v;
}
DI void stg_relaxed(void* p, uint32_t x, uint32_t y, uint32_t z, uint32_t w) {
  asm volatile("st.relaxed.gpu.global.v4.b32 [%0], {%1,%2,%3,%4};" :: "l"(p), "r"(x), "r"(y), "r"(z), "r"(w) : "memory");
}
DI void red_f16x8(void* p, uint32_t x, uint32_t y, uint32_t z, uint32_t w) {
  asm volatile("red.relaxed.gpu.global.add.noftz.v4.f16x2 [%0], {%1,%2,%3,%4};" :: "l"(p), "r"(x), "r"(y), "r"(z), "r"(w) : "memory");
}
DI void sq_acc(uint32_t& a, uint32_t x) { asm("fma.rn.bf16x2 %0, %1, %1, %0;" : "+r"(a) : "r"(x)); }
DI __half2 amax4(__half2 h, const uint32_t* v) {
  h = __hmax2_nan(__hmax2_nan(h, __habs2(*(const __half2*)&v[0])), __habs2(*(const __half2*)&v[1]));
  return __hmax2_nan(__hmax2_nan(h, __habs2(*(const __half2*)&v[2])), __habs2(*(const __half2*)&v[3]));
}
DI uint32_t wexp(__half2 h) { const uint32_t u = *(const uint32_t*)&h; return __reduce_max_sync(0xffffffffu, max((u >> 16) & 0x7fffu, u & 0x7fffu)) >> 7; }
DI float max10(const float* a) {
  return fmaxf(fmaxf(fmaxf(fmaxf(a[0], a[1]), fmaxf(a[2], a[3])), fmaxf(fmaxf(a[4], a[5]), fmaxf(a[6], a[7]))), fmaxf(a[8], a[9]));
}
DI float quad_max(float m) {
  return fmaxf(fmaxf(m, __shfl_xor_sync(0xffffffffu, m, 1)), fmaxf(__shfl_xor_sync(0xffffffffu, m, 2), __shfl_xor_sync(0xffffffffu, m, 3)));
}
DI float warp_sum(float v) {
#pragma unroll
  for (int o = 16; o; o >>= 1) v += __shfl_xor_sync(0xffffffffu, v, o);
  return v;
}

constexpr int SM_WO3 = 0;
constexpr int SM_X = 16384;
constexpr int XT = 36864;
constexpr int SM_EXP = 126976;
constexpr int SEGB = 10240;
constexpr int SM_BLK = SM_EXP + 8192;
constexpr int SM_VC = SM_BLK + 4 * SEGB;
constexpr int SM_PART = SM_VC + 16384;
constexpr int SM_QM = SM_PART + 4096;
constexpr int SM_E = SM_QM + 1024;
constexpr int SM_VM = SM_E + 1536;
constexpr int SM_OB = SM_VM + 2048;
constexpr int SM_FB = SM_OB + 2048;
constexpr int SM_STAGE = SM_X + XT;
constexpr int SM_MISC = 210944;
constexpr int SM_WOST = 212992;
constexpr int SM_MEM = SM_WOST;
constexpr int SM_MAX = SM_MEM + 11264;
#define MEM_BLK(q) ((q) / 3 * 4096 + (q) % 3 * 1024)
constexpr int SM_TOTAL = 229376;
constexpr int MB_W = SM_MISC;
constexpr int MB_WO = SM_MISC + 24;
constexpr int MB_WO3 = SM_MISC + 32;
constexpr int MB_X = SM_MISC + 40;
constexpr int MB_S = SM_MISC + 64;
constexpr int MB_F = SM_MISC + 72;
constexpr int MB_VX = SM_MISC + 80;
constexpr int SC_FPAR = SM_MISC + 136;
constexpr int SC_DEAD = SM_MISC + 96;
constexpr int SC_UNSC = SM_MISC + 112;
constexpr int SC_EPOCH = SM_MISC + 128;
constexpr int SC_EXPW = SM_MISC + 132;
constexpr int SC_ONES = SM_MISC + 144;
constexpr int SC_SS = SM_MISC + 160;
constexpr int SC_LAT = SM_MISC + 224;
constexpr int MB_T = SM_MISC + 232;
constexpr int T_SX = SM_X + XT;
constexpr int T_OB = SM_X + 2 * XT;
constexpr int T_WA = T_OB + 16384;
constexpr int T_OA = T_WA + 9216;
constexpr int T_G = T_OA + 4096;
constexpr int T_P = T_G + 512;
constexpr int T_UN = T_G + 256;
constexpr int T_RED = 131072;
constexpr int SC_XMAX = SM_MISC + 256;
constexpr int SC_PROF = 229376;

constexpr float SM_SCALE = 0.08838834764831845f;
constexpr float LOG2E = 1.4426950408889634f;
constexpr float E_LIM = 20.f;

template <bool B> struct BoolC { static constexpr bool value = B; };
struct RMaps { CUtensorMap x, wq, wk, wv, wo, woa, oa; unsigned char* red; bf16* out; uint32_t poll; };

DI uint32_t latest_hint(uint32_t h, uint32_t d, int s) {
  const uint32_t x = (((h | 0xc0c0c0c0u) - ((d >> 5) & 63) * 0x01010101u) & 0x3f3f3f3fu) | ((h ^ (((s >> 2) + 1) & 3) * 0x40404040u) & 0xc0c0c0c0u);
  const uint32_t y = __vmaxu2(x & 0x00ff00ffu, (x >> 8) & 0x00ff00ffu);
  return __reduce_max_sync(0xffffffffu, max(y & 0xffffu, y >> 16));
}
DI uint32_t near_half(uint32_t sb) {
  uint32_t a, b; lds64(sb + SC_LAT, a, b);
  return a > b;
}

template <int RT, int K0, int K1, bool D32 = false, int BAR = 0, int KB = 18>
DI void xproj(float* acc, const uint32_t (&wa)[2][18][4], uint64_t xd) {
  if (XP & 1) return;
  WG_FENCE();
#pragma unroll
  for (int k = K0; k < ((XP & 128) ? K0 + 1 : K1); k++)
  {
    uint64_t d = xd + (uint64_t)(((k >> 1) * 4096 + (k & 1) * 32) >> 4);
    if (D32) asm("mov.b64 %0, {%1, %2};" : "=l"(d) : "r"((uint32_t)xd + (((k >> 1) * 4096 + (k & 1) * 32) >> 4)), "r"((uint32_t)(xd >> 32)));
    wgmma_n32_rs(acc, wa[RT][k][0], wa[RT][k][1], wa[RT][k][2], wa[RT][k][3], d, k != 0);
    if (BAR && k == KB - 1 && KB < 18) bar_arrive(BAR, 256);
  }
  WG_COMMIT();
}

DI void seg_store(int seg, uint32_t sb, uint32_t off, uint32_t bytes) {
  asm volatile("cp.async.bulk.global.shared::cta.bulk_group [%0], [%1], %2;"
               :: "l"(g_seg + ((size_t)(seg % NRING) * 96 + blockIdx.x) * SEGB + off), "r"(sb + SM_BLK + (seg & 3) * SEGB + off), "r"(bytes) : "memory");
  asm volatile("cp.async.bulk.commit_group;" ::: "memory");
}
DI void seg_publish(int seg) {
  asm volatile("cp.async.bulk.wait_group 0;" ::: "memory");
  asm volatile("red.relaxed.gpu.global.add.u32 [%0], 1;" :: "l"(&g_scnt[(seg * 32 + blockIdx.x / 3) * 8]) : "memory");
  SSTAMP(10, seg);
}

#define NAP 64
DI uint32_t movm(uint32_t x) { uint32_t r; asm volatile("movmatrix.sync.aligned.m8n8.trans.b16 %0, %1;" : "=r"(r) : "r"(x)); return r; }
DI bool wait_count(const unsigned* p, unsigned target, bool nap = true) {
  int n = 0;
  unsigned v;
  while (true) {
    asm volatile("ld.acquire.gpu.global.b32 %0, [%1];" : "=r"(v) : "l"(p) : "memory");
    if ((int)(v - target) >= 0 || ++n > SPIN_LIMIT) break;
    if (nap) __nanosleep(NAP);
  }
  return n;
}
#define PACE 1200
#define PORD 0
DI void load_weights(uint32_t sb, const RMaps& tm, uint32_t rank, int c) {
  const int h = blockIdx.x / 3;
  if (c < 3) {
    mbar_expect(sb + MB_W + 8 * c, 49152);
    tma_load(sb + SM_STAGE + c * 49152, rank < 2 ? &tm.wk : &tm.wv, h * DH + (rank == 1 ? 64 : 0), c * 192, sb + MB_W + 8 * c);
    tma_load(sb + SM_STAGE + c * 49152 + 24576, rank < 2 ? &tm.wq : &tm.wv, h * DH + (rank == 0 ? 0 : 64), c * 192, sb + MB_W + 8 * c);
  } else {
    tma_prefetch(&tm.wo, rank * 192, h * DH);
    mbar_expect(sb + MB_WO, 16384);
    mbar_expect(sb + MB_WO3, 32768);
    tma_load(sb + SM_WOST, &tm.wo, rank * 192 + 64, h * DH, sb + MB_WO3);
    tma_load(sb + SM_WO3, &tm.wo, rank * 192 + 128, h * DH, sb + MB_WO3);
  }
}

DI void tail_attention(const uint32_t sb, const uint32_t rank, const int w, const int lane, const int sg, const int bar) {
  const int m = lane >> 3, g = lane >> 2, t = lane & 3;
  const uint32_t l16 = sb + lane * 16, src = l16 + T_SX + sg * 10240 + w * 1280;
  if (rank < 2) {
    const uint32_t base = l16 + SM_BLK + (2 + sg) * SEGB, dst = src + rank * 5120;
    uint32_t qb[2][4];
    ldsm4t(qb[0], base + w * 1024); ldsm4t(qb[1], base + w * 1024 + 512);
#pragma unroll
    for (int j = 0; j < 3; j++) {
      uint32_t kb[4][4];
      float c[4][4];
      const uint32_t ka = base + 4096 + j * 2048 + (m & 1) * (j == 2 ? 128 : 896) - (m >> 1) * 128;
#pragma unroll
      for (int k = 0; k < 4; k += j == 2 ? 2 : 1) ldsm4t(kb[k], ka + k * 256);
      mma16816z(c[0], kb[0], qb[0][0], qb[0][1]); mma16816z(c[1], kb[j == 2 ? 0 : 1], qb[0][2], qb[0][3]);
      mma16816z(c[2], kb[2], qb[1][0], qb[1][1]); mma16816z(c[3], kb[j == 2 ? 2 : 3], qb[1][2], qb[1][3]);
      uint32_t r[4];
#pragma unroll
      for (int i = 0; i < (j == 2 ? 2 : 4); i++) r[i] = __float_as_uint((c[0][i] + c[1][j == 2 ? i + 2 : i]) + (c[2][i] + c[3][j == 2 ? i + 2 : i]));
#pragma unroll
      for (int d = 0; d < 2; d++) {
        const uint32_t to = d ? 2 : rank ^ 1, mb = mapa(sb + MB_T + 8 + 8 * sg, to);
        if (j < 2) st_async4(mapa(dst + j * 512, to), r[0], r[1], r[2], r[3], mb);
        else st_async2(mapa(dst + 1024 - lane * 8, to), r[0], r[1], mb);
      }
      if (j < 2) sts128(dst + j * 512, r[0], r[1], r[2], r[3]); else sts64(dst + 1024 - lane * 8, r[0], r[1]);
    }
  }
  TSTAMP(50 + 2 * sg);
  uint32_t vx[4][4], vm[4];
  const uint32_t va = l16 + (rank < 2 ? SM_VC + sg * 8192 : SM_BLK + (2 + sg) * SEGB) + w * 1024 + (m & 1) * 384 - (m >> 1) * 128;
#pragma unroll
  for (int i = 0; i < 4; i++) ldsm4(vx[i], va + (i & 1) * 4096 + (i >> 1) * 256);
  if (sg && rank < 2) mbar_wait(sb + MB_T, 0);
  lds128(l16 + (sg ? SM_FB : SM_VM) + w * 512, vm);
  float a[10], b[10];
  mbar_wait(sb + MB_T + 8 + 8 * sg, 0);
  TSTAMP(58 + 2 * sg);
  lds128f(src, a); lds128f(src + 512, a + 4); lds64f(src + 1024 - lane * 8, a + 8);
  lds128f(src + 5120, b); lds128f(src + 5632, b + 4); lds64f(src + 6144 - lane * 8, b + 8);
#pragma unroll
  for (int i = 0; i < 10; i++) {
    a[i] = (a[i] + b[i]) * (SM_SCALE * LOG2E);
    if (i < 8 && (i >> 1) * 8 + g > w * 8 + 2 * t + (i & 1)) a[i] = -1.0e9f * LOG2E;
  }
  float m0 = fmaxf(fmaxf(fmaxf(a[0], a[2]), fmaxf(a[4], a[6])), a[8]), m1 = fmaxf(fmaxf(fmaxf(a[1], a[3]), fmaxf(a[5], a[7])), a[9]);
#pragma unroll
  for (int o = 4; o < 32; o <<= 1) { m0 = fmaxf(m0, __shfl_xor_sync(0xffffffffu, m0, o)); m1 = fmaxf(m1, __shfl_xor_sync(0xffffffffu, m1, o)); }
#pragma unroll
  for (int i = 0; i < 10; i++) a[i] = ex2(a[i] - (i & 1 ? m1 : m0));
  float s0 = ((a[0] + a[2]) + (a[4] + a[6])) + a[8], s1 = ((a[1] + a[3]) + (a[5] + a[7])) + a[9];
#pragma unroll
  for (int o = 4; o < 32; o <<= 1) { s0 += __shfl_xor_sync(0xffffffffu, s0, o); s1 += __shfl_xor_sync(0xffffffffu, s1, o); }
  s0 = rcp(s0); s1 = rcp(s1);
#pragma unroll
  for (int i = 0; i < 5; i++) sts32(sb + T_P + sg * 2560 + w * 640 + i * 128 + lane * 4, pack_bf16(a[2 * i] * s0, a[2 * i + 1] * s1));
  mbar_wait(sb + MB_WO, 1);
  bar_sync(bar, 128);
  TSTAMP(59 + 2 * sg);
#pragma unroll
  for (int j = 0; j < 4; j++) {
    uint32_t p[5];
    float o0[4], o1[4], f[2];
    lds64f(sb + T_G + sg * 128 + j * 32 + t * 8, f);
    f[0] = 1.f - f[0]; f[1] = 1.f - f[1];
    ldsm4t(p, l16 + T_P + sg * 2560 + j * 640);
    asm volatile("ldmatrix.sync.aligned.m8n8.x1.trans.shared.b16 {%0}, [%1];" : "=r"(p[4]) : "r"(l16 + T_P + sg * 2560 + j * 640 + 512) : "memory");
    mma16816z(o0, vx[0], p[0], p[1]); mma16816z(o1, vx[1], p[0], p[1]);
    mma16816(o0, vx[2], p[2], p[3]); mma16816(o1, vx[3], p[2], p[3]);
    mma1688(o0, vm[0], vm[1], p[4]); mma1688(o1, vm[2], vm[3], p[4]);
    stsm4(l16 + T_OB + sg * 8192 + j * 2048 + w * 512, pack_bf16(o0[0] * f[0], o0[1] * f[1]), pack_bf16(o0[2] * f[0], o0[3] * f[1]),
          pack_bf16(o1[0] * f[0], o1[1] * f[1]), pack_bf16(o1[2] * f[0], o1[3] * f[1]));
  }
}

DI void proj_role(const uint32_t sb, const RMaps& tm, const uint32_t rank, const int wg, const int w, const int lane) {
  const bool qk = rank < 2;
  uint32_t wa[2][18][4];
  {
    const int rr = (lane & 7) + ((lane >> 4) << 3);
    const uint32_t col = ((2 * w + ((lane >> 3) & 1)) ^ (lane & 7)) << 4;
    float ss = 0.f;
#pragma unroll
    for (int c = 0; c < 3; c++) {
      mbar_wait(sb + MB_W + 8 * c, 0);
      if (threadIdx.x == 0) SSTAMP(11, c);
#pragma unroll
      for (int rt = 0; rt < 2; rt++)
#pragma unroll
        for (int k = 0; k < 6; k++)
          ldsm4t(wa[rt][c * 6 + k], sb + SM_STAGE + c * 49152 + (rt ^ wg) * 24576 + (64 * (k >> 1) + 32 * wg + 16 * (k & 1) + rr) * 128 + col);
      if (c < 2) {
        fence_async();
        bar_sync(3, 256);
        if (threadIdx.x == 0) {
          if (c == 0) tma_load3(sb + SM_X + XT, &tm.x, 32, sb + MB_X + 8);
          else { tma_load(sb + SM_X + 2 * XT, &tm.wo, rank * 192, (blockIdx.x / 3) * DH, sb + MB_WO); SSTAMP(11, 11); }
        }
        __syncwarp();
      }
      uint32_t q[4] = {0, 0, 0, 0};
#pragma unroll
      for (int rt = 0; rt < 2; rt++)
#pragma unroll
        for (int k = 0; k < 6; k++)
#pragma unroll
          for (int i = 0; i < 4; i++) sq_acc(q[i], wa[rt][c * 6 + k][i]);
#pragma unroll
      for (int i = 0; i < 4; i++) ss += bf_lo(q[i]) + bf_hi(q[i]);
    }
    ss = warp_sum(ss);
    fence_async();
    cluster_arrive();
    if (lane == 0) sts32(sb + SC_SS + 4 * (wg * 4 + w), qk ? 0 : __float_as_uint(ss));
    bar_arrive(11, 384);
  }
  STAMP(1);
  MSTAMP(0);
  mbar_wait(sb + MB_X, 0);
  STAMP(2);

  uint32_t t16 = sb + (w * 32 + lane) * 16;
  uint32_t mem_a = sb + SM_MEM + wg * 512 + lane * 16;
  uint32_t fin_a = sb + (lane & 7) * 16 + SM_BLK + (qk ? (wg ^ 1) * 4096 + w * 256 + (lane & 8) * 16 + (lane & 16) * 64
                                              : wg * 4096 + w * 1024 + (lane & 8) * 64 + (lane & 16) * 8);
  PIN(t16); PIN(mem_a); PIN(fin_a);
  const uint32_t fence_reg = mem_a;
  const uint32_t fin2 = qk ? 2048 : 256;
  float acc[16];
  const uint64_t xd0 = make_desc(sb + SM_X + wg * 64, 16, 1024, 1);
  auto do_export = [&]() {
    WG_WAIT(0);
    uint32_t q[8];
#pragma unroll
    for (int j = 0; j < 8; j++) q[j] = pack_bf16(acc[2 * j], acc[2 * j + 1]);
    sts128(t16 + SM_EXP + wg * 4096, q[0], q[1], q[2], q[3]);
    sts128(t16 + SM_EXP + wg * 4096 + 2048, q[4], q[5], q[6], q[7]);
    if (RET) asm volatile("{\n.reg .pred p;\nsetp.eq.u32 p, %2, 0;\n@p add.u32 %0, %0, 1;\n@p add.u32 %1, %1, 1;\nsetp.eq.and.u32 p, %0, %1, p;\n@p exit;\n}"
                          : "+r"(q[3]), "+r"(q[7]) : "r"(t16) : "memory");
  };
  uint32_t o[8];
  auto import = [&]() { lds128(t16 + SM_EXP + (wg ^ 1) * 4096, o); lds128(t16 + SM_EXP + (wg ^ 1) * 4096 + 2048, o + 4); };
  auto finish = [&](int seg) {
    const uint32_t a = fin_a + (seg & 3) * SEGB;
    WG_WAIT(0);
#pragma unroll
    for (int i = 0; i < 8; i++) o[i] = FIN16 ? add_bf16(pack_bf16(acc[2 * i], acc[2 * i + 1]), o[i]) : pack_bf16(acc[2 * i] + bf_lo(o[i]), acc[2 * i + 1] + bf_hi(o[i]));
    stsm4(a, o[0], o[1], o[2], o[3]);
    stsm4(a + fin2, o[4], o[5], o[6], o[7]);
  };
  auto send_v = [&](int seg, int dst) {
    fence_async();
    if (seg < NSEG && !(XP & 2) && elect_one())
      bulk_s2s(mapa(sb + SM_VC + (seg & 1) * 8192, dst), sb + SM_BLK + (seg & 3) * SEGB, 8192, mapa(sb + MB_VX + (seg & 1) * 8, dst));
    __syncwarp();
  };
  auto wait_v = [&](int seg) {
    if (seg < NSEG && !(XP & 2)) {
      mbar_wait(sb + MB_VX + (seg & 1) * 8, (seg >> 1) & 1);
      if (elect_one()) mbar_expect(sb + MB_VX + (seg & 1) * 8, 8192);
      __syncwarp();
    }
  };
  bar_sync(3, 256);
  xproj<1, 0, 18>(acc, wa, xd0);
  do_export();
  SCHED_FENCE(11);
  xproj<0, 0, 18>(acc, wa, xd0);
  bar_sync(3, 256);
  if (threadIdx.x == 0) SSTAMP(11, 12);
  MSTAMP(1);
  cluster_wait();
  if (threadIdx.x == 0) SSTAMP(11, 13);
  mbar_wait(sb + MB_X + 8, 0);
  import();
  finish(0);
  SCHED_FENCE(12);
  bar_sync(3, 256);
  uint64_t dA = xd0 + (XT >> 4);
  xproj<1, 0, 18>(acc, wa, dA);
  if (!qk && wg == 0 && w < 2) send_v(0, w);
  do_export();
  if (qk && wg == 0 && w == 0) wait_v(0);
  bar_arrive(13, 384);
  if (!qk) {
    SCHED_FENCE(15);
    xproj<0, 0, 18>(acc, wa, dA);
    if (threadIdx.x == 0 && !(XP & 8)) { mbar_expect(sb + MB_X, XT); tma_load3(sb + SM_X, &tm.x, 96, sb + MB_X); }
    bar_sync(3, 256);
    mbar_wait(sb + MB_X + 16, 0);
    import();
    finish(1);
    SCHED_FENCE(16);
    bar_sync(3, 256);
    dA += XT >> 4;
    xproj<1, 0, 18>(acc, wa, dA);
    if (wg == 0 && ((w == 0 && VS0) || (w == 1 && VS1))) send_v(1, w);
    do_export();
  }
  if (threadIdx.x == 0) SSTAMP(11, 14);
  MSTAMP(2);
  bar_sync(0, 384);
  const int ro = __shfl_sync(0xffffffffu, near_half(sb) ^ wg, 0);
  STAMP(5);
  const uint32_t always = __shfl_sync(0xffffffffu, lds32(sb + SC_DEAD + 12), 0);
  const int ah = qk ? 1 : 2;
  int b2 = qk ? 2 : 0;
  int s = 0;
  uint32_t hint_lo = (uint32_t)(uint64_t)tm.red + HINT_OFF + blockIdx.x + (lane & 1) * 4096 + (lane >> 1) * 16384;
  PIN(hint_lo);
  auto post_hint = [&]() {
    asm volatile("{\n.reg .pred p;\n.reg .b64 a;\n.reg .u32 t;\nsetp.lt.u32 p, %0, %1;\nmov.b64 a, {%2, %3};\nmov.u32 t, %%globaltimer_lo;\n"
                 "bfe.u32 t, t, 5, 6;\nor.b32 t, t, %4;\n@p st.relaxed.gpu.global.u8 [a], t;\n}"
                 :: "r"(t16), "r"(sb + 128), "r"(hint_lo + RED_SLOT(s)), "r"((uint32_t)((uint64_t)tm.red >> 32)), "r"(((s >> 2) + 1) << 6) : "memory");
  };
  auto memproj = [&](auto second, int id, float u0, float u1, float* r) {
    constexpr bool R1 = decltype(second)::value;
    uint32_t b[NUP][4], b0[4];
    SCHED_FENCE(id);
    bar_sync(R1 ? 2 : 1, 256);
    PROF(0);
    ldsm4t(b0, mem_a);
#pragma unroll
    for (int q = 0; q < NUP; q++) {
      if (R1 && q == 2) {
        bar_sync(11, 256);
        SCHED_FENCE(id + 1);
      }
      ldsm4t(b[q], mem_a + MEM_BLK(q + 1));
    }
    mma16816z(&acc[0], wa[0][0], b0[0], b0[1]);
    mma16816z(&acc[4], wa[1][0], b0[0], b0[1]);
    mma16816z(&acc[8], wa[0][1], b0[2], b0[3]);
    mma16816z(&acc[12], wa[1][1], b0[2], b0[3]);
#pragma unroll
    for (int q = 1; q < 9; q++) {
      uint32_t* const c = b[(q - 1) % NUP];
      mma16816(&acc[0], wa[0][2 * q], c[0], c[1]);
      mma16816(&acc[4], wa[1][2 * q], c[0], c[1]);
      mma16816(&acc[8], wa[0][2 * q + 1], c[2], c[3]);
      mma16816(&acc[12], wa[1][2 * q + 1], c[2], c[3]);
      if (R1 && q + NUP == B3Q) bar_sync(3, 256);
      if (q + NUP < 9) ldsm4t_in(c, mem_a + MEM_BLK(q + NUP), always);
      else if (R1 && q + NUP < 11) lds128_in(c, t16 + SM_PART + (10 - q - NUP) * 2048, always);
      else if (!R1 && GATE && q == GATE) { bar_arrive(11, 256); lds128_in(c, sb + SC_DEAD, always); u0 = u1 = __uint_as_float(c[3]); }
    }
#pragma unroll
    for (int i = 0; i < 8; i++) {
      const float u = i < 4 ? u0 : u1;
      r[i] = R1 ? fmaf(acc[8 + i], u, (acc[i] + __uint_as_float(b[(8 + i / 4) % NUP][i & 3])) * u) : (GATE ? fmaf(acc[i], u, acc[8 + i]) : acc[i] + acc[8 + i]);
    }
  };
  if (ro == 0) {
    auto set_scale = [&]() {
      uint32_t m[8];
      lds128(t16 + SM_MAX - 512, m); lds128(t16 + SM_MAX, m + 4);
      const int em = (wexp(amax4(amax4(*(const __half2*)&m[0], m), m + 4)) >> 3) + (int)(lds32(sb + SC_UNSC + (s & 1) * 8) >> 23) - 15;
      const int ex = max(s ? em : 0, (int)lds32(sb + SC_XMAX + 4 * s)) - 127 + (int)lds32(sb + SC_EXPW);
      sts32(sb + SC_UNSC + (~s & 1) * 8, (127 + min(max(ex, -120), 120)) << 23);
    };
#pragma unroll 1
    while (true) {
      if (s == 8) STAMP(6);
      float r[8];
      memproj(BoolC<false>(), 30, 0.f, 0.f, r);
      sts128(t16 + SM_PART, __float_as_uint(r[0]), __float_as_uint(r[1]), __float_as_uint(r[2]), __float_as_uint(r[3]));
      sts128(t16 + SM_PART + 2048, __float_as_uint(r[4]), __float_as_uint(r[5]), __float_as_uint(r[6]), __float_as_uint(r[7]));
      bar_arrive(3, 256);
      PROF(1);
      bar_sync(9, 256);
      if (s == NSEG - 1) break;
      post_hint();
      if (w == 1) {
        set_scale();
        __syncwarp();
        if (elect_one()) mbar_arrive(sb + MB_S);
      }
      SCHED_FENCE(9);
      bar_sync(5, qk ? N5 : 256);
      PROF(2);
      import();
      xproj<0, 0, NII, (DD & 1) != 0>(acc, wa, dA);
      if (NII < 18) {
        if (qk) bar_sync(7, 384);
        xproj<0, NII, 18>(acc, wa, dA);
        if (!qk) bar_sync(7, 384);
      } else {
        if (F10) WG_WAIT(0);
        bar_sync(10, 256);
        if (F10) SCHED_FENCE(17);
      }
      dA += (int64_t)(b2 ? XT >> 4 : -(XT >> 3));
      finish(s + ah);
      if (qk || !VLATE(w)) bar_arrive(13, 384);
      PROF(6);
      SCHED_FENCE(14);
      bar_sync(12, 256);
      PROF(7);
      xproj<1, 0, 18, (DD & 2) != 0, 14, N14>(acc, wa, dA);
      if (N14 == 18) bar_arrive(14, 256);
      b2 = b2 == 2 ? 0 : b2 + 1;
      s++;
      if (!qk && VLATE(w)) { bar_sync(13, 384); send_v(s + 1, w); }
      PROFP(8);
      do_export();
      s--; RSTAMP(6); s++;
      PROFP(3);
    }
    if (!qk) bar_arrive(5, 256);
    if (w == 0 && elect_one()) {
      const uint32_t h18 = blockIdx.x / 3 * 18;
      mbar_expect(sb + MB_WO, 9216 + 4096 + 256);
      asm volatile("cp.async.bulk.shared::cluster.global.mbarrier::complete_tx::bytes [%0], [%1], 256, [%2];"
                   :: "r"(sb + T_G), "l"(g_gate + NAUXSEG * 32), "r"(sb + MB_WO) : "memory");
      tma_load(sb + T_OA, &tm.oa, 4096 + (h18 & ~7), NAUXSEG * 32, sb + MB_WO);
#pragma unroll 1
      for (int j = 0; j < 3; j++) tma_load(sb + T_WA + j * 3072, &tm.woa, rank * 192 + j * 64, h18, sb + MB_WO);
    }
    if (w == 1) {
      set_scale();
      __syncwarp();
      const int ea = (int)ldg_relaxed32(&g_amax[0]) + (int)ldg_relaxed32(&g_amax[16]) - 254 + 2 + 10 - 15;
      sts32(sb + T_UN + (lane & 1) * 4, (128 + max(min(ea, 120), (int)(lds32(sb + SC_UNSC + 8 - (lane & 1) * 8) >> 23) - 127)) << 23);
    }
    bar_arrive(8, 256);
  } else {
    uint32_t r0;
    float un;
    auto prepare = [&]() {
      un = __uint_as_float(lds32(sb + SC_UNSC + (s & 1) * 8));
      r0 = qk ? (t16 & ~256u) - w * 256 + (((t16 >> 8) ^ wg) & 1 ? SM_QM : SM_BLK + 8192 + (s & 3) * SEGB) : mapa(t16 + (s < NSEG - 1 ? SM_VM : SM_FB), 0);
      PIN(r0); PIN(un);
    };
    auto mem_out = [&](int off, uint32_t lo, uint32_t hi) {
      unsigned char* const d = g_seg + ((size_t)(s % NRING) * 96 + blockIdx.x) * SEGB + 8192 + off + w * 256 + ((t16 >> 2) & 124);
      if (!(XP & 4)) { stg_relaxed32(d, lo); stg_relaxed32(d + 128, hi); }
    };
    prepare();
#pragma unroll 1
    while (true) {
      if (s == 8) STAMP(6);
      float r[8];
      if (qk) {
        const float u0 = wg ? un * (SM_SCALE * LOG2E) : un, u1 = wg ? un : un * (SM_SCALE * LOG2E);
        memproj(BoolC<true>(), 32, u0, u1, r);
        const uint32_t p0 = pack_bf16(r[0], r[1]), p1 = pack_bf16(r[2], r[3]), p2 = pack_bf16(r[4], r[5]), p3 = pack_bf16(r[6], r[7]);
        stsm4(r0, p0, p1, p2, p3);
        bar_arrive(4, 256);
        if (EXM) { SCHED_FENCE(18); mem_out(0, wg ? p2 : p0, wg ? p3 : p1); }
      } else {
        const uint32_t mb = sb + (s < NSEG - 1 ? MB_S : MB_T), r1 = r0 + (1 << 24);
        memproj(BoolC<true>(), 34, un, un, r);
        const uint32_t p0 = pack_bf16(r[0], r[1]), p1 = pack_bf16(r[2], r[3]), p2 = pack_bf16(r[4], r[5]), p3 = pack_bf16(r[6], r[7]);
        const uint32_t v0 = wg ? p2 : p0, v1 = wg ? p3 : p1, v2 = wg ? p0 : p2, v3 = wg ? p1 : p3;
        st_async4(r0, v0, v1, v2, v3, mapa(mb, 0));
        st_async4(r1, v0, v1, v2, v3, mapa(mb, 1));
        bar_arrive(5, 256);
        sts128(r0 + (2 << 24), v0, v1, v2, v3);
        stsm4((t16 & ~256u) - w * 256 + SM_BLK + 8192 + (s & 3) * SEGB + (((t16 >> 8) ^ wg) & 1) * 1024, p0, p1, p2, p3);
        __syncwarp();
        if (elect_one()) mbar_arrive(sb + MB_S);
        __syncwarp();
        if (EXM) { SCHED_FENCE(19); mem_out(0, v0, v1); mem_out(1024, v2, v3); }
      }
      if (s == NSEG - 1) break;
      if (!qk && !EXM) bar_arrive(15, 160);
      PROF(1);
      auto rearm = [&]() { mbar_wait(sb + MB_S, s & 1); if (elect_one()) mbar_expect(sb + MB_S, qk ? 640 + 2048 : 1280); __syncwarp(); };
      if (w == 1) {
        if ((t16 & 384) == 0) stg_relaxed(tm.red + (RED_SLOT(s + 2) + RED_LINE(blockIdx.x)) + (t16 & 112), 0, 0, 0, 0);
      } else if (w == 0) {
        const int tn = s + ah + 1;
        if (RFW) mbar_wait(sb + MB_S, s & 1);
        if (tn + 1 < NSEG && !(XP & 8) && elect_one()) {
          const int b0 = b2 == 2 ? 0 : b2 + 1;
          mbar_expect(sb + MB_X + 8 * b0, XT);
          tma_load3(sb + SM_X + b0 * XT, &tm.x, (tn + 1) * 32, sb + MB_X + 8 * b0);
        }
        if (tn < NSEG && (!(XP & 8) || tn < 3)) mbar_wait(sb + MB_X + 8 * b2, (tn / 3) & 1);
      } else if (w == 2) {
        if (!qk) { if (VS0 == 0) send_v(s + 1, 0); if (VS1 == 0) send_v(s + 1, 1); }
      } else if (qk || !NIC) {
        rearm();
      }
      __syncwarp();
      import();
      PROF(4);
      SCHED_FENCE(10);
      if (NIC) {
        if (qk) bar_sync(7, NII < 18 ? 384 : 256);
        xproj<0, 0, NIC>(acc, wa, dA);
        if (!qk) { if (w == 3) rearm(); bar_sync(7, NII < 18 ? 384 : 256); }
      } else {
        bar_sync(7, NII < 18 ? 384 : 256);
      }
      xproj<0, NIC, 18, (DD & 4) != 0, 12, N12>(acc, wa, dA);
      if (N12 == 18) bar_arrive(12, 256);
      dA += (int64_t)(b2 ? XT >> 4 : -(XT >> 3));
      finish(s + ah);
      if (qk && w == 0) wait_v(s + 1);
      bar_arrive(13, 384);
      PROF(6);
      SCHED_FENCE(13);
      bar_sync(14, 256);
      PROF(7);
      xproj<1, 0, 18, (DD & 8) != 0>(acc, wa, dA);
      b2 = b2 == 2 ? 0 : b2 + 1;
      s++;
      if (HOIST) prepare();
      PROFP(8);
      do_export();
      if (!HOIST) prepare();
      s--; RSTAMP(7); s++;
      PROFP(3);
    }
    TSTAMP(2);
    bar_sync(3, 128);
    tail_attention(sb, rank, w, lane, 1, 3);
    bar_arrive(0, 256);
  }
  STAMP(3);
  if (CSY) cluster_sync();
  STAMP(4);
}

DI void attn_role(const uint32_t sb, unsigned char* smem_raw, const RMaps& tm, const uint32_t RANK, const bf16* __restrict__ x, const bf16* __restrict__ mem0,
                  const int w, const int lane) {
  const int t2 = w * 32 + lane;
  uint32_t wo[8][4], w1[8][4];
  const uint32_t wo_lane = sb + ((lane & 7) + ((lane >> 4) << 3)) * 128 + (((w + 4 * ((lane >> 3) & 1)) ^ (lane & 7)) << 4);
  unsigned char* const g_red = tm.red;
  {
    const uint32_t tag = *(volatile unsigned*)&g_epoch + 1;
    if (w == 0) {
      stg_relaxed(g_red + RED_SLOT(t2 >> 3) + RED_LINE(blockIdx.x) + (t2 & 7) * 16, 0, 0, 0, 0);
      stg_relaxed(g_red + T_RED + blockIdx.x * 1024 + t2 * 16, 0, 0, 0, 0);
      stg_relaxed(g_red + T_RED + blockIdx.x * 1024 + 512 + t2 * 16, 0, 0, 0, 0);
      asm volatile("st.relaxed.gpu.global.u8 [%0], 0;" :: "l"(g_red + RED_SLOT(t2) + HINT_OFF + (t2 & 4) * 1024 + (t2 >> 3) * 16384 + blockIdx.x) : "memory");
    }
    uint4 xv[18];
    uint32_t mv[20];
#pragma unroll
    for (int i = 0; i < 20; i++) mv[i] = i < 18 ? ((const uint32_t*)mem0)[(lane >> 2) * (DM / 2) + (w * 18 + i) * 4 + (lane & 3)] : 0;
#pragma unroll
    for (int i = 0; i < 18; i++) xv[i] = blockIdx.x < NSEG ? ((const uint4*)(x + blockIdx.x * 32 * DM))[t2 + 128 * i] : make_uint4(0, 0, 0, 0);
    bar_sync(0, 384);
    cluster_arrive();
    if (PACE && w == 3) {
      const uint32_t t0 = gtime();
#pragma unroll 1
      for (int c = 1; c < 4; c++) {
        wait_until(t0 + c * PACE);
        if (elect_one()) load_weights(sb, tm, RANK, PORD ? (c == 1 ? 3 : c - 1) : c);
        __syncwarp();
      }
    }
    __half2 hx = __float2half2_rn(0.f);
#pragma unroll
    for (int i = 0; i < 18; i++) hx = amax4(hx, &xv[i].x);
    if (blockIdx.x == 0)
#pragma unroll
      for (int i = 0; i < 5; i++) hx = amax4(hx, &mv[4 * i]);
    sts32(sb + SC_SS + 4 * (12 + w), wexp(hx));
    if (t2 == 0) { sts32(sb + SC_EPOCH, (tag - 1) * NSEG + 2 - NRING); sts32(sb + SC_UNSC, __float_as_uint(1.f)); sts128(sb + SC_DEAD, 0, 0, 0, 0x3f800000u); sts64(sb + SC_FPAR, 0, 0); sts128(sb + SC_ONES, 0x3f803f80u, 0x3f803f80u, 0x3f803f80u, 0x3f803f80u); }
    WSTAMP(27);
    if (w == 0) __threadfence();
    uint32_t q[8] = {0, 0, 0, 0, 0, 0, 0, 0};
    mbar_wait(sb + MB_WO3, 0);
    if (t2 == 0) SSTAMP(11, 3);
    MSTAMP(3);
#pragma unroll
    for (int k = 0; k < 8; k++) {
      ldsm4t(wo[k], wo_lane + SM_WO3 + k * 2048); ldsm4t(w1[k], wo_lane + SM_WOST + k * 2048);
#pragma unroll
      for (int i = 0; i < 4; i++) { sq_acc(q[i], wo[k][i]); sq_acc(q[i], w1[k][i]); }
    }
    bar_sync(6, 128);
    if (t2 == 0) SSTAMP(11, 7);
#pragma unroll
    for (int k = 0; k < 8; k++) sts128(sb + SM_WO3 + t2 * 16 + k * 2048, wo[k][0], wo[k][1], wo[k][2], wo[k][3]);
#pragma unroll
    for (int i = 0; i < 5; i++) {
      const int j = w * 18 + 4 * i + (lane >> 3), c = i < 4 || lane < 16 ? j * 8 + j / 24 * 64 : 192;
      stsm4t(sb + SM_MEM + (c + (lane & 7)) * 16, mv[4 * i], mv[4 * i + 1], mv[4 * i + 2], mv[4 * i + 3]);
    }
    bar_arrive(1, 256); bar_arrive(2, 256); bar_arrive(9, 256);
    if (t2 == 0) SSTAMP(11, 8);
    mbar_wait(sb + MB_WO, 0);
    if (t2 == 0) SSTAMP(11, 4);
#pragma unroll
    for (int k = 0; k < 8; k++) ldsm4t(wo[k], wo_lane + SM_X + 2 * XT + k * 2048);
    fence_async();
    bar_sync(6, 128);
    if (t2 == 32) tma_load3(sb + SM_X + 2 * XT, &tm.x, 64, sb + MB_X + 16);
    __syncwarp();
#pragma unroll
    for (int k = 0; k < 8; k++)
#pragma unroll
      for (int i = 0; i < 4; i++) sq_acc(q[4 + i], wo[k][i]);
    float ss = 0.f;
#pragma unroll
    for (int i = 0; i < 8; i++) ss += bf_lo(q[i]) + bf_hi(q[i]);
    ss = warp_sum(ss);
    if (lane == 0) sts32(sb + SC_SS + 4 * (8 + w), __float_as_uint(ss));
    if (t2 == 0) SSTAMP(11, 9);
    bar_sync(11, 384);
    if (t2 == 0) SSTAMP(11, 10);
    if (t2 == 0) {
      float a[16];
#pragma unroll
      for (int i = 0; i < 4; i++) lds128f(sb + SC_SS + 16 * i, &a[4 * i]);
      stg_relaxed(&g_stats[blockIdx.x * 2], __float_as_uint(((a[0] + a[1]) + (a[2] + a[3])) + ((a[4] + a[5]) + (a[6] + a[7]))),
                  __float_as_uint((a[8] + a[9]) + (a[10] + a[11])),
                  max(max(__float_as_uint(a[12]), __float_as_uint(a[13])), max(__float_as_uint(a[14]), __float_as_uint(a[15]))), tag);
    }
    __syncwarp();
    WSTAMP(24);
    MSTAMP(4);
    cluster_wait();
    if (w == 0) {
      uint4 v[3];
      int n = 0;
      while (true) {
#pragma unroll
        for (int i = 0; i < 3; i++) v[i] = ldg_relaxed(&g_stats[(i * 32 + lane) * 2]);
        if (__all_sync(0xffffffffu, v[0].w == tag && v[1].w == tag && v[2].w == tag) || ++n > SPIN_LIMIT) break;
        __nanosleep(100);
      }
      WSTAMP(25);
      MSTAMP(5);
      const float sv = warp_sum(__uint_as_float(v[0].x) + __uint_as_float(v[1].x) + __uint_as_float(v[2].x));
      const float so = warp_sum(__uint_as_float(v[0].y) + __uint_as_float(v[1].y) + __uint_as_float(v[2].y));
      const int expW = ((int)(__float_as_uint(sv) >> 23) + (int)(__float_as_uint(so) >> 23) - 254 + 2 + 10 + 1) >> 1;
      sts32(sb + SC_XMAX + 4 * lane, v[0].z); sts32(sb + SC_XMAX + 128 + 4 * lane, v[1].z);
      sts32(sb + SC_EXPW, expW + 1 - 15);
      if (blockIdx.x == 0 && lane == 0) *(volatile unsigned*)&g_epoch = tag;
      sts32(sb + SC_FPAR + 4, 1);
    } else if (w < 3) {
      const uint32_t u = blockIdx.x >> 4;
      unsigned char* const z = g_red + 98304 + (blockIdx.x & 15) * 128 + (u & 1) * 2048 + (u & 6) * 4096 + (((u >> 1) ^ w) & 1) * 4096 + lane * 4;
      stg_relaxed32(z, 0);
      uint32_t best = 0xffffffffu;
#pragma unroll 1
      for (int i = 0; i < 64; i++) {
        uint32_t last, dt;
        asm volatile("{\n.reg .pred p;\n.reg .u32 c, v;\nld.volatile.shared.u32 %0, [%3];\nmov.u32 c, %%clock;\n"
                     "atom.relaxed.gpu.global.exch.b32 v, [%2], 0;\nsetp.eq.u32 p, v, 0;\nmov.u32 %1, 0;\n@p mov.u32 %1, %%clock;\nsub.u32 %1, %1, c;\n}"
                     : "=r"(last), "=r"(dt) : "l"(z), "r"(sb + SC_FPAR + 4) : "memory");
        best = min(best, dt);
        if ((last || PFIX) && i >= NPROBE - 1) break;
      }
      sts32(sb + SC_LAT + (w - 1) * 4, best);
    }
    bar_sync(13, 384);
    bar_arrive(0, 384);
    WSTAMP(26);
    TSTAMP(1);
    MSTAMP(6);
  }

  const uint32_t nh = __shfl_sync(0xffffffffu, near_half(sb), 0);
  uint32_t l16 = sb + lane * 16;
  PIN(l16);
#define LV ((l16 >> 4) & 31)
#define fence_reg l16
  const uint32_t red_lo = (uint32_t)(uint64_t)g_red, red_hi = (uint32_t)((uint64_t)g_red >> 32);
  uint32_t lp;
  auto slot = [&](int s, uint32_t c, uint32_t ofs) {
    const uint32_t lo = lp | (red_lo + ((w >> 1) * 4 + (w & 1) * 2 + ((w ^ c) & 1)) * 4096 + RED_SLOT(s) + ofs);
    uint64_t a; asm("mov.b64 %0, {%1, %2};" : "=l"(a) : "r"(lo), "r"(red_hi));
    return (unsigned char*)a;
  };
  const uint32_t always = __shfl_sync(0xffffffffu, lds32(sb + SC_DEAD + 12), 0);
  const int mode0 = RANK < 2 ? w : w | 4;
  auto hint_addr = [&](int s) { return min(LV, 23u) * 4 + (red_lo + HINT_OFF + nh * 4096 + w * 16384 + RED_SLOT(s)); };
  auto load_hints = [&](uint32_t lo) {
    uint64_t a; asm("mov.b64 %0, {%1, %2};" : "=l"(a) : "r"(lo), "r"(red_hi));
    return ldg_relaxed32((const void*)a);
  };
  const uint32_t blk = RANK < 2 ? 9216 : SEGB;
  auto send_v = [&](int seg, int pos) {
    if (RANK == 2 && ((w == 0 && VS0 == pos) || (w == 1 && VS1 == pos)) && seg > 1 && seg < NSEG && !(XP & 2)) {
      if (elect_one()) {
        fence_async();
        bulk_s2s(mapa(sb + SM_VC + (seg & 1) * 8192, w), sb + SM_BLK + (seg & 3) * SEGB, 8192, mapa(sb + MB_VX + (seg & 1) * 8, w));
      }
      __syncwarp();
    }
  };
  int s = 0;
  uint32_t dl = __shfl_sync(0xffffffffu, gtime() - 768, 0);
  bool bad = false;
#pragma unroll 1
  while (true) {
    const uint32_t par = s & 1;
    uint32_t vx[4][4], oc[4], hints;
    if (HP == 2) { hints = hint_addr(s); PIN(hints); }
    auto load_vx = [&]() {
      const uint32_t va = l16 + (RANK < 2 ? SM_VC + par * 8192 : SM_BLK + (s & 3) * SEGB) + w * 1024 + ((LV >> 3) & 1) * 384 - (LV >> 4) * 128;
      if (WL & 4) lds128(sb + SC_ONES, oc);
#pragma unroll
      for (int i = 0; i < 4; i++) ldsm4(vx[i], va + (i & 1) * 4096 + (i >> 1) * 256);
    };
    auto retire = [&](uint32_t x) {
      asm volatile("{\n.reg .pred p;\nsetp.eq.u32 p, %0, 0;\n@p exit;\n}" :: "r"(vx[0][0] | vx[1][0] | vx[2][0] | vx[3][0] | x | ((WL & 4) ? oc[0] : 0)) : "memory");
    };
    auto scores = [&](auto memkeys, auto first, float* sc) {
      constexpr bool MK = decltype(memkeys)::value, FIRST = decltype(first)::value;
      uint32_t kb[4][4], qb[2][4];
      const uint32_t m = LV >> 3;
      uint32_t kaddr = l16 + SM_BLK + 4096 + (s & 3) * SEGB + w * 2048 + (m & 1) * (MK ? 128 : 896) - (m >> 1) * 128;
      if (MK) { PIN(kaddr); }
      else {
#pragma unroll
        for (int k = 0; k < 4; k++) ldsm4t(kb[k], kaddr + k * 256);
      }
      if (FIRST) { load_vx(); retire(MK ? kaddr : kb[0][0] | kb[1][0] | kb[2][0] | kb[3][0] | l16); bar_sync(4, 256); RSTAMP(4); PROF(4); }
      ldsm4t(qb[0], l16 + SM_QM);
      if (MK) ldsm4t(kb[0], kaddr);
      ldsm4t(qb[1], l16 + SM_QM + 512);
      if (MK) ldsm4t(kb[2], kaddr + 512);
      float c[4][4];
      mma16816z(c[0], kb[0], qb[0][0], qb[0][1]); mma16816z(c[1], kb[MK ? 0 : 1], qb[0][2], qb[0][3]);
      mma16816z(c[2], kb[2], qb[1][0], qb[1][1]); mma16816z(c[3], kb[MK ? 2 : 3], qb[1][2], qb[1][3]);
      if (FIRST && B5POS == 0) bar_arrive(5, N5);
#pragma unroll
      for (int i = 0; i < (MK ? 2 : 4); i++) sc[i] = ((c[0][i] + c[1][MK ? i + 2 : i]) + c[2][i]) + c[3][MK ? i + 2 : i];
    };
    auto send = [&](auto memkeys) {
      constexpr bool MK = decltype(memkeys)::value;
      constexpr int N = MK ? 1 : 2;
      const uint32_t sa = sb + LV * 4 + SM_E + (MK ? 1024 + RANK * 128 : RANK * 512 + w * 256);
      uint32_t ra[N][2], mb[N][2];
#pragma unroll
      for (int i = 0; i < N; i++)
#pragma unroll
        for (int j = 0; j < 2; j++) {
          ra[i][j] = mapa(sa + i * 128, j ? 2 : RANK ^ 1); mb[i][j] = mapa(sb + MB_S, j ? 2 : RANK ^ 1);
          PIN(ra[i][j]);
        }
      float sc[4];
      scores(memkeys, BoolC<true>(), sc);
      uint32_t e[N];
#pragma unroll
      for (int i = 0; i < N; i++) {
        e[i] = pack_bf16(ex2(sc[2 * i]), ex2(sc[2 * i + 1]));
        if (!(fmaxf(fabsf(sc[2 * i]), fabsf(sc[2 * i + 1])) <= E_LIM)) e[i] = 0x7fff7fffu;
        st_async1(ra[i][0], e[i], mb[i][0]);
        st_async1(ra[i][1], e[i], mb[i][1]);
      }
#pragma unroll
      for (int i = 0; i < N; i++) sts32(sa + i * 128, e[i]);
      __syncwarp();
      if (l16 == sb) mbar_arrive(sb + MB_S);
      PROF(5);
    };
    const int mode = bad ? 8 : mode0;
    if (mode < 2) {
      send(BoolC<false>());
    } else if (mode == 2) {
      send(BoolC<true>());
    } else if (mode == 8) {
      load_vx();
      retire(l16);
      const uint32_t fp = lds32(sb + SC_FPAR);
      bar_sync(6, 128);
      if (w == 0 && l16 == sb) { sts32(sb + SC_FPAR, fp ^ 1); mbar_expect(sb + MB_F, 3072); }
      if (RANK < 2 && w < 3) {
        float sc[4] = {0.f, 0.f, 0.f, 0.f};
        if (w < 2) scores(BoolC<false>(), BoolC<false>(), sc); else scores(BoolC<true>(), BoolC<false>(), sc);
#pragma unroll 1
        for (int r = 0; r < 3; r++)
          st_async4(mapa(l16 + SM_FB + RANK * 1536 + w * 512, r), __float_as_uint(sc[0]), __float_as_uint(sc[1]), __float_as_uint(sc[2]), __float_as_uint(sc[3]), mapa(sb + MB_F, r));
      }
      mbar_wait(sb + MB_F, fp);
      float a[12];
#pragma unroll
      for (int j = 0; j < 3; j++) {
        float b[4];
        lds128f(l16 + SM_FB + j * 512, a + 4 * j); lds128f(l16 + SM_FB + 1536 + j * 512, b);
#pragma unroll
        for (int i = 0; i < 4; i++) a[4 * j + i] += b[i];
      }
      float m0 = fmaxf(fmaxf(fmaxf(a[0], a[2]), fmaxf(a[4], a[6])), a[8]), m1 = fmaxf(fmaxf(fmaxf(a[1], a[3]), fmaxf(a[5], a[7])), a[9]);
#pragma unroll
      for (int o = 4; o < 32; o <<= 1) { m0 = fmaxf(m0, __shfl_xor_sync(0xffffffffu, m0, o)); m1 = fmaxf(m1, __shfl_xor_sync(0xffffffffu, m1, o)); }
#pragma unroll
      for (int i = 0; i < 5; i++) {
        const uint32_t ea = sb + SM_E + LV * 4 + (i < 4 ? i * 128 : 1024);
        sts32(ea, pack_bf16(ex2(a[2 * i] - m0), ex2(a[2 * i + 1] - m1)));
        sts32(ea + (i < 4 ? 512 : 128), 0x3f803f80u);
      }
      __syncwarp();
    } else {
      load_vx();
      if (EXM && mode == 3) bar_arrive(4, 256);
      retire(l16 + 1);
      if (VS0 == 2 || VS1 == 2) send_v(s + 1, 2);
      if (w == 3) {
        uint32_t used = ldg_relaxed32(&g_used[blockIdx.x / 3 * 32]);
        if (!(XP & 4) && elect_one()) {
          if (s > 0) seg_publish(s - 1);
          fence_async();
          seg_store(s, sb, 0, 8192);
        }
        __syncwarp();
        if (!EXM) {
          bar_sync(RANK < 2 ? 4 : 15, RANK < 2 ? 256 : 160);
          if (!(XP & 4) && elect_one()) { fence_async(); seg_store(s, sb, 8192, blk - 8192); }
          __syncwarp();
        }
        const uint32_t need = lds32(sb + SC_EPOCH) + (s >= NRING - 1 ? s : -4 * NSEG);
#pragma unroll 1
        for (int n = 0; (int)(used - need) < 0 && n < ((XP & 64) ? 1 : SPIN_LIMIT); n++) used = ldg_relaxed32(&g_used[blockIdx.x / 3 * 32]);
      }
    }
    {
      uint32_t wa[4], wb[4];
      constexpr int WS = 2048;
      const uint32_t w3a = l16 + SM_WO3 + w * 512;
      if (HP == 1) { hints = hint_addr(s); PIN(hints); }
      if (!(WL & 1)) { lds128(w3a + KP(0) * WS, wa); lds128(w3a + KP(1) * WS, wb); }
      if (WL & 2) {
#pragma unroll
        for (int i = 0; i < 4; i++) oc[i] = always | (always >> 16) | (always & (i + 1));
      } else if (!(WL & 4)) lds128(sb + SC_ONES, oc);
      if (B5POS == 1 && mode < 3) bar_arrive(5, N5);
      uint32_t e[10], p[5], vm[4], ob[4];
      float o0[4], o1[4], f[3][2][4], rs[4];
      if (!(RV & 1)) { reserve2(vm); reserve2(vm + 2); }
      if (!(RV & 2)) reserve2(e + 8);
      if (!HP) { hints = hint_addr(s); PIN(hints); }
      if (CLR & 2) asm volatile("{\n.reg .pred p;\nsetp.eq.u32 p, %0, 0;\n@p exit;\n}" :: "r"(wa[0] | wb[0] | oc[0] | hints) : "memory");
      if (RV & 4) mbar_wait_fast(sb + MB_S, par); else mbar_wait(sb + MB_S, par);
      RSTAMP(5);
      PROF(6);
      if (RV & 2) { ldsm4t(e, l16 + SM_E); ldsm4t(e + 4, l16 + SM_E + 512); ldsm2t(e + 8, l16 + SM_E + 1024); }
      else { ldsm4t(e, l16 + SM_E); ldsm2t_in(e + 8, l16 + SM_E + 1024, always); ldsm4t(e + 4, l16 + SM_E + 512); }
      if (RV & 1) lds128(l16 + w * 512 + SM_VM, vm); else lds128_in(vm, l16 + w * 512 + SM_VM, always);
      const float scl = __uint_as_float(lds32(sb + SC_UNSC + 8 - par * 8));
      if (HL == 0) hints = load_hints(hints);
      if (GF & 1) SCHED_FENCE(4);
#pragma unroll
      for (int i = 0; i < 4; i++) p[i] = mul_bf16(e[i], e[4 + i]);
      p[4] = mul_bf16(e[8], e[9]);
      if (HL) hints = load_hints(hints | (p[HL - 1] & always & 1));
      mma16816z(o0, vx[0], p[0], p[1]);
      if (WL & 1) { lds128_in(vx[0], w3a + KP(0) * WS, always); }
      mma16816z(o1, vx[1], p[0], p[1]);
      if (WL & 1) { lds128_in(vx[1], w3a + KP(1) * WS, always); }
      mma16816z(rs, oc, p[0], p[1]);
      mma16816(o0, vx[2], p[2], p[3]); lds128_in(vx[2], w3a + KP(2) * WS, always);
      mma16816(o1, vx[3], p[2], p[3]); lds128_in(vx[3], w3a + KP(3) * WS, always);
      mma16816(rs, oc, p[2], p[3]);
      mma1688(o0, vm[0], vm[1], p[4]); mma1688(o1, vm[2], vm[3], p[4]); mma1688(rs, oc[0], oc[1], p[4]);
      stsm4(l16 + w * 512 + SM_OB, pack_bf16(o0[0], o0[1]), pack_bf16(o0[2], o0[3]), pack_bf16(o1[0], o1[1]), pack_bf16(o1[2], o1[3]));
      bar_sync(6, 128);
      RSTAMP(3);
      PROF(7);
      ldsm4t_in(oc, l16 + SM_OB, always);
      bad = __any_sync(0xffffffffu, !(rs[0] + rs[1] > 0.f) && !bad);
      rs[0] *= scl; rs[1] *= scl;
      asm volatile("{\n.reg .pred p;\nsetp.ne.u32 p, %1, 0;\n@p rcp.approx.ftz.f32 %0, %0;\n}" : "+f"(rs[0]) : "r"(always));
      asm volatile("{\n.reg .pred p;\nsetp.ne.u32 p, %1, 1;\n@p rcp.approx.ftz.f32 %0, %0;\n}" : "+f"(rs[1]) : "r"(always));
      asm volatile("lop3.b32 %0, %1, %2, %3, 0xfe;" : "=r"(lp) : "r"((l16 & 128) * 2), "r"((l16 & 256) * 4), "r"(l16 & 112));
      if (bad) continue;
      ldsm4t(ob, l16 + SM_OB + 512);
      mma16816z(f[2][0], WL & 1 ? vx[0] : wa, oc[0], oc[1]); mma16816z(f[2][1], WL & 1 ? vx[1] : wb, oc[2], oc[3]);
      mma16816z(f[0][0], wo[0], oc[0], oc[1]); mma16816z(f[0][1], wo[4], oc[2], oc[3]);
      mma16816z(f[1][0], w1[0], oc[0], oc[1]); mma16816z(f[1][1], w1[4], oc[2], oc[3]);
      ldsm4t_in(oc, l16 + SM_OB + 1024, always);
      mma16816(f[2][0], vx[2], ob[0], ob[1]); lds128_in(vx[2], w3a + KP(4) * WS, always);
      mma16816(f[2][1], vx[3], ob[2], ob[3]); lds128_in(vx[3], w3a + KP(5) * WS, always);
      mma16816(f[0][0], wo[1], ob[0], ob[1]); mma16816(f[0][1], wo[5], ob[2], ob[3]);
      mma16816(f[1][0], w1[1], ob[0], ob[1]); mma16816(f[1][1], w1[5], ob[2], ob[3]);
      ldsm4t_in(ob, l16 + SM_OB + 1536, always);
      mma16816(f[0][0], wo[2], oc[0], oc[1]); mma16816(f[0][1], wo[6], oc[2], oc[3]);
      mma16816(f[2][0], vx[2], oc[0], oc[1]); lds128_in(vx[2], w3a + KP(6) * WS, always);
      mma16816(f[2][1], vx[3], oc[2], oc[3]); lds128_in(vx[3], w3a + KP(7) * WS, always);
      mma16816(f[1][0], w1[2], oc[0], oc[1]); mma16816(f[1][1], w1[6], oc[2], oc[3]);
      mma16816(f[0][0], wo[3], ob[0], ob[1]); mma16816(f[0][1], wo[7], ob[2], ob[3]);
      mma16816(f[1][0], w1[3], ob[0], ob[1]); mma16816(f[1][1], w1[7], ob[2], ob[3]);
      mma16816(f[2][0], vx[2], ob[0], ob[1]); mma16816(f[2][1], vx[3], ob[2], ob[3]);
      bar_arrive(7, NII < 18 ? 384 : 256);
      lds128_in(ob, sb + SC_DEAD, always);
      uint32_t h[3][2];
#pragma unroll
      for (int j = 0; j < 3; j++)
#pragma unroll
        for (int i = 0; i < 2; i++)
        {
          scale_sum(f[j][1][2 * i], f[j][0][2 * i], rs[0], always); scale_sum(f[j][1][2 * i + 1], f[j][0][2 * i + 1], rs[1], always);
          h[j][i] = pack_f16(f[j][1][2 * i], f[j][1][2 * i + 1]);
        }
      const uint32_t rofs = RANK * 32768;
      red_f16x8(slot(s, RANK >> 1, rofs), h[0][0], h[1][0], h[2][0], 0x3c00u);
      red_f16x8(slot(s, (RANK >> 1) ^ 1, rofs), h[0][1], h[1][1], h[2][1], 0x3c00u);
      if (NII == 18) bar_arrive(10, 256);
      SCHED_FENCE(5);
      RSTAMP(0);
      l16 += ob[B7R];
    }
    {
    PROF(8);
    if (VS0 == 3 || VS1 == 3) send_v(s + 1, 3);
    const uint32_t ma0 = l16 + SM_MEM + w * 128 + (LV >> 3) * 896 + nh * 512;
    const unsigned char* const sl[2] = {slot(s, nh, 0), slot(s, nh ^ 1, 0)};
    uint32_t late = latest_hint(hints, dl, s);
    if (late >= 64) {
      int n = 0;
#pragma unroll 1
      do {
        late = latest_hint(load_hints(hint_addr(s)), dl, s);
      } while (late >= 64 && ++n < SPIN_LIMIT);
    }
    dl += late * 32 + tm.poll;
    if (s == 0 && PSTAMP) MSTAMP(7);
    PROF(9);
    {
      auto wait_until = [&](uint32_t t) {
        asm volatile("{\n.reg .pred p;\n.reg .s32 c;\n.reg .u64 t;\nTL: mov.u64 t, %%globaltimer;\ncvt.u32.u64 c, t;\nsub.s32 c, c, %0;\nsetp.lt.s32 p, c, 0;\n@p bra.uni TL;\n}" :: "r"(t + (l16 & 15)) : "memory");
      };
      uint4 v[2][3];
      auto load = [&](int c) {
#pragma unroll
        for (int r = 0; r < 3; r++) v[c][r] = ldg_relaxed(sl[c ^ (r >> 1)] + r * 32768);
      };
      auto decode = [&](int c, int n) {
        uint32_t q[9];
        __half2 hm;
        const uint32_t ma = ma0 ^ (c * 512);
#pragma unroll
        for (int i = 0; i < 9; i++) {
          const uint32_t h = i % 3 == 0 ? v[c][i / 3].x : (i % 3 == 1 ? v[c][i / 3].y : v[c][i / 3].z);
          const float2 f = __half22float2(*(const __half2*)&h);
          q[i] = pack_bf16(f.x, f.y);
          hm = i ? __hmax2(hm, __habs2(*(const __half2*)&h)) : __habs2(*(const __half2*)&h);
        }
#pragma unroll
        for (int r = 0; r < 3; r++) stsm4(ma + r * 4096, q[3 * r], q[3 * r + 1], q[3 * r + 2], r < 2 ? v[c][r].w : *(const uint32_t*)&hm);
        const bool done = __all_sync(0xffffffffu, v[c][0].w == 0x5000u && v[c][1].w == 0x5000u && v[c][2].w == 0x5000u) || n > SPIN_LIMIT;
        asm volatile("{\n.reg .pred p;\nsetp.ne.u32 p, %0, 0;\n@p bar.arrive %1, 256;\n}" :: "r"((int)done), "r"(1 + c) : "memory");
        return done;
      };
      if (LEAD) { wait_until(dl - LEAD); load(1); }
      wait_until(dl);
      PROF(10);
      int n = 0;
#pragma unroll 1
      do {
        load(0);
        if (!LEAD) load(1);
        asm volatile("{\n.reg .pred p;\nsetp.eq.u32 p, %0, 0;\n@p bar.sync 13, 384;\n}" :: "r"(n) : "memory");
      } while (!decode(0, n++));
      PROF(11);
      RSTAMP(1);
#pragma unroll 1
      while (!decode(1, n++)) load(1);
      bar_arrive(9, 256);
      RSTAMP(2);
      PROF(12);
    }
    PROF(13);
    if (++s == NSEG - 1) break;
    }
  }
#undef fence_reg
  if (RANK < 2) bar_arrive(4, 256);
  TSTAMP(49);
  {
    PIN(l16);
    tail_attention(sb, RANK, w, LV, 0, 6);
#pragma unroll 1
    for (int sg = 0; sg < 2; sg++) {
      PIN(l16);
      const int lane = LV, m = lane >> 3, g = lane >> 2, t = lane & 3;
      const uint32_t ob = l16 + T_OB + sg * 8192;
      bar_sync(sg ? 0 : 8, 256);
      TSTAMP(54 + 2 * sg);
      const float inv = __uint_as_float(0x7f000000u - lds32(sb + T_UN + sg * 4));
#pragma unroll 1
      for (int j = 0; j < 4; j += 2) {
        float c[2][3][4];
        uint32_t x[4], y[4], z[2][4];
#pragma unroll
        for (int e = 0; e < 2; e++) {
          const uint32_t oa = sb + T_OA + ((sg * 4 + j + e) * 8 + g) * 64 + (blockIdx.x / 3 * 36 & 15) + t * 4;
          z[e][0] = lds32(oa); z[e][1] = lds32(oa + 16); z[e][2] = t ? 0u : lds32(oa + 32);
        }
#pragma unroll
        for (int i = 0; i < 3; i++) {
          const uint32_t wa = sb + T_WA + ((lane & 7) + ((lane >> 4) << 3)) * 128 + (((w + 4 * (m & 1)) ^ (lane & 7)) << 4);
          ldsm4t(x, wa + i * 3072); ldsm2t(y, wa + i * 3072 + 2048);
#pragma unroll
          for (int e = 0; e < 2; e++) { mma1688z(c[e][i], y[0], y[1], z[e][2]); mma16816(c[e][i], x, z[e][0], z[e][1]); }
        }
#pragma unroll
        for (int r = 0; r < 4; r++) {
          ldsm4t(z[0], ob + j * 2048 + r * 512); ldsm4t(z[1], ob + j * 2048 + 2048 + r * 512);
          lds128(l16 + SM_WO3 + w * 512 + r * 2048, x); lds128(l16 + SM_WO3 + w * 512 + (r + 4) * 2048, y);
#pragma unroll
          for (int e = 0; e < 2; e++) { mma16816(c[e][0], wo[r], z[e][0], z[e][1]); mma16816(c[e][1], w1[r], z[e][0], z[e][1]); mma16816(c[e][2], x, z[e][0], z[e][1]); }
#pragma unroll
          for (int e = 0; e < 2; e++) { mma16816(c[e][0], wo[r + 4], z[e][2], z[e][3]); mma16816(c[e][1], w1[r + 4], z[e][2], z[e][3]); mma16816(c[e][2], y, z[e][2], z[e][3]); }
        }
#pragma unroll
        for (int i = 0; i < 4; i++) {
          const float (&d)[3][4] = c[i >> 1];
          const int q = (i & 1) * 2;
          red_f16x8(g_red + T_RED + ((((sg * 4 + j + (i >> 1)) * 3 + RANK) * 4 + w) * 2 + (i & 1)) * 512 + lane * 16, pack_f16(d[0][q] * inv, d[0][q + 1] * inv),
                    pack_f16(d[1][q] * inv, d[1][q + 1] * inv), pack_f16(d[2][q] * inv, d[2][q + 1] * inv), 0x3c00u);
        }
      }
      TSTAMP(55 + 2 * sg);
    }
    if (RSLOW) { wait_until(gtime() + 8000); wait_until(gtime() + 8000); wait_until(gtime() + 4000); }
    if (w < 2) {
      const int b = blockIdx.x, lane = LV, g = lane >> 2, t = lane & 3;
      uint4 v;
#pragma unroll 1
      for (int n = 0; n < SPIN_LIMIT; n++) {
        v = ldg_relaxed(g_red + T_RED + (w * 96 + b) * 512 + lane * 16);
        if (__all_sync(0xffffffffu, v.w == 0x5000u)) break;
        __nanosleep(40);
      }
      const float un = __uint_as_float(lds32(sb + T_UN + w * 4));
      uint32_t* const o = (uint32_t*)(tm.out + (size_t)((NAUXSEG + w) * 32 + b / 24 * 8 + g) * DM + (b >> 3) % 3 * 192 + (b & 1) * 32 + (b & 6) * 4) + t;
#pragma unroll
      for (int j = 0; j < 3; j++) {
        const float2 f = __half22float2(*(const __half2*)(&v.x + j));
        o[j * 32] = movm(pack_bf16(f.x * un, f.y * un));
      }
    }
  }
  TSTAMP(3);
  MSTAMP(8);
  if (CSY) cluster_sync();
}

__global__ void __cluster_dims__(3, 1, 1) __launch_bounds__(384, 1)
rec_kernel(const __grid_constant__ RMaps tm, const bf16* __restrict__ x, const bf16* __restrict__ mem0) {
  extern __shared__ __align__(1024) unsigned char smem_raw[];
  const uint32_t sb = smem_u32(smem_raw);
  const int tid = threadIdx.x, lane = tid & 31;
  const int wg = __shfl_sync(0xffffffffu, tid >> 7, 0);
  const int w = __shfl_sync(0xffffffffu, (tid >> 5) & 3, 0);
  uint32_t rank; asm("mov.u32 %0, %%cluster_ctarank;" : "=r"(rank));
  STAMP(0);
  TSTAMP(0);
  asm volatile("griddepcontrol.launch_dependents;" ::: "memory");

#define PFT 1
  if (PFT && wg == 1 && lane == 0) asm volatile("prefetch.tensormap [%0];\nprefetch.tensormap [%1];" :: "l"(w & 1 ? &tm.woa : &tm.oa), "l"(w == 0 ? (rank < 2 ? &tm.wk : &tm.wv) : w == 1 ? &tm.wq : w == 2 ? &tm.x : &tm.wo) : "memory");
  if (wg < 2) {
    asm volatile("setmaxnreg.inc.sync.aligned.u32 192;");
    if (tid == 0) {
      for (int i = 0; i < 3; i++) { mbar_init(sb + MB_W + 8 * i, 1); mbar_init(sb + MB_X + 8 * i, 1); }
      mbar_init(sb + MB_WO, 1); mbar_init(sb + MB_WO3, 1);
      mbar_init(sb + MB_S, rank < 2 ? 5 : 6);
      mbar_init(sb + MB_F, 1);
      for (int i = 0; i < 3; i++) mbar_init(sb + MB_T + 8 * i, 1);
      mbar_init(sb + MB_VX, 1); mbar_init(sb + MB_VX + 8, 1);
      asm volatile("fence.mbarrier_init.release.cluster;" ::: "memory");
      fence_async();
      SSTAMP(11, 6);
      load_weights(sb, tm, rank, 0);
      for (int i = 0; i < 3; i++) mbar_expect(sb + MB_X + 8 * i, XT);
      tma_load3(sb + SM_X, &tm.x, 0, sb + MB_X);
      if (!PACE) for (int c = 1; c < 4; c++) load_weights(sb, tm, rank, c);
      mbar_expect(sb + MB_S, rank < 2 ? 640 + 2048 : 1280);
      mbar_expect(sb + MB_VX, 8192); mbar_expect(sb + MB_VX + 8, 8192);
      mbar_expect(sb + MB_T, 2048);
      for (int i = 1; i < 3; i++) mbar_expect(sb + MB_T + 8 * i, rank < 2 ? 5120 : 10240);
      SSTAMP(11, 5);
    }
    __syncwarp();
    bar_sync(0, 384);
    proj_role(sb, tm, rank, wg, w, lane);
  } else {
    asm volatile("setmaxnreg.dec.sync.aligned.u32 120;");
    attn_role(sb, smem_raw, tm, rank, x, mem0, w, lane);
  }
}

constexpr int A_XH = 73728;
constexpr int A_NS = 9, A_WM = 6144, A_WT = 768;
constexpr int A_RING = 2 * A_XH, A_TAIL = A_RING + A_NS * A_WM, A_GW = A_TAIL + A_NS * A_WT;
constexpr int A_EPI = 212864, A_EPW = 9344;
constexpr int A_XW = 4 * XT, A_XT = A_XW + 4096, A_NR = 4;
constexpr int A_IN = A_XT + 2048, A_INS = 2 * 9216 + SEGB;
constexpr int A_GATE = A_EPI + 2 * A_EPW, A_BAR = A_GATE + 512;
constexpr int A_TOTAL = A_BAR + 384;
struct AMaps { CUtensorMap x, wa, wt, oa, o, o3, o8, wob, woa, wo8; };

DI void wgmma_n192_ss_nt(float* d, uint64_t da, uint64_t db, int acc) {
  asm volatile("{\n.reg .pred p;\nsetp.ne.b32 p, %98, 0;\n"
               "wgmma.mma_async.sync.aligned.m64n192k16.f32.bf16.bf16 {"
               "%0,%1,%2,%3,%4,%5,%6,%7,%8,%9,%10,%11,%12,%13,%14,%15,%16,%17,%18,%19,%20,%21,%22,%23,%24,%25,%26,%27,%28,%29,%30,%31,"
               "%32,%33,%34,%35,%36,%37,%38,%39,%40,%41,%42,%43,%44,%45,%46,%47,%48,%49,%50,%51,%52,%53,%54,%55,%56,%57,%58,%59,%60,%61,%62,%63,"
               "%64,%65,%66,%67,%68,%69,%70,%71,%72,%73,%74,%75,%76,%77,%78,%79,%80,%81,%82,%83,%84,%85,%86,%87,%88,%89,%90,%91,%92,%93,%94,%95"
               "}, %96, %97, p, 1, 1, 0, 1;\n}\n"
               : ACC8(d, 0), ACC8(d, 8), ACC8(d, 16), ACC8(d, 24), ACC8(d, 32), ACC8(d, 40), ACC8(d, 48), ACC8(d, 56),
                 ACC8(d, 64), ACC8(d, 72), ACC8(d, 80), ACC8(d, 88) : "l"(da), "l"(db), "r"(acc));
}
#define ACC4(d, o) "+f"(d[o]), "+f"(d[o + 1]), "+f"(d[o + 2]), "+f"(d[o + 3])
DI void wgmma_n24_ss_nt(float* d, uint64_t da, uint64_t db, int acc) {
  asm volatile("{\n.reg .pred p;\nsetp.ne.b32 p, %14, 0;\n"
               "wgmma.mma_async.sync.aligned.m64n24k16.f32.bf16.bf16 {%0,%1,%2,%3,%4,%5,%6,%7,%8,%9,%10,%11}, %12, %13, p, 1, 1, 0, 1;\n}\n"
               : ACC8(d, 0), ACC4(d, 8) : "l"(da), "l"(db), "r"(acc));
}
DI void wgmma_n8_ss(float* d, uint64_t da, uint64_t db, int acc) {
  asm volatile("{\n.reg .pred p;\nsetp.ne.b32 p, %6, 0;\n"
               "wgmma.mma_async.sync.aligned.m64n8k16.f32.bf16.bf16 {%0,%1,%2,%3}, %4, %5, p, 1, 1, 0, 0;\n}\n"
               : ACC4(d, 0) : "l"(da), "l"(db), "r"(acc));
}
DI void wgmma_n40_ss_tt(float* d, uint64_t da, uint64_t db, int acc) {
  asm volatile("{\n.reg .pred p;\nsetp.ne.b32 p, %22, 0;\n"
               "wgmma.mma_async.sync.aligned.m64n40k16.f32.bf16.bf16 {%0,%1,%2,%3,%4,%5,%6,%7,%8,%9,%10,%11,%12,%13,%14,%15,%16,%17,%18,%19}, "
               "%20, %21, p, 1, 1, 1, 1;\n}\n"
               : ACC8(d, 0), ACC8(d, 8), ACC4(d, 16) : "l"(da), "l"(db), "r"(acc));
}
DI void wgmma_n64_rs(float* d, const uint32_t* a, uint64_t db, int acc) {
  asm volatile("{\n.reg .pred p;\nsetp.ne.b32 p, %37, 0;\n"
               "wgmma.mma_async.sync.aligned.m64n64k16.f32.bf16.bf16 {"
               "%0,%1,%2,%3,%4,%5,%6,%7,%8,%9,%10,%11,%12,%13,%14,%15,%16,%17,%18,%19,%20,%21,%22,%23,%24,%25,%26,%27,%28,%29,%30,%31"
               "}, {%32,%33,%34,%35}, %36, p, 1, 1, 0;\n}\n"
               : ACC8(d, 0), ACC8(d, 8), ACC8(d, 16), ACC8(d, 24) : "r"(a[0]), "r"(a[1]), "r"(a[2]), "r"(a[3]), "l"(db), "r"(acc));
}
DI void wgmma_n32_ss_tn(float* d, uint64_t da, uint64_t db, int acc) {
  asm volatile("{\n.reg .pred p;\nsetp.ne.b32 p, %18, 0;\n"
               "wgmma.mma_async.sync.aligned.m64n32k16.f32.bf16.bf16 {%0,%1,%2,%3,%4,%5,%6,%7,%8,%9,%10,%11,%12,%13,%14,%15}, "
               "%16, %17, p, 1, 1, 1, 0;\n}\n"
               : ACC8(d, 0), ACC8(d, 8) : "l"(da), "l"(db), "r"(acc));
}
DI void tma_load3c(uint32_t dst, const CUtensorMap* m, int c0, int c1, int c2, uint32_t mb) {
  asm volatile("cp.async.bulk.tensor.3d.shared::cluster.global.mbarrier::complete_tx::bytes [%0], [%1, {%3, %4, %5}], [%2];"
               :: "r"(dst), "l"(m), "r"(mb), "r"(c0), "r"(c1), "r"(c2) : "memory");
}
DI void count_up(unsigned* p) {
  asm volatile("fence.proxy.async;" ::: "memory");
  asm volatile("red.release.gpu.global.add.u32 [%0], 1;" :: "l"(p) : "memory");
}
#define AX 0
#define FDLY 400
#define FEND 59
DI void publish(unsigned* p) {
  asm volatile("cp.async.bulk.wait_group 0;\nfence.proxy.async;" ::: "memory");
  asm volatile("red.relaxed.gpu.global.add.u32 [%0], 1;" :: "l"(p) : "memory");
}
#define PL 2
#define SER 35
#define DRAIN 0
#define PR 4
#define NQ 3
#define PUB 0
#define LA 1
#define LAG0 10
#define LEND 56
#define PDLY 0
#define ADLY 0

__global__ void __launch_bounds__(512, 1)
aux_kernel(const __grid_constant__ AMaps tm, const bf16* __restrict__ wqkv, const bf16* __restrict__ woa, const bf16* __restrict__ gate_w, bf16* __restrict__ out) {
  extern __shared__ __align__(1024) unsigned char smem_raw[];
  const uint32_t sb = smem_u32(smem_raw);
  const uint32_t fullx = sb + A_BAR, full1 = fullx + 24, empty1 = full1 + 8 * A_NS, fullw = empty1 + 8 * A_NS, full3 = fullw + 8, empty3 = full3 + 8 * A_NR,
                 fullq = empty3 + 8 * A_NR, emptyq = fullq + 24;
  const int tid = threadIdx.x, lane = tid & 31, cta = blockIdx.x;
  const int wg = __shfl_sync(0xffffffffu, tid >> 7, 0), w = __shfl_sync(0xffffffffu, (tid >> 5) & 3, 0);
  ASTAMP(14);
  if (tid == 384) {
    for (int i = 0; i < 3; i++) mbar_init(fullx + 8 * i, 1);
    for (int i = 0; i < A_NS; i++) { mbar_init(full1 + 8 * i, 1); mbar_init(empty1 + 8 * i, 8); }
    mbar_init(fullw, 1);
    for (int i = 0; i < 3; i++) { mbar_init(fullq + 8 * i, 1); mbar_init(emptyq + 8 * i, 4); }
    for (int i = 0; i < A_NR; i++) { mbar_init(full3 + 8 * i, 1); mbar_init(empty3 + 8 * i, cta < NH ? 8 : 4); }
    fence_async();
  }
  __syncthreads();
  ASTAMP(0);
  const int tile = cta >> 1, hh = cta & 1;
  auto p3_n = [&](int g) { return cta < NH ? (cta & 3) * 2 + g : 8; };
  auto p3_next = [&](int& sl, int& ph) {
    sl += cta < NH ? 1 : 2;
    if (sl >= (cta < NH ? 6 - NQ : 4)) { sl -= cta < NH ? 6 - NQ : 4; ph ^= 1; }
  };
  auto p3_k = [&](int g) { return cta < NH ? cta >> 2 : (cta & 3) * 2 + g; };
  if (wg == 3) {
    asm volatile("setmaxnreg.dec.sync.aligned.u32 24;");
    const bool lead = lane == 0;
    if (w < 3) {
      if (ADLY) wait_until(gtime() + ADLY);
      if (elect_one()) {
        mbar_expect(fullx + 8 * w, 49152);
        for (int p = 0; p < 2; p++)
          asm volatile("cp.async.bulk.tensor.4d.shared::cluster.global.mbarrier::complete_tx::bytes [%0], [%1, {%3, %4, %5, %6}], [%2];"
                       :: "r"(sb + p * A_XH + w * 24576), "l"(&tm.x), "r"(fullx + 8 * w), "r"(0), "r"(p), "r"(57 * tile - 7), "r"(3 * w) : "memory");
      }
#pragma unroll 1
      for (int r = 0; r < 17; r++) {
#pragma unroll 1
        for (int st = w; st < A_NS; st += 3) {
          if (r > 0) mbar_wait(empty1 + 8 * st, ~r & 1);
          if (r < 16 && elect_one()) {
            const int col = hh * 288 + (r >> 2) * 72, row = (r & 3) * 144 + st * 16;
            mbar_expect(full1 + 8 * st, A_WM + (AX & 1 ? 0 : A_WT));
            tma_load3c(sb + A_RING + st * A_WM, &tm.wa, col, row, 0, full1 + 8 * st);
            if (!(AX & 1)) tma_load3c(sb + A_TAIL + st * A_WT, &tm.wt, col + 64, row, 0, full1 + 8 * st);
          }
          __syncwarp();
        }
        if (r == 0 && elect_one())
          for (int j = 0; j < 3; j++)
            asm volatile("cp.async.bulk.prefetch.L2.global [%0], %1;" :: "l"((const char*)wqkv + cta * 55296 + (w * 3 + j) * 6144), "r"(6144) : "memory");
        __syncwarp();
      }
      bar_sync(8, 96);
    }
    const unsigned epoch = lds32(sb + A_BAR + 376);
    if (w == 2 && cta < NH) {
      if (lead) {
        int avail = 0, q = 0, ph = 1;
#pragma unroll 1
        for (int seg = 0; seg < NAUXSEG; seg++) {
          const unsigned char* const src = g_seg + ((size_t)(AX & 128 ? 0 : seg % NRING) * 96 + cta * 3) * SEGB;
          SSTAMP(0, seg);
          const int ref = seg + max(LAG0 * (LEND - seg) / LEND, 0);
          if (ref >= avail) {
            const unsigned* const c = &g_scnt[(ref * 32 + cta) * 8];
            const int c2 = ldg_relaxed32(c + 512) - 3 * (epoch + 1), c0 = ldg_acquire32(c) - 3 * (epoch + 1);
            avail = ref + (c2 >= 0 && LA ? 3 : 1);
            if (c0 < 0) {
              wait_count(c, 3 * (epoch + 1), !(TL & 2) || seg < NAUXSEG - 2);
              if (FDLY && seg < FEND) wait_until(gtime() + FDLY);
            }
          }
          SSTAMP(1, seg);
          const uint32_t mb = fullq + q * 8;
          mbar_wait(emptyq + q * 8, q == 2 ? ph ^ 1 : ph);
          if (AX & 8) mbar_arrive(mb); else mbar_expect(mb, A_INS);
#pragma unroll 1
          for (int r = 0; r < ((AX & 8) ? 0 : 3); r++)
            asm volatile("cp.async.bulk.shared::cluster.global.mbarrier::complete_tx::bytes [%0], [%1], %2, [%3];"
                         :: "r"(sb + (q < 2 ? A_IN + q * A_INS : 3 * XT) + r * 9216), "l"(src + r * SEGB), "r"(r < 2 ? 9216 : SEGB), "r"(mb) : "memory");
          if (seg == 1) wait_count(&g_abar[32], NAUX * (epoch + 1));
          if (seg > 1) stg_relaxed32(&g_used[cta * 32], epoch * NSEG + seg + 1 - NQ);
          if (++q == NQ) { q = 0; ph ^= 1; }
        }
      }
      return;
    }
    if (w == 3) {
#pragma unroll 1
      for (int c = 0; c < 4; c++) {
        if (lead) asm volatile("cp.async.bulk.wait_group.read 0;" ::: "memory");
        __syncwarp();
        bar_arrive(11, 160); bar_arrive(12, 160);
#pragma unroll 1
        for (int g = 0; g < 2; g++) {
          bar_sync(13 + g, 160);
          if (lead) {
            asm volatile("cp.async.bulk.tensor.3d.global.shared::cta.bulk_group [%0, {%2, %3, %4}], [%1];"
                         :: "l"(&tm.oa), "r"(sb + A_EPI + g * A_EPW + 1024), "r"(4096 + hh * 288 + c * 72), "r"(g), "r"(57 * tile) : "memory");
            asm volatile("cp.async.bulk.commit_group;" ::: "memory");
          }
        }
      }
      if (lead) publish(&g_abar[32]);
      __syncwarp();
    }
    if ((w & 1) && cta < NH) {
#pragma unroll 1
      for (int seg = w >> 1; seg < NAUXSEG; seg += 2) {
        bar_sync(w == 1 ? 4 : 15, 160);
        if (lead) {
          if (PUB == 0 || seg >= NAUXSEG - 2) publish(&g_ocnt[seg * 64 + 2 * cta / 9 * 8]);
          else {
            if (PUB == 1) asm volatile("fence.acq_rel.gpu;" ::: "memory"); else if (PUB > 2) wait_until(gtime() + PUB);
            asm volatile("red.relaxed.gpu.global.add.u32 [%0], 1;" :: "l"(&g_ocnt[seg * 64 + 2 * cta / 9 * 8]) : "memory");
          }
          if (2 * cta / 9 != (2 * cta + 1) / 9) asm volatile("red.relaxed.gpu.global.add.u32 [%0], 1;" :: "l"(&g_ocnt[seg * 64 + (2 * cta + 1) / 9 * 8]) : "memory");
          SSTAMP(9, seg);
        }
        __syncwarp();
      }
    }
    if (w & 1) return;
    if (w == 0) {
      if (lead) {
        mbar_expect(fullw, 18 * 8192 + 2048);
#pragma unroll 1
        for (int k = 0; k < 18; k++) {
          const int g = k / 9, kb = p3_k(g) * 9 + k - 9 * g;
          if (kb < 64) tma_load(sb + k * 8192, &tm.wob, p3_n(g) * 64, kb * 64, fullw);
          else tma_load(sb + k * 8192, &tm.woa, p3_n(g) * 64, (kb - 64) * 64, fullw);
        }
        for (int g = 0; g < 2; g++) tma_load(sb + A_XW + g * 2048, &tm.wo8, p3_n(g) * 64, 512 + p3_k(g) * 8, fullw);
      }
      __syncwarp();
    }
    bar_sync(6, cta >= NH ? 320 : 288);
    if (lead) {
      if (NQ == 3) for (int i = 0; i < 4; i++) mbar_arrive(emptyq + 16);
      wait_count(&g_abar[32], NAUX * (epoch + 1));
      int avail = 0, sl = w >> 1, ph = 1;
      const int ke = p3_k(w >> 1);
      const unsigned nheads = (ke < 7 ? 5 : 1) * (epoch + 1);
#pragma unroll 1
      for (int seg = 0; seg < NAUXSEG; seg++) {
        bool waited = false;
        if (seg >= avail) {
          const unsigned* const c = &g_ocnt[seg * 64 + ke * 8];
          const int c2 = ldg_relaxed32(c + 128) - nheads, c1 = ldg_relaxed32(c + 64) - nheads, c0 = ldg_acquire32(c) - nheads;
          waited = c0 < 0;
          if (waited) { wait_count(c, nheads, !(TL & 2) || seg < NAUXSEG - 2); if (PDLY && seg < FEND) wait_until(gtime() + PDLY); }
          else if (c1 >= 0) avail = seg + (c2 >= 0 ? 3 : 2);
        }
        SSTAMP(5, seg);
        mbar_wait(empty3 + 8 * sl, ph);
        if (AX & 4) mbar_arrive(full3 + 8 * sl);
        else {
          mbar_expect(full3 + 8 * sl, XT + 512);
          tma_load3c(sb + sl * XT, &tm.o3, 0, seg * 32, ke * 9, full3 + 8 * sl);
          tma_load(sb + A_XT + sl * 512, &tm.o8, 72 * 64 + ke * 8, seg * 32, full3 + 8 * sl);
        }
        p3_next(sl, ph);
      }
    }
  } else if (wg == 2) {
    asm volatile("setmaxnreg.dec.sync.aligned.u32 88;");
    {
      const unsigned epoch = *(volatile unsigned*)&g_epoch2;
      if ((tid & 127) < 80) { const uint4 g = __ldg((const uint4*)gate_w + min(tid & 127, 71)); sts128(sb + A_GW + (tid & 127) * 16, g.x, g.y, g.z, g.w); }
      fence_async();
      bar_sync(3, 128);
      float gt[2][4];
      const uint32_t d0 = (sb & 0x3FFFF) >> 4;
#pragma unroll 1
      for (int j = 0; j < 3; j++) {
        mbar_wait(fullx + 8 * j, 0);
        WG_FENCE();
#pragma unroll
        for (int k = 0; k < 24; k++)
          wgmma_n8_ss(gt[k & 1], desc_at(d0 + (k & 1) * (A_XH >> 4) + j * 1536 + (k >> 3) * 512 + (k & 6), 16, 1024, 1), desc_at(d0 + (A_GW >> 4) + j * 24 + (k & 30), 16, 128, 0), j | (k >> 1));
        WG_COMMIT();
      }
      WG_WAIT(0);
      if ((lane & 3) == 0)
#pragma unroll
        for (int i = 0; i < 4; i++) {
          const float gv = 1.f / (1.f + __expf(-gt[i >> 1][(i & 1) * 2]));
          const int r = w * 16 + (lane >> 2) + (i & 1) * 8, tok = 2 * (57 * tile - 7 + r) + (i >> 1);
          sts32(sb + A_GATE + ((i >> 1) * 64 + r) * 4, __float_as_uint(gv));
          if (hh == 0 && r >= 7 && tok < S_LEN) g_gate[tok] = gv;
        }
      if (tid == 256) sts32(sb + A_BAR + 376, epoch);
      __syncwarp();
      bar_arrive(7, 384);
      __half2 hw = __float2half2_rn(0.f);
#pragma unroll
      for (int i = 0; i < 9; i++) { const uint4 v = __ldg((const uint4*)woa + cta * 1152 + i * 128 + (tid & 127)); hw = amax4(hw, &v.x); }
      const uint32_t ew = wexp(hw);
      if (lane == 0) atomicMax(&g_amax[0], (unsigned long long)(epoch + 1) << 32 | ew);
      bar_sync(3, 128);
      if (tid == 256) {
        count_up(&g_abar[0]);
        wait_count(&g_abar[0], NAUX * (epoch + 1));
        if (cta == 0) *(volatile unsigned*)&g_epoch2 = epoch + 1;
      }
      __syncwarp();
      bar_sync(3, 128);
    }
    if (cta < NH) {
      const int lim = w * 8 + (lane >> 2) - 2 * (lane & 3);
      int q = 0, ph = 0;
      uint32_t p[5][4];
#pragma unroll
      for (int n = 0; n < 10; n++) p[n >> 1][1 + (n & 1)] = __shfl_sync(0xffffffffu, lane ^ n, n);
#pragma unroll 1
      for (int seg = 0; seg < NAUXSEG; seg++) {
        const float gt = __ldcg(&g_gate[seg * 32 + w * 8 + (lane >> 2)]);
        float sc[20], d[32];
        const uint32_t d0 = ((sb & 0x3FFFF) + (q < 2 ? A_IN + q * A_INS : 3 * XT)) >> 4;
        mbar_wait(fullq + q * 8, ph);
        if (tid == 256) SSTAMP(2, seg);
        WG_FENCE();
#pragma unroll
        for (int k = 0; k < 8; k++) {
          const int o = ((k >> 2) * 9216 + (k & 3) * 256) >> 4;
          wgmma_n40_ss_tt(sc, desc_at(d0 + o, 128, 512, 0), desc_at(d0 + o + 256, 128, 1024, 0), k > 0);
        }
        WG_COMMIT();
        WG_WAIT(0);
        if (tid == 256) SSTAMP(12, seg);
        float a[10];
#pragma unroll
        for (int i = 0; i < 10; i++) {
          a[i] = sc[(i >> 1) * 4 + (i & 1)] * (SM_SCALE * LOG2E);
          if (i < 8 && (i >> 1) * 8 + (i & 1) > lim) a[i] = -1.0e9f * LOG2E;
        }
        float m = max10(a);
        m = fmaxf(m, __shfl_xor_sync(0xffffffffu, m, 1)); m = fmaxf(m, __shfl_xor_sync(0xffffffffu, m, 2));
#pragma unroll
        for (int i = 0; i < 10; i++) a[i] = ex2(a[i] - m);
#pragma unroll
        for (int n = 0; n < 5; n++) {
          p[n][0] = pack_bf16(a[2 * n], a[2 * n + 1]); p[n][3] = p[n][0] | p[n][1];
          asm volatile("" : "+r"(p[n][0]), "+r"(p[n][3]) :: "memory");
        }
        float sum = ((a[0] + a[1]) + (a[2] + a[3])) + ((a[4] + a[5]) + (a[6] + a[7])) + (a[8] + a[9]);
        sum += __shfl_xor_sync(0xffffffffu, sum, 1);
        if (tid == 256) SSTAMP(3, seg);
        WG_FENCE();
#pragma unroll
        for (int n = 0; n < 5; n++) wgmma_n64_rs(d, p[n], n < 4 ? desc_at(d0 + 1152 + 8 * n, 4096, 512, 0) : desc_at(d0 + 1152 + 512, 1024, 128, 0), n);
        WG_COMMIT();
        sum += __shfl_xor_sync(0xffffffffu, sum, 2);
        const float f = (1.f - gt) * rcp(sum);
        WG_WAIT(0);
        if (lane == 0) mbar_arrive(emptyq + q * 8);
        if (++q == NQ) { q = 0; ph ^= 1; }
        if (tid == 256) SSTAMP(4, seg);
        unsigned char* const o = (unsigned char*)(g_Ocat + (size_t)(seg * 32 + w * 8 + (lane >> 2)) * KCAT + cta * DH) + (lane & 1) * 12 + (lane & 3) * 4;
#pragma unroll
        for (int n = 0; n < 8; n++) {
          const float* const v = d + (n & 3) * 8 + (n >> 2) * 2;
          const uint32_t x = pack_bf16(v[0] * f, v[1] * f), y = pack_bf16(v[4] * f, v[5] * f), z = __shfl_xor_sync(0xffffffffu, lane & 1 ? x : y, 1);
          if (!(AX & 32)) asm volatile("st.relaxed.gpu.global.v2.b32 [%0], {%1,%2};" :: "l"(o + n * 32), "r"(lane & 1 ? z : x), "r"(lane & 1 ? y : z) : "memory");
        }
        if (tid == 256) SSTAMP(13, seg);
        bar_sync(seg & 1 ? 15 : 4, 160);
      }
    }
  } else {
    asm volatile("setmaxnreg.inc.sync.aligned.u32 200;");
    {
      const int g = lane >> 2, t = lane & 3;
      const uint32_t eb = sb + A_EPI + wg * A_EPW, d0 = (sb & 0x3FFFF) >> 4;
      const uint32_t own = (2 * t <= g ? 0xffffu : 0u) | (2 * t < g ? 0xffff0000u : 0u);
      const int kmin = 7 - 57 * tile - 16 * w;
      __half2 ho = __float2half2_rn(0.f);
#pragma unroll 1
      for (int c = 0; c < 4; c++) {
        float acc[96], tl[12];
#pragma unroll 1
        for (int r = 0; r < 4; r++) {
#pragma unroll
          for (int st = 0; st < A_NS; st++) {
            const int ks = r * 9 + st;
            if (c == 0 && st % 3 == 0 && ks % 12 == 0) mbar_wait(fullx + 8 * (ks / 12), 0);
            mbar_wait(full1 + 8 * st, r & 1);
            const uint64_t da = desc_at(d0 + wg * (A_XH >> 4) + (ks >> 2) * 512 + (ks & 3) * 2, 16, 1024, 1);
            WG_FENCE();
            wgmma_n192_ss_nt(acc, da, desc_at(d0 + ((A_RING + st * A_WM) >> 4), 2048, 1024, 1), ks);
            if (!(AX & 2)) wgmma_n24_ss_nt(tl, da, desc_at(d0 + ((A_TAIL + st * A_WT) >> 4), 128, 256, 0), ks);
            WG_COMMIT();
            if (st == 0 && r == 2) bar_sync(11 + wg, 160);
            WG_WAIT(1);
            if (ks > 0 && lane == 0) mbar_arrive(empty1 + 8 * ((st + A_NS - 1) % A_NS));
          }
        }
        WG_WAIT(0);
        if (lane == 0) mbar_arrive(empty1 + 8 * (A_NS - 1));
        ASTAMP(16 + (c & 3));
        uint32_t ql[9], qh[9], kl[9], kh[9], kx[10], vl[9], vh[9], vx[10];
#pragma unroll
        for (int j = 0; j < 9; j++) {
          const float* const q = j < 8 ? acc + 4 * j : tl, * const k = j < 8 ? acc + 32 + 4 * j : tl + 4, * const v = j < 8 ? acc + 64 + 4 * j : tl + 8;
          kh[j] = pack_bf16(k[2], k[3]); vh[j] = pack_bf16(v[2], v[3]);
          ql[j] = pack_bf16(q[0], q[1]); qh[j] = pack_bf16(q[2], q[3]); kl[j] = pack_bf16(k[0], k[1]); vl[j] = pack_bf16(v[0], v[1]);
        }
        if (w < 3) {
          const uint32_t ha = eb + 1024 + w * 2304 + lane * 16;
          stsm4(ha, kh[0], kh[1], kh[2], kh[3]); stsm4(ha + 512, kh[4], kh[5], kh[6], kh[7]);
          stsm4(ha + 1024, vh[0], vh[1], vh[2], vh[3]); stsm4(ha + 1536, vh[4], vh[5], vh[6], vh[7]);
          asm volatile("stmatrix.sync.aligned.m8n8.x2.shared.b16 [%0], {%1,%2};" :: "r"(ha + 2048), "r"(kh[8]), "r"(vh[8]) : "memory");
        }
        if (c == 0) bar_sync(7, 384); else bar_sync(1 + wg, 128);
        {
          const uint32_t ha = eb + 1024 + max(w - 1, 0) * 2304 + lane * 16;
          ldsm4(kx, ha); ldsm4(kx + 4, ha + 512); ldsm4t(vx, ha + 1024); ldsm4t(vx + 4, ha + 1536);
          asm volatile("ldmatrix.sync.aligned.m8n8.x1.shared.b16 {%0}, [%1];" : "=r"(kx[8]) : "r"(ha + 2048) : "memory");
          asm volatile("ldmatrix.sync.aligned.m8n8.x1.trans.shared.b16 {%0}, [%1];" : "=r"(vx[8]) : "r"(ha + 2176) : "memory");
        }
        const float gl = __uint_as_float(lds32(sb + A_GATE + (wg * 64 + w * 16 + g) * 4)), gh = __uint_as_float(lds32(sb + A_GATE + (wg * 64 + w * 16 + g + 8) * 4));
#pragma unroll
        for (int j = 0; j < 9; j++) { vl[j] = movm(vl[j]); vh[j] = movm(vh[j]); }
        bar_sync(1 + wg, 128);
        uint32_t ol[9], oh[9];
#pragma unroll
        for (int i = 0; i < 4; i++) {
          const int b = 2 * i;
          const uint32_t a[4] = {t >= i ? ql[b] : 0u, t >= i ? qh[b] : 0u, ql[b + 1], qh[b + 1]}, a4 = t <= i ? ql[b + 2] : 0u, a5 = t <= i ? qh[b + 2] : 0u;
          float sx[4], sl[4], sh[4];
          mma16816z(sx, a, kx[b], kx[b + 1]); mma16816z(sl, a, kl[b], kl[b + 1]); mma16816z(sh, a, kh[b], kh[b + 1]);
          mma1688(sx, a4, a5, kx[b + 2]); mma1688(sl, a4, a5, kl[b + 2]); mma1688(sh, a4, a5, kh[b + 2]);
          float e[4];
#pragma unroll
          for (int u = 0; u < 4; u++) {
            const int cc = 2 * t + (u & 1);
            e[u] = (cc <= g ? (u < 2 ? sl[u] : sh[u]) : (u < 2 ? sx[u] : sl[u])) * (0.23570226039551584f * LOG2E);
            if ((cc <= g ? cc : cc - 8) + (u & 2) * 4 < kmin) e[u] = -1.0e9f * LOG2E;
          }
          float m0 = fmaxf(e[0], e[1]), m1 = fmaxf(e[2], e[3]);
#pragma unroll
          for (int o = 1; o < 4; o <<= 1) { m0 = fmaxf(m0, __shfl_xor_sync(0xffffffffu, m0, o)); m1 = fmaxf(m1, __shfl_xor_sync(0xffffffffu, m1, o)); }
          e[0] = ex2(e[0] - m0); e[1] = ex2(e[1] - m0); e[2] = ex2(e[2] - m1); e[3] = ex2(e[3] - m1);
          const uint32_t p0 = pack_bf16(e[0], e[1]), p1 = pack_bf16(e[2], e[3]);
          const uint32_t p[4] = {p0 & ~own, 0u, p0 & own, p1 & ~own};
          float s0 = e[0] + e[1], s1 = e[2] + e[3];
#pragma unroll
          for (int o = 1; o < 4; o <<= 1) { s0 += __shfl_xor_sync(0xffffffffu, s0, o); s1 += __shfl_xor_sync(0xffffffffu, s1, o); }
          const float f0 = gl * rcp(s0), f1 = gh * rcp(s1);
#pragma unroll
          for (int j = b; j < b + 3; j++) {
            float o[4];
            mma16816z(o, p, vx[j], vl[j]);
            mma1688(o, 0u, p1 & own, vh[j]);
            const uint32_t lo = pack_bf16(o[0] * f0, o[1] * f0), hi = pack_bf16(o[2] * f1, o[3] * f1);
            if (j > b || i == 0) { ol[j] = lo; oh[j] = hi; }
            else { ol[j] = t >= i ? lo : ol[j]; oh[j] = t >= i ? hi : oh[j]; }
          }
        }
        const uint32_t sa = eb + 16 + (w * 16 + (lane & 15)) * 144 + (lane >> 4) * 16;
#pragma unroll
        for (int j = 0; j < 8; j += 2) stsm4(sa + j * 16, ol[j], oh[j], ol[j + 1], oh[j + 1]);
        asm volatile("stmatrix.sync.aligned.m8n8.x2.shared.b16 [%0], {%1,%2};" :: "r"(sa + 128), "r"(ol[8]), "r"(oh[8]) : "memory");
        ho = amax4(amax4(amax4(amax4(ho, ol), ol + 4), oh), oh + 4);
        ho = __hmax2_nan(__hmax2_nan(ho, __habs2(*(const __half2*)&ol[8])), __habs2(*(const __half2*)&oh[8]));
        if (c == 3 && tile == 17) {
          const uint32_t eo = wexp(ho);
          if (lane == 0) atomicMax(&g_amax[16], (unsigned long long)(lds32(sb + A_BAR + 376) + 1) << 32 | eo);
        }
        fence_async();
        bar_arrive(13 + wg, 160);
        ASTAMP(20 + (c & 3));
      }
    }
    ASTAMP(3);
    uint32_t wa[36][4];
    mbar_wait(fullw, 0);
    const uint32_t la = sb + wg * 73728 + ((lane & 7) + ((lane >> 4) << 3)) * 128 + (((2 * w + ((lane >> 3) & 1)) ^ (lane & 7)) << 4);
#pragma unroll
    for (int k = 0; k < 36; k++) ldsm4t(wa[k], la + k * 2048);
    sts64(sb + A_XW + wg * 2048 + 1024 + (tid & 127) * 8, 0, 0);
    fence_async();
    bar_arrive(6, cta >= NH ? 320 : 288);
    bar_sync(1 + wg, 128);
    ASTAMP(4);
    const int nsl = p3_n(wg), ke = p3_k(wg), t = lane & 3;
    const unsigned epoch = lds32(sb + A_BAR + 376);
    uint2* const part = g_part + nsl * 4096 + w * 16 + (lane >> 2) * 2 + (t & 1);
    auto tag = [&](int seg) { return PR == 8 ? ((seg >> 3) + 1 + (epoch & (seg >> 1) & (seg >> 2))) & 1 : ((seg >> 2) + 1 + (epoch & (seg >> 1))) & 1; };
    uint2 v[4];
    auto fetch = [&](int seg) {
#pragma unroll
      for (int j = 0; j < 4; j++)
        asm volatile("ld.relaxed.gpu.global.v2.b32 {%0,%1}, [%2];" : "=r"(v[j].x), "=r"(v[j].y) : "l"(part + (seg & (PR - 1)) * 36864 + ke * 512 + ((t >> 1) * 4 + j) * 64) : "memory");
    };
    auto finish = [&](int seg) {
      int n = 0;
#pragma unroll 1
      while (!(AX & 16) && __any_sync(0xffffffffu, (((v[0].x ^ tag(seg)) | (v[1].x ^ tag(seg)) | (v[2].x ^ tag(seg)) | (v[3].x ^ tag(seg))) & 1) != 0) && ++n < SPIN_LIMIT) {
        if (seg < NAUXSEG - ((TL & 2) ? 2 : 1)) __nanosleep(100);
        fetch(seg);
      }
      const float a0 = (bf_lo(v[0].x) + bf_lo(v[1].x)) + (bf_lo(v[2].x) + bf_lo(v[3].x)), a1 = (bf_hi(v[0].x) + bf_hi(v[1].x)) + (bf_hi(v[2].x) + bf_hi(v[3].x));
      const float b0 = (bf_lo(v[0].y) + bf_lo(v[1].y)) + (bf_lo(v[2].y) + bf_lo(v[3].y)), b1 = (bf_hi(v[0].y) + bf_hi(v[1].y)) + (bf_hi(v[2].y) + bf_hi(v[3].y));
      const float c0 = (t < 2 ? a0 : b0) + __shfl_xor_sync(0xffffffffu, t < 2 ? b0 : a0, 2), c1 = (t < 2 ? a1 : b1) + __shfl_xor_sync(0xffffffffu, t < 2 ? b1 : a1, 2);
      ((uint32_t*)(out + (size_t)(seg * 32 + ke * 4 + ((lane >> 2) & 3)) * DM + nsl * 64 + w * 16 + (lane >> 4) * 8))[t] = movm(pack_bf16(c0, c1));
    };
    float acc[16];
    if (AX & 64) for (int i = 0; i < 16; i++) acc[i] = 0.f;
    int done = 0, sl = cta < NH ? 0 : wg, ph = 0;
    const uint32_t d0 = (sb & 0x3FFFF) >> 4;
#pragma unroll 1
    for (int seg = 0; seg < NAUXSEG; seg++) {
      if (DRAIN) {
#pragma unroll 1
        while (done < seg && !mbar_test(full3 + 8 * sl, ph)) { fetch(done); finish(done); done++; }
      }
      mbar_wait(full3 + 8 * sl, ph);
      if (SER && !(AX & 64) && (wg == 1 || seg > 0)) bar_sync(10 - wg, 256);
      if (tid == 128) SSTAMP(6, seg);
      if (!(AX & 16)) fetch(done);
      if (!(AX & 64)) {
        const uint64_t db = desc_at(d0 + sl * (XT >> 4), 16, 1024, 1);
        WG_FENCE();
        wgmma_n32_ss_tn(acc, desc_at(d0 + ((A_XW + wg * 2048) >> 4), 8192, 1024, 1), desc_at(d0 + (A_XT >> 4) + sl * 32, 0, 128, 0), 0);
#pragma unroll
        for (int k = 0; k < 36; k++) {
          wgmma_n32_rs(acc, wa[k][0], wa[k][1], wa[k][2], wa[k][3], db + (k >> 2) * 256 + (k & 3) * 2, 1);
          if (SER && k == SER && (wg == 0 || seg < NAUXSEG - 1)) bar_arrive(9 + wg, 256);
        }
        WG_COMMIT();
      }
      if (done <= seg - PL) finish(done++);
      WG_WAIT(0);
      if (lane == 0) mbar_arrive(empty3 + 8 * sl);
      p3_next(sl, ph);
#pragma unroll
      for (int j = 0; j < 4; j++)
        if (!(AX & 16) || acc[4 * j] == 1.2345678f)
          asm volatile("st.relaxed.gpu.global.v2.b32 [%0], {%1,%2};" :: "l"(part + (seg & (PR - 1)) * 36864 + (2 * j + (t >> 1)) * 512 + ke * 64),
                       "r"((pack_bf16(acc[4 * j], acc[4 * j + 1]) & ~1u) | tag(seg)), "r"(pack_bf16(acc[4 * j + 2], acc[4 * j + 3])) : "memory");
      if (tid == 128) SSTAMP(7, seg);
      if (tid == 128) SSTAMP(8, seg);
      if ((seg & 7) == 6) ASTAMP(5 + (seg >> 3));
    }
#pragma unroll 1
    for (; done < NAUXSEG; done++) { fetch(done); finish(done); }
    ASTAMP(13);
    TSTAMP(48);
    MSTAMP(9);
  }
}

typedef CUresult (*EncodeFn)(CUtensorMap*, CUtensorMapDataType, cuuint32_t, void*, const cuuint64_t*, const cuuint64_t*,
                             const cuuint32_t*, const cuuint32_t*, CUtensorMapInterleave, CUtensorMapSwizzle,
                             CUtensorMapL2promotion, CUtensorMapFloatOOBfill);
static void make_map(EncodeFn enc, CUtensorMap* m, const void* p, int rows, int cols, int box_rows) {
  cuuint64_t dims[2] = {(cuuint64_t)cols, (cuuint64_t)rows};
  cuuint64_t strides[1] = {(cuuint64_t)cols * 2};
  cuuint32_t box[2] = {64, (cuuint32_t)box_rows};
  cuuint32_t es[2] = {1, 1};
  enc(m, CU_TENSOR_MAP_DATA_TYPE_BFLOAT16, 2, (void*)p, dims, strides, box, es, CU_TENSOR_MAP_INTERLEAVE_NONE,
      CU_TENSOR_MAP_SWIZZLE_128B, CU_TENSOR_MAP_L2_PROMOTION_L2_128B, CU_TENSOR_MAP_FLOAT_OOB_FILL_NONE);
}

constexpr int g_poll = POLL_NS;
extern "C" void kernel_launch(void* const* d_in, const int* in_sizes, int n_in, void* d_out, int out_size) {
  const bf16* x = (const bf16*)d_in[0];
  const bf16* wqkvA = (const bf16*)d_in[1];
  const bf16* woA = (const bf16*)d_in[2];
  const bf16* mem0 = (const bf16*)d_in[4];
  const bf16* Wq = (const bf16*)d_in[5];
  const bf16* Wk = (const bf16*)d_in[6];
  const bf16* Wv = (const bf16*)d_in[7];
  const bf16* Wo = (const bf16*)d_in[8];
  const bf16* gate_w = (const bf16*)d_in[10];
  static EncodeFn enc = nullptr;
  static void *pO = nullptr, *pR = nullptr;
  if (!enc) {
    cudaDriverEntryPointQueryResult qr;
    cudaGetDriverEntryPoint("cuTensorMapEncodeTiled", (void**)&enc, cudaEnableDefault, &qr);
    cudaGetSymbolAddress(&pO, g_Ocat);
    cudaGetSymbolAddress(&pR, g_red_raw);
    cudaFuncSetAttribute(rec_kernel, cudaFuncAttributeMaxDynamicSharedMemorySize, SM_TOTAL);
    cudaFuncSetAttribute(aux_kernel, cudaFuncAttributeMaxDynamicSharedMemorySize, A_TOTAL);
  }
  RMaps rm;
  rm.poll = g_poll; rm.out = (bf16*)d_out;
  make_map(enc, &rm.woa, woA, DM, DM, 24);
  {
    cuuint64_t dims[2] = {KCAT, S_LEN}, strides[1] = {KCAT * 2};
    cuuint32_t box[2] = {32, 64}, es[2] = {1, 1};
    enc(&rm.oa, CU_TENSOR_MAP_DATA_TYPE_BFLOAT16, 2, pO, dims, strides, box, es, CU_TENSOR_MAP_INTERLEAVE_NONE,
        CU_TENSOR_MAP_SWIZZLE_NONE, CU_TENSOR_MAP_L2_PROMOTION_NONE, CU_TENSOR_MAP_FLOAT_OOB_FILL_NONE);
  }
  rm.red = (unsigned char*)(((uintptr_t)pR + 262143) & ~(uintptr_t)262143);
  {
    cuuint64_t dims[3] = {64, S_LEN, 9}, strides[2] = {DM * 2, 128};
    cuuint32_t box[3] = {64, 32, 9}, es[3] = {1, 1, 1};
    enc(&rm.x, CU_TENSOR_MAP_DATA_TYPE_BFLOAT16, 3, (void*)x, dims, strides, box, es, CU_TENSOR_MAP_INTERLEAVE_NONE,
        CU_TENSOR_MAP_SWIZZLE_128B, CU_TENSOR_MAP_L2_PROMOTION_L2_128B, CU_TENSOR_MAP_FLOAT_OOB_FILL_NONE);
  }
  make_map(enc, &rm.wq, Wq, DM, 4096, 192);
  make_map(enc, &rm.wk, Wk, DM, 4096, 192);
  make_map(enc, &rm.wv, Wv, DM, 4096, 192);
  make_map(enc, &rm.wo, Wo, 4096, DM, 128);
  AMaps am;
  {
    cuuint32_t es[4] = {1, 1, 1, 1};
    cuuint64_t dx[4] = {64, 2, S_LEN / 2, 9}, sx[3] = {DM * 2, DM * 4, 128};
    cuuint32_t bx[4] = {64, 1, 64, 3};
    enc(&am.x, CU_TENSOR_MAP_DATA_TYPE_BFLOAT16, 4, (void*)x, dx, sx, bx, es, CU_TENSOR_MAP_INTERLEAVE_NONE,
        CU_TENSOR_MAP_SWIZZLE_128B, CU_TENSOR_MAP_L2_PROMOTION_L2_128B, CU_TENSOR_MAP_FLOAT_OOB_FILL_NONE);
    cuuint64_t dw[3] = {DM, DM, 3}, sw[2] = {DM * 6, DM * 2};
    cuuint32_t bw[3] = {64, 16, 3}, bt[3] = {8, 16, 3};
    enc(&am.wa, CU_TENSOR_MAP_DATA_TYPE_BFLOAT16, 3, (void*)wqkvA, dw, sw, bw, es, CU_TENSOR_MAP_INTERLEAVE_NONE,
        CU_TENSOR_MAP_SWIZZLE_128B, CU_TENSOR_MAP_L2_PROMOTION_L2_128B, CU_TENSOR_MAP_FLOAT_OOB_FILL_NONE);
    enc(&am.wt, CU_TENSOR_MAP_DATA_TYPE_BFLOAT16, 3, (void*)wqkvA, dw, sw, bt, es, CU_TENSOR_MAP_INTERLEAVE_NONE,
        CU_TENSOR_MAP_SWIZZLE_NONE, CU_TENSOR_MAP_L2_PROMOTION_NONE, CU_TENSOR_MAP_FLOAT_OOB_FILL_NONE);
    cuuint64_t dz[3] = {KCAT, 2, S_LEN / 2}, sz[2] = {KCAT * 2, KCAT * 4};
    cuuint32_t bz[3] = {72, 1, 57};
    enc(&am.oa, CU_TENSOR_MAP_DATA_TYPE_BFLOAT16, 3, pO, dz, sz, bz, es, CU_TENSOR_MAP_INTERLEAVE_NONE,
        CU_TENSOR_MAP_SWIZZLE_NONE, CU_TENSOR_MAP_L2_PROMOTION_NONE, CU_TENSOR_MAP_FLOAT_OOB_FILL_NONE);
  }
  {
    cuuint64_t dims[3] = {64, S_LEN, KCAT / 64}, strides[2] = {KCAT * 2, 128};
    cuuint32_t box[3] = {64, 32, 9}, es[3] = {1, 1, 1};
    make_map(enc, &am.o, pO, S_LEN, KCAT, 32);
    enc(&am.o3, CU_TENSOR_MAP_DATA_TYPE_BFLOAT16, 3, pO, dims, strides, box, es, CU_TENSOR_MAP_INTERLEAVE_NONE,
        CU_TENSOR_MAP_SWIZZLE_128B, CU_TENSOR_MAP_L2_PROMOTION_L2_128B, CU_TENSOR_MAP_FLOAT_OOB_FILL_NONE);
  }
  make_map(enc, &am.wob, Wo, 4096, DM, 64);
  make_map(enc, &am.woa, woA, DM, DM, 64);
  make_map(enc, &am.wo8, woA, DM, DM, 8);
  {
    cuuint64_t dims[2] = {KCAT, S_LEN}, strides[1] = {KCAT * 2};
    cuuint32_t box[2] = {8, 32}, es[2] = {1, 1};
    enc(&am.o8, CU_TENSOR_MAP_DATA_TYPE_BFLOAT16, 2, pO, dims, strides, box, es, CU_TENSOR_MAP_INTERLEAVE_NONE,
        CU_TENSOR_MAP_SWIZZLE_NONE, CU_TENSOR_MAP_L2_PROMOTION_NONE, CU_TENSOR_MAP_FLOAT_OOB_FILL_NONE);
  }

  rec_kernel<<<96, 384, SM_TOTAL, cudaStreamPerThread>>>(rm, x, mem0);
  cudaLaunchConfig_t cfg = {};
  cfg.gridDim = dim3(NAUX); cfg.blockDim = dim3(512); cfg.dynamicSmemBytes = A_TOTAL; cfg.stream = cudaStreamPerThread;
  cudaLaunchAttribute at[1];
  at[0].id = cudaLaunchAttributeProgrammaticStreamSerialization; at[0].val.programmaticStreamSerializationAllowed = 1;
  cfg.attrs = at; cfg.numAttrs = 1;
  if (XP & 16) cfg.numAttrs = 0;
  if (!(XP & 64)) cudaLaunchKernelEx(&cfg, aux_kernel, am, wqkvA, woA, gate_w, (bf16*)d_out);
}
```

```cpp
#include <cuda_runtime.h>
#include <cuda_bf16.h>
#include <cuda_fp16.h>
#include <cuda.h>
#include <stdint.h>

typedef __nv_bfloat16 bf16;

constexpr int S_LEN = 2048, DM = 576, NH = 32, DH = 128, NSEG = 64, KCAT = 4096 + 576;
constexpr int NAUXSEG = NSEG - 2;
constexpr int NAUX = 36;
#define RED_LINE(i) (((i) >> 2) * 4096 + ((i) & 1) * 256 + ((i) & 2) * 512)
#define RED_SLOT(s) (((s) & 1) * 128 + ((s) & 2) * 256)

#define POLL_NS 880
#define NII 18
#define W3PRE 4
#define W3MID 4
#define GF 0
#define B5POS 0
#define NUP 4
#define UPF 1
#define B3Q 9
#define B3F 0
#define GATE 7
#define NTL 2
#define B7R 1
#define VS0 1
#define VS1 0
#define VLATE(w) ((w) == 0 ? VS0 == 1 : (w) == 1 ? VS1 == 1 : false)
#define HOIST 0
#define RSLOW 0
#define CSY 0
#define DD 2
#define N12 18
#define N14 18
#define HP 0
#define HL 0
#define WL 1
#define RV 3
#define EXM 1
#define PSTAMP 0
#define PFIX 1
#define RET 1
#define TL 6
#define CLR 1
#define RFW 0
#define NIC 0
#define LEAD 0
#define FIN16 1
#define VXG 0
#define NRING 20
#define EXD 0
#define HDLY 0
#define F10 1
#define NPROBE 2
#define QM 0
#define N5 224
#define KP(i) (((i) >> 1) + 4 * ((i) & 1))
#define SPIN_LIMIT (1 << 14)
#define XP 0

__device__ __align__(1024) bf16 g_Ocat[S_LEN * KCAT];
__device__ __align__(1024) unsigned char g_red_raw[2 * 262144];
constexpr int HINT_OFF = 2048;
__device__ __align__(16) float g_gate[S_LEN];
__device__ __align__(128) uint4 g_stats[96 * 2];
__device__ unsigned g_epoch;
__device__ unsigned g_epoch2;
__device__ unsigned g_ocnt[NSEG * 64];
__device__ unsigned g_abar[3 * 32];
__device__ unsigned long long g_amax[2 * 16];
__device__ unsigned g_scnt[NSEG * 32 * 8];
__device__ __align__(1024) unsigned char g_seg[NRING * 96 * 10240];
__device__ unsigned g_used[NH * 32];
__device__ __align__(1024) uint2 g_part[8 * 9 * 64 * 64];
__device__ int g_err;
#define MSTAMP(i)
#define TSTAMP(i)
#define PROF(idx)
#define PROFP(idx)
#define RSTAMP(k)
#define STAMP(idx)
#define ASTAMP(idx)
#define SSTAMP(k, seg)
#define WSTAMP(idx)

#define DI __device__ __forceinline__
DI uint32_t smem_u32(const void* p) { return (uint32_t)__cvta_generic_to_shared(p); }
DI uint32_t clock32() { uint32_t c; asm volatile("mov.u32 %0, %%clock;" : "=r"(c) :: "memory"); return c; }
DI uint32_t gtime() { uint32_t c; asm volatile("mov.u32 %0, %%globaltimer_lo;" : "=r"(c) :: "memory"); return c; }
DI uint32_t ldg_relaxed32(const void* p) { uint32_t v; asm volatile("ld.relaxed.gpu.global.b32 %0, [%1];" : "=r"(v) : "l"(p) : "memory"); return v; }
DI uint32_t ldg_acquire32(const void* p) { uint32_t v; asm volatile("ld.acquire.gpu.global.b32 %0, [%1];" : "=r"(v) : "l"(p) : "memory"); return v; }
DI void stg_relaxed32(void* p, uint32_t v) { asm volatile("st.relaxed.gpu.global.b32 [%0], %1;" :: "l"(p), "r"(v) : "memory"); }
DI int head_id() { int c; asm volatile("mov.u32 %0, %%clusterid.x;" : "=r"(c)); return c; }
DI uint32_t mapa(uint32_t a, uint32_t r) { uint32_t o; asm("mapa.shared::cluster.u32 %0, %1, %2;" : "=r"(o) : "r"(a), "r"(r)); return o; }
DI void cluster_arrive() { asm volatile("barrier.cluster.arrive.relaxed.aligned;" ::: "memory"); }
DI void cluster_wait() { asm volatile("barrier.cluster.wait.aligned;" ::: "memory"); }
DI void cluster_sync() { asm volatile("barrier.cluster.arrive.release.aligned;\nbarrier.cluster.wait.acquire.aligned;" ::: "memory"); }
DI void mbar_init(uint32_t b, uint32_t c) { asm volatile("mbarrier.init.shared::cta.b64 [%0], %1;" :: "r"(b), "r"(c) : "memory"); }
DI void mbar_expect(uint32_t b, uint32_t tx) { asm volatile("mbarrier.arrive.expect_tx.shared::cta.b64 _, [%0], %1;" :: "r"(b), "r"(tx) : "memory"); }
DI void mbar_arrive(uint32_t b) { asm volatile("mbarrier.arrive.shared::cta.b64 _, [%0];" :: "r"(b) : "memory"); }
DI void mbar_wait(uint32_t b, uint32_t par) {
  asm volatile("{\n.reg .pred p;\n.reg .u32 n, q;\nmov.u32 n, 0;\n"
               "WL: add.u32 n, n, 1;\nshr.u32 q, n, 12;\nxor.b32 q, q, %1;\n"
               "mbarrier.try_wait.parity.shared::cta.b64 p, [%0], q;\n@!p bra.uni WL;\n}"
               :: "r"(b), "r"(par) : "memory");
}
DI bool mbar_test(uint32_t b, uint32_t par) {
  uint32_t r;
  asm volatile("{\n.reg .pred p;\nmbarrier.test_wait.parity.shared::cta.b64 p, [%1], %2;\nselp.u32 %0, 1, 0, p;\n}" : "=r"(r) : "r"(b), "r"(par) : "memory");
  return r;
}
DI void mbar_wait_fast(uint32_t b, uint32_t par) {
  asm volatile("{\n.reg .pred p;\n.reg .u32 n, q;\nmbarrier.try_wait.parity.shared::cta.b64 p, [%0], %1;\n@p bra.uni WD;\nmov.u32 n, 0;\n"
               "WL: add.u32 n, n, 1;\nshr.u32 q, n, 12;\nxor.b32 q, q, %1;\n"
               "mbarrier.try_wait.parity.shared::cta.b64 p, [%0], q;\n@!p bra.uni WL;\nWD:\n}"
               :: "r"(b), "r"(par) : "memory");
}
DI void wait_until(uint32_t t) {
  const uint32_t now = gtime();
  t = min(t, now + 8192);
  asm volatile("{\n.reg .pred p;\n.reg .u32 c;\nTL: mov.u32 c, %%globaltimer_lo;\nsetp.lt.u32 p, c, %0;\n@p bra.uni TL;\n}" :: "r"(t) : "memory");
}
#define PIN(v) v = __shfl_xor_sync(0xffffffffu, v, 0)
#define SCHED_FENCE(k) asm volatile("{\n.reg .pred p;\nsetp.eq.u32 p, %0, %1;\n@p exit;\n}" :: "r"(fence_reg), "r"(k) : "memory")
#define MEM_ORDER(k) asm volatile("{\n.reg .pred p;\nsetp.eq.u32 p, %0, %1;\n@p st.shared.u32 [%0], %0;\n}" :: "r"(fence_reg), "r"(k + 64) : "memory")
DI void bar_sync(int id, int n) { asm volatile("bar.sync %0, %1;" :: "r"(id), "r"(n) : "memory"); }
DI void bar_arrive(int id, int n) { asm volatile("bar.arrive %0, %1;" :: "r"(id), "r"(n) : "memory"); }
DI void fence_async() { asm volatile("fence.proxy.async.shared::cta;" ::: "memory"); }
DI void st_async4(uint32_t a, uint32_t x, uint32_t y, uint32_t z, uint32_t w, uint32_t mb) {
  asm volatile("st.async.weak.shared::cluster.mbarrier::complete_tx::bytes.v4.b32 [%0], {%1,%2,%3,%4}, [%5];"
               :: "r"(a), "r"(x), "r"(y), "r"(z), "r"(w), "r"(mb) : "memory");
}
DI void st_async2(uint32_t a, uint32_t x, uint32_t y, uint32_t mb) {
  asm volatile("st.async.weak.shared::cluster.mbarrier::complete_tx::bytes.v2.b32 [%0], {%1,%2}, [%3];"
               :: "r"(a), "r"(x), "r"(y), "r"(mb) : "memory");
}
DI void sts32(uint32_t a, uint32_t x) { asm volatile("st.shared.b32 [%0], %1;" :: "r"(a), "r"(x) : "memory"); }
DI void sts64(uint32_t a, uint32_t x, uint32_t y) { asm volatile("st.shared.v2.b32 [%0], {%1,%2};" :: "r"(a), "r"(x), "r"(y) : "memory"); }
DI void sts128(uint32_t a, uint32_t x, uint32_t y, uint32_t z, uint32_t w) {
  asm volatile("st.shared.v4.b32 [%0], {%1,%2,%3,%4};" :: "r"(a), "r"(x), "r"(y), "r"(z), "r"(w) : "memory");
}
DI uint32_t lds32(uint32_t a) { uint32_t x; asm volatile("ld.shared.b32 %0, [%1];" : "=r"(x) : "r"(a) : "memory"); return x; }
DI void lds64(uint32_t a, uint32_t& x, uint32_t& y) { asm volatile("ld.shared.v2.b32 {%0,%1}, [%2];" : "=r"(x), "=r"(y) : "r"(a) : "memory"); }
DI void lds128(uint32_t a, uint32_t* r) {
  asm volatile("ld.shared.v4.b32 {%0,%1,%2,%3}, [%4];" : "=r"(r[0]), "=r"(r[1]), "=r"(r[2]), "=r"(r[3]) : "r"(a) : "memory");
}
DI void lds128f(uint32_t a, float* r) {
  asm volatile("ld.shared.v4.f32 {%0,%1,%2,%3}, [%4];" : "=f"(r[0]), "=f"(r[1]), "=f"(r[2]), "=f"(r[3]) : "r"(a) : "memory");
}
DI void lds64f(uint32_t a, float* r) { asm volatile("ld.shared.v2.f32 {%0,%1}, [%2];" : "=f"(r[0]), "=f"(r[1]) : "r"(a) : "memory"); }
DI void ldsm4t(uint32_t* r, uint32_t a) {
  asm volatile("ldmatrix.sync.aligned.m8n8.x4.trans.shared.b16 {%0,%1,%2,%3}, [%4];"
               : "=r"(r[0]), "=r"(r[1]), "=r"(r[2]), "=r"(r[3]) : "r"(a) : "memory");
}
DI void ldsm4t_in(uint32_t* r, uint32_t a, uint32_t t) {
  asm volatile("{\n.reg .pred p;\nsetp.ne.u32 p, %5, 0;\n@p ldmatrix.sync.aligned.m8n8.x4.trans.shared.b16 {%0,%1,%2,%3}, [%4];\n}"
               : "+r"(r[0]), "+r"(r[1]), "+r"(r[2]), "+r"(r[3]) : "r"(a), "r"(t) : "memory");
}
DI void lds128_in(uint32_t* r, uint32_t a, uint32_t t) {
  asm volatile("{\n.reg .pred p;\nsetp.ne.u32 p, %5, 0;\n@p ld.shared.v4.b32 {%0,%1,%2,%3}, [%4];\n}"
               : "+r"(r[0]), "+r"(r[1]), "+r"(r[2]), "+r"(r[3]) : "r"(a), "r"(t) : "memory");
}
DI void ldsm2t_in(uint32_t* r, uint32_t a, uint32_t t) {
  asm volatile("{\n.reg .pred p;\nsetp.ne.u32 p, %3, 0;\n@p ldmatrix.sync.aligned.m8n8.x2.trans.shared.b16 {%0,%1}, [%2];\n}" : "+r"(r[0]), "+r"(r[1]) : "r"(a), "r"(t) : "memory");
}
DI void reserve2(uint32_t* r) { asm volatile("{\n.reg .u64 t;\nmov.u64 t, %%clock64;\nmov.b64 {%0, %1}, t;\n}" : "=r"(r[0]), "=r"(r[1])); }
DI void scale_sum(float& x, float& y, float s, uint32_t t) {
  asm volatile("{\n.reg .pred p;\nsetp.ne.u32 p, %2, 0;\n@p mul.f32 %0, %0, %1;\n}" : "+f"(y) : "f"(s), "r"(t));
  asm volatile("{\n.reg .pred p;\nsetp.ne.u32 p, %3, 1;\n@p fma.rn.f32 %0, %0, %1, %2;\n}" : "+f"(x) : "f"(s), "f"(y), "r"(t));
}
DI void ldsm4(uint32_t* r, uint32_t a) {
  asm volatile("ldmatrix.sync.aligned.m8n8.x4.shared.b16 {%0,%1,%2,%3}, [%4];"
               : "=r"(r[0]), "=r"(r[1]), "=r"(r[2]), "=r"(r[3]) : "r"(a) : "memory");
}
DI void st_async1(uint32_t a, uint32_t x, uint32_t mb) {
  asm volatile("st.async.weak.shared::cluster.mbarrier::complete_tx::bytes.b32 [%0], %1, [%2];" :: "r"(a), "r"(x), "r"(mb) : "memory");
}
DI void stsm4(uint32_t a, uint32_t x, uint32_t y, uint32_t z, uint32_t w) {
  asm volatile("stmatrix.sync.aligned.m8n8.x4.shared.b16 [%0], {%1,%2,%3,%4};" :: "r"(a), "r"(x), "r"(y), "r"(z), "r"(w) : "memory");
}
DI void stsm4t(uint32_t a, uint32_t x, uint32_t y, uint32_t z, uint32_t w) {
  asm volatile("stmatrix.sync.aligned.m8n8.x4.trans.shared.b16 [%0], {%1,%2,%3,%4};" :: "r"(a), "r"(x), "r"(y), "r"(z), "r"(w) : "memory");
}
DI uint32_t pack_bf16(float lo, float hi) { uint32_t r; asm("cvt.rn.bf16x2.f32 %0, %1, %2;" : "=r"(r) : "f"(hi), "f"(lo)); return r; }
DI uint32_t pack_f16(float lo, float hi) { uint32_t r; asm("cvt.rn.f16x2.f32 %0, %1, %2;" : "=r"(r) : "f"(hi), "f"(lo)); return r; }
DI float ex2(float x) { float y; asm("ex2.approx.ftz.f32 %0, %1;" : "=f"(y) : "f"(x)); return y; }
DI float rcp(float x) { float y; asm("rcp.approx.ftz.f32 %0, %1;" : "=f"(y) : "f"(x)); return y; }
DI float bf_lo(uint32_t x) { return __uint_as_float(x << 16); }
DI float bf_hi(uint32_t x) { return __uint_as_float(x & 0xffff0000u); }
DI void mma16816(float* d, const uint32_t* a, uint32_t b0, uint32_t b1) {
  asm volatile("mma.sync.aligned.m16n8k16.row.col.f32.bf16.bf16.f32 {%0,%1,%2,%3}, {%4,%5,%6,%7}, {%8,%9}, {%0,%1,%2,%3};"
               : "+f"(d[0]), "+f"(d[1]), "+f"(d[2]), "+f"(d[3]) : "r"(a[0]), "r"(a[1]), "r"(a[2]), "r"(a[3]), "r"(b0), "r"(b1));
}
DI void mma16816z(float* d, const uint32_t* a, uint32_t b0, uint32_t b1) {
  asm volatile("mma.sync.aligned.m16n8k16.row.col.f32.bf16.bf16.f32 {%0,%1,%2,%3}, {%4,%5,%6,%7}, {%8,%9}, {%10,%10,%10,%10};"
               : "=f"(d[0]), "=f"(d[1]), "=f"(d[2]), "=f"(d[3]) : "r"(a[0]), "r"(a[1]), "r"(a[2]), "r"(a[3]), "r"(b0), "r"(b1), "f"(0.f));
}
DI void mma1688z(float* d, uint32_t a0, uint32_t a1, uint32_t b0) {
  asm volatile("mma.sync.aligned.m16n8k8.row.col.f32.bf16.bf16.f32 {%0,%1,%2,%3}, {%4,%5}, {%6}, {%7,%7,%7,%7};"
               : "=f"(d[0]), "=f"(d[1]), "=f"(d[2]), "=f"(d[3]) : "r"(a0), "r"(a1), "r"(b0), "f"(0.f));
}
DI void mma1688(float* d, uint32_t a0, uint32_t a1, uint32_t b0) {
  asm volatile("mma.sync.aligned.m16n8k8.row.col.f32.bf16.bf16.f32 {%0,%1,%2,%3}, {%4,%5}, {%6}, {%0,%1,%2,%3};"
               : "+f"(d[0]), "+f"(d[1]), "+f"(d[2]), "+f"(d[3]) : "r"(a0), "r"(a1), "r"(b0));
}
DI void ldsm2t(uint32_t* r, uint32_t a) {
  asm volatile("ldmatrix.sync.aligned.m8n8.x2.trans.shared.b16 {%0,%1}, [%2];" : "=r"(r[0]), "=r"(r[1]) : "r"(a) : "memory");
}
DI uint32_t add_bf16(uint32_t a, uint32_t b) { uint32_t r; asm("add.rn.bf16x2 %0, %1, %2;" : "=r"(r) : "r"(a), "r"(b)); return r; }
DI uint32_t mul_bf16(uint32_t a, uint32_t b) { uint32_t r; asm("mul.rn.bf16x2 %0, %1, %2;" : "=r"(r) : "r"(a), "r"(b)); return r; }
DI uint64_t make_desc(uint32_t addr, uint32_t lbo, uint32_t sbo, uint32_t swz) {
  return (uint64_t)((addr & 0x3FFFF) >> 4) | ((uint64_t)(lbo >> 4) << 16) | ((uint64_t)(sbo >> 4) << 32) | ((uint64_t)swz << 62);
}
DI uint64_t desc_at(uint32_t a16, uint32_t lbo, uint32_t sbo, uint32_t swz) {
  uint64_t d; asm("mov.b64 %0, {%1, %2};" : "=l"(d) : "r"(a16 + ((lbo >> 4) << 16)), "r"((sbo >> 4) | (swz << 30)));
  return d;
}
#define WG_FENCE() asm volatile("wgmma.fence.sync.aligned;" ::: "memory")
#define WG_COMMIT() asm volatile("wgmma.commit_group.sync.aligned;" ::: "memory")
#define WG_WAIT(n) asm volatile("wgmma.wait_group.sync.aligned %0;" :: "n"(n) : "memory")
#define ACC8(d, o) "+f"(d[o]), "+f"(d[o + 1]), "+f"(d[o + 2]), "+f"(d[o + 3]), "+f"(d[o + 4]), "+f"(d[o + 5]), "+f"(d[o + 6]), "+f"(d[o + 7])
DI void wgmma_n32_rs(float* d, uint32_t a0, uint32_t a1, uint32_t a2, uint32_t a3, uint64_t db, int acc) {
  asm volatile("{\n.reg .pred p;\nsetp.ne.b32 p, %21, 0;\n"
               "wgmma.mma_async.sync.aligned.m64n32k16.f32.bf16.bf16 {%0,%1,%2,%3,%4,%5,%6,%7,%8,%9,%10,%11,%12,%13,%14,%15}, "
               "{%16,%17,%18,%19}, %20, p, 1, 1, 0;\n}\n"
               : ACC8(d, 0), ACC8(d, 8) : "r"(a0), "r"(a1), "r"(a2), "r"(a3), "l"(db), "r"(acc));
}
template <int TA>
DI void wgmma_n32_ss(float* d, uint64_t da, uint64_t db, int acc) {
  asm volatile("{\n.reg .pred p;\nsetp.ne.b32 p, %18, 0;\n"
               "wgmma.mma_async.sync.aligned.m64n32k16.f32.bf16.bf16 {%0,%1,%2,%3,%4,%5,%6,%7,%8,%9,%10,%11,%12,%13,%14,%15}, "
               "%16, %17, p, 1, 1, %19, 1;\n}\n"
               : ACC8(d, 0), ACC8(d, 8) : "l"(da), "l"(db), "r"(acc), "n"(TA));
}
DI void tma_load(uint32_t dst, const CUtensorMap* m, int c0, int c1, uint32_t mb) {
  asm volatile("cp.async.bulk.tensor.2d.shared::cluster.global.mbarrier::complete_tx::bytes [%0], [%1, {%3, %4}], [%2];"
               :: "r"(dst), "l"(m), "r"(mb), "r"(c0), "r"(c1) : "memory");
}
DI void tma_load3(uint32_t dst, const CUtensorMap* m, int row, uint32_t mb) {
  asm volatile("cp.async.bulk.tensor.3d.shared::cluster.global.mbarrier::complete_tx::bytes [%0], [%1, {%3, %4, %3}], [%2];"
               :: "r"(dst), "l"(m), "r"(mb), "r"(0), "r"(row) : "memory");
}
DI bool elect_one() {
  uint32_t p;
  asm volatile("{\n.reg .pred p;\nelect.sync _|p, 0xffffffff;\nselp.u32 %0, 1, 0, p;\n}" : "=r"(p));
  return p;
}
DI void bulk_s2s(uint32_t dst, uint32_t src, uint32_t bytes, uint32_t mb) {
  asm volatile("cp.async.bulk.shared::cluster.shared::cta.mbarrier::complete_tx::bytes [%0], [%1], %2, [%3];"
               :: "r"(dst), "r"(src), "r"(bytes), "r"(mb) : "memory");
}
DI void tma_prefetch(const CUtensorMap* m, int c0, int c1) {
  asm volatile("cp.async.bulk.prefetch.tensor.2d.L2.global.tile [%0, {%1, %2}];" :: "l"(m), "r"(c0), "r"(c1) : "memory");
}
DI void tma_store(const CUtensorMap* m, uint32_t src, int c0, int c1) {
  asm volatile("cp.async.bulk.tensor.2d.global.shared::cta.bulk_group [%0, {%2, %3}], [%1];" :: "l"(m), "r"(src), "r"(c0), "r"(c1) : "memory");
}
DI uint4 ldg_relaxed(const void* p) {
  uint4 v;
  asm volatile("ld.relaxed.gpu.global.v4.b32 {%0,%1,%2,%3}, [%4];" : "=r"(v.x), "=r"(v.y), "=r"(v.z), "=r"(v.w) : "l"(p) : "memory");
  return v;
}
DI void stg_relaxed(void* p, uint32_t x, uint32_t y, uint32_t z, uint32_t w) {
  asm volatile("st.relaxed.gpu.global.v4.b32 [%0], {%1,%2,%3,%4};" :: "l"(p), "r"(x), "r"(y), "r"(z), "r"(w) : "memory");
}
DI void red_f16x8(void* p, uint32_t x, uint32_t y, uint32_t z, uint32_t w) {
  asm volatile("red.relaxed.gpu.global.add.noftz.v4.f16x2 [%0], {%1,%2,%3,%4};" :: "l"(p), "r"(x), "r"(y), "r"(z), "r"(w) : "memory");
}
DI void sq_acc(uint32_t& a, uint32_t x) { asm("fma.rn.bf16x2 %0, %1, %1, %0;" : "+r"(a) : "r"(x)); }
DI __half2 amax4(__half2 h, const uint32_t* v) {
  h = __hmax2_nan(__hmax2_nan(h, __habs2(*(const __half2*)&v[0])), __habs2(*(const __half2*)&v[1]));
  return __hmax2_nan(__hmax2_nan(h, __habs2(*(const __half2*)&v[2])), __habs2(*(const __half2*)&v[3]));
}
DI uint32_t wexp(__half2 h) { const uint32_t u = *(const uint32_t*)&h; return __reduce_max_sync(0xffffffffu, max((u >> 16) & 0x7fffu, u & 0x7fffu)) >> 7; }
DI float max10(const float* a) {
  return fmaxf(fmaxf(fmaxf(fmaxf(a[0], a[1]), fmaxf(a[2], a[3])), fmaxf(fmaxf(a[4], a[5]), fmaxf(a[6], a[7]))), fmaxf(a[8], a[9]));
}
DI float quad_max(float m) {
  return fmaxf(fmaxf(m, __shfl_xor_sync(0xffffffffu, m, 1)), fmaxf(__shfl_xor_sync(0xffffffffu, m, 2), __shfl_xor_sync(0xffffffffu, m, 3)));
}
DI float warp_sum(float v) {
#pragma unroll
  for (int o = 16; o; o >>= 1) v += __shfl_xor_sync(0xffffffffu, v, o);
  return v;
}

constexpr int SM_WO3 = 0;
constexpr int SM_X = 16384;
constexpr int XT = 36864;
constexpr int SM_EXP = 126976;
constexpr int SEGB = 10240;
constexpr int SM_BLK = SM_EXP + 8192;
constexpr int SM_VC = SM_BLK + 4 * SEGB;
constexpr int SM_PART = SM_VC + 16384;
constexpr int SM_QM = SM_PART + 4096;
constexpr int SM_E = SM_QM + 1024;
constexpr int SM_VM = SM_E + 1536;
constexpr int SM_OB = SM_VM + 2048;
constexpr int SM_FB = SM_OB + 2048;
constexpr int SM_STAGE = SM_X + XT;
constexpr int SM_MISC = 210944;
constexpr int SM_WOST = 212992;
constexpr int SM_MEM = SM_WOST;
constexpr int SM_MAX = SM_MEM + 11264;
#define MEM_BLK(q) ((q) / 3 * 4096 + (q) % 3 * 1024)
constexpr int SM_TOTAL = 229376;
constexpr int MB_W = SM_MISC;
constexpr int MB_WO = SM_MISC + 24;
constexpr int MB_WO3 = SM_MISC + 32;
constexpr int MB_X = SM_MISC + 40;
constexpr int MB_S = SM_MISC + 64;
constexpr int MB_F = SM_MISC + 72;
constexpr int MB_VX = SM_MISC + 80;
constexpr int SC_FPAR = SM_MISC + 136;
constexpr int SC_DEAD = SM_MISC + 96;
constexpr int SC_UNSC = SM_MISC + 112;
constexpr int SC_EPOCH = SM_MISC + 128;
constexpr int SC_EXPW = SM_MISC + 132;
constexpr int SC_ONES = SM_MISC + 144;
constexpr int SC_SS = SM_MISC + 160;
constexpr int SC_LAT = SM_MISC + 224;
constexpr int MB_T = SM_MISC + 232;
constexpr int T_SX = SM_X + XT;
constexpr int T_OB = SM_X + 2 * XT;
constexpr int T_WA = T_OB + 16384;
constexpr int T_OA = T_WA + 9216;
constexpr int T_G = T_OA + 4096;
constexpr int T_P = T_G + 512;
constexpr int T_UN = T_G + 256;
constexpr int T_RED = 131072;
constexpr int SC_XMAX = SM_MISC + 256;
constexpr int SC_PROF = 229376;

constexpr float SM_SCALE = 0.08838834764831845f;
constexpr float LOG2E = 1.4426950408889634f;
constexpr float E_LIM = 20.f;

template <bool B> struct BoolC { static constexpr bool value = B; };
struct RMaps { CUtensorMap x, wq, wk, wv, wo, woa, oa; unsigned char* red; bf16* out; uint32_t poll; };

DI uint32_t latest_hint(uint32_t h, uint32_t d, int s) {
  const uint32_t x = (((h | 0xc0c0c0c0u) - ((d >> 5) & 63) * 0x01010101u) & 0x3f3f3f3fu) | ((h ^ (((s >> 2) + 1) & 3) * 0x40404040u) & 0xc0c0c0c0u);
  const uint32_t y = __vmaxu2(x & 0x00ff00ffu, (x >> 8) & 0x00ff00ffu);
  return __reduce_max_sync(0xffffffffu, max(y & 0xffffu, y >> 16));
}
DI uint32_t near_half(uint32_t sb) {
  uint32_t a, b; lds64(sb + SC_LAT, a, b);
  return a > b;
}

template <int RT, int K0, int K1, bool D32 = false, int BAR = 0, int KB = 18>
DI void xproj(float* acc, const uint32_t (&wa)[2][18][4], uint64_t xd) {
  if (XP & 1) return;
  WG_FENCE();
#pragma unroll
  for (int k = K0; k < ((XP & 128) ? K0 + 1 : K1); k++)
  {
    uint64_t d = xd + (uint64_t)(((k >> 1) * 4096 + (k & 1) * 32) >> 4);
    if (D32) asm("mov.b64 %0, {%1, %2};" : "=l"(d) : "r"((uint32_t)xd + (((k >> 1) * 4096 + (k & 1) * 32) >> 4)), "r"((uint32_t)(xd >> 32)));
    wgmma_n32_rs(acc, wa[RT][k][0], wa[RT][k][1], wa[RT][k][2], wa[RT][k][3], d, k != 0);
    if (BAR && k == KB - 1 && KB < 18) bar_arrive(BAR, 256);
  }
  WG_COMMIT();
}

DI void seg_store(int seg, uint32_t sb, uint32_t off, uint32_t bytes) {
  asm volatile("cp.async.bulk.global.shared::cta.bulk_group [%0], [%1], %2;"
               :: "l"(g_seg + ((size_t)(seg % NRING) * 96 + blockIdx.x) * SEGB + off), "r"(sb + SM_BLK + (seg & 3) * SEGB + off), "r"(bytes) : "memory");
  asm volatile("cp.async.bulk.commit_group;" ::: "memory");
}
DI void seg_publish(int seg) {
  asm volatile("cp.async.bulk.wait_group 0;" ::: "memory");
  asm volatile("red.relaxed.gpu.global.add.u32 [%0], 1;" :: "l"(&g_scnt[(seg * 32 + blockIdx.x / 3) * 8]) : "memory");
  SSTAMP(10, seg);
}

#define NAP 64
DI uint32_t movm(uint32_t x) { uint32_t r; asm volatile("movmatrix.sync.aligned.m8n8.trans.b16 %0, %1;" : "=r"(r) : "r"(x)); return r; }
DI bool wait_count(const unsigned* p, unsigned target, bool nap = true) {
  int n = 0;
  unsigned v;
  while (true) {
    asm volatile("ld.acquire.gpu.global.b32 %0, [%1];" : "=r"(v) : "l"(p) : "memory");
    if ((int)(v - target) >= 0 || ++n > SPIN_LIMIT) break;
    if (nap) __nanosleep(NAP);
  }
  return n;
}
#define PACE 1200
#define PACE2 600
#define PACE3 (3 * PACE)
#define PORD 0
DI void load_weights(uint32_t sb, const RMaps& tm, uint32_t rank, int c) {
  const int h = blockIdx.x / 3;
  if (c < 3) {
    mbar_expect(sb + MB_W + 8 * c, 49152);
    tma_load(sb + SM_STAGE + c * 49152, rank < 2 ? &tm.wk : &tm.wv, h * DH + (rank == 1 ? 64 : 0), c * 192, sb + MB_W + 8 * c);
    tma_load(sb + SM_STAGE + c * 49152 + 24576, rank < 2 ? &tm.wq : &tm.wv, h * DH + (rank == 0 ? 0 : 64), c * 192, sb + MB_W + 8 * c);
  } else {
    tma_prefetch(&tm.wo, rank * 192, h * DH);
    mbar_expect(sb + MB_WO, 16384);
    mbar_expect(sb + MB_WO3, 32768);
    tma_load(sb + SM_WOST, &tm.wo, rank * 192 + 64, h * DH, sb + MB_WO3);
    tma_load(sb + SM_WO3, &tm.wo, rank * 192 + 128, h * DH, sb + MB_WO3);
  }
}

DI void tail_attention(const uint32_t sb, const uint32_t rank, const int w, const int lane, const int sg, const int bar) {
  const int m = lane >> 3, g = lane >> 2, t = lane & 3;
  const uint32_t l16 = sb + lane * 16, src = l16 + T_SX + sg * 10240 + w * 1280;
  if (rank < 2) {
    const uint32_t base = l16 + SM_BLK + (2 + sg) * SEGB, dst = src + rank * 5120;
    uint32_t qb[2][4];
    ldsm4t(qb[0], base + w * 1024); ldsm4t(qb[1], base + w * 1024 + 512);
#pragma unroll
    for (int j = 0; j < 3; j++) {
      uint32_t kb[4][4];
      float c[4][4];
      const uint32_t ka = base + 4096 + j * 2048 + (m & 1) * (j == 2 ? 128 : 896) - (m >> 1) * 128;
#pragma unroll
      for (int k = 0; k < 4; k += j == 2 ? 2 : 1) ldsm4t(kb[k], ka + k * 256);
      mma16816z(c[0], kb[0], qb[0][0], qb[0][1]); mma16816z(c[1], kb[j == 2 ? 0 : 1], qb[0][2], qb[0][3]);
      mma16816z(c[2], kb[2], qb[1][0], qb[1][1]); mma16816z(c[3], kb[j == 2 ? 2 : 3], qb[1][2], qb[1][3]);
      uint32_t r[4];
#pragma unroll
      for (int i = 0; i < (j == 2 ? 2 : 4); i++) r[i] = __float_as_uint((c[0][i] + c[1][j == 2 ? i + 2 : i]) + (c[2][i] + c[3][j == 2 ? i + 2 : i]));
#pragma unroll
      for (int d = 0; d < 2; d++) {
        const uint32_t to = d ? 2 : rank ^ 1, mb = mapa(sb + MB_T + 8 + 8 * sg, to);
        if (j < 2) st_async4(mapa(dst + j * 512, to), r[0], r[1], r[2], r[3], mb);
        else st_async2(mapa(dst + 1024 - lane * 8, to), r[0], r[1], mb);
      }
      if (j < 2) sts128(dst + j * 512, r[0], r[1], r[2], r[3]); else sts64(dst + 1024 - lane * 8, r[0], r[1]);
    }
  }
  TSTAMP(50 + 2 * sg);
  uint32_t vx[4][4], vm[4];
  const uint32_t va = l16 + (rank < 2 ? SM_VC + sg * 8192 : SM_BLK + (2 + sg) * SEGB) + w * 1024 + (m & 1) * 384 - (m >> 1) * 128;
#pragma unroll
  for (int i = 0; i < 4; i++) ldsm4(vx[i], va + (i & 1) * 4096 + (i >> 1) * 256);
  if (sg && rank < 2) mbar_wait(sb + MB_T, 0);
  lds128(l16 + (sg ? SM_FB : SM_VM) + w * 512, vm);
  float a[10], b[10];
  mbar_wait(sb + MB_T + 8 + 8 * sg, 0);
  TSTAMP(58 + 2 * sg);
  lds128f(src, a); lds128f(src + 512, a + 4); lds64f(src + 1024 - lane * 8, a + 8);
  lds128f(src + 5120, b); lds128f(src + 5632, b + 4); lds64f(src + 6144 - lane * 8, b + 8);
#pragma unroll
  for (int i = 0; i < 10; i++) {
    a[i] = (a[i] + b[i]) * (SM_SCALE * LOG2E);
    if (i < 8 && (i >> 1) * 8 + g > w * 8 + 2 * t + (i & 1)) a[i] = -1.0e9f * LOG2E;
  }
  float m0 = fmaxf(fmaxf(fmaxf(a[0], a[2]), fmaxf(a[4], a[6])), a[8]), m1 = fmaxf(fmaxf(fmaxf(a[1], a[3]), fmaxf(a[5], a[7])), a[9]);
#pragma unroll
  for (int o = 4; o < 32; o <<= 1) { m0 = fmaxf(m0, __shfl_xor_sync(0xffffffffu, m0, o)); m1 = fmaxf(m1, __shfl_xor_sync(0xffffffffu, m1, o)); }
#pragma unroll
  for (int i = 0; i < 10; i++) a[i] = ex2(a[i] - (i & 1 ? m1 : m0));
  float s0 = ((a[0] + a[2]) + (a[4] + a[6])) + a[8], s1 = ((a[1] + a[3]) + (a[5] + a[7])) + a[9];
#pragma unroll
  for (int o = 4; o < 32; o <<= 1) { s0 += __shfl_xor_sync(0xffffffffu, s0, o); s1 += __shfl_xor_sync(0xffffffffu, s1, o); }
  s0 = rcp(s0); s1 = rcp(s1);
#pragma unroll
  for (int i = 0; i < 5; i++) sts32(sb + T_P + sg * 2560 + w * 640 + i * 128 + lane * 4, pack_bf16(a[2 * i] * s0, a[2 * i + 1] * s1));
  mbar_wait(sb + MB_WO, 1);
  bar_sync(bar, 128);
  TSTAMP(59 + 2 * sg);
#pragma unroll
  for (int j = 0; j < 4; j++) {
    uint32_t p[5];
    float o0[4], o1[4], f[2];
    lds64f(sb + T_G + sg * 128 + j * 32 + t * 8, f);
    f[0] = 1.f - f[0]; f[1] = 1.f - f[1];
    ldsm4t(p, l16 + T_P + sg * 2560 + j * 640);
    asm volatile("ldmatrix.sync.aligned.m8n8.x1.trans.shared.b16 {%0}, [%1];" : "=r"(p[4]) : "r"(l16 + T_P + sg * 2560 + j * 640 + 512) : "memory");
    mma16816z(o0, vx[0], p[0], p[1]); mma16816z(o1, vx[1], p[0], p[1]);
    mma16816(o0, vx[2], p[2], p[3]); mma16816(o1, vx[3], p[2], p[3]);
    mma1688(o0, vm[0], vm[1], p[4]); mma1688(o1, vm[2], vm[3], p[4]);
    stsm4(l16 + T_OB + sg * 8192 + j * 2048 + w * 512, pack_bf16(o0[0] * f[0], o0[1] * f[1]), pack_bf16(o0[2] * f[0], o0[3] * f[1]),
          pack_bf16(o1[0] * f[0], o1[1] * f[1]), pack_bf16(o1[2] * f[0], o1[3] * f[1]));
  }
}

DI void proj_role(const uint32_t sb, const RMaps& tm, const uint32_t rank, const int wg, const int w, const int lane) {
  const bool qk = rank < 2;
  uint32_t wa[2][18][4];
  {
    const int rr = (lane & 7) + ((lane >> 4) << 3);
    const uint32_t col = ((2 * w + ((lane >> 3) & 1)) ^ (lane & 7)) << 4;
    float ss = 0.f;
#pragma unroll
    for (int c = 0; c < 3; c++) {
      mbar_wait(sb + MB_W + 8 * c, 0);
      if (threadIdx.x == 0) SSTAMP(11, c);
#pragma unroll
      for (int rt = 0; rt < 2; rt++)
#pragma unroll
        for (int k = 0; k < 6; k++)
          ldsm4t(wa[rt][c * 6 + k], sb + SM_STAGE + c * 49152 + (rt ^ wg) * 24576 + (64 * (k >> 1) + 32 * wg + 16 * (k & 1) + rr) * 128 + col);
      if (c < 2) {
        fence_async();
        bar_sync(3, 256);
        if (threadIdx.x == 0) {
          if (c == 0) tma_load3(sb + SM_X + XT, &tm.x, 32, sb + MB_X + 8);
          else { tma_load(sb + SM_X + 2 * XT, &tm.wo, rank * 192, (blockIdx.x / 3) * DH, sb + MB_WO); SSTAMP(11, 11); }
        }
        __syncwarp();
      }
      uint32_t q[4] = {0, 0, 0, 0};
#pragma unroll
      for (int rt = 0; rt < 2; rt++)
#pragma unroll
        for (int k = 0; k < 6; k++)
#pragma unroll
          for (int i = 0; i < 4; i++) sq_acc(q[i], wa[rt][c * 6 + k][i]);
#pragma unroll
      for (int i = 0; i < 4; i++) ss += bf_lo(q[i]) + bf_hi(q[i]);
    }
    ss = warp_sum(ss);
    fence_async();
    cluster_arrive();
    if (lane == 0) sts32(sb + SC_SS + 4 * (wg * 4 + w), qk ? 0 : __float_as_uint(ss));
    bar_arrive(11, 384);
  }
  STAMP(1);
  MSTAMP(0);
  mbar_wait(sb + MB_X, 0);
  STAMP(2);

  uint32_t t16 = sb + (w * 32 + lane) * 16;
  uint32_t mem_a = sb + SM_MEM + wg * 512 + lane * 16;
  uint32_t fin_a = sb + (lane & 7) * 16 + SM_BLK + (qk ? (wg ^ 1) * 4096 + w * 256 + (lane & 8) * 16 + (lane & 16) * 64
                                              : wg * 4096 + w * 1024 + (lane & 8) * 64 + (lane & 16) * 8);
  PIN(t16); PIN(mem_a); PIN(fin_a);
  const uint32_t fence_reg = mem_a;
  const uint32_t fin2 = qk ? 2048 : 256;
  float acc[16];
  const uint64_t xd0 = make_desc(sb + SM_X + wg * 64, 16, 1024, 1);
  auto do_export = [&]() {
    WG_WAIT(0);
    uint32_t q[8];
#pragma unroll
    for (int j = 0; j < 8; j++) q[j] = pack_bf16(acc[2 * j], acc[2 * j + 1]);
    sts128(t16 + SM_EXP + wg * 4096, q[0], q[1], q[2], q[3]);
    sts128(t16 + SM_EXP + wg * 4096 + 2048, q[4], q[5], q[6], q[7]);
    if (RET) asm volatile("{\n.reg .pred p;\nsetp.eq.u32 p, %2, 0;\n@p add.u32 %0, %0, 1;\n@p add.u32 %1, %1, 1;\nsetp.eq.and.u32 p, %0, %1, p;\n@p exit;\n}"
                          : "+r"(q[3]), "+r"(q[7]) : "r"(t16) : "memory");
  };
  uint32_t o[8];
  auto import = [&]() { lds128(t16 + SM_EXP + (wg ^ 1) * 4096, o); lds128(t16 + SM_EXP + (wg ^ 1) * 4096 + 2048, o + 4); };
  auto finish = [&](int seg) {
    const uint32_t a = fin_a + (seg & 3) * SEGB;
    WG_WAIT(0);
#pragma unroll
    for (int i = 0; i < 8; i++) o[i] = FIN16 ? add_bf16(pack_bf16(acc[2 * i], acc[2 * i + 1]), o[i]) : pack_bf16(acc[2 * i] + bf_lo(o[i]), acc[2 * i + 1] + bf_hi(o[i]));
    stsm4(a, o[0], o[1], o[2], o[3]);
    stsm4(a + fin2, o[4], o[5], o[6], o[7]);
  };
  auto send_v = [&](int seg, int dst) {
    fence_async();
    if (seg < NSEG && !(XP & 2) && elect_one())
      bulk_s2s(mapa(sb + SM_VC + (seg & 1) * 8192, dst), sb + SM_BLK + (seg & 3) * SEGB, 8192, mapa(sb + MB_VX + (seg & 1) * 8, dst));
    __syncwarp();
  };
  auto wait_v = [&](int seg) {
    if (seg < NSEG && !(XP & 2)) {
      mbar_wait(sb + MB_VX + (seg & 1) * 8, (seg >> 1) & 1);
      if (elect_one()) mbar_expect(sb + MB_VX + (seg & 1) * 8, 8192);
      __syncwarp();
    }
  };
  bar_sync(3, 256);
  xproj<1, 0, 18>(acc, wa, xd0);
  do_export();
  SCHED_FENCE(11);
  xproj<0, 0, 18>(acc, wa, xd0);
  bar_sync(3, 256);
  if (threadIdx.x == 0) SSTAMP(11, 12);
  MSTAMP(1);
  cluster_wait();
  if (threadIdx.x == 0) SSTAMP(11, 13);
  mbar_wait(sb + MB_X + 8, 0);
  import();
  finish(0);
  SCHED_FENCE(12);
  bar_sync(3, 256);
  uint64_t dA = xd0 + (XT >> 4);
  xproj<1, 0, 18>(acc, wa, dA);
  if (!qk && wg == 0 && w < 2) send_v(0, w);
  do_export();
  if (qk && wg == 0 && w == 0) wait_v(0);
  bar_arrive(13, 384);
  if (!qk) {
    SCHED_FENCE(15);
    xproj<0, 0, 18>(acc, wa, dA);
    if (threadIdx.x == 0 && !(XP & 8)) { mbar_expect(sb + MB_X, XT); tma_load3(sb + SM_X, &tm.x, 96, sb + MB_X); }
    bar_sync(3, 256);
    mbar_wait(sb + MB_X + 16, 0);
    import();
    finish(1);
    SCHED_FENCE(16);
    bar_sync(3, 256);
    dA += XT >> 4;
    xproj<1, 0, 18>(acc, wa, dA);
    if (wg == 0 && ((w == 0 && VS0) || (w == 1 && VS1))) send_v(1, w);
    do_export();
  }
  if (threadIdx.x == 0) SSTAMP(11, 14);
  MSTAMP(2);
  bar_sync(0, 384);
  const int ro = __shfl_sync(0xffffffffu, near_half(sb) ^ wg, 0);
  STAMP(5);
  const uint32_t always = __shfl_sync(0xffffffffu, lds32(sb + SC_DEAD + 12), 0);
  const int ah = qk ? 1 : 2;
  int b2 = qk ? 2 : 0;
  int s = 0;
  uint32_t hint_lo = (uint32_t)(uint64_t)tm.red + HINT_OFF + blockIdx.x + (lane & 1) * 4096 + (lane >> 1) * 16384;
  PIN(hint_lo);
  auto post_hint = [&]() {
    asm volatile("{\n.reg .pred p;\n.reg .b64 a;\n.reg .u32 t;\nsetp.lt.u32 p, %0, %1;\nmov.b64 a, {%2, %3};\nmov.u32 t, %%globaltimer_lo;\n"
                 "bfe.u32 t, t, 5, 6;\nor.b32 t, t, %4;\n@p st.relaxed.gpu.global.u8 [a], t;\n}"
                 :: "r"(t16), "r"(sb + 128), "r"(hint_lo + RED_SLOT(s)), "r"((uint32_t)((uint64_t)tm.red >> 32)), "r"(((s >> 2) + 1) << 6) : "memory");
  };
  auto memproj = [&](auto second, int id, float u0, float u1, float* r) {
    constexpr bool R1 = decltype(second)::value;
    uint32_t b[NUP][4], b0[4];
    SCHED_FENCE(id);
    bar_sync(R1 ? 2 : 1, 256);
    PROF(0);
    ldsm4t(b0, mem_a);
#pragma unroll
    for (int q = 0; q < NUP; q++) {
      if (R1 && q == 2) {
        bar_sync(11, 256);
        SCHED_FENCE(id + 1);
      }
      ldsm4t(b[q], mem_a + MEM_BLK(q + 1));
    }
    mma16816z(&acc[0], wa[0][0], b0[0], b0[1]);
    mma16816z(&acc[4], wa[1][0], b0[0], b0[1]);
    mma16816z(&acc[8], wa[0][1], b0[2], b0[3]);
    mma16816z(&acc[12], wa[1][1], b0[2], b0[3]);
#pragma unroll
    for (int q = 1; q < 9; q++) {
      uint32_t* const c = b[(q - 1) % NUP];
      mma16816(&acc[0], wa[0][2 * q], c[0], c[1]);
      mma16816(&acc[4], wa[1][2 * q], c[0], c[1]);
      mma16816(&acc[8], wa[0][2 * q + 1], c[2], c[3]);
      mma16816(&acc[12], wa[1][2 * q + 1], c[2], c[3]);
      if (R1 && q + NUP == B3Q) bar_sync(3, 256);
      if (q + NUP < 9) ldsm4t_in(c, mem_a + MEM_BLK(q + NUP), always);
      else if (R1 && q + NUP < 11) lds128_in(c, t16 + SM_PART + (10 - q - NUP) * 2048, always);
      else if (!R1 && GATE && q == GATE) { bar_arrive(11, 256); lds128_in(c, sb + SC_DEAD, always); u0 = u1 = __uint_as_float(c[3]); }
    }
#pragma unroll
    for (int i = 0; i < 8; i++) {
      const float u = i < 4 ? u0 : u1;
      r[i] = R1 ? fmaf(acc[8 + i], u, (acc[i] + __uint_as_float(b[(8 + i / 4) % NUP][i & 3])) * u) : (GATE ? fmaf(acc[i], u, acc[8 + i]) : acc[i] + acc[8 + i]);
    }
  };
  if (ro == 0) {
    auto set_scale = [&]() {
      uint32_t m[8];
      lds128(t16 + SM_MAX - 512, m); lds128(t16 + SM_MAX, m + 4);
      const int em = (wexp(amax4(amax4(*(const __half2*)&m[0], m), m + 4)) >> 3) + (int)(lds32(sb + SC_UNSC + (s & 1) * 8) >> 23) - 15;
      const int ex = max(s ? em : 0, (int)lds32(sb + SC_XMAX + 4 * s)) - 127 + (int)lds32(sb + SC_EXPW);
      sts32(sb + SC_UNSC + (~s & 1) * 8, (127 + min(max(ex, -120), 120)) << 23);
    };
#pragma unroll 1
    while (true) {
      if (s == 8) STAMP(6);
      float r[8];
      memproj(BoolC<false>(), 30, 0.f, 0.f, r);
      sts128(t16 + SM_PART, __float_as_uint(r[0]), __float_as_uint(r[1]), __float_as_uint(r[2]), __float_as_uint(r[3]));
      sts128(t16 + SM_PART + 2048, __float_as_uint(r[4]), __float_as_uint(r[5]), __float_as_uint(r[6]), __float_as_uint(r[7]));
      bar_arrive(3, 256);
      PROF(1);
      bar_sync(9, 256);
      if (s == NSEG - 1) break;
      post_hint();
      if (w == 1) {
        set_scale();
        __syncwarp();
        if (elect_one()) mbar_arrive(sb + MB_S);
      }
      SCHED_FENCE(9);
      bar_sync(5, qk ? N5 : 256);
      PROF(2);
      import();
      xproj<0, 0, NII, (DD & 1) != 0>(acc, wa, dA);
      if (NII < 18) {
        if (qk) bar_sync(7, 384);
        xproj<0, NII, 18>(acc, wa, dA);
        if (!qk) bar_sync(7, 384);
      } else {
        if (F10) WG_WAIT(0);
        bar_sync(10, 256);
        if (F10) SCHED_FENCE(17);
      }
      dA += (int64_t)(b2 ? XT >> 4 : -(XT >> 3));
      finish(s + ah);
      if (qk || !VLATE(w)) bar_arrive(13, 384);
      PROF(6);
      SCHED_FENCE(14);
      bar_sync(12, 256);
      PROF(7);
      xproj<1, 0, 18, (DD & 2) != 0, 14, N14>(acc, wa, dA);
      if (N14 == 18) bar_arrive(14, 256);
      b2 = b2 == 2 ? 0 : b2 + 1;
      s++;
      if (!qk && VLATE(w)) { bar_sync(13, 384); send_v(s + 1, w); }
      PROFP(8);
      do_export();
      s--; RSTAMP(6); s++;
      PROFP(3);
    }
    if (!qk) bar_arrive(5, 256);
    if (w == 0 && elect_one()) {
      const uint32_t h18 = blockIdx.x / 3 * 18;
      mbar_expect(sb + MB_WO, 9216 + 4096 + 256);
      asm volatile("cp.async.bulk.shared::cluster.global.mbarrier::complete_tx::bytes [%0], [%1], 256, [%2];"
                   :: "r"(sb + T_G), "l"(g_gate + NAUXSEG * 32), "r"(sb + MB_WO) : "memory");
      tma_load(sb + T_OA, &tm.oa, 4096 + (h18 & ~7), NAUXSEG * 32, sb + MB_WO);
#pragma unroll 1
      for (int j = 0; j < 3; j++) tma_load(sb + T_WA + j * 3072, &tm.woa, rank * 192 + j * 64, h18, sb + MB_WO);
    }
    if (w == 1) {
      set_scale();
      __syncwarp();
      const int ea = (int)ldg_relaxed32(&g_amax[0]) + (int)ldg_relaxed32(&g_amax[16]) - 254 + 2 + 10 - 15;
      sts32(sb + T_UN + (lane & 1) * 4, (128 + max(min(ea, 120), (int)(lds32(sb + SC_UNSC + 8 - (lane & 1) * 8) >> 23) - 127)) << 23);
    }
    bar_arrive(8, 256);
  } else {
    uint32_t r0;
    float un;
    auto prepare = [&]() {
      un = __uint_as_float(lds32(sb + SC_UNSC + (s & 1) * 8));
      r0 = qk ? (t16 & ~256u) - w * 256 + (((t16 >> 8) ^ wg) & 1 ? SM_QM : SM_BLK + 8192 + (s & 3) * SEGB) : mapa(t16 + (s < NSEG - 1 ? SM_VM : SM_FB), 0);
      PIN(r0); PIN(un);
    };
    auto mem_out = [&](int off, uint32_t lo, uint32_t hi) {
      unsigned char* const d = g_seg + ((size_t)(s % NRING) * 96 + blockIdx.x) * SEGB + 8192 + off + w * 256 + ((t16 >> 2) & 124);
      if (!(XP & 4)) { stg_relaxed32(d, lo); stg_relaxed32(d + 128, hi); }
    };
    prepare();
#pragma unroll 1
    while (true) {
      if (s == 8) STAMP(6);
      float r[8];
      if (qk) {
        const float u0 = wg ? un * (SM_SCALE * LOG2E) : un, u1 = wg ? un : un * (SM_SCALE * LOG2E);
        memproj(BoolC<true>(), 32, u0, u1, r);
        const uint32_t p0 = pack_bf16(r[0], r[1]), p1 = pack_bf16(r[2], r[3]), p2 = pack_bf16(r[4], r[5]), p3 = pack_bf16(r[6], r[7]);
        stsm4(r0, p0, p1, p2, p3);
        bar_arrive(4, 256);
        if (EXM) { SCHED_FENCE(18); mem_out(0, wg ? p2 : p0, wg ? p3 : p1); }
      } else {
        const uint32_t mb = sb + (s < NSEG - 1 ? MB_S : MB_T), r1 = r0 + (1 << 24);
        memproj(BoolC<true>(), 34, un, un, r);
        const uint32_t p0 = pack_bf16(r[0], r[1]), p1 = pack_bf16(r[2], r[3]), p2 = pack_bf16(r[4], r[5]), p3 = pack_bf16(r[6], r[7]);
        const uint32_t v0 = wg ? p2 : p0, v1 = wg ? p3 : p1, v2 = wg ? p0 : p2, v3 = wg ? p1 : p3;
        st_async4(r0, v0, v1, v2, v3, mapa(mb, 0));
        st_async4(r1, v0, v1, v2, v3, mapa(mb, 1));
        bar_arrive(5, 256);
        sts128(r0 + (2 << 24), v0, v1, v2, v3);
        stsm4((t16 & ~256u) - w * 256 + SM_BLK + 8192 + (s & 3) * SEGB + (((t16 >> 8) ^ wg) & 1) * 1024, p0, p1, p2, p3);
        __syncwarp();
        if (elect_one()) mbar_arrive(sb + MB_S);
        __syncwarp();
        if (EXM) { SCHED_FENCE(19); mem_out(0, v0, v1); mem_out(1024, v2, v3); }
      }
      if (s == NSEG - 1) break;
      if (!qk && !EXM) bar_arrive(15, 160);
      PROF(1);
      auto rearm = [&]() { mbar_wait(sb + MB_S, s & 1); if (elect_one()) mbar_expect(sb + MB_S, qk ? 640 + 2048 : 1280); __syncwarp(); };
      if (w == 1) {
        if ((t16 & 384) == 0) stg_relaxed(tm.red + (RED_SLOT(s + 2) + RED_LINE(blockIdx.x)) + (t16 & 112), 0, 0, 0, 0);
      } else if (w == 0) {
        const int tn = s + ah + 1;
        if (RFW) mbar_wait(sb + MB_S, s & 1);
        if (tn + 1 < NSEG && !(XP & 8) && elect_one()) {
          const int b0 = b2 == 2 ? 0 : b2 + 1;
          mbar_expect(sb + MB_X + 8 * b0, XT);
          tma_load3(sb + SM_X + b0 * XT, &tm.x, (tn + 1) * 32, sb + MB_X + 8 * b0);
        }
        if (tn < NSEG && (!(XP & 8) || tn < 3)) mbar_wait(sb + MB_X + 8 * b2, (tn / 3) & 1);
      } else if (w == 2) {
        if (!qk) { if (VS0 == 0) send_v(s + 1, 0); if (VS1 == 0) send_v(s + 1, 1); }
      } else if (qk || !NIC) {
        rearm();
      }
      __syncwarp();
      import();
      PROF(4);
      SCHED_FENCE(10);
      if (NIC) {
        if (qk) bar_sync(7, NII < 18 ? 384 : 256);
        xproj<0, 0, NIC>(acc, wa, dA);
        if (!qk) { if (w == 3) rearm(); bar_sync(7, NII < 18 ? 384 : 256); }
      } else {
        bar_sync(7, NII < 18 ? 384 : 256);
      }
      xproj<0, NIC, 18, (DD & 4) != 0, 12, N12>(acc, wa, dA);
      if (N12 == 18) bar_arrive(12, 256);
      dA += (int64_t)(b2 ? XT >> 4 : -(XT >> 3));
      finish(s + ah);
      if (qk && w == 0) wait_v(s + 1);
      bar_arrive(13, 384);
      PROF(6);
      SCHED_FENCE(13);
      bar_sync(14, 256);
      PROF(7);
      xproj<1, 0, 18, (DD & 8) != 0>(acc, wa, dA);
      b2 = b2 == 2 ? 0 : b2 + 1;
      s++;
      if (HOIST) prepare();
      PROFP(8);
      do_export();
      if (!HOIST) prepare();
      s--; RSTAMP(7); s++;
      PROFP(3);
    }
    TSTAMP(2);
    bar_sync(3, 128);
    tail_attention(sb, rank, w, lane, 1, 3);
    bar_arrive(0, 256);
  }
  STAMP(3);
  if (CSY) cluster_sync();
  STAMP(4);
}

DI void attn_role(const uint32_t sb, unsigned char* smem_raw, const RMaps& tm, const uint32_t RANK, const bf16* __restrict__ x, const bf16* __restrict__ mem0,
                  const int w, const int lane) {
  const int t2 = w * 32 + lane;
  uint32_t wo[8][4], w1[8][4];
  const uint32_t wo_lane = sb + ((lane & 7) + ((lane >> 4) << 3)) * 128 + (((w + 4 * ((lane >> 3) & 1)) ^ (lane & 7)) << 4);
  unsigned char* const g_red = tm.red;
  {
    const uint32_t t0 = gtime();
    const uint32_t tag = *(volatile unsigned*)&g_epoch + 1;
    if (w == 0) {
      stg_relaxed(g_red + RED_SLOT(t2 >> 3) + RED_LINE(blockIdx.x) + (t2 & 7) * 16, 0, 0, 0, 0);
      stg_relaxed(g_red + T_RED + blockIdx.x * 1024 + t2 * 16, 0, 0, 0, 0);
      stg_relaxed(g_red + T_RED + blockIdx.x * 1024 + 512 + t2 * 16, 0, 0, 0, 0);
      asm volatile("st.relaxed.gpu.global.u8 [%0], 0;" :: "l"(g_red + RED_SLOT(t2) + HINT_OFF + (t2 & 4) * 1024 + (t2 >> 3) * 16384 + blockIdx.x) : "memory");
    }
    bar_sync(0, 384);
    cluster_arrive();
    if (PACE && w == 3) {
#pragma unroll 1
      for (int c = 1; c < 4; c++) {
        wait_until(t0 + (c == 3 ? PACE3 : c * (RANK < 2 ? PACE : PACE2)));
        if (elect_one()) load_weights(sb, tm, RANK, PORD ? (c == 1 ? 3 : c - 1) : c);
        __syncwarp();
      }
    }
    uint4 xv[18];
    uint32_t mv[20];
#pragma unroll
    for (int i = 0; i < 20; i++) mv[i] = i < 18 ? ((const uint32_t*)mem0)[(lane >> 2) * (DM / 2) + (w * 18 + i) * 4 + (lane & 3)] : 0;
#pragma unroll
    for (int i = 0; i < 18; i++) xv[i] = blockIdx.x < NSEG ? ((const uint4*)(x + blockIdx.x * 32 * DM))[t2 + 128 * i] : make_uint4(0, 0, 0, 0);
    __half2 hx = __float2half2_rn(0.f);
#pragma unroll
    for (int i = 0; i < 18; i++) hx = amax4(hx, &xv[i].x);
    if (blockIdx.x == 0)
#pragma unroll
      for (int i = 0; i < 5; i++) hx = amax4(hx, &mv[4 * i]);
    sts32(sb + SC_SS + 4 * (12 + w), wexp(hx));
    if (t2 == 0) { sts32(sb + SC_EPOCH, (tag - 1) * NSEG + 2 - NRING); sts32(sb + SC_UNSC, __float_as_uint(1.f)); sts128(sb + SC_DEAD, 0, 0, 0, 0x3f800000u); sts64(sb + SC_FPAR, 0, 0); sts128(sb + SC_ONES, 0x3f803f80u, 0x3f803f80u, 0x3f803f80u, 0x3f803f80u); }
    WSTAMP(27);
    if (w == 0) __threadfence();
    uint32_t q[8] = {0, 0, 0, 0, 0, 0, 0, 0};
    mbar_wait(sb + MB_WO3, 0);
    if (t2 == 0) SSTAMP(11, 3);
    MSTAMP(3);
#pragma unroll
    for (int k = 0; k < 8; k++) {
      ldsm4t(wo[k], wo_lane + SM_WO3 + k * 2048); ldsm4t(w1[k], wo_lane + SM_WOST + k * 2048);
#pragma unroll
      for (int i = 0; i < 4; i++) { sq_acc(q[i], wo[k][i]); sq_acc(q[i], w1[k][i]); }
    }
    bar_sync(6, 128);
    if (t2 == 0) SSTAMP(11, 7);
#pragma unroll
    for (int k = 0; k < 8; k++) sts128(sb + SM_WO3 + t2 * 16 + k * 2048, wo[k][0], wo[k][1], wo[k][2], wo[k][3]);
#pragma unroll
    for (int i = 0; i < 5; i++) {
      const int j = w * 18 + 4 * i + (lane >> 3), c = i < 4 || lane < 16 ? j * 8 + j / 24 * 64 : 192;
      stsm4t(sb + SM_MEM + (c + (lane & 7)) * 16, mv[4 * i], mv[4 * i + 1], mv[4 * i + 2], mv[4 * i + 3]);
    }
    bar_arrive(1, 256); bar_arrive(2, 256); bar_arrive(9, 256);
    if (t2 == 0) SSTAMP(11, 8);
    mbar_wait(sb + MB_WO, 0);
    if (t2 == 0) SSTAMP(11, 4);
#pragma unroll
    for (int k = 0; k < 8; k++) ldsm4t(wo[k], wo_lane + SM_X + 2 * XT + k * 2048);
    fence_async();
    bar_sync(6, 128);
    if (t2 == 32) tma_load3(sb + SM_X + 2 * XT, &tm.x, 64, sb + MB_X + 16);
    __syncwarp();
#pragma unroll
    for (int k = 0; k < 8; k++)
#pragma unroll
      for (int i = 0; i < 4; i++) sq_acc(q[4 + i], wo[k][i]);
    float ss = 0.f;
#pragma unroll
    for (int i = 0; i < 8; i++) ss += bf_lo(q[i]) + bf_hi(q[i]);
    ss = warp_sum(ss);
    if (lane == 0) sts32(sb + SC_SS + 4 * (8 + w), __float_as_uint(ss));
    if (t2 == 0) SSTAMP(11, 9);
    bar_sync(11, 384);
    if (t2 == 0) SSTAMP(11, 10);
    if (t2 == 0) {
      float a[16];
#pragma unroll
      for (int i = 0; i < 4; i++) lds128f(sb + SC_SS + 16 * i, &a[4 * i]);
      stg_relaxed(&g_stats[blockIdx.x * 2], __float_as_uint(((a[0] + a[1]) + (a[2] + a[3])) + ((a[4] + a[5]) + (a[6] + a[7]))),
                  __float_as_uint((a[8] + a[9]) + (a[10] + a[11])),
                  max(max(__float_as_uint(a[12]), __float_as_uint(a[13])), max(__float_as_uint(a[14]), __float_as_uint(a[15]))), tag);
    }
    __syncwarp();
    WSTAMP(24);
    MSTAMP(4);
    cluster_wait();
    if (w == 0) {
      uint4 v[3];
      int n = 0;
      while (true) {
#pragma unroll
        for (int i = 0; i < 3; i++) v[i] = ldg_relaxed(&g_stats[(i * 32 + lane) * 2]);
        if (__all_sync(0xffffffffu, v[0].w == tag && v[1].w == tag && v[2].w == tag) || ++n > SPIN_LIMIT) break;
        __nanosleep(100);
      }
      WSTAMP(25);
      MSTAMP(5);
      const float sv = warp_sum(__uint_as_float(v[0].x) + __uint_as_float(v[1].x) + __uint_as_float(v[2].x));
      const float so = warp_sum(__uint_as_float(v[0].y) + __uint_as_float(v[1].y) + __uint_as_float(v[2].y));
      const int expW = ((int)(__float_as_uint(sv) >> 23) + (int)(__float_as_uint(so) >> 23) - 254 + 2 + 10 + 1) >> 1;
      sts32(sb + SC_XMAX + 4 * lane, v[0].z); sts32(sb + SC_XMAX + 128 + 4 * lane, v[1].z);
      sts32(sb + SC_EXPW, expW + 1 - 15);
      if (blockIdx.x == 0 && lane == 0) *(volatile unsigned*)&g_epoch = tag;
      sts32(sb + SC_FPAR + 4, 1);
    } else if (w < 3) {
      const uint32_t u = blockIdx.x >> 4;
      unsigned char* const z = g_red + 98304 + (blockIdx.x & 15) * 128 + (u & 1) * 2048 + (u & 6) * 4096 + (((u >> 1) ^ w) & 1) * 4096 + lane * 4;
      stg_relaxed32(z, 0);
      uint32_t best = 0xffffffffu;
#pragma unroll 1
      for (int i = 0; i < 64; i++) {
        uint32_t last, dt;
        asm volatile("{\n.reg .pred p;\n.reg .u32 c, v;\nld.volatile.shared.u32 %0, [%3];\nmov.u32 c, %%clock;\n"
                     "atom.relaxed.gpu.global.exch.b32 v, [%2], 0;\nsetp.eq.u32 p, v, 0;\nmov.u32 %1, 0;\n@p mov.u32 %1, %%clock;\nsub.u32 %1, %1, c;\n}"
                     : "=r"(last), "=r"(dt) : "l"(z), "r"(sb + SC_FPAR + 4) : "memory");
        best = min(best, dt);
        if ((last || PFIX) && i >= NPROBE - 1) break;
      }
      sts32(sb + SC_LAT + (w - 1) * 4, best);
    }
    bar_sync(13, 384);
    bar_arrive(0, 384);
    WSTAMP(26);
    TSTAMP(1);
    MSTAMP(6);
  }

  const uint32_t nh = __shfl_sync(0xffffffffu, near_half(sb), 0);
  uint32_t l16 = sb + lane * 16;
  PIN(l16);
#define LV ((l16 >> 4) & 31)
#define fence_reg l16
  const uint32_t red_lo = (uint32_t)(uint64_t)g_red, red_hi = (uint32_t)((uint64_t)g_red >> 32);
  uint32_t lp;
  auto slot = [&](int s, uint32_t c, uint32_t ofs) {
    const uint32_t lo = lp | (red_lo + ((w >> 1) * 4 + (w & 1) * 2 + ((w ^ c) & 1)) * 4096 + RED_SLOT(s) + ofs);
    uint64_t a; asm("mov.b64 %0, {%1, %2};" : "=l"(a) : "r"(lo), "r"(red_hi));
    return (unsigned char*)a;
  };
  const uint32_t always = __shfl_sync(0xffffffffu, lds32(sb + SC_DEAD + 12), 0);
  const int mode0 = RANK < 2 ? w : w | 4;
  auto hint_addr = [&](int s) { return min(LV, 23u) * 4 + (red_lo + HINT_OFF + nh * 4096 + w * 16384 + RED_SLOT(s)); };
  auto load_hints = [&](uint32_t lo) {
    uint64_t a; asm("mov.b64 %0, {%1, %2};" : "=l"(a) : "r"(lo), "r"(red_hi));
    return ldg_relaxed32((const void*)a);
  };
  const uint32_t blk = RANK < 2 ? 9216 : SEGB;
  auto send_v = [&](int seg, int pos) {
    if (RANK == 2 && ((w == 0 && VS0 == pos) || (w == 1 && VS1 == pos)) && seg > 1 && seg < NSEG && !(XP & 2)) {
      if (elect_one()) {
        fence_async();
        bulk_s2s(mapa(sb + SM_VC + (seg & 1) * 8192, w), sb + SM_BLK + (seg & 3) * SEGB, 8192, mapa(sb + MB_VX + (seg & 1) * 8, w));
      }
      __syncwarp();
    }
  };
  int s = 0;
  uint32_t dl = __shfl_sync(0xffffffffu, gtime() - 768, 0);
  bool bad = false;
#pragma unroll 1
  while (true) {
    const uint32_t par = s & 1;
    uint32_t vx[4][4], oc[4], hints;
    if (HP == 2) { hints = hint_addr(s); PIN(hints); }
    auto load_vx = [&]() {
      const uint32_t va = l16 + (RANK < 2 ? SM_VC + par * 8192 : SM_BLK + (s & 3) * SEGB) + w * 1024 + ((LV >> 3) & 1) * 384 - (LV >> 4) * 128;
      if (WL & 4) lds128(sb + SC_ONES, oc);
#pragma unroll
      for (int i = 0; i < 4; i++) ldsm4(vx[i], va + (i & 1) * 4096 + (i >> 1) * 256);
    };
    auto retire = [&](uint32_t x) {
      asm volatile("{\n.reg .pred p;\nsetp.eq.u32 p, %0, 0;\n@p exit;\n}" :: "r"(vx[0][0] | vx[1][0] | vx[2][0] | vx[3][0] | x | ((WL & 4) ? oc[0] : 0)) : "memory");
    };
    auto scores = [&](auto memkeys, auto first, float* sc) {
      constexpr bool MK = decltype(memkeys)::value, FIRST = decltype(first)::value;
      uint32_t kb[4][4], qb[2][4];
      const uint32_t m = LV >> 3;
      uint32_t kaddr = l16 + SM_BLK + 4096 + (s & 3) * SEGB + w * 2048 + (m & 1) * (MK ? 128 : 896) - (m >> 1) * 128;
      if (MK) { PIN(kaddr); }
      else {
#pragma unroll
        for (int k = 0; k < 4; k++) ldsm4t(kb[k], kaddr + k * 256);
      }
      if (FIRST) { load_vx(); retire(MK ? kaddr : kb[0][0] | kb[1][0] | kb[2][0] | kb[3][0] | l16); bar_sync(4, 256); RSTAMP(4); PROF(4); }
      ldsm4t(qb[0], l16 + SM_QM);
      if (MK) ldsm4t(kb[0], kaddr);
      ldsm4t(qb[1], l16 + SM_QM + 512);
      if (MK) ldsm4t(kb[2], kaddr + 512);
      float c[4][4];
      mma16816z(c[0], kb[0], qb[0][0], qb[0][1]); mma16816z(c[1], kb[MK ? 0 : 1], qb[0][2], qb[0][3]);
      mma16816z(c[2], kb[2], qb[1][0], qb[1][1]); mma16816z(c[3], kb[MK ? 2 : 3], qb[1][2], qb[1][3]);
      if (FIRST && B5POS == 0) bar_arrive(5, N5);
#pragma unroll
      for (int i = 0; i < (MK ? 2 : 4); i++) sc[i] = ((c[0][i] + c[1][MK ? i + 2 : i]) + c[2][i]) + c[3][MK ? i + 2 : i];
    };
    auto send = [&](auto memkeys) {
      constexpr bool MK = decltype(memkeys)::value;
      constexpr int N = MK ? 1 : 2;
      const uint32_t sa = sb + LV * 4 + SM_E + (MK ? 1024 + RANK * 128 : RANK * 512 + w * 256);
      uint32_t ra[N][2], mb[N][2];
#pragma unroll
      for (int i = 0; i < N; i++)
#pragma unroll
        for (int j = 0; j < 2; j++) {
          ra[i][j] = mapa(sa + i * 128, j ? 2 : RANK ^ 1); mb[i][j] = mapa(sb + MB_S, j ? 2 : RANK ^ 1);
          PIN(ra[i][j]);
        }
      float sc[4];
      scores(memkeys, BoolC<true>(), sc);
      uint32_t e[N];
#pragma unroll
      for (int i = 0; i < N; i++) {
        e[i] = pack_bf16(ex2(sc[2 * i]), ex2(sc[2 * i + 1]));
        if (!(fmaxf(fabsf(sc[2 * i]), fabsf(sc[2 * i + 1])) <= E_LIM)) e[i] = 0x7fff7fffu;
        st_async1(ra[i][0], e[i], mb[i][0]);
        st_async1(ra[i][1], e[i], mb[i][1]);
      }
#pragma unroll
      for (int i = 0; i < N; i++) sts32(sa + i * 128, e[i]);
      __syncwarp();
      if (l16 == sb) mbar_arrive(sb + MB_S);
      PROF(5);
    };
    const int mode = bad ? 8 : mode0;
    if (mode < 2) {
      send(BoolC<false>());
    } else if (mode == 2) {
      send(BoolC<true>());
    } else if (mode == 8) {
      load_vx();
      retire(l16);
      const uint32_t fp = lds32(sb + SC_FPAR);
      bar_sync(6, 128);
      if (w == 0 && l16 == sb) { sts32(sb + SC_FPAR, fp ^ 1); mbar_expect(sb + MB_F, 3072); }
      if (RANK < 2 && w < 3) {
        float sc[4] = {0.f, 0.f, 0.f, 0.f};
        if (w < 2) scores(BoolC<false>(), BoolC<false>(), sc); else scores(BoolC<true>(), BoolC<false>(), sc);
#pragma unroll 1
        for (int r = 0; r < 3; r++)
          st_async4(mapa(l16 + SM_FB + RANK * 1536 + w * 512, r), __float_as_uint(sc[0]), __float_as_uint(sc[1]), __float_as_uint(sc[2]), __float_as_uint(sc[3]), mapa(sb + MB_F, r));
      }
      mbar_wait(sb + MB_F, fp);
      float a[12];
#pragma unroll
      for (int j = 0; j < 3; j++) {
        float b[4];
        lds128f(l16 + SM_FB + j * 512, a + 4 * j); lds128f(l16 + SM_FB + 1536 + j * 512, b);
#pragma unroll
        for (int i = 0; i < 4; i++) a[4 * j + i] += b[i];
      }
      float m0 = fmaxf(fmaxf(fmaxf(a[0], a[2]), fmaxf(a[4], a[6])), a[8]), m1 = fmaxf(fmaxf(fmaxf(a[1], a[3]), fmaxf(a[5], a[7])), a[9]);
#pragma unroll
      for (int o = 4; o < 32; o <<= 1) { m0 = fmaxf(m0, __shfl_xor_sync(0xffffffffu, m0, o)); m1 = fmaxf(m1, __shfl_xor_sync(0xffffffffu, m1, o)); }
#pragma unroll
      for (int i = 0; i < 5; i++) {
        const uint32_t ea = sb + SM_E + LV * 4 + (i < 4 ? i * 128 : 1024);
        sts32(ea, pack_bf16(ex2(a[2 * i] - m0), ex2(a[2 * i + 1] - m1)));
        sts32(ea + (i < 4 ? 512 : 128), 0x3f803f80u);
      }
      __syncwarp();
    } else {
      load_vx();
      if (EXM && mode == 3) bar_arrive(4, 256);
      retire(l16 + 1);
      if (VS0 == 2 || VS1 == 2) send_v(s + 1, 2);
      if (w == 3) {
        uint32_t used = ldg_relaxed32(&g_used[blockIdx.x / 3 * 32]);
        if (!(XP & 4) && elect_one()) {
          if (s > 0) seg_publish(s - 1);
          fence_async();
          seg_store(s, sb, 0, 8192);
        }
        __syncwarp();
        if (!EXM) {
          bar_sync(RANK < 2 ? 4 : 15, RANK < 2 ? 256 : 160);
          if (!(XP & 4) && elect_one()) { fence_async(); seg_store(s, sb, 8192, blk - 8192); }
          __syncwarp();
        }
        const uint32_t need = lds32(sb + SC_EPOCH) + (s >= NRING - 1 ? s : -4 * NSEG);
#pragma unroll 1
        for (int n = 0; (int)(used - need) < 0 && n < ((XP & 64) ? 1 : SPIN_LIMIT); n++) used = ldg_relaxed32(&g_used[blockIdx.x / 3 * 32]);
      }
    }
    {
      uint32_t wa[4], wb[4];
      constexpr int WS = 2048;
      const uint32_t w3a = l16 + SM_WO3 + w * 512;
      if (HP == 1) { hints = hint_addr(s); PIN(hints); }
      if (!(WL & 1)) { lds128(w3a + KP(0) * WS, wa); lds128(w3a + KP(1) * WS, wb); }
      if (WL & 2) {
#pragma unroll
        for (int i = 0; i < 4; i++) oc[i] = always | (always >> 16) | (always & (i + 1));
      } else if (!(WL & 4)) lds128(sb + SC_ONES, oc);
      if (B5POS == 1 && mode < 3) bar_arrive(5, N5);
      uint32_t e[10], p[5], vm[4], ob[4];
      float o0[4], o1[4], f[3][2][4], rs[4];
      if (!(RV & 1)) { reserve2(vm); reserve2(vm + 2); }
      if (!(RV & 2)) reserve2(e + 8);
      if (!HP) { hints = hint_addr(s); PIN(hints); }
      if (CLR & 2) asm volatile("{\n.reg .pred p;\nsetp.eq.u32 p, %0, 0;\n@p exit;\n}" :: "r"(wa[0] | wb[0] | oc[0] | hints) : "memory");
      if (RV & 4) mbar_wait_fast(sb + MB_S, par); else mbar_wait(sb + MB_S, par);
      RSTAMP(5);
      PROF(6);
      if (RV & 2) { ldsm4t(e, l16 + SM_E); ldsm4t(e + 4, l16 + SM_E + 512); ldsm2t(e + 8, l16 + SM_E + 1024); }
      else { ldsm4t(e, l16 + SM_E); ldsm2t_in(e + 8, l16 + SM_E + 1024, always); ldsm4t(e + 4, l16 + SM_E + 512); }
      if (RV & 1) lds128(l16 + w * 512 + SM_VM, vm); else lds128_in(vm, l16 + w * 512 + SM_VM, always);
      const float scl = __uint_as_float(lds32(sb + SC_UNSC + 8 - par * 8));
      if (HL == 0) hints = load_hints(hints);
      if (GF & 1) SCHED_FENCE(4);
#pragma unroll
      for (int i = 0; i < 4; i++) p[i] = mul_bf16(e[i], e[4 + i]);
      p[4] = mul_bf16(e[8], e[9]);
      if (HL) hints = load_hints(hints | (p[HL - 1] & always & 1));
      mma16816z(o0, vx[0], p[0], p[1]);
      if (WL & 1) { lds128_in(vx[0], w3a + KP(0) * WS, always); }
      mma16816z(o1, vx[1], p[0], p[1]);
      if (WL & 1) { lds128_in(vx[1], w3a + KP(1) * WS, always); }
      mma16816z(rs, oc, p[0], p[1]);
      mma16816(o0, vx[2], p[2], p[3]); lds128_in(vx[2], w3a + KP(2) * WS, always);
      mma16816(o1, vx[3], p[2], p[3]); lds128_in(vx[3], w3a + KP(3) * WS, always);
      mma16816(rs, oc, p[2], p[3]);
      mma1688(o0, vm[0], vm[1], p[4]); mma1688(o1, vm[2], vm[3], p[4]); mma1688(rs, oc[0], oc[1], p[4]);
      stsm4(l16 + w * 512 + SM_OB, pack_bf16(o0[0], o0[1]), pack_bf16(o0[2], o0[3]), pack_bf16(o1[0], o1[1]), pack_bf16(o1[2], o1[3]));
      bar_sync(6, 128);
      RSTAMP(3);
      PROF(7);
      ldsm4t_in(oc, l16 + SM_OB, always);
      bad = __any_sync(0xffffffffu, !(rs[0] + rs[1] > 0.f) && !bad);
      rs[0] *= scl; rs[1] *= scl;
      asm volatile("{\n.reg .pred p;\nsetp.ne.u32 p, %1, 0;\n@p rcp.approx.ftz.f32 %0, %0;\n}" : "+f"(rs[0]) : "r"(always));
      asm volatile("{\n.reg .pred p;\nsetp.ne.u32 p, %1, 1;\n@p rcp.approx.ftz.f32 %0, %0;\n}" : "+f"(rs[1]) : "r"(always));
      asm volatile("lop3.b32 %0, %1, %2, %3, 0xfe;" : "=r"(lp) : "r"((l16 & 128) * 2), "r"((l16 & 256) * 4), "r"(l16 & 112));
      if (bad) continue;
      ldsm4t(ob, l16 + SM_OB + 512);
      mma16816z(f[2][0], WL & 1 ? vx[0] : wa, oc[0], oc[1]); mma16816z(f[2][1], WL & 1 ? vx[1] : wb, oc[2], oc[3]);
      mma16816z(f[0][0], wo[0], oc[0], oc[1]); mma16816z(f[0][1], wo[4], oc[2], oc[3]);
      mma16816z(f[1][0], w1[0], oc[0], oc[1]); mma16816z(f[1][1], w1[4], oc[2], oc[3]);
      ldsm4t_in(oc, l16 + SM_OB + 1024, always);
      mma16816(f[2][0], vx[2], ob[0], ob[1]); lds128_in(vx[2], w3a + KP(4) * WS, always);
      mma16816(f[2][1], vx[3], ob[2], ob[3]); lds128_in(vx[3], w3a + KP(5) * WS, always);
      mma16816(f[0][0], wo[1], ob[0], ob[1]); mma16816(f[0][1], wo[5], ob[2], ob[3]);
      mma16816(f[1][0], w1[1], ob[0], ob[1]); mma16816(f[1][1], w1[5], ob[2], ob[3]);
      ldsm4t_in(ob, l16 + SM_OB + 1536, always);
      mma16816(f[0][0], wo[2], oc[0], oc[1]); mma16816(f[0][1], wo[6], oc[2], oc[3]);
      mma16816(f[2][0], vx[2], oc[0], oc[1]); lds128_in(vx[2], w3a + KP(6) * WS, always);
      mma16816(f[2][1], vx[3], oc[2], oc[3]); lds128_in(vx[3], w3a + KP(7) * WS, always);
      mma16816(f[1][0], w1[2], oc[0], oc[1]); mma16816(f[1][1], w1[6], oc[2], oc[3]);
      mma16816(f[0][0], wo[3], ob[0], ob[1]); mma16816(f[0][1], wo[7], ob[2], ob[3]);
      mma16816(f[1][0], w1[3], ob[0], ob[1]); mma16816(f[1][1], w1[7], ob[2], ob[3]);
      mma16816(f[2][0], vx[2], ob[0], ob[1]); mma16816(f[2][1], vx[3], ob[2], ob[3]);
      bar_arrive(7, NII < 18 ? 384 : 256);
      lds128_in(ob, sb + SC_DEAD, always);
      uint32_t h[3][2];
#pragma unroll
      for (int j = 0; j < 3; j++)
#pragma unroll
        for (int i = 0; i < 2; i++)
        {
          scale_sum(f[j][1][2 * i], f[j][0][2 * i], rs[0], always); scale_sum(f[j][1][2 * i + 1], f[j][0][2 * i + 1], rs[1], always);
          h[j][i] = pack_f16(f[j][1][2 * i], f[j][1][2 * i + 1]);
        }
      const uint32_t rofs = RANK * 32768;
      red_f16x8(slot(s, RANK >> 1, rofs), h[0][0], h[1][0], h[2][0], 0x3c00u);
      red_f16x8(slot(s, (RANK >> 1) ^ 1, rofs), h[0][1], h[1][1], h[2][1], 0x3c00u);
      if (NII == 18) bar_arrive(10, 256);
      SCHED_FENCE(5);
      RSTAMP(0);
      l16 += ob[B7R];
    }
    {
    PROF(8);
    if (VS0 == 3 || VS1 == 3) send_v(s + 1, 3);
    const uint32_t ma0 = l16 + SM_MEM + w * 128 + (LV >> 3) * 896 + nh * 512;
    const unsigned char* const sl[2] = {slot(s, nh, 0), slot(s, nh ^ 1, 0)};
    uint32_t late = latest_hint(hints, dl, s);
    if (late >= 64) {
      int n = 0;
#pragma unroll 1
      do {
        late = latest_hint(load_hints(hint_addr(s)), dl, s);
      } while (late >= 64 && ++n < SPIN_LIMIT);
    }
    dl += late * 32 + tm.poll;
    if (s == 0 && PSTAMP) MSTAMP(7);
    PROF(9);
    {
      auto wait_until = [&](uint32_t t) {
        asm volatile("{\n.reg .pred p;\n.reg .s32 c;\n.reg .u64 t;\nTL: mov.u64 t, %%globaltimer;\ncvt.u32.u64 c, t;\nsub.s32 c, c, %0;\nsetp.lt.s32 p, c, 0;\n@p bra.uni TL;\n}" :: "r"(t + (l16 & 15)) : "memory");
      };
      uint4 v[2][3];
      auto load = [&](int c) {
#pragma unroll
        for (int r = 0; r < 3; r++) v[c][r] = ldg_relaxed(sl[c ^ (r >> 1)] + r * 32768);
      };
      auto decode = [&](int c, int n) {
        uint32_t q[9];
        __half2 hm;
        const uint32_t ma = ma0 ^ (c * 512);
#pragma unroll
        for (int i = 0; i < 9; i++) {
          const uint32_t h = i % 3 == 0 ? v[c][i / 3].x : (i % 3 == 1 ? v[c][i / 3].y : v[c][i / 3].z);
          const float2 f = __half22float2(*(const __half2*)&h);
          q[i] = pack_bf16(f.x, f.y);
          hm = i ? __hmax2(hm, __habs2(*(const __half2*)&h)) : __habs2(*(const __half2*)&h);
        }
#pragma unroll
        for (int r = 0; r < 3; r++) stsm4(ma + r * 4096, q[3 * r], q[3 * r + 1], q[3 * r + 2], r < 2 ? v[c][r].w : *(const uint32_t*)&hm);
        const bool done = __all_sync(0xffffffffu, v[c][0].w == 0x5000u && v[c][1].w == 0x5000u && v[c][2].w == 0x5000u) || n > SPIN_LIMIT;
        asm volatile("{\n.reg .pred p;\nsetp.ne.u32 p, %0, 0;\n@p bar.arrive %1, 256;\n}" :: "r"((int)done), "r"(1 + c) : "memory");
        return done;
      };
      if (LEAD) { wait_until(dl - LEAD); load(1); }
      wait_until(dl);
      PROF(10);
      int n = 0;
#pragma unroll 1
      do {
        load(0);
        if (!LEAD) load(1);
        asm volatile("{\n.reg .pred p;\nsetp.eq.u32 p, %0, 0;\n@p bar.sync 13, 384;\n}" :: "r"(n) : "memory");
      } while (!decode(0, n++));
      PROF(11);
      RSTAMP(1);
#pragma unroll 1
      while (!decode(1, n++)) load(1);
      bar_arrive(9, 256);
      RSTAMP(2);
      PROF(12);
    }
    PROF(13);
    if (++s == NSEG - 1) break;
    }
  }
#undef fence_reg
  if (RANK < 2) bar_arrive(4, 256);
  TSTAMP(49);
  {
    PIN(l16);
    tail_attention(sb, RANK, w, LV, 0, 6);
#pragma unroll 1
    for (int sg = 0; sg < 2; sg++) {
      PIN(l16);
      const int lane = LV, m = lane >> 3, g = lane >> 2, t = lane & 3;
      const uint32_t ob = l16 + T_OB + sg * 8192;
      bar_sync(sg ? 0 : 8, 256);
      TSTAMP(54 + 2 * sg);
      const float inv = __uint_as_float(0x7f000000u - lds32(sb + T_UN + sg * 4));
#pragma unroll 1
      for (int j = 0; j < 4; j += 2) {
        float c[2][3][4];
        uint32_t x[4], y[4], z[2][4];
#pragma unroll
        for (int e = 0; e < 2; e++) {
          const uint32_t oa = sb + T_OA + ((sg * 4 + j + e) * 8 + g) * 64 + (blockIdx.x / 3 * 36 & 15) + t * 4;
          z[e][0] = lds32(oa); z[e][1] = lds32(oa + 16); z[e][2] = t ? 0u : lds32(oa + 32);
        }
#pragma unroll
        for (int i = 0; i < 3; i++) {
          const uint32_t wa = sb + T_WA + ((lane & 7) + ((lane >> 4) << 3)) * 128 + (((w + 4 * (m & 1)) ^ (lane & 7)) << 4);
          ldsm4t(x, wa + i * 3072); ldsm2t(y, wa + i * 3072 + 2048);
#pragma unroll
          for (int e = 0; e < 2; e++) { mma1688z(c[e][i], y[0], y[1], z[e][2]); mma16816(c[e][i], x, z[e][0], z[e][1]); }
        }
#pragma unroll
        for (int r = 0; r < 4; r++) {
          ldsm4t(z[0], ob + j * 2048 + r * 512); ldsm4t(z[1], ob + j * 2048 + 2048 + r * 512);
          lds128(l16 + SM_WO3 + w * 512 + r * 2048, x); lds128(l16 + SM_WO3 + w * 512 + (r + 4) * 2048, y);
#pragma unroll
          for (int e = 0; e < 2; e++) { mma16816(c[e][0], wo[r], z[e][0], z[e][1]); mma16816(c[e][1], w1[r], z[e][0], z[e][1]); mma16816(c[e][2], x, z[e][0], z[e][1]); }
#pragma unroll
          for (int e = 0; e < 2; e++) { mma16816(c[e][0], wo[r + 4], z[e][2], z[e][3]); mma16816(c[e][1], w1[r + 4], z[e][2], z[e][3]); mma16816(c[e][2], y, z[e][2], z[e][3]); }
        }
#pragma unroll
        for (int i = 0; i < 4; i++) {
          const float (&d)[3][4] = c[i >> 1];
          const int q = (i & 1) * 2;
          red_f16x8(g_red + T_RED + ((((sg * 4 + j + (i >> 1)) * 3 + RANK) * 4 + w) * 2 + (i & 1)) * 512 + lane * 16, pack_f16(d[0][q] * inv, d[0][q + 1] * inv),
                    pack_f16(d[1][q] * inv, d[1][q + 1] * inv), pack_f16(d[2][q] * inv, d[2][q + 1] * inv), 0x3c00u);
        }
      }
      TSTAMP(55 + 2 * sg);
    }
    if (RSLOW) { wait_until(gtime() + 8000); wait_until(gtime() + 8000); wait_until(gtime() + 4000); }
    if (w < 2) {
      const int b = blockIdx.x, lane = LV, g = lane >> 2, t = lane & 3;
      uint4 v;
#pragma unroll 1
      for (int n = 0; n < SPIN_LIMIT; n++) {
        v = ldg_relaxed(g_red + T_RED + (w * 96 + b) * 512 + lane * 16);
        if (__all_sync(0xffffffffu, v.w == 0x5000u)) break;
        __nanosleep(40);
      }
      const float un = __uint_as_float(lds32(sb + T_UN + w * 4));
      uint32_t* const o = (uint32_t*)(tm.out + (size_t)((NAUXSEG + w) * 32 + b / 24 * 8 + g) * DM + (b >> 3) % 3 * 192 + (b & 1) * 32 + (b & 6) * 4) + t;
#pragma unroll
      for (int j = 0; j < 3; j++) {
        const float2 f = __half22float2(*(const __half2*)(&v.x + j));
        o[j * 32] = movm(pack_bf16(f.x * un, f.y * un));
      }
    }
  }
  TSTAMP(3);
  MSTAMP(8);
  if (CSY) cluster_sync();
}

__global__ void __cluster_dims__(3, 1, 1) __launch_bounds__(384, 1)
rec_kernel(const __grid_constant__ RMaps tm, const bf16* __restrict__ x, const bf16* __restrict__ mem0) {
  extern __shared__ __align__(1024) unsigned char smem_raw[];
  const uint32_t sb = smem_u32(smem_raw);
  const int tid = threadIdx.x, lane = tid & 31;
  const int wg = __shfl_sync(0xffffffffu, tid >> 7, 0);
  const int w = __shfl_sync(0xffffffffu, (tid >> 5) & 3, 0);
  uint32_t rank; asm("mov.u32 %0, %%cluster_ctarank;" : "=r"(rank));
  STAMP(0);
  TSTAMP(0);
  asm volatile("griddepcontrol.launch_dependents;" ::: "memory");

#define PFT 1
  if (PFT && wg == 1 && lane == 0) asm volatile("prefetch.tensormap [%0];\nprefetch.tensormap [%1];" :: "l"(w & 1 ? &tm.woa : &tm.oa), "l"(w == 0 ? (rank < 2 ? &tm.wk : &tm.wv) : w == 1 ? &tm.wq : w == 2 ? &tm.x : &tm.wo) : "memory");
  if (wg < 2) {
    asm volatile("setmaxnreg.inc.sync.aligned.u32 192;");
    if (tid == 0) {
      for (int i = 0; i < 3; i++) { mbar_init(sb + MB_W + 8 * i, 1); mbar_init(sb + MB_X + 8 * i, 1); }
      mbar_init(sb + MB_WO, 1); mbar_init(sb + MB_WO3, 1);
      mbar_init(sb + MB_S, rank < 2 ? 5 : 6);
      mbar_init(sb + MB_F, 1);
      for (int i = 0; i < 3; i++) mbar_init(sb + MB_T + 8 * i, 1);
      mbar_init(sb + MB_VX, 1); mbar_init(sb + MB_VX + 8, 1);
      asm volatile("fence.mbarrier_init.release.cluster;" ::: "memory");
      fence_async();
      SSTAMP(11, 6);
      load_weights(sb, tm, rank, 0);
      for (int i = 0; i < 3; i++) mbar_expect(sb + MB_X + 8 * i, XT);
      tma_load3(sb + SM_X, &tm.x, 0, sb + MB_X);
      if (!PACE) for (int c = 1; c < 4; c++) load_weights(sb, tm, rank, c);
      mbar_expect(sb + MB_S, rank < 2 ? 640 + 2048 : 1280);
      mbar_expect(sb + MB_VX, 8192); mbar_expect(sb + MB_VX + 8, 8192);
      mbar_expect(sb + MB_T, 2048);
      for (int i = 1; i < 3; i++) mbar_expect(sb + MB_T + 8 * i, rank < 2 ? 5120 : 10240);
      SSTAMP(11, 5);
    }
    __syncwarp();
    bar_sync(0, 384);
    proj_role(sb, tm, rank, wg, w, lane);
  } else {
    asm volatile("setmaxnreg.dec.sync.aligned.u32 120;");
    attn_role(sb, smem_raw, tm, rank, x, mem0, w, lane);
  }
}

constexpr int A_XH = 73728;
constexpr int A_NS = 9, A_WM = 6144, A_WT = 768;
constexpr int A_RING = 2 * A_XH, A_TAIL = A_RING + A_NS * A_WM, A_GW = A_TAIL + A_NS * A_WT;
constexpr int A_EPI = 212864, A_EPW = 9344;
constexpr int A_XW = 4 * XT, A_XT = A_XW + 4096, A_NR = 4;
constexpr int A_IN = A_XT + 2048, A_INS = 2 * 9216 + SEGB;
constexpr int A_GATE = A_EPI + 2 * A_EPW, A_BAR = A_GATE + 512;
constexpr int A_TOTAL = A_BAR + 384;
struct AMaps { CUtensorMap x, wa, wt, oa, o, o3, o8, wob, woa, wo8; };

DI void wgmma_n192_ss_nt(float* d, uint64_t da, uint64_t db, int acc) {
  asm volatile("{\n.reg .pred p;\nsetp.ne.b32 p, %98, 0;\n"
               "wgmma.mma_async.sync.aligned.m64n192k16.f32.bf16.bf16 {"
               "%0,%1,%2,%3,%4,%5,%6,%7,%8,%9,%10,%11,%12,%13,%14,%15,%16,%17,%18,%19,%20,%21,%22,%23,%24,%25,%26,%27,%28,%29,%30,%31,"
               "%32,%33,%34,%35,%36,%37,%38,%39,%40,%41,%42,%43,%44,%45,%46,%47,%48,%49,%50,%51,%52,%53,%54,%55,%56,%57,%58,%59,%60,%61,%62,%63,"
               "%64,%65,%66,%67,%68,%69,%70,%71,%72,%73,%74,%75,%76,%77,%78,%79,%80,%81,%82,%83,%84,%85,%86,%87,%88,%89,%90,%91,%92,%93,%94,%95"
               "}, %96, %97, p, 1, 1, 0, 1;\n}\n"
               : ACC8(d, 0), ACC8(d, 8), ACC8(d, 16), ACC8(d, 24), ACC8(d, 32), ACC8(d, 40), ACC8(d, 48), ACC8(d, 56),
                 ACC8(d, 64), ACC8(d, 72), ACC8(d, 80), ACC8(d, 88) : "l"(da), "l"(db), "r"(acc));
}
#define ACC4(d, o) "+f"(d[o]), "+f"(d[o + 1]), "+f"(d[o + 2]), "+f"(d[o + 3])
DI void wgmma_n24_ss_nt(float* d, uint64_t da, uint64_t db, int acc) {
  asm volatile("{\n.reg .pred p;\nsetp.ne.b32 p, %14, 0;\n"
               "wgmma.mma_async.sync.aligned.m64n24k16.f32.bf16.bf16 {%0,%1,%2,%3,%4,%5,%6,%7,%8,%9,%10,%11}, %12, %13, p, 1, 1, 0, 1;\n}\n"
               : ACC8(d, 0), ACC4(d, 8) : "l"(da), "l"(db), "r"(acc));
}
DI void wgmma_n8_ss(float* d, uint64_t da, uint64_t db, int acc) {
  asm volatile("{\n.reg .pred p;\nsetp.ne.b32 p, %6, 0;\n"
               "wgmma.mma_async.sync.aligned.m64n8k16.f32.bf16.bf16 {%0,%1,%2,%3}, %4, %5, p, 1, 1, 0, 0;\n}\n"
               : ACC4(d, 0) : "l"(da), "l"(db), "r"(acc));
}
DI void wgmma_n40_ss_tt(float* d, uint64_t da, uint64_t db, int acc) {
  asm volatile("{\n.reg .pred p;\nsetp.ne.b32 p, %22, 0;\n"
               "wgmma.mma_async.sync.aligned.m64n40k16.f32.bf16.bf16 {%0,%1,%2,%3,%4,%5,%6,%7,%8,%9,%10,%11,%12,%13,%14,%15,%16,%17,%18,%19}, "
               "%20, %21, p, 1, 1, 1, 1;\n}\n"
               : ACC8(d, 0), ACC8(d, 8), ACC4(d, 16) : "l"(da), "l"(db), "r"(acc));
}
DI void wgmma_n64_rs(float* d, const uint32_t* a, uint64_t db, int acc) {
  asm volatile("{\n.reg .pred p;\nsetp.ne.b32 p, %37, 0;\n"
               "wgmma.mma_async.sync.aligned.m64n64k16.f32.bf16.bf16 {"
               "%0,%1,%2,%3,%4,%5,%6,%7,%8,%9,%10,%11,%12,%13,%14,%15,%16,%17,%18,%19,%20,%21,%22,%23,%24,%25,%26,%27,%28,%29,%30,%31"
               "}, {%32,%33,%34,%35}, %36, p, 1, 1, 0;\n}\n"
               : ACC8(d, 0), ACC8(d, 8), ACC8(d, 16), ACC8(d, 24) : "r"(a[0]), "r"(a[1]), "r"(a[2]), "r"(a[3]), "l"(db), "r"(acc));
}
DI void wgmma_n32_ss_tn(float* d, uint64_t da, uint64_t db, int acc) {
  asm volatile("{\n.reg .pred p;\nsetp.ne.b32 p, %18, 0;\n"
               "wgmma.mma_async.sync.aligned.m64n32k16.f32.bf16.bf16 {%0,%1,%2,%3,%4,%5,%6,%7,%8,%9,%10,%11,%12,%13,%14,%15}, "
               "%16, %17, p, 1, 1, 1, 0;\n}\n"
               : ACC8(d, 0), ACC8(d, 8) : "l"(da), "l"(db), "r"(acc));
}
DI void tma_load3c(uint32_t dst, const CUtensorMap* m, int c0, int c1, int c2, uint32_t mb) {
  asm volatile("cp.async.bulk.tensor.3d.shared::cluster.global.mbarrier::complete_tx::bytes [%0], [%1, {%3, %4, %5}], [%2];"
               :: "r"(dst), "l"(m), "r"(mb), "r"(c0), "r"(c1), "r"(c2) : "memory");
}
DI void count_up(unsigned* p) {
  asm volatile("fence.proxy.async;" ::: "memory");
  asm volatile("red.release.gpu.global.add.u32 [%0], 1;" :: "l"(p) : "memory");
}
#define AX 0
#define FDLY 400
#define FEND 59
DI void publish(unsigned* p) {
  asm volatile("cp.async.bulk.wait_group 0;\nfence.proxy.async;" ::: "memory");
  asm volatile("red.relaxed.gpu.global.add.u32 [%0], 1;" :: "l"(p) : "memory");
}
#define PL 2
#define SER 35
#define DRAIN 0
#define PR 4
#define NQ 3
#define PUB 0
#define LA 1
#define LAG0 10
#define LEND 56
#define PDLY 0
#define PIPE 1
#define ADLY 0

__global__ void __launch_bounds__(512, 1)
aux_kernel(const __grid_constant__ AMaps tm, const bf16* __restrict__ wqkv, const bf16* __restrict__ woa, const bf16* __restrict__ gate_w, bf16* __restrict__ out) {
  extern __shared__ __align__(1024) unsigned char smem_raw[];
  const uint32_t sb = smem_u32(smem_raw);
  const uint32_t fullx = sb + A_BAR, full1 = fullx + 24, empty1 = full1 + 8 * A_NS, fullw = empty1 + 8 * A_NS, full3 = fullw + 8, empty3 = full3 + 8 * A_NR,
                 fullq = empty3 + 8 * A_NR, emptyq = fullq + 24, fullo = emptyq + 24, emptyo = fullo + 16;
  const int tid = threadIdx.x, lane = tid & 31, cta = blockIdx.x;
  const int wg = __shfl_sync(0xffffffffu, tid >> 7, 0), w = __shfl_sync(0xffffffffu, (tid >> 5) & 3, 0);
  ASTAMP(14);
  if (tid == 384) {
    for (int i = 0; i < 3; i++) mbar_init(fullx + 8 * i, 1);
    for (int i = 0; i < A_NS; i++) { mbar_init(full1 + 8 * i, 1); mbar_init(empty1 + 8 * i, 8); }
    mbar_init(fullw, 1);
    for (int i = 0; i < 3; i++) { mbar_init(fullq + 8 * i, 1); mbar_init(emptyq + 8 * i, 4); }
    for (int i = 0; i < 2; i++) { mbar_init(fullo + 8 * i, 4); mbar_init(emptyo + 8 * i, 1); }
    for (int i = 0; i < A_NR; i++) { mbar_init(full3 + 8 * i, 1); mbar_init(empty3 + 8 * i, cta < NH ? 8 : 4); }
    fence_async();
  }
  __syncthreads();
  ASTAMP(0);
  const int tile = cta >> 1, hh = cta & 1;
  auto p3_n = [&](int g) { return cta < NH ? (cta & 3) * 2 + g : 8; };
  auto p3_next = [&](int& sl, int& ph) {
    sl += cta < NH ? 1 : 2;
    if (sl >= (cta < NH ? 6 - NQ : 4)) { sl -= cta < NH ? 6 - NQ : 4; ph ^= 1; }
  };
  auto p3_k = [&](int g) { return cta < NH ? cta >> 2 : (cta & 3) * 2 + g; };
  if (wg == 3) {
    asm volatile("setmaxnreg.dec.sync.aligned.u32 24;");
    const bool lead = lane == 0;
    if (w < 3) {
      if (ADLY) wait_until(gtime() + ADLY);
      if (elect_one()) {
        mbar_expect(fullx + 8 * w, 49152);
        for (int p = 0; p < 2; p++)
          asm volatile("cp.async.bulk.tensor.4d.shared::cluster.global.mbarrier::complete_tx::bytes [%0], [%1, {%3, %4, %5, %6}], [%2];"
                       :: "r"(sb + p * A_XH + w * 24576), "l"(&tm.x), "r"(fullx + 8 * w), "r"(0), "r"(p), "r"(57 * tile - 7), "r"(3 * w) : "memory");
      }
#pragma unroll 1
      for (int r = 0; r < 17; r++) {
#pragma unroll 1
        for (int st = w; st < A_NS; st += 3) {
          if (r > 0) mbar_wait(empty1 + 8 * st, ~r & 1);
          if (r < 16 && elect_one()) {
            const int col = hh * 288 + (r >> 2) * 72, row = (r & 3) * 144 + st * 16;
            mbar_expect(full1 + 8 * st, A_WM + (AX & 1 ? 0 : A_WT));
            tma_load3c(sb + A_RING + st * A_WM, &tm.wa, col, row, 0, full1 + 8 * st);
            if (!(AX & 1)) tma_load3c(sb + A_TAIL + st * A_WT, &tm.wt, col + 64, row, 0, full1 + 8 * st);
          }
          __syncwarp();
        }
        if (r == 0 && elect_one())
          for (int j = 0; j < 3; j++)
            asm volatile("cp.async.bulk.prefetch.L2.global [%0], %1;" :: "l"((const char*)wqkv + cta * 55296 + (w * 3 + j) * 6144), "r"(6144) : "memory");
        __syncwarp();
      }
      bar_sync(8, 96);
    }
    const unsigned epoch = lds32(sb + A_BAR + 376);
    if (w == 2 && cta < NH) {
      if (lead) {
        int avail = 0, q = 0, ph = 1;
#pragma unroll 1
        for (int seg = 0; seg < NAUXSEG; seg++) {
          const unsigned char* const src = g_seg + ((size_t)(AX & 128 ? 0 : seg % NRING) * 96 + cta * 3) * SEGB;
          SSTAMP(0, seg);
          const int ref = seg + max(LAG0 * (LEND - seg) / LEND, 0);
          if (ref >= avail) {
            const unsigned* const c = &g_scnt[(ref * 32 + cta) * 8];
            const int c2 = ldg_relaxed32(c + 512) - 3 * (epoch + 1), c0 = ldg_acquire32(c) - 3 * (epoch + 1);
            avail = ref + (c2 >= 0 && LA ? 3 : 1);
            if (c0 < 0) {
              wait_count(c, 3 * (epoch + 1), !(TL & 2) || seg < NAUXSEG - 2);
              if (FDLY && seg < FEND) wait_until(gtime() + FDLY);
            }
          }
          SSTAMP(1, seg);
          const uint32_t mb = fullq + q * 8;
          mbar_wait(emptyq + q * 8, q == 2 ? ph ^ 1 : ph);
          if (AX & 8) mbar_arrive(mb); else mbar_expect(mb, A_INS);
#pragma unroll 1
          for (int r = 0; r < ((AX & 8) ? 0 : 3); r++)
            asm volatile("cp.async.bulk.shared::cluster.global.mbarrier::complete_tx::bytes [%0], [%1], %2, [%3];"
                         :: "r"(sb + (q < 2 ? A_IN + q * A_INS : 3 * XT) + r * 9216), "l"(src + r * SEGB), "r"(r < 2 ? 9216 : SEGB), "r"(mb) : "memory");
          if (seg == 1) wait_count(&g_abar[32], NAUX * (epoch + 1));
          if (seg > 1) stg_relaxed32(&g_used[cta * 32], epoch * NSEG + seg + 1 - NQ);
          if (++q == NQ) { q = 0; ph ^= 1; }
        }
      }
      return;
    }
    if (w == 3) {
#pragma unroll 1
      for (int c = 0; c < 4; c++) {
        if (lead) asm volatile("cp.async.bulk.wait_group.read 0;" ::: "memory");
        __syncwarp();
        bar_arrive(11, 160); bar_arrive(12, 160);
#pragma unroll 1
        for (int g = 0; g < 2; g++) {
          bar_sync(13 + g, 160);
          if (lead) {
            asm volatile("cp.async.bulk.tensor.3d.global.shared::cta.bulk_group [%0, {%2, %3, %4}], [%1];"
                         :: "l"(&tm.oa), "r"(sb + A_EPI + g * A_EPW + 1024), "r"(4096 + hh * 288 + c * 72), "r"(g), "r"(57 * tile) : "memory");
            asm volatile("cp.async.bulk.commit_group;" ::: "memory");
          }
        }
      }
      if (lead) publish(&g_abar[32]);
      __syncwarp();
    }
    if ((w & 1) && cta < NH) {
#pragma unroll 1
      for (int seg = w >> 1; seg < NAUXSEG; seg += 2) {
        if (lead) {
          mbar_wait(fullo + (w >> 1) * 8, (seg >> 1) & 1);
          mbar_arrive(emptyo + (w >> 1) * 8);
          if (PUB == 0 || seg >= NAUXSEG - 2) publish(&g_ocnt[seg * 64 + 2 * cta / 9 * 8]);
          else {
            if (PUB == 1) asm volatile("fence.acq_rel.gpu;" ::: "memory"); else if (PUB > 2) wait_until(gtime() + PUB);
            asm volatile("red.relaxed.gpu.global.add.u32 [%0], 1;" :: "l"(&g_ocnt[seg * 64 + 2 * cta / 9 * 8]) : "memory");
          }
          if (2 * cta / 9 != (2 * cta + 1) / 9) asm volatile("red.relaxed.gpu.global.add.u32 [%0], 1;" :: "l"(&g_ocnt[seg * 64 + (2 * cta + 1) / 9 * 8]) : "memory");
          SSTAMP(9, seg);
        }
        __syncwarp();
      }
    }
    if (w & 1) return;
    if (w == 0) {
      if (lead) {
        mbar_expect(fullw, 18 * 8192 + 2048);
#pragma unroll 1
        for (int k = 0; k < 18; k++) {
          const int g = k / 9, kb = p3_k(g) * 9 + k - 9 * g;
          if (kb < 64) tma_load(sb + k * 8192, &tm.wob, p3_n(g) * 64, kb * 64, fullw);
          else tma_load(sb + k * 8192, &tm.woa, p3_n(g) * 64, (kb - 64) * 64, fullw);
        }
        for (int g = 0; g < 2; g++) tma_load(sb + A_XW + g * 2048, &tm.wo8, p3_n(g) * 64, 512 + p3_k(g) * 8, fullw);
      }
      __syncwarp();
    }
    bar_sync(6, cta >= NH ? 320 : 288);
    if (lead) {
      if (NQ == 3) for (int i = 0; i < 4; i++) mbar_arrive(emptyq + 16);
      wait_count(&g_abar[32], NAUX * (epoch + 1));
      int avail = 0, sl = w >> 1, ph = 1;
      const int ke = p3_k(w >> 1);
      const unsigned nheads = (ke < 7 ? 5 : 1) * (epoch + 1);
#pragma unroll 1
      for (int seg = 0; seg < NAUXSEG; seg++) {
        bool waited = false;
        if (seg >= avail) {
          const unsigned* const c = &g_ocnt[seg * 64 + ke * 8];
          const int c2 = ldg_relaxed32(c + 128) - nheads, c1 = ldg_relaxed32(c + 64) - nheads, c0 = ldg_acquire32(c) - nheads;
          waited = c0 < 0;
          if (waited) { wait_count(c, nheads, !(TL & 2) || seg < NAUXSEG - 2); if (PDLY && seg < FEND) wait_until(gtime() + PDLY); }
          else if (c1 >= 0) avail = seg + (c2 >= 0 ? 3 : 2);
        }
        SSTAMP(5, seg);
        mbar_wait(empty3 + 8 * sl, ph);
        if (AX & 4) mbar_arrive(full3 + 8 * sl);
        else {
          mbar_expect(full3 + 8 * sl, XT + 512);
          tma_load3c(sb + sl * XT, &tm.o3, 0, seg * 32, ke * 9, full3 + 8 * sl);
          tma_load(sb + A_XT + sl * 512, &tm.o8, 72 * 64 + ke * 8, seg * 32, full3 + 8 * sl);
        }
        p3_next(sl, ph);
      }
    }
  } else if (wg == 2) {
    asm volatile("setmaxnreg.dec.sync.aligned.u32 88;");
    {
      const unsigned epoch = *(volatile unsigned*)&g_epoch2;
      if ((tid & 127) < 80) { const uint4 g = __ldg((const uint4*)gate_w + min(tid & 127, 71)); sts128(sb + A_GW + (tid & 127) * 16, g.x, g.y, g.z, g.w); }
      fence_async();
      bar_sync(3, 128);
      float gt[2][4];
      const uint32_t d0 = (sb & 0x3FFFF) >> 4;
#pragma unroll 1
      for (int j = 0; j < 3; j++) {
        mbar_wait(fullx + 8 * j, 0);
        WG_FENCE();
#pragma unroll
        for (int k = 0; k < 24; k++)
          wgmma_n8_ss(gt[k & 1], desc_at(d0 + (k & 1) * (A_XH >> 4) + j * 1536 + (k >> 3) * 512 + (k & 6), 16, 1024, 1), desc_at(d0 + (A_GW >> 4) + j * 24 + (k & 30), 16, 128, 0), j | (k >> 1));
        WG_COMMIT();
      }
      WG_WAIT(0);
      if ((lane & 3) == 0)
#pragma unroll
        for (int i = 0; i < 4; i++) {
          const float gv = 1.f / (1.f + __expf(-gt[i >> 1][(i & 1) * 2]));
          const int r = w * 16 + (lane >> 2) + (i & 1) * 8, tok = 2 * (57 * tile - 7 + r) + (i >> 1);
          sts32(sb + A_GATE + ((i >> 1) * 64 + r) * 4, __float_as_uint(gv));
          if (hh == 0 && r >= 7 && tok < S_LEN) g_gate[tok] = gv;
        }
      if (tid == 256) sts32(sb + A_BAR + 376, epoch);
      __syncwarp();
      bar_arrive(7, 384);
      __half2 hw = __float2half2_rn(0.f);
#pragma unroll
      for (int i = 0; i < 9; i++) { const uint4 v = __ldg((const uint4*)woa + cta * 1152 + i * 128 + (tid & 127)); hw = amax4(hw, &v.x); }
      const uint32_t ew = wexp(hw);
      if (lane == 0) atomicMax(&g_amax[0], (unsigned long long)(epoch + 1) << 32 | ew);
      bar_sync(3, 128);
      if (tid == 256) {
        count_up(&g_abar[0]);
        wait_count(&g_abar[0], NAUX * (epoch + 1));
        if (cta == 0) *(volatile unsigned*)&g_epoch2 = epoch + 1;
      }
      __syncwarp();
      bar_sync(3, 128);
    }
    if (cta < NH) {
      const int lim = w * 8 + (lane >> 2) - 2 * (lane & 3);
      int q = 0, ph = 0;
      uint32_t o[16];
      bool pend = false;
      auto flush = [&](int seg) {
        unsigned char* const a = (unsigned char*)(g_Ocat + (size_t)(seg * 32 + w * 8 + (lane >> 2)) * KCAT + cta * DH) + (lane & 1) * 12 + (lane & 3) * 4;
#pragma unroll
        for (int n = 0; n < 8; n++) {
          const uint32_t x = o[2 * n], y = o[2 * n + 1], z = __shfl_xor_sync(0xffffffffu, lane & 1 ? x : y, 1);
          if (!(AX & 32)) asm volatile("st.relaxed.gpu.global.v2.b32 [%0], {%1,%2};" :: "l"(a + n * 32), "r"(lane & 1 ? z : x), "r"(lane & 1 ? y : z) : "memory");
        }
        if (tid == 256) SSTAMP(13, seg);
        mbar_wait(emptyo + (seg & 1) * 8, (~seg >> 1) & 1);
        __syncwarp();
        if (lane == 0) mbar_arrive(fullo + (seg & 1) * 8);
      };
      uint32_t p[5][4];
#pragma unroll
      for (int n = 0; n < 10; n++) p[n >> 1][1 + (n & 1)] = __shfl_sync(0xffffffffu, lane ^ n, n);
#pragma unroll 1
      for (int seg = 0; seg < NAUXSEG; seg++) {
        const float gt = __ldcg(&g_gate[seg * 32 + w * 8 + (lane >> 2)]);
        float sc[20], d[32];
        const uint32_t d0 = ((sb & 0x3FFFF) + (q < 2 ? A_IN + q * A_INS : 3 * XT)) >> 4;
        if (PIPE && pend && !__shfl_sync(0xffffffffu, mbar_test(fullq + q * 8, ph), 0)) { flush(seg - 1); pend = false; }
        mbar_wait(fullq + q * 8, ph);
        if (tid == 256) SSTAMP(2, seg);
        WG_FENCE();
#pragma unroll
        for (int k = 0; k < 8; k++) {
          const int o = ((k >> 2) * 9216 + (k & 3) * 256) >> 4;
          wgmma_n40_ss_tt(sc, desc_at(d0 + o, 128, 512, 0), desc_at(d0 + o + 256, 128, 1024, 0), k > 0);
        }
        WG_COMMIT();
        if (PIPE && pend) flush(seg - 1);
        WG_WAIT(0);
        if (tid == 256) SSTAMP(12, seg);
        float a[10];
#pragma unroll
        for (int i = 0; i < 10; i++) {
          a[i] = sc[(i >> 1) * 4 + (i & 1)] * (SM_SCALE * LOG2E);
          if (i < 8 && (i >> 1) * 8 + (i & 1) > lim) a[i] = -1.0e9f * LOG2E;
        }
        float m = max10(a);
        m = fmaxf(m, __shfl_xor_sync(0xffffffffu, m, 1)); m = fmaxf(m, __shfl_xor_sync(0xffffffffu, m, 2));
#pragma unroll
        for (int i = 0; i < 10; i++) a[i] = ex2(a[i] - m);
#pragma unroll
        for (int n = 0; n < 5; n++) {
          p[n][0] = pack_bf16(a[2 * n], a[2 * n + 1]); p[n][3] = p[n][0] | p[n][1];
          asm volatile("" : "+r"(p[n][0]), "+r"(p[n][3]) :: "memory");
        }
        float sum = ((a[0] + a[1]) + (a[2] + a[3])) + ((a[4] + a[5]) + (a[6] + a[7])) + (a[8] + a[9]);
        sum += __shfl_xor_sync(0xffffffffu, sum, 1);
        if (tid == 256) SSTAMP(3, seg);
        WG_FENCE();
#pragma unroll
        for (int n = 0; n < 5; n++) wgmma_n64_rs(d, p[n], n < 4 ? desc_at(d0 + 1152 + 8 * n, 4096, 512, 0) : desc_at(d0 + 1152 + 512, 1024, 128, 0), n);
        WG_COMMIT();
        sum += __shfl_xor_sync(0xffffffffu, sum, 2);
        const float f = (1.f - gt) * rcp(sum);
        WG_WAIT(0);
        if (lane == 0) mbar_arrive(emptyq + q * 8);
        if (++q == NQ) { q = 0; ph ^= 1; }
        if (tid == 256) SSTAMP(4, seg);
#pragma unroll
        for (int n = 0; n < 16; n++) { const float* const v = d + (n & 7) * 4 + (n >> 3) * 2; o[n] = pack_bf16(v[0] * f, v[1] * f); }
        if (PIPE) pend = true; else flush(seg);
      }
      if (PIPE) flush(NAUXSEG - 1);
    }
  } else {
    asm volatile("setmaxnreg.inc.sync.aligned.u32 200;");
    {
      const int g = lane >> 2, t = lane & 3;
      const uint32_t eb = sb + A_EPI + wg * A_EPW, d0 = (sb & 0x3FFFF) >> 4;
      const uint32_t own = (2 * t <= g ? 0xffffu : 0u) | (2 * t < g ? 0xffff0000u : 0u);
      const int kmin = 7 - 57 * tile - 16 * w;
      __half2 ho = __float2half2_rn(0.f);
#pragma unroll 1
      for (int c = 0; c < 4; c++) {
        float acc[96], tl[12];
#pragma unroll 1
        for (int r = 0; r < 4; r++) {
#pragma unroll
          for (int st = 0; st < A_NS; st++) {
            const int ks = r * 9 + st;
            if (c == 0 && st % 3 == 0 && ks % 12 == 0) mbar_wait(fullx + 8 * (ks / 12), 0);
            mbar_wait(full1 + 8 * st, r & 1);
            const uint64_t da = desc_at(d0 + wg * (A_XH >> 4) + (ks >> 2) * 512 + (ks & 3) * 2, 16, 1024, 1);
            WG_FENCE();
            wgmma_n192_ss_nt(acc, da, desc_at(d0 + ((A_RING + st * A_WM) >> 4), 2048, 1024, 1), ks);
            if (!(AX & 2)) wgmma_n24_ss_nt(tl, da, desc_at(d0 + ((A_TAIL + st * A_WT) >> 4), 128, 256, 0), ks);
            WG_COMMIT();
            if (st == 0 && r == 2) bar_sync(11 + wg, 160);
            WG_WAIT(1);
            if (ks > 0 && lane == 0) mbar_arrive(empty1 + 8 * ((st + A_NS - 1) % A_NS));
          }
        }
        WG_WAIT(0);
        if (lane == 0) mbar_arrive(empty1 + 8 * (A_NS - 1));
        ASTAMP(16 + (c & 3));
        uint32_t ql[9], qh[9], kl[9], kh[9], kx[10], vl[9], vh[9], vx[10];
#pragma unroll
        for (int j = 0; j < 9; j++) {
          const float* const q = j < 8 ? acc + 4 * j : tl, * const k = j < 8 ? acc + 32 + 4 * j : tl + 4, * const v = j < 8 ? acc + 64 + 4 * j : tl + 8;
          kh[j] = pack_bf16(k[2], k[3]); vh[j] = pack_bf16(v[2], v[3]);
          ql[j] = pack_bf16(q[0], q[1]); qh[j] = pack_bf16(q[2], q[3]); kl[j] = pack_bf16(k[0], k[1]); vl[j] = pack_bf16(v[0], v[1]);
        }
        if (w < 3) {
          const uint32_t ha = eb + 1024 + w * 2304 + lane * 16;
          stsm4(ha, kh[0], kh[1], kh[2], kh[3]); stsm4(ha + 512, kh[4], kh[5], kh[6], kh[7]);
          stsm4(ha + 1024, vh[0], vh[1], vh[2], vh[3]); stsm4(ha + 1536, vh[4], vh[5], vh[6], vh[7]);
          asm volatile("stmatrix.sync.aligned.m8n8.x2.shared.b16 [%0], {%1,%2};" :: "r"(ha + 2048), "r"(kh[8]), "r"(vh[8]) : "memory");
        }
        if (c == 0) bar_sync(7, 384); else bar_sync(1 + wg, 128);
        {
          const uint32_t ha = eb + 1024 + max(w - 1, 0) * 2304 + lane * 16;
          ldsm4(kx, ha); ldsm4(kx + 4, ha + 512); ldsm4t(vx, ha + 1024); ldsm4t(vx + 4, ha + 1536);
          asm volatile("ldmatrix.sync.aligned.m8n8.x1.shared.b16 {%0}, [%1];" : "=r"(kx[8]) : "r"(ha + 2048) : "memory");
          asm volatile("ldmatrix.sync.aligned.m8n8.x1.trans.shared.b16 {%0}, [%1];" : "=r"(vx[8]) : "r"(ha + 2176) : "memory");
        }
        const float gl = __uint_as_float(lds32(sb + A_GATE + (wg * 64 + w * 16 + g) * 4)), gh = __uint_as_float(lds32(sb + A_GATE + (wg * 64 + w * 16 + g + 8) * 4));
#pragma unroll
        for (int j = 0; j < 9; j++) { vl[j] = movm(vl[j]); vh[j] = movm(vh[j]); }
        bar_sync(1 + wg, 128);
        uint32_t ol[9], oh[9];
#pragma unroll
        for (int i = 0; i < 4; i++) {
          const int b = 2 * i;
          const uint32_t a[4] = {t >= i ? ql[b] : 0u, t >= i ? qh[b] : 0u, ql[b + 1], qh[b + 1]}, a4 = t <= i ? ql[b + 2] : 0u, a5 = t <= i ? qh[b + 2] : 0u;
          float sx[4], sl[4], sh[4];
          mma16816z(sx, a, kx[b], kx[b + 1]); mma16816z(sl, a, kl[b], kl[b + 1]); mma16816z(sh, a, kh[b], kh[b + 1]);
          mma1688(sx, a4, a5, kx[b + 2]); mma1688(sl, a4, a5, kl[b + 2]); mma1688(sh, a4, a5, kh[b + 2]);
          float e[4];
#pragma unroll
          for (int u = 0; u < 4; u++) {
            const int cc = 2 * t + (u & 1);
            e[u] = (cc <= g ? (u < 2 ? sl[u] : sh[u]) : (u < 2 ? sx[u] : sl[u])) * (0.23570226039551584f * LOG2E);
            if ((cc <= g ? cc : cc - 8) + (u & 2) * 4 < kmin) e[u] = -1.0e9f * LOG2E;
          }
          float m0 = fmaxf(e[0], e[1]), m1 = fmaxf(e[2], e[3]);
#pragma unroll
          for (int o = 1; o < 4; o <<= 1) { m0 = fmaxf(m0, __shfl_xor_sync(0xffffffffu, m0, o)); m1 = fmaxf(m1, __shfl_xor_sync(0xffffffffu, m1, o)); }
          e[0] = ex2(e[0] - m0); e[1] = ex2(e[1] - m0); e[2] = ex2(e[2] - m1); e[3] = ex2(e[3] - m1);
          const uint32_t p0 = pack_bf16(e[0], e[1]), p1 = pack_bf16(e[2], e[3]);
          const uint32_t p[4] = {p0 & ~own, 0u, p0 & own, p1 & ~own};
          float s0 = e[0] + e[1], s1 = e[2] + e[3];
#pragma unroll
          for (int o = 1; o < 4; o <<= 1) { s0 += __shfl_xor_sync(0xffffffffu, s0, o); s1 += __shfl_xor_sync(0xffffffffu, s1, o); }
          const float f0 = gl * rcp(s0), f1 = gh * rcp(s1);
#pragma unroll
          for (int j = b; j < b + 3; j++) {
            float o[4];
            mma16816z(o, p, vx[j], vl[j]);
            mma1688(o, 0u, p1 & own, vh[j]);
            const uint32_t lo = pack_bf16(o[0] * f0, o[1] * f0), hi = pack_bf16(o[2] * f1, o[3] * f1);
            if (j > b || i == 0) { ol[j] = lo; oh[j] = hi; }
            else { ol[j] = t >= i ? lo : ol[j]; oh[j] = t >= i ? hi : oh[j]; }
          }
        }
        const uint32_t sa = eb + 16 + (w * 16 + (lane & 15)) * 144 + (lane >> 4) * 16;
#pragma unroll
        for (int j = 0; j < 8; j += 2) stsm4(sa + j * 16, ol[j], oh[j], ol[j + 1], oh[j + 1]);
        asm volatile("stmatrix.sync.aligned.m8n8.x2.shared.b16 [%0], {%1,%2};" :: "r"(sa + 128), "r"(ol[8]), "r"(oh[8]) : "memory");
        ho = amax4(amax4(amax4(amax4(ho, ol), ol + 4), oh), oh + 4);
        ho = __hmax2_nan(__hmax2_nan(ho, __habs2(*(const __half2*)&ol[8])), __habs2(*(const __half2*)&oh[8]));
        if (c == 3 && tile == 17) {
          const uint32_t eo = wexp(ho);
          if (lane == 0) atomicMax(&g_amax[16], (unsigned long long)(lds32(sb + A_BAR + 376) + 1) << 32 | eo);
        }
        fence_async();
        bar_arrive(13 + wg, 160);
        ASTAMP(20 + (c & 3));
      }
    }
    ASTAMP(3);
    uint32_t wa[36][4];
    mbar_wait(fullw, 0);
    const uint32_t la = sb + wg * 73728 + ((lane & 7) + ((lane >> 4) << 3)) * 128 + (((2 * w + ((lane >> 3) & 1)) ^ (lane & 7)) << 4);
#pragma unroll
    for (int k = 0; k < 36; k++) ldsm4t(wa[k], la + k * 2048);
    sts64(sb + A_XW + wg * 2048 + 1024 + (tid & 127) * 8, 0, 0);
    fence_async();
    bar_arrive(6, cta >= NH ? 320 : 288);
    bar_sync(1 + wg, 128);
    ASTAMP(4);
    const int nsl = p3_n(wg), ke = p3_k(wg), t = lane & 3;
    const unsigned epoch = lds32(sb + A_BAR + 376);
    uint2* const part = g_part + nsl * 4096 + w * 16 + (lane >> 2) * 2 + (t & 1);
    auto tag = [&](int seg) { return PR == 8 ? ((seg >> 3) + 1 + (epoch & (seg >> 1) & (seg >> 2))) & 1 : ((seg >> 2) + 1 + (epoch & (seg >> 1))) & 1; };
    uint2 v[4];
    auto fetch = [&](int seg) {
#pragma unroll
      for (int j = 0; j < 4; j++)
        asm volatile("ld.relaxed.gpu.global.v2.b32 {%0,%1}, [%2];" : "=r"(v[j].x), "=r"(v[j].y) : "l"(part + (seg & (PR - 1)) * 36864 + ke * 512 + ((t >> 1) * 4 + j) * 64) : "memory");
    };
    auto finish = [&](int seg) {
      int n = 0;
#pragma unroll 1
      while (!(AX & 16) && __any_sync(0xffffffffu, (((v[0].x ^ tag(seg)) | (v[1].x ^ tag(seg)) | (v[2].x ^ tag(seg)) | (v[3].x ^ tag(seg))) & 1) != 0) && ++n < SPIN_LIMIT) {
        if (seg < NAUXSEG - ((TL & 2) ? 2 : 1)) __nanosleep(100);
        fetch(seg);
      }
      const float a0 = (bf_lo(v[0].x) + bf_lo(v[1].x)) + (bf_lo(v[2].x) + bf_lo(v[3].x)), a1 = (bf_hi(v[0].x) + bf_hi(v[1].x)) + (bf_hi(v[2].x) + bf_hi(v[3].x));
      const float b0 = (bf_lo(v[0].y) + bf_lo(v[1].y)) + (bf_lo(v[2].y) + bf_lo(v[3].y)), b1 = (bf_hi(v[0].y) + bf_hi(v[1].y)) + (bf_hi(v[2].y) + bf_hi(v[3].y));
      const float c0 = (t < 2 ? a0 : b0) + __shfl_xor_sync(0xffffffffu, t < 2 ? b0 : a0, 2), c1 = (t < 2 ? a1 : b1) + __shfl_xor_sync(0xffffffffu, t < 2 ? b1 : a1, 2);
      ((uint32_t*)(out + (size_t)(seg * 32 + ke * 4 + ((lane >> 2) & 3)) * DM + nsl * 64 + w * 16 + (lane >> 4) * 8))[t] = movm(pack_bf16(c0, c1));
    };
    float acc[16];
    if (AX & 64) for (int i = 0; i < 16; i++) acc[i] = 0.f;
    int done = 0, sl = cta < NH ? 0 : wg, ph = 0;
    const uint32_t d0 = (sb & 0x3FFFF) >> 4;
#pragma unroll 1
    for (int seg = 0; seg < NAUXSEG; seg++) {
      if (DRAIN) {
#pragma unroll 1
        while (done < seg && !mbar_test(full3 + 8 * sl, ph)) { fetch(done); finish(done); done++; }
      }
      mbar_wait(full3 + 8 * sl, ph);
      if (SER && !(AX & 64) && (wg == 1 || seg > 0)) bar_sync(10 - wg, 256);
      if (tid == 128) SSTAMP(6, seg);
      if (!(AX & 16)) fetch(done);
      if (!(AX & 64)) {
        const uint64_t db = desc_at(d0 + sl * (XT >> 4), 16, 1024, 1);
        WG_FENCE();
        wgmma_n32_ss_tn(acc, desc_at(d0 + ((A_XW + wg * 2048) >> 4), 8192, 1024, 1), desc_at(d0 + (A_XT >> 4) + sl * 32, 0, 128, 0), 0);
#pragma unroll
        for (int k = 0; k < 36; k++) {
          wgmma_n32_rs(acc, wa[k][0], wa[k][1], wa[k][2], wa[k][3], db + (k >> 2) * 256 + (k & 3) * 2, 1);
          if (SER && k == SER && (wg == 0 || seg < NAUXSEG - 1)) bar_arrive(9 + wg, 256);
        }
        WG_COMMIT();
      }
      if (done <= seg - PL) finish(done++);
      WG_WAIT(0);
      if (lane == 0) mbar_arrive(empty3 + 8 * sl);
      p3_next(sl, ph);
#pragma unroll
      for (int j = 0; j < 4; j++)
        if (!(AX & 16) || acc[4 * j] == 1.2345678f)
          asm volatile("st.relaxed.gpu.global.v2.b32 [%0], {%1,%2};" :: "l"(part + (seg & (PR - 1)) * 36864 + (2 * j + (t >> 1)) * 512 + ke * 64),
                       "r"((pack_bf16(acc[4 * j], acc[4 * j + 1]) & ~1u) | tag(seg)), "r"(pack_bf16(acc[4 * j + 2], acc[4 * j + 3])) : "memory");
      if (tid == 128) SSTAMP(7, seg);
      if (tid == 128) SSTAMP(8, seg);
      if ((seg & 7) == 6) ASTAMP(5 + (seg >> 3));
    }
#pragma unroll 1
    for (; done < NAUXSEG; done++) { fetch(done); finish(done); }
    ASTAMP(13);
    TSTAMP(48);
    MSTAMP(9);
  }
}

typedef CUresult (*EncodeFn)(CUtensorMap*, CUtensorMapDataType, cuuint32_t, void*, const cuuint64_t*, const cuuint64_t*,
                             const cuuint32_t*, const cuuint32_t*, CUtensorMapInterleave, CUtensorMapSwizzle,
                             CUtensorMapL2promotion, CUtensorMapFloatOOBfill);
static void make_map(EncodeFn enc, CUtensorMap* m, const void* p, int rows, int cols, int box_rows) {
  cuuint64_t dims[2] = {(cuuint64_t)cols, (cuuint64_t)rows};
  cuuint64_t strides[1] = {(cuuint64_t)cols * 2};
  cuuint32_t box[2] = {64, (cuuint32_t)box_rows};
  cuuint32_t es[2] = {1, 1};
  enc(m, CU_TENSOR_MAP_DATA_TYPE_BFLOAT16, 2, (void*)p, dims, strides, box, es, CU_TENSOR_MAP_INTERLEAVE_NONE,
      CU_TENSOR_MAP_SWIZZLE_128B, CU_TENSOR_MAP_L2_PROMOTION_L2_128B, CU_TENSOR_MAP_FLOAT_OOB_FILL_NONE);
}

constexpr int g_poll = POLL_NS;
extern "C" void kernel_launch(void* const* d_in, const int* in_sizes, int n_in, void* d_out, int out_size) {
  const bf16* x = (const bf16*)d_in[0];
  const bf16* wqkvA = (const bf16*)d_in[1];
  const bf16* woA = (const bf16*)d_in[2];
  const bf16* mem0 = (const bf16*)d_in[4];
  const bf16* Wq = (const bf16*)d_in[5];
  const bf16* Wk = (const bf16*)d_in[6];
  const bf16* Wv = (const bf16*)d_in[7];
  const bf16* Wo = (const bf16*)d_in[8];
  const bf16* gate_w = (const bf16*)d_in[10];
  static EncodeFn enc = nullptr;
  static void *pO = nullptr, *pR = nullptr;
  if (!enc) {
    cudaDriverEntryPointQueryResult qr;
    cudaGetDriverEntryPoint("cuTensorMapEncodeTiled", (void**)&enc, cudaEnableDefault, &qr);
    cudaGetSymbolAddress(&pO, g_Ocat);
    cudaGetSymbolAddress(&pR, g_red_raw);
    cudaFuncSetAttribute(rec_kernel, cudaFuncAttributeMaxDynamicSharedMemorySize, SM_TOTAL);
    cudaFuncSetAttribute(aux_kernel, cudaFuncAttributeMaxDynamicSharedMemorySize, A_TOTAL);
  }
  RMaps rm;
  rm.poll = g_poll; rm.out = (bf16*)d_out;
  make_map(enc, &rm.woa, woA, DM, DM, 24);
  {
    cuuint64_t dims[2] = {KCAT, S_LEN}, strides[1] = {KCAT * 2};
    cuuint32_t box[2] = {32, 64}, es[2] = {1, 1};
    enc(&rm.oa, CU_TENSOR_MAP_DATA_TYPE_BFLOAT16, 2, pO, dims, strides, box, es, CU_TENSOR_MAP_INTERLEAVE_NONE,
        CU_TENSOR_MAP_SWIZZLE_NONE, CU_TENSOR_MAP_L2_PROMOTION_NONE, CU_TENSOR_MAP_FLOAT_OOB_FILL_NONE);
  }
  rm.red = (unsigned char*)(((uintptr_t)pR + 262143) & ~(uintptr_t)262143);
  {
    cuuint64_t dims[3] = {64, S_LEN, 9}, strides[2] = {DM * 2, 128};
    cuuint32_t box[3] = {64, 32, 9}, es[3] = {1, 1, 1};
    enc(&rm.x, CU_TENSOR_MAP_DATA_TYPE_BFLOAT16, 3, (void*)x, dims, strides, box, es, CU_TENSOR_MAP_INTERLEAVE_NONE,
        CU_TENSOR_MAP_SWIZZLE_128B, CU_TENSOR_MAP_L2_PROMOTION_L2_128B, CU_TENSOR_MAP_FLOAT_OOB_FILL_NONE);
  }
  make_map(enc, &rm.wq, Wq, DM, 4096, 192);
  make_map(enc, &rm.wk, Wk, DM, 4096, 192);
  make_map(enc, &rm.wv, Wv, DM, 4096, 192);
  make_map(enc, &rm.wo, Wo, 4096, DM, 128);
  AMaps am;
  {
    cuuint32_t es[4] = {1, 1, 1, 1};
    cuuint64_t dx[4] = {64, 2, S_LEN / 2, 9}, sx[3] = {DM * 2, DM * 4, 128};
    cuuint32_t bx[4] = {64, 1, 64, 3};
    enc(&am.x, CU_TENSOR_MAP_DATA_TYPE_BFLOAT16, 4, (void*)x, dx, sx, bx, es, CU_TENSOR_MAP_INTERLEAVE_NONE,
        CU_TENSOR_MAP_SWIZZLE_128B, CU_TENSOR_MAP_L2_PROMOTION_L2_128B, CU_TENSOR_MAP_FLOAT_OOB_FILL_NONE);
    cuuint64_t dw[3] = {DM, DM, 3}, sw[2] = {DM * 6, DM * 2};
    cuuint32_t bw[3] = {64, 16, 3}, bt[3] = {8, 16, 3};
    enc(&am.wa, CU_TENSOR_MAP_DATA_TYPE_BFLOAT16, 3, (void*)wqkvA, dw, sw, bw, es, CU_TENSOR_MAP_INTERLEAVE_NONE,
        CU_TENSOR_MAP_SWIZZLE_128B, CU_TENSOR_MAP_L2_PROMOTION_L2_128B, CU_TENSOR_MAP_FLOAT_OOB_FILL_NONE);
    enc(&am.wt, CU_TENSOR_MAP_DATA_TYPE_BFLOAT16, 3, (void*)wqkvA, dw, sw, bt, es, CU_TENSOR_MAP_INTERLEAVE_NONE,
        CU_TENSOR_MAP_SWIZZLE_NONE, CU_TENSOR_MAP_L2_PROMOTION_NONE, CU_TENSOR_MAP_FLOAT_OOB_FILL_NONE);
    cuuint64_t dz[3] = {KCAT, 2, S_LEN / 2}, sz[2] = {KCAT * 2, KCAT * 4};
    cuuint32_t bz[3] = {72, 1, 57};
    enc(&am.oa, CU_TENSOR_MAP_DATA_TYPE_BFLOAT16, 3, pO, dz, sz, bz, es, CU_TENSOR_MAP_INTERLEAVE_NONE,
        CU_TENSOR_MAP_SWIZZLE_NONE, CU_TENSOR_MAP_L2_PROMOTION_NONE, CU_TENSOR_MAP_FLOAT_OOB_FILL_NONE);
  }
  {
    cuuint64_t dims[3] = {64, S_LEN, KCAT / 64}, strides[2] = {KCAT * 2, 128};
    cuuint32_t box[3] = {64, 32, 9}, es[3] = {1, 1, 1};
    make_map(enc, &am.o, pO, S_LEN, KCAT, 32);
    enc(&am.o3, CU_TENSOR_MAP_DATA_TYPE_BFLOAT16, 3, pO, dims, strides, box, es, CU_TENSOR_MAP_INTERLEAVE_NONE,
        CU_TENSOR_MAP_SWIZZLE_128B, CU_TENSOR_MAP_L2_PROMOTION_L2_128B, CU_TENSOR_MAP_FLOAT_OOB_FILL_NONE);
  }
  make_map(enc, &am.wob, Wo, 4096, DM, 64);
  make_map(enc, &am.woa, woA, DM, DM, 64);
  make_map(enc, &am.wo8, woA, DM, DM, 8);
  {
    cuuint64_t dims[2] = {KCAT, S_LEN}, strides[1] = {KCAT * 2};
    cuuint32_t box[2] = {8, 32}, es[2] = {1, 1};
    enc(&am.o8, CU_TENSOR_MAP_DATA_TYPE_BFLOAT16, 2, pO, dims, strides, box, es, CU_TENSOR_MAP_INTERLEAVE_NONE,
        CU_TENSOR_MAP_SWIZZLE_NONE, CU_TENSOR_MAP_L2_PROMOTION_NONE, CU_TENSOR_MAP_FLOAT_OOB_FILL_NONE);
  }

  rec_kernel<<<96, 384, SM_TOTAL, cudaStreamPerThread>>>(rm, x, mem0);
  cudaLaunchConfig_t cfg = {};
  cfg.gridDim = dim3(NAUX); cfg.blockDim = dim3(512); cfg.dynamicSmemBytes = A_TOTAL; cfg.stream = cudaStreamPerThread;
  cudaLaunchAttribute at[1];
  at[0].id = cudaLaunchAttributeProgrammaticStreamSerialization; at[0].val.programmaticStreamSerializationAllowed = 1;
  cfg.attrs = at; cfg.numAttrs = 1;
  if (XP & 16) cfg.numAttrs = 0;
  if (!(XP & 64)) cudaLaunchKernelEx(&cfg, aux_kernel, am, wqkvA, woA, gate_w, (bf16*)d_out);
}
```

```cpp
#include <cuda_runtime.h>
#include <cuda_bf16.h>
#include <cuda_fp16.h>
#include <cuda.h>
#include <stdint.h>

typedef __nv_bfloat16 bf16;

constexpr int S_LEN = 2048, DM = 576, NH = 32, DH = 128, NSEG = 64, KCAT = 4096 + 576;
constexpr int NAUXSEG = NSEG - 2;
constexpr int NAUX = 36;
#define RED_LINE(i) (((i) >> 2) * 4096 + ((i) & 1) * 256 + ((i) & 2) * 512)
#define RED_SLOT(s) (((s) & 1) * 128 + ((s) & 2) * 256)

#define POLL_NS 880
#define NII 18
#define W3PRE 4
#define W3MID 4
#define GF 0
#define B5POS 0
#define NUP 4
#define UPF 1
#define B3Q 9
#define B3F 0
#define GATE 7
#define NTL 2
#define B7R 1
#define VS0 1
#define VS1 0
#define VLATE(w) ((w) == 0 ? VS0 == 1 : (w) == 1 ? VS1 == 1 : false)
#define HOIST 0
#define RSLOW 0
#define CSY 0
#define DD 2
#define N12 18
#define N14 18
#define HP 0
#define HL 0
#define WL 1
#define RV 3
#define EXM 1
#define PSTAMP 0
#define PFIX 1
#define RET 1
#define TL 6
#define CLR 1
#define RFW 0
#define NIC 0
#define LEAD 0
#define FIN16 1
#define VXG 0
#define NRING 20
#define EXD 0
#define HDLY 0
#define F10 1
#define NPROBE 2
#define QM 0
#define N5 224
#define KP(i) (((i) >> 1) + 4 * ((i) & 1))
#define SPIN_LIMIT (1 << 14)
#define XP 0

__device__ __align__(1024) bf16 g_Ocat[S_LEN * KCAT];
__device__ __align__(1024) unsigned char g_red_raw[2 * 262144];
constexpr int HINT_OFF = 2048;
__device__ __align__(16) float g_gate[S_LEN];
__device__ __align__(128) uint4 g_stats[96 * 2];
__device__ unsigned g_epoch;
__device__ unsigned g_epoch2;
__device__ unsigned g_ocnt[NSEG * 64];
__device__ unsigned g_abar[3 * 32];
__device__ unsigned long long g_amax[2 * 16];
__device__ unsigned g_scnt[NSEG * 32 * 8];
__device__ __align__(1024) unsigned char g_seg[NRING * 96 * 10240];
__device__ unsigned g_used[NH * 32];
__device__ __align__(1024) uint2 g_part[8 * 9 * 64 * 64];
__device__ int g_err;
#define MSTAMP(i)
#define TSTAMP(i)
#define PROF(idx)
#define PROFP(idx)
#define RSTAMP(k)
#define STAMP(idx)
#define ASTAMP(idx)
#define SSTAMP(k, seg)
#define WSTAMP(idx)

#define DI __device__ __forceinline__
DI uint32_t smem_u32(const void* p) { return (uint32_t)__cvta_generic_to_shared(p); }
DI uint32_t clock32() { uint32_t c; asm volatile("mov.u32 %0, %%clock;" : "=r"(c) :: "memory"); return c; }
DI uint32_t gtime() { uint32_t c; asm volatile("mov.u32 %0, %%globaltimer_lo;" : "=r"(c) :: "memory"); return c; }
DI uint32_t ldg_relaxed32(const void* p) { uint32_t v; asm volatile("ld.relaxed.gpu.global.b32 %0, [%1];" : "=r"(v) : "l"(p) : "memory"); return v; }
DI uint32_t ldg_acquire32(const void* p) { uint32_t v; asm volatile("ld.acquire.gpu.global.b32 %0, [%1];" : "=r"(v) : "l"(p) : "memory"); return v; }
DI void stg_relaxed32(void* p, uint32_t v) { asm volatile("st.relaxed.gpu.global.b32 [%0], %1;" :: "l"(p), "r"(v) : "memory"); }
DI int head_id() { int c; asm volatile("mov.u32 %0, %%clusterid.x;" : "=r"(c)); return c; }
DI uint32_t mapa(uint32_t a, uint32_t r) { uint32_t o; asm("mapa.shared::cluster.u32 %0, %1, %2;" : "=r"(o) : "r"(a), "r"(r)); return o; }
DI void cluster_arrive() { asm volatile("barrier.cluster.arrive.relaxed.aligned;" ::: "memory"); }
DI void cluster_wait() { asm volatile("barrier.cluster.wait.aligned;" ::: "memory"); }
DI void cluster_sync() { asm volatile("barrier.cluster.arrive.release.aligned;\nbarrier.cluster.wait.acquire.aligned;" ::: "memory"); }
DI void mbar_init(uint32_t b, uint32_t c) { asm volatile("mbarrier.init.shared::cta.b64 [%0], %1;" :: "r"(b), "r"(c) : "memory"); }
DI void mbar_expect(uint32_t b, uint32_t tx) { asm volatile("mbarrier.arrive.expect_tx.shared::cta.b64 _, [%0], %1;" :: "r"(b), "r"(tx) : "memory"); }
DI void mbar_arrive(uint32_t b) { asm volatile("mbarrier.arrive.shared::cta.b64 _, [%0];" :: "r"(b) : "memory"); }
DI void mbar_wait(uint32_t b, uint32_t par) {
  asm volatile("{\n.reg .pred p;\n.reg .u32 n, q;\nmov.u32 n, 0;\n"
               "WL: add.u32 n, n, 1;\nshr.u32 q, n, 12;\nxor.b32 q, q, %1;\n"
               "mbarrier.try_wait.parity.shared::cta.b64 p, [%0], q;\n@!p bra.uni WL;\n}"
               :: "r"(b), "r"(par) : "memory");
}
DI bool mbar_test(uint32_t b, uint32_t par) {
  uint32_t r;
  asm volatile("{\n.reg .pred p;\nmbarrier.test_wait.parity.shared::cta.b64 p, [%1], %2;\nselp.u32 %0, 1, 0, p;\n}" : "=r"(r) : "r"(b), "r"(par) : "memory");
  return r;
}
DI void mbar_wait_fast(uint32_t b, uint32_t par) {
  asm volatile("{\n.reg .pred p;\n.reg .u32 n, q;\nmbarrier.try_wait.parity.shared::cta.b64 p, [%0], %1;\n@p bra.uni WD;\nmov.u32 n, 0;\n"
               "WL: add.u32 n, n, 1;\nshr.u32 q, n, 12;\nxor.b32 q, q, %1;\n"
               "mbarrier.try_wait.parity.shared::cta.b64 p, [%0], q;\n@!p bra.uni WL;\nWD:\n}"
               :: "r"(b), "r"(par) : "memory");
}
DI void wait_until(uint32_t t) {
  const uint32_t now = gtime();
  t = min(t, now + 8192);
  asm volatile("{\n.reg .pred p;\n.reg .u32 c;\nTL: mov.u32 c, %%globaltimer_lo;\nsetp.lt.u32 p, c, %0;\n@p bra.uni TL;\n}" :: "r"(t) : "memory");
}
#define PIN(v) v = __shfl_xor_sync(0xffffffffu, v, 0)
#define SCHED_FENCE(k) asm volatile("{\n.reg .pred p;\nsetp.eq.u32 p, %0, %1;\n@p exit;\n}" :: "r"(fence_reg), "r"(k) : "memory")
#define MEM_ORDER(k) asm volatile("{\n.reg .pred p;\nsetp.eq.u32 p, %0, %1;\n@p st.shared.u32 [%0], %0;\n}" :: "r"(fence_reg), "r"(k + 64) : "memory")
DI void bar_sync(int id, int n) { asm volatile("bar.sync %0, %1;" :: "r"(id), "r"(n) : "memory"); }
DI void bar_arrive(int id, int n) { asm volatile("bar.arrive %0, %1;" :: "r"(id), "r"(n) : "memory"); }
DI void fence_async() { asm volatile("fence.proxy.async.shared::cta;" ::: "memory"); }
DI void st_async4(uint32_t a, uint32_t x, uint32_t y, uint32_t z, uint32_t w, uint32_t mb) {
  asm volatile("st.async.weak.shared::cluster.mbarrier::complete_tx::bytes.v4.b32 [%0], {%1,%2,%3,%4}, [%5];"
               :: "r"(a), "r"(x), "r"(y), "r"(z), "r"(w), "r"(mb) : "memory");
}
DI void st_async2(uint32_t a, uint32_t x, uint32_t y, uint32_t mb) {
  asm volatile("st.async.weak.shared::cluster.mbarrier::complete_tx::bytes.v2.b32 [%0], {%1,%2}, [%3];"
               :: "r"(a), "r"(x), "r"(y), "r"(mb) : "memory");
}
DI void sts32(uint32_t a, uint32_t x) { asm volatile("st.shared.b32 [%0], %1;" :: "r"(a), "r"(x) : "memory"); }
DI void sts64(uint32_t a, uint32_t x, uint32_t y) { asm volatile("st.shared.v2.b32 [%0], {%1,%2};" :: "r"(a), "r"(x), "r"(y) : "memory"); }
DI void sts128(uint32_t a, uint32_t x, uint32_t y, uint32_t z, uint32_t w) {
  asm volatile("st.shared.v4.b32 [%0], {%1,%2,%3,%4};" :: "r"(a), "r"(x), "r"(y), "r"(z), "r"(w) : "memory");
}
DI uint32_t lds32(uint32_t a) { uint32_t x; asm volatile("ld.shared.b32 %0, [%1];" : "=r"(x) : "r"(a) : "memory"); return x; }
DI void lds64(uint32_t a, uint32_t& x, uint32_t& y) { asm volatile("ld.shared.v2.b32 {%0,%1}, [%2];" : "=r"(x), "=r"(y) : "r"(a) : "memory"); }
DI void lds128(uint32_t a, uint32_t* r) {
  asm volatile("ld.shared.v4.b32 {%0,%1,%2,%3}, [%4];" : "=r"(r[0]), "=r"(r[1]), "=r"(r[2]), "=r"(r[3]) : "r"(a) : "memory");
}
DI void lds128f(uint32_t a, float* r) {
  asm volatile("ld.shared.v4.f32 {%0,%1,%2,%3}, [%4];" : "=f"(r[0]), "=f"(r[1]), "=f"(r[2]), "=f"(r[3]) : "r"(a) : "memory");
}
DI void lds64f(uint32_t a, float* r) { asm volatile("ld.shared.v2.f32 {%0,%1}, [%2];" : "=f"(r[0]), "=f"(r[1]) : "r"(a) : "memory"); }
DI void ldsm4t(uint32_t* r, uint32_t a) {
  asm volatile("ldmatrix.sync.aligned.m8n8.x4.trans.shared.b16 {%0,%1,%2,%3}, [%4];"
               : "=r"(r[0]), "=r"(r[1]), "=r"(r[2]), "=r"(r[3]) : "r"(a) : "memory");
}
DI void ldsm4t_in(uint32_t* r, uint32_t a, uint32_t t) {
  asm volatile("{\n.reg .pred p;\nsetp.ne.u32 p, %5, 0;\n@p ldmatrix.sync.aligned.m8n8.x4.trans.shared.b16 {%0,%1,%2,%3}, [%4];\n}"
               : "+r"(r[0]), "+r"(r[1]), "+r"(r[2]), "+r"(r[3]) : "r"(a), "r"(t) : "memory");
}
DI void lds128_in(uint32_t* r, uint32_t a, uint32_t t) {
  asm volatile("{\n.reg .pred p;\nsetp.ne.u32 p, %5, 0;\n@p ld.shared.v4.b32 {%0,%1,%2,%3}, [%4];\n}"
               : "+r"(r[0]), "+r"(r[1]), "+r"(r[2]), "+r"(r[3]) : "r"(a), "r"(t) : "memory");
}
DI void ldsm2t_in(uint32_t* r, uint32_t a, uint32_t t) {
  asm volatile("{\n.reg .pred p;\nsetp.ne.u32 p, %3, 0;\n@p ldmatrix.sync.aligned.m8n8.x2.trans.shared.b16 {%0,%1}, [%2];\n}" : "+r"(r[0]), "+r"(r[1]) : "r"(a), "r"(t) : "memory");
}
DI void reserve2(uint32_t* r) { asm volatile("{\n.reg .u64 t;\nmov.u64 t, %%clock64;\nmov.b64 {%0, %1}, t;\n}" : "=r"(r[0]), "=r"(r[1])); }
DI void scale_sum(float& x, float& y, float s, uint32_t t) {
  asm volatile("{\n.reg .pred p;\nsetp.ne.u32 p, %2, 0;\n@p mul.f32 %0, %0, %1;\n}" : "+f"(y) : "f"(s), "r"(t));
  asm volatile("{\n.reg .pred p;\nsetp.ne.u32 p, %3, 1;\n@p fma.rn.f32 %0, %0, %1, %2;\n}" : "+f"(x) : "f"(s), "f"(y), "r"(t));
}
DI void ldsm4(uint32_t* r, uint32_t a) {
  asm volatile("ldmatrix.sync.aligned.m8n8.x4.shared.b16 {%0,%1,%2,%3}, [%4];"
               : "=r"(r[0]), "=r"(r[1]), "=r"(r[2]), "=r"(r[3]) : "r"(a) : "memory");
}
DI void st_async1(uint32_t a, uint32_t x, uint32_t mb) {
  asm volatile("st.async.weak.shared::cluster.mbarrier::complete_tx::bytes.b32 [%0], %1, [%2];" :: "r"(a), "r"(x), "r"(mb) : "memory");
}
DI void stsm4(uint32_t a, uint32_t x, uint32_t y, uint32_t z, uint32_t w) {
  asm volatile("stmatrix.sync.aligned.m8n8.x4.shared.b16 [%0], {%1,%2,%3,%4};" :: "r"(a), "r"(x), "r"(y), "r"(z), "r"(w) : "memory");
}
DI void stsm4t(uint32_t a, uint32_t x, uint32_t y, uint32_t z, uint32_t w) {
  asm volatile("stmatrix.sync.aligned.m8n8.x4.trans.shared.b16 [%0], {%1,%2,%3,%4};" :: "r"(a), "r"(x), "r"(y), "r"(z), "r"(w) : "memory");
}
DI uint32_t pack_bf16(float lo, float hi) { uint32_t r; asm("cvt.rn.bf16x2.f32 %0, %1, %2;" : "=r"(r) : "f"(hi), "f"(lo)); return r; }
DI uint32_t pack_f16(float lo, float hi) { uint32_t r; asm("cvt.rn.f16x2.f32 %0, %1, %2;" : "=r"(r) : "f"(hi), "f"(lo)); return r; }
DI float ex2(float x) { float y; asm("ex2.approx.ftz.f32 %0, %1;" : "=f"(y) : "f"(x)); return y; }
DI float rcp(float x) { float y; asm("rcp.approx.ftz.f32 %0, %1;" : "=f"(y) : "f"(x)); return y; }
DI float bf_lo(uint32_t x) { return __uint_as_float(x << 16); }
DI float bf_hi(uint32_t x) { return __uint_as_float(x & 0xffff0000u); }
DI void mma16816(float* d, const uint32_t* a, uint32_t b0, uint32_t b1) {
  asm volatile("mma.sync.aligned.m16n8k16.row.col.f32.bf16.bf16.f32 {%0,%1,%2,%3}, {%4,%5,%6,%7}, {%8,%9}, {%0,%1,%2,%3};"
               : "+f"(d[0]), "+f"(d[1]), "+f"(d[2]), "+f"(d[3]) : "r"(a[0]), "r"(a[1]), "r"(a[2]), "r"(a[3]), "r"(b0), "r"(b1));
}
DI void mma16816z(float* d, const uint32_t* a, uint32_t b0, uint32_t b1) {
  asm volatile("mma.sync.aligned.m16n8k16.row.col.f32.bf16.bf16.f32 {%0,%1,%2,%3}, {%4,%5,%6,%7}, {%8,%9}, {%10,%10,%10,%10};"
               : "=f"(d[0]), "=f"(d[1]), "=f"(d[2]), "=f"(d[3]) : "r"(a[0]), "r"(a[1]), "r"(a[2]), "r"(a[3]), "r"(b0), "r"(b1), "f"(0.f));
}
DI void mma1688z(float* d, uint32_t a0, uint32_t a1, uint32_t b0) {
  asm volatile("mma.sync.aligned.m16n8k8.row.col.f32.bf16.bf16.f32 {%0,%1,%2,%3}, {%4,%5}, {%6}, {%7,%7,%7,%7};"
               : "=f"(d[0]), "=f"(d[1]), "=f"(d[2]), "=f"(d[3]) : "r"(a0), "r"(a1), "r"(b0), "f"(0.f));
}
DI void mma1688(float* d, uint32_t a0, uint32_t a1, uint32_t b0) {
  asm volatile("mma.sync.aligned.m16n8k8.row.col.f32.bf16.bf16.f32 {%0,%1,%2,%3}, {%4,%5}, {%6}, {%0,%1,%2,%3};"
               : "+f"(d[0]), "+f"(d[1]), "+f"(d[2]), "+f"(d[3]) : "r"(a0), "r"(a1), "r"(b0));
}
DI void ldsm2t(uint32_t* r, uint32_t a) {
  asm volatile("ldmatrix.sync.aligned.m8n8.x2.trans.shared.b16 {%0,%1}, [%2];" : "=r"(r[0]), "=r"(r[1]) : "r"(a) : "memory");
}
DI uint32_t add_bf16(uint32_t a, uint32_t b) { uint32_t r; asm("add.rn.bf16x2 %0, %1, %2;" : "=r"(r) : "r"(a), "r"(b)); return r; }
DI uint32_t mul_bf16(uint32_t a, uint32_t b) { uint32_t r; asm("mul.rn.bf16x2 %0, %1, %2;" : "=r"(r) : "r"(a), "r"(b)); return r; }
DI uint64_t make_desc(uint32_t addr, uint32_t lbo, uint32_t sbo, uint32_t swz) {
  return (uint64_t)((addr & 0x3FFFF) >> 4) | ((uint64_t)(lbo >> 4) << 16) | ((uint64_t)(sbo >> 4) << 32) | ((uint64_t)swz << 62);
}
DI uint64_t desc_at(uint32_t a16, uint32_t lbo, uint32_t sbo, uint32_t swz) {
  uint64_t d; asm("mov.b64 %0, {%1, %2};" : "=l"(d) : "r"(a16 + ((lbo >> 4) << 16)), "r"((sbo >> 4) | (swz << 30)));
  return d;
}
#define WG_FENCE() asm volatile("wgmma.fence.sync.aligned;" ::: "memory")
#define WG_COMMIT() asm volatile("wgmma.commit_group.sync.aligned;" ::: "memory")
#define WG_WAIT(n) asm volatile("wgmma.wait_group.sync.aligned %0;" :: "n"(n) : "memory")
#define ACC8(d, o) "+f"(d[o]), "+f"(d[o + 1]), "+f"(d[o + 2]), "+f"(d[o + 3]), "+f"(d[o + 4]), "+f"(d[o + 5]), "+f"(d[o + 6]), "+f"(d[o + 7])
DI void wgmma_n32_rs(float* d, uint32_t a0, uint32_t a1, uint32_t a2, uint32_t a3, uint64_t db, int acc) {
  asm volatile("{\n.reg .pred p;\nsetp.ne.b32 p, %21, 0;\n"
               "wgmma.mma_async.sync.aligned.m64n32k16.f32.bf16.bf16 {%0,%1,%2,%3,%4,%5,%6,%7,%8,%9,%10,%11,%12,%13,%14,%15}, "
               "{%16,%17,%18,%19}, %20, p, 1, 1, 0;\n}\n"
               : ACC8(d, 0), ACC8(d, 8) : "r"(a0), "r"(a1), "r"(a2), "r"(a3), "l"(db), "r"(acc));
}
template <int TA>
DI void wgmma_n32_ss(float* d, uint64_t da, uint64_t db, int acc) {
  asm volatile("{\n.reg .pred p;\nsetp.ne.b32 p, %18, 0;\n"
               "wgmma.mma_async.sync.aligned.m64n32k16.f32.bf16.bf16 {%0,%1,%2,%3,%4,%5,%6,%7,%8,%9,%10,%11,%12,%13,%14,%15}, "
               "%16, %17, p, 1, 1, %19, 1;\n}\n"
               : ACC8(d, 0), ACC8(d, 8) : "l"(da), "l"(db), "r"(acc), "n"(TA));
}
DI void tma_load(uint32_t dst, const CUtensorMap* m, int c0, int c1, uint32_t mb) {
  asm volatile("cp.async.bulk.tensor.2d.shared::cluster.global.mbarrier::complete_tx::bytes [%0], [%1, {%3, %4}], [%2];"
               :: "r"(dst), "l"(m), "r"(mb), "r"(c0), "r"(c1) : "memory");
}
DI void tma_load3(uint32_t dst, const CUtensorMap* m, int row, uint32_t mb) {
  asm volatile("cp.async.bulk.tensor.3d.shared::cluster.global.mbarrier::complete_tx::bytes [%0], [%1, {%3, %4, %3}], [%2];"
               :: "r"(dst), "l"(m), "r"(mb), "r"(0), "r"(row) : "memory");
}
DI bool elect_one() {
  uint32_t p;
  asm volatile("{\n.reg .pred p;\nelect.sync _|p, 0xffffffff;\nselp.u32 %0, 1, 0, p;\n}" : "=r"(p));
  return p;
}
DI void bulk_s2s(uint32_t dst, uint32_t src, uint32_t bytes, uint32_t mb) {
  asm volatile("cp.async.bulk.shared::cluster.shared::cta.mbarrier::complete_tx::bytes [%0], [%1], %2, [%3];"
               :: "r"(dst), "r"(src), "r"(bytes), "r"(mb) : "memory");
}
DI void tma_prefetch(const CUtensorMap* m, int c0, int c1) {
  asm volatile("cp.async.bulk.prefetch.tensor.2d.L2.global.tile [%0, {%1, %2}];" :: "l"(m), "r"(c0), "r"(c1) : "memory");
}
DI void tma_store(const CUtensorMap* m, uint32_t src, int c0, int c1) {
  asm volatile("cp.async.bulk.tensor.2d.global.shared::cta.bulk_group [%0, {%2, %3}], [%1];" :: "l"(m), "r"(src), "r"(c0), "r"(c1) : "memory");
}
DI uint4 ldg_relaxed(const void* p) {
  uint4 v;
  asm volatile("ld.relaxed.gpu.global.v4.b32 {%0,%1,%2,%3}, [%4];" : "=r"(v.x), "=r"(v.y), "=r"(v.z), "=r"(v.w) : "l"(p) : "memory");
  return v;
}
DI void stg_relaxed(void* p, uint32_t x, uint32_t y, uint32_t z, uint32_t w) {
  asm volatile("st.relaxed.gpu.global.v4.b32 [%0], {%1,%2,%3,%4};" :: "l"(p), "r"(x), "r"(y), "r"(z), "r"(w) : "memory");
}
DI void red_f16x8(void* p, uint32_t x, uint32_t y, uint32_t z, uint32_t w) {
  asm volatile("red.relaxed.gpu.global.add.noftz.v4.f16x2 [%0], {%1,%2,%3,%4};" :: "l"(p), "r"(x), "r"(y), "r"(z), "r"(w) : "memory");
}
DI void sq_acc(uint32_t& a, uint32_t x) { asm("fma.rn.bf16x2 %0, %1, %1, %0;" : "+r"(a) : "r"(x)); }
DI __half2 amax4(__half2 h, const uint32_t* v) {
  h = __hmax2_nan(__hmax2_nan(h, __habs2(*(const __half2*)&v[0])), __habs2(*(const __half2*)&v[1]));
  return __hmax2_nan(__hmax2_nan(h, __habs2(*(const __half2*)&v[2])), __habs2(*(const __half2*)&v[3]));
}
DI uint32_t wexp(__half2 h) { const uint32_t u = *(const uint32_t*)&h; return __reduce_max_sync(0xffffffffu, max((u >> 16) & 0x7fffu, u & 0x7fffu)) >> 7; }
DI float max10(const float* a) {
  return fmaxf(fmaxf(fmaxf(fmaxf(a[0], a[1]), fmaxf(a[2], a[3])), fmaxf(fmaxf(a[4], a[5]), fmaxf(a[6], a[7]))), fmaxf(a[8], a[9]));
}
DI float quad_max(float m) {
  return fmaxf(fmaxf(m, __shfl_xor_sync(0xffffffffu, m, 1)), fmaxf(__shfl_xor_sync(0xffffffffu, m, 2), __shfl_xor_sync(0xffffffffu, m, 3)));
}
DI float warp_sum(float v) {
#pragma unroll
  for (int o = 16; o; o >>= 1) v += __shfl_xor_sync(0xffffffffu, v, o);
  return v;
}

constexpr int SM_WO3 = 0;
constexpr int SM_X = 16384;
constexpr int XT = 36864;
constexpr int SM_EXP = 126976;
constexpr int SEGB = 10240;
constexpr int SM_BLK = SM_EXP + 8192;
constexpr int SM_VC = SM_BLK + 4 * SEGB;
constexpr int SM_PART = SM_VC + 16384;
constexpr int SM_QM = SM_PART + 4096;
constexpr int SM_E = SM_QM + 1024;
constexpr int SM_VM = SM_E + 1536;
constexpr int SM_OB = SM_VM + 2048;
constexpr int SM_FB = SM_OB + 2048;
constexpr int SM_STAGE = SM_X + XT;
constexpr int SM_MISC = 210944;
constexpr int SM_WOST = 212992;
constexpr int SM_MEM = SM_WOST;
constexpr int SM_MAX = SM_MEM + 11264;
#define MEM_BLK(q) ((q) / 3 * 4096 + (q) % 3 * 1024)
constexpr int SM_TOTAL = 229376;
constexpr int MB_W = SM_MISC;
constexpr int MB_WO = SM_MISC + 24;
constexpr int MB_WO3 = SM_MISC + 32;
constexpr int MB_X = SM_MISC + 40;
constexpr int MB_S = SM_MISC + 64;
constexpr int MB_F = SM_MISC + 72;
constexpr int MB_VX = SM_MISC + 80;
constexpr int SC_FPAR = SM_MISC + 136;
constexpr int SC_DEAD = SM_MISC + 96;
constexpr int SC_UNSC = SM_MISC + 112;
constexpr int SC_EPOCH = SM_MISC + 128;
constexpr int SC_EXPW = SM_MISC + 132;
constexpr int SC_ONES = SM_MISC + 144;
constexpr int SC_SS = SM_MISC + 160;
constexpr int SC_LAT = SM_MISC + 224;
constexpr int MB_T = SM_MISC + 232;
constexpr int T_SX = SM_X + XT;
constexpr int T_OB = SM_X + 2 * XT;
constexpr int T_WA = T_OB + 16384;
constexpr int T_OA = T_WA + 9216;
constexpr int T_G = T_OA + 4096;
constexpr int T_P = T_G + 512;
constexpr int T_UN = T_G + 256;
constexpr int T_RED = 131072;
constexpr int SC_XMAX = SM_MISC + 256;
constexpr int SC_PROF = 229376;

constexpr float SM_SCALE = 0.08838834764831845f;
constexpr float LOG2E = 1.4426950408889634f;
constexpr float E_LIM = 20.f;

template <bool B> struct BoolC { static constexpr bool value = B; };
struct RMaps { CUtensorMap x, wq, wk, wv, wo, woa, oa; unsigned char* red; bf16* out; uint32_t poll; };

DI uint32_t latest_hint(uint32_t h, uint32_t d, int s) {
  const uint32_t x = (((h | 0xc0c0c0c0u) - ((d >> 5) & 63) * 0x01010101u) & 0x3f3f3f3fu) | ((h ^ (((s >> 2) + 1) & 3) * 0x40404040u) & 0xc0c0c0c0u);
  const uint32_t y = __vmaxu2(x & 0x00ff00ffu, (x >> 8) & 0x00ff00ffu);
  return __reduce_max_sync(0xffffffffu, max(y & 0xffffu, y >> 16));
}
DI uint32_t near_half(uint32_t sb) {
  uint32_t a, b; lds64(sb + SC_LAT, a, b);
  return a > b;
}

template <int RT, int K0, int K1, bool D32 = false, int BAR = 0, int KB = 18>
DI void xproj(float* acc, const uint32_t (&wa)[2][18][4], uint64_t xd) {
  if (XP & 1) return;
  WG_FENCE();
#pragma unroll
  for (int k = K0; k < ((XP & 128) ? K0 + 1 : K1); k++)
  {
    uint64_t d = xd + (uint64_t)(((k >> 1) * 4096 + (k & 1) * 32) >> 4);
    if (D32) asm("mov.b64 %0, {%1, %2};" : "=l"(d) : "r"((uint32_t)xd + (((k >> 1) * 4096 + (k & 1) * 32) >> 4)), "r"((uint32_t)(xd >> 32)));
    wgmma_n32_rs(acc, wa[RT][k][0], wa[RT][k][1], wa[RT][k][2], wa[RT][k][3], d, k != 0);
    if (BAR && k == KB - 1 && KB < 18) bar_arrive(BAR, 256);
  }
  WG_COMMIT();
}

DI void seg_store(int seg, uint32_t sb, uint32_t off, uint32_t bytes) {
  asm volatile("cp.async.bulk.global.shared::cta.bulk_group [%0], [%1], %2;"
               :: "l"(g_seg + ((size_t)(seg % NRING) * 96 + blockIdx.x) * SEGB + off), "r"(sb + SM_BLK + (seg & 3) * SEGB + off), "r"(bytes) : "memory");
  asm volatile("cp.async.bulk.commit_group;" ::: "memory");
}
DI void seg_publish(int seg) {
  asm volatile("cp.async.bulk.wait_group 0;" ::: "memory");
  asm volatile("red.relaxed.gpu.global.add.u32 [%0], 1;" :: "l"(&g_scnt[(seg * 32 + blockIdx.x / 3) * 8]) : "memory");
  SSTAMP(10, seg);
}

#define NAP 64
DI uint32_t movm(uint32_t x) { uint32_t r; asm volatile("movmatrix.sync.aligned.m8n8.trans.b16 %0, %1;" : "=r"(r) : "r"(x)); return r; }
DI bool wait_count(const unsigned* p, unsigned target, bool nap = true) {
  int n = 0;
  unsigned v;
  while (true) {
    asm volatile("ld.acquire.gpu.global.b32 %0, [%1];" : "=r"(v) : "l"(p) : "memory");
    if ((int)(v - target) >= 0 || ++n > SPIN_LIMIT) break;
    if (nap) __nanosleep(NAP);
  }
  return n;
}
#define PACE 1200
#define PACE2 600
#define PACE3 (3 * PACE)
#define PORD 0
DI void load_weights(uint32_t sb, const RMaps& tm, uint32_t rank, int c) {
  const int h = blockIdx.x / 3;
  if (c < 3) {
    mbar_expect(sb + MB_W + 8 * c, 49152);
    tma_load(sb + SM_STAGE + c * 49152, rank < 2 ? &tm.wk : &tm.wv, h * DH + (rank == 1 ? 64 : 0), c * 192, sb + MB_W + 8 * c);
    tma_load(sb + SM_STAGE + c * 49152 + 24576, rank < 2 ? &tm.wq : &tm.wv, h * DH + (rank == 0 ? 0 : 64), c * 192, sb + MB_W + 8 * c);
  } else {
    tma_prefetch(&tm.wo, rank * 192, h * DH);
    mbar_expect(sb + MB_WO, 16384);
    mbar_expect(sb + MB_WO3, 32768);
    tma_load(sb + SM_WOST, &tm.wo, rank * 192 + 64, h * DH, sb + MB_WO3);
    tma_load(sb + SM_WO3, &tm.wo, rank * 192 + 128, h * DH, sb + MB_WO3);
  }
}

DI void tail_attention(const uint32_t sb, const uint32_t rank, const int w, const int lane, const int sg, const int bar) {
  const int m = lane >> 3, g = lane >> 2, t = lane & 3;
  const uint32_t l16 = sb + lane * 16, src = l16 + T_SX + sg * 10240 + w * 1280;
  if (rank < 2) {
    const uint32_t base = l16 + SM_BLK + (2 + sg) * SEGB, dst = src + rank * 5120;
    uint32_t qb[2][4];
    ldsm4t(qb[0], base + w * 1024); ldsm4t(qb[1], base + w * 1024 + 512);
#pragma unroll
    for (int j = 0; j < 3; j++) {
      uint32_t kb[4][4];
      float c[4][4];
      const uint32_t ka = base + 4096 + j * 2048 + (m & 1) * (j == 2 ? 128 : 896) - (m >> 1) * 128;
#pragma unroll
      for (int k = 0; k < 4; k += j == 2 ? 2 : 1) ldsm4t(kb[k], ka + k * 256);
      mma16816z(c[0], kb[0], qb[0][0], qb[0][1]); mma16816z(c[1], kb[j == 2 ? 0 : 1], qb[0][2], qb[0][3]);
      mma16816z(c[2], kb[2], qb[1][0], qb[1][1]); mma16816z(c[3], kb[j == 2 ? 2 : 3], qb[1][2], qb[1][3]);
      uint32_t r[4];
#pragma unroll
      for (int i = 0; i < (j == 2 ? 2 : 4); i++) r[i] = __float_as_uint((c[0][i] + c[1][j == 2 ? i + 2 : i]) + (c[2][i] + c[3][j == 2 ? i + 2 : i]));
#pragma unroll
      for (int d = 0; d < 2; d++) {
        const uint32_t to = d ? 2 : rank ^ 1, mb = mapa(sb + MB_T + 8 + 8 * sg, to);
        if (j < 2) st_async4(mapa(dst + j * 512, to), r[0], r[1], r[2], r[3], mb);
        else st_async2(mapa(dst + 1024 - lane * 8, to), r[0], r[1], mb);
      }
      if (j < 2) sts128(dst + j * 512, r[0], r[1], r[2], r[3]); else sts64(dst + 1024 - lane * 8, r[0], r[1]);
    }
  }
  TSTAMP(50 + 2 * sg);
  uint32_t vx[4][4], vm[4];
  const uint32_t va = l16 + (rank < 2 ? SM_VC + sg * 8192 : SM_BLK + (2 + sg) * SEGB) + w * 1024 + (m & 1) * 384 - (m >> 1) * 128;
#pragma unroll
  for (int i = 0; i < 4; i++) ldsm4(vx[i], va + (i & 1) * 4096 + (i >> 1) * 256);
  if (sg && rank < 2) mbar_wait(sb + MB_T, 0);
  lds128(l16 + (sg ? SM_FB : SM_VM) + w * 512, vm);
  float a[10], b[10];
  mbar_wait(sb + MB_T + 8 + 8 * sg, 0);
  TSTAMP(58 + 2 * sg);
  lds128f(src, a); lds128f(src + 512, a + 4); lds64f(src + 1024 - lane * 8, a + 8);
  lds128f(src + 5120, b); lds128f(src + 5632, b + 4); lds64f(src + 6144 - lane * 8, b + 8);
#pragma unroll
  for (int i = 0; i < 10; i++) {
    a[i] = (a[i] + b[i]) * (SM_SCALE * LOG2E);
    if (i < 8 && (i >> 1) * 8 + g > w * 8 + 2 * t + (i & 1)) a[i] = -1.0e9f * LOG2E;
  }
  float m0 = fmaxf(fmaxf(fmaxf(a[0], a[2]), fmaxf(a[4], a[6])), a[8]), m1 = fmaxf(fmaxf(fmaxf(a[1], a[3]), fmaxf(a[5], a[7])), a[9]);
#pragma unroll
  for (int o = 4; o < 32; o <<= 1) { m0 = fmaxf(m0, __shfl_xor_sync(0xffffffffu, m0, o)); m1 = fmaxf(m1, __shfl_xor_sync(0xffffffffu, m1, o)); }
#pragma unroll
  for (int i = 0; i < 10; i++) a[i] = ex2(a[i] - (i & 1 ? m1 : m0));
  float s0 = ((a[0] + a[2]) + (a[4] + a[6])) + a[8], s1 = ((a[1] + a[3]) + (a[5] + a[7])) + a[9];
#pragma unroll
  for (int o = 4; o < 32; o <<= 1) { s0 += __shfl_xor_sync(0xffffffffu, s0, o); s1 += __shfl_xor_sync(0xffffffffu, s1, o); }
  s0 = rcp(s0); s1 = rcp(s1);
#pragma unroll
  for (int i = 0; i < 5; i++) sts32(sb + T_P + sg * 2560 + w * 640 + i * 128 + lane * 4, pack_bf16(a[2 * i] * s0, a[2 * i + 1] * s1));
  mbar_wait(sb + MB_WO, 1);
  bar_sync(bar, 128);
  TSTAMP(59 + 2 * sg);
#pragma unroll
  for (int j = 0; j < 4; j++) {
    uint32_t p[5];
    float o0[4], o1[4], f[2];
    lds64f(sb + T_G + sg * 128 + j * 32 + t * 8, f);
    f[0] = 1.f - f[0]; f[1] = 1.f - f[1];
    ldsm4t(p, l16 + T_P + sg * 2560 + j * 640);
    asm volatile("ldmatrix.sync.aligned.m8n8.x1.trans.shared.b16 {%0}, [%1];" : "=r"(p[4]) : "r"(l16 + T_P + sg * 2560 + j * 640 + 512) : "memory");
    mma16816z(o0, vx[0], p[0], p[1]); mma16816z(o1, vx[1], p[0], p[1]);
    mma16816(o0, vx[2], p[2], p[3]); mma16816(o1, vx[3], p[2], p[3]);
    mma1688(o0, vm[0], vm[1], p[4]); mma1688(o1, vm[2], vm[3], p[4]);
    stsm4(l16 + T_OB + sg * 8192 + j * 2048 + w * 512, pack_bf16(o0[0] * f[0], o0[1] * f[1]), pack_bf16(o0[2] * f[0], o0[3] * f[1]),
          pack_bf16(o1[0] * f[0], o1[1] * f[1]), pack_bf16(o1[2] * f[0], o1[3] * f[1]));
  }
}

DI void proj_role(const uint32_t sb, const RMaps& tm, const uint32_t rank, const int wg, const int w, const int lane) {
  const bool qk = rank < 2;
  uint32_t wa[2][18][4];
  {
    const int rr = (lane & 7) + ((lane >> 4) << 3);
    const uint32_t col = ((2 * w + ((lane >> 3) & 1)) ^ (lane & 7)) << 4;
    float ss = 0.f;
#pragma unroll
    for (int c = 0; c < 3; c++) {
      mbar_wait(sb + MB_W + 8 * c, 0);
      if (threadIdx.x == 0) SSTAMP(11, c);
#pragma unroll
      for (int rt = 0; rt < 2; rt++)
#pragma unroll
        for (int k = 0; k < 6; k++)
          ldsm4t(wa[rt][c * 6 + k], sb + SM_STAGE + c * 49152 + (rt ^ wg) * 24576 + (64 * (k >> 1) + 32 * wg + 16 * (k & 1) + rr) * 128 + col);
      if (c < 2) {
        fence_async();
        bar_sync(3, 256);
        if (threadIdx.x == 0) {
          if (c == 0) tma_load3(sb + SM_X + XT, &tm.x, 32, sb + MB_X + 8);
          else { tma_load(sb + SM_X + 2 * XT, &tm.wo, rank * 192, (blockIdx.x / 3) * DH, sb + MB_WO); SSTAMP(11, 11); }
        }
        __syncwarp();
      }
      uint32_t q[4] = {0, 0, 0, 0};
#pragma unroll
      for (int rt = 0; rt < 2; rt++)
#pragma unroll
        for (int k = 0; k < 6; k++)
#pragma unroll
          for (int i = 0; i < 4; i++) sq_acc(q[i], wa[rt][c * 6 + k][i]);
#pragma unroll
      for (int i = 0; i < 4; i++) ss += bf_lo(q[i]) + bf_hi(q[i]);
    }
    ss = warp_sum(ss);
    fence_async();
    cluster_arrive();
    if (lane == 0) sts32(sb + SC_SS + 4 * (wg * 4 + w), qk ? 0 : __float_as_uint(ss));
    bar_arrive(11, 384);
  }
  STAMP(1);
  MSTAMP(0);
  mbar_wait(sb + MB_X, 0);
  STAMP(2);

  uint32_t t16 = sb + (w * 32 + lane) * 16;
  uint32_t mem_a = sb + SM_MEM + wg * 512 + lane * 16;
  uint32_t fin_a = sb + (lane & 7) * 16 + SM_BLK + (qk ? (wg ^ 1) * 4096 + w * 256 + (lane & 8) * 16 + (lane & 16) * 64
                                              : wg * 4096 + w * 1024 + (lane & 8) * 64 + (lane & 16) * 8);
  PIN(t16); PIN(mem_a); PIN(fin_a);
  const uint32_t fence_reg = mem_a;
  const uint32_t fin2 = qk ? 2048 : 256;
  float acc[16];
  const uint64_t xd0 = make_desc(sb + SM_X + wg * 64, 16, 1024, 1);
  auto do_export = [&]() {
    WG_WAIT(0);
    uint32_t q[8];
#pragma unroll
    for (int j = 0; j < 8; j++) q[j] = pack_bf16(acc[2 * j], acc[2 * j + 1]);
    sts128(t16 + SM_EXP + wg * 4096, q[0], q[1], q[2], q[3]);
    sts128(t16 + SM_EXP + wg * 4096 + 2048, q[4], q[5], q[6], q[7]);
    if (RET) asm volatile("{\n.reg .pred p;\nsetp.eq.u32 p, %2, 0;\n@p add.u32 %0, %0, 1;\n@p add.u32 %1, %1, 1;\nsetp.eq.and.u32 p, %0, %1, p;\n@p exit;\n}"
                          : "+r"(q[3]), "+r"(q[7]) : "r"(t16) : "memory");
  };
  uint32_t o[8];
  auto import = [&]() { lds128(t16 + SM_EXP + (wg ^ 1) * 4096, o); lds128(t16 + SM_EXP + (wg ^ 1) * 4096 + 2048, o + 4); };
  auto finish = [&](int seg) {
    const uint32_t a = fin_a + (seg & 3) * SEGB;
    WG_WAIT(0);
#pragma unroll
    for (int i = 0; i < 8; i++) o[i] = FIN16 ? add_bf16(pack_bf16(acc[2 * i], acc[2 * i + 1]), o[i]) : pack_bf16(acc[2 * i] + bf_lo(o[i]), acc[2 * i + 1] + bf_hi(o[i]));
    stsm4(a, o[0], o[1], o[2], o[3]);
    stsm4(a + fin2, o[4], o[5], o[6], o[7]);
  };
  auto send_v = [&](int seg, int dst) {
    fence_async();
    if (seg < NSEG && !(XP & 2) && elect_one())
      bulk_s2s(mapa(sb + SM_VC + (seg & 1) * 8192, dst), sb + SM_BLK + (seg & 3) * SEGB, 8192, mapa(sb + MB_VX + (seg & 1) * 8, dst));
    __syncwarp();
  };
  auto wait_v = [&](int seg) {
    if (seg < NSEG && !(XP & 2)) {
      mbar_wait(sb + MB_VX + (seg & 1) * 8, (seg >> 1) & 1);
      if (elect_one()) mbar_expect(sb + MB_VX + (seg & 1) * 8, 8192);
      __syncwarp();
    }
  };
  bar_sync(3, 256);
  xproj<1, 0, 18>(acc, wa, xd0);
  do_export();
  SCHED_FENCE(11);
  xproj<0, 0, 18>(acc, wa, xd0);
  bar_sync(3, 256);
  if (threadIdx.x == 0) SSTAMP(11, 12);
  MSTAMP(1);
  cluster_wait();
  if (threadIdx.x == 0) SSTAMP(11, 13);
  mbar_wait(sb + MB_X + 8, 0);
  import();
  finish(0);
  SCHED_FENCE(12);
  bar_sync(3, 256);
  uint64_t dA = xd0 + (XT >> 4);
  xproj<1, 0, 18>(acc, wa, dA);
  if (!qk && wg == 0 && w < 2) send_v(0, w);
  do_export();
  if (qk && wg == 0 && w == 0) wait_v(0);
  bar_arrive(13, 384);
  if (!qk) {
    SCHED_FENCE(15);
    xproj<0, 0, 18>(acc, wa, dA);
    if (threadIdx.x == 0 && !(XP & 8)) { mbar_expect(sb + MB_X, XT); tma_load3(sb + SM_X, &tm.x, 96, sb + MB_X); }
    bar_sync(3, 256);
    mbar_wait(sb + MB_X + 16, 0);
    import();
    finish(1);
    SCHED_FENCE(16);
    bar_sync(3, 256);
    dA += XT >> 4;
    xproj<1, 0, 18>(acc, wa, dA);
    if (wg == 0 && ((w == 0 && VS0) || (w == 1 && VS1))) send_v(1, w);
    do_export();
  }
  if (threadIdx.x == 0) SSTAMP(11, 14);
  MSTAMP(2);
  bar_sync(0, 384);
  const int ro = __shfl_sync(0xffffffffu, near_half(sb) ^ wg, 0);
  STAMP(5);
  const uint32_t always = __shfl_sync(0xffffffffu, lds32(sb + SC_DEAD + 12), 0);
  const int ah = qk ? 1 : 2;
  int b2 = qk ? 2 : 0;
  int s = 0;
  uint32_t hint_lo = (uint32_t)(uint64_t)tm.red + HINT_OFF + blockIdx.x + (lane & 1) * 4096 + (lane >> 1) * 16384;
  PIN(hint_lo);
  auto post_hint = [&]() {
    asm volatile("{\n.reg .pred p;\n.reg .b64 a;\n.reg .u32 t;\nsetp.lt.u32 p, %0, %1;\nmov.b64 a, {%2, %3};\nmov.u32 t, %%globaltimer_lo;\n"
                 "bfe.u32 t, t, 5, 6;\nor.b32 t, t, %4;\n@p st.relaxed.gpu.global.u8 [a], t;\n}"
                 :: "r"(t16), "r"(sb + 128), "r"(hint_lo + RED_SLOT(s)), "r"((uint32_t)((uint64_t)tm.red >> 32)), "r"(((s >> 2) + 1) << 6) : "memory");
  };
  auto memproj = [&](auto second, int id, float u0, float u1, float* r) {
    constexpr bool R1 = decltype(second)::value;
    uint32_t b[NUP][4], b0[4];
    SCHED_FENCE(id);
    bar_sync(R1 ? 2 : 1, 256);
    PROF(0);
    ldsm4t(b0, mem_a);
#pragma unroll
    for (int q = 0; q < NUP; q++) {
      if (R1 && q == 2) {
        bar_sync(11, 256);
        SCHED_FENCE(id + 1);
      }
      ldsm4t(b[q], mem_a + MEM_BLK(q + 1));
    }
    mma16816z(&acc[0], wa[0][0], b0[0], b0[1]);
    mma16816z(&acc[4], wa[1][0], b0[0], b0[1]);
    mma16816z(&acc[8], wa[0][1], b0[2], b0[3]);
    mma16816z(&acc[12], wa[1][1], b0[2], b0[3]);
#pragma unroll
    for (int q = 1; q < 9; q++) {
      uint32_t* const c = b[(q - 1) % NUP];
      mma16816(&acc[0], wa[0][2 * q], c[0], c[1]);
      mma16816(&acc[4], wa[1][2 * q], c[0], c[1]);
      mma16816(&acc[8], wa[0][2 * q + 1], c[2], c[3]);
      mma16816(&acc[12], wa[1][2 * q + 1], c[2], c[3]);
      if (R1 && q + NUP == B3Q) bar_sync(3, 256);
      if (q + NUP < 9) ldsm4t_in(c, mem_a + MEM_BLK(q + NUP), always);
      else if (R1 && q + NUP < 11) lds128_in(c, t16 + SM_PART + (10 - q - NUP) * 2048, always);
      else if (!R1 && GATE && q == GATE) { bar_arrive(11, 256); lds128_in(c, sb + SC_DEAD, always); u0 = u1 = __uint_as_float(c[3]); }
    }
#pragma unroll
    for (int i = 0; i < 8; i++) {
      const float u = i < 4 ? u0 : u1;
      r[i] = R1 ? fmaf(acc[8 + i], u, (acc[i] + __uint_as_float(b[(8 + i / 4) % NUP][i & 3])) * u) : (GATE ? fmaf(acc[i], u, acc[8 + i]) : acc[i] + acc[8 + i]);
    }
  };
  if (ro == 0) {
    auto set_scale = [&]() {
      uint32_t m[8];
      lds128(t16 + SM_MAX - 512, m); lds128(t16 + SM_MAX, m + 4);
      const int em = (wexp(amax4(amax4(*(const __half2*)&m[0], m), m + 4)) >> 3) + (int)(lds32(sb + SC_UNSC + (s & 1) * 8) >> 23) - 15;
      const int ex = max(s ? em : 0, (int)lds32(sb + SC_XMAX + 4 * s)) - 127 + (int)lds32(sb + SC_EXPW);
      sts32(sb + SC_UNSC + (~s & 1) * 8, (127 + min(max(ex, -120), 120)) << 23);
    };
#pragma unroll 1
    while (true) {
      if (s == 8) STAMP(6);
      float r[8];
      memproj(BoolC<false>(), 30, 0.f, 0.f, r);
      sts128(t16 + SM_PART, __float_as_uint(r[0]), __float_as_uint(r[1]), __float_as_uint(r[2]), __float_as_uint(r[3]));
      sts128(t16 + SM_PART + 2048, __float_as_uint(r[4]), __float_as_uint(r[5]), __float_as_uint(r[6]), __float_as_uint(r[7]));
      bar_arrive(3, 256);
      PROF(1);
      bar_sync(9, 256);
      if (s == NSEG - 1) break;
      post_hint();
      if (w == 1) {
        set_scale();
        __syncwarp();
        if (elect_one()) mbar_arrive(sb + MB_S);
      }
      SCHED_FENCE(9);
      bar_sync(5, qk ? N5 : 256);
      PROF(2);
      import();
      xproj<0, 0, NII, (DD & 1) != 0>(acc, wa, dA);
      if (NII < 18) {
        if (qk) bar_sync(7, 384);
        xproj<0, NII, 18>(acc, wa, dA);
        if (!qk) bar_sync(7, 384);
      } else {
        if (F10) WG_WAIT(0);
        bar_sync(10, 256);
        if (F10) SCHED_FENCE(17);
      }
      dA += (int64_t)(b2 ? XT >> 4 : -(XT >> 3));
      finish(s + ah);
      if (qk || !VLATE(w)) bar_arrive(13, 384);
      PROF(6);
      SCHED_FENCE(14);
      bar_sync(12, 256);
      PROF(7);
      xproj<1, 0, 18, (DD & 2) != 0, 14, N14>(acc, wa, dA);
      if (N14 == 18) bar_arrive(14, 256);
      b2 = b2 == 2 ? 0 : b2 + 1;
      s++;
      if (!qk && VLATE(w)) { bar_sync(13, 384); send_v(s + 1, w); }
      PROFP(8);
      do_export();
      s--; RSTAMP(6); s++;
      PROFP(3);
    }
    if (!qk) bar_arrive(5, 256);
    if (w == 0 && elect_one()) {
      const uint32_t h18 = blockIdx.x / 3 * 18;
      mbar_expect(sb + MB_WO, 9216 + 4096 + 256);
      asm volatile("cp.async.bulk.shared::cluster.global.mbarrier::complete_tx::bytes [%0], [%1], 256, [%2];"
                   :: "r"(sb + T_G), "l"(g_gate + NAUXSEG * 32), "r"(sb + MB_WO) : "memory");
      tma_load(sb + T_OA, &tm.oa, 4096 + (h18 & ~7), NAUXSEG * 32, sb + MB_WO);
#pragma unroll 1
      for (int j = 0; j < 3; j++) tma_load(sb + T_WA + j * 3072, &tm.woa, rank * 192 + j * 64, h18, sb + MB_WO);
    }
    if (w == 1) {
      set_scale();
      __syncwarp();
      const int ea = (int)ldg_relaxed32(&g_amax[0]) + (int)ldg_relaxed32(&g_amax[16]) - 254 + 2 + 10 - 15;
      sts32(sb + T_UN + (lane & 1) * 4, (128 + max(min(ea, 120), (int)(lds32(sb + SC_UNSC + 8 - (lane & 1) * 8) >> 23) - 127)) << 23);
    }
    bar_arrive(8, 256);
  } else {
    uint32_t r0;
    float un;
    auto prepare = [&]() {
      un = __uint_as_float(lds32(sb + SC_UNSC + (s & 1) * 8));
      r0 = qk ? (t16 & ~256u) - w * 256 + (((t16 >> 8) ^ wg) & 1 ? SM_QM : SM_BLK + 8192 + (s & 3) * SEGB) : mapa(t16 + (s < NSEG - 1 ? SM_VM : SM_FB), 0);
      PIN(r0); PIN(un);
    };
    auto mem_out = [&](int off, uint32_t lo, uint32_t hi) {
      unsigned char* const d = g_seg + ((size_t)(s % NRING) * 96 + blockIdx.x) * SEGB + 8192 + off + w * 256 + ((t16 >> 2) & 124);
      if (!(XP & 4)) { stg_relaxed32(d, lo); stg_relaxed32(d + 128, hi); }
    };
    prepare();
#pragma unroll 1
    while (true) {
      if (s == 8) STAMP(6);
      float r[8];
      if (qk) {
        const float u0 = wg ? un * (SM_SCALE * LOG2E) : un, u1 = wg ? un : un * (SM_SCALE * LOG2E);
        memproj(BoolC<true>(), 32, u0, u1, r);
        const uint32_t p0 = pack_bf16(r[0], r[1]), p1 = pack_bf16(r[2], r[3]), p2 = pack_bf16(r[4], r[5]), p3 = pack_bf16(r[6], r[7]);
        stsm4(r0, p0, p1, p2, p3);
        bar_arrive(4, 256);
        if (EXM) { SCHED_FENCE(18); mem_out(0, wg ? p2 : p0, wg ? p3 : p1); }
      } else {
        const uint32_t mb = sb + (s < NSEG - 1 ? MB_S : MB_T), r1 = r0 + (1 << 24);
        memproj(BoolC<true>(), 34, un, un, r);
        const uint32_t p0 = pack_bf16(r[0], r[1]), p1 = pack_bf16(r[2], r[3]), p2 = pack_bf16(r[4], r[5]), p3 = pack_bf16(r[6], r[7]);
        const uint32_t v0 = wg ? p2 : p0, v1 = wg ? p3 : p1, v2 = wg ? p0 : p2, v3 = wg ? p1 : p3;
        st_async4(r0, v0, v1, v2, v3, mapa(mb, 0));
        st_async4(r1, v0, v1, v2, v3, mapa(mb, 1));
        bar_arrive(5, 256);
        sts128(r0 + (2 << 24), v0, v1, v2, v3);
        stsm4((t16 & ~256u) - w * 256 + SM_BLK + 8192 + (s & 3) * SEGB + (((t16 >> 8) ^ wg) & 1) * 1024, p0, p1, p2, p3);
        __syncwarp();
        if (elect_one()) mbar_arrive(sb + MB_S);
        __syncwarp();
        if (EXM) { SCHED_FENCE(19); mem_out(0, v0, v1); mem_out(1024, v2, v3); }
      }
      if (s == NSEG - 1) break;
      if (!qk && !EXM) bar_arrive(15, 160);
      PROF(1);
      auto rearm = [&]() { mbar_wait(sb + MB_S, s & 1); if (elect_one()) mbar_expect(sb + MB_S, qk ? 640 + 2048 : 1280); __syncwarp(); };
      if (w == 1) {
        if ((t16 & 384) == 0) stg_relaxed(tm.red + (RED_SLOT(s + 2) + RED_LINE(blockIdx.x)) + (t16 & 112), 0, 0, 0, 0);
      } else if (w == 0) {
        const int tn = s + ah + 1;
        if (RFW) mbar_wait(sb + MB_S, s & 1);
        if (tn + 1 < NSEG && !(XP & 8) && elect_one()) {
          const int b0 = b2 == 2 ? 0 : b2 + 1;
          mbar_expect(sb + MB_X + 8 * b0, XT);
          tma_load3(sb + SM_X + b0 * XT, &tm.x, (tn + 1) * 32, sb + MB_X + 8 * b0);
        }
        if (tn < NSEG && (!(XP & 8) || tn < 3)) mbar_wait(sb + MB_X + 8 * b2, (tn / 3) & 1);
      } else if (w == 2) {
        if (!qk) { if (VS0 == 0) send_v(s + 1, 0); if (VS1 == 0) send_v(s + 1, 1); }
      } else if (qk || !NIC) {
        rearm();
      }
      __syncwarp();
      import();
      PROF(4);
      SCHED_FENCE(10);
      if (NIC) {
        if (qk) bar_sync(7, NII < 18 ? 384 : 256);
        xproj<0, 0, NIC>(acc, wa, dA);
        if (!qk) { if (w == 3) rearm(); bar_sync(7, NII < 18 ? 384 : 256); }
      } else {
        bar_sync(7, NII < 18 ? 384 : 256);
      }
      xproj<0, NIC, 18, (DD & 4) != 0, 12, N12>(acc, wa, dA);
      if (N12 == 18) bar_arrive(12, 256);
      dA += (int64_t)(b2 ? XT >> 4 : -(XT >> 3));
      finish(s + ah);
      if (qk && w == 0) wait_v(s + 1);
      bar_arrive(13, 384);
      PROF(6);
      SCHED_FENCE(13);
      bar_sync(14, 256);
      PROF(7);
      xproj<1, 0, 18, (DD & 8) != 0>(acc, wa, dA);
      b2 = b2 == 2 ? 0 : b2 + 1;
      s++;
      if (HOIST) prepare();
      PROFP(8);
      do_export();
      if (!HOIST) prepare();
      s--; RSTAMP(7); s++;
      PROFP(3);
    }
    TSTAMP(2);
    bar_sync(3, 128);
    tail_attention(sb, rank, w, lane, 1, 3);
    bar_arrive(0, 256);
  }
  STAMP(3);
  if (CSY) cluster_sync();
  STAMP(4);
}

DI void attn_role(const uint32_t sb, unsigned char* smem_raw, const RMaps& tm, const uint32_t RANK, const bf16* __restrict__ x, const bf16* __restrict__ mem0,
                  const int w, const int lane) {
  const int t2 = w * 32 + lane;
  uint32_t wo[8][4], w1[8][4];
  const uint32_t wo_lane = sb + ((lane & 7) + ((lane >> 4) << 3)) * 128 + (((w + 4 * ((lane >> 3) & 1)) ^ (lane & 7)) << 4);
  unsigned char* const g_red = tm.red;
  {
    const uint32_t t0 = gtime();
    const uint32_t tag = *(volatile unsigned*)&g_epoch + 1;
    if (w == 0) {
      stg_relaxed(g_red + RED_SLOT(t2 >> 3) + RED_LINE(blockIdx.x) + (t2 & 7) * 16, 0, 0, 0, 0);
      stg_relaxed(g_red + T_RED + blockIdx.x * 1024 + t2 * 16, 0, 0, 0, 0);
      stg_relaxed(g_red + T_RED + blockIdx.x * 1024 + 512 + t2 * 16, 0, 0, 0, 0);
      asm volatile("st.relaxed.gpu.global.u8 [%0], 0;" :: "l"(g_red + RED_SLOT(t2) + HINT_OFF + (t2 & 4) * 1024 + (t2 >> 3) * 16384 + blockIdx.x) : "memory");
    }
    bar_sync(0, 384);
    cluster_arrive();
    if (PACE && w == 3) {
#pragma unroll 1
      for (int c = 1; c < 4; c++) {
        wait_until(t0 + (c == 3 ? PACE3 : c * (RANK < 2 ? PACE : PACE2)));
        if (elect_one()) load_weights(sb, tm, RANK, PORD ? (c == 1 ? 3 : c - 1) : c);
        __syncwarp();
      }
    }
    uint4 xv[18];
    uint32_t mv[20];
#pragma unroll
    for (int i = 0; i < 20; i++) mv[i] = i < 18 ? ((const uint32_t*)mem0)[(lane >> 2) * (DM / 2) + (w * 18 + i) * 4 + (lane & 3)] : 0;
#pragma unroll
    for (int i = 0; i < 18; i++) xv[i] = blockIdx.x < NSEG ? ((const uint4*)(x + blockIdx.x * 32 * DM))[t2 + 128 * i] : make_uint4(0, 0, 0, 0);
    __half2 hx = __float2half2_rn(0.f);
#pragma unroll
    for (int i = 0; i < 18; i++) hx = amax4(hx, &xv[i].x);
    if (blockIdx.x == 0)
#pragma unroll
      for (int i = 0; i < 5; i++) hx = amax4(hx, &mv[4 * i]);
    sts32(sb + SC_SS + 4 * (12 + w), wexp(hx));
    if (t2 == 0) { sts32(sb + SC_EPOCH, (tag - 1) * NSEG + 2 - NRING); sts32(sb + SC_UNSC, __float_as_uint(1.f)); sts128(sb + SC_DEAD, 0, 0, 0, 0x3f800000u); sts64(sb + SC_FPAR, 0, 0); sts128(sb + SC_ONES, 0x3f803f80u, 0x3f803f80u, 0x3f803f80u, 0x3f803f80u); }
    WSTAMP(27);
    if (w == 0) __threadfence();
    uint32_t q[8] = {0, 0, 0, 0, 0, 0, 0, 0};
    mbar_wait(sb + MB_WO3, 0);
    if (t2 == 0) SSTAMP(11, 3);
    MSTAMP(3);
#pragma unroll
    for (int k = 0; k < 8; k++) {
      ldsm4t(wo[k], wo_lane + SM_WO3 + k * 2048); ldsm4t(w1[k], wo_lane + SM_WOST + k * 2048);
#pragma unroll
      for (int i = 0; i < 4; i++) { sq_acc(q[i], wo[k][i]); sq_acc(q[i], w1[k][i]); }
    }
    bar_sync(6, 128);
    if (t2 == 0) SSTAMP(11, 7);
#pragma unroll
    for (int k = 0; k < 8; k++) sts128(sb + SM_WO3 + t2 * 16 + k * 2048, wo[k][0], wo[k][1], wo[k][2], wo[k][3]);
#pragma unroll
    for (int i = 0; i < 5; i++) {
      const int j = w * 18 + 4 * i + (lane >> 3), c = i < 4 || lane < 16 ? j * 8 + j / 24 * 64 : 192;
      stsm4t(sb + SM_MEM + (c + (lane & 7)) * 16, mv[4 * i], mv[4 * i + 1], mv[4 * i + 2], mv[4 * i + 3]);
    }
    bar_arrive(1, 256); bar_arrive(2, 256); bar_arrive(9, 256);
    if (t2 == 0) SSTAMP(11, 8);
    mbar_wait(sb + MB_WO, 0);
    if (t2 == 0) SSTAMP(11, 4);
#pragma unroll
    for (int k = 0; k < 8; k++) ldsm4t(wo[k], wo_lane + SM_X + 2 * XT + k * 2048);
    fence_async();
    bar_sync(6, 128);
    if (t2 == 32) tma_load3(sb + SM_X + 2 * XT, &tm.x, 64, sb + MB_X + 16);
    __syncwarp();
#pragma unroll
    for (int k = 0; k < 8; k++)
#pragma unroll
      for (int i = 0; i < 4; i++) sq_acc(q[4 + i], wo[k][i]);
    float ss = 0.f;
#pragma unroll
    for (int i = 0; i < 8; i++) ss += bf_lo(q[i]) + bf_hi(q[i]);
    ss = warp_sum(ss);
    if (lane == 0) sts32(sb + SC_SS + 4 * (8 + w), __float_as_uint(ss));
    if (t2 == 0) SSTAMP(11, 9);
    bar_sync(11, 384);
    if (t2 == 0) SSTAMP(11, 10);
    if (t2 == 0) {
      float a[16];
#pragma unroll
      for (int i = 0; i < 4; i++) lds128f(sb + SC_SS + 16 * i, &a[4 * i]);
      stg_relaxed(&g_stats[blockIdx.x * 2], __float_as_uint(((a[0] + a[1]) + (a[2] + a[3])) + ((a[4] + a[5]) + (a[6] + a[7]))),
                  __float_as_uint((a[8] + a[9]) + (a[10] + a[11])),
                  max(max(__float_as_uint(a[12]), __float_as_uint(a[13])), max(__float_as_uint(a[14]), __float_as_uint(a[15]))), tag);
    }
    __syncwarp();
    WSTAMP(24);
    MSTAMP(4);
    cluster_wait();
    if (w == 0) {
      uint4 v[3];
      int n = 0;
      while (true) {
#pragma unroll
        for (int i = 0; i < 3; i++) v[i] = ldg_relaxed(&g_stats[(i * 32 + lane) * 2]);
        if (__all_sync(0xffffffffu, v[0].w == tag && v[1].w == tag && v[2].w == tag) || ++n > SPIN_LIMIT) break;
        __nanosleep(100);
      }
      WSTAMP(25);
      MSTAMP(5);
      const float sv = warp_sum(__uint_as_float(v[0].x) + __uint_as_float(v[1].x) + __uint_as_float(v[2].x));
      const float so = warp_sum(__uint_as_float(v[0].y) + __uint_as_float(v[1].y) + __uint_as_float(v[2].y));
      const int expW = ((int)(__float_as_uint(sv) >> 23) + (int)(__float_as_uint(so) >> 23) - 254 + 2 + 10 + 1) >> 1;
      sts32(sb + SC_XMAX + 4 * lane, v[0].z); sts32(sb + SC_XMAX + 128 + 4 * lane, v[1].z);
      sts32(sb + SC_EXPW, expW + 1 - 15);
      if (blockIdx.x == 0 && lane == 0) *(volatile unsigned*)&g_epoch = tag;
      sts32(sb + SC_FPAR + 4, 1);
    } else if (w < 3) {
      const uint32_t u = blockIdx.x >> 4;
      unsigned char* const z = g_red + 98304 + (blockIdx.x & 15) * 128 + (u & 1) * 2048 + (u & 6) * 4096 + (((u >> 1) ^ w) & 1) * 4096 + lane * 4;
      stg_relaxed32(z, 0);
      uint32_t best = 0xffffffffu;
#pragma unroll 1
      for (int i = 0; i < 64; i++) {
        uint32_t last, dt;
        asm volatile("{\n.reg .pred p;\n.reg .u32 c, v;\nld.volatile.shared.u32 %0, [%3];\nmov.u32 c, %%clock;\n"
                     "atom.relaxed.gpu.global.exch.b32 v, [%2], 0;\nsetp.eq.u32 p, v, 0;\nmov.u32 %1, 0;\n@p mov.u32 %1, %%clock;\nsub.u32 %1, %1, c;\n}"
                     : "=r"(last), "=r"(dt) : "l"(z), "r"(sb + SC_FPAR + 4) : "memory");
        best = min(best, dt);
        if ((last || PFIX) && i >= NPROBE - 1) break;
      }
      sts32(sb + SC_LAT + (w - 1) * 4, best);
    }
    bar_sync(13, 384);
    bar_arrive(0, 384);
    WSTAMP(26);
    TSTAMP(1);
    MSTAMP(6);
  }

  const uint32_t nh = __shfl_sync(0xffffffffu, near_half(sb), 0);
  uint32_t l16 = sb + lane * 16;
  PIN(l16);
#define LV ((l16 >> 4) & 31)
#define fence_reg l16
  const uint32_t red_lo = (uint32_t)(uint64_t)g_red, red_hi = (uint32_t)((uint64_t)g_red >> 32);
  uint32_t lp;
  auto slot = [&](int s, uint32_t c, uint32_t ofs) {
    const uint32_t lo = lp | (red_lo + ((w >> 1) * 4 + (w & 1) * 2 + ((w ^ c) & 1)) * 4096 + RED_SLOT(s) + ofs);
    uint64_t a; asm("mov.b64 %0, {%1, %2};" : "=l"(a) : "r"(lo), "r"(red_hi));
    return (unsigned char*)a;
  };
  const uint32_t always = __shfl_sync(0xffffffffu, lds32(sb + SC_DEAD + 12), 0);
  const int mode0 = RANK < 2 ? w : w | 4;
  auto hint_addr = [&](int s) { return min(LV, 23u) * 4 + (red_lo + HINT_OFF + nh * 4096 + w * 16384 + RED_SLOT(s)); };
  auto load_hints = [&](uint32_t lo) {
    uint64_t a; asm("mov.b64 %0, {%1, %2};" : "=l"(a) : "r"(lo), "r"(red_hi));
    return ldg_relaxed32((const void*)a);
  };
  const uint32_t blk = RANK < 2 ? 9216 : SEGB;
  auto send_v = [&](int seg, int pos) {
    if (RANK == 2 && ((w == 0 && VS0 == pos) || (w == 1 && VS1 == pos)) && seg > 1 && seg < NSEG && !(XP & 2)) {
      if (elect_one()) {
        fence_async();
        bulk_s2s(mapa(sb + SM_VC + (seg & 1) * 8192, w), sb + SM_BLK + (seg & 3) * SEGB, 8192, mapa(sb + MB_VX + (seg & 1) * 8, w));
      }
      __syncwarp();
    }
  };
  int s = 0;
  uint32_t dl = __shfl_sync(0xffffffffu, gtime() - 768, 0);
  bool bad = false;
#pragma unroll 1
  while (true) {
    const uint32_t par = s & 1;
    uint32_t vx[4][4], oc[4], hints;
    if (HP == 2) { hints = hint_addr(s); PIN(hints); }
    auto load_vx = [&]() {
      const uint32_t va = l16 + (RANK < 2 ? SM_VC + par * 8192 : SM_BLK + (s & 3) * SEGB) + w * 1024 + ((LV >> 3) & 1) * 384 - (LV >> 4) * 128;
      if (WL & 4) lds128(sb + SC_ONES, oc);
#pragma unroll
      for (int i = 0; i < 4; i++) ldsm4(vx[i], va + (i & 1) * 4096 + (i >> 1) * 256);
    };
    auto retire = [&](uint32_t x) {
      asm volatile("{\n.reg .pred p;\nsetp.eq.u32 p, %0, 0;\n@p exit;\n}" :: "r"(vx[0][0] | vx[1][0] | vx[2][0] | vx[3][0] | x | ((WL & 4) ? oc[0] : 0)) : "memory");
    };
    auto scores = [&](auto memkeys, auto first, float* sc) {
      constexpr bool MK = decltype(memkeys)::value, FIRST = decltype(first)::value;
      uint32_t kb[4][4], qb[2][4];
      const uint32_t m = LV >> 3;
      uint32_t kaddr = l16 + SM_BLK + 4096 + (s & 3) * SEGB + w * 2048 + (m & 1) * (MK ? 128 : 896) - (m >> 1) * 128;
      if (MK) { PIN(kaddr); }
      else {
#pragma unroll
        for (int k = 0; k < 4; k++) ldsm4t(kb[k], kaddr + k * 256);
      }
      if (FIRST) { load_vx(); retire(MK ? kaddr : kb[0][0] | kb[1][0] | kb[2][0] | kb[3][0] | l16); bar_sync(4, 256); RSTAMP(4); PROF(4); }
      ldsm4t(qb[0], l16 + SM_QM);
      if (MK) ldsm4t(kb[0], kaddr);
      ldsm4t(qb[1], l16 + SM_QM + 512);
      if (MK) ldsm4t(kb[2], kaddr + 512);
      float c[4][4];
      mma16816z(c[0], kb[0], qb[0][0], qb[0][1]); mma16816z(c[1], kb[MK ? 0 : 1], qb[0][2], qb[0][3]);
      mma16816z(c[2], kb[2], qb[1][0], qb[1][1]); mma16816z(c[3], kb[MK ? 2 : 3], qb[1][2], qb[1][3]);
      if (FIRST && B5POS == 0) bar_arrive(5, N5);
#pragma unroll
      for (int i = 0; i < (MK ? 2 : 4); i++) sc[i] = ((c[0][i] + c[1][MK ? i + 2 : i]) + c[2][i]) + c[3][MK ? i + 2 : i];
    };
    auto send = [&](auto memkeys) {
      constexpr bool MK = decltype(memkeys)::value;
      constexpr int N = MK ? 1 : 2;
      const uint32_t sa = sb + LV * 4 + SM_E + (MK ? 1024 + RANK * 128 : RANK * 512 + w * 256);
      uint32_t ra[N][2], mb[N][2];
#pragma unroll
      for (int i = 0; i < N; i++)
#pragma unroll
        for (int j = 0; j < 2; j++) {
          ra[i][j] = mapa(sa + i * 128, j ? 2 : RANK ^ 1); mb[i][j] = mapa(sb + MB_S, j ? 2 : RANK ^ 1);
          PIN(ra[i][j]);
        }
      float sc[4];
      scores(memkeys, BoolC<true>(), sc);
      uint32_t e[N];
#pragma unroll
      for (int i = 0; i < N; i++) {
        e[i] = pack_bf16(ex2(sc[2 * i]), ex2(sc[2 * i + 1]));
        if (!(fmaxf(fabsf(sc[2 * i]), fabsf(sc[2 * i + 1])) <= E_LIM)) e[i] = 0x7fff7fffu;
        st_async1(ra[i][0], e[i], mb[i][0]);
        st_async1(ra[i][1], e[i], mb[i][1]);
      }
#pragma unroll
      for (int i = 0; i < N; i++) sts32(sa + i * 128, e[i]);
      __syncwarp();
      if (l16 == sb) mbar_arrive(sb + MB_S);
      PROF(5);
    };
    const int mode = bad ? 8 : mode0;
    if (mode < 2) {
      send(BoolC<false>());
    } else if (mode == 2) {
      send(BoolC<true>());
    } else if (mode == 8) {
      load_vx();
      retire(l16);
      const uint32_t fp = lds32(sb + SC_FPAR);
      bar_sync(6, 128);
      if (w == 0 && l16 == sb) { sts32(sb + SC_FPAR, fp ^ 1); mbar_expect(sb + MB_F, 3072); }
      if (RANK < 2 && w < 3) {
        float sc[4] = {0.f, 0.f, 0.f, 0.f};
        if (w < 2) scores(BoolC<false>(), BoolC<false>(), sc); else scores(BoolC<true>(), BoolC<false>(), sc);
#pragma unroll 1
        for (int r = 0; r < 3; r++)
          st_async4(mapa(l16 + SM_FB + RANK * 1536 + w * 512, r), __float_as_uint(sc[0]), __float_as_uint(sc[1]), __float_as_uint(sc[2]), __float_as_uint(sc[3]), mapa(sb + MB_F, r));
      }
      mbar_wait(sb + MB_F, fp);
      float a[12];
#pragma unroll
      for (int j = 0; j < 3; j++) {
        float b[4];
        lds128f(l16 + SM_FB + j * 512, a + 4 * j); lds128f(l16 + SM_FB + 1536 + j * 512, b);
#pragma unroll
        for (int i = 0; i < 4; i++) a[4 * j + i] += b[i];
      }
      float m0 = fmaxf(fmaxf(fmaxf(a[0], a[2]), fmaxf(a[4], a[6])), a[8]), m1 = fmaxf(fmaxf(fmaxf(a[1], a[3]), fmaxf(a[5], a[7])), a[9]);
#pragma unroll
      for (int o = 4; o < 32; o <<= 1) { m0 = fmaxf(m0, __shfl_xor_sync(0xffffffffu, m0, o)); m1 = fmaxf(m1, __shfl_xor_sync(0xffffffffu, m1, o)); }
#pragma unroll
      for (int i = 0; i < 5; i++) {
        const uint32_t ea = sb + SM_E + LV * 4 + (i < 4 ? i * 128 : 1024);
        sts32(ea, pack_bf16(ex2(a[2 * i] - m0), ex2(a[2 * i + 1] - m1)));
        sts32(ea + (i < 4 ? 512 : 128), 0x3f803f80u);
      }
      __syncwarp();
    } else {
      load_vx();
      if (EXM && mode == 3) bar_arrive(4, 256);
      retire(l16 + 1);
      if (VS0 == 2 || VS1 == 2) send_v(s + 1, 2);
      if (w == 3) {
        uint32_t used = ldg_relaxed32(&g_used[blockIdx.x / 3 * 32]);
        if (!(XP & 4) && elect_one()) {
          if (s > 0) seg_publish(s - 1);
          fence_async();
          seg_store(s, sb, 0, 8192);
        }
        __syncwarp();
        if (!EXM) {
          bar_sync(RANK < 2 ? 4 : 15, RANK < 2 ? 256 : 160);
          if (!(XP & 4) && elect_one()) { fence_async(); seg_store(s, sb, 8192, blk - 8192); }
          __syncwarp();
        }
        const uint32_t need = lds32(sb + SC_EPOCH) + (s >= NRING - 1 ? s : -4 * NSEG);
#pragma unroll 1
        for (int n = 0; (int)(used - need) < 0 && n < ((XP & 64) ? 1 : SPIN_LIMIT); n++) used = ldg_relaxed32(&g_used[blockIdx.x / 3 * 32]);
      }
    }
    {
      uint32_t wa[4], wb[4];
      constexpr int WS = 2048;
      const uint32_t w3a = l16 + SM_WO3 + w * 512;
      if (HP == 1) { hints = hint_addr(s); PIN(hints); }
      if (!(WL & 1)) { lds128(w3a + KP(0) * WS, wa); lds128(w3a + KP(1) * WS, wb); }
      if (WL & 2) {
#pragma unroll
        for (int i = 0; i < 4; i++) oc[i] = always | (always >> 16) | (always & (i + 1));
      } else if (!(WL & 4)) lds128(sb + SC_ONES, oc);
      if (B5POS == 1 && mode < 3) bar_arrive(5, N5);
      uint32_t e[10], p[5], vm[4], ob[4];
      float o0[4], o1[4], f[3][2][4], rs[4];
      if (!(RV & 1)) { reserve2(vm); reserve2(vm + 2); }
      if (!(RV & 2)) reserve2(e + 8);
      if (!HP) { hints = hint_addr(s); PIN(hints); }
      if (CLR & 2) asm volatile("{\n.reg .pred p;\nsetp.eq.u32 p, %0, 0;\n@p exit;\n}" :: "r"(wa[0] | wb[0] | oc[0] | hints) : "memory");
      if (RV & 4) mbar_wait_fast(sb + MB_S, par); else mbar_wait(sb + MB_S, par);
      RSTAMP(5);
      PROF(6);
      if (RV & 2) { ldsm4t(e, l16 + SM_E); ldsm4t(e + 4, l16 + SM_E + 512); ldsm2t(e + 8, l16 + SM_E + 1024); }
      else { ldsm4t(e, l16 + SM_E); ldsm2t_in(e + 8, l16 + SM_E + 1024, always); ldsm4t(e + 4, l16 + SM_E + 512); }
      if (RV & 1) lds128(l16 + w * 512 + SM_VM, vm); else lds128_in(vm, l16 + w * 512 + SM_VM, always);
      const float scl = __uint_as_float(lds32(sb + SC_UNSC + 8 - par * 8));
      if (HL == 0) hints = load_hints(hints);
      if (GF & 1) SCHED_FENCE(4);
#pragma unroll
      for (int i = 0; i < 4; i++) p[i] = mul_bf16(e[i], e[4 + i]);
      p[4] = mul_bf16(e[8], e[9]);
      if (HL) hints = load_hints(hints | (p[HL - 1] & always & 1));
      mma16816z(o0, vx[0], p[0], p[1]);
      if (WL & 1) { lds128_in(vx[0], w3a + KP(0) * WS, always); }
      mma16816z(o1, vx[1], p[0], p[1]);
      if (WL & 1) { lds128_in(vx[1], w3a + KP(1) * WS, always); }
      mma16816z(rs, oc, p[0], p[1]);
      mma16816(o0, vx[2], p[2], p[3]); lds128_in(vx[2], w3a + KP(2) * WS, always);
      mma16816(o1, vx[3], p[2], p[3]); lds128_in(vx[3], w3a + KP(3) * WS, always);
      mma16816(rs, oc, p[2], p[3]);
      mma1688(o0, vm[0], vm[1], p[4]); mma1688(o1, vm[2], vm[3], p[4]); mma1688(rs, oc[0], oc[1], p[4]);
      stsm4(l16 + w * 512 + SM_OB, pack_bf16(o0[0], o0[1]), pack_bf16(o0[2], o0[3]), pack_bf16(o1[0], o1[1]), pack_bf16(o1[2], o1[3]));
      bar_sync(6, 128);
      RSTAMP(3);
      PROF(7);
      ldsm4t_in(oc, l16 + SM_OB, always);
      bad = __any_sync(0xffffffffu, !(rs[0] + rs[1] > 0.f) && !bad);
      rs[0] *= scl; rs[1] *= scl;
      asm volatile("{\n.reg .pred p;\nsetp.ne.u32 p, %1, 0;\n@p rcp.approx.ftz.f32 %0, %0;\n}" : "+f"(rs[0]) : "r"(always));
      asm volatile("{\n.reg .pred p;\nsetp.ne.u32 p, %1, 1;\n@p rcp.approx.ftz.f32 %0, %0;\n}" : "+f"(rs[1]) : "r"(always));
      asm volatile("lop3.b32 %0, %1, %2, %3, 0xfe;" : "=r"(lp) : "r"((l16 & 128) * 2), "r"((l16 & 256) * 4), "r"(l16 & 112));
      if (bad) continue;
      ldsm4t(ob, l16 + SM_OB + 512);
      mma16816z(f[2][0], WL & 1 ? vx[0] : wa, oc[0], oc[1]); mma16816z(f[2][1], WL & 1 ? vx[1] : wb, oc[2], oc[3]);
      mma16816z(f[0][0], wo[0], oc[0], oc[1]); mma16816z(f[0][1], wo[4], oc[2], oc[3]);
      mma16816z(f[1][0], w1[0], oc[0], oc[1]); mma16816z(f[1][1], w1[4], oc[2], oc[3]);
      ldsm4t_in(oc, l16 + SM_OB + 1024, always);
      mma16816(f[2][0], vx[2], ob[0], ob[1]); lds128_in(vx[2], w3a + KP(4) * WS, always);
      mma16816(f[2][1], vx[3], ob[2], ob[3]); lds128_in(vx[3], w3a + KP(5) * WS, always);
      mma16816(f[0][0], wo[1], ob[0], ob[1]); mma16816(f[0][1], wo[5], ob[2], ob[3]);
      mma16816(f[1][0], w1[1], ob[0], ob[1]); mma16816(f[1][1], w1[5], ob[2], ob[3]);
      ldsm4t_in(ob, l16 + SM_OB + 1536, always);
      mma16816(f[0][0], wo[2], oc[0], oc[1]); mma16816(f[0][1], wo[6], oc[2], oc[3]);
      mma16816(f[2][0], vx[2], oc[0], oc[1]); lds128_in(vx[2], w3a + KP(6) * WS, always);
      mma16816(f[2][1], vx[3], oc[2], oc[3]); lds128_in(vx[3], w3a + KP(7) * WS, always);
      mma16816(f[1][0], w1[2], oc[0], oc[1]); mma16816(f[1][1], w1[6], oc[2], oc[3]);
      mma16816(f[0][0], wo[3], ob[0], ob[1]); mma16816(f[0][1], wo[7], ob[2], ob[3]);
      mma16816(f[1][0], w1[3], ob[0], ob[1]); mma16816(f[1][1], w1[7], ob[2], ob[3]);
      mma16816(f[2][0], vx[2], ob[0], ob[1]); mma16816(f[2][1], vx[3], ob[2], ob[3]);
      bar_arrive(7, NII < 18 ? 384 : 256);
      lds128_in(ob, sb + SC_DEAD, always);
      uint32_t h[3][2];
#pragma unroll
      for (int j = 0; j < 3; j++)
#pragma unroll
        for (int i = 0; i < 2; i++)
        {
          scale_sum(f[j][1][2 * i], f[j][0][2 * i], rs[0], always); scale_sum(f[j][1][2 * i + 1], f[j][0][2 * i + 1], rs[1], always);
          h[j][i] = pack_f16(f[j][1][2 * i], f[j][1][2 * i + 1]);
        }
      const uint32_t rofs = RANK * 32768;
      red_f16x8(slot(s, RANK >> 1, rofs), h[0][0], h[1][0], h[2][0], 0x3c00u);
      red_f16x8(slot(s, (RANK >> 1) ^ 1, rofs), h[0][1], h[1][1], h[2][1], 0x3c00u);
      if (NII == 18) bar_arrive(10, 256);
      SCHED_FENCE(5);
      RSTAMP(0);
      l16 += ob[B7R];
    }
    {
    PROF(8);
    if (VS0 == 3 || VS1 == 3) send_v(s + 1, 3);
    const uint32_t ma0 = l16 + SM_MEM + w * 128 + (LV >> 3) * 896 + nh * 512;
    const unsigned char* const sl[2] = {slot(s, nh, 0), slot(s, nh ^ 1, 0)};
    uint32_t late = latest_hint(hints, dl, s);
    if (late >= 64) {
      int n = 0;
#pragma unroll 1
      do {
        late = latest_hint(load_hints(hint_addr(s)), dl, s);
      } while (late >= 64 && ++n < SPIN_LIMIT);
    }
    dl += late * 32 + tm.poll;
    if (s == 0 && PSTAMP) MSTAMP(7);
    PROF(9);
    {
      auto wait_until = [&](uint32_t t) {
        asm volatile("{\n.reg .pred p;\n.reg .s32 c;\n.reg .u64 t;\nTL: mov.u64 t, %%globaltimer;\ncvt.u32.u64 c, t;\nsub.s32 c, c, %0;\nsetp.lt.s32 p, c, 0;\n@p bra.uni TL;\n}" :: "r"(t + (l16 & 15)) : "memory");
      };
      uint4 v[2][3];
      auto load = [&](int c) {
#pragma unroll
        for (int r = 0; r < 3; r++) v[c][r] = ldg_relaxed(sl[c ^ (r >> 1)] + r * 32768);
      };
      auto decode = [&](int c, int n) {
        uint32_t q[9];
        __half2 hm;
        const uint32_t ma = ma0 ^ (c * 512);
#pragma unroll
        for (int i = 0; i < 9; i++) {
          const uint32_t h = i % 3 == 0 ? v[c][i / 3].x : (i % 3 == 1 ? v[c][i / 3].y : v[c][i / 3].z);
          const float2 f = __half22float2(*(const __half2*)&h);
          q[i] = pack_bf16(f.x, f.y);
          hm = i ? __hmax2(hm, __habs2(*(const __half2*)&h)) : __habs2(*(const __half2*)&h);
        }
#pragma unroll
        for (int r = 0; r < 3; r++) stsm4(ma + r * 4096, q[3 * r], q[3 * r + 1], q[3 * r + 2], r < 2 ? v[c][r].w : *(const uint32_t*)&hm);
        const bool done = __all_sync(0xffffffffu, v[c][0].w == 0x5000u && v[c][1].w == 0x5000u && v[c][2].w == 0x5000u) || n > SPIN_LIMIT;
        asm volatile("{\n.reg .pred p;\nsetp.ne.u32 p, %0, 0;\n@p bar.arrive %1, 256;\n}" :: "r"((int)done), "r"(1 + c) : "memory");
        return done;
      };
      if (LEAD) { wait_until(dl - LEAD); load(1); }
      wait_until(dl);
      PROF(10);
      int n = 0;
#pragma unroll 1
      do {
        load(0);
        if (!LEAD) load(1);
        asm volatile("{\n.reg .pred p;\nsetp.eq.u32 p, %0, 0;\n@p bar.sync 13, 384;\n}" :: "r"(n) : "memory");
      } while (!decode(0, n++));
      PROF(11);
      RSTAMP(1);
#pragma unroll 1
      while (!decode(1, n++)) load(1);
      bar_arrive(9, 256);
      RSTAMP(2);
      PROF(12);
    }
    PROF(13);
    if (++s == NSEG - 1) break;
    }
  }
#undef fence_reg
  if (RANK < 2) bar_arrive(4, 256);
  TSTAMP(49);
  {
    PIN(l16);
    tail_attention(sb, RANK, w, LV, 0, 6);
#pragma unroll 1
    for (int sg = 0; sg < 2; sg++) {
      PIN(l16);
      const int lane = LV, m = lane >> 3, g = lane >> 2, t = lane & 3;
      const uint32_t ob = l16 + T_OB + sg * 8192;
      bar_sync(sg ? 0 : 8, 256);
      TSTAMP(54 + 2 * sg);
      const float inv = __uint_as_float(0x7f000000u - lds32(sb + T_UN + sg * 4));
#pragma unroll 1
      for (int j = 0; j < 4; j += 2) {
        float c[2][3][4];
        uint32_t x[4], y[4], z[2][4];
#pragma unroll
        for (int e = 0; e < 2; e++) {
          const uint32_t oa = sb + T_OA + ((sg * 4 + j + e) * 8 + g) * 64 + (blockIdx.x / 3 * 36 & 15) + t * 4;
          z[e][0] = lds32(oa); z[e][1] = lds32(oa + 16); z[e][2] = t ? 0u : lds32(oa + 32);
        }
#pragma unroll
        for (int i = 0; i < 3; i++) {
          const uint32_t wa = sb + T_WA + ((lane & 7) + ((lane >> 4) << 3)) * 128 + (((w + 4 * (m & 1)) ^ (lane & 7)) << 4);
          ldsm4t(x, wa + i * 3072); ldsm2t(y, wa + i * 3072 + 2048);
#pragma unroll
          for (int e = 0; e < 2; e++) { mma1688z(c[e][i], y[0], y[1], z[e][2]); mma16816(c[e][i], x, z[e][0], z[e][1]); }
        }
#pragma unroll
        for (int r = 0; r < 4; r++) {
          ldsm4t(z[0], ob + j * 2048 + r * 512); ldsm4t(z[1], ob + j * 2048 + 2048 + r * 512);
          lds128(l16 + SM_WO3 + w * 512 + r * 2048, x); lds128(l16 + SM_WO3 + w * 512 + (r + 4) * 2048, y);
#pragma unroll
          for (int e = 0; e < 2; e++) { mma16816(c[e][0], wo[r], z[e][0], z[e][1]); mma16816(c[e][1], w1[r], z[e][0], z[e][1]); mma16816(c[e][2], x, z[e][0], z[e][1]); }
#pragma unroll
          for (int e = 0; e < 2; e++) { mma16816(c[e][0], wo[r + 4], z[e][2], z[e][3]); mma16816(c[e][1], w1[r + 4], z[e][2], z[e][3]); mma16816(c[e][2], y, z[e][2], z[e][3]); }
        }
#pragma unroll
        for (int i = 0; i < 4; i++) {
          const float (&d)[3][4] = c[i >> 1];
          const int q = (i & 1) * 2;
          red_f16x8(g_red + T_RED + ((((sg * 4 + j + (i >> 1)) * 3 + RANK) * 4 + w) * 2 + (i & 1)) * 512 + lane * 16, pack_f16(d[0][q] * inv, d[0][q + 1] * inv),
                    pack_f16(d[1][q] * inv, d[1][q + 1] * inv), pack_f16(d[2][q] * inv, d[2][q + 1] * inv), 0x3c00u);
        }
      }
      TSTAMP(55 + 2 * sg);
    }
    if (RSLOW) { wait_until(gtime() + 8000); wait_until(gtime() + 8000); wait_until(gtime() + 4000); }
    if (w < 2) {
      const int b = blockIdx.x, lane = LV, g = lane >> 2, t = lane & 3;
      uint4 v;
#pragma unroll 1
      for (int n = 0; n < SPIN_LIMIT; n++) {
        v = ldg_relaxed(g_red + T_RED + (w * 96 + b) * 512 + lane * 16);
        if (__all_sync(0xffffffffu, v.w == 0x5000u)) break;
        __nanosleep(40);
      }
      const float un = __uint_as_float(lds32(sb + T_UN + w * 4));
      uint32_t* const o = (uint32_t*)(tm.out + (size_t)((NAUXSEG + w) * 32 + b / 24 * 8 + g) * DM + (b >> 3) % 3 * 192 + (b & 1) * 32 + (b & 6) * 4) + t;
#pragma unroll
      for (int j = 0; j < 3; j++) {
        const float2 f = __half22float2(*(const __half2*)(&v.x + j));
        o[j * 32] = movm(pack_bf16(f.x * un, f.y * un));
      }
    }
  }
  TSTAMP(3);
  MSTAMP(8);
  if (CSY) cluster_sync();
}

__global__ void __cluster_dims__(3, 1, 1) __launch_bounds__(384, 1)
rec_kernel(const __grid_constant__ RMaps tm, const bf16* __restrict__ x, const bf16* __restrict__ mem0) {
  extern __shared__ __align__(1024) unsigned char smem_raw[];
  const uint32_t sb = smem_u32(smem_raw);
  const int tid = threadIdx.x, lane = tid & 31;
  const int wg = __shfl_sync(0xffffffffu, tid >> 7, 0);
  const int w = __shfl_sync(0xffffffffu, (tid >> 5) & 3, 0);
  uint32_t rank; asm("mov.u32 %0, %%cluster_ctarank;" : "=r"(rank));
  STAMP(0);
  TSTAMP(0);
  asm volatile("griddepcontrol.launch_dependents;" ::: "memory");

#define PFT 1
  if (PFT && wg == 1 && lane == 0) asm volatile("prefetch.tensormap [%0];\nprefetch.tensormap [%1];" :: "l"(w & 1 ? &tm.woa : &tm.oa), "l"(w == 0 ? (rank < 2 ? &tm.wk : &tm.wv) : w == 1 ? &tm.wq : w == 2 ? &tm.x : &tm.wo) : "memory");
  if (wg < 2) {
    asm volatile("setmaxnreg.inc.sync.aligned.u32 192;");
    if (tid == 0) {
      for (int i = 0; i < 3; i++) { mbar_init(sb + MB_W + 8 * i, 1); mbar_init(sb + MB_X + 8 * i, 1); }
      mbar_init(sb + MB_WO, 1); mbar_init(sb + MB_WO3, 1);
      mbar_init(sb + MB_S, rank < 2 ? 5 : 6);
      mbar_init(sb + MB_F, 1);
      for (int i = 0; i < 3; i++) mbar_init(sb + MB_T + 8 * i, 1);
      mbar_init(sb + MB_VX, 1); mbar_init(sb + MB_VX + 8, 1);
      asm volatile("fence.mbarrier_init.release.cluster;" ::: "memory");
      fence_async();
      SSTAMP(11, 6);
      load_weights(sb, tm, rank, 0);
      for (int i = 0; i < 3; i++) mbar_expect(sb + MB_X + 8 * i, XT);
      tma_load3(sb + SM_X, &tm.x, 0, sb + MB_X);
      if (!PACE) for (int c = 1; c < 4; c++) load_weights(sb, tm, rank, c);
      mbar_expect(sb + MB_S, rank < 2 ? 640 + 2048 : 1280);
      mbar_expect(sb + MB_VX, 8192); mbar_expect(sb + MB_VX + 8, 8192);
      mbar_expect(sb + MB_T, 2048);
      for (int i = 1; i < 3; i++) mbar_expect(sb + MB_T + 8 * i, rank < 2 ? 5120 : 10240);
      SSTAMP(11, 5);
    }
    __syncwarp();
    bar_sync(0, 384);
    proj_role(sb, tm, rank, wg, w, lane);
  } else {
    asm volatile("setmaxnreg.dec.sync.aligned.u32 120;");
    attn_role(sb, smem_raw, tm, rank, x, mem0, w, lane);
  }
}

constexpr int A_XH = 73728;
constexpr int A_NS = 9, A_WM = 6144, A_WT = 768;
constexpr int A_RING = 2 * A_XH, A_TAIL = A_RING + A_NS * A_WM, A_GW = A_TAIL + A_NS * A_WT;
constexpr int A_EPI = 212864, A_EPW = 9344;
constexpr int A_XW = 4 * XT, A_XT = A_XW + 4096, A_NR = 4;
constexpr int A_IN = A_XT + 2048, A_INS = 2 * 9216 + SEGB, A_OST = A_IN + 2 * A_INS;
constexpr int A_GATE = A_EPI + 2 * A_EPW, A_BAR = A_GATE + 512;
constexpr int A_TOTAL = A_BAR + 384;
struct AMaps { CUtensorMap x, wa, wt, oa, o, o3, o8, wob, woa, wo8; };

DI void wgmma_n192_ss_nt(float* d, uint64_t da, uint64_t db, int acc) {
  asm volatile("{\n.reg .pred p;\nsetp.ne.b32 p, %98, 0;\n"
               "wgmma.mma_async.sync.aligned.m64n192k16.f32.bf16.bf16 {"
               "%0,%1,%2,%3,%4,%5,%6,%7,%8,%9,%10,%11,%12,%13,%14,%15,%16,%17,%18,%19,%20,%21,%22,%23,%24,%25,%26,%27,%28,%29,%30,%31,"
               "%32,%33,%34,%35,%36,%37,%38,%39,%40,%41,%42,%43,%44,%45,%46,%47,%48,%49,%50,%51,%52,%53,%54,%55,%56,%57,%58,%59,%60,%61,%62,%63,"
               "%64,%65,%66,%67,%68,%69,%70,%71,%72,%73,%74,%75,%76,%77,%78,%79,%80,%81,%82,%83,%84,%85,%86,%87,%88,%89,%90,%91,%92,%93,%94,%95"
               "}, %96, %97, p, 1, 1, 0, 1;\n}\n"
               : ACC8(d, 0), ACC8(d, 8), ACC8(d, 16), ACC8(d, 24), ACC8(d, 32), ACC8(d, 40), ACC8(d, 48), ACC8(d, 56),
                 ACC8(d, 64), ACC8(d, 72), ACC8(d, 80), ACC8(d, 88) : "l"(da), "l"(db), "r"(acc));
}
#define ACC4(d, o) "+f"(d[o]), "+f"(d[o + 1]), "+f"(d[o + 2]), "+f"(d[o + 3])
DI void wgmma_n24_ss_nt(float* d, uint64_t da, uint64_t db, int acc) {
  asm volatile("{\n.reg .pred p;\nsetp.ne.b32 p, %14, 0;\n"
               "wgmma.mma_async.sync.aligned.m64n24k16.f32.bf16.bf16 {%0,%1,%2,%3,%4,%5,%6,%7,%8,%9,%10,%11}, %12, %13, p, 1, 1, 0, 1;\n}\n"
               : ACC8(d, 0), ACC4(d, 8) : "l"(da), "l"(db), "r"(acc));
}
DI void wgmma_n8_ss(float* d, uint64_t da, uint64_t db, int acc) {
  asm volatile("{\n.reg .pred p;\nsetp.ne.b32 p, %6, 0;\n"
               "wgmma.mma_async.sync.aligned.m64n8k16.f32.bf16.bf16 {%0,%1,%2,%3}, %4, %5, p, 1, 1, 0, 0;\n}\n"
               : ACC4(d, 0) : "l"(da), "l"(db), "r"(acc));
}
DI void wgmma_n40_ss_tt(float* d, uint64_t da, uint64_t db, int acc) {
  asm volatile("{\n.reg .pred p;\nsetp.ne.b32 p, %22, 0;\n"
               "wgmma.mma_async.sync.aligned.m64n40k16.f32.bf16.bf16 {%0,%1,%2,%3,%4,%5,%6,%7,%8,%9,%10,%11,%12,%13,%14,%15,%16,%17,%18,%19}, "
               "%20, %21, p, 1, 1, 1, 1;\n}\n"
               : ACC8(d, 0), ACC8(d, 8), ACC4(d, 16) : "l"(da), "l"(db), "r"(acc));
}
DI void wgmma_n64_rs(float* d, const uint32_t* a, uint64_t db, int acc) {
  asm volatile("{\n.reg .pred p;\nsetp.ne.b32 p, %37, 0;\n"
               "wgmma.mma_async.sync.aligned.m64n64k16.f32.bf16.bf16 {"
               "%0,%1,%2,%3,%4,%5,%6,%7,%8,%9,%10,%11,%12,%13,%14,%15,%16,%17,%18,%19,%20,%21,%22,%23,%24,%25,%26,%27,%28,%29,%30,%31"
               "}, {%32,%33,%34,%35}, %36, p, 1, 1, 0;\n}\n"
               : ACC8(d, 0), ACC8(d, 8), ACC8(d, 16), ACC8(d, 24) : "r"(a[0]), "r"(a[1]), "r"(a[2]), "r"(a[3]), "l"(db), "r"(acc));
}
DI void wgmma_n32_ss_tn(float* d, uint64_t da, uint64_t db, int acc) {
  asm volatile("{\n.reg .pred p;\nsetp.ne.b32 p, %18, 0;\n"
               "wgmma.mma_async.sync.aligned.m64n32k16.f32.bf16.bf16 {%0,%1,%2,%3,%4,%5,%6,%7,%8,%9,%10,%11,%12,%13,%14,%15}, "
               "%16, %17, p, 1, 1, 1, 0;\n}\n"
               : ACC8(d, 0), ACC8(d, 8) : "l"(da), "l"(db), "r"(acc));
}
DI void tma_load3c(uint32_t dst, const CUtensorMap* m, int c0, int c1, int c2, uint32_t mb) {
  asm volatile("cp.async.bulk.tensor.3d.shared::cluster.global.mbarrier::complete_tx::bytes [%0], [%1, {%3, %4, %5}], [%2];"
               :: "r"(dst), "l"(m), "r"(mb), "r"(c0), "r"(c1), "r"(c2) : "memory");
}
DI void count_up(unsigned* p) {
  asm volatile("fence.proxy.async;" ::: "memory");
  asm volatile("red.release.gpu.global.add.u32 [%0], 1;" :: "l"(p) : "memory");
}
#define AX 0
#define FDLY 400
#define FEND 59
DI void publish(unsigned* p) {
  asm volatile("cp.async.bulk.wait_group 0;\nfence.proxy.async;" ::: "memory");
  asm volatile("red.relaxed.gpu.global.add.u32 [%0], 1;" :: "l"(p) : "memory");
}
#define PL 2
#define SER 35
#define DRAIN 0
#define PR 4
#define NQ 3
#define PUB 0
#define LA 1
#define LAG0 10
#define LEND 56
#define PDLY 0
#define ADLY 0

__global__ void __launch_bounds__(512, 1)
aux_kernel(const __grid_constant__ AMaps tm, const bf16* __restrict__ wqkv, const bf16* __restrict__ woa, const bf16* __restrict__ gate_w, bf16* __restrict__ out) {
  extern __shared__ __align__(1024) unsigned char smem_raw[];
  const uint32_t sb = smem_u32(smem_raw);
  const uint32_t fullx = sb + A_BAR, full1 = fullx + 24, empty1 = full1 + 8 * A_NS, fullw = empty1 + 8 * A_NS, full3 = fullw + 8, empty3 = full3 + 8 * A_NR,
                 fullq = empty3 + 8 * A_NR, emptyq = fullq + 24, fullo = emptyq + 24, emptyo = fullo + 16;
  const int tid = threadIdx.x, lane = tid & 31, cta = blockIdx.x;
  const int wg = __shfl_sync(0xffffffffu, tid >> 7, 0), w = __shfl_sync(0xffffffffu, (tid >> 5) & 3, 0);
  ASTAMP(14);
  if (tid == 384) {
    for (int i = 0; i < 3; i++) mbar_init(fullx + 8 * i, 1);
    for (int i = 0; i < A_NS; i++) { mbar_init(full1 + 8 * i, 1); mbar_init(empty1 + 8 * i, 8); }
    mbar_init(fullw, 1);
    for (int i = 0; i < 3; i++) { mbar_init(fullq + 8 * i, 1); mbar_init(emptyq + 8 * i, 4); }
    for (int i = 0; i < 2; i++) { mbar_init(fullo + 8 * i, 4); mbar_init(emptyo + 8 * i, 1); }
    for (int i = 0; i < A_NR; i++) { mbar_init(full3 + 8 * i, 1); mbar_init(empty3 + 8 * i, cta < NH ? 8 : 4); }
    fence_async();
  }
  __syncthreads();
  ASTAMP(0);
  const int tile = cta >> 1, hh = cta & 1;
  auto p3_n = [&](int g) { return cta < NH ? (cta & 3) * 2 + g : 8; };
  auto p3_next = [&](int& sl, int& ph) {
    sl += cta < NH ? 1 : 2;
    if (sl >= (cta < NH ? 6 - NQ : 4)) { sl -= cta < NH ? 6 - NQ : 4; ph ^= 1; }
  };
  auto p3_k = [&](int g) { return cta < NH ? cta >> 2 : (cta & 3) * 2 + g; };
  if (wg == 3) {
    asm volatile("setmaxnreg.dec.sync.aligned.u32 24;");
    const bool lead = lane == 0;
    if (w < 3) {
      if (ADLY) wait_until(gtime() + ADLY);
      if (elect_one()) {
        mbar_expect(fullx + 8 * w, 49152);
        for (int p = 0; p < 2; p++)
          asm volatile("cp.async.bulk.tensor.4d.shared::cluster.global.mbarrier::complete_tx::bytes [%0], [%1, {%3, %4, %5, %6}], [%2];"
                       :: "r"(sb + p * A_XH + w * 24576), "l"(&tm.x), "r"(fullx + 8 * w), "r"(0), "r"(p), "r"(57 * tile - 7), "r"(3 * w) : "memory");
      }
#pragma unroll 1
      for (int r = 0; r < 17; r++) {
#pragma unroll 1
        for (int st = w; st < A_NS; st += 3) {
          if (r > 0) mbar_wait(empty1 + 8 * st, ~r & 1);
          if (r < 16 && elect_one()) {
            const int col = hh * 288 + (r >> 2) * 72, row = (r & 3) * 144 + st * 16;
            mbar_expect(full1 + 8 * st, A_WM + (AX & 1 ? 0 : A_WT));
            tma_load3c(sb + A_RING + st * A_WM, &tm.wa, col, row, 0, full1 + 8 * st);
            if (!(AX & 1)) tma_load3c(sb + A_TAIL + st * A_WT, &tm.wt, col + 64, row, 0, full1 + 8 * st);
          }
          __syncwarp();
        }
        if (r == 0 && elect_one())
          for (int j = 0; j < 3; j++)
            asm volatile("cp.async.bulk.prefetch.L2.global [%0], %1;" :: "l"((const char*)wqkv + cta * 55296 + (w * 3 + j) * 6144), "r"(6144) : "memory");
        __syncwarp();
      }
      bar_sync(8, 96);
    }
    const unsigned epoch = lds32(sb + A_BAR + 376);
    if (w == 2 && cta < NH) {
      if (lead) {
        int avail = 0, q = 0, ph = 1;
#pragma unroll 1
        for (int seg = 0; seg < NAUXSEG; seg++) {
          const unsigned char* const src = g_seg + ((size_t)(AX & 128 ? 0 : seg % NRING) * 96 + cta * 3) * SEGB;
          SSTAMP(0, seg);
          const int ref = seg + max(LAG0 * (LEND - seg) / LEND, 0);
          if (ref >= avail) {
            const unsigned* const c = &g_scnt[(ref * 32 + cta) * 8];
            const int c2 = ldg_relaxed32(c + 512) - 3 * (epoch + 1), c0 = ldg_acquire32(c) - 3 * (epoch + 1);
            avail = ref + (c2 >= 0 && LA ? 3 : 1);
            if (c0 < 0) {
              wait_count(c, 3 * (epoch + 1), !(TL & 2) || seg < NAUXSEG - 2);
              if (FDLY && seg < FEND) wait_until(gtime() + FDLY);
            }
          }
          SSTAMP(1, seg);
          const uint32_t mb = fullq + q * 8;
          mbar_wait(emptyq + q * 8, q == 2 ? ph ^ 1 : ph);
          if (AX & 8) mbar_arrive(mb); else mbar_expect(mb, A_INS);
#pragma unroll 1
          for (int r = 0; r < ((AX & 8) ? 0 : 3); r++)
            asm volatile("cp.async.bulk.shared::cluster.global.mbarrier::complete_tx::bytes [%0], [%1], %2, [%3];"
                         :: "r"(sb + (q < 2 ? A_IN + q * A_INS : 3 * XT) + r * 9216), "l"(src + r * SEGB), "r"(r < 2 ? 9216 : SEGB), "r"(mb) : "memory");
          if (seg == 1) wait_count(&g_abar[32], NAUX * (epoch + 1));
          if (seg > 1) stg_relaxed32(&g_used[cta * 32], epoch * NSEG + seg + 1 - NQ);
          if (++q == NQ) { q = 0; ph ^= 1; }
        }
      }
      return;
    }
    if (w == 3) {
#pragma unroll 1
      for (int c = 0; c < 4; c++) {
        if (lead) asm volatile("cp.async.bulk.wait_group.read 0;" ::: "memory");
        __syncwarp();
        bar_arrive(11, 160); bar_arrive(12, 160);
#pragma unroll 1
        for (int g = 0; g < 2; g++) {
          bar_sync(13 + g, 160);
          if (lead) {
            asm volatile("cp.async.bulk.tensor.3d.global.shared::cta.bulk_group [%0, {%2, %3, %4}], [%1];"
                         :: "l"(&tm.oa), "r"(sb + A_EPI + g * A_EPW + 1024), "r"(4096 + hh * 288 + c * 72), "r"(g), "r"(57 * tile) : "memory");
            asm volatile("cp.async.bulk.commit_group;" ::: "memory");
          }
        }
      }
      if (lead) {
        asm volatile("cp.async.bulk.wait_group.read 0;" ::: "memory");
        mbar_arrive(emptyo); mbar_arrive(emptyo + 8);
        publish(&g_abar[32]);
      }
      __syncwarp();
    }
    if ((w & 1) && cta < NH) {
#pragma unroll 1
      for (int seg = w >> 1; seg < NAUXSEG; seg += 2) {
        if (lead) {
          mbar_wait(fullo + (w >> 1) * 8, (seg >> 1) & 1);
          fence_async();
          tma_store(&tm.o, sb + A_OST + (w >> 1) * 8192, cta * DH, seg * 32);
          tma_store(&tm.o, sb + A_OST + (w >> 1) * 8192 + 4096, cta * DH + 64, seg * 32);
          asm volatile("cp.async.bulk.commit_group;\ncp.async.bulk.wait_group.read 0;" ::: "memory");
          mbar_arrive(emptyo + (w >> 1) * 8);
          if (PUB == 0 || seg >= NAUXSEG - 2) publish(&g_ocnt[seg * 64 + 2 * cta / 9 * 8]);
          else {
            if (PUB == 1) asm volatile("fence.acq_rel.gpu;" ::: "memory"); else if (PUB > 2) wait_until(gtime() + PUB);
            asm volatile("red.relaxed.gpu.global.add.u32 [%0], 1;" :: "l"(&g_ocnt[seg * 64 + 2 * cta / 9 * 8]) : "memory");
          }
          if (2 * cta / 9 != (2 * cta + 1) / 9) asm volatile("red.relaxed.gpu.global.add.u32 [%0], 1;" :: "l"(&g_ocnt[seg * 64 + (2 * cta + 1) / 9 * 8]) : "memory");
          SSTAMP(9, seg);
        }
        __syncwarp();
      }
    }
    if (w & 1) return;
    if (w == 0) {
      if (lead) {
        mbar_expect(fullw, 18 * 8192 + 2048);
#pragma unroll 1
        for (int k = 0; k < 18; k++) {
          const int g = k / 9, kb = p3_k(g) * 9 + k - 9 * g;
          if (kb < 64) tma_load(sb + k * 8192, &tm.wob, p3_n(g) * 64, kb * 64, fullw);
          else tma_load(sb + k * 8192, &tm.woa, p3_n(g) * 64, (kb - 64) * 64, fullw);
        }
        for (int g = 0; g < 2; g++) tma_load(sb + A_XW + g * 2048, &tm.wo8, p3_n(g) * 64, 512 + p3_k(g) * 8, fullw);
      }
      __syncwarp();
    }
    bar_sync(6, cta >= NH ? 320 : 288);
    if (lead) {
      if (NQ == 3) for (int i = 0; i < 4; i++) mbar_arrive(emptyq + 16);
      wait_count(&g_abar[32], NAUX * (epoch + 1));
      int avail = 0, sl = w >> 1, ph = 1;
      const int ke = p3_k(w >> 1);
      const unsigned nheads = (ke < 7 ? 5 : 1) * (epoch + 1);
#pragma unroll 1
      for (int seg = 0; seg < NAUXSEG; seg++) {
        bool waited = false;
        if (seg >= avail) {
          const unsigned* const c = &g_ocnt[seg * 64 + ke * 8];
          const int c2 = ldg_relaxed32(c + 128) - nheads, c1 = ldg_relaxed32(c + 64) - nheads, c0 = ldg_acquire32(c) - nheads;
          waited = c0 < 0;
          if (waited) { wait_count(c, nheads, !(TL & 2) || seg < NAUXSEG - 2); if (PDLY && seg < FEND) wait_until(gtime() + PDLY); }
          else if (c1 >= 0) avail = seg + (c2 >= 0 ? 3 : 2);
        }
        SSTAMP(5, seg);
        mbar_wait(empty3 + 8 * sl, ph);
        if (AX & 4) mbar_arrive(full3 + 8 * sl);
        else {
          mbar_expect(full3 + 8 * sl, XT + 512);
          tma_load3c(sb + sl * XT, &tm.o3, 0, seg * 32, ke * 9, full3 + 8 * sl);
          tma_load(sb + A_XT + sl * 512, &tm.o8, 72 * 64 + ke * 8, seg * 32, full3 + 8 * sl);
        }
        p3_next(sl, ph);
      }
    }
  } else if (wg == 2) {
    asm volatile("setmaxnreg.dec.sync.aligned.u32 88;");
    {
      const unsigned epoch = *(volatile unsigned*)&g_epoch2;
      if ((tid & 127) < 80) { const uint4 g = __ldg((const uint4*)gate_w + min(tid & 127, 71)); sts128(sb + A_GW + (tid & 127) * 16, g.x, g.y, g.z, g.w); }
      fence_async();
      bar_sync(3, 128);
      float gt[2][4];
      const uint32_t d0 = (sb & 0x3FFFF) >> 4;
#pragma unroll 1
      for (int j = 0; j < 3; j++) {
        mbar_wait(fullx + 8 * j, 0);
        WG_FENCE();
#pragma unroll
        for (int k = 0; k < 24; k++)
          wgmma_n8_ss(gt[k & 1], desc_at(d0 + (k & 1) * (A_XH >> 4) + j * 1536 + (k >> 3) * 512 + (k & 6), 16, 1024, 1), desc_at(d0 + (A_GW >> 4) + j * 24 + (k & 30), 16, 128, 0), j | (k >> 1));
        WG_COMMIT();
      }
      WG_WAIT(0);
      if ((lane & 3) == 0)
#pragma unroll
        for (int i = 0; i < 4; i++) {
          const float gv = 1.f / (1.f + __expf(-gt[i >> 1][(i & 1) * 2]));
          const int r = w * 16 + (lane >> 2) + (i & 1) * 8, tok = 2 * (57 * tile - 7 + r) + (i >> 1);
          sts32(sb + A_GATE + ((i >> 1) * 64 + r) * 4, __float_as_uint(gv));
          if (hh == 0 && r >= 7 && tok < S_LEN) g_gate[tok] = gv;
        }
      if (tid == 256) sts32(sb + A_BAR + 376, epoch);
      __syncwarp();
      bar_arrive(7, 384);
      __half2 hw = __float2half2_rn(0.f);
#pragma unroll
      for (int i = 0; i < 9; i++) { const uint4 v = __ldg((const uint4*)woa + cta * 1152 + i * 128 + (tid & 127)); hw = amax4(hw, &v.x); }
      const uint32_t ew = wexp(hw);
      if (lane == 0) atomicMax(&g_amax[0], (unsigned long long)(epoch + 1) << 32 | ew);
      bar_sync(3, 128);
      if (tid == 256) {
        count_up(&g_abar[0]);
        wait_count(&g_abar[0], NAUX * (epoch + 1));
        if (cta == 0) *(volatile unsigned*)&g_epoch2 = epoch + 1;
      }
      __syncwarp();
      bar_sync(3, 128);
    }
    if (cta < NH) {
      const int lim = w * 8 + (lane >> 2) - 2 * (lane & 3);
      int q = 0, ph = 0;
      uint32_t p[5][4];
#pragma unroll
      for (int n = 0; n < 10; n++) p[n >> 1][1 + (n & 1)] = __shfl_sync(0xffffffffu, lane ^ n, n);
#pragma unroll 1
      for (int seg = 0; seg < NAUXSEG; seg++) {
        const float gt = __ldcg(&g_gate[seg * 32 + w * 8 + (lane >> 2)]);
        float sc[20], d[32];
        const uint32_t d0 = ((sb & 0x3FFFF) + (q < 2 ? A_IN + q * A_INS : 3 * XT)) >> 4;
        mbar_wait(fullq + q * 8, ph);
        if (tid == 256) SSTAMP(2, seg);
        WG_FENCE();
#pragma unroll
        for (int k = 0; k < 8; k++) {
          const int o = ((k >> 2) * 9216 + (k & 3) * 256) >> 4;
          wgmma_n40_ss_tt(sc, desc_at(d0 + o, 128, 512, 0), desc_at(d0 + o + 256, 128, 1024, 0), k > 0);
        }
        WG_COMMIT();
        WG_WAIT(0);
        if (tid == 256) SSTAMP(12, seg);
        float a[10];
#pragma unroll
        for (int i = 0; i < 10; i++) {
          a[i] = sc[(i >> 1) * 4 + (i & 1)] * (SM_SCALE * LOG2E);
          if (i < 8 && (i >> 1) * 8 + (i & 1) > lim) a[i] = -1.0e9f * LOG2E;
        }
        float m = max10(a);
        m = fmaxf(m, __shfl_xor_sync(0xffffffffu, m, 1)); m = fmaxf(m, __shfl_xor_sync(0xffffffffu, m, 2));
#pragma unroll
        for (int i = 0; i < 10; i++) a[i] = ex2(a[i] - m);
#pragma unroll
        for (int n = 0; n < 5; n++) {
          p[n][0] = pack_bf16(a[2 * n], a[2 * n + 1]); p[n][3] = p[n][0] | p[n][1];
          asm volatile("" : "+r"(p[n][0]), "+r"(p[n][3]) :: "memory");
        }
        float sum = ((a[0] + a[1]) + (a[2] + a[3])) + ((a[4] + a[5]) + (a[6] + a[7])) + (a[8] + a[9]);
        sum += __shfl_xor_sync(0xffffffffu, sum, 1);
        if (tid == 256) SSTAMP(3, seg);
        WG_FENCE();
#pragma unroll
        for (int n = 0; n < 5; n++) wgmma_n64_rs(d, p[n], n < 4 ? desc_at(d0 + 1152 + 8 * n, 4096, 512, 0) : desc_at(d0 + 1152 + 512, 1024, 128, 0), n);
        WG_COMMIT();
        sum += __shfl_xor_sync(0xffffffffu, sum, 2);
        const float f = (1.f - gt) * rcp(sum);
        WG_WAIT(0);
        if (lane == 0) mbar_arrive(emptyq + q * 8);
        if (++q == NQ) { q = 0; ph ^= 1; }
        if (tid == 256) SSTAMP(4, seg);
        mbar_wait(emptyo + (seg & 1) * 8, (seg >> 1) & 1);
#pragma unroll
        for (int n = 0; n < 4; n++) {
          const float* const v = d + (n & 1) * 16 + (n & 2);
          stsm4(sb + A_OST + (seg & 1) * 8192 + (n >> 1) * 4096 + (w * 8 + (lane & 7)) * 128 + ((((n & 1) * 4 + (lane >> 3)) ^ (lane & 7)) << 4),
                pack_bf16(v[0] * f, v[1] * f), pack_bf16(v[4] * f, v[5] * f), pack_bf16(v[8] * f, v[9] * f), pack_bf16(v[12] * f, v[13] * f));
        }
        __syncwarp();
        if (lane == 0) mbar_arrive(fullo + (seg & 1) * 8);
        if (tid == 256) SSTAMP(13, seg);
      }
    }
  } else {
    asm volatile("setmaxnreg.inc.sync.aligned.u32 200;");
    {
      const int g = lane >> 2, t = lane & 3;
      const uint32_t eb = sb + A_EPI + wg * A_EPW, d0 = (sb & 0x3FFFF) >> 4;
      const uint32_t own = (2 * t <= g ? 0xffffu : 0u) | (2 * t < g ? 0xffff0000u : 0u);
      const int kmin = 7 - 57 * tile - 16 * w;
      __half2 ho = __float2half2_rn(0.f);
#pragma unroll 1
      for (int c = 0; c < 4; c++) {
        float acc[96], tl[12];
#pragma unroll 1
        for (int r = 0; r < 4; r++) {
#pragma unroll
          for (int st = 0; st < A_NS; st++) {
            const int ks = r * 9 + st;
            if (c == 0 && st % 3 == 0 && ks % 12 == 0) mbar_wait(fullx + 8 * (ks / 12), 0);
            mbar_wait(full1 + 8 * st, r & 1);
            const uint64_t da = desc_at(d0 + wg * (A_XH >> 4) + (ks >> 2) * 512 + (ks & 3) * 2, 16, 1024, 1);
            WG_FENCE();
            wgmma_n192_ss_nt(acc, da, desc_at(d0 + ((A_RING + st * A_WM) >> 4), 2048, 1024, 1), ks);
            if (!(AX & 2)) wgmma_n24_ss_nt(tl, da, desc_at(d0 + ((A_TAIL + st * A_WT) >> 4), 128, 256, 0), ks);
            WG_COMMIT();
            if (st == 0 && r == 2) bar_sync(11 + wg, 160);
            WG_WAIT(1);
            if (ks > 0 && lane == 0) mbar_arrive(empty1 + 8 * ((st + A_NS - 1) % A_NS));
          }
        }
        WG_WAIT(0);
        if (lane == 0) mbar_arrive(empty1 + 8 * (A_NS - 1));
        ASTAMP(16 + (c & 3));
        uint32_t ql[9], qh[9], kl[9], kh[9], kx[10], vl[9], vh[9], vx[10];
#pragma unroll
        for (int j = 0; j < 9; j++) {
          const float* const q = j < 8 ? acc + 4 * j : tl, * const k = j < 8 ? acc + 32 + 4 * j : tl + 4, * const v = j < 8 ? acc + 64 + 4 * j : tl + 8;
          kh[j] = pack_bf16(k[2], k[3]); vh[j] = pack_bf16(v[2], v[3]);
          ql[j] = pack_bf16(q[0], q[1]); qh[j] = pack_bf16(q[2], q[3]); kl[j] = pack_bf16(k[0], k[1]); vl[j] = pack_bf16(v[0], v[1]);
        }
        if (w < 3) {
          const uint32_t ha = eb + 1024 + w * 2304 + lane * 16;
          stsm4(ha, kh[0], kh[1], kh[2], kh[3]); stsm4(ha + 512, kh[4], kh[5], kh[6], kh[7]);
          stsm4(ha + 1024, vh[0], vh[1], vh[2], vh[3]); stsm4(ha + 1536, vh[4], vh[5], vh[6], vh[7]);
          asm volatile("stmatrix.sync.aligned.m8n8.x2.shared.b16 [%0], {%1,%2};" :: "r"(ha + 2048), "r"(kh[8]), "r"(vh[8]) : "memory");
        }
        if (c == 0) bar_sync(7, 384); else bar_sync(1 + wg, 128);
        {
          const uint32_t ha = eb + 1024 + max(w - 1, 0) * 2304 + lane * 16;
          ldsm4(kx, ha); ldsm4(kx + 4, ha + 512); ldsm4t(vx, ha + 1024); ldsm4t(vx + 4, ha + 1536);
          asm volatile("ldmatrix.sync.aligned.m8n8.x1.shared.b16 {%0}, [%1];" : "=r"(kx[8]) : "r"(ha + 2048) : "memory");
          asm volatile("ldmatrix.sync.aligned.m8n8.x1.trans.shared.b16 {%0}, [%1];" : "=r"(vx[8]) : "r"(ha + 2176) : "memory");
        }
        const float gl = __uint_as_float(lds32(sb + A_GATE + (wg * 64 + w * 16 + g) * 4)), gh = __uint_as_float(lds32(sb + A_GATE + (wg * 64 + w * 16 + g + 8) * 4));
#pragma unroll
        for (int j = 0; j < 9; j++) { vl[j] = movm(vl[j]); vh[j] = movm(vh[j]); }
        bar_sync(1 + wg, 128);
        uint32_t ol[9], oh[9];
#pragma unroll
        for (int i = 0; i < 4; i++) {
          const int b = 2 * i;
          const uint32_t a[4] = {t >= i ? ql[b] : 0u, t >= i ? qh[b] : 0u, ql[b + 1], qh[b + 1]}, a4 = t <= i ? ql[b + 2] : 0u, a5 = t <= i ? qh[b + 2] : 0u;
          float sx[4], sl[4], sh[4];
          mma16816z(sx, a, kx[b], kx[b + 1]); mma16816z(sl, a, kl[b], kl[b + 1]); mma16816z(sh, a, kh[b], kh[b + 1]);
          mma1688(sx, a4, a5, kx[b + 2]); mma1688(sl, a4, a5, kl[b + 2]); mma1688(sh, a4, a5, kh[b + 2]);
          float e[4];
#pragma unroll
          for (int u = 0; u < 4; u++) {
            const int cc = 2 * t + (u & 1);
            e[u] = (cc <= g ? (u < 2 ? sl[u] : sh[u]) : (u < 2 ? sx[u] : sl[u])) * (0.23570226039551584f * LOG2E);
            if ((cc <= g ? cc : cc - 8) + (u & 2) * 4 < kmin) e[u] = -1.0e9f * LOG2E;
          }
          float m0 = fmaxf(e[0], e[1]), m1 = fmaxf(e[2], e[3]);
#pragma unroll
          for (int o = 1; o < 4; o <<= 1) { m0 = fmaxf(m0, __shfl_xor_sync(0xffffffffu, m0, o)); m1 = fmaxf(m1, __shfl_xor_sync(0xffffffffu, m1, o)); }
          e[0] = ex2(e[0] - m0); e[1] = ex2(e[1] - m0); e[2] = ex2(e[2] - m1); e[3] = ex2(e[3] - m1);
          const uint32_t p0 = pack_bf16(e[0], e[1]), p1 = pack_bf16(e[2], e[3]);
          const uint32_t p[4] = {p0 & ~own, 0u, p0 & own, p1 & ~own};
          float s0 = e[0] + e[1], s1 = e[2] + e[3];
#pragma unroll
          for (int o = 1; o < 4; o <<= 1) { s0 += __shfl_xor_sync(0xffffffffu, s0, o); s1 += __shfl_xor_sync(0xffffffffu, s1, o); }
          const float f0 = gl * rcp(s0), f1 = gh * rcp(s1);
#pragma unroll
          for (int j = b; j < b + 3; j++) {
            float o[4];
            mma16816z(o, p, vx[j], vl[j]);
            mma1688(o, 0u, p1 & own, vh[j]);
            const uint32_t lo = pack_bf16(o[0] * f0, o[1] * f0), hi = pack_bf16(o[2] * f1, o[3] * f1);
            if (j > b || i == 0) { ol[j] = lo; oh[j] = hi; }
            else { ol[j] = t >= i ? lo : ol[j]; oh[j] = t >= i ? hi : oh[j]; }
          }
        }
        const uint32_t sa = eb + 16 + (w * 16 + (lane & 15)) * 144 + (lane >> 4) * 16;
#pragma unroll
        for (int j = 0; j < 8; j += 2) stsm4(sa + j * 16, ol[j], oh[j], ol[j + 1], oh[j + 1]);
        asm volatile("stmatrix.sync.aligned.m8n8.x2.shared.b16 [%0], {%1,%2};" :: "r"(sa + 128), "r"(ol[8]), "r"(oh[8]) : "memory");
        ho = amax4(amax4(amax4(amax4(ho, ol), ol + 4), oh), oh + 4);
        ho = __hmax2_nan(__hmax2_nan(ho, __habs2(*(const __half2*)&ol[8])), __habs2(*(const __half2*)&oh[8]));
        if (c == 3 && tile == 17) {
          const uint32_t eo = wexp(ho);
          if (lane == 0) atomicMax(&g_amax[16], (unsigned long long)(lds32(sb + A_BAR + 376) + 1) << 32 | eo);
        }
        fence_async();
        bar_arrive(13 + wg, 160);
        ASTAMP(20 + (c & 3));
      }
    }
    ASTAMP(3);
    uint32_t wa[36][4];
    mbar_wait(fullw, 0);
    const uint32_t la = sb + wg * 73728 + ((lane & 7) + ((lane >> 4) << 3)) * 128 + (((2 * w + ((lane >> 3) & 1)) ^ (lane & 7)) << 4);
#pragma unroll
    for (int k = 0; k < 36; k++) ldsm4t(wa[k], la + k * 2048);
    sts64(sb + A_XW + wg * 2048 + 1024 + (tid & 127) * 8, 0, 0);
    fence_async();
    bar_arrive(6, cta >= NH ? 320 : 288);
    bar_sync(1 + wg, 128);
    ASTAMP(4);
    const int nsl = p3_n(wg), ke = p3_k(wg), t = lane & 3;
    const unsigned epoch = lds32(sb + A_BAR + 376);
    uint2* const part = g_part + nsl * 4096 + w * 16 + (lane >> 2) * 2 + (t & 1);
    auto tag = [&](int seg) { return PR == 8 ? ((seg >> 3) + 1 + (epoch & (seg >> 1) & (seg >> 2))) & 1 : ((seg >> 2) + 1 + (epoch & (seg >> 1))) & 1; };
    uint2 v[4];
    auto fetch = [&](int seg) {
#pragma unroll
      for (int j = 0; j < 4; j++)
        asm volatile("ld.relaxed.gpu.global.v2.b32 {%0,%1}, [%2];" : "=r"(v[j].x), "=r"(v[j].y) : "l"(part + (seg & (PR - 1)) * 36864 + ke * 512 + ((t >> 1) * 4 + j) * 64) : "memory");
    };
    auto finish = [&](int seg) {
      int n = 0;
#pragma unroll 1
      while (!(AX & 16) && __any_sync(0xffffffffu, (((v[0].x ^ tag(seg)) | (v[1].x ^ tag(seg)) | (v[2].x ^ tag(seg)) | (v[3].x ^ tag(seg))) & 1) != 0) && ++n < SPIN_LIMIT) {
        if (seg < NAUXSEG - ((TL & 2) ? 2 : 1)) __nanosleep(100);
        fetch(seg);
      }
      const float a0 = (bf_lo(v[0].x) + bf_lo(v[1].x)) + (bf_lo(v[2].x) + bf_lo(v[3].x)), a1 = (bf_hi(v[0].x) + bf_hi(v[1].x)) + (bf_hi(v[2].x) + bf_hi(v[3].x));
      const float b0 = (bf_lo(v[0].y) + bf_lo(v[1].y)) + (bf_lo(v[2].y) + bf_lo(v[3].y)), b1 = (bf_hi(v[0].y) + bf_hi(v[1].y)) + (bf_hi(v[2].y) + bf_hi(v[3].y));
      const float c0 = (t < 2 ? a0 : b0) + __shfl_xor_sync(0xffffffffu, t < 2 ? b0 : a0, 2), c1 = (t < 2 ? a1 : b1) + __shfl_xor_sync(0xffffffffu, t < 2 ? b1 : a1, 2);
      ((uint32_t*)(out + (size_t)(seg * 32 + ke * 4 + ((lane >> 2) & 3)) * DM + nsl * 64 + w * 16 + (lane >> 4) * 8))[t] = movm(pack_bf16(c0, c1));
    };
    float acc[16];
    if (AX & 64) for (int i = 0; i < 16; i++) acc[i] = 0.f;
    int done = 0, sl = cta < NH ? 0 : wg, ph = 0;
    const uint32_t d0 = (sb & 0x3FFFF) >> 4;
#pragma unroll 1
    for (int seg = 0; seg < NAUXSEG; seg++) {
      if (DRAIN) {
#pragma unroll 1
        while (done < seg && !mbar_test(full3 + 8 * sl, ph)) { fetch(done); finish(done); done++; }
      }
      mbar_wait(full3 + 8 * sl, ph);
      if (SER && !(AX & 64) && (wg == 1 || seg > 0)) bar_sync(10 - wg, 256);
      if (tid == 128) SSTAMP(6, seg);
      if (!(AX & 16)) fetch(done);
      if (!(AX & 64)) {
        const uint64_t db = desc_at(d0 + sl * (XT >> 4), 16, 1024, 1);
        WG_FENCE();
        wgmma_n32_ss_tn(acc, desc_at(d0 + ((A_XW + wg * 2048) >> 4), 8192, 1024, 1), desc_at(d0 + (A_XT >> 4) + sl * 32, 0, 128, 0), 0);
#pragma unroll
        for (int k = 0; k < 36; k++) {
          wgmma_n32_rs(acc, wa[k][0], wa[k][1], wa[k][2], wa[k][3], db + (k >> 2) * 256 + (k & 3) * 2, 1);
          if (SER && k == SER && (wg == 0 || seg < NAUXSEG - 1)) bar_arrive(9 + wg, 256);
        }
        WG_COMMIT();
      }
      if (done <= seg - PL) finish(done++);
      WG_WAIT(0);
      if (lane == 0) mbar_arrive(empty3 + 8 * sl);
      p3_next(sl, ph);
#pragma unroll
      for (int j = 0; j < 4; j++)
        if (!(AX & 16) || acc[4 * j] == 1.2345678f)
          asm volatile("st.relaxed.gpu.global.v2.b32 [%0], {%1,%2};" :: "l"(part + (seg & (PR - 1)) * 36864 + (2 * j + (t >> 1)) * 512 + ke * 64),
                       "r"((pack_bf16(acc[4 * j], acc[4 * j + 1]) & ~1u) | tag(seg)), "r"(pack_bf16(acc[4 * j + 2], acc[4 * j + 3])) : "memory");
      if (tid == 128) SSTAMP(7, seg);
      if (tid == 128) SSTAMP(8, seg);
      if ((seg & 7) == 6) ASTAMP(5 + (seg >> 3));
    }
#pragma unroll 1
    for (; done < NAUXSEG; done++) { fetch(done); finish(done); }
    ASTAMP(13);
    TSTAMP(48);
    MSTAMP(9);
  }
}

typedef CUresult (*EncodeFn)(CUtensorMap*, CUtensorMapDataType, cuuint32_t, void*, const cuuint64_t*, const cuuint64_t*,
                             const cuuint32_t*, const cuuint32_t*, CUtensorMapInterleave, CUtensorMapSwizzle,
                             CUtensorMapL2promotion, CUtensorMapFloatOOBfill);
static void make_map(EncodeFn enc, CUtensorMap* m, const void* p, int rows, int cols, int box_rows) {
  cuuint64_t dims[2] = {(cuuint64_t)cols, (cuuint64_t)rows};
  cuuint64_t strides[1] = {(cuuint64_t)cols * 2};
  cuuint32_t box[2] = {64, (cuuint32_t)box_rows};
  cuuint32_t es[2] = {1, 1};
  enc(m, CU_TENSOR_MAP_DATA_TYPE_BFLOAT16, 2, (void*)p, dims, strides, box, es, CU_TENSOR_MAP_INTERLEAVE_NONE,
      CU_TENSOR_MAP_SWIZZLE_128B, CU_TENSOR_MAP_L2_PROMOTION_L2_128B, CU_TENSOR_MAP_FLOAT_OOB_FILL_NONE);
}

constexpr int g_poll = POLL_NS;
extern "C" void kernel_launch(void* const* d_in, const int* in_sizes, int n_in, void* d_out, int out_size) {
  const bf16* x = (const bf16*)d_in[0];
  const bf16* wqkvA = (const bf16*)d_in[1];
  const bf16* woA = (const bf16*)d_in[2];
  const bf16* mem0 = (const bf16*)d_in[4];
  const bf16* Wq = (const bf16*)d_in[5];
  const bf16* Wk = (const bf16*)d_in[6];
  const bf16* Wv = (const bf16*)d_in[7];
  const bf16* Wo = (const bf16*)d_in[8];
  const bf16* gate_w = (const bf16*)d_in[10];
  static EncodeFn enc = nullptr;
  static void *pO = nullptr, *pR = nullptr;
  if (!enc) {
    cudaDriverEntryPointQueryResult qr;
    cudaGetDriverEntryPoint("cuTensorMapEncodeTiled", (void**)&enc, cudaEnableDefault, &qr);
    cudaGetSymbolAddress(&pO, g_Ocat);
    cudaGetSymbolAddress(&pR, g_red_raw);
    cudaFuncSetAttribute(rec_kernel, cudaFuncAttributeMaxDynamicSharedMemorySize, SM_TOTAL);
    cudaFuncSetAttribute(aux_kernel, cudaFuncAttributeMaxDynamicSharedMemorySize, A_TOTAL);
  }
  RMaps rm;
  rm.poll = g_poll; rm.out = (bf16*)d_out;
  make_map(enc, &rm.woa, woA, DM, DM, 24);
  {
    cuuint64_t dims[2] = {KCAT, S_LEN}, strides[1] = {KCAT * 2};
    cuuint32_t box[2] = {32, 64}, es[2] = {1, 1};
    enc(&rm.oa, CU_TENSOR_MAP_DATA_TYPE_BFLOAT16, 2, pO, dims, strides, box, es, CU_TENSOR_MAP_INTERLEAVE_NONE,
        CU_TENSOR_MAP_SWIZZLE_NONE, CU_TENSOR_MAP_L2_PROMOTION_NONE, CU_TENSOR_MAP_FLOAT_OOB_FILL_NONE);
  }
  rm.red = (unsigned char*)(((uintptr_t)pR + 262143) & ~(uintptr_t)262143);
  {
    cuuint64_t dims[3] = {64, S_LEN, 9}, strides[2] = {DM * 2, 128};
    cuuint32_t box[3] = {64, 32, 9}, es[3] = {1, 1, 1};
    enc(&rm.x, CU_TENSOR_MAP_DATA_TYPE_BFLOAT16, 3, (void*)x, dims, strides, box, es, CU_TENSOR_MAP_INTERLEAVE_NONE,
        CU_TENSOR_MAP_SWIZZLE_128B, CU_TENSOR_MAP_L2_PROMOTION_L2_128B, CU_TENSOR_MAP_FLOAT_OOB_FILL_NONE);
  }
  make_map(enc, &rm.wq, Wq, DM, 4096, 192);
  make_map(enc, &rm.wk, Wk, DM, 4096, 192);
  make_map(enc, &rm.wv, Wv, DM, 4096, 192);
  make_map(enc, &rm.wo, Wo, 4096, DM, 128);
  AMaps am;
  {
    cuuint32_t es[4] = {1, 1, 1, 1};
    cuuint64_t dx[4] = {64, 2, S_LEN / 2, 9}, sx[3] = {DM * 2, DM * 4, 128};
    cuuint32_t bx[4] = {64, 1, 64, 3};
    enc(&am.x, CU_TENSOR_MAP_DATA_TYPE_BFLOAT16, 4, (void*)x, dx, sx, bx, es, CU_TENSOR_MAP_INTERLEAVE_NONE,
        CU_TENSOR_MAP_SWIZZLE_128B, CU_TENSOR_MAP_L2_PROMOTION_L2_128B, CU_TENSOR_MAP_FLOAT_OOB_FILL_NONE);
    cuuint64_t dw[3] = {DM, DM, 3}, sw[2] = {DM * 6, DM * 2};
    cuuint32_t bw[3] = {64, 16, 3}, bt[3] = {8, 16, 3};
    enc(&am.wa, CU_TENSOR_MAP_DATA_TYPE_BFLOAT16, 3, (void*)wqkvA, dw, sw, bw, es, CU_TENSOR_MAP_INTERLEAVE_NONE,
        CU_TENSOR_MAP_SWIZZLE_128B, CU_TENSOR_MAP_L2_PROMOTION_L2_128B, CU_TENSOR_MAP_FLOAT_OOB_FILL_NONE);
    enc(&am.wt, CU_TENSOR_MAP_DATA_TYPE_BFLOAT16, 3, (void*)wqkvA, dw, sw, bt, es, CU_TENSOR_MAP_INTERLEAVE_NONE,
        CU_TENSOR_MAP_SWIZZLE_NONE, CU_TENSOR_MAP_L2_PROMOTION_NONE, CU_TENSOR_MAP_FLOAT_OOB_FILL_NONE);
    cuuint64_t dz[3] = {KCAT, 2, S_LEN / 2}, sz[2] = {KCAT * 2, KCAT * 4};
    cuuint32_t bz[3] = {72, 1, 57};
    enc(&am.oa, CU_TENSOR_MAP_DATA_TYPE_BFLOAT16, 3, pO, dz, sz, bz, es, CU_TENSOR_MAP_INTERLEAVE_NONE,
        CU_TENSOR_MAP_SWIZZLE_NONE, CU_TENSOR_MAP_L2_PROMOTION_NONE, CU_TENSOR_MAP_FLOAT_OOB_FILL_NONE);
  }
  {
    cuuint64_t dims[3] = {64, S_LEN, KCAT / 64}, strides[2] = {KCAT * 2, 128};
    cuuint32_t box[3] = {64, 32, 9}, es[3] = {1, 1, 1};
    make_map(enc, &am.o, pO, S_LEN, KCAT, 32);
    enc(&am.o3, CU_TENSOR_MAP_DATA_TYPE_BFLOAT16, 3, pO, dims, strides, box, es, CU_TENSOR_MAP_INTERLEAVE_NONE,
        CU_TENSOR_MAP_SWIZZLE_128B, CU_TENSOR_MAP_L2_PROMOTION_L2_128B, CU_TENSOR_MAP_FLOAT_OOB_FILL_NONE);
  }
  make_map(enc, &am.wob, Wo, 4096, DM, 64);
  make_map(enc, &am.woa, woA, DM, DM, 64);
  make_map(enc, &am.wo8, woA, DM, DM, 8);
  {
    cuuint64_t dims[2] = {KCAT, S_LEN}, strides[1] = {KCAT * 2};
    cuuint32_t box[2] = {8, 32}, es[2] = {1, 1};
    enc(&am.o8, CU_TENSOR_MAP_DATA_TYPE_BFLOAT16, 2, pO, dims, strides, box, es, CU_TENSOR_MAP_INTERLEAVE_NONE,
        CU_TENSOR_MAP_SWIZZLE_NONE, CU_TENSOR_MAP_L2_PROMOTION_NONE, CU_TENSOR_MAP_FLOAT_OOB_FILL_NONE);
  }

  rec_kernel<<<96, 384, SM_TOTAL, cudaStreamPerThread>>>(rm, x, mem0);
  cudaLaunchConfig_t cfg = {};
  cfg.gridDim = dim3(NAUX); cfg.blockDim = dim3(512); cfg.dynamicSmemBytes = A_TOTAL; cfg.stream = cudaStreamPerThread;
  cudaLaunchAttribute at[1];
  at[0].id = cudaLaunchAttributeProgrammaticStreamSerialization; at[0].val.programmaticStreamSerializationAllowed = 1;
  cfg.attrs = at; cfg.numAttrs = 1;
  if (XP & 16) cfg.numAttrs = 0;
  if (!(XP & 64)) cudaLaunchKernelEx(&cfg, aux_kernel, am, wqkvA, woA, gate_w, (bf16*)d_out);
}
```

```cpp
#include <cuda_runtime.h>
#include <cuda_bf16.h>
#include <cuda_fp16.h>
#include <cuda.h>
#include <stdint.h>

typedef __nv_bfloat16 bf16;

constexpr int S_LEN = 2048, DM = 576, NH = 32, DH = 128, NSEG = 64, KCAT = 4096 + 576;
constexpr int NAUXSEG = NSEG - 2;
constexpr int NAUX = 36;
#define RED_LINE(i) (((i) >> 2) * 4096 + ((i) & 1) * 256 + ((i) & 2) * 512)
#define RED_SLOT(s) (((s) & 1) * 128 + ((s) & 2) * 256)

#define POLL_NS 848
#define NII 14
#define W3PRE 4
#define W3MID 4
#define GF 0
#define B5POS 0
#define NUP 4
#define UPF 1
#define B3Q 9
#define B3F 0
#define GATE 7
#define NTL 2
#define B7R 1
#define VS0 1
#define VS1 0
#define VLATE(w) ((w) == 0 ? VS0 == 1 : (w) == 1 ? VS1 == 1 : false)
#define HOIST 0
#define RSLOW 0
#define CSY 0
#define DD 2
#define N12 18
#define N14 18
#define HP 0
#define HL 0
#define WL 1
#define RV 3
#define EXM 1
#define PSTAMP 0
#define PFIX 1
#define RET 1
#define TL 6
#define CLR 1
#define RFW 0
#define NIC 0
#define LEAD 0
#define FIN16 1
#define VXG 0
#define NRING 20
#define EXD 0
#define HDLY 0
#define F10 1
#define NPROBE 2
#define QM 0
#define N5 224
#define KP(i) (((i) >> 1) + 4 * ((i) & 1))
#define SPIN_LIMIT (1 << 14)
#define XP 0

__device__ __align__(1024) bf16 g_Ocat[S_LEN * KCAT];
__device__ __align__(1024) unsigned char g_red_raw[2 * 262144];
constexpr int HINT_OFF = 2048;
__device__ __align__(16) float g_gate[S_LEN];
__device__ __align__(128) uint4 g_stats[96 * 2];
__device__ unsigned g_epoch;
__device__ unsigned g_epoch2;
__device__ unsigned g_ocnt[NSEG * 64];
__device__ unsigned g_abar[3 * 32];
__device__ unsigned long long g_amax[2 * 16];
__device__ unsigned g_scnt[NSEG * 32 * 8];
__device__ __align__(1024) unsigned char g_seg[NRING * 96 * 10240];
__device__ unsigned g_used[NH * 32];
__device__ __align__(1024) uint2 g_part[8 * 9 * 64 * 64];
__device__ int g_err;
#define MSTAMP(i)
#define TSTAMP(i)
#define PROF(idx)
#define PROFP(idx)
#define RSTAMP(k)
#define STAMP(idx)
#define ASTAMP(idx)
#define SSTAMP(k, seg)
#define WSTAMP(idx)

#define DI __device__ __forceinline__
DI uint32_t smem_u32(const void* p) { return (uint32_t)__cvta_generic_to_shared(p); }
DI uint32_t clock32() { uint32_t c; asm volatile("mov.u32 %0, %%clock;" : "=r"(c) :: "memory"); return c; }
DI uint32_t gtime() { uint32_t c; asm volatile("mov.u32 %0, %%globaltimer_lo;" : "=r"(c) :: "memory"); return c; }
DI uint32_t ldg_relaxed32(const void* p) { uint32_t v; asm volatile("ld.relaxed.gpu.global.b32 %0, [%1];" : "=r"(v) : "l"(p) : "memory"); return v; }
DI uint32_t ldg_acquire32(const void* p) { uint32_t v; asm volatile("ld.acquire.gpu.global.b32 %0, [%1];" : "=r"(v) : "l"(p) : "memory"); return v; }
DI void stg_relaxed32(void* p, uint32_t v) { asm volatile("st.relaxed.gpu.global.b32 [%0], %1;" :: "l"(p), "r"(v) : "memory"); }
DI int head_id() { int c; asm volatile("mov.u32 %0, %%clusterid.x;" : "=r"(c)); return c; }
DI uint32_t mapa(uint32_t a, uint32_t r) { uint32_t o; asm("mapa.shared::cluster.u32 %0, %1, %2;" : "=r"(o) : "r"(a), "r"(r)); return o; }
DI void cluster_arrive() { asm volatile("barrier.cluster.arrive.relaxed.aligned;" ::: "memory"); }
DI void cluster_wait() { asm volatile("barrier.cluster.wait.aligned;" ::: "memory"); }
DI void cluster_sync() { asm volatile("barrier.cluster.arrive.release.aligned;\nbarrier.cluster.wait.acquire.aligned;" ::: "memory"); }
DI void mbar_init(uint32_t b, uint32_t c) { asm volatile("mbarrier.init.shared::cta.b64 [%0], %1;" :: "r"(b), "r"(c) : "memory"); }
DI void mbar_expect(uint32_t b, uint32_t tx) { asm volatile("mbarrier.arrive.expect_tx.shared::cta.b64 _, [%0], %1;" :: "r"(b), "r"(tx) : "memory"); }
DI void mbar_arrive(uint32_t b) { asm volatile("mbarrier.arrive.shared::cta.b64 _, [%0];" :: "r"(b) : "memory"); }
DI void mbar_wait(uint32_t b, uint32_t par) {
  asm volatile("{\n.reg .pred p;\n.reg .u32 n, q;\nmov.u32 n, 0;\n"
               "WL: add.u32 n, n, 1;\nshr.u32 q, n, 12;\nxor.b32 q, q, %1;\n"
               "mbarrier.try_wait.parity.shared::cta.b64 p, [%0], q;\n@!p bra.uni WL;\n}"
               :: "r"(b), "r"(par) : "memory");
}
DI bool mbar_test(uint32_t b, uint32_t par) {
  uint32_t r;
  asm volatile("{\n.reg .pred p;\nmbarrier.test_wait.parity.shared::cta.b64 p, [%1], %2;\nselp.u32 %0, 1, 0, p;\n}" : "=r"(r) : "r"(b), "r"(par) : "memory");
  return r;
}
DI void mbar_wait_fast(uint32_t b, uint32_t par) {
  asm volatile("{\n.reg .pred p;\n.reg .u32 n, q;\nmbarrier.try_wait.parity.shared::cta.b64 p, [%0], %1;\n@p bra.uni WD;\nmov.u32 n, 0;\n"
               "WL: add.u32 n, n, 1;\nshr.u32 q, n, 12;\nxor.b32 q, q, %1;\n"
               "mbarrier.try_wait.parity.shared::cta.b64 p, [%0], q;\n@!p bra.uni WL;\nWD:\n}"
               :: "r"(b), "r"(par) : "memory");
}
DI void wait_until(uint32_t t) {
  const uint32_t now = gtime();
  t = min(t, now + 8192);
  asm volatile("{\n.reg .pred p;\n.reg .u32 c;\nTL: mov.u32 c, %%globaltimer_lo;\nsetp.lt.u32 p, c, %0;\n@p bra.uni TL;\n}" :: "r"(t) : "memory");
}
#define PIN(v) v = __shfl_xor_sync(0xffffffffu, v, 0)
#define SCHED_FENCE(k) asm volatile("{\n.reg .pred p;\nsetp.eq.u32 p, %0, %1;\n@p exit;\n}" :: "r"(fence_reg), "r"(k) : "memory")
#define MEM_ORDER(k) asm volatile("{\n.reg .pred p;\nsetp.eq.u32 p, %0, %1;\n@p st.shared.u32 [%0], %0;\n}" :: "r"(fence_reg), "r"(k + 64) : "memory")
DI void bar_sync(int id, int n) { asm volatile("bar.sync %0, %1;" :: "r"(id), "r"(n) : "memory"); }
DI void bar_arrive(int id, int n) { asm volatile("bar.arrive %0, %1;" :: "r"(id), "r"(n) : "memory"); }
DI void fence_async() { asm volatile("fence.proxy.async.shared::cta;" ::: "memory"); }
DI void st_async4(uint32_t a, uint32_t x, uint32_t y, uint32_t z, uint32_t w, uint32_t mb) {
  asm volatile("st.async.weak.shared::cluster.mbarrier::complete_tx::bytes.v4.b32 [%0], {%1,%2,%3,%4}, [%5];"
               :: "r"(a), "r"(x), "r"(y), "r"(z), "r"(w), "r"(mb) : "memory");
}
DI void st_async2(uint32_t a, uint32_t x, uint32_t y, uint32_t mb) {
  asm volatile("st.async.weak.shared::cluster.mbarrier::complete_tx::bytes.v2.b32 [%0], {%1,%2}, [%3];"
               :: "r"(a), "r"(x), "r"(y), "r"(mb) : "memory");
}
DI void sts32(uint32_t a, uint32_t x) { asm volatile("st.shared.b32 [%0], %1;" :: "r"(a), "r"(x) : "memory"); }
DI void sts64(uint32_t a, uint32_t x, uint32_t y) { asm volatile("st.shared.v2.b32 [%0], {%1,%2};" :: "r"(a), "r"(x), "r"(y) : "memory"); }
DI void sts128(uint32_t a, uint32_t x, uint32_t y, uint32_t z, uint32_t w) {
  asm volatile("st.shared.v4.b32 [%0], {%1,%2,%3,%4};" :: "r"(a), "r"(x), "r"(y), "r"(z), "r"(w) : "memory");
}
DI uint32_t lds32(uint32_t a) { uint32_t x; asm volatile("ld.shared.b32 %0, [%1];" : "=r"(x) : "r"(a) : "memory"); return x; }
DI void lds64(uint32_t a, uint32_t& x, uint32_t& y) { asm volatile("ld.shared.v2.b32 {%0,%1}, [%2];" : "=r"(x), "=r"(y) : "r"(a) : "memory"); }
DI void lds128(uint32_t a, uint32_t* r) {
  asm volatile("ld.shared.v4.b32 {%0,%1,%2,%3}, [%4];" : "=r"(r[0]), "=r"(r[1]), "=r"(r[2]), "=r"(r[3]) : "r"(a) : "memory");
}
DI void lds128f(uint32_t a, float* r) {
  asm volatile("ld.shared.v4.f32 {%0,%1,%2,%3}, [%4];" : "=f"(r[0]), "=f"(r[1]), "=f"(r[2]), "=f"(r[3]) : "r"(a) : "memory");
}
DI void lds64f(uint32_t a, float* r) { asm volatile("ld.shared.v2.f32 {%0,%1}, [%2];" : "=f"(r[0]), "=f"(r[1]) : "r"(a) : "memory"); }
DI void ldsm4t(uint32_t* r, uint32_t a) {
  asm volatile("ldmatrix.sync.aligned.m8n8.x4.trans.shared.b16 {%0,%1,%2,%3}, [%4];"
               : "=r"(r[0]), "=r"(r[1]), "=r"(r[2]), "=r"(r[3]) : "r"(a) : "memory");
}
DI void ldsm4t_in(uint32_t* r, uint32_t a, uint32_t t) {
  asm volatile("{\n.reg .pred p;\nsetp.ne.u32 p, %5, 0;\n@p ldmatrix.sync.aligned.m8n8.x4.trans.shared.b16 {%0,%1,%2,%3}, [%4];\n}"
               : "+r"(r[0]), "+r"(r[1]), "+r"(r[2]), "+r"(r[3]) : "r"(a), "r"(t) : "memory");
}
DI void lds128_in(uint32_t* r, uint32_t a, uint32_t t) {
  asm volatile("{\n.reg .pred p;\nsetp.ne.u32 p, %5, 0;\n@p ld.shared.v4.b32 {%0,%1,%2,%3}, [%4];\n}"
               : "+r"(r[0]), "+r"(r[1]), "+r"(r[2]), "+r"(r[3]) : "r"(a), "r"(t) : "memory");
}
DI void ldsm2t_in(uint32_t* r, uint32_t a, uint32_t t) {
  asm volatile("{\n.reg .pred p;\nsetp.ne.u32 p, %3, 0;\n@p ldmatrix.sync.aligned.m8n8.x2.trans.shared.b16 {%0,%1}, [%2];\n}" : "+r"(r[0]), "+r"(r[1]) : "r"(a), "r"(t) : "memory");
}
DI void reserve2(uint32_t* r) { asm volatile("{\n.reg .u64 t;\nmov.u64 t, %%clock64;\nmov.b64 {%0, %1}, t;\n}" : "=r"(r[0]), "=r"(r[1])); }
DI void scale_sum(float& x, float& y, float s, uint32_t t) {
  asm volatile("{\n.reg .pred p;\nsetp.ne.u32 p, %2, 0;\n@p mul.f32 %0, %0, %1;\n}" : "+f"(y) : "f"(s), "r"(t));
  asm volatile("{\n.reg .pred p;\nsetp.ne.u32 p, %3, 1;\n@p fma.rn.f32 %0, %0, %1, %2;\n}" : "+f"(x) : "f"(s), "f"(y), "r"(t));
}
DI void ldsm4(uint32_t* r, uint32_t a) {
  asm volatile("ldmatrix.sync.aligned.m8n8.x4.shared.b16 {%0,%1,%2,%3}, [%4];"
               : "=r"(r[0]), "=r"(r[1]), "=r"(r[2]), "=r"(r[3]) : "r"(a) : "memory");
}
DI void st_async1(uint32_t a, uint32_t x, uint32_t mb) {
  asm volatile("st.async.weak.shared::cluster.mbarrier::complete_tx::bytes.b32 [%0], %1, [%2];" :: "r"(a), "r"(x), "r"(mb) : "memory");
}
DI void stsm4(uint32_t a, uint32_t x, uint32_t y, uint32_t z, uint32_t w) {
  asm volatile("stmatrix.sync.aligned.m8n8.x4.shared.b16 [%0], {%1,%2,%3,%4};" :: "r"(a), "r"(x), "r"(y), "r"(z), "r"(w) : "memory");
}
DI void stsm4t(uint32_t a, uint32_t x, uint32_t y, uint32_t z, uint32_t w) {
  asm volatile("stmatrix.sync.aligned.m8n8.x4.trans.shared.b16 [%0], {%1,%2,%3,%4};" :: "r"(a), "r"(x), "r"(y), "r"(z), "r"(w) : "memory");
}
DI uint32_t pack_bf16(float lo, float hi) { uint32_t r; asm("cvt.rn.bf16x2.f32 %0, %1, %2;" : "=r"(r) : "f"(hi), "f"(lo)); return r; }
DI uint32_t pack_f16(float lo, float hi) { uint32_t r; asm("cvt.rn.f16x2.f32 %0, %1, %2;" : "=r"(r) : "f"(hi), "f"(lo)); return r; }
DI float ex2(float x) { float y; asm("ex2.approx.ftz.f32 %0, %1;" : "=f"(y) : "f"(x)); return y; }
DI float rcp(float x) { float y; asm("rcp.approx.ftz.f32 %0, %1;" : "=f"(y) : "f"(x)); return y; }
DI float bf_lo(uint32_t x) { return __uint_as_float(x << 16); }
DI float bf_hi(uint32_t x) { return __uint_as_float(x & 0xffff0000u); }
DI void mma16816(float* d, const uint32_t* a, uint32_t b0, uint32_t b1) {
  asm volatile("mma.sync.aligned.m16n8k16.row.col.f32.bf16.bf16.f32 {%0,%1,%2,%3}, {%4,%5,%6,%7}, {%8,%9}, {%0,%1,%2,%3};"
               : "+f"(d[0]), "+f"(d[1]), "+f"(d[2]), "+f"(d[3]) : "r"(a[0]), "r"(a[1]), "r"(a[2]), "r"(a[3]), "r"(b0), "r"(b1));
}
DI void mma16816z(float* d, const uint32_t* a, uint32_t b0, uint32_t b1) {
  asm volatile("mma.sync.aligned.m16n8k16.row.col.f32.bf16.bf16.f32 {%0,%1,%2,%3}, {%4,%5,%6,%7}, {%8,%9}, {%10,%10,%10,%10};"
               : "=f"(d[0]), "=f"(d[1]), "=f"(d[2]), "=f"(d[3]) : "r"(a[0]), "r"(a[1]), "r"(a[2]), "r"(a[3]), "r"(b0), "r"(b1), "f"(0.f));
}
DI void mma1688z(float* d, uint32_t a0, uint32_t a1, uint32_t b0) {
  asm volatile("mma.sync.aligned.m16n8k8.row.col.f32.bf16.bf16.f32 {%0,%1,%2,%3}, {%4,%5}, {%6}, {%7,%7,%7,%7};"
               : "=f"(d[0]), "=f"(d[1]), "=f"(d[2]), "=f"(d[3]) : "r"(a0), "r"(a1), "r"(b0), "f"(0.f));
}
DI void mma1688(float* d, uint32_t a0, uint32_t a1, uint32_t b0) {
  asm volatile("mma.sync.aligned.m16n8k8.row.col.f32.bf16.bf16.f32 {%0,%1,%2,%3}, {%4,%5}, {%6}, {%0,%1,%2,%3};"
               : "+f"(d[0]), "+f"(d[1]), "+f"(d[2]), "+f"(d[3]) : "r"(a0), "r"(a1), "r"(b0));
}
DI void ldsm2t(uint32_t* r, uint32_t a) {
  asm volatile("ldmatrix.sync.aligned.m8n8.x2.trans.shared.b16 {%0,%1}, [%2];" : "=r"(r[0]), "=r"(r[1]) : "r"(a) : "memory");
}
DI uint32_t add_bf16(uint32_t a, uint32_t b) { uint32_t r; asm("add.rn.bf16x2 %0, %1, %2;" : "=r"(r) : "r"(a), "r"(b)); return r; }
DI uint32_t mul_bf16(uint32_t a, uint32_t b) { uint32_t r; asm("mul.rn.bf16x2 %0, %1, %2;" : "=r"(r) : "r"(a), "r"(b)); return r; }
DI uint64_t make_desc(uint32_t addr, uint32_t lbo, uint32_t sbo, uint32_t swz) {
  return (uint64_t)((addr & 0x3FFFF) >> 4) | ((uint64_t)(lbo >> 4) << 16) | ((uint64_t)(sbo >> 4) << 32) | ((uint64_t)swz << 62);
}
DI uint64_t desc_at(uint32_t a16, uint32_t lbo, uint32_t sbo, uint32_t swz) {
  uint64_t d; asm("mov.b64 %0, {%1, %2};" : "=l"(d) : "r"(a16 + ((lbo >> 4) << 16)), "r"((sbo >> 4) | (swz << 30)));
  return d;
}
#define WG_FENCE() asm volatile("wgmma.fence.sync.aligned;" ::: "memory")
#define WG_COMMIT() asm volatile("wgmma.commit_group.sync.aligned;" ::: "memory")
#define WG_WAIT(n) asm volatile("wgmma.wait_group.sync.aligned %0;" :: "n"(n) : "memory")
#define ACC8(d, o) "+f"(d[o]), "+f"(d[o + 1]), "+f"(d[o + 2]), "+f"(d[o + 3]), "+f"(d[o + 4]), "+f"(d[o + 5]), "+f"(d[o + 6]), "+f"(d[o + 7])
DI void wgmma_n32_rs(float* d, uint32_t a0, uint32_t a1, uint32_t a2, uint32_t a3, uint64_t db, int acc) {
  asm volatile("{\n.reg .pred p;\nsetp.ne.b32 p, %21, 0;\n"
               "wgmma.mma_async.sync.aligned.m64n32k16.f32.bf16.bf16 {%0,%1,%2,%3,%4,%5,%6,%7,%8,%9,%10,%11,%12,%13,%14,%15}, "
               "{%16,%17,%18,%19}, %20, p, 1, 1, 0;\n}\n"
               : ACC8(d, 0), ACC8(d, 8) : "r"(a0), "r"(a1), "r"(a2), "r"(a3), "l"(db), "r"(acc));
}
template <int TA>
DI void wgmma_n32_ss(float* d, uint64_t da, uint64_t db, int acc) {
  asm volatile("{\n.reg .pred p;\nsetp.ne.b32 p, %18, 0;\n"
               "wgmma.mma_async.sync.aligned.m64n32k16.f32.bf16.bf16 {%0,%1,%2,%3,%4,%5,%6,%7,%8,%9,%10,%11,%12,%13,%14,%15}, "
               "%16, %17, p, 1, 1, %19, 1;\n}\n"
               : ACC8(d, 0), ACC8(d, 8) : "l"(da), "l"(db), "r"(acc), "n"(TA));
}
DI void tma_load(uint32_t dst, const CUtensorMap* m, int c0, int c1, uint32_t mb) {
  asm volatile("cp.async.bulk.tensor.2d.shared::cluster.global.mbarrier::complete_tx::bytes [%0], [%1, {%3, %4}], [%2];"
               :: "r"(dst), "l"(m), "r"(mb), "r"(c0), "r"(c1) : "memory");
}
DI void tma_load3(uint32_t dst, const CUtensorMap* m, int row, uint32_t mb) {
  asm volatile("cp.async.bulk.tensor.3d.shared::cluster.global.mbarrier::complete_tx::bytes [%0], [%1, {%3, %4, %3}], [%2];"
               :: "r"(dst), "l"(m), "r"(mb), "r"(0), "r"(row) : "memory");
}
DI bool elect_one() {
  uint32_t p;
  asm volatile("{\n.reg .pred p;\nelect.sync _|p, 0xffffffff;\nselp.u32 %0, 1, 0, p;\n}" : "=r"(p));
  return p;
}
DI void bulk_s2s(uint32_t dst, uint32_t src, uint32_t bytes, uint32_t mb) {
  asm volatile("cp.async.bulk.shared::cluster.shared::cta.mbarrier::complete_tx::bytes [%0], [%1], %2, [%3];"
               :: "r"(dst), "r"(src), "r"(bytes), "r"(mb) : "memory");
}
DI void tma_prefetch(const CUtensorMap* m, int c0, int c1) {
  asm volatile("cp.async.bulk.prefetch.tensor.2d.L2.global.tile [%0, {%1, %2}];" :: "l"(m), "r"(c0), "r"(c1) : "memory");
}
DI void tma_store(const CUtensorMap* m, uint32_t src, int c0, int c1) {
  asm volatile("cp.async.bulk.tensor.2d.global.shared::cta.bulk_group [%0, {%2, %3}], [%1];" :: "l"(m), "r"(src), "r"(c0), "r"(c1) : "memory");
}
DI uint4 ldg_relaxed(const void* p) {
  uint4 v;
  asm volatile("ld.relaxed.gpu.global.v4.b32 {%0,%1,%2,%3}, [%4];" : "=r"(v.x), "=r"(v.y), "=r"(v.z), "=r"(v.w) : "l"(p) : "memory");
  return v;
}
DI void stg_relaxed(void* p, uint32_t x, uint32_t y, uint32_t z, uint32_t w) {
  asm volatile("st.relaxed.gpu.global.v4.b32 [%0], {%1,%2,%3,%4};" :: "l"(p), "r"(x), "r"(y), "r"(z), "r"(w) : "memory");
}
DI void red_f16x8(void* p, uint32_t x, uint32_t y, uint32_t z, uint32_t w) {
  asm volatile("red.relaxed.gpu.global.add.noftz.v4.f16x2 [%0], {%1,%2,%3,%4};" :: "l"(p), "r"(x), "r"(y), "r"(z), "r"(w) : "memory");
}
DI void sq_acc(uint32_t& a, uint32_t x) { asm("fma.rn.bf16x2 %0, %1, %1, %0;" : "+r"(a) : "r"(x)); }
DI __half2 amax4(__half2 h, const uint32_t* v) {
  h = __hmax2_nan(__hmax2_nan(h, __habs2(*(const __half2*)&v[0])), __habs2(*(const __half2*)&v[1]));
  return __hmax2_nan(__hmax2_nan(h, __habs2(*(const __half2*)&v[2])), __habs2(*(const __half2*)&v[3]));
}
DI uint32_t wexp(__half2 h) { const uint32_t u = *(const uint32_t*)&h; return __reduce_max_sync(0xffffffffu, max((u >> 16) & 0x7fffu, u & 0x7fffu)) >> 7; }
DI float max10(const float* a) {
  return fmaxf(fmaxf(fmaxf(fmaxf(a[0], a[1]), fmaxf(a[2], a[3])), fmaxf(fmaxf(a[4], a[5]), fmaxf(a[6], a[7]))), fmaxf(a[8], a[9]));
}
DI float quad_max(float m) {
  return fmaxf(fmaxf(m, __shfl_xor_sync(0xffffffffu, m, 1)), fmaxf(__shfl_xor_sync(0xffffffffu, m, 2), __shfl_xor_sync(0xffffffffu, m, 3)));
}
DI float warp_sum(float v) {
#pragma unroll
  for (int o = 16; o; o >>= 1) v += __shfl_xor_sync(0xffffffffu, v, o);
  return v;
}

constexpr int SM_WO3 = 0;
constexpr int SM_X = 16384;
constexpr int XT = 36864;
constexpr int SM_EXP = 126976;
constexpr int SEGB = 10240;
constexpr int SM_BLK = SM_EXP + 8192;
constexpr int SM_VC = SM_BLK + 4 * SEGB;
constexpr int SM_PART = SM_VC + 16384;
constexpr int SM_QM = SM_PART + 4096;
constexpr int SM_E = SM_QM + 1024;
constexpr int SM_VM = SM_E + 1536;
constexpr int SM_OB = SM_VM + 2048;
constexpr int SM_FB = SM_OB + 2048;
constexpr int SM_STAGE = SM_X + XT;
constexpr int SM_MISC = 210944;
constexpr int SM_WOST = 212992;
constexpr int SM_MEM = SM_WOST;
constexpr int SM_MAX = SM_MEM + 11264;
#define MEM_BLK(q) ((q) / 3 * 4096 + (q) % 3 * 1024)
constexpr int SM_TOTAL = 229376;
constexpr int MB_W = SM_MISC;
constexpr int MB_WO = SM_MISC + 24;
constexpr int MB_WO3 = SM_MISC + 32;
constexpr int MB_X = SM_MISC + 40;
constexpr int MB_S = SM_MISC + 64;
constexpr int MB_F = SM_MISC + 72;
constexpr int MB_VX = SM_MISC + 80;
constexpr int SC_FPAR = SM_MISC + 136;
constexpr int SC_DEAD = SM_MISC + 96;
constexpr int SC_UNSC = SM_MISC + 112;
constexpr int SC_EPOCH = SM_MISC + 128;
constexpr int SC_EXPW = SM_MISC + 132;
constexpr int SC_ONES = SM_MISC + 144;
constexpr int SC_SS = SM_MISC + 160;
constexpr int SC_LAT = SM_MISC + 224;
constexpr int MB_T = SM_MISC + 232;
constexpr int T_SX = SM_X + XT;
constexpr int T_OB = SM_X + 2 * XT;
constexpr int T_WA = T_OB + 16384;
constexpr int T_OA = T_WA + 9216;
constexpr int T_G = T_OA + 4096;
constexpr int T_P = T_G + 512;
constexpr int T_UN = T_G + 256;
constexpr int T_RED = 131072;
constexpr int SC_XMAX = SM_MISC + 256;
constexpr int SC_PROF = 229376;

constexpr float SM_SCALE = 0.08838834764831845f;
constexpr float LOG2E = 1.4426950408889634f;
constexpr float E_LIM = 20.f;

template <bool B> struct BoolC { static constexpr bool value = B; };
struct RMaps { CUtensorMap x, wq, wk, wv, wo, woa, oa; unsigned char* red; bf16* out; uint32_t poll; };

DI uint32_t latest_hint(uint32_t h, uint32_t d, int s) {
  const uint32_t x = (((h | 0xc0c0c0c0u) - ((d >> 5) & 63) * 0x01010101u) & 0x3f3f3f3fu) | ((h ^ (((s >> 2) + 1) & 3) * 0x40404040u) & 0xc0c0c0c0u);
  const uint32_t y = __vmaxu2(x & 0x00ff00ffu, (x >> 8) & 0x00ff00ffu);
  return __reduce_max_sync(0xffffffffu, max(y & 0xffffu, y >> 16));
}
DI uint32_t near_half(uint32_t sb) {
  uint32_t a, b; lds64(sb + SC_LAT, a, b);
  return a > b;
}

template <int RT, int K0, int K1, bool D32 = false, int BAR = 0, int KB = 18>
DI void xproj(float* acc, const uint32_t (&wa)[2][18][4], uint64_t xd) {
  if (XP & 1) return;
  WG_FENCE();
#pragma unroll
  for (int k = K0; k < ((XP & 128) ? K0 + 1 : K1); k++)
  {
    uint64_t d = xd + (uint64_t)(((k >> 1) * 4096 + (k & 1) * 32) >> 4);
    if (D32) asm("mov.b64 %0, {%1, %2};" : "=l"(d) : "r"((uint32_t)xd + (((k >> 1) * 4096 + (k & 1) * 32) >> 4)), "r"((uint32_t)(xd >> 32)));
    wgmma_n32_rs(acc, wa[RT][k][0], wa[RT][k][1], wa[RT][k][2], wa[RT][k][3], d, k != 0);
    if (BAR && k == KB - 1 && KB < 18) bar_arrive(BAR, 256);
  }
  WG_COMMIT();
}

DI void seg_store(int seg, uint32_t sb, uint32_t off, uint32_t bytes) {
  asm volatile("cp.async.bulk.global.shared::cta.bulk_group [%0], [%1], %2;"
               :: "l"(g_seg + ((size_t)(seg % NRING) * 96 + blockIdx.x) * SEGB + off), "r"(sb + SM_BLK + (seg & 3) * SEGB + off), "r"(bytes) : "memory");
  asm volatile("cp.async.bulk.commit_group;" ::: "memory");
}
DI void seg_publish(int seg) {
  asm volatile("cp.async.bulk.wait_group 0;" ::: "memory");
  asm volatile("red.relaxed.gpu.global.add.u32 [%0], 1;" :: "l"(&g_scnt[(seg * 32 + blockIdx.x / 3) * 8]) : "memory");
  SSTAMP(10, seg);
}

#define NAP 64
DI uint32_t movm(uint32_t x) { uint32_t r; asm volatile("movmatrix.sync.aligned.m8n8.trans.b16 %0, %1;" : "=r"(r) : "r"(x)); return r; }
DI bool wait_count(const unsigned* p, unsigned target, bool nap = true) {
  int n = 0;
  unsigned v;
  while (true) {
    asm volatile("ld.acquire.gpu.global.b32 %0, [%1];" : "=r"(v) : "l"(p) : "memory");
    if ((int)(v - target) >= 0 || ++n > SPIN_LIMIT) break;
    if (nap) __nanosleep(NAP);
  }
  return n;
}
#define PACE 1200
#define PACE2 600
#define PACE3 (3 * PACE)
#define PORD 0
DI void load_weights(uint32_t sb, const RMaps& tm, uint32_t rank, int c) {
  const int h = blockIdx.x / 3;
  if (c < 3) {
    mbar_expect(sb + MB_W + 8 * c, 49152);
    tma_load(sb + SM_STAGE + c * 49152, rank < 2 ? &tm.wk : &tm.wv, h * DH + (rank == 1 ? 64 : 0), c * 192, sb + MB_W + 8 * c);
    tma_load(sb + SM_STAGE + c * 49152 + 24576, rank < 2 ? &tm.wq : &tm.wv, h * DH + (rank == 0 ? 0 : 64), c * 192, sb + MB_W + 8 * c);
  } else {
    tma_prefetch(&tm.wo, rank * 192, h * DH);
    mbar_expect(sb + MB_WO, 16384);
    mbar_expect(sb + MB_WO3, 32768);
    tma_load(sb + SM_WOST, &tm.wo, rank * 192 + 64, h * DH, sb + MB_WO3);
    tma_load(sb + SM_WO3, &tm.wo, rank * 192 + 128, h * DH, sb + MB_WO3);
  }
}

DI void tail_attention(const uint32_t sb, const uint32_t rank, const int w, const int lane, const int sg, const int bar) {
  const int m = lane >> 3, g = lane >> 2, t = lane & 3;
  const uint32_t l16 = sb + lane * 16, src = l16 + T_SX + sg * 10240 + w * 1280;
  if (rank < 2) {
    const uint32_t base = l16 + SM_BLK + (2 + sg) * SEGB, dst = src + rank * 5120;
    uint32_t qb[2][4];
    ldsm4t(qb[0], base + w * 1024); ldsm4t(qb[1], base + w * 1024 + 512);
#pragma unroll
    for (int j = 0; j < 3; j++) {
      uint32_t kb[4][4];
      float c[4][4];
      const uint32_t ka = base + 4096 + j * 2048 + (m & 1) * (j == 2 ? 128 : 896) - (m >> 1) * 128;
#pragma unroll
      for (int k = 0; k < 4; k += j == 2 ? 2 : 1) ldsm4t(kb[k], ka + k * 256);
      mma16816z(c[0], kb[0], qb[0][0], qb[0][1]); mma16816z(c[1], kb[j == 2 ? 0 : 1], qb[0][2], qb[0][3]);
      mma16816z(c[2], kb[2], qb[1][0], qb[1][1]); mma16816z(c[3], kb[j == 2 ? 2 : 3], qb[1][2], qb[1][3]);
      uint32_t r[4];
#pragma unroll
      for (int i = 0; i < (j == 2 ? 2 : 4); i++) r[i] = __float_as_uint((c[0][i] + c[1][j == 2 ? i + 2 : i]) + (c[2][i] + c[3][j == 2 ? i + 2 : i]));
#pragma unroll
      for (int d = 0; d < 2; d++) {
        const uint32_t to = d ? 2 : rank ^ 1, mb = mapa(sb + MB_T + 8 + 8 * sg, to);
        if (j < 2) st_async4(mapa(dst + j * 512, to), r[0], r[1], r[2], r[3], mb);
        else st_async2(mapa(dst + 1024 - lane * 8, to), r[0], r[1], mb);
      }
      if (j < 2) sts128(dst + j * 512, r[0], r[1], r[2], r[3]); else sts64(dst + 1024 - lane * 8, r[0], r[1]);
    }
  }
  TSTAMP(50 + 2 * sg);
  uint32_t vx[4][4], vm[4];
  const uint32_t va = l16 + (rank < 2 ? SM_VC + sg * 8192 : SM_BLK + (2 + sg) * SEGB) + w * 1024 + (m & 1) * 384 - (m >> 1) * 128;
#pragma unroll
  for (int i = 0; i < 4; i++) ldsm4(vx[i], va + (i & 1) * 4096 + (i >> 1) * 256);
  if (sg && rank < 2) mbar_wait(sb + MB_T, 0);
  lds128(l16 + (sg ? SM_FB : SM_VM) + w * 512, vm);
  float a[10], b[10];
  mbar_wait(sb + MB_T + 8 + 8 * sg, 0);
  TSTAMP(58 + 2 * sg);
  lds128f(src, a); lds128f(src + 512, a + 4); lds64f(src + 1024 - lane * 8, a + 8);
  lds128f(src + 5120, b); lds128f(src + 5632, b + 4); lds64f(src + 6144 - lane * 8, b + 8);
#pragma unroll
  for (int i = 0; i < 10; i++) {
    a[i] = (a[i] + b[i]) * (SM_SCALE * LOG2E);
    if (i < 8 && (i >> 1) * 8 + g > w * 8 + 2 * t + (i & 1)) a[i] = -1.0e9f * LOG2E;
  }
  float m0 = fmaxf(fmaxf(fmaxf(a[0], a[2]), fmaxf(a[4], a[6])), a[8]), m1 = fmaxf(fmaxf(fmaxf(a[1], a[3]), fmaxf(a[5], a[7])), a[9]);
#pragma unroll
  for (int o = 4; o < 32; o <<= 1) { m0 = fmaxf(m0, __shfl_xor_sync(0xffffffffu, m0, o)); m1 = fmaxf(m1, __shfl_xor_sync(0xffffffffu, m1, o)); }
#pragma unroll
  for (int i = 0; i < 10; i++) a[i] = ex2(a[i] - (i & 1 ? m1 : m0));
  float s0 = ((a[0] + a[2]) + (a[4] + a[6])) + a[8], s1 = ((a[1] + a[3]) + (a[5] + a[7])) + a[9];
#pragma unroll
  for (int o = 4; o < 32; o <<= 1) { s0 += __shfl_xor_sync(0xffffffffu, s0, o); s1 += __shfl_xor_sync(0xffffffffu, s1, o); }
  s0 = rcp(s0); s1 = rcp(s1);
#pragma unroll
  for (int i = 0; i < 5; i++) sts32(sb + T_P + sg * 2560 + w * 640 + i * 128 + lane * 4, pack_bf16(a[2 * i] * s0, a[2 * i + 1] * s1));
  mbar_wait(sb + MB_WO, 1);
  bar_sync(bar, 128);
  TSTAMP(59 + 2 * sg);
#pragma unroll
  for (int j = 0; j < 4; j++) {
    uint32_t p[5];
    float o0[4], o1[4], f[2];
    lds64f(sb + T_G + sg * 128 + j * 32 + t * 8, f);
    f[0] = 1.f - f[0]; f[1] = 1.f - f[1];
    ldsm4t(p, l16 + T_P + sg * 2560 + j * 640);
    asm volatile("ldmatrix.sync.aligned.m8n8.x1.trans.shared.b16 {%0}, [%1];" : "=r"(p[4]) : "r"(l16 + T_P + sg * 2560 + j * 640 + 512) : "memory");
    mma16816z(o0, vx[0], p[0], p[1]); mma16816z(o1, vx[1], p[0], p[1]);
    mma16816(o0, vx[2], p[2], p[3]); mma16816(o1, vx[3], p[2], p[3]);
    mma1688(o0, vm[0], vm[1], p[4]); mma1688(o1, vm[2], vm[3], p[4]);
    stsm4(l16 + T_OB + sg * 8192 + j * 2048 + w * 512, pack_bf16(o0[0] * f[0], o0[1] * f[1]), pack_bf16(o0[2] * f[0], o0[3] * f[1]),
          pack_bf16(o1[0] * f[0], o1[1] * f[1]), pack_bf16(o1[2] * f[0], o1[3] * f[1]));
  }
}

DI void proj_role(const uint32_t sb, const RMaps& tm, const uint32_t rank, const int wg, const int w, const int lane) {
  const bool qk = rank < 2;
  uint32_t wa[2][18][4];
  {
    const int rr = (lane & 7) + ((lane >> 4) << 3);
    const uint32_t col = ((2 * w + ((lane >> 3) & 1)) ^ (lane & 7)) << 4;
    float ss = 0.f;
#pragma unroll
    for (int c = 0; c < 3; c++) {
      mbar_wait(sb + MB_W + 8 * c, 0);
      if (threadIdx.x == 0) SSTAMP(11, c);
#pragma unroll
      for (int rt = 0; rt < 2; rt++)
#pragma unroll
        for (int k = 0; k < 6; k++)
          ldsm4t(wa[rt][c * 6 + k], sb + SM_STAGE + c * 49152 + (rt ^ wg) * 24576 + (64 * (k >> 1) + 32 * wg + 16 * (k & 1) + rr) * 128 + col);
      if (c < 2) {
        fence_async();
        bar_sync(3, 256);
        if (threadIdx.x == 0) {
          if (c == 0) tma_load3(sb + SM_X + XT, &tm.x, 32, sb + MB_X + 8);
          else { tma_load(sb + SM_X + 2 * XT, &tm.wo, rank * 192, (blockIdx.x / 3) * DH, sb + MB_WO); SSTAMP(11, 11); }
        }
        __syncwarp();
      }
      uint32_t q[4] = {0, 0, 0, 0};
#pragma unroll
      for (int rt = 0; rt < 2; rt++)
#pragma unroll
        for (int k = 0; k < 6; k++)
#pragma unroll
          for (int i = 0; i < 4; i++) sq_acc(q[i], wa[rt][c * 6 + k][i]);
#pragma unroll
      for (int i = 0; i < 4; i++) ss += bf_lo(q[i]) + bf_hi(q[i]);
    }
    ss = warp_sum(ss);
    fence_async();
    cluster_arrive();
    if (lane == 0) sts32(sb + SC_SS + 4 * (wg * 4 + w), qk ? 0 : __float_as_uint(ss));
    bar_arrive(11, 384);
  }
  STAMP(1);
  MSTAMP(0);
  mbar_wait(sb + MB_X, 0);
  STAMP(2);

  uint32_t t16 = sb + (w * 32 + lane) * 16;
  uint32_t mem_a = sb + SM_MEM + wg * 512 + lane * 16;
  uint32_t fin_a = sb + (lane & 7) * 16 + SM_BLK + (qk ? (wg ^ 1) * 4096 + w * 256 + (lane & 8) * 16 + (lane & 16) * 64
                                              : wg * 4096 + w * 1024 + (lane & 8) * 64 + (lane & 16) * 8);
  PIN(t16); PIN(mem_a); PIN(fin_a);
  const uint32_t fence_reg = mem_a;
  const uint32_t fin2 = qk ? 2048 : 256;
  float acc[16];
  const uint64_t xd0 = make_desc(sb + SM_X + wg * 64, 16, 1024, 1);
  auto do_export = [&]() {
    WG_WAIT(0);
    uint32_t q[8];
#pragma unroll
    for (int j = 0; j < 8; j++) q[j] = pack_bf16(acc[2 * j], acc[2 * j + 1]);
    sts128(t16 + SM_EXP + wg * 4096, q[0], q[1], q[2], q[3]);
    sts128(t16 + SM_EXP + wg * 4096 + 2048, q[4], q[5], q[6], q[7]);
    if (RET) asm volatile("{\n.reg .pred p;\nsetp.eq.u32 p, %2, 0;\n@p add.u32 %0, %0, 1;\n@p add.u32 %1, %1, 1;\nsetp.eq.and.u32 p, %0, %1, p;\n@p exit;\n}"
                          : "+r"(q[3]), "+r"(q[7]) : "r"(t16) : "memory");
  };
  uint32_t o[8];
  auto import = [&]() { lds128(t16 + SM_EXP + (wg ^ 1) * 4096, o); lds128(t16 + SM_EXP + (wg ^ 1) * 4096 + 2048, o + 4); };
  auto finish = [&](int seg) {
    const uint32_t a = fin_a + (seg & 3) * SEGB;
    WG_WAIT(0);
#pragma unroll
    for (int i = 0; i < 8; i++) o[i] = FIN16 ? add_bf16(pack_bf16(acc[2 * i], acc[2 * i + 1]), o[i]) : pack_bf16(acc[2 * i] + bf_lo(o[i]), acc[2 * i + 1] + bf_hi(o[i]));
    stsm4(a, o[0], o[1], o[2], o[3]);
    stsm4(a + fin2, o[4], o[5], o[6], o[7]);
  };
  auto send_v = [&](int seg, int dst) {
    fence_async();
    if (seg < NSEG && !(XP & 2) && elect_one())
      bulk_s2s(mapa(sb + SM_VC + (seg & 1) * 8192, dst), sb + SM_BLK + (seg & 3) * SEGB, 8192, mapa(sb + MB_VX + (seg & 1) * 8, dst));
    __syncwarp();
  };
  auto wait_v = [&](int seg) {
    if (seg < NSEG && !(XP & 2)) {
      mbar_wait(sb + MB_VX + (seg & 1) * 8, (seg >> 1) & 1);
      if (elect_one()) mbar_expect(sb + MB_VX + (seg & 1) * 8, 8192);
      __syncwarp();
    }
  };
  bar_sync(3, 256);
  xproj<1, 0, 18>(acc, wa, xd0);
  do_export();
  SCHED_FENCE(11);
  xproj<0, 0, 18>(acc, wa, xd0);
  bar_sync(3, 256);
  if (threadIdx.x == 0) SSTAMP(11, 12);
  MSTAMP(1);
  cluster_wait();
  if (threadIdx.x == 0) SSTAMP(11, 13);
  mbar_wait(sb + MB_X + 8, 0);
  import();
  finish(0);
  SCHED_FENCE(12);
  bar_sync(3, 256);
  uint64_t dA = xd0 + (XT >> 4);
  xproj<1, 0, 18>(acc, wa, dA);
  if (!qk && wg == 0 && w < 2) send_v(0, w);
  do_export();
  if (qk && wg == 0 && w == 0) wait_v(0);
  bar_arrive(13, 384);
  if (!qk) {
    SCHED_FENCE(15);
    xproj<0, 0, 18>(acc, wa, dA);
    if (threadIdx.x == 0 && !(XP & 8)) { mbar_expect(sb + MB_X, XT); tma_load3(sb + SM_X, &tm.x, 96, sb + MB_X); }
    bar_sync(3, 256);
    mbar_wait(sb + MB_X + 16, 0);
    import();
    finish(1);
    SCHED_FENCE(16);
    bar_sync(3, 256);
    dA += XT >> 4;
    xproj<1, 0, 18>(acc, wa, dA);
    if (wg == 0 && ((w == 0 && VS0) || (w == 1 && VS1))) send_v(1, w);
    do_export();
  }
  if (threadIdx.x == 0) SSTAMP(11, 14);
  MSTAMP(2);
  bar_sync(0, 384);
  const int ro = __shfl_sync(0xffffffffu, near_half(sb) ^ wg, 0);
  STAMP(5);
  const uint32_t always = __shfl_sync(0xffffffffu, lds32(sb + SC_DEAD + 12), 0);
  const int ah = qk ? 1 : 2;
  int b2 = qk ? 2 : 0;
  int s = 0;
  uint32_t hint_lo = (uint32_t)(uint64_t)tm.red + HINT_OFF + blockIdx.x + (lane & 1) * 4096 + (lane >> 1) * 16384;
  PIN(hint_lo);
  auto post_hint = [&]() {
    asm volatile("{\n.reg .pred p;\n.reg .b64 a;\n.reg .u32 t;\nsetp.lt.u32 p, %0, %1;\nmov.b64 a, {%2, %3};\nmov.u32 t, %%globaltimer_lo;\n"
                 "bfe.u32 t, t, 5, 6;\nor.b32 t, t, %4;\n@p st.relaxed.gpu.global.u8 [a], t;\n}"
                 :: "r"(t16), "r"(sb + 128), "r"(hint_lo + RED_SLOT(s)), "r"((uint32_t)((uint64_t)tm.red >> 32)), "r"(((s >> 2) + 1) << 6) : "memory");
  };
  auto memproj = [&](auto second, int id, float u0, float u1, float* r) {
    constexpr bool R1 = decltype(second)::value;
    uint32_t b[NUP][4], b0[4];
    SCHED_FENCE(id);
    bar_sync(R1 ? 2 : 1, 256);
    PROF(0);
    ldsm4t(b0, mem_a);
#pragma unroll
    for (int q = 0; q < NUP; q++) {
      if (R1 && q == 2) {
        bar_sync(11, 256);
        SCHED_FENCE(id + 1);
      }
      ldsm4t(b[q], mem_a + MEM_BLK(q + 1));
    }
    mma16816z(&acc[0], wa[0][0], b0[0], b0[1]);
    mma16816z(&acc[4], wa[1][0], b0[0], b0[1]);
    mma16816z(&acc[8], wa[0][1], b0[2], b0[3]);
    mma16816z(&acc[12], wa[1][1], b0[2], b0[3]);
#pragma unroll
    for (int q = 1; q < 9; q++) {
      uint32_t* const c = b[(q - 1) % NUP];
      mma16816(&acc[0], wa[0][2 * q], c[0], c[1]);
      mma16816(&acc[4], wa[1][2 * q], c[0], c[1]);
      mma16816(&acc[8], wa[0][2 * q + 1], c[2], c[3]);
      mma16816(&acc[12], wa[1][2 * q + 1], c[2], c[3]);
      if (R1 && q + NUP == B3Q) bar_sync(3, 256);
      if (q + NUP < 9) ldsm4t_in(c, mem_a + MEM_BLK(q + NUP), always);
      else if (R1 && q + NUP < 11) lds128_in(c, t16 + SM_PART + (10 - q - NUP) * 2048, always);
      else if (!R1 && GATE && q == GATE) { bar_arrive(11, 256); lds128_in(c, sb + SC_DEAD, always); u0 = u1 = __uint_as_float(c[3]); }
    }
#pragma unroll
    for (int i = 0; i < 8; i++) {
      const float u = i < 4 ? u0 : u1;
      r[i] = R1 ? fmaf(acc[8 + i], u, (acc[i] + __uint_as_float(b[(8 + i / 4) % NUP][i & 3])) * u) : (GATE ? fmaf(acc[i], u, acc[8 + i]) : acc[i] + acc[8 + i]);
    }
  };
  if (ro == 0) {
    auto set_scale = [&]() {
      uint32_t m[8];
      lds128(t16 + SM_MAX - 512, m); lds128(t16 + SM_MAX, m + 4);
      const int em = (wexp(amax4(amax4(*(const __half2*)&m[0], m), m + 4)) >> 3) + (int)(lds32(sb + SC_UNSC + (s & 1) * 8) >> 23) - 15;
      const int ex = max(s ? em : 0, (int)lds32(sb + SC_XMAX + 4 * s)) - 127 + (int)lds32(sb + SC_EXPW);
      sts32(sb + SC_UNSC + (~s & 1) * 8, (127 + min(max(ex, -120), 120)) << 23);
    };
#pragma unroll 1
    while (true) {
      if (s == 8) STAMP(6);
      float r[8];
      memproj(BoolC<false>(), 30, 0.f, 0.f, r);
      sts128(t16 + SM_PART, __float_as_uint(r[0]), __float_as_uint(r[1]), __float_as_uint(r[2]), __float_as_uint(r[3]));
      sts128(t16 + SM_PART + 2048, __float_as_uint(r[4]), __float_as_uint(r[5]), __float_as_uint(r[6]), __float_as_uint(r[7]));
      bar_arrive(3, 256);
      PROF(1);
      bar_sync(9, 256);
      if (s == NSEG - 1) break;
      post_hint();
      if (w == 1) {
        set_scale();
        __syncwarp();
        if (elect_one()) mbar_arrive(sb + MB_S);
      }
      SCHED_FENCE(9);
      bar_sync(5, qk ? N5 : 256);
      PROF(2);
      import();
      xproj<0, 0, NII, (DD & 1) != 0>(acc, wa, dA);
      if (NII < 18) {
        if (qk) bar_sync(7, 384);
        xproj<0, NII, 18>(acc, wa, dA);
        if (!qk) bar_sync(7, 384);
      } else {
        if (F10) WG_WAIT(0);
        bar_sync(10, 256);
        if (F10) SCHED_FENCE(17);
      }
      dA += (int64_t)(b2 ? XT >> 4 : -(XT >> 3));
      finish(s + ah);
      if (qk || !VLATE(w)) bar_arrive(13, 384);
      PROF(6);
      SCHED_FENCE(14);
      bar_sync(12, 256);
      PROF(7);
      xproj<1, 0, 18, (DD & 2) != 0, 14, N14>(acc, wa, dA);
      if (N14 == 18) bar_arrive(14, 256);
      b2 = b2 == 2 ? 0 : b2 + 1;
      s++;
      if (!qk && VLATE(w)) { bar_sync(13, 384); send_v(s + 1, w); }
      PROFP(8);
      do_export();
      s--; RSTAMP(6); s++;
      PROFP(3);
    }
    if (!qk) bar_arrive(5, 256);
    if (w == 0 && elect_one()) {
      const uint32_t h18 = blockIdx.x / 3 * 18;
      mbar_expect(sb + MB_WO, 9216 + 4096 + 256);
      asm volatile("cp.async.bulk.shared::cluster.global.mbarrier::complete_tx::bytes [%0], [%1], 256, [%2];"
                   :: "r"(sb + T_G), "l"(g_gate + NAUXSEG * 32), "r"(sb + MB_WO) : "memory");
      tma_load(sb + T_OA, &tm.oa, 4096 + (h18 & ~7), NAUXSEG * 32, sb + MB_WO);
#pragma unroll 1
      for (int j = 0; j < 3; j++) tma_load(sb + T_WA + j * 3072, &tm.woa, rank * 192 + j * 64, h18, sb + MB_WO);
    }
    if (w == 1) {
      set_scale();
      __syncwarp();
      const int ea = (int)ldg_relaxed32(&g_amax[0]) + (int)ldg_relaxed32(&g_amax[16]) - 254 + 2 + 10 - 15;
      sts32(sb + T_UN + (lane & 1) * 4, (128 + max(min(ea, 120), (int)(lds32(sb + SC_UNSC + 8 - (lane & 1) * 8) >> 23) - 127)) << 23);
    }
    bar_arrive(8, 256);
  } else {
    uint32_t r0;
    float un;
    auto prepare = [&]() {
      un = __uint_as_float(lds32(sb + SC_UNSC + (s & 1) * 8));
      r0 = qk ? (t16 & ~256u) - w * 256 + (((t16 >> 8) ^ wg) & 1 ? SM_QM : SM_BLK + 8192 + (s & 3) * SEGB) : mapa(t16 + (s < NSEG - 1 ? SM_VM : SM_FB), 0);
      PIN(r0); PIN(un);
    };
    auto mem_out = [&](int off, uint32_t lo, uint32_t hi) {
      unsigned char* const d = g_seg + ((size_t)(s % NRING) * 96 + blockIdx.x) * SEGB + 8192 + off + w * 256 + ((t16 >> 2) & 124);
      if (!(XP & 4)) { stg_relaxed32(d, lo); stg_relaxed32(d + 128, hi); }
    };
    prepare();
#pragma unroll 1
    while (true) {
      if (s == 8) STAMP(6);
      float r[8];
      if (qk) {
        const float u0 = wg ? un * (SM_SCALE * LOG2E) : un, u1 = wg ? un : un * (SM_SCALE * LOG2E);
        memproj(BoolC<true>(), 32, u0, u1, r);
        const uint32_t p0 = pack_bf16(r[0], r[1]), p1 = pack_bf16(r[2], r[3]), p2 = pack_bf16(r[4], r[5]), p3 = pack_bf16(r[6], r[7]);
        stsm4(r0, p0, p1, p2, p3);
        bar_arrive(4, 256);
        if (EXM) { SCHED_FENCE(18); mem_out(0, wg ? p2 : p0, wg ? p3 : p1); }
      } else {
        const uint32_t mb = sb + (s < NSEG - 1 ? MB_S : MB_T), r1 = r0 + (1 << 24);
        memproj(BoolC<true>(), 34, un, un, r);
        const uint32_t p0 = pack_bf16(r[0], r[1]), p1 = pack_bf16(r[2], r[3]), p2 = pack_bf16(r[4], r[5]), p3 = pack_bf16(r[6], r[7]);
        const uint32_t v0 = wg ? p2 : p0, v1 = wg ? p3 : p1, v2 = wg ? p0 : p2, v3 = wg ? p1 : p3;
        st_async4(r0, v0, v1, v2, v3, mapa(mb, 0));
        st_async4(r1, v0, v1, v2, v3, mapa(mb, 1));
        bar_arrive(5, 256);
        sts128(r0 + (2 << 24), v0, v1, v2, v3);
        stsm4((t16 & ~256u) - w * 256 + SM_BLK + 8192 + (s & 3) * SEGB + (((t16 >> 8) ^ wg) & 1) * 1024, p0, p1, p2, p3);
        __syncwarp();
        if (elect_one()) mbar_arrive(sb + MB_S);
        __syncwarp();
        if (EXM) { SCHED_FENCE(19); mem_out(0, v0, v1); mem_out(1024, v2, v3); }
      }
      if (s == NSEG - 1) break;
      if (!qk && !EXM) bar_arrive(15, 160);
      PROF(1);
      auto rearm = [&]() { mbar_wait(sb + MB_S, s & 1); if (elect_one()) mbar_expect(sb + MB_S, qk ? 640 + 2048 : 1280); __syncwarp(); };
      if (w == 1) {
        if ((t16 & 384) == 0) stg_relaxed(tm.red + (RED_SLOT(s + 2) + RED_LINE(blockIdx.x)) + (t16 & 112), 0, 0, 0, 0);
      } else if (w == 0) {
        const int tn = s + ah + 1;
        if (RFW) mbar_wait(sb + MB_S, s & 1);
        if (tn + 1 < NSEG && !(XP & 8) && elect_one()) {
          const int b0 = b2 == 2 ? 0 : b2 + 1;
          mbar_expect(sb + MB_X + 8 * b0, XT);
          tma_load3(sb + SM_X + b0 * XT, &tm.x, (tn + 1) * 32, sb + MB_X + 8 * b0);
        }
        if (tn < NSEG && (!(XP & 8) || tn < 3)) mbar_wait(sb + MB_X + 8 * b2, (tn / 3) & 1);
      } else if (w == 2) {
        if (!qk) { if (VS0 == 0) send_v(s + 1, 0); if (VS1 == 0) send_v(s + 1, 1); }
      } else if (qk || !NIC) {
        rearm();
      }
      __syncwarp();
      import();
      PROF(4);
      SCHED_FENCE(10);
      if (NIC) {
        if (qk) bar_sync(7, NII < 18 ? 384 : 256);
        xproj<0, 0, NIC>(acc, wa, dA);
        if (!qk) { if (w == 3) rearm(); bar_sync(7, NII < 18 ? 384 : 256); }
      } else {
        bar_sync(7, NII < 18 ? 384 : 256);
      }
      xproj<0, NIC, 18, (DD & 4) != 0, 12, N12>(acc, wa, dA);
      if (N12 == 18) bar_arrive(12, 256);
      dA += (int64_t)(b2 ? XT >> 4 : -(XT >> 3));
      finish(s + ah);
      if (qk && w == 0) wait_v(s + 1);
      bar_arrive(13, 384);
      PROF(6);
      SCHED_FENCE(13);
      bar_sync(14, 256);
      PROF(7);
      xproj<1, 0, 18, (DD & 8) != 0>(acc, wa, dA);
      b2 = b2 == 2 ? 0 : b2 + 1;
      s++;
      if (HOIST) prepare();
      PROFP(8);
      do_export();
      if (!HOIST) prepare();
      s--; RSTAMP(7); s++;
      PROFP(3);
    }
    TSTAMP(2);
    bar_sync(3, 128);
    tail_attention(sb, rank, w, lane, 1, 3);
    bar_arrive(0, 256);
  }
  STAMP(3);
  if (CSY) cluster_sync();
  STAMP(4);
}

DI void attn_role(const uint32_t sb, unsigned char* smem_raw, const RMaps& tm, const uint32_t RANK, const bf16* __restrict__ x, const bf16* __restrict__ mem0,
                  const int w, const int lane) {
  const int t2 = w * 32 + lane;
  uint32_t wo[8][4], w1[8][4];
  const uint32_t wo_lane = sb + ((lane & 7) + ((lane >> 4) << 3)) * 128 + (((w + 4 * ((lane >> 3) & 1)) ^ (lane & 7)) << 4);
  unsigned char* const g_red = tm.red;
  {
    const uint32_t t0 = gtime();
    const uint32_t tag = *(volatile unsigned*)&g_epoch + 1;
    if (w == 0) {
      stg_relaxed(g_red + RED_SLOT(t2 >> 3) + RED_LINE(blockIdx.x) + (t2 & 7) * 16, 0, 0, 0, 0);
      stg_relaxed(g_red + T_RED + blockIdx.x * 1024 + t2 * 16, 0, 0, 0, 0);
      stg_relaxed(g_red + T_RED + blockIdx.x * 1024 + 512 + t2 * 16, 0, 0, 0, 0);
      asm volatile("st.relaxed.gpu.global.u8 [%0], 0;" :: "l"(g_red + RED_SLOT(t2) + HINT_OFF + (t2 & 4) * 1024 + (t2 >> 3) * 16384 + blockIdx.x) : "memory");
    }
    bar_sync(0, 384);
    cluster_arrive();
    if (PACE && w == 3) {
#pragma unroll 1
      for (int c = 1; c < 4; c++) {
        wait_until(t0 + (c == 3 ? PACE3 : c * (RANK < 2 ? PACE : PACE2)));
        if (elect_one()) load_weights(sb, tm, RANK, PORD ? (c == 1 ? 3 : c - 1) : c);
        __syncwarp();
      }
    }
    uint4 xv[18];
    uint32_t mv[20];
#pragma unroll
    for (int i = 0; i < 20; i++) mv[i] = i < 18 ? ((const uint32_t*)mem0)[(lane >> 2) * (DM / 2) + (w * 18 + i) * 4 + (lane & 3)] : 0;
#pragma unroll
    for (int i = 0; i < 18; i++) xv[i] = blockIdx.x < NSEG ? ((const uint4*)(x + blockIdx.x * 32 * DM))[t2 + 128 * i] : make_uint4(0, 0, 0, 0);
    __half2 hx = __float2half2_rn(0.f);
#pragma unroll
    for (int i = 0; i < 18; i++) hx = amax4(hx, &xv[i].x);
    if (blockIdx.x == 0)
#pragma unroll
      for (int i = 0; i < 5; i++) hx = amax4(hx, &mv[4 * i]);
    sts32(sb + SC_SS + 4 * (12 + w), wexp(hx));
    if (t2 == 0) { sts32(sb + SC_EPOCH, (tag - 1) * NSEG + 2 - NRING); sts32(sb + SC_UNSC, __float_as_uint(1.f)); sts128(sb + SC_DEAD, 0, 0, 0, 0x3f800000u); sts64(sb + SC_FPAR, 0, 0); sts128(sb + SC_ONES, 0x3f803f80u, 0x3f803f80u, 0x3f803f80u, 0x3f803f80u); }
    WSTAMP(27);
    if (w == 0) __threadfence();
    uint32_t q[8] = {0, 0, 0, 0, 0, 0, 0, 0};
    mbar_wait(sb + MB_WO3, 0);
    if (t2 == 0) SSTAMP(11, 3);
    MSTAMP(3);
#pragma unroll
    for (int k = 0; k < 8; k++) {
      ldsm4t(wo[k], wo_lane + SM_WO3 + k * 2048); ldsm4t(w1[k], wo_lane + SM_WOST + k * 2048);
#pragma unroll
      for (int i = 0; i < 4; i++) { sq_acc(q[i], wo[k][i]); sq_acc(q[i], w1[k][i]); }
    }
    bar_sync(6, 128);
    if (t2 == 0) SSTAMP(11, 7);
#pragma unroll
    for (int k = 0; k < 8; k++) sts128(sb + SM_WO3 + t2 * 16 + k * 2048, wo[k][0], wo[k][1], wo[k][2], wo[k][3]);
#pragma unroll
    for (int i = 0; i < 5; i++) {
      const int j = w * 18 + 4 * i + (lane >> 3), c = i < 4 || lane < 16 ? j * 8 + j / 24 * 64 : 192;
      stsm4t(sb + SM_MEM + (c + (lane & 7)) * 16, mv[4 * i], mv[4 * i + 1], mv[4 * i + 2], mv[4 * i + 3]);
    }
    bar_arrive(1, 256); bar_arrive(2, 256); bar_arrive(9, 256);
    if (t2 == 0) SSTAMP(11, 8);
    mbar_wait(sb + MB_WO, 0);
    if (t2 == 0) SSTAMP(11, 4);
#pragma unroll
    for (int k = 0; k < 8; k++) ldsm4t(wo[k], wo_lane + SM_X + 2 * XT + k * 2048);
    fence_async();
    bar_sync(6, 128);
    if (t2 == 32) tma_load3(sb + SM_X + 2 * XT, &tm.x, 64, sb + MB_X + 16);
    __syncwarp();
#pragma unroll
    for (int k = 0; k < 8; k++)
#pragma unroll
      for (int i = 0; i < 4; i++) sq_acc(q[4 + i], wo[k][i]);
    float ss = 0.f;
#pragma unroll
    for (int i = 0; i < 8; i++) ss += bf_lo(q[i]) + bf_hi(q[i]);
    ss = warp_sum(ss);
    if (lane == 0) sts32(sb + SC_SS + 4 * (8 + w), __float_as_uint(ss));
    if (t2 == 0) SSTAMP(11, 9);
    bar_sync(11, 384);
    if (t2 == 0) SSTAMP(11, 10);
    if (t2 == 0) {
      float a[16];
#pragma unroll
      for (int i = 0; i < 4; i++) lds128f(sb + SC_SS + 16 * i, &a[4 * i]);
      stg_relaxed(&g_stats[blockIdx.x * 2], __float_as_uint(((a[0] + a[1]) + (a[2] + a[3])) + ((a[4] + a[5]) + (a[6] + a[7]))),
                  __float_as_uint((a[8] + a[9]) + (a[10] + a[11])),
                  max(max(__float_as_uint(a[12]), __float_as_uint(a[13])), max(__float_as_uint(a[14]), __float_as_uint(a[15]))), tag);
    }
    __syncwarp();
    WSTAMP(24);
    MSTAMP(4);
    cluster_wait();
    if (w == 0) {
      uint4 v[3];
      int n = 0;
      while (true) {
#pragma unroll
        for (int i = 0; i < 3; i++) v[i] = ldg_relaxed(&g_stats[(i * 32 + lane) * 2]);
        if (__all_sync(0xffffffffu, v[0].w == tag && v[1].w == tag && v[2].w == tag) || ++n > SPIN_LIMIT) break;
        __nanosleep(100);
      }
      WSTAMP(25);
      MSTAMP(5);
      const float sv = warp_sum(__uint_as_float(v[0].x) + __uint_as_float(v[1].x) + __uint_as_float(v[2].x));
      const float so = warp_sum(__uint_as_float(v[0].y) + __uint_as_float(v[1].y) + __uint_as_float(v[2].y));
      const int expW = ((int)(__float_as_uint(sv) >> 23) + (int)(__float_as_uint(so) >> 23) - 254 + 2 + 10 + 1) >> 1;
      sts32(sb + SC_XMAX + 4 * lane, v[0].z); sts32(sb + SC_XMAX + 128 + 4 * lane, v[1].z);
      sts32(sb + SC_EXPW, expW + 1 - 15);
      if (blockIdx.x == 0 && lane == 0) *(volatile unsigned*)&g_epoch = tag;
      sts32(sb + SC_FPAR + 4, 1);
    } else if (w < 3) {
      const uint32_t u = blockIdx.x >> 4;
      unsigned char* const z = g_red + 98304 + (blockIdx.x & 15) * 128 + (u & 1) * 2048 + (u & 6) * 4096 + (((u >> 1) ^ w) & 1) * 4096 + lane * 4;
      stg_relaxed32(z, 0);
      uint32_t best = 0xffffffffu;
#pragma unroll 1
      for (int i = 0; i < 64; i++) {
        uint32_t last, dt;
        asm volatile("{\n.reg .pred p;\n.reg .u32 c, v;\nld.volatile.shared.u32 %0, [%3];\nmov.u32 c, %%clock;\n"
                     "atom.relaxed.gpu.global.exch.b32 v, [%2], 0;\nsetp.eq.u32 p, v, 0;\nmov.u32 %1, 0;\n@p mov.u32 %1, %%clock;\nsub.u32 %1, %1, c;\n}"
                     : "=r"(last), "=r"(dt) : "l"(z), "r"(sb + SC_FPAR + 4) : "memory");
        best = min(best, dt);
        if ((last || PFIX) && i >= NPROBE - 1) break;
      }
      sts32(sb + SC_LAT + (w - 1) * 4, best);
    }
    bar_sync(13, 384);
    bar_arrive(0, 384);
    WSTAMP(26);
    TSTAMP(1);
    MSTAMP(6);
  }

  const uint32_t nh = __shfl_sync(0xffffffffu, near_half(sb), 0);
  uint32_t l16 = sb + lane * 16;
  PIN(l16);
#define LV ((l16 >> 4) & 31)
#define fence_reg l16
  const uint32_t red_lo = (uint32_t)(uint64_t)g_red, red_hi = (uint32_t)((uint64_t)g_red >> 32);
  uint32_t lp;
  auto slot = [&](int s, uint32_t c, uint32_t ofs) {
    const uint32_t lo = lp | (red_lo + ((w >> 1) * 4 + (w & 1) * 2 + ((w ^ c) & 1)) * 4096 + RED_SLOT(s) + ofs);
    uint64_t a; asm("mov.b64 %0, {%1, %2};" : "=l"(a) : "r"(lo), "r"(red_hi));
    return (unsigned char*)a;
  };
  const uint32_t always = __shfl_sync(0xffffffffu, lds32(sb + SC_DEAD + 12), 0);
  const int mode0 = RANK < 2 ? w : w | 4;
  auto hint_addr = [&](int s) { return min(LV, 23u) * 4 + (red_lo + HINT_OFF + nh * 4096 + w * 16384 + RED_SLOT(s)); };
  auto load_hints = [&](uint32_t lo) {
    uint64_t a; asm("mov.b64 %0, {%1, %2};" : "=l"(a) : "r"(lo), "r"(red_hi));
    return ldg_relaxed32((const void*)a);
  };
  const uint32_t blk = RANK < 2 ? 9216 : SEGB;
  auto send_v = [&](int seg, int pos) {
    if (RANK == 2 && ((w == 0 && VS0 == pos) || (w == 1 && VS1 == pos)) && seg > 1 && seg < NSEG && !(XP & 2)) {
      if (elect_one()) {
        fence_async();
        bulk_s2s(mapa(sb + SM_VC + (seg & 1) * 8192, w), sb + SM_BLK + (seg & 3) * SEGB, 8192, mapa(sb + MB_VX + (seg & 1) * 8, w));
      }
      __syncwarp();
    }
  };
  int s = 0;
  uint32_t dl = __shfl_sync(0xffffffffu, gtime() - 768, 0);
  bool bad = false;
#pragma unroll 1
  while (true) {
    const uint32_t par = s & 1;
    uint32_t vx[4][4], oc[4], hints;
    if (HP == 2) { hints = hint_addr(s); PIN(hints); }
    auto load_vx = [&]() {
      const uint32_t va = l16 + (RANK < 2 ? SM_VC + par * 8192 : SM_BLK + (s & 3) * SEGB) + w * 1024 + ((LV >> 3) & 1) * 384 - (LV >> 4) * 128;
      if (WL & 4) lds128(sb + SC_ONES, oc);
#pragma unroll
      for (int i = 0; i < 4; i++) ldsm4(vx[i], va + (i & 1) * 4096 + (i >> 1) * 256);
    };
    auto retire = [&](uint32_t x) {
      asm volatile("{\n.reg .pred p;\nsetp.eq.u32 p, %0, 0;\n@p exit;\n}" :: "r"(vx[0][0] | vx[1][0] | vx[2][0] | vx[3][0] | x | ((WL & 4) ? oc[0] : 0)) : "memory");
    };
    auto scores = [&](auto memkeys, auto first, float* sc) {
      constexpr bool MK = decltype(memkeys)::value, FIRST = decltype(first)::value;
      uint32_t kb[4][4], qb[2][4];
      const uint32_t m = LV >> 3;
      uint32_t kaddr = l16 + SM_BLK + 4096 + (s & 3) * SEGB + w * 2048 + (m & 1) * (MK ? 128 : 896) - (m >> 1) * 128;
      if (MK) { PIN(kaddr); }
      else {
#pragma unroll
        for (int k = 0; k < 4; k++) ldsm4t(kb[k], kaddr + k * 256);
      }
      if (FIRST) { load_vx(); retire(MK ? kaddr : kb[0][0] | kb[1][0] | kb[2][0] | kb[3][0] | l16); bar_sync(4, 256); RSTAMP(4); PROF(4); }
      ldsm4t(qb[0], l16 + SM_QM);
      if (MK) ldsm4t(kb[0], kaddr);
      ldsm4t(qb[1], l16 + SM_QM + 512);
      if (MK) ldsm4t(kb[2], kaddr + 512);
      float c[4][4];
      mma16816z(c[0], kb[0], qb[0][0], qb[0][1]); mma16816z(c[1], kb[MK ? 0 : 1], qb[0][2], qb[0][3]);
      mma16816z(c[2], kb[2], qb[1][0], qb[1][1]); mma16816z(c[3], kb[MK ? 2 : 3], qb[1][2], qb[1][3]);
      if (FIRST && B5POS == 0) bar_arrive(5, N5);
#pragma unroll
      for (int i = 0; i < (MK ? 2 : 4); i++) sc[i] = ((c[0][i] + c[1][MK ? i + 2 : i]) + c[2][i]) + c[3][MK ? i + 2 : i];
    };
    auto send = [&](auto memkeys) {
      constexpr bool MK = decltype(memkeys)::value;
      constexpr int N = MK ? 1 : 2;
      const uint32_t sa = sb + LV * 4 + SM_E + (MK ? 1024 + RANK * 128 : RANK * 512 + w * 256);
      uint32_t ra[N][2], mb[N][2];
#pragma unroll
      for (int i = 0; i < N; i++)
#pragma unroll
        for (int j = 0; j < 2; j++) {
          ra[i][j] = mapa(sa + i * 128, j ? 2 : RANK ^ 1); mb[i][j] = mapa(sb + MB_S, j ? 2 : RANK ^ 1);
          PIN(ra[i][j]);
        }
      float sc[4];
      scores(memkeys, BoolC<true>(), sc);
      uint32_t e[N];
#pragma unroll
      for (int i = 0; i < N; i++) {
        e[i] = pack_bf16(ex2(sc[2 * i]), ex2(sc[2 * i + 1]));
        if (!(fmaxf(fabsf(sc[2 * i]), fabsf(sc[2 * i + 1])) <= E_LIM)) e[i] = 0x7fff7fffu;
        st_async1(ra[i][0], e[i], mb[i][0]);
        st_async1(ra[i][1], e[i], mb[i][1]);
      }
#pragma unroll
      for (int i = 0; i < N; i++) sts32(sa + i * 128, e[i]);
      __syncwarp();
      if (l16 == sb) mbar_arrive(sb + MB_S);
      PROF(5);
    };
    const int mode = bad ? 8 : mode0;
    if (mode < 2) {
      send(BoolC<false>());
    } else if (mode == 2) {
      send(BoolC<true>());
    } else if (mode == 8) {
      load_vx();
      retire(l16);
      const uint32_t fp = lds32(sb + SC_FPAR);
      bar_sync(6, 128);
      if (w == 0 && l16 == sb) { sts32(sb + SC_FPAR, fp ^ 1); mbar_expect(sb + MB_F, 3072); }
      if (RANK < 2 && w < 3) {
        float sc[4] = {0.f, 0.f, 0.f, 0.f};
        if (w < 2) scores(BoolC<false>(), BoolC<false>(), sc); else scores(BoolC<true>(), BoolC<false>(), sc);
#pragma unroll 1
        for (int r = 0; r < 3; r++)
          st_async4(mapa(l16 + SM_FB + RANK * 1536 + w * 512, r), __float_as_uint(sc[0]), __float_as_uint(sc[1]), __float_as_uint(sc[2]), __float_as_uint(sc[3]), mapa(sb + MB_F, r));
      }
      mbar_wait(sb + MB_F, fp);
      float a[12];
#pragma unroll
      for (int j = 0; j < 3; j++) {
        float b[4];
        lds128f(l16 + SM_FB + j * 512, a + 4 * j); lds128f(l16 + SM_FB + 1536 + j * 512, b);
#pragma unroll
        for (int i = 0; i < 4; i++) a[4 * j + i] += b[i];
      }
      float m0 = fmaxf(fmaxf(fmaxf(a[0], a[2]), fmaxf(a[4], a[6])), a[8]), m1 = fmaxf(fmaxf(fmaxf(a[1], a[3]), fmaxf(a[5], a[7])), a[9]);
#pragma unroll
      for (int o = 4; o < 32; o <<= 1) { m0 = fmaxf(m0, __shfl_xor_sync(0xffffffffu, m0, o)); m1 = fmaxf(m1, __shfl_xor_sync(0xffffffffu, m1, o)); }
#pragma unroll
      for (int i = 0; i < 5; i++) {
        const uint32_t ea = sb + SM_E + LV * 4 + (i < 4 ? i * 128 : 1024);
        sts32(ea, pack_bf16(ex2(a[2 * i] - m0), ex2(a[2 * i + 1] - m1)));
        sts32(ea + (i < 4 ? 512 : 128), 0x3f803f80u);
      }
      __syncwarp();
    } else {
      load_vx();
      if (EXM && mode == 3) bar_arrive(4, 256);
      retire(l16 + 1);
      if (VS0 == 2 || VS1 == 2) send_v(s + 1, 2);
      if (w == 3) {
        uint32_t used = ldg_relaxed32(&g_used[blockIdx.x / 3 * 32]);
        if (!(XP & 4) && elect_one()) {
          if (s > 0) seg_publish(s - 1);
          fence_async();
          seg_store(s, sb, 0, 8192);
        }
        __syncwarp();
        if (!EXM) {
          bar_sync(RANK < 2 ? 4 : 15, RANK < 2 ? 256 : 160);
          if (!(XP & 4) && elect_one()) { fence_async(); seg_store(s, sb, 8192, blk - 8192); }
          __syncwarp();
        }
        const uint32_t need = lds32(sb + SC_EPOCH) + (s >= NRING - 1 ? s : -4 * NSEG);
#pragma unroll 1
        for (int n = 0; (int)(used - need) < 0 && n < ((XP & 64) ? 1 : SPIN_LIMIT); n++) used = ldg_relaxed32(&g_used[blockIdx.x / 3 * 32]);
      }
    }
    {
      uint32_t wa[4], wb[4];
      constexpr int WS = 2048;
      const uint32_t w3a = l16 + SM_WO3 + w * 512;
      if (HP == 1) { hints = hint_addr(s); PIN(hints); }
      if (!(WL & 1)) { lds128(w3a + KP(0) * WS, wa); lds128(w3a + KP(1) * WS, wb); }
      if (WL & 2) {
#pragma unroll
        for (int i = 0; i < 4; i++) oc[i] = always | (always >> 16) | (always & (i + 1));
      } else if (!(WL & 4)) lds128(sb + SC_ONES, oc);
      if (B5POS == 1 && mode < 3) bar_arrive(5, N5);
      uint32_t e[10], p[5], vm[4], ob[4];
      float o0[4], o1[4], f[3][2][4], rs[4];
      if (!(RV & 1)) { reserve2(vm); reserve2(vm + 2); }
      if (!(RV & 2)) reserve2(e + 8);
      if (!HP) { hints = hint_addr(s); PIN(hints); }
      if (CLR & 2) asm volatile("{\n.reg .pred p;\nsetp.eq.u32 p, %0, 0;\n@p exit;\n}" :: "r"(wa[0] | wb[0] | oc[0] | hints) : "memory");
      if (RV & 4) mbar_wait_fast(sb + MB_S, par); else mbar_wait(sb + MB_S, par);
      RSTAMP(5);
      PROF(6);
      if (RV & 2) { ldsm4t(e, l16 + SM_E); ldsm4t(e + 4, l16 + SM_E + 512); ldsm2t(e + 8, l16 + SM_E + 1024); }
      else { ldsm4t(e, l16 + SM_E); ldsm2t_in(e + 8, l16 + SM_E + 1024, always); ldsm4t(e + 4, l16 + SM_E + 512); }
      if (RV & 1) lds128(l16 + w * 512 + SM_VM, vm); else lds128_in(vm, l16 + w * 512 + SM_VM, always);
      const float scl = __uint_as_float(lds32(sb + SC_UNSC + 8 - par * 8));
      if (HL == 0) hints = load_hints(hints);
      if (GF & 1) SCHED_FENCE(4);
#pragma unroll
      for (int i = 0; i < 4; i++) p[i] = mul_bf16(e[i], e[4 + i]);
      p[4] = mul_bf16(e[8], e[9]);
      if (HL) hints = load_hints(hints | (p[HL - 1] & always & 1));
      mma16816z(o0, vx[0], p[0], p[1]);
      if (WL & 1) { lds128_in(vx[0], w3a + KP(0) * WS, always); }
      mma16816z(o1, vx[1], p[0], p[1]);
      if (WL & 1) { lds128_in(vx[1], w3a + KP(1) * WS, always); }
      mma16816z(rs, oc, p[0], p[1]);
      mma16816(o0, vx[2], p[2], p[3]); lds128_in(vx[2], w3a + KP(2) * WS, always);
      mma16816(o1, vx[3], p[2], p[3]); lds128_in(vx[3], w3a + KP(3) * WS, always);
      mma16816(rs, oc, p[2], p[3]);
      mma1688(o0, vm[0], vm[1], p[4]); mma1688(o1, vm[2], vm[3], p[4]); mma1688(rs, oc[0], oc[1], p[4]);
      stsm4(l16 + w * 512 + SM_OB, pack_bf16(o0[0], o0[1]), pack_bf16(o0[2], o0[3]), pack_bf16(o1[0], o1[1]), pack_bf16(o1[2], o1[3]));
      bar_sync(6, 128);
      RSTAMP(3);
      PROF(7);
      ldsm4t_in(oc, l16 + SM_OB, always);
      bad = __any_sync(0xffffffffu, !(rs[0] + rs[1] > 0.f) && !bad);
      rs[0] *= scl; rs[1] *= scl;
      asm volatile("{\n.reg .pred p;\nsetp.ne.u32 p, %1, 0;\n@p rcp.approx.ftz.f32 %0, %0;\n}" : "+f"(rs[0]) : "r"(always));
      asm volatile("{\n.reg .pred p;\nsetp.ne.u32 p, %1, 1;\n@p rcp.approx.ftz.f32 %0, %0;\n}" : "+f"(rs[1]) : "r"(always));
      asm volatile("lop3.b32 %0, %1, %2, %3, 0xfe;" : "=r"(lp) : "r"((l16 & 128) * 2), "r"((l16 & 256) * 4), "r"(l16 & 112));
      if (bad) continue;
      ldsm4t(ob, l16 + SM_OB + 512);
      mma16816z(f[2][0], WL & 1 ? vx[0] : wa, oc[0], oc[1]); mma16816z(f[2][1], WL & 1 ? vx[1] : wb, oc[2], oc[3]);
      mma16816z(f[0][0], wo[0], oc[0], oc[1]); mma16816z(f[0][1], wo[4], oc[2], oc[3]);
      mma16816z(f[1][0], w1[0], oc[0], oc[1]); mma16816z(f[1][1], w1[4], oc[2], oc[3]);
      ldsm4t_in(oc, l16 + SM_OB + 1024, always);
      mma16816(f[2][0], vx[2], ob[0], ob[1]); lds128_in(vx[2], w3a + KP(4) * WS, always);
      mma16816(f[2][1], vx[3], ob[2], ob[3]); lds128_in(vx[3], w3a + KP(5) * WS, always);
      mma16816(f[0][0], wo[1], ob[0], ob[1]); mma16816(f[0][1], wo[5], ob[2], ob[3]);
      mma16816(f[1][0], w1[1], ob[0], ob[1]); mma16816(f[1][1], w1[5], ob[2], ob[3]);
      ldsm4t_in(ob, l16 + SM_OB + 1536, always);
      mma16816(f[0][0], wo[2], oc[0], oc[1]); mma16816(f[0][1], wo[6], oc[2], oc[3]);
      mma16816(f[2][0], vx[2], oc[0], oc[1]); lds128_in(vx[2], w3a + KP(6) * WS, always);
      mma16816(f[2][1], vx[3], oc[2], oc[3]); lds128_in(vx[3], w3a + KP(7) * WS, always);
      mma16816(f[1][0], w1[2], oc[0], oc[1]); mma16816(f[1][1], w1[6], oc[2], oc[3]);
      mma16816(f[0][0], wo[3], ob[0], ob[1]); mma16816(f[0][1], wo[7], ob[2], ob[3]);
      mma16816(f[1][0], w1[3], ob[0], ob[1]); mma16816(f[1][1], w1[7], ob[2], ob[3]);
      mma16816(f[2][0], vx[2], ob[0], ob[1]); mma16816(f[2][1], vx[3], ob[2], ob[3]);
      bar_arrive(7, NII < 18 ? 384 : 256);
      lds128_in(ob, sb + SC_DEAD, always);
      uint32_t h[3][2];
#pragma unroll
      for (int j = 0; j < 3; j++)
#pragma unroll
        for (int i = 0; i < 2; i++)
        {
          scale_sum(f[j][1][2 * i], f[j][0][2 * i], rs[0], always); scale_sum(f[j][1][2 * i + 1], f[j][0][2 * i + 1], rs[1], always);
          h[j][i] = pack_f16(f[j][1][2 * i], f[j][1][2 * i + 1]);
        }
      const uint32_t rofs = RANK * 32768;
      red_f16x8(slot(s, RANK >> 1, rofs), h[0][0], h[1][0], h[2][0], 0x3c00u);
      red_f16x8(slot(s, (RANK >> 1) ^ 1, rofs), h[0][1], h[1][1], h[2][1], 0x3c00u);
      if (NII == 18) bar_arrive(10, 256);
      SCHED_FENCE(5);
      RSTAMP(0);
      l16 += ob[B7R];
    }
    {
    PROF(8);
    if (VS0 == 3 || VS1 == 3) send_v(s + 1, 3);
    const uint32_t ma0 = l16 + SM_MEM + w * 128 + (LV >> 3) * 896 + nh * 512;
    const unsigned char* const sl[2] = {slot(s, nh, 0), slot(s, nh ^ 1, 0)};
    uint32_t late = latest_hint(hints, dl, s);
    if (late >= 64) {
      int n = 0;
#pragma unroll 1
      do {
        late = latest_hint(load_hints(hint_addr(s)), dl, s);
      } while (late >= 64 && ++n < SPIN_LIMIT);
    }
    dl += late * 32 + tm.poll;
    if (s == 0 && PSTAMP) MSTAMP(7);
    PROF(9);
    {
      auto wait_until = [&](uint32_t t) {
        asm volatile("{\n.reg .pred p;\n.reg .s32 c;\n.reg .u64 t;\nTL: mov.u64 t, %%globaltimer;\ncvt.u32.u64 c, t;\nsub.s32 c, c, %0;\nsetp.lt.s32 p, c, 0;\n@p bra.uni TL;\n}" :: "r"(t + (l16 & 15)) : "memory");
      };
      uint4 v[2][3];
      auto load = [&](int c) {
#pragma unroll
        for (int r = 0; r < 3; r++) v[c][r] = ldg_relaxed(sl[c ^ (r >> 1)] + r * 32768);
      };
      auto decode = [&](int c, int n) {
        uint32_t q[9];
        __half2 hm;
        const uint32_t ma = ma0 ^ (c * 512);
#pragma unroll
        for (int i = 0; i < 9; i++) {
          const uint32_t h = i % 3 == 0 ? v[c][i / 3].x : (i % 3 == 1 ? v[c][i / 3].y : v[c][i / 3].z);
          const float2 f = __half22float2(*(const __half2*)&h);
          q[i] = pack_bf16(f.x, f.y);
          hm = i ? __hmax2(hm, __habs2(*(const __half2*)&h)) : __habs2(*(const __half2*)&h);
        }
#pragma unroll
        for (int r = 0; r < 3; r++) stsm4(ma + r * 4096, q[3 * r], q[3 * r + 1], q[3 * r + 2], r < 2 ? v[c][r].w : *(const uint32_t*)&hm);
        const bool done = __all_sync(0xffffffffu, v[c][0].w == 0x5000u && v[c][1].w == 0x5000u && v[c][2].w == 0x5000u) || n > SPIN_LIMIT;
        asm volatile("{\n.reg .pred p;\nsetp.ne.u32 p, %0, 0;\n@p bar.arrive %1, 256;\n}" :: "r"((int)done), "r"(1 + c) : "memory");
        return done;
      };
      if (LEAD) { wait_until(dl - LEAD); load(1); }
      wait_until(dl);
      PROF(10);
      int n = 0;
#pragma unroll 1
      do {
        load(0);
        if (!LEAD) load(1);
        asm volatile("{\n.reg .pred p;\nsetp.eq.u32 p, %0, 0;\n@p bar.sync 13, 384;\n}" :: "r"(n) : "memory");
      } while (!decode(0, n++));
      PROF(11);
      RSTAMP(1);
#pragma unroll 1
      while (!decode(1, n++)) load(1);
      bar_arrive(9, 256);
      RSTAMP(2);
      PROF(12);
    }
    PROF(13);
    if (++s == NSEG - 1) break;
    }
  }
#undef fence_reg
  if (RANK < 2) bar_arrive(4, 256);
  TSTAMP(49);
  {
    PIN(l16);
    tail_attention(sb, RANK, w, LV, 0, 6);
#pragma unroll 1
    for (int sg = 0; sg < 2; sg++) {
      PIN(l16);
      const int lane = LV, m = lane >> 3, g = lane >> 2, t = lane & 3;
      const uint32_t ob = l16 + T_OB + sg * 8192;
      bar_sync(sg ? 0 : 8, 256);
      TSTAMP(54 + 2 * sg);
      const float inv = __uint_as_float(0x7f000000u - lds32(sb + T_UN + sg * 4));
#pragma unroll 1
      for (int j = 0; j < 4; j += 2) {
        float c[2][3][4];
        uint32_t x[4], y[4], z[2][4];
#pragma unroll
        for (int e = 0; e < 2; e++) {
          const uint32_t oa = sb + T_OA + ((sg * 4 + j + e) * 8 + g) * 64 + (blockIdx.x / 3 * 36 & 15) + t * 4;
          z[e][0] = lds32(oa); z[e][1] = lds32(oa + 16); z[e][2] = t ? 0u : lds32(oa + 32);
        }
#pragma unroll
        for (int i = 0; i < 3; i++) {
          const uint32_t wa = sb + T_WA + ((lane & 7) + ((lane >> 4) << 3)) * 128 + (((w + 4 * (m & 1)) ^ (lane & 7)) << 4);
          ldsm4t(x, wa + i * 3072); ldsm2t(y, wa + i * 3072 + 2048);
#pragma unroll
          for (int e = 0; e < 2; e++) { mma1688z(c[e][i], y[0], y[1], z[e][2]); mma16816(c[e][i], x, z[e][0], z[e][1]); }
        }
#pragma unroll
        for (int r = 0; r < 4; r++) {
          ldsm4t(z[0], ob + j * 2048 + r * 512); ldsm4t(z[1], ob + j * 2048 + 2048 + r * 512);
          lds128(l16 + SM_WO3 + w * 512 + r * 2048, x); lds128(l16 + SM_WO3 + w * 512 + (r + 4) * 2048, y);
#pragma unroll
          for (int e = 0; e < 2; e++) { mma16816(c[e][0], wo[r], z[e][0], z[e][1]); mma16816(c[e][1], w1[r], z[e][0], z[e][1]); mma16816(c[e][2], x, z[e][0], z[e][1]); }
#pragma unroll
          for (int e = 0; e < 2; e++) { mma16816(c[e][0], wo[r + 4], z[e][2], z[e][3]); mma16816(c[e][1], w1[r + 4], z[e][2], z[e][3]); mma16816(c[e][2], y, z[e][2], z[e][3]); }
        }
#pragma unroll
        for (int i = 0; i < 4; i++) {
          const float (&d)[3][4] = c[i >> 1];
          const int q = (i & 1) * 2;
          red_f16x8(g_red + T_RED + ((((sg * 4 + j + (i >> 1)) * 3 + RANK) * 4 + w) * 2 + (i & 1)) * 512 + lane * 16, pack_f16(d[0][q] * inv, d[0][q + 1] * inv),
                    pack_f16(d[1][q] * inv, d[1][q + 1] * inv), pack_f16(d[2][q] * inv, d[2][q + 1] * inv), 0x3c00u);
        }
      }
      TSTAMP(55 + 2 * sg);
    }
    if (RSLOW) { wait_until(gtime() + 8000); wait_until(gtime() + 8000); wait_until(gtime() + 4000); }
    if (w < 2) {
      const int b = blockIdx.x, lane = LV, g = lane >> 2, t = lane & 3;
      uint4 v;
#pragma unroll 1
      for (int n = 0; n < SPIN_LIMIT; n++) {
        v = ldg_relaxed(g_red + T_RED + (w * 96 + b) * 512 + lane * 16);
        if (__all_sync(0xffffffffu, v.w == 0x5000u)) break;
        __nanosleep(40);
      }
      const float un = __uint_as_float(lds32(sb + T_UN + w * 4));
      uint32_t* const o = (uint32_t*)(tm.out + (size_t)((NAUXSEG + w) * 32 + b / 24 * 8 + g) * DM + (b >> 3) % 3 * 192 + (b & 1) * 32 + (b & 6) * 4) + t;
#pragma unroll
      for (int j = 0; j < 3; j++) {
        const float2 f = __half22float2(*(const __half2*)(&v.x + j));
        o[j * 32] = movm(pack_bf16(f.x * un, f.y * un));
      }
    }
  }
  TSTAMP(3);
  MSTAMP(8);
  if (CSY) cluster_sync();
}

__global__ void __cluster_dims__(3, 1, 1) __launch_bounds__(384, 1)
rec_kernel(const __grid_constant__ RMaps tm, const bf16* __restrict__ x, const bf16* __restrict__ mem0) {
  extern __shared__ __align__(1024) unsigned char smem_raw[];
  const uint32_t sb = smem_u32(smem_raw);
  const int tid = threadIdx.x, lane = tid & 31;
  const int wg = __shfl_sync(0xffffffffu, tid >> 7, 0);
  const int w = __shfl_sync(0xffffffffu, (tid >> 5) & 3, 0);
  uint32_t rank; asm("mov.u32 %0, %%cluster_ctarank;" : "=r"(rank));
  STAMP(0);
  TSTAMP(0);
  asm volatile("griddepcontrol.launch_dependents;" ::: "memory");

#define PFT 1
  if (PFT && wg == 1 && lane == 0) asm volatile("prefetch.tensormap [%0];\nprefetch.tensormap [%1];" :: "l"(w & 1 ? &tm.woa : &tm.oa), "l"(w == 0 ? (rank < 2 ? &tm.wk : &tm.wv) : w == 1 ? &tm.wq : w == 2 ? &tm.x : &tm.wo) : "memory");
  if (wg < 2) {
    asm volatile("setmaxnreg.inc.sync.aligned.u32 192;");
    if (tid == 0) {
      for (int i = 0; i < 3; i++) { mbar_init(sb + MB_W + 8 * i, 1); mbar_init(sb + MB_X + 8 * i, 1); }
      mbar_init(sb + MB_WO, 1); mbar_init(sb + MB_WO3, 1);
      mbar_init(sb + MB_S, rank < 2 ? 5 : 6);
      mbar_init(sb + MB_F, 1);
      for (int i = 0; i < 3; i++) mbar_init(sb + MB_T + 8 * i, 1);
      mbar_init(sb + MB_VX, 1); mbar_init(sb + MB_VX + 8, 1);
      asm volatile("fence.mbarrier_init.release.cluster;" ::: "memory");
      fence_async();
      SSTAMP(11, 6);
      load_weights(sb, tm, rank, 0);
      for (int i = 0; i < 3; i++) mbar_expect(sb + MB_X + 8 * i, XT);
      tma_load3(sb + SM_X, &tm.x, 0, sb + MB_X);
      if (!PACE) for (int c = 1; c < 4; c++) load_weights(sb, tm, rank, c);
      mbar_expect(sb + MB_S, rank < 2 ? 640 + 2048 : 1280);
      mbar_expect(sb + MB_VX, 8192); mbar_expect(sb + MB_VX + 8, 8192);
      mbar_expect(sb + MB_T, 2048);
      for (int i = 1; i < 3; i++) mbar_expect(sb + MB_T + 8 * i, rank < 2 ? 5120 : 10240);
      SSTAMP(11, 5);
    }
    __syncwarp();
    bar_sync(0, 384);
    proj_role(sb, tm, rank, wg, w, lane);
  } else {
    asm volatile("setmaxnreg.dec.sync.aligned.u32 120;");
    attn_role(sb, smem_raw, tm, rank, x, mem0, w, lane);
  }
}

constexpr int A_XH = 73728;
constexpr int A_NS = 9, A_WM = 6144, A_WT = 768;
constexpr int A_RING = 2 * A_XH, A_TAIL = A_RING + A_NS * A_WM, A_GW = A_TAIL + A_NS * A_WT;
constexpr int A_EPI = 212864, A_EPW = 9344;
constexpr int A_XW = 4 * XT, A_XT = A_XW + 4096, A_NR = 4;
constexpr int A_IN = A_XT + 2048, A_INS = 2 * 9216 + SEGB, A_OST = A_IN + 2 * A_INS;
constexpr int A_GATE = A_EPI + 2 * A_EPW, A_BAR = A_GATE + 512;
constexpr int A_TOTAL = A_BAR + 384;
struct AMaps { CUtensorMap x, wa, wt, oa, o, o3, o8, wob, woa, wo8; };

DI void wgmma_n192_ss_nt(float* d, uint64_t da, uint64_t db, int acc) {
  asm volatile("{\n.reg .pred p;\nsetp.ne.b32 p, %98, 0;\n"
               "wgmma.mma_async.sync.aligned.m64n192k16.f32.bf16.bf16 {"
               "%0,%1,%2,%3,%4,%5,%6,%7,%8,%9,%10,%11,%12,%13,%14,%15,%16,%17,%18,%19,%20,%21,%22,%23,%24,%25,%26,%27,%28,%29,%30,%31,"
               "%32,%33,%34,%35,%36,%37,%38,%39,%40,%41,%42,%43,%44,%45,%46,%47,%48,%49,%50,%51,%52,%53,%54,%55,%56,%57,%58,%59,%60,%61,%62,%63,"
               "%64,%65,%66,%67,%68,%69,%70,%71,%72,%73,%74,%75,%76,%77,%78,%79,%80,%81,%82,%83,%84,%85,%86,%87,%88,%89,%90,%91,%92,%93,%94,%95"
               "}, %96, %97, p, 1, 1, 0, 1;\n}\n"
               : ACC8(d, 0), ACC8(d, 8), ACC8(d, 16), ACC8(d, 24), ACC8(d, 32), ACC8(d, 40), ACC8(d, 48), ACC8(d, 56),
                 ACC8(d, 64), ACC8(d, 72), ACC8(d, 80), ACC8(d, 88) : "l"(da), "l"(db), "r"(acc));
}
#define ACC4(d, o) "+f"(d[o]), "+f"(d[o + 1]), "+f"(d[o + 2]), "+f"(d[o + 3])
DI void wgmma_n24_ss_nt(float* d, uint64_t da, uint64_t db, int acc) {
  asm volatile("{\n.reg .pred p;\nsetp.ne.b32 p, %14, 0;\n"
               "wgmma.mma_async.sync.aligned.m64n24k16.f32.bf16.bf16 {%0,%1,%2,%3,%4,%5,%6,%7,%8,%9,%10,%11}, %12, %13, p, 1, 1, 0, 1;\n}\n"
               : ACC8(d, 0), ACC4(d, 8) : "l"(da), "l"(db), "r"(acc));
}
DI void wgmma_n8_ss(float* d, uint64_t da, uint64_t db, int acc) {
  asm volatile("{\n.reg .pred p;\nsetp.ne.b32 p, %6, 0;\n"
               "wgmma.mma_async.sync.aligned.m64n8k16.f32.bf16.bf16 {%0,%1,%2,%3}, %4, %5, p, 1, 1, 0, 0;\n}\n"
               : ACC4(d, 0) : "l"(da), "l"(db), "r"(acc));
}
DI void wgmma_n40_ss_tt(float* d, uint64_t da, uint64_t db, int acc) {
  asm volatile("{\n.reg .pred p;\nsetp.ne.b32 p, %22, 0;\n"
               "wgmma.mma_async.sync.aligned.m64n40k16.f32.bf16.bf16 {%0,%1,%2,%3,%4,%5,%6,%7,%8,%9,%10,%11,%12,%13,%14,%15,%16,%17,%18,%19}, "
               "%20, %21, p, 1, 1, 1, 1;\n}\n"
               : ACC8(d, 0), ACC8(d, 8), ACC4(d, 16) : "l"(da), "l"(db), "r"(acc));
}
DI void wgmma_n64_rs(float* d, const uint32_t* a, uint64_t db, int acc) {
  asm volatile("{\n.reg .pred p;\nsetp.ne.b32 p, %37, 0;\n"
               "wgmma.mma_async.sync.aligned.m64n64k16.f32.bf16.bf16 {"
               "%0,%1,%2,%3,%4,%5,%6,%7,%8,%9,%10,%11,%12,%13,%14,%15,%16,%17,%18,%19,%20,%21,%22,%23,%24,%25,%26,%27,%28,%29,%30,%31"
               "}, {%32,%33,%34,%35}, %36, p, 1, 1, 0;\n}\n"
               : ACC8(d, 0), ACC8(d, 8), ACC8(d, 16), ACC8(d, 24) : "r"(a[0]), "r"(a[1]), "r"(a[2]), "r"(a[3]), "l"(db), "r"(acc));
}
DI void wgmma_n32_ss_tn(float* d, uint64_t da, uint64_t db, int acc) {
  asm volatile("{\n.reg .pred p;\nsetp.ne.b32 p, %18, 0;\n"
               "wgmma.mma_async.sync.aligned.m64n32k16.f32.bf16.bf16 {%0,%1,%2,%3,%4,%5,%6,%7,%8,%9,%10,%11,%12,%13,%14,%15}, "
               "%16, %17, p, 1, 1, 1, 0;\n}\n"
               : ACC8(d, 0), ACC8(d, 8) : "l"(da), "l"(db), "r"(acc));
}
DI void tma_load3c(uint32_t dst, const CUtensorMap* m, int c0, int c1, int c2, uint32_t mb) {
  asm volatile("cp.async.bulk.tensor.3d.shared::cluster.global.mbarrier::complete_tx::bytes [%0], [%1, {%3, %4, %5}], [%2];"
               :: "r"(dst), "l"(m), "r"(mb), "r"(c0), "r"(c1), "r"(c2) : "memory");
}
DI void count_up(unsigned* p) {
  asm volatile("fence.proxy.async;" ::: "memory");
  asm volatile("red.release.gpu.global.add.u32 [%0], 1;" :: "l"(p) : "memory");
}
#define AX 0
#define FDLY 400
#define FEND 59
DI void publish(unsigned* p) {
  asm volatile("cp.async.bulk.wait_group 0;\nfence.proxy.async;" ::: "memory");
  asm volatile("red.relaxed.gpu.global.add.u32 [%0], 1;" :: "l"(p) : "memory");
}
#define PL 2
#define SER 35
#define DRAIN 0
#define PR 4
#define NQ 3
#define PUB 0
#define LA 1
#define LAG0 12
#define LEND 58
#define PDLY 0
#define ADLY 0

__global__ void __launch_bounds__(512, 1)
aux_kernel(const __grid_constant__ AMaps tm, const bf16* __restrict__ wqkv, const bf16* __restrict__ woa, const bf16* __restrict__ gate_w, bf16* __restrict__ out) {
  extern __shared__ __align__(1024) unsigned char smem_raw[];
  const uint32_t sb = smem_u32(smem_raw);
  const uint32_t fullx = sb + A_BAR, full1 = fullx + 24, empty1 = full1 + 8 * A_NS, fullw = empty1 + 8 * A_NS, full3 = fullw + 8, empty3 = full3 + 8 * A_NR,
                 fullq = empty3 + 8 * A_NR, emptyq = fullq + 24, fullo = emptyq + 24, emptyo = fullo + 16;
  const int tid = threadIdx.x, lane = tid & 31, cta = blockIdx.x;
  const int wg = __shfl_sync(0xffffffffu, tid >> 7, 0), w = __shfl_sync(0xffffffffu, (tid >> 5) & 3, 0);
  ASTAMP(14);
  if (tid == 384) {
    for (int i = 0; i < 3; i++) mbar_init(fullx + 8 * i, 1);
    for (int i = 0; i < A_NS; i++) { mbar_init(full1 + 8 * i, 1); mbar_init(empty1 + 8 * i, 8); }
    mbar_init(fullw, 1);
    for (int i = 0; i < 3; i++) { mbar_init(fullq + 8 * i, 1); mbar_init(emptyq + 8 * i, 4); }
    for (int i = 0; i < 2; i++) { mbar_init(fullo + 8 * i, 4); mbar_init(emptyo + 8 * i, 1); }
    for (int i = 0; i < A_NR; i++) { mbar_init(full3 + 8 * i, 1); mbar_init(empty3 + 8 * i, cta < NH ? 8 : 4); }
    fence_async();
  }
  __syncthreads();
  ASTAMP(0);
  const int tile = cta >> 1, hh = cta & 1;
  auto p3_n = [&](int g) { return cta < NH ? (cta & 3) * 2 + g : 8; };
  auto p3_next = [&](int& sl, int& ph) {
    sl += cta < NH ? 1 : 2;
    if (sl >= (cta < NH ? 6 - NQ : 4)) { sl -= cta < NH ? 6 - NQ : 4; ph ^= 1; }
  };
  auto p3_k = [&](int g) { return cta < NH ? cta >> 2 : (cta & 3) * 2 + g; };
  if (wg == 3) {
    asm volatile("setmaxnreg.dec.sync.aligned.u32 24;");
    const bool lead = lane == 0;
    if (w < 3) {
      if (ADLY) wait_until(gtime() + ADLY);
      if (elect_one()) {
        mbar_expect(fullx + 8 * w, 49152);
        for (int p = 0; p < 2; p++)
          asm volatile("cp.async.bulk.tensor.4d.shared::cluster.global.mbarrier::complete_tx::bytes [%0], [%1, {%3, %4, %5, %6}], [%2];"
                       :: "r"(sb + p * A_XH + w * 24576), "l"(&tm.x), "r"(fullx + 8 * w), "r"(0), "r"(p), "r"(57 * tile - 7), "r"(3 * w) : "memory");
      }
#pragma unroll 1
      for (int r = 0; r < 17; r++) {
#pragma unroll 1
        for (int st = w; st < A_NS; st += 3) {
          if (r > 0) mbar_wait(empty1 + 8 * st, ~r & 1);
          if (r < 16 && elect_one()) {
            const int col = hh * 288 + (r >> 2) * 72, row = (r & 3) * 144 + st * 16;
            mbar_expect(full1 + 8 * st, A_WM + (AX & 1 ? 0 : A_WT));
            tma_load3c(sb + A_RING + st * A_WM, &tm.wa, col, row, 0, full1 + 8 * st);
            if (!(AX & 1)) tma_load3c(sb + A_TAIL + st * A_WT, &tm.wt, col + 64, row, 0, full1 + 8 * st);
          }
          __syncwarp();
        }
        if (r == 0 && elect_one())
          for (int j = 0; j < 3; j++)
            asm volatile("cp.async.bulk.prefetch.L2.global [%0], %1;" :: "l"((const char*)wqkv + cta * 55296 + (w * 3 + j) * 6144), "r"(6144) : "memory");
        __syncwarp();
      }
      bar_sync(8, 96);
    }
    const unsigned epoch = lds32(sb + A_BAR + 376);
    if (w == 2 && cta < NH) {
      if (lead) {
        int avail = 0, q = 0, ph = 1;
#pragma unroll 1
        for (int seg = 0; seg < NAUXSEG; seg++) {
          const unsigned char* const src = g_seg + ((size_t)(AX & 128 ? 0 : seg % NRING) * 96 + cta * 3) * SEGB;
          SSTAMP(0, seg);
          const int ref = seg + max(LAG0 * (LEND - seg) / LEND, 0);
          if (ref >= avail) {
            const unsigned* const c = &g_scnt[(ref * 32 + cta) * 8];
            const int c2 = ldg_relaxed32(c + 512) - 3 * (epoch + 1), c0 = ldg_acquire32(c) - 3 * (epoch + 1);
            avail = ref + (c2 >= 0 && LA ? 3 : 1);
            if (c0 < 0) {
              wait_count(c, 3 * (epoch + 1), !(TL & 2) || seg < NAUXSEG - 2);
              if (FDLY && seg < FEND) wait_until(gtime() + FDLY);
            }
          }
          SSTAMP(1, seg);
          const uint32_t mb = fullq + q * 8;
          mbar_wait(emptyq + q * 8, q == 2 ? ph ^ 1 : ph);
          if (AX & 8) mbar_arrive(mb); else mbar_expect(mb, A_INS);
#pragma unroll 1
          for (int r = 0; r < ((AX & 8) ? 0 : 3); r++)
            asm volatile("cp.async.bulk.shared::cluster.global.mbarrier::complete_tx::bytes [%0], [%1], %2, [%3];"
                         :: "r"(sb + (q < 2 ? A_IN + q * A_INS : 3 * XT) + r * 9216), "l"(src + r * SEGB), "r"(r < 2 ? 9216 : SEGB), "r"(mb) : "memory");
          if (seg == 1) wait_count(&g_abar[32], NAUX * (epoch + 1));
          if (seg > 1) stg_relaxed32(&g_used[cta * 32], epoch * NSEG + seg + 1 - NQ);
          if (++q == NQ) { q = 0; ph ^= 1; }
        }
      }
      return;
    }
    if (w == 3) {
#pragma unroll 1
      for (int c = 0; c < 4; c++) {
        if (lead) asm volatile("cp.async.bulk.wait_group.read 0;" ::: "memory");
        __syncwarp();
        bar_arrive(11, 160); bar_arrive(12, 160);
#pragma unroll 1
        for (int g = 0; g < 2; g++) {
          bar_sync(13 + g, 160);
          if (lead) {
            asm volatile("cp.async.bulk.tensor.3d.global.shared::cta.bulk_group [%0, {%2, %3, %4}], [%1];"
                         :: "l"(&tm.oa), "r"(sb + A_EPI + g * A_EPW + 1024), "r"(4096 + hh * 288 + c * 72), "r"(g), "r"(57 * tile) : "memory");
            asm volatile("cp.async.bulk.commit_group;" ::: "memory");
          }
        }
      }
      if (lead) {
        asm volatile("cp.async.bulk.wait_group.read 0;" ::: "memory");
        mbar_arrive(emptyo); mbar_arrive(emptyo + 8);
        publish(&g_abar[32]);
      }
      __syncwarp();
    }
    if ((w & 1) && cta < NH) {
#pragma unroll 1
      for (int seg = w >> 1; seg < NAUXSEG; seg += 2) {
        if (lead) {
          mbar_wait(fullo + (w >> 1) * 8, (seg >> 1) & 1);
          fence_async();
          tma_store(&tm.o, sb + A_OST + (w >> 1) * 8192, cta * DH, seg * 32);
          tma_store(&tm.o, sb + A_OST + (w >> 1) * 8192 + 4096, cta * DH + 64, seg * 32);
          asm volatile("cp.async.bulk.commit_group;\ncp.async.bulk.wait_group.read 0;" ::: "memory");
          mbar_arrive(emptyo + (w >> 1) * 8);
          if (PUB == 0 || seg >= NAUXSEG - 2) publish(&g_ocnt[seg * 64 + 2 * cta / 9 * 8]);
          else {
            if (PUB == 1) asm volatile("fence.acq_rel.gpu;" ::: "memory"); else if (PUB > 2) wait_until(gtime() + PUB);
            asm volatile("red.relaxed.gpu.global.add.u32 [%0], 1;" :: "l"(&g_ocnt[seg * 64 + 2 * cta / 9 * 8]) : "memory");
          }
          if (2 * cta / 9 != (2 * cta + 1) / 9) asm volatile("red.relaxed.gpu.global.add.u32 [%0], 1;" :: "l"(&g_ocnt[seg * 64 + (2 * cta + 1) / 9 * 8]) : "memory");
          SSTAMP(9, seg);
        }
        __syncwarp();
      }
    }
    if (w & 1) return;
    if (w == 0) {
      if (lead) {
        mbar_expect(fullw, 18 * 8192 + 2048);
#pragma unroll 1
        for (int k = 0; k < 18; k++) {
          const int g = k / 9, kb = p3_k(g) * 9 + k - 9 * g;
          if (kb < 64) tma_load(sb + k * 8192, &tm.wob, p3_n(g) * 64, kb * 64, fullw);
          else tma_load(sb + k * 8192, &tm.woa, p3_n(g) * 64, (kb - 64) * 64, fullw);
        }
        for (int g = 0; g < 2; g++) tma_load(sb + A_XW + g * 2048, &tm.wo8, p3_n(g) * 64, 512 + p3_k(g) * 8, fullw);
      }
      __syncwarp();
    }
    bar_sync(6, cta >= NH ? 320 : 288);
    if (lead) {
      if (NQ == 3) for (int i = 0; i < 4; i++) mbar_arrive(emptyq + 16);
      wait_count(&g_abar[32], NAUX * (epoch + 1));
      int avail = 0, sl = w >> 1, ph = 1;
      const int ke = p3_k(w >> 1);
      const unsigned nheads = (ke < 7 ? 5 : 1) * (epoch + 1);
#pragma unroll 1
      for (int seg = 0; seg < NAUXSEG; seg++) {
        bool waited = false;
        if (seg >= avail) {
          const unsigned* const c = &g_ocnt[seg * 64 + ke * 8];
          const int c2 = ldg_relaxed32(c + 128) - nheads, c1 = ldg_relaxed32(c + 64) - nheads, c0 = ldg_acquire32(c) - nheads;
          waited = c0 < 0;
          if (waited) { wait_count(c, nheads, !(TL & 2) || seg < NAUXSEG - 2); if (PDLY && seg < FEND) wait_until(gtime() + PDLY); }
          else if (c1 >= 0) avail = seg + (c2 >= 0 ? 3 : 2);
        }
        SSTAMP(5, seg);
        mbar_wait(empty3 + 8 * sl, ph);
        if (AX & 4) mbar_arrive(full3 + 8 * sl);
        else {
          mbar_expect(full3 + 8 * sl, XT + 512);
          tma_load3c(sb + sl * XT, &tm.o3, 0, seg * 32, ke * 9, full3 + 8 * sl);
          tma_load(sb + A_XT + sl * 512, &tm.o8, 72 * 64 + ke * 8, seg * 32, full3 + 8 * sl);
        }
        p3_next(sl, ph);
      }
    }
  } else if (wg == 2) {
    asm volatile("setmaxnreg.dec.sync.aligned.u32 88;");
    {
      const unsigned epoch = *(volatile unsigned*)&g_epoch2;
      if ((tid & 127) < 80) { const uint4 g = __ldg((const uint4*)gate_w + min(tid & 127, 71)); sts128(sb + A_GW + (tid & 127) * 16, g.x, g.y, g.z, g.w); }
      fence_async();
      bar_sync(3, 128);
      float gt[2][4];
      const uint32_t d0 = (sb & 0x3FFFF) >> 4;
#pragma unroll 1
      for (int j = 0; j < 3; j++) {
        mbar_wait(fullx + 8 * j, 0);
        WG_FENCE();
#pragma unroll
        for (int k = 0; k < 24; k++)
          wgmma_n8_ss(gt[k & 1], desc_at(d0 + (k & 1) * (A_XH >> 4) + j * 1536 + (k >> 3) * 512 + (k & 6), 16, 1024, 1), desc_at(d0 + (A_GW >> 4) + j * 24 + (k & 30), 16, 128, 0), j | (k >> 1));
        WG_COMMIT();
      }
      WG_WAIT(0);
      if ((lane & 3) == 0)
#pragma unroll
        for (int i = 0; i < 4; i++) {
          const float gv = 1.f / (1.f + __expf(-gt[i >> 1][(i & 1) * 2]));
          const int r = w * 16 + (lane >> 2) + (i & 1) * 8, tok = 2 * (57 * tile - 7 + r) + (i >> 1);
          sts32(sb + A_GATE + ((i >> 1) * 64 + r) * 4, __float_as_uint(gv));
          if (hh == 0 && r >= 7 && tok < S_LEN) g_gate[tok] = gv;
        }
      if (tid == 256) sts32(sb + A_BAR + 376, epoch);
      __syncwarp();
      bar_arrive(7, 384);
      __half2 hw = __float2half2_rn(0.f);
#pragma unroll
      for (int i = 0; i < 9; i++) { const uint4 v = __ldg((const uint4*)woa + cta * 1152 + i * 128 + (tid & 127)); hw = amax4(hw, &v.x); }
      const uint32_t ew = wexp(hw);
      if (lane == 0) atomicMax(&g_amax[0], (unsigned long long)(epoch + 1) << 32 | ew);
      bar_sync(3, 128);
      if (tid == 256) {
        count_up(&g_abar[0]);
        wait_count(&g_abar[0], NAUX * (epoch + 1));
        if (cta == 0) *(volatile unsigned*)&g_epoch2 = epoch + 1;
      }
      __syncwarp();
      bar_sync(3, 128);
    }
    if (cta < NH) {
      const int lim = w * 8 + (lane >> 2) - 2 * (lane & 3);
      int q = 0, ph = 0;
      uint32_t p[5][4];
#pragma unroll
      for (int n = 0; n < 10; n++) p[n >> 1][1 + (n & 1)] = __shfl_sync(0xffffffffu, lane ^ n, n);
#pragma unroll 1
      for (int seg = 0; seg < NAUXSEG; seg++) {
        const float gt = __ldcg(&g_gate[seg * 32 + w * 8 + (lane >> 2)]);
        float sc[20], d[32];
        const uint32_t d0 = ((sb & 0x3FFFF) + (q < 2 ? A_IN + q * A_INS : 3 * XT)) >> 4;
        mbar_wait(fullq + q * 8, ph);
        if (tid == 256) SSTAMP(2, seg);
        WG_FENCE();
#pragma unroll
        for (int k = 0; k < 8; k++) {
          const int o = ((k >> 2) * 9216 + (k & 3) * 256) >> 4;
          wgmma_n40_ss_tt(sc, desc_at(d0 + o, 128, 512, 0), desc_at(d0 + o + 256, 128, 1024, 0), k > 0);
        }
        WG_COMMIT();
        WG_WAIT(0);
        if (tid == 256) SSTAMP(12, seg);
        float a[10];
#pragma unroll
        for (int i = 0; i < 10; i++) {
          a[i] = sc[(i >> 1) * 4 + (i & 1)] * (SM_SCALE * LOG2E);
          if (i < 8 && (i >> 1) * 8 + (i & 1) > lim) a[i] = -1.0e9f * LOG2E;
        }
        float m = max10(a);
        m = fmaxf(m, __shfl_xor_sync(0xffffffffu, m, 1)); m = fmaxf(m, __shfl_xor_sync(0xffffffffu, m, 2));
#pragma unroll
        for (int i = 0; i < 10; i++) a[i] = ex2(a[i] - m);
#pragma unroll
        for (int n = 0; n < 5; n++) {
          p[n][0] = pack_bf16(a[2 * n], a[2 * n + 1]); p[n][3] = p[n][0] | p[n][1];
          asm volatile("" : "+r"(p[n][0]), "+r"(p[n][3]) :: "memory");
        }
        float sum = ((a[0] + a[1]) + (a[2] + a[3])) + ((a[4] + a[5]) + (a[6] + a[7])) + (a[8] + a[9]);
        sum += __shfl_xor_sync(0xffffffffu, sum, 1);
        if (tid == 256) SSTAMP(3, seg);
        WG_FENCE();
#pragma unroll
        for (int n = 0; n < 5; n++) wgmma_n64_rs(d, p[n], n < 4 ? desc_at(d0 + 1152 + 8 * n, 4096, 512, 0) : desc_at(d0 + 1152 + 512, 1024, 128, 0), n);
        WG_COMMIT();
        sum += __shfl_xor_sync(0xffffffffu, sum, 2);
        const float f = (1.f - gt) * rcp(sum);
        WG_WAIT(0);
        if (lane == 0) mbar_arrive(emptyq + q * 8);
        if (++q == NQ) { q = 0; ph ^= 1; }
        if (tid == 256) SSTAMP(4, seg);
        mbar_wait(emptyo + (seg & 1) * 8, (seg >> 1) & 1);
#pragma unroll
        for (int n = 0; n < 4; n++) {
          const float* const v = d + (n & 1) * 16 + (n & 2);
          stsm4(sb + A_OST + (seg & 1) * 8192 + (n >> 1) * 4096 + (w * 8 + (lane & 7)) * 128 + ((((n & 1) * 4 + (lane >> 3)) ^ (lane & 7)) << 4),
                pack_bf16(v[0] * f, v[1] * f), pack_bf16(v[4] * f, v[5] * f), pack_bf16(v[8] * f, v[9] * f), pack_bf16(v[12] * f, v[13] * f));
        }
        __syncwarp();
        if (lane == 0) mbar_arrive(fullo + (seg & 1) * 8);
        if (tid == 256) SSTAMP(13, seg);
      }
    }
  } else {
    asm volatile("setmaxnreg.inc.sync.aligned.u32 200;");
    {
      const int g = lane >> 2, t = lane & 3;
      const uint32_t eb = sb + A_EPI + wg * A_EPW, d0 = (sb & 0x3FFFF) >> 4;
      const uint32_t own = (2 * t <= g ? 0xffffu : 0u) | (2 * t < g ? 0xffff0000u : 0u);
      const int kmin = 7 - 57 * tile - 16 * w;
      __half2 ho = __float2half2_rn(0.f);
#pragma unroll 1
      for (int c = 0; c < 4; c++) {
        float acc[96], tl[12];
#pragma unroll 1
        for (int r = 0; r < 4; r++) {
#pragma unroll
          for (int st = 0; st < A_NS; st++) {
            const int ks = r * 9 + st;
            if (c == 0 && st % 3 == 0 && ks % 12 == 0) mbar_wait(fullx + 8 * (ks / 12), 0);
            mbar_wait(full1 + 8 * st, r & 1);
            const uint64_t da = desc_at(d0 + wg * (A_XH >> 4) + (ks >> 2) * 512 + (ks & 3) * 2, 16, 1024, 1);
            WG_FENCE();
            wgmma_n192_ss_nt(acc, da, desc_at(d0 + ((A_RING + st * A_WM) >> 4), 2048, 1024, 1), ks);
            if (!(AX & 2)) wgmma_n24_ss_nt(tl, da, desc_at(d0 + ((A_TAIL + st * A_WT) >> 4), 128, 256, 0), ks);
            WG_COMMIT();
            if (st == 0 && r == 2) bar_sync(11 + wg, 160);
            WG_WAIT(1);
            if (ks > 0 && lane == 0) mbar_arrive(empty1 + 8 * ((st + A_NS - 1) % A_NS));
          }
        }
        WG_WAIT(0);
        if (lane == 0) mbar_arrive(empty1 + 8 * (A_NS - 1));
        ASTAMP(16 + (c & 3));
        uint32_t ql[9], qh[9], kl[9], kh[9], kx[10], vl[9], vh[9], vx[10];
#pragma unroll
        for (int j = 0; j < 9; j++) {
          const float* const q = j < 8 ? acc + 4 * j : tl, * const k = j < 8 ? acc + 32 + 4 * j : tl + 4, * const v = j < 8 ? acc + 64 + 4 * j : tl + 8;
          kh[j] = pack_bf16(k[2], k[3]); vh[j] = pack_bf16(v[2], v[3]);
          ql[j] = pack_bf16(q[0], q[1]); qh[j] = pack_bf16(q[2], q[3]); kl[j] = pack_bf16(k[0], k[1]); vl[j] = pack_bf16(v[0], v[1]);
        }
        if (w < 3) {
          const uint32_t ha = eb + 1024 + w * 2304 + lane * 16;
          stsm4(ha, kh[0], kh[1], kh[2], kh[3]); stsm4(ha + 512, kh[4], kh[5], kh[6], kh[7]);
          stsm4(ha + 1024, vh[0], vh[1], vh[2], vh[3]); stsm4(ha + 1536, vh[4], vh[5], vh[6], vh[7]);
          asm volatile("stmatrix.sync.aligned.m8n8.x2.shared.b16 [%0], {%1,%2};" :: "r"(ha + 2048), "r"(kh[8]), "r"(vh[8]) : "memory");
        }
        if (c == 0) bar_sync(7, 384); else bar_sync(1 + wg, 128);
        {
          const uint32_t ha = eb + 1024 + max(w - 1, 0) * 2304 + lane * 16;
          ldsm4(kx, ha); ldsm4(kx + 4, ha + 512); ldsm4t(vx, ha + 1024); ldsm4t(vx + 4, ha + 1536);
          asm volatile("ldmatrix.sync.aligned.m8n8.x1.shared.b16 {%0}, [%1];" : "=r"(kx[8]) : "r"(ha + 2048) : "memory");
          asm volatile("ldmatrix.sync.aligned.m8n8.x1.trans.shared.b16 {%0}, [%1];" : "=r"(vx[8]) : "r"(ha + 2176) : "memory");
        }
        const float gl = __uint_as_float(lds32(sb + A_GATE + (wg * 64 + w * 16 + g) * 4)), gh = __uint_as_float(lds32(sb + A_GATE + (wg * 64 + w * 16 + g + 8) * 4));
#pragma unroll
        for (int j = 0; j < 9; j++) { vl[j] = movm(vl[j]); vh[j] = movm(vh[j]); }
        bar_sync(1 + wg, 128);
        uint32_t ol[9], oh[9];
#pragma unroll
        for (int i = 0; i < 4; i++) {
          const int b = 2 * i;
          const uint32_t a[4] = {t >= i ? ql[b] : 0u, t >= i ? qh[b] : 0u, ql[b + 1], qh[b + 1]}, a4 = t <= i ? ql[b + 2] : 0u, a5 = t <= i ? qh[b + 2] : 0u;
          float sx[4], sl[4], sh[4];
          mma16816z(sx, a, kx[b], kx[b + 1]); mma16816z(sl, a, kl[b], kl[b + 1]); mma16816z(sh, a, kh[b], kh[b + 1]);
          mma1688(sx, a4, a5, kx[b + 2]); mma1688(sl, a4, a5, kl[b + 2]); mma1688(sh, a4, a5, kh[b + 2]);
          float e[4];
#pragma unroll
          for (int u = 0; u < 4; u++) {
            const int cc = 2 * t + (u & 1);
            e[u] = (cc <= g ? (u < 2 ? sl[u] : sh[u]) : (u < 2 ? sx[u] : sl[u])) * (0.23570226039551584f * LOG2E);
            if ((cc <= g ? cc : cc - 8) + (u & 2) * 4 < kmin) e[u] = -1.0e9f * LOG2E;
          }
          float m0 = fmaxf(e[0], e[1]), m1 = fmaxf(e[2], e[3]);
#pragma unroll
          for (int o = 1; o < 4; o <<= 1) { m0 = fmaxf(m0, __shfl_xor_sync(0xffffffffu, m0, o)); m1 = fmaxf(m1, __shfl_xor_sync(0xffffffffu, m1, o)); }
          e[0] = ex2(e[0] - m0); e[1] = ex2(e[1] - m0); e[2] = ex2(e[2] - m1); e[3] = ex2(e[3] - m1);
          const uint32_t p0 = pack_bf16(e[0], e[1]), p1 = pack_bf16(e[2], e[3]);
          const uint32_t p[4] = {p0 & ~own, 0u, p0 & own, p1 & ~own};
          float s0 = e[0] + e[1], s1 = e[2] + e[3];
#pragma unroll
          for (int o = 1; o < 4; o <<= 1) { s0 += __shfl_xor_sync(0xffffffffu, s0, o); s1 += __shfl_xor_sync(0xffffffffu, s1, o); }
          const float f0 = gl * rcp(s0), f1 = gh * rcp(s1);
#pragma unroll
          for (int j = b; j < b + 3; j++) {
            float o[4];
            mma16816z(o, p, vx[j], vl[j]);
            mma1688(o, 0u, p1 & own, vh[j]);
            const uint32_t lo = pack_bf16(o[0] * f0, o[1] * f0), hi = pack_bf16(o[2] * f1, o[3] * f1);
            if (j > b || i == 0) { ol[j] = lo; oh[j] = hi; }
            else { ol[j] = t >= i ? lo : ol[j]; oh[j] = t >= i ? hi : oh[j]; }
          }
        }
        const uint32_t sa = eb + 16 + (w * 16 + (lane & 15)) * 144 + (lane >> 4) * 16;
#pragma unroll
        for (int j = 0; j < 8; j += 2) stsm4(sa + j * 16, ol[j], oh[j], ol[j + 1], oh[j + 1]);
        asm volatile("stmatrix.sync.aligned.m8n8.x2.shared.b16 [%0], {%1,%2};" :: "r"(sa + 128), "r"(ol[8]), "r"(oh[8]) : "memory");
        ho = amax4(amax4(amax4(amax4(ho, ol), ol + 4), oh), oh + 4);
        ho = __hmax2_nan(__hmax2_nan(ho, __habs2(*(const __half2*)&ol[8])), __habs2(*(const __half2*)&oh[8]));
        if (c == 3 && tile == 17) {
          const uint32_t eo = wexp(ho);
          if (lane == 0) atomicMax(&g_amax[16], (unsigned long long)(lds32(sb + A_BAR + 376) + 1) << 32 | eo);
        }
        fence_async();
        bar_arrive(13 + wg, 160);
        ASTAMP(20 + (c & 3));
      }
    }
    ASTAMP(3);
    uint32_t wa[36][4];
    mbar_wait(fullw, 0);
    const uint32_t la = sb + wg * 73728 + ((lane & 7) + ((lane >> 4) << 3)) * 128 + (((2 * w + ((lane >> 3) & 1)) ^ (lane & 7)) << 4);
#pragma unroll
    for (int k = 0; k < 36; k++) ldsm4t(wa[k], la + k * 2048);
    sts64(sb + A_XW + wg * 2048 + 1024 + (tid & 127) * 8, 0, 0);
    fence_async();
    bar_arrive(6, cta >= NH ? 320 : 288);
    bar_sync(1 + wg, 128);
    ASTAMP(4);
    const int nsl = p3_n(wg), ke = p3_k(wg), t = lane & 3;
    const unsigned epoch = lds32(sb + A_BAR + 376);
    uint2* const part = g_part + nsl * 4096 + w * 16 + (lane >> 2) * 2 + (t & 1);
    auto tag = [&](int seg) { return PR == 8 ? ((seg >> 3) + 1 + (epoch & (seg >> 1) & (seg >> 2))) & 1 : ((seg >> 2) + 1 + (epoch & (seg >> 1))) & 1; };
    uint2 v[4];
    auto fetch = [&](int seg) {
#pragma unroll
      for (int j = 0; j < 4; j++)
        asm volatile("ld.relaxed.gpu.global.v2.b32 {%0,%1}, [%2];" : "=r"(v[j].x), "=r"(v[j].y) : "l"(part + (seg & (PR - 1)) * 36864 + ke * 512 + ((t >> 1) * 4 + j) * 64) : "memory");
    };
    auto finish = [&](int seg) {
      int n = 0;
#pragma unroll 1
      while (!(AX & 16) && __any_sync(0xffffffffu, (((v[0].x ^ tag(seg)) | (v[1].x ^ tag(seg)) | (v[2].x ^ tag(seg)) | (v[3].x ^ tag(seg))) & 1) != 0) && ++n < SPIN_LIMIT) {
        if (seg < NAUXSEG - ((TL & 2) ? 2 : 1)) __nanosleep(100);
        fetch(seg);
      }
      const float a0 = (bf_lo(v[0].x) + bf_lo(v[1].x)) + (bf_lo(v[2].x) + bf_lo(v[3].x)), a1 = (bf_hi(v[0].x) + bf_hi(v[1].x)) + (bf_hi(v[2].x) + bf_hi(v[3].x));
      const float b0 = (bf_lo(v[0].y) + bf_lo(v[1].y)) + (bf_lo(v[2].y) + bf_lo(v[3].y)), b1 = (bf_hi(v[0].y) + bf_hi(v[1].y)) + (bf_hi(v[2].y) + bf_hi(v[3].y));
      const float c0 = (t < 2 ? a0 : b0) + __shfl_xor_sync(0xffffffffu, t < 2 ? b0 : a0, 2), c1 = (t < 2 ? a1 : b1) + __shfl_xor_sync(0xffffffffu, t < 2 ? b1 : a1, 2);
      ((uint32_t*)(out + (size_t)(seg * 32 + ke * 4 + ((lane >> 2) & 3)) * DM + nsl * 64 + w * 16 + (lane >> 4) * 8))[t] = movm(pack_bf16(c0, c1));
    };
    float acc[16];
    if (AX & 64) for (int i = 0; i < 16; i++) acc[i] = 0.f;
    int done = 0, sl = cta < NH ? 0 : wg, ph = 0;
    const uint32_t d0 = (sb & 0x3FFFF) >> 4;
#pragma unroll 1
    for (int seg = 0; seg < NAUXSEG; seg++) {
      if (DRAIN) {
#pragma unroll 1
        while (done < seg && !mbar_test(full3 + 8 * sl, ph)) { fetch(done); finish(done); done++; }
      }
      mbar_wait(full3 + 8 * sl, ph);
      if (SER && !(AX & 64) && (wg == 1 || seg > 0)) bar_sync(10 - wg, 256);
      if (tid == 128) SSTAMP(6, seg);
      if (!(AX & 16)) fetch(done);
      if (!(AX & 64)) {
        const uint64_t db = desc_at(d0 + sl * (XT >> 4), 16, 1024, 1);
        WG_FENCE();
        wgmma_n32_ss_tn(acc, desc_at(d0 + ((A_XW + wg * 2048) >> 4), 8192, 1024, 1), desc_at(d0 + (A_XT >> 4) + sl * 32, 0, 128, 0), 0);
#pragma unroll
        for (int k = 0; k < 36; k++) {
          wgmma_n32_rs(acc, wa[k][0], wa[k][1], wa[k][2], wa[k][3], db + (k >> 2) * 256 + (k & 3) * 2, 1);
          if (SER && k == SER && (wg == 0 || seg < NAUXSEG - 1)) bar_arrive(9 + wg, 256);
        }
        WG_COMMIT();
      }
      if (done <= seg - PL) finish(done++);
      WG_WAIT(0);
      if (lane == 0) mbar_arrive(empty3 + 8 * sl);
      p3_next(sl, ph);
#pragma unroll
      for (int j = 0; j < 4; j++)
        if (!(AX & 16) || acc[4 * j] == 1.2345678f)
          asm volatile("st.relaxed.gpu.global.v2.b32 [%0], {%1,%2};" :: "l"(part + (seg & (PR - 1)) * 36864 + (2 * j + (t >> 1)) * 512 + ke * 64),
                       "r"((pack_bf16(acc[4 * j], acc[4 * j + 1]) & ~1u) | tag(seg)), "r"(pack_bf16(acc[4 * j + 2], acc[4 * j + 3])) : "memory");
      if (tid == 128) SSTAMP(7, seg);
      if (tid == 128) SSTAMP(8, seg);
      if ((seg & 7) == 6) ASTAMP(5 + (seg >> 3));
    }
#pragma unroll 1
    for (; done < NAUXSEG; done++) { fetch(done); finish(done); }
    ASTAMP(13);
    TSTAMP(48);
    MSTAMP(9);
  }
}

typedef CUresult (*EncodeFn)(CUtensorMap*, CUtensorMapDataType, cuuint32_t, void*, const cuuint64_t*, const cuuint64_t*,
                             const cuuint32_t*, const cuuint32_t*, CUtensorMapInterleave, CUtensorMapSwizzle,
                             CUtensorMapL2promotion, CUtensorMapFloatOOBfill);
static void make_map(EncodeFn enc, CUtensorMap* m, const void* p, int rows, int cols, int box_rows) {
  cuuint64_t dims[2] = {(cuuint64_t)cols, (cuuint64_t)rows};
  cuuint64_t strides[1] = {(cuuint64_t)cols * 2};
  cuuint32_t box[2] = {64, (cuuint32_t)box_rows};
  cuuint32_t es[2] = {1, 1};
  enc(m, CU_TENSOR_MAP_DATA_TYPE_BFLOAT16, 2, (void*)p, dims, strides, box, es, CU_TENSOR_MAP_INTERLEAVE_NONE,
      CU_TENSOR_MAP_SWIZZLE_128B, CU_TENSOR_MAP_L2_PROMOTION_L2_128B, CU_TENSOR_MAP_FLOAT_OOB_FILL_NONE);
}

constexpr int g_poll = POLL_NS;
extern "C" void kernel_launch(void* const* d_in, const int* in_sizes, int n_in, void* d_out, int out_size) {
  const bf16* x = (const bf16*)d_in[0];
  const bf16* wqkvA = (const bf16*)d_in[1];
  const bf16* woA = (const bf16*)d_in[2];
  const bf16* mem0 = (const bf16*)d_in[4];
  const bf16* Wq = (const bf16*)d_in[5];
  const bf16* Wk = (const bf16*)d_in[6];
  const bf16* Wv = (const bf16*)d_in[7];
  const bf16* Wo = (const bf16*)d_in[8];
  const bf16* gate_w = (const bf16*)d_in[10];
  static EncodeFn enc = nullptr;
  static void *pO = nullptr, *pR = nullptr;
  if (!enc) {
    cudaDriverEntryPointQueryResult qr;
    cudaGetDriverEntryPoint("cuTensorMapEncodeTiled", (void**)&enc, cudaEnableDefault, &qr);
    cudaGetSymbolAddress(&pO, g_Ocat);
    cudaGetSymbolAddress(&pR, g_red_raw);
    cudaFuncSetAttribute(rec_kernel, cudaFuncAttributeMaxDynamicSharedMemorySize, SM_TOTAL);
    cudaFuncSetAttribute(aux_kernel, cudaFuncAttributeMaxDynamicSharedMemorySize, A_TOTAL);
  }
  RMaps rm;
  rm.poll = g_poll; rm.out = (bf16*)d_out;
  make_map(enc, &rm.woa, woA, DM, DM, 24);
  {
    cuuint64_t dims[2] = {KCAT, S_LEN}, strides[1] = {KCAT * 2};
    cuuint32_t box[2] = {32, 64}, es[2] = {1, 1};
    enc(&rm.oa, CU_TENSOR_MAP_DATA_TYPE_BFLOAT16, 2, pO, dims, strides, box, es, CU_TENSOR_MAP_INTERLEAVE_NONE,
        CU_TENSOR_MAP_SWIZZLE_NONE, CU_TENSOR_MAP_L2_PROMOTION_NONE, CU_TENSOR_MAP_FLOAT_OOB_FILL_NONE);
  }
  rm.red = (unsigned char*)(((uintptr_t)pR + 262143) & ~(uintptr_t)262143);
  {
    cuuint64_t dims[3] = {64, S_LEN, 9}, strides[2] = {DM * 2, 128};
    cuuint32_t box[3] = {64, 32, 9}, es[3] = {1, 1, 1};
    enc(&rm.x, CU_TENSOR_MAP_DATA_TYPE_BFLOAT16, 3, (void*)x, dims, strides, box, es, CU_TENSOR_MAP_INTERLEAVE_NONE,
        CU_TENSOR_MAP_SWIZZLE_128B, CU_TENSOR_MAP_L2_PROMOTION_L2_128B, CU_TENSOR_MAP_FLOAT_OOB_FILL_NONE);
  }
  make_map(enc, &rm.wq, Wq, DM, 4096, 192);
  make_map(enc, &rm.wk, Wk, DM, 4096, 192);
  make_map(enc, &rm.wv, Wv, DM, 4096, 192);
  make_map(enc, &rm.wo, Wo, 4096, DM, 128);
  AMaps am;
  {
    cuuint32_t es[4] = {1, 1, 1, 1};
    cuuint64_t dx[4] = {64, 2, S_LEN / 2, 9}, sx[3] = {DM * 2, DM * 4, 128};
    cuuint32_t bx[4] = {64, 1, 64, 3};
    enc(&am.x, CU_TENSOR_MAP_DATA_TYPE_BFLOAT16, 4, (void*)x, dx, sx, bx, es, CU_TENSOR_MAP_INTERLEAVE_NONE,
        CU_TENSOR_MAP_SWIZZLE_128B, CU_TENSOR_MAP_L2_PROMOTION_L2_128B, CU_TENSOR_MAP_FLOAT_OOB_FILL_NONE);
    cuuint64_t dw[3] = {DM, DM, 3}, sw[2] = {DM * 6, DM * 2};
    cuuint32_t bw[3] = {64, 16, 3}, bt[3] = {8, 16, 3};
    enc(&am.wa, CU_TENSOR_MAP_DATA_TYPE_BFLOAT16, 3, (void*)wqkvA, dw, sw, bw, es, CU_TENSOR_MAP_INTERLEAVE_NONE,
        CU_TENSOR_MAP_SWIZZLE_128B, CU_TENSOR_MAP_L2_PROMOTION_L2_128B, CU_TENSOR_MAP_FLOAT_OOB_FILL_NONE);
    enc(&am.wt, CU_TENSOR_MAP_DATA_TYPE_BFLOAT16, 3, (void*)wqkvA, dw, sw, bt, es, CU_TENSOR_MAP_INTERLEAVE_NONE,
        CU_TENSOR_MAP_SWIZZLE_NONE, CU_TENSOR_MAP_L2_PROMOTION_NONE, CU_TENSOR_MAP_FLOAT_OOB_FILL_NONE);
    cuuint64_t dz[3] = {KCAT, 2, S_LEN / 2}, sz[2] = {KCAT * 2, KCAT * 4};
    cuuint32_t bz[3] = {72, 1, 57};
    enc(&am.oa, CU_TENSOR_MAP_DATA_TYPE_BFLOAT16, 3, pO, dz, sz, bz, es, CU_TENSOR_MAP_INTERLEAVE_NONE,
        CU_TENSOR_MAP_SWIZZLE_NONE, CU_TENSOR_MAP_L2_PROMOTION_NONE, CU_TENSOR_MAP_FLOAT_OOB_FILL_NONE);
  }
  {
    cuuint64_t dims[3] = {64, S_LEN, KCAT / 64}, strides[2] = {KCAT * 2, 128};
    cuuint32_t box[3] = {64, 32, 9}, es[3] = {1, 1, 1};
    make_map(enc, &am.o, pO, S_LEN, KCAT, 32);
    enc(&am.o3, CU_TENSOR_MAP_DATA_TYPE_BFLOAT16, 3, pO, dims, strides, box, es, CU_TENSOR_MAP_INTERLEAVE_NONE,
        CU_TENSOR_MAP_SWIZZLE_128B, CU_TENSOR_MAP_L2_PROMOTION_L2_128B, CU_TENSOR_MAP_FLOAT_OOB_FILL_NONE);
  }
  make_map(enc, &am.wob, Wo, 4096, DM, 64);
  make_map(enc, &am.woa, woA, DM, DM, 64);
  make_map(enc, &am.wo8, woA, DM, DM, 8);
  {
    cuuint64_t dims[2] = {KCAT, S_LEN}, strides[1] = {KCAT * 2};
    cuuint32_t box[2] = {8, 32}, es[2] = {1, 1};
    enc(&am.o8, CU_TENSOR_MAP_DATA_TYPE_BFLOAT16, 2, pO, dims, strides, box, es, CU_TENSOR_MAP_INTERLEAVE_NONE,
        CU_TENSOR_MAP_SWIZZLE_NONE, CU_TENSOR_MAP_L2_PROMOTION_NONE, CU_TENSOR_MAP_FLOAT_OOB_FILL_NONE);
  }

  rec_kernel<<<96, 384, SM_TOTAL, cudaStreamPerThread>>>(rm, x, mem0);
  cudaLaunchConfig_t cfg = {};
  cfg.gridDim = dim3(NAUX); cfg.blockDim = dim3(512); cfg.dynamicSmemBytes = A_TOTAL; cfg.stream = cudaStreamPerThread;
  cudaLaunchAttribute at[1];
  at[0].id = cudaLaunchAttributeProgrammaticStreamSerialization; at[0].val.programmaticStreamSerializationAllowed = 1;
  cfg.attrs = at; cfg.numAttrs = 1;
  if (XP & 16) cfg.numAttrs = 0;
  if (!(XP & 64)) cudaLaunchKernelEx(&cfg, aux_kernel, am, wqkvA, woA, gate_w, (bf16*)d_out);
}
```

```cpp
#include <cuda_runtime.h>
#include <cuda_bf16.h>
#include <cuda_fp16.h>
#include <cuda.h>
#include <stdint.h>

typedef __nv_bfloat16 bf16;

constexpr int S_LEN = 2048, DM = 576, NH = 32, DH = 128, NSEG = 64, KCAT = 4096 + 576;
constexpr int NAUXSEG = NSEG - 2;
constexpr int NAUX = 36;
#define RED_LINE(i) (((i) >> 2) * 4096 + ((i) & 1) * 256 + ((i) & 2) * 512)
#define RED_SLOT(s) (((s) & 1) * 128 + ((s) & 2) * 256)

#define POLL_NS 848
#define NII 14
#define W3PRE 4
#define W3MID 4
#define GF 0
#define B5POS 0
#define NUP 4
#define UPF 1
#define B3Q 9
#define B3F 0
#define GATE 7
#define NTL 2
#define B7R 1
#define VS0 1
#define VS1 0
#define VLATE(w) ((w) == 0 ? VS0 == 1 : (w) == 1 ? VS1 == 1 : false)
#define HOIST 0
#define RSLOW 0
#define CSY 0
#define DD 2
#define N12 18
#define N14 18
#define HP 0
#define HL 0
#define WL 1
#define RV 3
#define EXM 1
#define PSTAMP 0
#define PFIX 1
#define RET 1
#define TL 6
#define CLR 1
#define RFW 0
#define NIC 0
#define LEAD 0
#define FIN16 1
#define VXG 0
#define NRING 20
#define EXD 0
#define HDLY 0
#define F10 1
#define NPROBE 2
#define QM 0
#define N5 224
#define KP(i) (((i) >> 1) + 4 * ((i) & 1))
#define SPIN_LIMIT (1 << 14)
#define XP 0

__device__ __align__(1024) bf16 g_Ocat[S_LEN * KCAT];
__device__ __align__(1024) unsigned char g_red_raw[2 * 262144];
constexpr int HINT_OFF = 2048;
__device__ __align__(16) float g_gate[S_LEN];
__device__ __align__(128) uint4 g_stats[96 * 2];
__device__ unsigned g_epoch;
__device__ unsigned g_epoch2;
__device__ unsigned g_ocnt[NSEG * 64];
__device__ unsigned g_abar[3 * 32];
__device__ unsigned long long g_amax[2 * 16];
__device__ unsigned g_scnt[NSEG * 32 * 8];
__device__ __align__(1024) unsigned char g_seg[NRING * 96 * 10240];
__device__ unsigned g_used[NH * 32];
__device__ __align__(1024) uint2 g_part[8 * 9 * 64 * 64];
__device__ int g_err;
#define MSTAMP(i)
#define TSTAMP(i)
#define PROF(idx)
#define PROFP(idx)
#define RSTAMP(k)
#define STAMP(idx)
#define ASTAMP(idx)
#define SSTAMP(k, seg)
#define WSTAMP(idx)

#define DI __device__ __forceinline__
DI uint32_t smem_u32(const void* p) { return (uint32_t)__cvta_generic_to_shared(p); }
DI uint32_t clock32() { uint32_t c; asm volatile("mov.u32 %0, %%clock;" : "=r"(c) :: "memory"); return c; }
DI uint32_t gtime() { uint32_t c; asm volatile("mov.u32 %0, %%globaltimer_lo;" : "=r"(c) :: "memory"); return c; }
DI uint32_t ldg_relaxed32(const void* p) { uint32_t v; asm volatile("ld.relaxed.gpu.global.b32 %0, [%1];" : "=r"(v) : "l"(p) : "memory"); return v; }
DI uint32_t ldg_acquire32(const void* p) { uint32_t v; asm volatile("ld.acquire.gpu.global.b32 %0, [%1];" : "=r"(v) : "l"(p) : "memory"); return v; }
DI void stg_relaxed32(void* p, uint32_t v) { asm volatile("st.relaxed.gpu.global.b32 [%0], %1;" :: "l"(p), "r"(v) : "memory"); }
DI int head_id() { int c; asm volatile("mov.u32 %0, %%clusterid.x;" : "=r"(c)); return c; }
DI uint32_t mapa(uint32_t a, uint32_t r) { uint32_t o; asm("mapa.shared::cluster.u32 %0, %1, %2;" : "=r"(o) : "r"(a), "r"(r)); return o; }
DI void cluster_arrive() { asm volatile("barrier.cluster.arrive.relaxed.aligned;" ::: "memory"); }
DI void cluster_wait() { asm volatile("barrier.cluster.wait.aligned;" ::: "memory"); }
DI void cluster_sync() { asm volatile("barrier.cluster.arrive.release.aligned;\nbarrier.cluster.wait.acquire.aligned;" ::: "memory"); }
DI void mbar_init(uint32_t b, uint32_t c) { asm volatile("mbarrier.init.shared::cta.b64 [%0], %1;" :: "r"(b), "r"(c) : "memory"); }
DI void mbar_expect(uint32_t b, uint32_t tx) { asm volatile("mbarrier.arrive.expect_tx.shared::cta.b64 _, [%0], %1;" :: "r"(b), "r"(tx) : "memory"); }
DI void mbar_arrive(uint32_t b) { asm volatile("mbarrier.arrive.shared::cta.b64 _, [%0];" :: "r"(b) : "memory"); }
DI void mbar_wait(uint32_t b, uint32_t par) {
  asm volatile("{\n.reg .pred p;\n.reg .u32 n, q;\nmov.u32 n, 0;\n"
               "WL: add.u32 n, n, 1;\nshr.u32 q, n, 12;\nxor.b32 q, q, %1;\n"
               "mbarrier.try_wait.parity.shared::cta.b64 p, [%0], q;\n@!p bra.uni WL;\n}"
               :: "r"(b), "r"(par) : "memory");
}
DI bool mbar_test(uint32_t b, uint32_t par) {
  uint32_t r;
  asm volatile("{\n.reg .pred p;\nmbarrier.test_wait.parity.shared::cta.b64 p, [%1], %2;\nselp.u32 %0, 1, 0, p;\n}" : "=r"(r) : "r"(b), "r"(par) : "memory");
  return r;
}
DI void mbar_wait_fast(uint32_t b, uint32_t par) {
  asm volatile("{\n.reg .pred p;\n.reg .u32 n, q;\nmbarrier.try_wait.parity.shared::cta.b64 p, [%0], %1;\n@p bra.uni WD;\nmov.u32 n, 0;\n"
               "WL: add.u32 n, n, 1;\nshr.u32 q, n, 12;\nxor.b32 q, q, %1;\n"
               "mbarrier.try_wait.parity.shared::cta.b64 p, [%0], q;\n@!p bra.uni WL;\nWD:\n}"
               :: "r"(b), "r"(par) : "memory");
}
DI void wait_until(uint32_t t) {
  const uint32_t now = gtime();
  t = min(t, now + 8192);
  asm volatile("{\n.reg .pred p;\n.reg .u32 c;\nTL: mov.u32 c, %%globaltimer_lo;\nsetp.lt.u32 p, c, %0;\n@p bra.uni TL;\n}" :: "r"(t) : "memory");
}
#define PIN(v) v = __shfl_xor_sync(0xffffffffu, v, 0)
#define SCHED_FENCE(k) asm volatile("{\n.reg .pred p;\nsetp.eq.u32 p, %0, %1;\n@p exit;\n}" :: "r"(fence_reg), "r"(k) : "memory")
#define MEM_ORDER(k) asm volatile("{\n.reg .pred p;\nsetp.eq.u32 p, %0, %1;\n@p st.shared.u32 [%0], %0;\n}" :: "r"(fence_reg), "r"(k + 64) : "memory")
DI void bar_sync(int id, int n) { asm volatile("bar.sync %0, %1;" :: "r"(id), "r"(n) : "memory"); }
DI void bar_arrive(int id, int n) { asm volatile("bar.arrive %0, %1;" :: "r"(id), "r"(n) : "memory"); }
DI void fence_async() { asm volatile("fence.proxy.async.shared::cta;" ::: "memory"); }
DI void st_async4(uint32_t a, uint32_t x, uint32_t y, uint32_t z, uint32_t w, uint32_t mb) {
  asm volatile("st.async.weak.shared::cluster.mbarrier::complete_tx::bytes.v4.b32 [%0], {%1,%2,%3,%4}, [%5];"
               :: "r"(a), "r"(x), "r"(y), "r"(z), "r"(w), "r"(mb) : "memory");
}
DI void st_async2(uint32_t a, uint32_t x, uint32_t y, uint32_t mb) {
  asm volatile("st.async.weak.shared::cluster.mbarrier::complete_tx::bytes.v2.b32 [%0], {%1,%2}, [%3];"
               :: "r"(a), "r"(x), "r"(y), "r"(mb) : "memory");
}
DI void sts32(uint32_t a, uint32_t x) { asm volatile("st.shared.b32 [%0], %1;" :: "r"(a), "r"(x) : "memory"); }
DI void sts64(uint32_t a, uint32_t x, uint32_t y) { asm volatile("st.shared.v2.b32 [%0], {%1,%2};" :: "r"(a), "r"(x), "r"(y) : "memory"); }
DI void sts128(uint32_t a, uint32_t x, uint32_t y, uint32_t z, uint32_t w) {
  asm volatile("st.shared.v4.b32 [%0], {%1,%2,%3,%4};" :: "r"(a), "r"(x), "r"(y), "r"(z), "r"(w) : "memory");
}
DI uint32_t lds32(uint32_t a) { uint32_t x; asm volatile("ld.shared.b32 %0, [%1];" : "=r"(x) : "r"(a) : "memory"); return x; }
DI void lds64(uint32_t a, uint32_t& x, uint32_t& y) { asm volatile("ld.shared.v2.b32 {%0,%1}, [%2];" : "=r"(x), "=r"(y) : "r"(a) : "memory"); }
DI void lds128(uint32_t a, uint32_t* r) {
  asm volatile("ld.shared.v4.b32 {%0,%1,%2,%3}, [%4];" : "=r"(r[0]), "=r"(r[1]), "=r"(r[2]), "=r"(r[3]) : "r"(a) : "memory");
}
DI void lds128f(uint32_t a, float* r) {
  asm volatile("ld.shared.v4.f32 {%0,%1,%2,%3}, [%4];" : "=f"(r[0]), "=f"(r[1]), "=f"(r[2]), "=f"(r[3]) : "r"(a) : "memory");
}
DI void lds64f(uint32_t a, float* r) { asm volatile("ld.shared.v2.f32 {%0,%1}, [%2];" : "=f"(r[0]), "=f"(r[1]) : "r"(a) : "memory"); }
DI void ldsm4t(uint32_t* r, uint32_t a) {
  asm volatile("ldmatrix.sync.aligned.m8n8.x4.trans.shared.b16 {%0,%1,%2,%3}, [%4];"
               : "=r"(r[0]), "=r"(r[1]), "=r"(r[2]), "=r"(r[3]) : "r"(a) : "memory");
}
DI void ldsm4t_in(uint32_t* r, uint32_t a, uint32_t t) {
  asm volatile("{\n.reg .pred p;\nsetp.ne.u32 p, %5, 0;\n@p ldmatrix.sync.aligned.m8n8.x4.trans.shared.b16 {%0,%1,%2,%3}, [%4];\n}"
               : "+r"(r[0]), "+r"(r[1]), "+r"(r[2]), "+r"(r[3]) : "r"(a), "r"(t) : "memory");
}
DI void lds128_in(uint32_t* r, uint32_t a, uint32_t t) {
  asm volatile("{\n.reg .pred p;\nsetp.ne.u32 p, %5, 0;\n@p ld.shared.v4.b32 {%0,%1,%2,%3}, [%4];\n}"
               : "+r"(r[0]), "+r"(r[1]), "+r"(r[2]), "+r"(r[3]) : "r"(a), "r"(t) : "memory");
}
DI void ldsm2t_in(uint32_t* r, uint32_t a, uint32_t t) {
  asm volatile("{\n.reg .pred p;\nsetp.ne.u32 p, %3, 0;\n@p ldmatrix.sync.aligned.m8n8.x2.trans.shared.b16 {%0,%1}, [%2];\n}" : "+r"(r[0]), "+r"(r[1]) : "r"(a), "r"(t) : "memory");
}
DI void reserve2(uint32_t* r) { asm volatile("{\n.reg .u64 t;\nmov.u64 t, %%clock64;\nmov.b64 {%0, %1}, t;\n}" : "=r"(r[0]), "=r"(r[1])); }
DI void scale_sum(float& x, float& y, float s, uint32_t t) {
  asm volatile("{\n.reg .pred p;\nsetp.ne.u32 p, %2, 0;\n@p mul.f32 %0, %0, %1;\n}" : "+f"(y) : "f"(s), "r"(t));
  asm volatile("{\n.reg .pred p;\nsetp.ne.u32 p, %3, 1;\n@p fma.rn.f32 %0, %0, %1, %2;\n}" : "+f"(x) : "f"(s), "f"(y), "r"(t));
}
DI void ldsm4(uint32_t* r, uint32_t a) {
  asm volatile("ldmatrix.sync.aligned.m8n8.x4.shared.b16 {%0,%1,%2,%3}, [%4];"
               : "=r"(r[0]), "=r"(r[1]), "=r"(r[2]), "=r"(r[3]) : "r"(a) : "memory");
}
DI void st_async1(uint32_t a, uint32_t x, uint32_t mb) {
  asm volatile("st.async.weak.shared::cluster.mbarrier::complete_tx::bytes.b32 [%0], %1, [%2];" :: "r"(a), "r"(x), "r"(mb) : "memory");
}
DI void stsm4(uint32_t a, uint32_t x, uint32_t y, uint32_t z, uint32_t w) {
  asm volatile("stmatrix.sync.aligned.m8n8.x4.shared.b16 [%0], {%1,%2,%3,%4};" :: "r"(a), "r"(x), "r"(y), "r"(z), "r"(w) : "memory");
}
DI void stsm4t(uint32_t a, uint32_t x, uint32_t y, uint32_t z, uint32_t w) {
  asm volatile("stmatrix.sync.aligned.m8n8.x4.trans.shared.b16 [%0], {%1,%2,%3,%4};" :: "r"(a), "r"(x), "r"(y), "r"(z), "r"(w) : "memory");
}
DI uint32_t pack_bf16(float lo, float hi) { uint32_t r; asm("cvt.rn.bf16x2.f32 %0, %1, %2;" : "=r"(r) : "f"(hi), "f"(lo)); return r; }
DI uint32_t pack_f16(float lo, float hi) { uint32_t r; asm("cvt.rn.f16x2.f32 %0, %1, %2;" : "=r"(r) : "f"(hi), "f"(lo)); return r; }
DI float ex2(float x) { float y; asm("ex2.approx.ftz.f32 %0, %1;" : "=f"(y) : "f"(x)); return y; }
DI float rcp(float x) { float y; asm("rcp.approx.ftz.f32 %0, %1;" : "=f"(y) : "f"(x)); return y; }
DI float bf_lo(uint32_t x) { return __uint_as_float(x << 16); }
DI float bf_hi(uint32_t x) { return __uint_as_float(x & 0xffff0000u); }
DI void mma16816(float* d, const uint32_t* a, uint32_t b0, uint32_t b1) {
  asm volatile("mma.sync.aligned.m16n8k16.row.col.f32.bf16.bf16.f32 {%0,%1,%2,%3}, {%4,%5,%6,%7}, {%8,%9}, {%0,%1,%2,%3};"
               : "+f"(d[0]), "+f"(d[1]), "+f"(d[2]), "+f"(d[3]) : "r"(a[0]), "r"(a[1]), "r"(a[2]), "r"(a[3]), "r"(b0), "r"(b1));
}
DI void mma16816z(float* d, const uint32_t* a, uint32_t b0, uint32_t b1) {
  asm volatile("mma.sync.aligned.m16n8k16.row.col.f32.bf16.bf16.f32 {%0,%1,%2,%3}, {%4,%5,%6,%7}, {%8,%9}, {%10,%10,%10,%10};"
               : "=f"(d[0]), "=f"(d[1]), "=f"(d[2]), "=f"(d[3]) : "r"(a[0]), "r"(a[1]), "r"(a[2]), "r"(a[3]), "r"(b0), "r"(b1), "f"(0.f));
}
DI void mma1688z(float* d, uint32_t a0, uint32_t a1, uint32_t b0) {
  asm volatile("mma.sync.aligned.m16n8k8.row.col.f32.bf16.bf16.f32 {%0,%1,%2,%3}, {%4,%5}, {%6}, {%7,%7,%7,%7};"
               : "=f"(d[0]), "=f"(d[1]), "=f"(d[2]), "=f"(d[3]) : "r"(a0), "r"(a1), "r"(b0), "f"(0.f));
}
DI void mma1688(float* d, uint32_t a0, uint32_t a1, uint32_t b0) {
  asm volatile("mma.sync.aligned.m16n8k8.row.col.f32.bf16.bf16.f32 {%0,%1,%2,%3}, {%4,%5}, {%6}, {%0,%1,%2,%3};"
               : "+f"(d[0]), "+f"(d[1]), "+f"(d[2]), "+f"(d[3]) : "r"(a0), "r"(a1), "r"(b0));
}
DI void ldsm2t(uint32_t* r, uint32_t a) {
  asm volatile("ldmatrix.sync.aligned.m8n8.x2.trans.shared.b16 {%0,%1}, [%2];" : "=r"(r[0]), "=r"(r[1]) : "r"(a) : "memory");
}
DI uint32_t add_bf16(uint32_t a, uint32_t b) { uint32_t r; asm("add.rn.bf16x2 %0, %1, %2;" : "=r"(r) : "r"(a), "r"(b)); return r; }
DI uint32_t mul_bf16(uint32_t a, uint32_t b) { uint32_t r; asm("mul.rn.bf16x2 %0, %1, %2;" : "=r"(r) : "r"(a), "r"(b)); return r; }
DI uint64_t make_desc(uint32_t addr, uint32_t lbo, uint32_t sbo, uint32_t swz) {
  return (uint64_t)((addr & 0x3FFFF) >> 4) | ((uint64_t)(lbo >> 4) << 16) | ((uint64_t)(sbo >> 4) << 32) | ((uint64_t)swz << 62);
}
DI uint64_t desc_at(uint32_t a16, uint32_t lbo, uint32_t sbo, uint32_t swz) {
  uint64_t d; asm("mov.b64 %0, {%1, %2};" : "=l"(d) : "r"(a16 + ((lbo >> 4) << 16)), "r"((sbo >> 4) | (swz << 30)));
  return d;
}
#define WG_FENCE() asm volatile("wgmma.fence.sync.aligned;" ::: "memory")
#define WG_COMMIT() asm volatile("wgmma.commit_group.sync.aligned;" ::: "memory")
#define WG_WAIT(n) asm volatile("wgmma.wait_group.sync.aligned %0;" :: "n"(n) : "memory")
#define ACC8(d, o) "+f"(d[o]), "+f"(d[o + 1]), "+f"(d[o + 2]), "+f"(d[o + 3]), "+f"(d[o + 4]), "+f"(d[o + 5]), "+f"(d[o + 6]), "+f"(d[o + 7])
DI void wgmma_n32_rs(float* d, uint32_t a0, uint32_t a1, uint32_t a2, uint32_t a3, uint64_t db, int acc) {
  asm volatile("{\n.reg .pred p;\nsetp.ne.b32 p, %21, 0;\n"
               "wgmma.mma_async.sync.aligned.m64n32k16.f32.bf16.bf16 {%0,%1,%2,%3,%4,%5,%6,%7,%8,%9,%10,%11,%12,%13,%14,%15}, "
               "{%16,%17,%18,%19}, %20, p, 1, 1, 0;\n}\n"
               : ACC8(d, 0), ACC8(d, 8) : "r"(a0), "r"(a1), "r"(a2), "r"(a3), "l"(db), "r"(acc));
}
template <int TA>
DI void wgmma_n32_ss(float* d, uint64_t da, uint64_t db, int acc) {
  asm volatile("{\n.reg .pred p;\nsetp.ne.b32 p, %18, 0;\n"
               "wgmma.mma_async.sync.aligned.m64n32k16.f32.bf16.bf16 {%0,%1,%2,%3,%4,%5,%6,%7,%8,%9,%10,%11,%12,%13,%14,%15}, "
               "%16, %17, p, 1, 1, %19, 1;\n}\n"
               : ACC8(d, 0), ACC8(d, 8) : "l"(da), "l"(db), "r"(acc), "n"(TA));
}
DI void tma_load(uint32_t dst, const CUtensorMap* m, int c0, int c1, uint32_t mb) {
  asm volatile("cp.async.bulk.tensor.2d.shared::cluster.global.mbarrier::complete_tx::bytes [%0], [%1, {%3, %4}], [%2];"
               :: "r"(dst), "l"(m), "r"(mb), "r"(c0), "r"(c1) : "memory");
}
DI void tma_load3(uint32_t dst, const CUtensorMap* m, int row, uint32_t mb) {
  asm volatile("cp.async.bulk.tensor.3d.shared::cluster.global.mbarrier::complete_tx::bytes [%0], [%1, {%3, %4, %3}], [%2];"
               :: "r"(dst), "l"(m), "r"(mb), "r"(0), "r"(row) : "memory");
}
DI bool elect_one() {
  uint32_t p;
  asm volatile("{\n.reg .pred p;\nelect.sync _|p, 0xffffffff;\nselp.u32 %0, 1, 0, p;\n}" : "=r"(p));
  return p;
}
DI void bulk_s2s(uint32_t dst, uint32_t src, uint32_t bytes, uint32_t mb) {
  asm volatile("cp.async.bulk.shared::cluster.shared::cta.mbarrier::complete_tx::bytes [%0], [%1], %2, [%3];"
               :: "r"(dst), "r"(src), "r"(bytes), "r"(mb) : "memory");
}
DI void tma_prefetch(const CUtensorMap* m, int c0, int c1) {
  asm volatile("cp.async.bulk.prefetch.tensor.2d.L2.global.tile [%0, {%1, %2}];" :: "l"(m), "r"(c0), "r"(c1) : "memory");
}
DI void tma_store(const CUtensorMap* m, uint32_t src, int c0, int c1) {
  asm volatile("cp.async.bulk.tensor.2d.global.shared::cta.bulk_group [%0, {%2, %3}], [%1];" :: "l"(m), "r"(src), "r"(c0), "r"(c1) : "memory");
}
DI uint4 ldg_relaxed(const void* p) {
  uint4 v;
  asm volatile("ld.relaxed.gpu.global.v4.b32 {%0,%1,%2,%3}, [%4];" : "=r"(v.x), "=r"(v.y), "=r"(v.z), "=r"(v.w) : "l"(p) : "memory");
  return v;
}
DI void stg_relaxed(void* p, uint32_t x, uint32_t y, uint32_t z, uint32_t w) {
  asm volatile("st.relaxed.gpu.global.v4.b32 [%0], {%1,%2,%3,%4};" :: "l"(p), "r"(x), "r"(y), "r"(z), "r"(w) : "memory");
}
DI void red_f16x8(void* p, uint32_t x, uint32_t y, uint32_t z, uint32_t w) {
  asm volatile("red.relaxed.gpu.global.add.noftz.v4.f16x2 [%0], {%1,%2,%3,%4};" :: "l"(p), "r"(x), "r"(y), "r"(z), "r"(w) : "memory");
}
DI void sq_acc(uint32_t& a, uint32_t x) { asm("fma.rn.bf16x2 %0, %1, %1, %0;" : "+r"(a) : "r"(x)); }
DI __half2 amax4(__half2 h, const uint32_t* v) {
  h = __hmax2_nan(__hmax2_nan(h, __habs2(*(const __half2*)&v[0])), __habs2(*(const __half2*)&v[1]));
  return __hmax2_nan(__hmax2_nan(h, __habs2(*(const __half2*)&v[2])), __habs2(*(const __half2*)&v[3]));
}
DI uint32_t wexp(__half2 h) { const uint32_t u = *(const uint32_t*)&h; return __reduce_max_sync(0xffffffffu, max((u >> 16) & 0x7fffu, u & 0x7fffu)) >> 7; }
DI float max10(const float* a) {
  return fmaxf(fmaxf(fmaxf(fmaxf(a[0], a[1]), fmaxf(a[2], a[3])), fmaxf(fmaxf(a[4], a[5]), fmaxf(a[6], a[7]))), fmaxf(a[8], a[9]));
}
DI float quad_max(float m) {
  return fmaxf(fmaxf(m, __shfl_xor_sync(0xffffffffu, m, 1)), fmaxf(__shfl_xor_sync(0xffffffffu, m, 2), __shfl_xor_sync(0xffffffffu, m, 3)));
}
DI float warp_sum(float v) {
#pragma unroll
  for (int o = 16; o; o >>= 1) v += __shfl_xor_sync(0xffffffffu, v, o);
  return v;
}

constexpr int SM_WO3 = 0;
constexpr int SM_X = 16384;
constexpr int XT = 36864;
constexpr int SM_EXP = 126976;
constexpr int SEGB = 10240;
constexpr int SM_BLK = SM_EXP + 8192;
constexpr int SM_VC = SM_BLK + 4 * SEGB;
constexpr int SM_PART = SM_VC + 16384;
constexpr int SM_QM = SM_PART + 4096;
constexpr int SM_E = SM_QM + 1024;
constexpr int SM_VM = SM_E + 1536;
constexpr int SM_OB = SM_VM + 2048;
constexpr int SM_FB = SM_OB + 2048;
constexpr int SM_STAGE = SM_X + XT;
constexpr int SM_MISC = 210944;
constexpr int SM_WOST = 212992;
constexpr int SM_MEM = SM_WOST;
constexpr int SM_MAX = SM_MEM + 11264;
#define MEM_BLK(q) ((q) / 3 * 4096 + (q) % 3 * 1024)
constexpr int SM_TOTAL = 229376;
constexpr int MB_W = SM_MISC;
constexpr int MB_WO = SM_MISC + 24;
constexpr int MB_WO3 = SM_MISC + 32;
constexpr int MB_X = SM_MISC + 40;
constexpr int MB_S = SM_MISC + 64;
constexpr int MB_F = SM_MISC + 72;
constexpr int MB_VX = SM_MISC + 80;
constexpr int SC_FPAR = SM_MISC + 136;
constexpr int SC_DEAD = SM_MISC + 96;
constexpr int SC_UNSC = SM_MISC + 112;
constexpr int SC_EPOCH = SM_MISC + 128;
constexpr int SC_EXPW = SM_MISC + 132;
constexpr int SC_ONES = SM_MISC + 144;
constexpr int SC_SS = SM_MISC + 160;
constexpr int SC_LAT = SM_MISC + 224;
constexpr int MB_T = SM_MISC + 232;
constexpr int T_SX = SM_X + XT;
constexpr int T_OB = SM_X + 2 * XT;
constexpr int T_WA = T_OB + 16384;
constexpr int T_OA = T_WA + 9216;
constexpr int T_P = T_OA + 4096 + 128;
constexpr int T_UN = T_OA + 4096;
constexpr int T_RED = 131072;
constexpr int SC_XMAX = SM_MISC + 256;
constexpr int SC_PROF = 229376;

constexpr float SM_SCALE = 0.08838834764831845f;
constexpr float LOG2E = 1.4426950408889634f;
constexpr float E_LIM = 20.f;

template <bool B> struct BoolC { static constexpr bool value = B; };
struct RMaps { CUtensorMap x, wq, wk, wv, wo, woa, oa; unsigned char* red; bf16* out; uint32_t poll; };

DI uint32_t latest_hint(uint32_t h, uint32_t d, int s) {
  const uint32_t x = (((h | 0xc0c0c0c0u) - ((d >> 5) & 63) * 0x01010101u) & 0x3f3f3f3fu) | ((h ^ (((s >> 2) + 1) & 3) * 0x40404040u) & 0xc0c0c0c0u);
  const uint32_t y = __vmaxu2(x & 0x00ff00ffu, (x >> 8) & 0x00ff00ffu);
  return __reduce_max_sync(0xffffffffu, max(y & 0xffffu, y >> 16));
}
DI uint32_t near_half(uint32_t sb) {
  uint32_t a, b; lds64(sb + SC_LAT, a, b);
  return a > b;
}

template <int RT, int K0, int K1, bool D32 = false, int BAR = 0, int KB = 18>
DI void xproj(float* acc, const uint32_t (&wa)[2][18][4], uint64_t xd) {
  if (XP & 1) return;
  WG_FENCE();
#pragma unroll
  for (int k = K0; k < ((XP & 128) ? K0 + 1 : K1); k++)
  {
    uint64_t d = xd + (uint64_t)(((k >> 1) * 4096 + (k & 1) * 32) >> 4);
    if (D32) asm("mov.b64 %0, {%1, %2};" : "=l"(d) : "r"((uint32_t)xd + (((k >> 1) * 4096 + (k & 1) * 32) >> 4)), "r"((uint32_t)(xd >> 32)));
    wgmma_n32_rs(acc, wa[RT][k][0], wa[RT][k][1], wa[RT][k][2], wa[RT][k][3], d, k != 0);
    if (BAR && k == KB - 1 && KB < 18) bar_arrive(BAR, 256);
  }
  WG_COMMIT();
}

DI void seg_store(int seg, uint32_t sb, uint32_t off, uint32_t bytes) {
  asm volatile("cp.async.bulk.global.shared::cta.bulk_group [%0], [%1], %2;"
               :: "l"(g_seg + ((size_t)(seg % NRING) * 96 + blockIdx.x) * SEGB + off), "r"(sb + SM_BLK + (seg & 3) * SEGB + off), "r"(bytes) : "memory");
  asm volatile("cp.async.bulk.commit_group;" ::: "memory");
}
DI void seg_publish(int seg) {
  asm volatile("cp.async.bulk.wait_group 0;" ::: "memory");
  asm volatile("red.relaxed.gpu.global.add.u32 [%0], 1;" :: "l"(&g_scnt[(seg * 32 + blockIdx.x / 3) * 8]) : "memory");
  SSTAMP(10, seg);
}

#define NAP 64
DI uint32_t movm(uint32_t x) { uint32_t r; asm volatile("movmatrix.sync.aligned.m8n8.trans.b16 %0, %1;" : "=r"(r) : "r"(x)); return r; }
DI bool wait_count(const unsigned* p, unsigned target, bool nap = true) {
  int n = 0;
  unsigned v;
  while (true) {
    asm volatile("ld.acquire.gpu.global.b32 %0, [%1];" : "=r"(v) : "l"(p) : "memory");
    if ((int)(v - target) >= 0 || ++n > SPIN_LIMIT) break;
    if (nap) __nanosleep(NAP);
  }
  return n;
}
#define PACE 1200
#define PACE2 600
#define PACE3 (3 * PACE)
#define PORD 0
DI void load_weights(uint32_t sb, const RMaps& tm, uint32_t rank, int c) {
  const int h = blockIdx.x / 3;
  if (c < 3) {
    mbar_expect(sb + MB_W + 8 * c, 49152);
    tma_load(sb + SM_STAGE + c * 49152, rank < 2 ? &tm.wk : &tm.wv, h * DH + (rank == 1 ? 64 : 0), c * 192, sb + MB_W + 8 * c);
    tma_load(sb + SM_STAGE + c * 49152 + 24576, rank < 2 ? &tm.wq : &tm.wv, h * DH + (rank == 0 ? 0 : 64), c * 192, sb + MB_W + 8 * c);
  } else {
    tma_prefetch(&tm.wo, rank * 192, h * DH);
    mbar_expect(sb + MB_WO, 16384);
    mbar_expect(sb + MB_WO3, 32768);
    tma_load(sb + SM_WOST, &tm.wo, rank * 192 + 64, h * DH, sb + MB_WO3);
    tma_load(sb + SM_WO3, &tm.wo, rank * 192 + 128, h * DH, sb + MB_WO3);
  }
}

DI void tail_attention(const uint32_t sb, const uint32_t rank, const int w, const int lane, const int sg, const int bar) {
  const int m = lane >> 3, g = lane >> 2, t = lane & 3;
  const uint32_t l16 = sb + lane * 16, src = l16 + T_SX + sg * 10240 + w * 1280;
  const float2 gt = __ldcg((const float2*)&g_gate[(NAUXSEG + sg) * 32 + w * 8 + 2 * t]);
  if (rank < 2) {
    const uint32_t base = l16 + SM_BLK + (2 + sg) * SEGB, dst = src + rank * 5120;
    uint32_t qb[2][4];
    ldsm4t(qb[0], base + w * 1024); ldsm4t(qb[1], base + w * 1024 + 512);
#pragma unroll
    for (int j = 0; j < 3; j++) {
      uint32_t kb[4][4];
      float c[4][4];
      const uint32_t ka = base + 4096 + j * 2048 + (m & 1) * (j == 2 ? 128 : 896) - (m >> 1) * 128;
#pragma unroll
      for (int k = 0; k < 4; k += j == 2 ? 2 : 1) ldsm4t(kb[k], ka + k * 256);
      mma16816z(c[0], kb[0], qb[0][0], qb[0][1]); mma16816z(c[1], kb[j == 2 ? 0 : 1], qb[0][2], qb[0][3]);
      mma16816z(c[2], kb[2], qb[1][0], qb[1][1]); mma16816z(c[3], kb[j == 2 ? 2 : 3], qb[1][2], qb[1][3]);
      uint32_t r[4];
#pragma unroll
      for (int i = 0; i < (j == 2 ? 2 : 4); i++) r[i] = __float_as_uint((c[0][i] + c[1][j == 2 ? i + 2 : i]) + (c[2][i] + c[3][j == 2 ? i + 2 : i]));
#pragma unroll
      for (int d = 0; d < 2; d++) {
        const uint32_t to = d ? 2 : rank ^ 1, mb = mapa(sb + MB_T + 8 + 8 * sg, to);
        if (j < 2) st_async4(mapa(dst + j * 512, to), r[0], r[1], r[2], r[3], mb);
        else st_async2(mapa(dst + 1024 - lane * 8, to), r[0], r[1], mb);
      }
      if (j < 2) sts128(dst + j * 512, r[0], r[1], r[2], r[3]); else sts64(dst + 1024 - lane * 8, r[0], r[1]);
    }
  }
  TSTAMP(50 + 2 * sg);
  uint32_t vx[4][4], vm[4];
  const uint32_t va = l16 + (rank < 2 ? SM_VC + sg * 8192 : SM_BLK + (2 + sg) * SEGB) + w * 1024 + (m & 1) * 384 - (m >> 1) * 128;
#pragma unroll
  for (int i = 0; i < 4; i++) ldsm4(vx[i], va + (i & 1) * 4096 + (i >> 1) * 256);
  if (sg && rank < 2) mbar_wait(sb + MB_T, 0);
  lds128(l16 + (sg ? SM_FB : SM_VM) + w * 512, vm);
  float a[10], b[10];
  mbar_wait(sb + MB_T + 8 + 8 * sg, 0);
  TSTAMP(58 + 2 * sg);
  lds128f(src, a); lds128f(src + 512, a + 4); lds64f(src + 1024 - lane * 8, a + 8);
  lds128f(src + 5120, b); lds128f(src + 5632, b + 4); lds64f(src + 6144 - lane * 8, b + 8);
#pragma unroll
  for (int i = 0; i < 10; i++) {
    a[i] = (a[i] + b[i]) * (SM_SCALE * LOG2E);
    if (i < 8 && (i >> 1) * 8 + g > w * 8 + 2 * t + (i & 1)) a[i] = -1.0e9f * LOG2E;
  }
  float m0 = fmaxf(fmaxf(fmaxf(a[0], a[2]), fmaxf(a[4], a[6])), a[8]), m1 = fmaxf(fmaxf(fmaxf(a[1], a[3]), fmaxf(a[5], a[7])), a[9]);
#pragma unroll
  for (int o = 4; o < 32; o <<= 1) { m0 = fmaxf(m0, __shfl_xor_sync(0xffffffffu, m0, o)); m1 = fmaxf(m1, __shfl_xor_sync(0xffffffffu, m1, o)); }
#pragma unroll
  for (int i = 0; i < 10; i++) a[i] = ex2(a[i] - (i & 1 ? m1 : m0));
  float s0 = ((a[0] + a[2]) + (a[4] + a[6])) + a[8], s1 = ((a[1] + a[3]) + (a[5] + a[7])) + a[9];
#pragma unroll
  for (int o = 4; o < 32; o <<= 1) { s0 += __shfl_xor_sync(0xffffffffu, s0, o); s1 += __shfl_xor_sync(0xffffffffu, s1, o); }
  s0 = (1.f - gt.x) * rcp(s0); s1 = (1.f - gt.y) * rcp(s1);
#pragma unroll
  for (int i = 0; i < 5; i++) sts32(sb + T_P + sg * 2560 + w * 640 + i * 128 + lane * 4, pack_bf16(a[2 * i] * s0, a[2 * i + 1] * s1));
  bar_sync(bar, 128);
  TSTAMP(59 + 2 * sg);
#pragma unroll
  for (int j = 0; j < 4; j++) {
    uint32_t p[5];
    float o0[4], o1[4];
    ldsm4t(p, l16 + T_P + sg * 2560 + j * 640);
    asm volatile("ldmatrix.sync.aligned.m8n8.x1.trans.shared.b16 {%0}, [%1];" : "=r"(p[4]) : "r"(l16 + T_P + sg * 2560 + j * 640 + 512) : "memory");
    mma16816z(o0, vx[0], p[0], p[1]); mma16816z(o1, vx[1], p[0], p[1]);
    mma16816(o0, vx[2], p[2], p[3]); mma16816(o1, vx[3], p[2], p[3]);
    mma1688(o0, vm[0], vm[1], p[4]); mma1688(o1, vm[2], vm[3], p[4]);
    stsm4(l16 + T_OB + sg * 8192 + j * 2048 + w * 512, pack_bf16(o0[0], o0[1]), pack_bf16(o0[2], o0[3]), pack_bf16(o1[0], o1[1]), pack_bf16(o1[2], o1[3]));
  }
}

DI void proj_role(const uint32_t sb, const RMaps& tm, const uint32_t rank, const int wg, const int w, const int lane) {
  const bool qk = rank < 2;
  uint32_t wa[2][18][4];
  {
    const int rr = (lane & 7) + ((lane >> 4) << 3);
    const uint32_t col = ((2 * w + ((lane >> 3) & 1)) ^ (lane & 7)) << 4;
    float ss = 0.f;
#pragma unroll
    for (int c = 0; c < 3; c++) {
      mbar_wait(sb + MB_W + 8 * c, 0);
      if (threadIdx.x == 0) SSTAMP(11, c);
#pragma unroll
      for (int rt = 0; rt < 2; rt++)
#pragma unroll
        for (int k = 0; k < 6; k++)
          ldsm4t(wa[rt][c * 6 + k], sb + SM_STAGE + c * 49152 + (rt ^ wg) * 24576 + (64 * (k >> 1) + 32 * wg + 16 * (k & 1) + rr) * 128 + col);
      if (c < 2) {
        fence_async();
        bar_sync(3, 256);
        if (threadIdx.x == 0) {
          if (c == 0) tma_load3(sb + SM_X + XT, &tm.x, 32, sb + MB_X + 8);
          else { tma_load(sb + SM_X + 2 * XT, &tm.wo, rank * 192, (blockIdx.x / 3) * DH, sb + MB_WO); SSTAMP(11, 11); }
        }
        __syncwarp();
      }
      uint32_t q[4] = {0, 0, 0, 0};
#pragma unroll
      for (int rt = 0; rt < 2; rt++)
#pragma unroll
        for (int k = 0; k < 6; k++)
#pragma unroll
          for (int i = 0; i < 4; i++) sq_acc(q[i], wa[rt][c * 6 + k][i]);
#pragma unroll
      for (int i = 0; i < 4; i++) ss += bf_lo(q[i]) + bf_hi(q[i]);
    }
    ss = warp_sum(ss);
    fence_async();
    cluster_arrive();
    if (lane == 0) sts32(sb + SC_SS + 4 * (wg * 4 + w), qk ? 0 : __float_as_uint(ss));
    bar_arrive(11, 384);
  }
  STAMP(1);
  MSTAMP(0);
  mbar_wait(sb + MB_X, 0);
  STAMP(2);

  uint32_t t16 = sb + (w * 32 + lane) * 16;
  uint32_t mem_a = sb + SM_MEM + wg * 512 + lane * 16;
  uint32_t fin_a = sb + (lane & 7) * 16 + SM_BLK + (qk ? (wg ^ 1) * 4096 + w * 256 + (lane & 8) * 16 + (lane & 16) * 64
                                              : wg * 4096 + w * 1024 + (lane & 8) * 64 + (lane & 16) * 8);
  PIN(t16); PIN(mem_a); PIN(fin_a);
  const uint32_t fence_reg = mem_a;
  const uint32_t fin2 = qk ? 2048 : 256;
  float acc[16];
  const uint64_t xd0 = make_desc(sb + SM_X + wg * 64, 16, 1024, 1);
  auto do_export = [&]() {
    WG_WAIT(0);
    uint32_t q[8];
#pragma unroll
    for (int j = 0; j < 8; j++) q[j] = pack_bf16(acc[2 * j], acc[2 * j + 1]);
    sts128(t16 + SM_EXP + wg * 4096, q[0], q[1], q[2], q[3]);
    sts128(t16 + SM_EXP + wg * 4096 + 2048, q[4], q[5], q[6], q[7]);
    if (RET) asm volatile("{\n.reg .pred p;\nsetp.eq.u32 p, %2, 0;\n@p add.u32 %0, %0, 1;\n@p add.u32 %1, %1, 1;\nsetp.eq.and.u32 p, %0, %1, p;\n@p exit;\n}"
                          : "+r"(q[3]), "+r"(q[7]) : "r"(t16) : "memory");
  };
  uint32_t o[8];
  auto import = [&]() { lds128(t16 + SM_EXP + (wg ^ 1) * 4096, o); lds128(t16 + SM_EXP + (wg ^ 1) * 4096 + 2048, o + 4); };
  auto finish = [&](int seg) {
    const uint32_t a = fin_a + (seg & 3) * SEGB;
    WG_WAIT(0);
#pragma unroll
    for (int i = 0; i < 8; i++) o[i] = FIN16 ? add_bf16(pack_bf16(acc[2 * i], acc[2 * i + 1]), o[i]) : pack_bf16(acc[2 * i] + bf_lo(o[i]), acc[2 * i + 1] + bf_hi(o[i]));
    stsm4(a, o[0], o[1], o[2], o[3]);
    stsm4(a + fin2, o[4], o[5], o[6], o[7]);
  };
  auto send_v = [&](int seg, int dst) {
    fence_async();
    if (seg < NSEG && !(XP & 2) && elect_one())
      bulk_s2s(mapa(sb + SM_VC + (seg & 1) * 8192, dst), sb + SM_BLK + (seg & 3) * SEGB, 8192, mapa(sb + MB_VX + (seg & 1) * 8, dst));
    __syncwarp();
  };
  auto wait_v = [&](int seg) {
    if (seg < NSEG && !(XP & 2)) {
      mbar_wait(sb + MB_VX + (seg & 1) * 8, (seg >> 1) & 1);
      if (elect_one()) mbar_expect(sb + MB_VX + (seg & 1) * 8, 8192);
      __syncwarp();
    }
  };
  bar_sync(3, 256);
  xproj<1, 0, 18>(acc, wa, xd0);
  do_export();
  SCHED_FENCE(11);
  xproj<0, 0, 18>(acc, wa, xd0);
  bar_sync(3, 256);
  if (threadIdx.x == 0) SSTAMP(11, 12);
  MSTAMP(1);
  cluster_wait();
  if (threadIdx.x == 0) SSTAMP(11, 13);
  mbar_wait(sb + MB_X + 8, 0);
  import();
  finish(0);
  SCHED_FENCE(12);
  bar_sync(3, 256);
  uint64_t dA = xd0 + (XT >> 4);
  xproj<1, 0, 18>(acc, wa, dA);
  if (!qk && wg == 0 && w < 2) send_v(0, w);
  do_export();
  if (qk && wg == 0 && w == 0) wait_v(0);
  bar_arrive(13, 384);
  if (!qk) {
    SCHED_FENCE(15);
    xproj<0, 0, 18>(acc, wa, dA);
    if (threadIdx.x == 0 && !(XP & 8)) { mbar_expect(sb + MB_X, XT); tma_load3(sb + SM_X, &tm.x, 96, sb + MB_X); }
    bar_sync(3, 256);
    mbar_wait(sb + MB_X + 16, 0);
    import();
    finish(1);
    SCHED_FENCE(16);
    bar_sync(3, 256);
    dA += XT >> 4;
    xproj<1, 0, 18>(acc, wa, dA);
    if (wg == 0 && ((w == 0 && VS0) || (w == 1 && VS1))) send_v(1, w);
    do_export();
  }
  if (threadIdx.x == 0) SSTAMP(11, 14);
  MSTAMP(2);
  bar_sync(0, 384);
  const int ro = __shfl_sync(0xffffffffu, near_half(sb) ^ wg, 0);
  STAMP(5);
  const uint32_t always = __shfl_sync(0xffffffffu, lds32(sb + SC_DEAD + 12), 0);
  const int ah = qk ? 1 : 2;
  int b2 = qk ? 2 : 0;
  int s = 0;
  uint32_t hint_lo = (uint32_t)(uint64_t)tm.red + HINT_OFF + blockIdx.x + (lane & 1) * 4096 + (lane >> 1) * 16384;
  PIN(hint_lo);
  auto post_hint = [&]() {
    asm volatile("{\n.reg .pred p;\n.reg .b64 a;\n.reg .u32 t;\nsetp.lt.u32 p, %0, %1;\nmov.b64 a, {%2, %3};\nmov.u32 t, %%globaltimer_lo;\n"
                 "bfe.u32 t, t, 5, 6;\nor.b32 t, t, %4;\n@p st.relaxed.gpu.global.u8 [a], t;\n}"
                 :: "r"(t16), "r"(sb + 128), "r"(hint_lo + RED_SLOT(s)), "r"((uint32_t)((uint64_t)tm.red >> 32)), "r"(((s >> 2) + 1) << 6) : "memory");
  };
  auto memproj = [&](auto second, int id, float u0, float u1, float* r) {
    constexpr bool R1 = decltype(second)::value;
    uint32_t b[NUP][4], b0[4];
    SCHED_FENCE(id);
    bar_sync(R1 ? 2 : 1, 256);
    PROF(0);
    ldsm4t(b0, mem_a);
#pragma unroll
    for (int q = 0; q < NUP; q++) {
      if (R1 && q == 2) {
        bar_sync(11, 256);
        SCHED_FENCE(id + 1);
      }
      ldsm4t(b[q], mem_a + MEM_BLK(q + 1));
    }
    mma16816z(&acc[0], wa[0][0], b0[0], b0[1]);
    mma16816z(&acc[4], wa[1][0], b0[0], b0[1]);
    mma16816z(&acc[8], wa[0][1], b0[2], b0[3]);
    mma16816z(&acc[12], wa[1][1], b0[2], b0[3]);
#pragma unroll
    for (int q = 1; q < 9; q++) {
      uint32_t* const c = b[(q - 1) % NUP];
      mma16816(&acc[0], wa[0][2 * q], c[0], c[1]);
      mma16816(&acc[4], wa[1][2 * q], c[0], c[1]);
      mma16816(&acc[8], wa[0][2 * q + 1], c[2], c[3]);
      mma16816(&acc[12], wa[1][2 * q + 1], c[2], c[3]);
      if (R1 && q + NUP == B3Q) bar_sync(3, 256);
      if (q + NUP < 9) ldsm4t_in(c, mem_a + MEM_BLK(q + NUP), always);
      else if (R1 && q + NUP < 11) lds128_in(c, t16 + SM_PART + (10 - q - NUP) * 2048, always);
      else if (!R1 && GATE && q == GATE) { bar_arrive(11, 256); lds128_in(c, sb + SC_DEAD, always); u0 = u1 = __uint_as_float(c[3]); }
    }
#pragma unroll
    for (int i = 0; i < 8; i++) {
      const float u = i < 4 ? u0 : u1;
      r[i] = R1 ? fmaf(acc[8 + i], u, (acc[i] + __uint_as_float(b[(8 + i / 4) % NUP][i & 3])) * u) : (GATE ? fmaf(acc[i], u, acc[8 + i]) : acc[i] + acc[8 + i]);
    }
  };
  if (ro == 0) {
    auto set_scale = [&]() {
      uint32_t m[8];
      lds128(t16 + SM_MAX - 512, m); lds128(t16 + SM_MAX, m + 4);
      const int em = (wexp(amax4(amax4(*(const __half2*)&m[0], m), m + 4)) >> 3) + (int)(lds32(sb + SC_UNSC + (s & 1) * 8) >> 23) - 15;
      const int ex = max(s ? em : 0, (int)lds32(sb + SC_XMAX + 4 * s)) - 127 + (int)lds32(sb + SC_EXPW);
      sts32(sb + SC_UNSC + (~s & 1) * 8, (127 + min(max(ex, -120), 120)) << 23);
    };
#pragma unroll 1
    while (true) {
      if (s == 8) STAMP(6);
      float r[8];
      memproj(BoolC<false>(), 30, 0.f, 0.f, r);
      sts128(t16 + SM_PART, __float_as_uint(r[0]), __float_as_uint(r[1]), __float_as_uint(r[2]), __float_as_uint(r[3]));
      sts128(t16 + SM_PART + 2048, __float_as_uint(r[4]), __float_as_uint(r[5]), __float_as_uint(r[6]), __float_as_uint(r[7]));
      bar_arrive(3, 256);
      PROF(1);
      bar_sync(9, 256);
      if (s == NSEG - 1) break;
      post_hint();
      if (w == 1) {
        set_scale();
        __syncwarp();
        if (elect_one()) mbar_arrive(sb + MB_S);
      }
      SCHED_FENCE(9);
      bar_sync(5, qk ? N5 : 256);
      PROF(2);
      import();
      xproj<0, 0, NII, (DD & 1) != 0>(acc, wa, dA);
      if (NII < 18) {
        if (qk) bar_sync(7, 384);
        xproj<0, NII, 18>(acc, wa, dA);
        if (!qk) bar_sync(7, 384);
      } else {
        if (F10) WG_WAIT(0);
        bar_sync(10, 256);
        if (F10) SCHED_FENCE(17);
      }
      dA += (int64_t)(b2 ? XT >> 4 : -(XT >> 3));
      finish(s + ah);
      if (qk || !VLATE(w)) bar_arrive(13, 384);
      PROF(6);
      SCHED_FENCE(14);
      bar_sync(12, 256);
      PROF(7);
      xproj<1, 0, 18, (DD & 2) != 0, 14, N14>(acc, wa, dA);
      if (N14 == 18) bar_arrive(14, 256);
      b2 = b2 == 2 ? 0 : b2 + 1;
      s++;
      if (!qk && VLATE(w)) { bar_sync(13, 384); send_v(s + 1, w); }
      PROFP(8);
      do_export();
      s--; RSTAMP(6); s++;
      PROFP(3);
    }
    if (!qk) bar_arrive(5, 256);
    if (w == 0 && elect_one()) {
      const uint32_t h18 = blockIdx.x / 3 * 18;
      mbar_expect(sb + MB_WO, 9216 + 4096);
      tma_load(sb + T_OA, &tm.oa, 4096 + (h18 & ~7), NAUXSEG * 32, sb + MB_WO);
#pragma unroll 1
      for (int j = 0; j < 3; j++) tma_load(sb + T_WA + j * 3072, &tm.woa, rank * 192 + j * 64, h18, sb + MB_WO);
    }
    if (w == 1) {
      const int ea = (int)ldg_relaxed32(&g_amax[0]) + (int)ldg_relaxed32(&g_amax[16]) - 254 + 2 + 10 - 15;
      set_scale();
      __syncwarp();
      sts32(sb + T_UN + (lane & 1) * 4, (128 + max(min(ea, 120), (int)(lds32(sb + SC_UNSC + 8 - (lane & 1) * 8) >> 23) - 127)) << 23);
    }
    bar_arrive(8, 256);
  } else {
    uint32_t r0;
    float un;
    auto prepare = [&]() {
      un = __uint_as_float(lds32(sb + SC_UNSC + (s & 1) * 8));
      r0 = qk ? (t16 & ~256u) - w * 256 + (((t16 >> 8) ^ wg) & 1 ? SM_QM : SM_BLK + 8192 + (s & 3) * SEGB) : mapa(t16 + (s < NSEG - 1 ? SM_VM : SM_FB), 0);
      PIN(r0); PIN(un);
    };
    auto mem_out = [&](int off, uint32_t lo, uint32_t hi) {
      unsigned char* const d = g_seg + ((size_t)(s % NRING) * 96 + blockIdx.x) * SEGB + 8192 + off + w * 256 + ((t16 >> 2) & 124);
      if (!(XP & 4)) { stg_relaxed32(d, lo); stg_relaxed32(d + 128, hi); }
    };
    prepare();
#pragma unroll 1
    while (true) {
      if (s == 8) STAMP(6);
      float r[8];
      if (qk) {
        const float u0 = wg ? un * (SM_SCALE * LOG2E) : un, u1 = wg ? un : un * (SM_SCALE * LOG2E);
        memproj(BoolC<true>(), 32, u0, u1, r);
        const uint32_t p0 = pack_bf16(r[0], r[1]), p1 = pack_bf16(r[2], r[3]), p2 = pack_bf16(r[4], r[5]), p3 = pack_bf16(r[6], r[7]);
        stsm4(r0, p0, p1, p2, p3);
        bar_arrive(4, 256);
        if (EXM) { SCHED_FENCE(18); mem_out(0, wg ? p2 : p0, wg ? p3 : p1); }
      } else {
        const uint32_t mb = sb + (s < NSEG - 1 ? MB_S : MB_T), r1 = r0 + (1 << 24);
        memproj(BoolC<true>(), 34, un, un, r);
        const uint32_t p0 = pack_bf16(r[0], r[1]), p1 = pack_bf16(r[2], r[3]), p2 = pack_bf16(r[4], r[5]), p3 = pack_bf16(r[6], r[7]);
        const uint32_t v0 = wg ? p2 : p0, v1 = wg ? p3 : p1, v2 = wg ? p0 : p2, v3 = wg ? p1 : p3;
        st_async4(r0, v0, v1, v2, v3, mapa(mb, 0));
        st_async4(r1, v0, v1, v2, v3, mapa(mb, 1));
        bar_arrive(5, 256);
        sts128(r0 + (2 << 24), v0, v1, v2, v3);
        stsm4((t16 & ~256u) - w * 256 + SM_BLK + 8192 + (s & 3) * SEGB + (((t16 >> 8) ^ wg) & 1) * 1024, p0, p1, p2, p3);
        __syncwarp();
        if (elect_one()) mbar_arrive(sb + MB_S);
        __syncwarp();
        if (EXM) { SCHED_FENCE(19); mem_out(0, v0, v1); mem_out(1024, v2, v3); }
      }
      if (s == NSEG - 1) break;
      if (!qk && !EXM) bar_arrive(15, 160);
      PROF(1);
      auto rearm = [&]() { mbar_wait(sb + MB_S, s & 1); if (elect_one()) mbar_expect(sb + MB_S, qk ? 640 + 2048 : 1280); __syncwarp(); };
      if (w == 1) {
        if ((t16 & 384) == 0) stg_relaxed(tm.red + (RED_SLOT(s + 2) + RED_LINE(blockIdx.x)) + (t16 & 112), 0, 0, 0, 0);
      } else if (w == 0) {
        const int tn = s + ah + 1;
        if (RFW) mbar_wait(sb + MB_S, s & 1);
        if (tn + 1 < NSEG && !(XP & 8) && elect_one()) {
          const int b0 = b2 == 2 ? 0 : b2 + 1;
          mbar_expect(sb + MB_X + 8 * b0, XT);
          tma_load3(sb + SM_X + b0 * XT, &tm.x, (tn + 1) * 32, sb + MB_X + 8 * b0);
        }
        if (tn < NSEG && (!(XP & 8) || tn < 3)) mbar_wait(sb + MB_X + 8 * b2, (tn / 3) & 1);
      } else if (w == 2) {
        if (!qk) { if (VS0 == 0) send_v(s + 1, 0); if (VS1 == 0) send_v(s + 1, 1); }
      } else if (qk || !NIC) {
        rearm();
      }
      __syncwarp();
      import();
      PROF(4);
      SCHED_FENCE(10);
      if (NIC) {
        if (qk) bar_sync(7, NII < 18 ? 384 : 256);
        xproj<0, 0, NIC>(acc, wa, dA);
        if (!qk) { if (w == 3) rearm(); bar_sync(7, NII < 18 ? 384 : 256); }
      } else {
        bar_sync(7, NII < 18 ? 384 : 256);
      }
      xproj<0, NIC, 18, (DD & 4) != 0, 12, N12>(acc, wa, dA);
      if (N12 == 18) bar_arrive(12, 256);
      dA += (int64_t)(b2 ? XT >> 4 : -(XT >> 3));
      finish(s + ah);
      if (qk && w == 0) wait_v(s + 1);
      bar_arrive(13, 384);
      PROF(6);
      SCHED_FENCE(13);
      bar_sync(14, 256);
      PROF(7);
      xproj<1, 0, 18, (DD & 8) != 0>(acc, wa, dA);
      b2 = b2 == 2 ? 0 : b2 + 1;
      s++;
      if (HOIST) prepare();
      PROFP(8);
      do_export();
      if (!HOIST) prepare();
      s--; RSTAMP(7); s++;
      PROFP(3);
    }
    TSTAMP(2);
    bar_sync(3, 128);
    tail_attention(sb, rank, w, lane, 1, 3);
    bar_arrive(0, 256);
  }
  STAMP(3);
  if (CSY) cluster_sync();
  STAMP(4);
}

DI void attn_role(const uint32_t sb, unsigned char* smem_raw, const RMaps& tm, const uint32_t RANK, const bf16* __restrict__ x, const bf16* __restrict__ mem0,
                  const int w, const int lane) {
  const int t2 = w * 32 + lane;
  uint32_t wo[8][4], w1[8][4];
  const uint32_t wo_lane = sb + ((lane & 7) + ((lane >> 4) << 3)) * 128 + (((w + 4 * ((lane >> 3) & 1)) ^ (lane & 7)) << 4);
  unsigned char* const g_red = tm.red;
  {
    const uint32_t t0 = gtime();
    const uint32_t tag = *(volatile unsigned*)&g_epoch + 1;
    if (w == 0) {
      stg_relaxed(g_red + RED_SLOT(t2 >> 3) + RED_LINE(blockIdx.x) + (t2 & 7) * 16, 0, 0, 0, 0);
      stg_relaxed(g_red + T_RED + blockIdx.x * 1024 + t2 * 16, 0, 0, 0, 0);
      stg_relaxed(g_red + T_RED + blockIdx.x * 1024 + 512 + t2 * 16, 0, 0, 0, 0);
      asm volatile("st.relaxed.gpu.global.u8 [%0], 0;" :: "l"(g_red + RED_SLOT(t2) + HINT_OFF + (t2 & 4) * 1024 + (t2 >> 3) * 16384 + blockIdx.x) : "memory");
    }
    bar_sync(0, 384);
    cluster_arrive();
    if (PACE && w == 3) {
#pragma unroll 1
      for (int c = 1; c < 4; c++) {
        wait_until(t0 + (c == 3 ? PACE3 : c * (RANK < 2 ? PACE : PACE2)));
        if (elect_one()) load_weights(sb, tm, RANK, PORD ? (c == 1 ? 3 : c - 1) : c);
        __syncwarp();
      }
    }
    uint4 xv[18];
    uint32_t mv[20];
#pragma unroll
    for (int i = 0; i < 20; i++) mv[i] = i < 18 ? ((const uint32_t*)mem0)[(lane >> 2) * (DM / 2) + (w * 18 + i) * 4 + (lane & 3)] : 0;
#pragma unroll
    for (int i = 0; i < 18; i++) xv[i] = blockIdx.x < NSEG ? ((const uint4*)(x + blockIdx.x * 32 * DM))[t2 + 128 * i] : make_uint4(0, 0, 0, 0);
    __half2 hx = __float2half2_rn(0.f);
#pragma unroll
    for (int i = 0; i < 18; i++) hx = amax4(hx, &xv[i].x);
    if (blockIdx.x == 0)
#pragma unroll
      for (int i = 0; i < 5; i++) hx = amax4(hx, &mv[4 * i]);
    sts32(sb + SC_SS + 4 * (12 + w), wexp(hx));
    if (t2 == 0) { sts32(sb + SC_EPOCH, (tag - 1) * NSEG + 2 - NRING); sts32(sb + SC_UNSC, __float_as_uint(1.f)); sts128(sb + SC_DEAD, 0, 0, 0, 0x3f800000u); sts64(sb + SC_FPAR, 0, 0); sts128(sb + SC_ONES, 0x3f803f80u, 0x3f803f80u, 0x3f803f80u, 0x3f803f80u); }
    WSTAMP(27);
    if (w == 0) __threadfence();
    uint32_t q[8] = {0, 0, 0, 0, 0, 0, 0, 0};
    mbar_wait(sb + MB_WO3, 0);
    if (t2 == 0) SSTAMP(11, 3);
    MSTAMP(3);
#pragma unroll
    for (int k = 0; k < 8; k++) {
      ldsm4t(wo[k], wo_lane + SM_WO3 + k * 2048); ldsm4t(w1[k], wo_lane + SM_WOST + k * 2048);
#pragma unroll
      for (int i = 0; i < 4; i++) { sq_acc(q[i], wo[k][i]); sq_acc(q[i], w1[k][i]); }
    }
    bar_sync(6, 128);
    if (t2 == 0) SSTAMP(11, 7);
#pragma unroll
    for (int k = 0; k < 8; k++) sts128(sb + SM_WO3 + t2 * 16 + k * 2048, wo[k][0], wo[k][1], wo[k][2], wo[k][3]);
#pragma unroll
    for (int i = 0; i < 5; i++) {
      const int j = w * 18 + 4 * i + (lane >> 3), c = i < 4 || lane < 16 ? j * 8 + j / 24 * 64 : 192;
      stsm4t(sb + SM_MEM + (c + (lane & 7)) * 16, mv[4 * i], mv[4 * i + 1], mv[4 * i + 2], mv[4 * i + 3]);
    }
    bar_arrive(1, 256); bar_arrive(2, 256); bar_arrive(9, 256);
    if (t2 == 0) SSTAMP(11, 8);
    mbar_wait(sb + MB_WO, 0);
    if (t2 == 0) SSTAMP(11, 4);
#pragma unroll
    for (int k = 0; k < 8; k++) ldsm4t(wo[k], wo_lane + SM_X + 2 * XT + k * 2048);
    fence_async();
    bar_sync(6, 128);
    if (t2 == 32) tma_load3(sb + SM_X + 2 * XT, &tm.x, 64, sb + MB_X + 16);
    __syncwarp();
#pragma unroll
    for (int k = 0; k < 8; k++)
#pragma unroll
      for (int i = 0; i < 4; i++) sq_acc(q[4 + i], wo[k][i]);
    float ss = 0.f;
#pragma unroll
    for (int i = 0; i < 8; i++) ss += bf_lo(q[i]) + bf_hi(q[i]);
    ss = warp_sum(ss);
    if (lane == 0) sts32(sb + SC_SS + 4 * (8 + w), __float_as_uint(ss));
    if (t2 == 0) SSTAMP(11, 9);
    bar_sync(11, 384);
    if (t2 == 0) SSTAMP(11, 10);
    if (t2 == 0) {
      float a[16];
#pragma unroll
      for (int i = 0; i < 4; i++) lds128f(sb + SC_SS + 16 * i, &a[4 * i]);
      stg_relaxed(&g_stats[blockIdx.x * 2], __float_as_uint(((a[0] + a[1]) + (a[2] + a[3])) + ((a[4] + a[5]) + (a[6] + a[7]))),
                  __float_as_uint((a[8] + a[9]) + (a[10] + a[11])),
                  max(max(__float_as_uint(a[12]), __float_as_uint(a[13])), max(__float_as_uint(a[14]), __float_as_uint(a[15]))), tag);
    }
    __syncwarp();
    WSTAMP(24);
    MSTAMP(4);
    cluster_wait();
    if (w == 0) {
      uint4 v[3];
      int n = 0;
      while (true) {
#pragma unroll
        for (int i = 0; i < 3; i++) v[i] = ldg_relaxed(&g_stats[(i * 32 + lane) * 2]);
        if (__all_sync(0xffffffffu, v[0].w == tag && v[1].w == tag && v[2].w == tag) || ++n > SPIN_LIMIT) break;
        __nanosleep(100);
      }
      WSTAMP(25);
      MSTAMP(5);
      const float sv = warp_sum(__uint_as_float(v[0].x) + __uint_as_float(v[1].x) + __uint_as_float(v[2].x));
      const float so = warp_sum(__uint_as_float(v[0].y) + __uint_as_float(v[1].y) + __uint_as_float(v[2].y));
      const int expW = ((int)(__float_as_uint(sv) >> 23) + (int)(__float_as_uint(so) >> 23) - 254 + 2 + 10 + 1) >> 1;
      sts32(sb + SC_XMAX + 4 * lane, v[0].z); sts32(sb + SC_XMAX + 128 + 4 * lane, v[1].z);
      sts32(sb + SC_EXPW, expW + 1 - 15);
      if (blockIdx.x == 0 && lane == 0) *(volatile unsigned*)&g_epoch = tag;
      sts32(sb + SC_FPAR + 4, 1);
    } else if (w < 3) {
      const uint32_t u = blockIdx.x >> 4;
      unsigned char* const z = g_red + 98304 + (blockIdx.x & 15) * 128 + (u & 1) * 2048 + (u & 6) * 4096 + (((u >> 1) ^ w) & 1) * 4096 + lane * 4;
      stg_relaxed32(z, 0);
      uint32_t best = 0xffffffffu;
#pragma unroll 1
      for (int i = 0; i < 64; i++) {
        uint32_t last, dt;
        asm volatile("{\n.reg .pred p;\n.reg .u32 c, v;\nld.volatile.shared.u32 %0, [%3];\nmov.u32 c, %%clock;\n"
                     "atom.relaxed.gpu.global.exch.b32 v, [%2], 0;\nsetp.eq.u32 p, v, 0;\nmov.u32 %1, 0;\n@p mov.u32 %1, %%clock;\nsub.u32 %1, %1, c;\n}"
                     : "=r"(last), "=r"(dt) : "l"(z), "r"(sb + SC_FPAR + 4) : "memory");
        best = min(best, dt);
        if ((last || PFIX) && i >= NPROBE - 1) break;
      }
      sts32(sb + SC_LAT + (w - 1) * 4, best);
    }
    bar_sync(13, 384);
    bar_arrive(0, 384);
    WSTAMP(26);
    TSTAMP(1);
    MSTAMP(6);
  }

  const uint32_t nh = __shfl_sync(0xffffffffu, near_half(sb), 0);
  uint32_t l16 = sb + lane * 16;
  PIN(l16);
#define LV ((l16 >> 4) & 31)
#define fence_reg l16
  const uint32_t red_lo = (uint32_t)(uint64_t)g_red, red_hi = (uint32_t)((uint64_t)g_red >> 32);
  uint32_t lp;
  auto slot = [&](int s, uint32_t c, uint32_t ofs) {
    const uint32_t lo = lp | (red_lo + ((w >> 1) * 4 + (w & 1) * 2 + ((w ^ c) & 1)) * 4096 + RED_SLOT(s) + ofs);
    uint64_t a; asm("mov.b64 %0, {%1, %2};" : "=l"(a) : "r"(lo), "r"(red_hi));
    return (unsigned char*)a;
  };
  const uint32_t always = __shfl_sync(0xffffffffu, lds32(sb + SC_DEAD + 12), 0);
  const int mode0 = RANK < 2 ? w : w | 4;
  auto hint_addr = [&](int s) { return min(LV, 23u) * 4 + (red_lo + HINT_OFF + nh * 4096 + w * 16384 + RED_SLOT(s)); };
  auto load_hints = [&](uint32_t lo) {
    uint64_t a; asm("mov.b64 %0, {%1, %2};" : "=l"(a) : "r"(lo), "r"(red_hi));
    return ldg_relaxed32((const void*)a);
  };
  const uint32_t blk = RANK < 2 ? 9216 : SEGB;
  auto send_v = [&](int seg, int pos) {
    if (RANK == 2 && ((w == 0 && VS0 == pos) || (w == 1 && VS1 == pos)) && seg > 1 && seg < NSEG && !(XP & 2)) {
      if (elect_one()) {
        fence_async();
        bulk_s2s(mapa(sb + SM_VC + (seg & 1) * 8192, w), sb + SM_BLK + (seg & 3) * SEGB, 8192, mapa(sb + MB_VX + (seg & 1) * 8, w));
      }
      __syncwarp();
    }
  };
  int s = 0;
  uint32_t dl = __shfl_sync(0xffffffffu, gtime() - 768, 0);
  bool bad = false;
#pragma unroll 1
  while (true) {
    const uint32_t par = s & 1;
    uint32_t vx[4][4], oc[4], hints;
    if (HP == 2) { hints = hint_addr(s); PIN(hints); }
    auto load_vx = [&]() {
      const uint32_t va = l16 + (RANK < 2 ? SM_VC + par * 8192 : SM_BLK + (s & 3) * SEGB) + w * 1024 + ((LV >> 3) & 1) * 384 - (LV >> 4) * 128;
      if (WL & 4) lds128(sb + SC_ONES, oc);
#pragma unroll
      for (int i = 0; i < 4; i++) ldsm4(vx[i], va + (i & 1) * 4096 + (i >> 1) * 256);
    };
    auto retire = [&](uint32_t x) {
      asm volatile("{\n.reg .pred p;\nsetp.eq.u32 p, %0, 0;\n@p exit;\n}" :: "r"(vx[0][0] | vx[1][0] | vx[2][0] | vx[3][0] | x | ((WL & 4) ? oc[0] : 0)) : "memory");
    };
    auto scores = [&](auto memkeys, auto first, float* sc) {
      constexpr bool MK = decltype(memkeys)::value, FIRST = decltype(first)::value;
      uint32_t kb[4][4], qb[2][4];
      const uint32_t m = LV >> 3;
      uint32_t kaddr = l16 + SM_BLK + 4096 + (s & 3) * SEGB + w * 2048 + (m & 1) * (MK ? 128 : 896) - (m >> 1) * 128;
      if (MK) { PIN(kaddr); }
      else {
#pragma unroll
        for (int k = 0; k < 4; k++) ldsm4t(kb[k], kaddr + k * 256);
      }
      if (FIRST) { load_vx(); retire(MK ? kaddr : kb[0][0] | kb[1][0] | kb[2][0] | kb[3][0] | l16); bar_sync(4, 256); RSTAMP(4); PROF(4); }
      ldsm4t(qb[0], l16 + SM_QM);
      if (MK) ldsm4t(kb[0], kaddr);
      ldsm4t(qb[1], l16 + SM_QM + 512);
      if (MK) ldsm4t(kb[2], kaddr + 512);
      float c[4][4];
      mma16816z(c[0], kb[0], qb[0][0], qb[0][1]); mma16816z(c[1], kb[MK ? 0 : 1], qb[0][2], qb[0][3]);
      mma16816z(c[2], kb[2], qb[1][0], qb[1][1]); mma16816z(c[3], kb[MK ? 2 : 3], qb[1][2], qb[1][3]);
      if (FIRST && B5POS == 0) bar_arrive(5, N5);
#pragma unroll
      for (int i = 0; i < (MK ? 2 : 4); i++) sc[i] = ((c[0][i] + c[1][MK ? i + 2 : i]) + c[2][i]) + c[3][MK ? i + 2 : i];
    };
    auto send = [&](auto memkeys) {
      constexpr bool MK = decltype(memkeys)::value;
      constexpr int N = MK ? 1 : 2;
      const uint32_t sa = sb + LV * 4 + SM_E + (MK ? 1024 + RANK * 128 : RANK * 512 + w * 256);
      uint32_t ra[N][2], mb[N][2];
#pragma unroll
      for (int i = 0; i < N; i++)
#pragma unroll
        for (int j = 0; j < 2; j++) {
          ra[i][j] = mapa(sa + i * 128, j ? 2 : RANK ^ 1); mb[i][j] = mapa(sb + MB_S, j ? 2 : RANK ^ 1);
          PIN(ra[i][j]);
        }
      float sc[4];
      scores(memkeys, BoolC<true>(), sc);
      uint32_t e[N];
#pragma unroll
      for (int i = 0; i < N; i++) {
        e[i] = pack_bf16(ex2(sc[2 * i]), ex2(sc[2 * i + 1]));
        if (!(fmaxf(fabsf(sc[2 * i]), fabsf(sc[2 * i + 1])) <= E_LIM)) e[i] = 0x7fff7fffu;
        st_async1(ra[i][0], e[i], mb[i][0]);
        st_async1(ra[i][1], e[i], mb[i][1]);
      }
#pragma unroll
      for (int i = 0; i < N; i++) sts32(sa + i * 128, e[i]);
      __syncwarp();
      if (l16 == sb) mbar_arrive(sb + MB_S);
      PROF(5);
    };
    const int mode = bad ? 8 : mode0;
    if (mode < 2) {
      send(BoolC<false>());
    } else if (mode == 2) {
      send(BoolC<true>());
    } else if (mode == 8) {
      load_vx();
      retire(l16);
      const uint32_t fp = lds32(sb + SC_FPAR);
      bar_sync(6, 128);
      if (w == 0 && l16 == sb) { sts32(sb + SC_FPAR, fp ^ 1); mbar_expect(sb + MB_F, 3072); }
      if (RANK < 2 && w < 3) {
        float sc[4] = {0.f, 0.f, 0.f, 0.f};
        if (w < 2) scores(BoolC<false>(), BoolC<false>(), sc); else scores(BoolC<true>(), BoolC<false>(), sc);
#pragma unroll 1
        for (int r = 0; r < 3; r++)
          st_async4(mapa(l16 + SM_FB + RANK * 1536 + w * 512, r), __float_as_uint(sc[0]), __float_as_uint(sc[1]), __float_as_uint(sc[2]), __float_as_uint(sc[3]), mapa(sb + MB_F, r));
      }
      mbar_wait(sb + MB_F, fp);
      float a[12];
#pragma unroll
      for (int j = 0; j < 3; j++) {
        float b[4];
        lds128f(l16 + SM_FB + j * 512, a + 4 * j); lds128f(l16 + SM_FB + 1536 + j * 512, b);
#pragma unroll
        for (int i = 0; i < 4; i++) a[4 * j + i] += b[i];
      }
      float m0 = fmaxf(fmaxf(fmaxf(a[0], a[2]), fmaxf(a[4], a[6])), a[8]), m1 = fmaxf(fmaxf(fmaxf(a[1], a[3]), fmaxf(a[5], a[7])), a[9]);
#pragma unroll
      for (int o = 4; o < 32; o <<= 1) { m0 = fmaxf(m0, __shfl_xor_sync(0xffffffffu, m0, o)); m1 = fmaxf(m1, __shfl_xor_sync(0xffffffffu, m1, o)); }
#pragma unroll
      for (int i = 0; i < 5; i++) {
        const uint32_t ea = sb + SM_E + LV * 4 + (i < 4 ? i * 128 : 1024);
        sts32(ea, pack_bf16(ex2(a[2 * i] - m0), ex2(a[2 * i + 1] - m1)));
        sts32(ea + (i < 4 ? 512 : 128), 0x3f803f80u);
      }
      __syncwarp();
    } else {
      load_vx();
      if (EXM && mode == 3) bar_arrive(4, 256);
      retire(l16 + 1);
      if (VS0 == 2 || VS1 == 2) send_v(s + 1, 2);
      if (w == 3) {
        uint32_t used = ldg_relaxed32(&g_used[blockIdx.x / 3 * 32]);
        if (!(XP & 4) && elect_one()) {
          if (s > 0) seg_publish(s - 1);
          fence_async();
          seg_store(s, sb, 0, 8192);
        }
        __syncwarp();
        if (!EXM) {
          bar_sync(RANK < 2 ? 4 : 15, RANK < 2 ? 256 : 160);
          if (!(XP & 4) && elect_one()) { fence_async(); seg_store(s, sb, 8192, blk - 8192); }
          __syncwarp();
        }
        const uint32_t need = lds32(sb + SC_EPOCH) + (s >= NRING - 1 ? s : -4 * NSEG);
#pragma unroll 1
        for (int n = 0; (int)(used - need) < 0 && n < ((XP & 64) ? 1 : SPIN_LIMIT); n++) used = ldg_relaxed32(&g_used[blockIdx.x / 3 * 32]);
      }
    }
    {
      uint32_t wa[4], wb[4];
      constexpr int WS = 2048;
      const uint32_t w3a = l16 + SM_WO3 + w * 512;
      if (HP == 1) { hints = hint_addr(s); PIN(hints); }
      if (!(WL & 1)) { lds128(w3a + KP(0) * WS, wa); lds128(w3a + KP(1) * WS, wb); }
      if (WL & 2) {
#pragma unroll
        for (int i = 0; i < 4; i++) oc[i] = always | (always >> 16) | (always & (i + 1));
      } else if (!(WL & 4)) lds128(sb + SC_ONES, oc);
      if (B5POS == 1 && mode < 3) bar_arrive(5, N5);
      uint32_t e[10], p[5], vm[4], ob[4];
      float o0[4], o1[4], f[3][2][4], rs[4];
      if (!(RV & 1)) { reserve2(vm); reserve2(vm + 2); }
      if (!(RV & 2)) reserve2(e + 8);
      if (!HP) { hints = hint_addr(s); PIN(hints); }
      if (CLR & 2) asm volatile("{\n.reg .pred p;\nsetp.eq.u32 p, %0, 0;\n@p exit;\n}" :: "r"(wa[0] | wb[0] | oc[0] | hints) : "memory");
      if (RV & 4) mbar_wait_fast(sb + MB_S, par); else mbar_wait(sb + MB_S, par);
      RSTAMP(5);
      PROF(6);
      if (RV & 2) { ldsm4t(e, l16 + SM_E); ldsm4t(e + 4, l16 + SM_E + 512); ldsm2t(e + 8, l16 + SM_E + 1024); }
      else { ldsm4t(e, l16 + SM_E); ldsm2t_in(e + 8, l16 + SM_E + 1024, always); ldsm4t(e + 4, l16 + SM_E + 512); }
      if (RV & 1) lds128(l16 + w * 512 + SM_VM, vm); else lds128_in(vm, l16 + w * 512 + SM_VM, always);
      const float scl = __uint_as_float(lds32(sb + SC_UNSC + 8 - par * 8));
      if (HL == 0) hints = load_hints(hints);
      if (GF & 1) SCHED_FENCE(4);
#pragma unroll
      for (int i = 0; i < 4; i++) p[i] = mul_bf16(e[i], e[4 + i]);
      p[4] = mul_bf16(e[8], e[9]);
      if (HL) hints = load_hints(hints | (p[HL - 1] & always & 1));
      mma16816z(o0, vx[0], p[0], p[1]);
      if (WL & 1) { lds128_in(vx[0], w3a + KP(0) * WS, always); }
      mma16816z(o1, vx[1], p[0], p[1]);
      if (WL & 1) { lds128_in(vx[1], w3a + KP(1) * WS, always); }
      mma16816z(rs, oc, p[0], p[1]);
      mma16816(o0, vx[2], p[2], p[3]); lds128_in(vx[2], w3a + KP(2) * WS, always);
      mma16816(o1, vx[3], p[2], p[3]); lds128_in(vx[3], w3a + KP(3) * WS, always);
      mma16816(rs, oc, p[2], p[3]);
      mma1688(o0, vm[0], vm[1], p[4]); mma1688(o1, vm[2], vm[3], p[4]); mma1688(rs, oc[0], oc[1], p[4]);
      stsm4(l16 + w * 512 + SM_OB, pack_bf16(o0[0], o0[1]), pack_bf16(o0[2], o0[3]), pack_bf16(o1[0], o1[1]), pack_bf16(o1[2], o1[3]));
      bar_sync(6, 128);
      RSTAMP(3);
      PROF(7);
      ldsm4t_in(oc, l16 + SM_OB, always);
      bad = __any_sync(0xffffffffu, !(rs[0] + rs[1] > 0.f) && !bad);
      rs[0] *= scl; rs[1] *= scl;
      asm volatile("{\n.reg .pred p;\nsetp.ne.u32 p, %1, 0;\n@p rcp.approx.ftz.f32 %0, %0;\n}" : "+f"(rs[0]) : "r"(always));
      asm volatile("{\n.reg .pred p;\nsetp.ne.u32 p, %1, 1;\n@p rcp.approx.ftz.f32 %0, %0;\n}" : "+f"(rs[1]) : "r"(always));
      asm volatile("lop3.b32 %0, %1, %2, %3, 0xfe;" : "=r"(lp) : "r"((l16 & 128) * 2), "r"((l16 & 256) * 4), "r"(l16 & 112));
      if (bad) continue;
      ldsm4t(ob, l16 + SM_OB + 512);
      mma16816z(f[2][0], WL & 1 ? vx[0] : wa, oc[0], oc[1]); mma16816z(f[2][1], WL & 1 ? vx[1] : wb, oc[2], oc[3]);
      mma16816z(f[0][0], wo[0], oc[0], oc[1]); mma16816z(f[0][1], wo[4], oc[2], oc[3]);
      mma16816z(f[1][0], w1[0], oc[0], oc[1]); mma16816z(f[1][1], w1[4], oc[2], oc[3]);
      ldsm4t_in(oc, l16 + SM_OB + 1024, always);
      mma16816(f[2][0], vx[2], ob[0], ob[1]); lds128_in(vx[2], w3a + KP(4) * WS, always);
      mma16816(f[2][1], vx[3], ob[2], ob[3]); lds128_in(vx[3], w3a + KP(5) * WS, always);
      mma16816(f[0][0], wo[1], ob[0], ob[1]); mma16816(f[0][1], wo[5], ob[2], ob[3]);
      mma16816(f[1][0], w1[1], ob[0], ob[1]); mma16816(f[1][1], w1[5], ob[2], ob[3]);
      ldsm4t_in(ob, l16 + SM_OB + 1536, always);
      mma16816(f[0][0], wo[2], oc[0], oc[1]); mma16816(f[0][1], wo[6], oc[2], oc[3]);
      mma16816(f[2][0], vx[2], oc[0], oc[1]); lds128_in(vx[2], w3a + KP(6) * WS, always);
      mma16816(f[2][1], vx[3], oc[2], oc[3]); lds128_in(vx[3], w3a + KP(7) * WS, always);
      mma16816(f[1][0], w1[2], oc[0], oc[1]); mma16816(f[1][1], w1[6], oc[2], oc[3]);
      mma16816(f[0][0], wo[3], ob[0], ob[1]); mma16816(f[0][1], wo[7], ob[2], ob[3]);
      mma16816(f[1][0], w1[3], ob[0], ob[1]); mma16816(f[1][1], w1[7], ob[2], ob[3]);
      mma16816(f[2][0], vx[2], ob[0], ob[1]); mma16816(f[2][1], vx[3], ob[2], ob[3]);
      bar_arrive(7, NII < 18 ? 384 : 256);
      lds128_in(ob, sb + SC_DEAD, always);
      uint32_t h[3][2];
#pragma unroll
      for (int j = 0; j < 3; j++)
#pragma unroll
        for (int i = 0; i < 2; i++)
        {
          scale_sum(f[j][1][2 * i], f[j][0][2 * i], rs[0], always); scale_sum(f[j][1][2 * i + 1], f[j][0][2 * i + 1], rs[1], always);
          h[j][i] = pack_f16(f[j][1][2 * i], f[j][1][2 * i + 1]);
        }
      const uint32_t rofs = RANK * 32768;
      red_f16x8(slot(s, RANK >> 1, rofs), h[0][0], h[1][0], h[2][0], 0x3c00u);
      red_f16x8(slot(s, (RANK >> 1) ^ 1, rofs), h[0][1], h[1][1], h[2][1], 0x3c00u);
      if (NII == 18) bar_arrive(10, 256);
      SCHED_FENCE(5);
      RSTAMP(0);
      l16 += ob[B7R];
    }
    {
    PROF(8);
    if (VS0 == 3 || VS1 == 3) send_v(s + 1, 3);
    const uint32_t ma0 = l16 + SM_MEM + w * 128 + (LV >> 3) * 896 + nh * 512;
    const unsigned char* const sl[2] = {slot(s, nh, 0), slot(s, nh ^ 1, 0)};
    uint32_t late = latest_hint(hints, dl, s);
    if (late >= 64) {
      int n = 0;
#pragma unroll 1
      do {
        late = latest_hint(load_hints(hint_addr(s)), dl, s);
      } while (late >= 64 && ++n < SPIN_LIMIT);
    }
    dl += late * 32 + tm.poll;
    if (s == 0 && PSTAMP) MSTAMP(7);
    PROF(9);
    {
      auto wait_until = [&](uint32_t t) {
        asm volatile("{\n.reg .pred p;\n.reg .s32 c;\n.reg .u64 t;\nTL: mov.u64 t, %%globaltimer;\ncvt.u32.u64 c, t;\nsub.s32 c, c, %0;\nsetp.lt.s32 p, c, 0;\n@p bra.uni TL;\n}" :: "r"(t + (l16 & 15)) : "memory");
      };
      uint4 v[2][3];
      auto load = [&](int c) {
#pragma unroll
        for (int r = 0; r < 3; r++) v[c][r] = ldg_relaxed(sl[c ^ (r >> 1)] + r * 32768);
      };
      auto decode = [&](int c, int n) {
        uint32_t q[9];
        __half2 hm;
        const uint32_t ma = ma0 ^ (c * 512);
#pragma unroll
        for (int i = 0; i < 9; i++) {
          const uint32_t h = i % 3 == 0 ? v[c][i / 3].x : (i % 3 == 1 ? v[c][i / 3].y : v[c][i / 3].z);
          const float2 f = __half22float2(*(const __half2*)&h);
          q[i] = pack_bf16(f.x, f.y);
          hm = i ? __hmax2(hm, __habs2(*(const __half2*)&h)) : __habs2(*(const __half2*)&h);
        }
#pragma unroll
        for (int r = 0; r < 3; r++) stsm4(ma + r * 4096, q[3 * r], q[3 * r + 1], q[3 * r + 2], r < 2 ? v[c][r].w : *(const uint32_t*)&hm);
        const bool done = __all_sync(0xffffffffu, v[c][0].w == 0x5000u && v[c][1].w == 0x5000u && v[c][2].w == 0x5000u) || n > SPIN_LIMIT;
        asm volatile("{\n.reg .pred p;\nsetp.ne.u32 p, %0, 0;\n@p bar.arrive %1, 256;\n}" :: "r"((int)done), "r"(1 + c) : "memory");
        return done;
      };
      if (LEAD) { wait_until(dl - LEAD); load(1); }
      wait_until(dl);
      PROF(10);
      int n = 0;
#pragma unroll 1
      do {
        load(0);
        if (!LEAD) load(1);
        asm volatile("{\n.reg .pred p;\nsetp.eq.u32 p, %0, 0;\n@p bar.sync 13, 384;\n}" :: "r"(n) : "memory");
      } while (!decode(0, n++));
      PROF(11);
      RSTAMP(1);
#pragma unroll 1
      while (!decode(1, n++)) load(1);
      bar_arrive(9, 256);
      RSTAMP(2);
      PROF(12);
    }
    PROF(13);
    if (++s == NSEG - 1) break;
    }
  }
#undef fence_reg
  if (RANK < 2) bar_arrive(4, 256);
  TSTAMP(49);
  {
    PIN(l16);
    tail_attention(sb, RANK, w, LV, 0, 6);
    TSTAMP(51);
    mbar_wait(sb + MB_WO, 1);
    TSTAMP(53);
#pragma unroll 1
    for (int sg = 0; sg < 2; sg++) {
      PIN(l16);
      const int lane = LV, m = lane >> 3, g = lane >> 2, t = lane & 3;
      const uint32_t ob = l16 + T_OB + sg * 8192;
      bar_sync(sg ? 0 : 8, 256);
      TSTAMP(54 + 2 * sg);
      const float inv = __uint_as_float(0x7f000000u - lds32(sb + T_UN + sg * 4));
#pragma unroll 1
      for (int j = 0; j < 4; j += 2) {
        float c[2][3][4];
        uint32_t x[4], y[4], z[2][4];
#pragma unroll
        for (int e = 0; e < 2; e++) {
          const uint32_t oa = sb + T_OA + ((sg * 4 + j + e) * 8 + g) * 64 + (blockIdx.x / 3 * 36 & 15) + t * 4;
          z[e][0] = lds32(oa); z[e][1] = lds32(oa + 16); z[e][2] = t ? 0u : lds32(oa + 32);
        }
#pragma unroll
        for (int i = 0; i < 3; i++) {
          const uint32_t wa = sb + T_WA + ((lane & 7) + ((lane >> 4) << 3)) * 128 + (((w + 4 * (m & 1)) ^ (lane & 7)) << 4);
          ldsm4t(x, wa + i * 3072); ldsm2t(y, wa + i * 3072 + 2048);
#pragma unroll
          for (int e = 0; e < 2; e++) { mma1688z(c[e][i], y[0], y[1], z[e][2]); mma16816(c[e][i], x, z[e][0], z[e][1]); }
        }
#pragma unroll
        for (int r = 0; r < 4; r++) {
          ldsm4t(z[0], ob + j * 2048 + r * 512); ldsm4t(z[1], ob + j * 2048 + 2048 + r * 512);
          lds128(l16 + SM_WO3 + w * 512 + r * 2048, x); lds128(l16 + SM_WO3 + w * 512 + (r + 4) * 2048, y);
#pragma unroll
          for (int e = 0; e < 2; e++) { mma16816(c[e][0], wo[r], z[e][0], z[e][1]); mma16816(c[e][1], w1[r], z[e][0], z[e][1]); mma16816(c[e][2], x, z[e][0], z[e][1]); }
#pragma unroll
          for (int e = 0; e < 2; e++) { mma16816(c[e][0], wo[r + 4], z[e][2], z[e][3]); mma16816(c[e][1], w1[r + 4], z[e][2], z[e][3]); mma16816(c[e][2], y, z[e][2], z[e][3]); }
        }
#pragma unroll
        for (int i = 0; i < 4; i++) {
          const float (&d)[3][4] = c[i >> 1];
          const int q = (i & 1) * 2;
          red_f16x8(g_red + T_RED + ((((sg * 4 + j + (i >> 1)) * 3 + RANK) * 4 + w) * 2 + (i & 1)) * 512 + lane * 16, pack_f16(d[0][q] * inv, d[0][q + 1] * inv),
                    pack_f16(d[1][q] * inv, d[1][q + 1] * inv), pack_f16(d[2][q] * inv, d[2][q + 1] * inv), 0x3c00u);
        }
      }
      TSTAMP(55 + 2 * sg);
    }
    if (RSLOW) { wait_until(gtime() + 8000); wait_until(gtime() + 8000); wait_until(gtime() + 4000); }
    if (w < 2) {
      const int b = blockIdx.x, lane = LV, g = lane >> 2, t = lane & 3;
      uint4 v;
#pragma unroll 1
      for (int n = 0; n < SPIN_LIMIT; n++) {
        v = ldg_relaxed(g_red + T_RED + (w * 96 + b) * 512 + lane * 16);
        if (__all_sync(0xffffffffu, v.w == 0x5000u)) break;
        __nanosleep(40);
      }
      const float un = __uint_as_float(lds32(sb + T_UN + w * 4));
      uint32_t* const o = (uint32_t*)(tm.out + (size_t)((NAUXSEG + w) * 32 + b / 24 * 8 + g) * DM + (b >> 3) % 3 * 192 + (b & 1) * 32 + (b & 6) * 4) + t;
#pragma unroll
      for (int j = 0; j < 3; j++) {
        const float2 f = __half22float2(*(const __half2*)(&v.x + j));
        o[j * 32] = movm(pack_bf16(f.x * un, f.y * un));
      }
    }
  }
  TSTAMP(3);
  MSTAMP(8);
  if (CSY) cluster_sync();
}

__global__ void __cluster_dims__(3, 1, 1) __launch_bounds__(384, 1)
rec_kernel(const __grid_constant__ RMaps tm, const bf16* __restrict__ x, const bf16* __restrict__ mem0) {
  extern __shared__ __align__(1024) unsigned char smem_raw[];
  const uint32_t sb = smem_u32(smem_raw);
  const int tid = threadIdx.x, lane = tid & 31;
  const int wg = __shfl_sync(0xffffffffu, tid >> 7, 0);
  const int w = __shfl_sync(0xffffffffu, (tid >> 5) & 3, 0);
  uint32_t rank; asm("mov.u32 %0, %%cluster_ctarank;" : "=r"(rank));
  STAMP(0);
  TSTAMP(0);
  asm volatile("griddepcontrol.launch_dependents;" ::: "memory");

#define PFT 1
  if (PFT && wg == 1 && lane == 0) asm volatile("prefetch.tensormap [%0];\nprefetch.tensormap [%1];" :: "l"(w & 1 ? &tm.woa : &tm.oa), "l"(w == 0 ? (rank < 2 ? &tm.wk : &tm.wv) : w == 1 ? &tm.wq : w == 2 ? &tm.x : &tm.wo) : "memory");
  if (wg < 2) {
    asm volatile("setmaxnreg.inc.sync.aligned.u32 192;");
    if (tid == 0) {
      for (int i = 0; i < 3; i++) { mbar_init(sb + MB_W + 8 * i, 1); mbar_init(sb + MB_X + 8 * i, 1); }
      mbar_init(sb + MB_WO, 1); mbar_init(sb + MB_WO3, 1);
      mbar_init(sb + MB_S, rank < 2 ? 5 : 6);
      mbar_init(sb + MB_F, 1);
      for (int i = 0; i < 3; i++) mbar_init(sb + MB_T + 8 * i, 1);
      mbar_init(sb + MB_VX, 1); mbar_init(sb + MB_VX + 8, 1);
      asm volatile("fence.mbarrier_init.release.cluster;" ::: "memory");
      fence_async();
      SSTAMP(11, 6);
      load_weights(sb, tm, rank, 0);
      for (int i = 0; i < 3; i++) mbar_expect(sb + MB_X + 8 * i, XT);
      tma_load3(sb + SM_X, &tm.x, 0, sb + MB_X);
      if (!PACE) for (int c = 1; c < 4; c++) load_weights(sb, tm, rank, c);
      mbar_expect(sb + MB_S, rank < 2 ? 640 + 2048 : 1280);
      mbar_expect(sb + MB_VX, 8192); mbar_expect(sb + MB_VX + 8, 8192);
      mbar_expect(sb + MB_T, 2048);
      for (int i = 1; i < 3; i++) mbar_expect(sb + MB_T + 8 * i, rank < 2 ? 5120 : 10240);
      SSTAMP(11, 5);
    }
    __syncwarp();
    bar_sync(0, 384);
    proj_role(sb, tm, rank, wg, w, lane);
  } else {
    asm volatile("setmaxnreg.dec.sync.aligned.u32 120;");
    attn_role(sb, smem_raw, tm, rank, x, mem0, w, lane);
  }
}

constexpr int A_XH = 73728;
constexpr int A_NS = 9, A_WM = 6144, A_WT = 768;
constexpr int A_RING = 2 * A_XH, A_TAIL = A_RING + A_NS * A_WM, A_GW = A_TAIL + A_NS * A_WT;
constexpr int A_EPI = 212864, A_EPW = 9344;
constexpr int A_XW = 4 * XT, A_XT = A_XW + 4096, A_NR = 4;
constexpr int A_IN = A_XT + 2048, A_INS = 2 * 9216 + SEGB, A_OST = A_IN + 2 * A_INS;
constexpr int A_GATE = A_EPI + 2 * A_EPW, A_BAR = A_GATE + 512;
constexpr int A_TOTAL = A_BAR + 384;
struct AMaps { CUtensorMap x, wa, wt, oa, o, o3, o8, wob, woa, wo8; };

DI void wgmma_n192_ss_nt(float* d, uint64_t da, uint64_t db, int acc) {
  asm volatile("{\n.reg .pred p;\nsetp.ne.b32 p, %98, 0;\n"
               "wgmma.mma_async.sync.aligned.m64n192k16.f32.bf16.bf16 {"
               "%0,%1,%2,%3,%4,%5,%6,%7,%8,%9,%10,%11,%12,%13,%14,%15,%16,%17,%18,%19,%20,%21,%22,%23,%24,%25,%26,%27,%28,%29,%30,%31,"
               "%32,%33,%34,%35,%36,%37,%38,%39,%40,%41,%42,%43,%44,%45,%46,%47,%48,%49,%50,%51,%52,%53,%54,%55,%56,%57,%58,%59,%60,%61,%62,%63,"
               "%64,%65,%66,%67,%68,%69,%70,%71,%72,%73,%74,%75,%76,%77,%78,%79,%80,%81,%82,%83,%84,%85,%86,%87,%88,%89,%90,%91,%92,%93,%94,%95"
               "}, %96, %97, p, 1, 1, 0, 1;\n}\n"
               : ACC8(d, 0), ACC8(d, 8), ACC8(d, 16), ACC8(d, 24), ACC8(d, 32), ACC8(d, 40), ACC8(d, 48), ACC8(d, 56),
                 ACC8(d, 64), ACC8(d, 72), ACC8(d, 80), ACC8(d, 88) : "l"(da), "l"(db), "r"(acc));
}
#define ACC4(d, o) "+f"(d[o]), "+f"(d[o + 1]), "+f"(d[o + 2]), "+f"(d[o + 3])
DI void wgmma_n24_ss_nt(float* d, uint64_t da, uint64_t db, int acc) {
  asm volatile("{\n.reg .pred p;\nsetp.ne.b32 p, %14, 0;\n"
               "wgmma.mma_async.sync.aligned.m64n24k16.f32.bf16.bf16 {%0,%1,%2,%3,%4,%5,%6,%7,%8,%9,%10,%11}, %12, %13, p, 1, 1, 0, 1;\n}\n"
               : ACC8(d, 0), ACC4(d, 8) : "l"(da), "l"(db), "r"(acc));
}
DI void wgmma_n8_ss(float* d, uint64_t da, uint64_t db, int acc) {
  asm volatile("{\n.reg .pred p;\nsetp.ne.b32 p, %6, 0;\n"
               "wgmma.mma_async.sync.aligned.m64n8k16.f32.bf16.bf16 {%0,%1,%2,%3}, %4, %5, p, 1, 1, 0, 0;\n}\n"
               : ACC4(d, 0) : "l"(da), "l"(db), "r"(acc));
}
DI void wgmma_n40_ss_tt(float* d, uint64_t da, uint64_t db, int acc) {
  asm volatile("{\n.reg .pred p;\nsetp.ne.b32 p, %22, 0;\n"
               "wgmma.mma_async.sync.aligned.m64n40k16.f32.bf16.bf16 {%0,%1,%2,%3,%4,%5,%6,%7,%8,%9,%10,%11,%12,%13,%14,%15,%16,%17,%18,%19}, "
               "%20, %21, p, 1, 1, 1, 1;\n}\n"
               : ACC8(d, 0), ACC8(d, 8), ACC4(d, 16) : "l"(da), "l"(db), "r"(acc));
}
DI void wgmma_n64_rs(float* d, const uint32_t* a, uint64_t db, int acc) {
  asm volatile("{\n.reg .pred p;\nsetp.ne.b32 p, %37, 0;\n"
               "wgmma.mma_async.sync.aligned.m64n64k16.f32.bf16.bf16 {"
               "%0,%1,%2,%3,%4,%5,%6,%7,%8,%9,%10,%11,%12,%13,%14,%15,%16,%17,%18,%19,%20,%21,%22,%23,%24,%25,%26,%27,%28,%29,%30,%31"
               "}, {%32,%33,%34,%35}, %36, p, 1, 1, 0;\n}\n"
               : ACC8(d, 0), ACC8(d, 8), ACC8(d, 16), ACC8(d, 24) : "r"(a[0]), "r"(a[1]), "r"(a[2]), "r"(a[3]), "l"(db), "r"(acc));
}
DI void wgmma_n32_ss_tn(float* d, uint64_t da, uint64_t db, int acc) {
  asm volatile("{\n.reg .pred p;\nsetp.ne.b32 p, %18, 0;\n"
               "wgmma.mma_async.sync.aligned.m64n32k16.f32.bf16.bf16 {%0,%1,%2,%3,%4,%5,%6,%7,%8,%9,%10,%11,%12,%13,%14,%15}, "
               "%16, %17, p, 1, 1, 1, 0;\n}\n"
               : ACC8(d, 0), ACC8(d, 8) : "l"(da), "l"(db), "r"(acc));
}
DI void tma_load3c(uint32_t dst, const CUtensorMap* m, int c0, int c1, int c2, uint32_t mb) {
  asm volatile("cp.async.bulk.tensor.3d.shared::cluster.global.mbarrier::complete_tx::bytes [%0], [%1, {%3, %4, %5}], [%2];"
               :: "r"(dst), "l"(m), "r"(mb), "r"(c0), "r"(c1), "r"(c2) : "memory");
}
DI void count_up(unsigned* p) {
  asm volatile("fence.proxy.async;" ::: "memory");
  asm volatile("red.release.gpu.global.add.u32 [%0], 1;" :: "l"(p) : "memory");
}
#define AX 0
#define FDLY 400
#define FEND 59
DI void publish(unsigned* p) {
  asm volatile("cp.async.bulk.wait_group 0;\nfence.proxy.async;" ::: "memory");
  asm volatile("red.relaxed.gpu.global.add.u32 [%0], 1;" :: "l"(p) : "memory");
}
#define PL 2
#define SER 35
#define DRAIN 0
#define PR 4
#define NQ 3
#define PUB 0
#define LA 1
#define LAG0 12
#define LEND 58
#define PDLY 0
#define ADLY 0

__global__ void __launch_bounds__(512, 1)
aux_kernel(const __grid_constant__ AMaps tm, const bf16* __restrict__ wqkv, const bf16* __restrict__ woa, const bf16* __restrict__ gate_w, bf16* __restrict__ out) {
  extern __shared__ __align__(1024) unsigned char smem_raw[];
  const uint32_t sb = smem_u32(smem_raw);
  const uint32_t fullx = sb + A_BAR, full1 = fullx + 24, empty1 = full1 + 8 * A_NS, fullw = empty1 + 8 * A_NS, full3 = fullw + 8, empty3 = full3 + 8 * A_NR,
                 fullq = empty3 + 8 * A_NR, emptyq = fullq + 24, fullo = emptyq + 24, emptyo = fullo + 16;
  const int tid = threadIdx.x, lane = tid & 31, cta = blockIdx.x;
  const int wg = __shfl_sync(0xffffffffu, tid >> 7, 0), w = __shfl_sync(0xffffffffu, (tid >> 5) & 3, 0);
  ASTAMP(14);
  if (tid == 384) {
    for (int i = 0; i < 3; i++) mbar_init(fullx + 8 * i, 1);
    for (int i = 0; i < A_NS; i++) { mbar_init(full1 + 8 * i, 1); mbar_init(empty1 + 8 * i, 8); }
    mbar_init(fullw, 1);
    for (int i = 0; i < 3; i++) { mbar_init(fullq + 8 * i, 1); mbar_init(emptyq + 8 * i, 4); }
    for (int i = 0; i < 2; i++) { mbar_init(fullo + 8 * i, 4); mbar_init(emptyo + 8 * i, 1); }
    for (int i = 0; i < A_NR; i++) { mbar_init(full3 + 8 * i, 1); mbar_init(empty3 + 8 * i, cta < NH ? 8 : 4); }
    fence_async();
  }
  __syncthreads();
  ASTAMP(0);
  const int tile = cta >> 1, hh = cta & 1;
  auto p3_n = [&](int g) { return cta < NH ? (cta & 3) * 2 + g : 8; };
  auto p3_next = [&](int& sl, int& ph) {
    sl += cta < NH ? 1 : 2;
    if (sl >= (cta < NH ? 6 - NQ : 4)) { sl -= cta < NH ? 6 - NQ : 4; ph ^= 1; }
  };
  auto p3_k = [&](int g) { return cta < NH ? cta >> 2 : (cta & 3) * 2 + g; };
  if (wg == 3) {
    asm volatile("setmaxnreg.dec.sync.aligned.u32 24;");
    const bool lead = lane == 0;
    if (w < 3) {
      if (ADLY) wait_until(gtime() + ADLY);
      if (elect_one()) {
        mbar_expect(fullx + 8 * w, 49152);
        for (int p = 0; p < 2; p++)
          asm volatile("cp.async.bulk.tensor.4d.shared::cluster.global.mbarrier::complete_tx::bytes [%0], [%1, {%3, %4, %5, %6}], [%2];"
                       :: "r"(sb + p * A_XH + w * 24576), "l"(&tm.x), "r"(fullx + 8 * w), "r"(0), "r"(p), "r"(57 * tile - 7), "r"(3 * w) : "memory");
      }
#pragma unroll 1
      for (int r = 0; r < 17; r++) {
#pragma unroll 1
        for (int st = w; st < A_NS; st += 3) {
          if (r > 0) mbar_wait(empty1 + 8 * st, ~r & 1);
          if (r < 16 && elect_one()) {
            const int col = hh * 288 + (r >> 2) * 72, row = (r & 3) * 144 + st * 16;
            mbar_expect(full1 + 8 * st, A_WM + (AX & 1 ? 0 : A_WT));
            tma_load3c(sb + A_RING + st * A_WM, &tm.wa, col, row, 0, full1 + 8 * st);
            if (!(AX & 1)) tma_load3c(sb + A_TAIL + st * A_WT, &tm.wt, col + 64, row, 0, full1 + 8 * st);
          }
          __syncwarp();
        }
        if (r == 0 && elect_one())
          for (int j = 0; j < 3; j++)
            asm volatile("cp.async.bulk.prefetch.L2.global [%0], %1;" :: "l"((const char*)wqkv + cta * 55296 + (w * 3 + j) * 6144), "r"(6144) : "memory");
        __syncwarp();
      }
      bar_sync(8, 96);
    }
    const unsigned epoch = lds32(sb + A_BAR + 376);
    if (w == 2 && cta < NH) {
      if (lead) {
        int avail = 0, q = 0, ph = 1;
#pragma unroll 1
        for (int seg = 0; seg < NAUXSEG; seg++) {
          const unsigned char* const src = g_seg + ((size_t)(AX & 128 ? 0 : seg % NRING) * 96 + cta * 3) * SEGB;
          SSTAMP(0, seg);
          const int ref = seg + max(LAG0 * (LEND - seg) / LEND, 0);
          if (ref >= avail) {
            const unsigned* const c = &g_scnt[(ref * 32 + cta) * 8];
            const int c2 = ldg_relaxed32(c + 512) - 3 * (epoch + 1), c0 = ldg_acquire32(c) - 3 * (epoch + 1);
            avail = ref + (c2 >= 0 && LA ? 3 : 1);
            if (c0 < 0) {
              wait_count(c, 3 * (epoch + 1), !(TL & 2) || seg < NAUXSEG - 2);
              if (FDLY && seg < FEND) wait_until(gtime() + FDLY);
            }
          }
          SSTAMP(1, seg);
          const uint32_t mb = fullq + q * 8;
          mbar_wait(emptyq + q * 8, q == 2 ? ph ^ 1 : ph);
          if (AX & 8) mbar_arrive(mb); else mbar_expect(mb, A_INS);
#pragma unroll 1
          for (int r = 0; r < ((AX & 8) ? 0 : 3); r++)
            asm volatile("cp.async.bulk.shared::cluster.global.mbarrier::complete_tx::bytes [%0], [%1], %2, [%3];"
                         :: "r"(sb + (q < 2 ? A_IN + q * A_INS : 3 * XT) + r * 9216), "l"(src + r * SEGB), "r"(r < 2 ? 9216 : SEGB), "r"(mb) : "memory");
          if (seg == 1) wait_count(&g_abar[32], NAUX * (epoch + 1));
          if (seg > 1) stg_relaxed32(&g_used[cta * 32], epoch * NSEG + seg + 1 - NQ);
          if (++q == NQ) { q = 0; ph ^= 1; }
        }
      }
      return;
    }
    if (w == 3) {
#pragma unroll 1
      for (int c = 0; c < 4; c++) {
        if (lead) asm volatile("cp.async.bulk.wait_group.read 0;" ::: "memory");
        __syncwarp();
        bar_arrive(11, 160); bar_arrive(12, 160);
#pragma unroll 1
        for (int g = 0; g < 2; g++) {
          bar_sync(13 + g, 160);
          if (lead) {
            asm volatile("cp.async.bulk.tensor.3d.global.shared::cta.bulk_group [%0, {%2, %3, %4}], [%1];"
                         :: "l"(&tm.oa), "r"(sb + A_EPI + g * A_EPW + 1024), "r"(4096 + hh * 288 + c * 72), "r"(g), "r"(57 * tile) : "memory");
            asm volatile("cp.async.bulk.commit_group;" ::: "memory");
          }
        }
      }
      if (lead) {
        asm volatile("cp.async.bulk.wait_group.read 0;" ::: "memory");
        mbar_arrive(emptyo); mbar_arrive(emptyo + 8);
        publish(&g_abar[32]);
      }
      __syncwarp();
    }
    if ((w & 1) && cta < NH) {
#pragma unroll 1
      for (int seg = w >> 1; seg < NAUXSEG; seg += 2) {
        if (lead) {
          mbar_wait(fullo + (w >> 1) * 8, (seg >> 1) & 1);
          fence_async();
          tma_store(&tm.o, sb + A_OST + (w >> 1) * 8192, cta * DH, seg * 32);
          tma_store(&tm.o, sb + A_OST + (w >> 1) * 8192 + 4096, cta * DH + 64, seg * 32);
          asm volatile("cp.async.bulk.commit_group;\ncp.async.bulk.wait_group.read 0;" ::: "memory");
          mbar_arrive(emptyo + (w >> 1) * 8);
          if (PUB == 0 || seg >= NAUXSEG - 2) publish(&g_ocnt[seg * 64 + 2 * cta / 9 * 8]);
          else {
            if (PUB == 1) asm volatile("fence.acq_rel.gpu;" ::: "memory"); else if (PUB > 2) wait_until(gtime() + PUB);
            asm volatile("red.relaxed.gpu.global.add.u32 [%0], 1;" :: "l"(&g_ocnt[seg * 64 + 2 * cta / 9 * 8]) : "memory");
          }
          if (2 * cta / 9 != (2 * cta + 1) / 9) asm volatile("red.relaxed.gpu.global.add.u32 [%0], 1;" :: "l"(&g_ocnt[seg * 64 + (2 * cta + 1) / 9 * 8]) : "memory");
          SSTAMP(9, seg);
        }
        __syncwarp();
      }
    }
    if (w & 1) return;
    if (w == 0) {
      if (lead) {
        mbar_expect(fullw, 18 * 8192 + 2048);
#pragma unroll 1
        for (int k = 0; k < 18; k++) {
          const int g = k / 9, kb = p3_k(g) * 9 + k - 9 * g;
          if (kb < 64) tma_load(sb + k * 8192, &tm.wob, p3_n(g) * 64, kb * 64, fullw);
          else tma_load(sb + k * 8192, &tm.woa, p3_n(g) * 64, (kb - 64) * 64, fullw);
        }
        for (int g = 0; g < 2; g++) tma_load(sb + A_XW + g * 2048, &tm.wo8, p3_n(g) * 64, 512 + p3_k(g) * 8, fullw);
      }
      __syncwarp();
    }
    bar_sync(6, cta >= NH ? 320 : 288);
    if (lead) {
      if (NQ == 3) for (int i = 0; i < 4; i++) mbar_arrive(emptyq + 16);
      wait_count(&g_abar[32], NAUX * (epoch + 1));
      int avail = 0, sl = w >> 1, ph = 1;
      const int ke = p3_k(w >> 1);
      const unsigned nheads = (ke < 7 ? 5 : 1) * (epoch + 1);
#pragma unroll 1
      for (int seg = 0; seg < NAUXSEG; seg++) {
        bool waited = false;
        if (seg >= avail) {
          const unsigned* const c = &g_ocnt[seg * 64 + ke * 8];
          const int c2 = ldg_relaxed32(c + 128) - nheads, c1 = ldg_relaxed32(c + 64) - nheads, c0 = ldg_acquire32(c) - nheads;
          waited = c0 < 0;
          if (waited) { wait_count(c, nheads, !(TL & 2) || seg < NAUXSEG - 2); if (PDLY && seg < FEND) wait_until(gtime() + PDLY); }
          else if (c1 >= 0) avail = seg + (c2 >= 0 ? 3 : 2);
        }
        SSTAMP(5, seg);
        mbar_wait(empty3 + 8 * sl, ph);
        if (AX & 4) mbar_arrive(full3 + 8 * sl);
        else {
          mbar_expect(full3 + 8 * sl, XT + 512);
          tma_load3c(sb + sl * XT, &tm.o3, 0, seg * 32, ke * 9, full3 + 8 * sl);
          tma_load(sb + A_XT + sl * 512, &tm.o8, 72 * 64 + ke * 8, seg * 32, full3 + 8 * sl);
        }
        p3_next(sl, ph);
      }
    }
  } else if (wg == 2) {
    asm volatile("setmaxnreg.dec.sync.aligned.u32 88;");
    {
      const unsigned epoch = *(volatile unsigned*)&g_epoch2;
      if ((tid & 127) < 80) { const uint4 g = __ldg((const uint4*)gate_w + min(tid & 127, 71)); sts128(sb + A_GW + (tid & 127) * 16, g.x, g.y, g.z, g.w); }
      fence_async();
      bar_sync(3, 128);
      float gt[2][4];
      const uint32_t d0 = (sb & 0x3FFFF) >> 4;
#pragma unroll 1
      for (int j = 0; j < 3; j++) {
        mbar_wait(fullx + 8 * j, 0);
        WG_FENCE();
#pragma unroll
        for (int k = 0; k < 24; k++)
          wgmma_n8_ss(gt[k & 1], desc_at(d0 + (k & 1) * (A_XH >> 4) + j * 1536 + (k >> 3) * 512 + (k & 6), 16, 1024, 1), desc_at(d0 + (A_GW >> 4) + j * 24 + (k & 30), 16, 128, 0), j | (k >> 1));
        WG_COMMIT();
      }
      WG_WAIT(0);
      if ((lane & 3) == 0)
#pragma unroll
        for (int i = 0; i < 4; i++) {
          const float gv = 1.f / (1.f + __expf(-gt[i >> 1][(i & 1) * 2]));
          const int r = w * 16 + (lane >> 2) + (i & 1) * 8, tok = 2 * (57 * tile - 7 + r) + (i >> 1);
          sts32(sb + A_GATE + ((i >> 1) * 64 + r) * 4, __float_as_uint(gv));
          if (hh == 0 && r >= 7 && tok < S_LEN) g_gate[tok] = gv;
        }
      if (tid == 256) sts32(sb + A_BAR + 376, epoch);
      __syncwarp();
      bar_arrive(7, 384);
      __half2 hw = __float2half2_rn(0.f);
#pragma unroll
      for (int i = 0; i < 9; i++) { const uint4 v = __ldg((const uint4*)woa + cta * 1152 + i * 128 + (tid & 127)); hw = amax4(hw, &v.x); }
      const uint32_t ew = wexp(hw);
      if (lane == 0) atomicMax(&g_amax[0], (unsigned long long)(epoch + 1) << 32 | ew);
      bar_sync(3, 128);
      if (tid == 256) {
        count_up(&g_abar[0]);
        wait_count(&g_abar[0], NAUX * (epoch + 1));
        if (cta == 0) *(volatile unsigned*)&g_epoch2 = epoch + 1;
      }
      __syncwarp();
      bar_sync(3, 128);
    }
    if (cta < NH) {
      const int lim = w * 8 + (lane >> 2) - 2 * (lane & 3);
      int q = 0, ph = 0;
      uint32_t p[5][4];
#pragma unroll
      for (int n = 0; n < 10; n++) p[n >> 1][1 + (n & 1)] = __shfl_sync(0xffffffffu, lane ^ n, n);
#pragma unroll 1
      for (int seg = 0; seg < NAUXSEG; seg++) {
        const float gt = __ldcg(&g_gate[seg * 32 + w * 8 + (lane >> 2)]);
        float sc[20], d[32];
        const uint32_t d0 = ((sb & 0x3FFFF) + (q < 2 ? A_IN + q * A_INS : 3 * XT)) >> 4;
        mbar_wait(fullq + q * 8, ph);
        if (tid == 256) SSTAMP(2, seg);
        WG_FENCE();
#pragma unroll
        for (int k = 0; k < 8; k++) {
          const int o = ((k >> 2) * 9216 + (k & 3) * 256) >> 4;
          wgmma_n40_ss_tt(sc, desc_at(d0 + o, 128, 512, 0), desc_at(d0 + o + 256, 128, 1024, 0), k > 0);
        }
        WG_COMMIT();
        WG_WAIT(0);
        if (tid == 256) SSTAMP(12, seg);
        float a[10];
#pragma unroll
        for (int i = 0; i < 10; i++) {
          a[i] = sc[(i >> 1) * 4 + (i & 1)] * (SM_SCALE * LOG2E);
          if (i < 8 && (i >> 1) * 8 + (i & 1) > lim) a[i] = -1.0e9f * LOG2E;
        }
        float m = max10(a);
        m = fmaxf(m, __shfl_xor_sync(0xffffffffu, m, 1)); m = fmaxf(m, __shfl_xor_sync(0xffffffffu, m, 2));
#pragma unroll
        for (int i = 0; i < 10; i++) a[i] = ex2(a[i] - m);
#pragma unroll
        for (int n = 0; n < 5; n++) {
          p[n][0] = pack_bf16(a[2 * n], a[2 * n + 1]); p[n][3] = p[n][0] | p[n][1];
          asm volatile("" : "+r"(p[n][0]), "+r"(p[n][3]) :: "memory");
        }
        float sum = ((a[0] + a[1]) + (a[2] + a[3])) + ((a[4] + a[5]) + (a[6] + a[7])) + (a[8] + a[9]);
        sum += __shfl_xor_sync(0xffffffffu, sum, 1);
        if (tid == 256) SSTAMP(3, seg);
        WG_FENCE();
#pragma unroll
        for (int n = 0; n < 5; n++) wgmma_n64_rs(d, p[n], n < 4 ? desc_at(d0 + 1152 + 8 * n, 4096, 512, 0) : desc_at(d0 + 1152 + 512, 1024, 128, 0), n);
        WG_COMMIT();
        sum += __shfl_xor_sync(0xffffffffu, sum, 2);
        const float f = (1.f - gt) * rcp(sum);
        WG_WAIT(0);
        if (lane == 0) mbar_arrive(emptyq + q * 8);
        if (++q == NQ) { q = 0; ph ^= 1; }
        if (tid == 256) SSTAMP(4, seg);
        mbar_wait(emptyo + (seg & 1) * 8, (seg >> 1) & 1);
#pragma unroll
        for (int n = 0; n < 4; n++) {
          const float* const v = d + (n & 1) * 16 + (n & 2);
          stsm4(sb + A_OST + (seg & 1) * 8192 + (n >> 1) * 4096 + (w * 8 + (lane & 7)) * 128 + ((((n & 1) * 4 + (lane >> 3)) ^ (lane & 7)) << 4),
                pack_bf16(v[0] * f, v[1] * f), pack_bf16(v[4] * f, v[5] * f), pack_bf16(v[8] * f, v[9] * f), pack_bf16(v[12] * f, v[13] * f));
        }
        __syncwarp();
        if (lane == 0) mbar_arrive(fullo + (seg & 1) * 8);
        if (tid == 256) SSTAMP(13, seg);
      }
    }
  } else {
    asm volatile("setmaxnreg.inc.sync.aligned.u32 200;");
    {
      const int g = lane >> 2, t = lane & 3;
      const uint32_t eb = sb + A_EPI + wg * A_EPW, d0 = (sb & 0x3FFFF) >> 4;
      const uint32_t own = (2 * t <= g ? 0xffffu : 0u) | (2 * t < g ? 0xffff0000u : 0u);
      const int kmin = 7 - 57 * tile - 16 * w;
      __half2 ho = __float2half2_rn(0.f);
#pragma unroll 1
      for (int c = 0; c < 4; c++) {
        float acc[96], tl[12];
#pragma unroll 1
        for (int r = 0; r < 4; r++) {
#pragma unroll
          for (int st = 0; st < A_NS; st++) {
            const int ks = r * 9 + st;
            if (c == 0 && st % 3 == 0 && ks % 12 == 0) mbar_wait(fullx + 8 * (ks / 12), 0);
            mbar_wait(full1 + 8 * st, r & 1);
            const uint64_t da = desc_at(d0 + wg * (A_XH >> 4) + (ks >> 2) * 512 + (ks & 3) * 2, 16, 1024, 1);
            WG_FENCE();
            wgmma_n192_ss_nt(acc, da, desc_at(d0 + ((A_RING + st * A_WM) >> 4), 2048, 1024, 1), ks);
            if (!(AX & 2)) wgmma_n24_ss_nt(tl, da, desc_at(d0 + ((A_TAIL + st * A_WT) >> 4), 128, 256, 0), ks);
            WG_COMMIT();
            if (st == 0 && r == 2) bar_sync(11 + wg, 160);
            WG_WAIT(1);
            if (ks > 0 && lane == 0) mbar_arrive(empty1 + 8 * ((st + A_NS - 1) % A_NS));
          }
        }
        WG_WAIT(0);
        if (lane == 0) mbar_arrive(empty1 + 8 * (A_NS - 1));
        ASTAMP(16 + (c & 3));
        uint32_t ql[9], qh[9], kl[9], kh[9], kx[10], vl[9], vh[9], vx[10];
#pragma unroll
        for (int j = 0; j < 9; j++) {
          const float* const q = j < 8 ? acc + 4 * j : tl, * const k = j < 8 ? acc + 32 + 4 * j : tl + 4, * const v = j < 8 ? acc + 64 + 4 * j : tl + 8;
          kh[j] = pack_bf16(k[2], k[3]); vh[j] = pack_bf16(v[2], v[3]);
          ql[j] = pack_bf16(q[0], q[1]); qh[j] = pack_bf16(q[2], q[3]); kl[j] = pack_bf16(k[0], k[1]); vl[j] = pack_bf16(v[0], v[1]);
        }
        if (w < 3) {
          const uint32_t ha = eb + 1024 + w * 2304 + lane * 16;
          stsm4(ha, kh[0], kh[1], kh[2], kh[3]); stsm4(ha + 512, kh[4], kh[5], kh[6], kh[7]);
          stsm4(ha + 1024, vh[0], vh[1], vh[2], vh[3]); stsm4(ha + 1536, vh[4], vh[5], vh[6], vh[7]);
          asm volatile("stmatrix.sync.aligned.m8n8.x2.shared.b16 [%0], {%1,%2};" :: "r"(ha + 2048), "r"(kh[8]), "r"(vh[8]) : "memory");
        }
        if (c == 0) bar_sync(7, 384); else bar_sync(1 + wg, 128);
        {
          const uint32_t ha = eb + 1024 + max(w - 1, 0) * 2304 + lane * 16;
          ldsm4(kx, ha); ldsm4(kx + 4, ha + 512); ldsm4t(vx, ha + 1024); ldsm4t(vx + 4, ha + 1536);
          asm volatile("ldmatrix.sync.aligned.m8n8.x1.shared.b16 {%0}, [%1];" : "=r"(kx[8]) : "r"(ha + 2048) : "memory");
          asm volatile("ldmatrix.sync.aligned.m8n8.x1.trans.shared.b16 {%0}, [%1];" : "=r"(vx[8]) : "r"(ha + 2176) : "memory");
        }
        const float gl = __uint_as_float(lds32(sb + A_GATE + (wg * 64 + w * 16 + g) * 4)), gh = __uint_as_float(lds32(sb + A_GATE + (wg * 64 + w * 16 + g + 8) * 4));
#pragma unroll
        for (int j = 0; j < 9; j++) { vl[j] = movm(vl[j]); vh[j] = movm(vh[j]); }
        bar_sync(1 + wg, 128);
        uint32_t ol[9], oh[9];
#pragma unroll
        for (int i = 0; i < 4; i++) {
          const int b = 2 * i;
          const uint32_t a[4] = {t >= i ? ql[b] : 0u, t >= i ? qh[b] : 0u, ql[b + 1], qh[b + 1]}, a4 = t <= i ? ql[b + 2] : 0u, a5 = t <= i ? qh[b + 2] : 0u;
          float sx[4], sl[4], sh[4];
          mma16816z(sx, a, kx[b], kx[b + 1]); mma16816z(sl, a, kl[b], kl[b + 1]); mma16816z(sh, a, kh[b], kh[b + 1]);
          mma1688(sx, a4, a5, kx[b + 2]); mma1688(sl, a4, a5, kl[b + 2]); mma1688(sh, a4, a5, kh[b + 2]);
          float e[4];
#pragma unroll
          for (int u = 0; u < 4; u++) {
            const int cc = 2 * t + (u & 1);
            e[u] = (cc <= g ? (u < 2 ? sl[u] : sh[u]) : (u < 2 ? sx[u] : sl[u])) * (0.23570226039551584f * LOG2E);
            if ((cc <= g ? cc : cc - 8) + (u & 2) * 4 < kmin) e[u] = -1.0e9f * LOG2E;
          }
          float m0 = fmaxf(e[0], e[1]), m1 = fmaxf(e[2], e[3]);
#pragma unroll
          for (int o = 1; o < 4; o <<= 1) { m0 = fmaxf(m0, __shfl_xor_sync(0xffffffffu, m0, o)); m1 = fmaxf(m1, __shfl_xor_sync(0xffffffffu, m1, o)); }
          e[0] = ex2(e[0] - m0); e[1] = ex2(e[1] - m0); e[2] = ex2(e[2] - m1); e[3] = ex2(e[3] - m1);
          const uint32_t p0 = pack_bf16(e[0], e[1]), p1 = pack_bf16(e[2], e[3]);
          const uint32_t p[4] = {p0 & ~own, 0u, p0 & own, p1 & ~own};
          float s0 = e[0] + e[1], s1 = e[2] + e[3];
#pragma unroll
          for (int o = 1; o < 4; o <<= 1) { s0 += __shfl_xor_sync(0xffffffffu, s0, o); s1 += __shfl_xor_sync(0xffffffffu, s1, o); }
          const float f0 = gl * rcp(s0), f1 = gh * rcp(s1);
#pragma unroll
          for (int j = b; j < b + 3; j++) {
            float o[4];
            mma16816z(o, p, vx[j], vl[j]);
            mma1688(o, 0u, p1 & own, vh[j]);
            const uint32_t lo = pack_bf16(o[0] * f0, o[1] * f0), hi = pack_bf16(o[2] * f1, o[3] * f1);
            if (j > b || i == 0) { ol[j] = lo; oh[j] = hi; }
            else { ol[j] = t >= i ? lo : ol[j]; oh[j] = t >= i ? hi : oh[j]; }
          }
        }
        const uint32_t sa = eb + 16 + (w * 16 + (lane & 15)) * 144 + (lane >> 4) * 16;
#pragma unroll
        for (int j = 0; j < 8; j += 2) stsm4(sa + j * 16, ol[j], oh[j], ol[j + 1], oh[j + 1]);
        asm volatile("stmatrix.sync.aligned.m8n8.x2.shared.b16 [%0], {%1,%2};" :: "r"(sa + 128), "r"(ol[8]), "r"(oh[8]) : "memory");
        ho = amax4(amax4(amax4(amax4(ho, ol), ol + 4), oh), oh + 4);
        ho = __hmax2_nan(__hmax2_nan(ho, __habs2(*(const __half2*)&ol[8])), __habs2(*(const __half2*)&oh[8]));
        if (c == 3 && tile == 17) {
          const uint32_t eo = wexp(ho);
          if (lane == 0) atomicMax(&g_amax[16], (unsigned long long)(lds32(sb + A_BAR + 376) + 1) << 32 | eo);
        }
        fence_async();
        bar_arrive(13 + wg, 160);
        ASTAMP(20 + (c & 3));
      }
    }
    ASTAMP(3);
    uint32_t wa[36][4];
    mbar_wait(fullw, 0);
    const uint32_t la = sb + wg * 73728 + ((lane & 7) + ((lane >> 4) << 3)) * 128 + (((2 * w + ((lane >> 3) & 1)) ^ (lane & 7)) << 4);
#pragma unroll
    for (int k = 0; k < 36; k++) ldsm4t(wa[k], la + k * 2048);
    sts64(sb + A_XW + wg * 2048 + 1024 + (tid & 127) * 8, 0, 0);
    fence_async();
    bar_arrive(6, cta >= NH ? 320 : 288);
    bar_sync(1 + wg, 128);
    ASTAMP(4);
    const int nsl = p3_n(wg), ke = p3_k(wg), t = lane & 3;
    const unsigned epoch = lds32(sb + A_BAR + 376);
    uint2* const part = g_part + nsl * 4096 + w * 16 + (lane >> 2) * 2 + (t & 1);
    auto tag = [&](int seg) { return PR == 8 ? ((seg >> 3) + 1 + (epoch & (seg >> 1) & (seg >> 2))) & 1 : ((seg >> 2) + 1 + (epoch & (seg >> 1))) & 1; };
    uint2 v[4];
    auto fetch = [&](int seg) {
#pragma unroll
      for (int j = 0; j < 4; j++)
        asm volatile("ld.relaxed.gpu.global.v2.b32 {%0,%1}, [%2];" : "=r"(v[j].x), "=r"(v[j].y) : "l"(part + (seg & (PR - 1)) * 36864 + ke * 512 + ((t >> 1) * 4 + j) * 64) : "memory");
    };
    auto finish = [&](int seg) {
      int n = 0;
#pragma unroll 1
      while (!(AX & 16) && __any_sync(0xffffffffu, (((v[0].x ^ tag(seg)) | (v[1].x ^ tag(seg)) | (v[2].x ^ tag(seg)) | (v[3].x ^ tag(seg))) & 1) != 0) && ++n < SPIN_LIMIT) {
        if (seg < NAUXSEG - ((TL & 2) ? 2 : 1)) __nanosleep(100);
        fetch(seg);
      }
      const float a0 = (bf_lo(v[0].x) + bf_lo(v[1].x)) + (bf_lo(v[2].x) + bf_lo(v[3].x)), a1 = (bf_hi(v[0].x) + bf_hi(v[1].x)) + (bf_hi(v[2].x) + bf_hi(v[3].x));
      const float b0 = (bf_lo(v[0].y) + bf_lo(v[1].y)) + (bf_lo(v[2].y) + bf_lo(v[3].y)), b1 = (bf_hi(v[0].y) + bf_hi(v[1].y)) + (bf_hi(v[2].y) + bf_hi(v[3].y));
      const float c0 = (t < 2 ? a0 : b0) + __shfl_xor_sync(0xffffffffu, t < 2 ? b0 : a0, 2), c1 = (t < 2 ? a1 : b1) + __shfl_xor_sync(0xffffffffu, t < 2 ? b1 : a1, 2);
      ((uint32_t*)(out + (size_t)(seg * 32 + ke * 4 + ((lane >> 2) & 3)) * DM + nsl * 64 + w * 16 + (lane >> 4) * 8))[t] = movm(pack_bf16(c0, c1));
    };
    float acc[16];
    if (AX & 64) for (int i = 0; i < 16; i++) acc[i] = 0.f;
    int done = 0, sl = cta < NH ? 0 : wg, ph = 0;
    const uint32_t d0 = (sb & 0x3FFFF) >> 4;
#pragma unroll 1
    for (int seg = 0; seg < NAUXSEG; seg++) {
      if (DRAIN) {
#pragma unroll 1
        while (done < seg && !mbar_test(full3 + 8 * sl, ph)) { fetch(done); finish(done); done++; }
      }
      mbar_wait(full3 + 8 * sl, ph);
      if (SER && !(AX & 64) && (wg == 1 || seg > 0)) bar_sync(10 - wg, 256);
      if (tid == 128) SSTAMP(6, seg);
      if (!(AX & 16)) fetch(done);
      if (!(AX & 64)) {
        const uint64_t db = desc_at(d0 + sl * (XT >> 4), 16, 1024, 1);
        WG_FENCE();
        wgmma_n32_ss_tn(acc, desc_at(d0 + ((A_XW + wg * 2048) >> 4), 8192, 1024, 1), desc_at(d0 + (A_XT >> 4) + sl * 32, 0, 128, 0), 0);
#pragma unroll
        for (int k = 0; k < 36; k++) {
          wgmma_n32_rs(acc, wa[k][0], wa[k][1], wa[k][2], wa[k][3], db + (k >> 2) * 256 + (k & 3) * 2, 1);
          if (SER && k == SER && (wg == 0 || seg < NAUXSEG - 1)) bar_arrive(9 + wg, 256);
        }
        WG_COMMIT();
      }
      if (done <= seg - PL) finish(done++);
      WG_WAIT(0);
      if (lane == 0) mbar_arrive(empty3 + 8 * sl);
      p3_next(sl, ph);
#pragma unroll
      for (int j = 0; j < 4; j++)
        if (!(AX & 16) || acc[4 * j] == 1.2345678f)
          asm volatile("st.relaxed.gpu.global.v2.b32 [%0], {%1,%2};" :: "l"(part + (seg & (PR - 1)) * 36864 + (2 * j + (t >> 1)) * 512 + ke * 64),
                       "r"((pack_bf16(acc[4 * j], acc[4 * j + 1]) & ~1u) | tag(seg)), "r"(pack_bf16(acc[4 * j + 2], acc[4 * j + 3])) : "memory");
      if (tid == 128) SSTAMP(7, seg);
      if (tid == 128) SSTAMP(8, seg);
      if ((seg & 7) == 6) ASTAMP(5 + (seg >> 3));
    }
#pragma unroll 1
    for (; done < NAUXSEG; done++) { fetch(done); finish(done); }
    ASTAMP(13);
    TSTAMP(48);
    MSTAMP(9);
  }
}

typedef CUresult (*EncodeFn)(CUtensorMap*, CUtensorMapDataType, cuuint32_t, void*, const cuuint64_t*, const cuuint64_t*,
                             const cuuint32_t*, const cuuint32_t*, CUtensorMapInterleave, CUtensorMapSwizzle,
                             CUtensorMapL2promotion, CUtensorMapFloatOOBfill);
static void make_map(EncodeFn enc, CUtensorMap* m, const void* p, int rows, int cols, int box_rows) {
  cuuint64_t dims[2] = {(cuuint64_t)cols, (cuuint64_t)rows};
  cuuint64_t strides[1] = {(cuuint64_t)cols * 2};
  cuuint32_t box[2] = {64, (cuuint32_t)box_rows};
  cuuint32_t es[2] = {1, 1};
  enc(m, CU_TENSOR_MAP_DATA_TYPE_BFLOAT16, 2, (void*)p, dims, strides, box, es, CU_TENSOR_MAP_INTERLEAVE_NONE,
      CU_TENSOR_MAP_SWIZZLE_128B, CU_TENSOR_MAP_L2_PROMOTION_L2_128B, CU_TENSOR_MAP_FLOAT_OOB_FILL_NONE);
}

constexpr int g_poll = POLL_NS;
extern "C" void kernel_launch(void* const* d_in, const int* in_sizes, int n_in, void* d_out, int out_size) {
  const bf16* x = (const bf16*)d_in[0];
  const bf16* wqkvA = (const bf16*)d_in[1];
  const bf16* woA = (const bf16*)d_in[2];
  const bf16* mem0 = (const bf16*)d_in[4];
  const bf16* Wq = (const bf16*)d_in[5];
  const bf16* Wk = (const bf16*)d_in[6];
  const bf16* Wv = (const bf16*)d_in[7];
  const bf16* Wo = (const bf16*)d_in[8];
  const bf16* gate_w = (const bf16*)d_in[10];
  static EncodeFn enc = nullptr;
  static void *pO = nullptr, *pR = nullptr;
  if (!enc) {
    cudaDriverEntryPointQueryResult qr;
    cudaGetDriverEntryPoint("cuTensorMapEncodeTiled", (void**)&enc, cudaEnableDefault, &qr);
    cudaGetSymbolAddress(&pO, g_Ocat);
    cudaGetSymbolAddress(&pR, g_red_raw);
    cudaFuncSetAttribute(rec_kernel, cudaFuncAttributeMaxDynamicSharedMemorySize, SM_TOTAL);
    cudaFuncSetAttribute(aux_kernel, cudaFuncAttributeMaxDynamicSharedMemorySize, A_TOTAL);
  }
  RMaps rm;
  rm.poll = g_poll; rm.out = (bf16*)d_out;
  make_map(enc, &rm.woa, woA, DM, DM, 24);
  {
    cuuint64_t dims[2] = {KCAT, S_LEN}, strides[1] = {KCAT * 2};
    cuuint32_t box[2] = {32, 64}, es[2] = {1, 1};
    enc(&rm.oa, CU_TENSOR_MAP_DATA_TYPE_BFLOAT16, 2, pO, dims, strides, box, es, CU_TENSOR_MAP_INTERLEAVE_NONE,
        CU_TENSOR_MAP_SWIZZLE_NONE, CU_TENSOR_MAP_L2_PROMOTION_NONE, CU_TENSOR_MAP_FLOAT_OOB_FILL_NONE);
  }
  rm.red = (unsigned char*)(((uintptr_t)pR + 262143) & ~(uintptr_t)262143);
  {
    cuuint64_t dims[3] = {64, S_LEN, 9}, strides[2] = {DM * 2, 128};
    cuuint32_t box[3] = {64, 32, 9}, es[3] = {1, 1, 1};
    enc(&rm.x, CU_TENSOR_MAP_DATA_TYPE_BFLOAT16, 3, (void*)x, dims, strides, box, es, CU_TENSOR_MAP_INTERLEAVE_NONE,
        CU_TENSOR_MAP_SWIZZLE_128B, CU_TENSOR_MAP_L2_PROMOTION_L2_128B, CU_TENSOR_MAP_FLOAT_OOB_FILL_NONE);
  }
  make_map(enc, &rm.wq, Wq, DM, 4096, 192);
  make_map(enc, &rm.wk, Wk, DM, 4096, 192);
  make_map(enc, &rm.wv, Wv, DM, 4096, 192);
  make_map(enc, &rm.wo, Wo, 4096, DM, 128);
  AMaps am;
  {
    cuuint32_t es[4] = {1, 1, 1, 1};
    cuuint64_t dx[4] = {64, 2, S_LEN / 2, 9}, sx[3] = {DM * 2, DM * 4, 128};
    cuuint32_t bx[4] = {64, 1, 64, 3};
    enc(&am.x, CU_TENSOR_MAP_DATA_TYPE_BFLOAT16, 4, (void*)x, dx, sx, bx, es, CU_TENSOR_MAP_INTERLEAVE_NONE,
        CU_TENSOR_MAP_SWIZZLE_128B, CU_TENSOR_MAP_L2_PROMOTION_L2_128B, CU_TENSOR_MAP_FLOAT_OOB_FILL_NONE);
    cuuint64_t dw[3] = {DM, DM, 3}, sw[2] = {DM * 6, DM * 2};
    cuuint32_t bw[3] = {64, 16, 3}, bt[3] = {8, 16, 3};
    enc(&am.wa, CU_TENSOR_MAP_DATA_TYPE_BFLOAT16, 3, (void*)wqkvA, dw, sw, bw, es, CU_TENSOR_MAP_INTERLEAVE_NONE,
        CU_TENSOR_MAP_SWIZZLE_128B, CU_TENSOR_MAP_L2_PROMOTION_L2_128B, CU_TENSOR_MAP_FLOAT_OOB_FILL_NONE);
    enc(&am.wt, CU_TENSOR_MAP_DATA_TYPE_BFLOAT16, 3, (void*)wqkvA, dw, sw, bt, es, CU_TENSOR_MAP_INTERLEAVE_NONE,
        CU_TENSOR_MAP_SWIZZLE_NONE, CU_TENSOR_MAP_L2_PROMOTION_NONE, CU_TENSOR_MAP_FLOAT_OOB_FILL_NONE);
    cuuint64_t dz[3] = {KCAT, 2, S_LEN / 2}, sz[2] = {KCAT * 2, KCAT * 4};
    cuuint32_t bz[3] = {72, 1, 57};
    enc(&am.oa, CU_TENSOR_MAP_DATA_TYPE_BFLOAT16, 3, pO, dz, sz, bz, es, CU_TENSOR_MAP_INTERLEAVE_NONE,
        CU_TENSOR_MAP_SWIZZLE_NONE, CU_TENSOR_MAP_L2_PROMOTION_NONE, CU_TENSOR_MAP_FLOAT_OOB_FILL_NONE);
  }
  {
    cuuint64_t dims[3] = {64, S_LEN, KCAT / 64}, strides[2] = {KCAT * 2, 128};
    cuuint32_t box[3] = {64, 32, 9}, es[3] = {1, 1, 1};
    make_map(enc, &am.o, pO, S_LEN, KCAT, 32);
    enc(&am.o3, CU_TENSOR_MAP_DATA_TYPE_BFLOAT16, 3, pO, dims, strides, box, es, CU_TENSOR_MAP_INTERLEAVE_NONE,
        CU_TENSOR_MAP_SWIZZLE_128B, CU_TENSOR_MAP_L2_PROMOTION_L2_128B, CU_TENSOR_MAP_FLOAT_OOB_FILL_NONE);
  }
  make_map(enc, &am.wob, Wo, 4096, DM, 64);
  make_map(enc, &am.woa, woA, DM, DM, 64);
  make_map(enc, &am.wo8, woA, DM, DM, 8);
  {
    cuuint64_t dims[2] = {KCAT, S_LEN}, strides[1] = {KCAT * 2};
    cuuint32_t box[2] = {8, 32}, es[2] = {1, 1};
    enc(&am.o8, CU_TENSOR_MAP_DATA_TYPE_BFLOAT16, 2, pO, dims, strides, box, es, CU_TENSOR_MAP_INTERLEAVE_NONE,
        CU_TENSOR_MAP_SWIZZLE_NONE, CU_TENSOR_MAP_L2_PROMOTION_NONE, CU_TENSOR_MAP_FLOAT_OOB_FILL_NONE);
  }

  rec_kernel<<<96, 384, SM_TOTAL, cudaStreamPerThread>>>(rm, x, mem0);
  cudaLaunchConfig_t cfg = {};
  cfg.gridDim = dim3(NAUX); cfg.blockDim = dim3(512); cfg.dynamicSmemBytes = A_TOTAL; cfg.stream = cudaStreamPerThread;
  cudaLaunchAttribute at[1];
  at[0].id = cudaLaunchAttributeProgrammaticStreamSerialization; at[0].val.programmaticStreamSerializationAllowed = 1;
  cfg.attrs = at; cfg.numAttrs = 1;
  if (XP & 16) cfg.numAttrs = 0;
  if (!(XP & 64)) cudaLaunchKernelEx(&cfg, aux_kernel, am, wqkvA, woA, gate_w, (bf16*)d_out);
}
```

```cpp
#include <cuda_runtime.h>
#include <cuda_bf16.h>
#include <cuda_fp16.h>
#include <cuda.h>
#include <stdint.h>

typedef __nv_bfloat16 bf16;

constexpr int S_LEN = 2048, DM = 576, NH = 32, DH = 128, NSEG = 64, KCAT = 4096 + 576;
constexpr int NAUXSEG = NSEG - 2;
constexpr int NAUX = 36;
#define RED_LINE(i) (((i) >> 2) * 4096 + ((i) & 1) * 256 + ((i) & 2) * 512)
#define RED_SLOT(s) (((s) & 1) * 128 + ((s) & 2) * 256)

#define POLL_NS 848
#define NII 14
#define W3PRE 4
#define W3MID 4
#define GF 0
#define B5POS 0
#define NUP 4
#define UPF 1
#define B3Q 9
#define B3F 0
#define GATE 7
#define NTL 2
#define B7R 1
#define VS0 1
#define VS1 0
#define VLATE(w) ((w) == 0 ? VS0 == 1 : (w) == 1 ? VS1 == 1 : false)
#define HOIST 0
#define RSLOW 0
#define CSY 0
#define DD 2
#define N12 18
#define N14 18
#define HP 2
#define HL 0
#define WL 1
#define RV 7
#define EXM 1
#define PSTAMP 0
#define PFIX 1
#define VE 1
#define PV2 2
#define RET 1
#define TL 6
#define CLR 1
#define RFW 0
#define NIC 0
#define LEAD 0
#define FIN16 1
#define VXG 0
#define NRING 20
#define EXD 0
#define HDLY 0
#define F10 1
#define NPROBE 2
#define QM 0
#define N5 224
#define KP(i) (((i) >> 1) + 4 * ((i) & 1))
#define SPIN_LIMIT (1 << 14)
#define XP 0

__device__ __align__(1024) bf16 g_Ocat[S_LEN * KCAT];
__device__ __align__(1024) unsigned char g_red_raw[2 * 262144];
constexpr int HINT_OFF = 2048;
__device__ __align__(16) float g_gate[S_LEN];
__device__ __align__(128) uint4 g_stats[96 * 2];
__device__ unsigned g_epoch;
__device__ unsigned g_epoch2;
__device__ unsigned g_ocnt[NSEG * 64];
__device__ unsigned g_abar[3 * 32];
__device__ unsigned long long g_amax[2 * 16];
__device__ unsigned g_scnt[NSEG * 32 * 8];
__device__ __align__(1024) unsigned char g_seg[NRING * 96 * 10240];
__device__ unsigned g_used[NH * 32];
__device__ __align__(1024) uint2 g_part[8 * 9 * 64 * 64];
__device__ int g_err;
#define MSTAMP(i)
#define TSTAMP(i)
#define PROF(idx)
#define PROFP(idx)
#define RSTAMP(k)
#define STAMP(idx)
#define ASTAMP(idx)
#define SSTAMP(k, seg)
#define WSTAMP(idx)

#define DI __device__ __forceinline__
DI uint32_t smem_u32(const void* p) { return (uint32_t)__cvta_generic_to_shared(p); }
DI uint32_t clock32() { uint32_t c; asm volatile("mov.u32 %0, %%clock;" : "=r"(c) :: "memory"); return c; }
DI uint32_t gtime() { uint32_t c; asm volatile("mov.u32 %0, %%globaltimer_lo;" : "=r"(c) :: "memory"); return c; }
DI uint32_t ldg_relaxed32(const void* p) { uint32_t v; asm volatile("ld.relaxed.gpu.global.b32 %0, [%1];" : "=r"(v) : "l"(p) : "memory"); return v; }
DI uint32_t ldg_acquire32(const void* p) { uint32_t v; asm volatile("ld.acquire.gpu.global.b32 %0, [%1];" : "=r"(v) : "l"(p) : "memory"); return v; }
DI void stg_relaxed32(void* p, uint32_t v) { asm volatile("st.relaxed.gpu.global.b32 [%0], %1;" :: "l"(p), "r"(v) : "memory"); }
DI int head_id() { int c; asm volatile("mov.u32 %0, %%clusterid.x;" : "=r"(c)); return c; }
DI uint32_t mapa(uint32_t a, uint32_t r) { uint32_t o; asm("mapa.shared::cluster.u32 %0, %1, %2;" : "=r"(o) : "r"(a), "r"(r)); return o; }
DI void cluster_arrive() { asm volatile("barrier.cluster.arrive.relaxed.aligned;" ::: "memory"); }
DI void cluster_wait() { asm volatile("barrier.cluster.wait.aligned;" ::: "memory"); }
DI void cluster_sync() { asm volatile("barrier.cluster.arrive.release.aligned;\nbarrier.cluster.wait.acquire.aligned;" ::: "memory"); }
DI void mbar_init(uint32_t b, uint32_t c) { asm volatile("mbarrier.init.shared::cta.b64 [%0], %1;" :: "r"(b), "r"(c) : "memory"); }
DI void mbar_expect(uint32_t b, uint32_t tx) { asm volatile("mbarrier.arrive.expect_tx.shared::cta.b64 _, [%0], %1;" :: "r"(b), "r"(tx) : "memory"); }
DI void mbar_arrive(uint32_t b) { asm volatile("mbarrier.arrive.shared::cta.b64 _, [%0];" :: "r"(b) : "memory"); }
DI void mbar_wait(uint32_t b, uint32_t par) {
  asm volatile("{\n.reg .pred p;\n.reg .u32 n, q;\nmov.u32 n, 0;\n"
               "WL: add.u32 n, n, 1;\nshr.u32 q, n, 12;\nxor.b32 q, q, %1;\n"
               "mbarrier.try_wait.parity.shared::cta.b64 p, [%0], q;\n@!p bra.uni WL;\n}"
               :: "r"(b), "r"(par) : "memory");
}
DI bool mbar_test(uint32_t b, uint32_t par) {
  uint32_t r;
  asm volatile("{\n.reg .pred p;\nmbarrier.test_wait.parity.shared::cta.b64 p, [%1], %2;\nselp.u32 %0, 1, 0, p;\n}" : "=r"(r) : "r"(b), "r"(par) : "memory");
  return r;
}
DI void mbar_wait_fast(uint32_t b, uint32_t par) {
  asm volatile("{\n.reg .pred p;\n.reg .u32 n, q;\nmbarrier.try_wait.parity.shared::cta.b64 p, [%0], %1;\n@p bra.uni WD;\nmov.u32 n, 0;\n"
               "WL: add.u32 n, n, 1;\nshr.u32 q, n, 12;\nxor.b32 q, q, %1;\n"
               "mbarrier.try_wait.parity.shared::cta.b64 p, [%0], q;\n@!p bra.uni WL;\nWD:\n}"
               :: "r"(b), "r"(par) : "memory");
}
DI void wait_until(uint32_t t) {
  const uint32_t now = gtime();
  t = min(t, now + 8192);
  asm volatile("{\n.reg .pred p;\n.reg .u32 c;\nTL: mov.u32 c, %%globaltimer_lo;\nsetp.lt.u32 p, c, %0;\n@p bra.uni TL;\n}" :: "r"(t) : "memory");
}
#define PIN(v) v = __shfl_xor_sync(0xffffffffu, v, 0)
#define SCHED_FENCE(k) asm volatile("{\n.reg .pred p;\nsetp.eq.u32 p, %0, %1;\n@p exit;\n}" :: "r"(fence_reg), "r"(k) : "memory")
#define MEM_ORDER(k) asm volatile("{\n.reg .pred p;\nsetp.eq.u32 p, %0, %1;\n@p st.shared.u32 [%0], %0;\n}" :: "r"(fence_reg), "r"(k + 64) : "memory")
DI void bar_sync(int id, int n) { asm volatile("bar.sync %0, %1;" :: "r"(id), "r"(n) : "memory"); }
DI void bar_arrive(int id, int n) { asm volatile("bar.arrive %0, %1;" :: "r"(id), "r"(n) : "memory"); }
DI void fence_async() { asm volatile("fence.proxy.async.shared::cta;" ::: "memory"); }
DI void st_async4(uint32_t a, uint32_t x, uint32_t y, uint32_t z, uint32_t w, uint32_t mb) {
  asm volatile("st.async.weak.shared::cluster.mbarrier::complete_tx::bytes.v4.b32 [%0], {%1,%2,%3,%4}, [%5];"
               :: "r"(a), "r"(x), "r"(y), "r"(z), "r"(w), "r"(mb) : "memory");
}
DI void st_async2(uint32_t a, uint32_t x, uint32_t y, uint32_t mb) {
  asm volatile("st.async.weak.shared::cluster.mbarrier::complete_tx::bytes.v2.b32 [%0], {%1,%2}, [%3];"
               :: "r"(a), "r"(x), "r"(y), "r"(mb) : "memory");
}
DI void sts32(uint32_t a, uint32_t x) { asm volatile("st.shared.b32 [%0], %1;" :: "r"(a), "r"(x) : "memory"); }
DI void sts64(uint32_t a, uint32_t x, uint32_t y) { asm volatile("st.shared.v2.b32 [%0], {%1,%2};" :: "r"(a), "r"(x), "r"(y) : "memory"); }
DI void sts128(uint32_t a, uint32_t x, uint32_t y, uint32_t z, uint32_t w) {
  asm volatile("st.shared.v4.b32 [%0], {%1,%2,%3,%4};" :: "r"(a), "r"(x), "r"(y), "r"(z), "r"(w) : "memory");
}
DI uint32_t lds32(uint32_t a) { uint32_t x; asm volatile("ld.shared.b32 %0, [%1];" : "=r"(x) : "r"(a) : "memory"); return x; }
DI void lds64(uint32_t a, uint32_t& x, uint32_t& y) { asm volatile("ld.shared.v2.b32 {%0,%1}, [%2];" : "=r"(x), "=r"(y) : "r"(a) : "memory"); }
DI void lds128(uint32_t a, uint32_t* r) {
  asm volatile("ld.shared.v4.b32 {%0,%1,%2,%3}, [%4];" : "=r"(r[0]), "=r"(r[1]), "=r"(r[2]), "=r"(r[3]) : "r"(a) : "memory");
}
DI void lds128f(uint32_t a, float* r) {
  asm volatile("ld.shared.v4.f32 {%0,%1,%2,%3}, [%4];" : "=f"(r[0]), "=f"(r[1]), "=f"(r[2]), "=f"(r[3]) : "r"(a) : "memory");
}
DI void lds64f(uint32_t a, float* r) { asm volatile("ld.shared.v2.f32 {%0,%1}, [%2];" : "=f"(r[0]), "=f"(r[1]) : "r"(a) : "memory"); }
DI void ldsm4t(uint32_t* r, uint32_t a) {
  asm volatile("ldmatrix.sync.aligned.m8n8.x4.trans.shared.b16 {%0,%1,%2,%3}, [%4];"
               : "=r"(r[0]), "=r"(r[1]), "=r"(r[2]), "=r"(r[3]) : "r"(a) : "memory");
}
DI void ldsm4t_in(uint32_t* r, uint32_t a, uint32_t t) {
  asm volatile("{\n.reg .pred p;\nsetp.ne.u32 p, %5, 0;\n@p ldmatrix.sync.aligned.m8n8.x4.trans.shared.b16 {%0,%1,%2,%3}, [%4];\n}"
               : "+r"(r[0]), "+r"(r[1]), "+r"(r[2]), "+r"(r[3]) : "r"(a), "r"(t) : "memory");
}
DI void lds128_in(uint32_t* r, uint32_t a, uint32_t t) {
  asm volatile("{\n.reg .pred p;\nsetp.ne.u32 p, %5, 0;\n@p ld.shared.v4.b32 {%0,%1,%2,%3}, [%4];\n}"
               : "+r"(r[0]), "+r"(r[1]), "+r"(r[2]), "+r"(r[3]) : "r"(a), "r"(t) : "memory");
}
DI void ldsm2t_in(uint32_t* r, uint32_t a, uint32_t t) {
  asm volatile("{\n.reg .pred p;\nsetp.ne.u32 p, %3, 0;\n@p ldmatrix.sync.aligned.m8n8.x2.trans.shared.b16 {%0,%1}, [%2];\n}" : "+r"(r[0]), "+r"(r[1]) : "r"(a), "r"(t) : "memory");
}
DI void reserve2(uint32_t* r) { asm volatile("{\n.reg .u64 t;\nmov.u64 t, %%clock64;\nmov.b64 {%0, %1}, t;\n}" : "=r"(r[0]), "=r"(r[1])); }
DI void scale_sum(float& x, float& y, float s, uint32_t t) {
  asm volatile("{\n.reg .pred p;\nsetp.ne.u32 p, %2, 0;\n@p mul.f32 %0, %0, %1;\n}" : "+f"(y) : "f"(s), "r"(t));
  asm volatile("{\n.reg .pred p;\nsetp.ne.u32 p, %3, 1;\n@p fma.rn.f32 %0, %0, %1, %2;\n}" : "+f"(x) : "f"(s), "f"(y), "r"(t));
}
DI void ldsm4(uint32_t* r, uint32_t a) {
  asm volatile("ldmatrix.sync.aligned.m8n8.x4.shared.b16 {%0,%1,%2,%3}, [%4];"
               : "=r"(r[0]), "=r"(r[1]), "=r"(r[2]), "=r"(r[3]) : "r"(a) : "memory");
}
DI void st_async1(uint32_t a, uint32_t x, uint32_t mb) {
  asm volatile("st.async.weak.shared::cluster.mbarrier::complete_tx::bytes.b32 [%0], %1, [%2];" :: "r"(a), "r"(x), "r"(mb) : "memory");
}
DI void stsm4(uint32_t a, uint32_t x, uint32_t y, uint32_t z, uint32_t w) {
  asm volatile("stmatrix.sync.aligned.m8n8.x4.shared.b16 [%0], {%1,%2,%3,%4};" :: "r"(a), "r"(x), "r"(y), "r"(z), "r"(w) : "memory");
}
DI void stsm4t(uint32_t a, uint32_t x, uint32_t y, uint32_t z, uint32_t w) {
  asm volatile("stmatrix.sync.aligned.m8n8.x4.trans.shared.b16 [%0], {%1,%2,%3,%4};" :: "r"(a), "r"(x), "r"(y), "r"(z), "r"(w) : "memory");
}
DI uint32_t pack_bf16(float lo, float hi) { uint32_t r; asm("cvt.rn.bf16x2.f32 %0, %1, %2;" : "=r"(r) : "f"(hi), "f"(lo)); return r; }
DI uint32_t pack_f16(float lo, float hi) { uint32_t r; asm("cvt.rn.f16x2.f32 %0, %1, %2;" : "=r"(r) : "f"(hi), "f"(lo)); return r; }
DI float ex2(float x) { float y; asm("ex2.approx.ftz.f32 %0, %1;" : "=f"(y) : "f"(x)); return y; }
DI float rcp(float x) { float y; asm("rcp.approx.ftz.f32 %0, %1;" : "=f"(y) : "f"(x)); return y; }
DI float bf_lo(uint32_t x) { return __uint_as_float(x << 16); }
DI float bf_hi(uint32_t x) { return __uint_as_float(x & 0xffff0000u); }
DI void mma16816(float* d, const uint32_t* a, uint32_t b0, uint32_t b1) {
  asm volatile("mma.sync.aligned.m16n8k16.row.col.f32.bf16.bf16.f32 {%0,%1,%2,%3}, {%4,%5,%6,%7}, {%8,%9}, {%0,%1,%2,%3};"
               : "+f"(d[0]), "+f"(d[1]), "+f"(d[2]), "+f"(d[3]) : "r"(a[0]), "r"(a[1]), "r"(a[2]), "r"(a[3]), "r"(b0), "r"(b1));
}
DI void mma16816z(float* d, const uint32_t* a, uint32_t b0, uint32_t b1) {
  asm volatile("mma.sync.aligned.m16n8k16.row.col.f32.bf16.bf16.f32 {%0,%1,%2,%3}, {%4,%5,%6,%7}, {%8,%9}, {%10,%10,%10,%10};"
               : "=f"(d[0]), "=f"(d[1]), "=f"(d[2]), "=f"(d[3]) : "r"(a[0]), "r"(a[1]), "r"(a[2]), "r"(a[3]), "r"(b0), "r"(b1), "f"(0.f));
}
DI void mma1688z(float* d, uint32_t a0, uint32_t a1, uint32_t b0) {
  asm volatile("mma.sync.aligned.m16n8k8.row.col.f32.bf16.bf16.f32 {%0,%1,%2,%3}, {%4,%5}, {%6}, {%7,%7,%7,%7};"
               : "=f"(d[0]), "=f"(d[1]), "=f"(d[2]), "=f"(d[3]) : "r"(a0), "r"(a1), "r"(b0), "f"(0.f));
}
DI void mma1688(float* d, uint32_t a0, uint32_t a1, uint32_t b0) {
  asm volatile("mma.sync.aligned.m16n8k8.row.col.f32.bf16.bf16.f32 {%0,%1,%2,%3}, {%4,%5}, {%6}, {%0,%1,%2,%3};"
               : "+f"(d[0]), "+f"(d[1]), "+f"(d[2]), "+f"(d[3]) : "r"(a0), "r"(a1), "r"(b0));
}
DI void ldsm2t(uint32_t* r, uint32_t a) {
  asm volatile("ldmatrix.sync.aligned.m8n8.x2.trans.shared.b16 {%0,%1}, [%2];" : "=r"(r[0]), "=r"(r[1]) : "r"(a) : "memory");
}
DI uint32_t add_bf16(uint32_t a, uint32_t b) { uint32_t r; asm("add.rn.bf16x2 %0, %1, %2;" : "=r"(r) : "r"(a), "r"(b)); return r; }
DI uint32_t mul_bf16(uint32_t a, uint32_t b) { uint32_t r; asm("mul.rn.bf16x2 %0, %1, %2;" : "=r"(r) : "r"(a), "r"(b)); return r; }
DI uint64_t make_desc(uint32_t addr, uint32_t lbo, uint32_t sbo, uint32_t swz) {
  return (uint64_t)((addr & 0x3FFFF) >> 4) | ((uint64_t)(lbo >> 4) << 16) | ((uint64_t)(sbo >> 4) << 32) | ((uint64_t)swz << 62);
}
DI uint64_t desc_at(uint32_t a16, uint32_t lbo, uint32_t sbo, uint32_t swz) {
  uint64_t d; asm("mov.b64 %0, {%1, %2};" : "=l"(d) : "r"(a16 + ((lbo >> 4) << 16)), "r"((sbo >> 4) | (swz << 30)));
  return d;
}
#define WG_FENCE() asm volatile("wgmma.fence.sync.aligned;" ::: "memory")
#define WG_COMMIT() asm volatile("wgmma.commit_group.sync.aligned;" ::: "memory")
#define WG_WAIT(n) asm volatile("wgmma.wait_group.sync.aligned %0;" :: "n"(n) : "memory")
#define ACC8(d, o) "+f"(d[o]), "+f"(d[o + 1]), "+f"(d[o + 2]), "+f"(d[o + 3]), "+f"(d[o + 4]), "+f"(d[o + 5]), "+f"(d[o + 6]), "+f"(d[o + 7])
DI void wgmma_n32_rs(float* d, uint32_t a0, uint32_t a1, uint32_t a2, uint32_t a3, uint64_t db, int acc) {
  asm volatile("{\n.reg .pred p;\nsetp.ne.b32 p, %21, 0;\n"
               "wgmma.mma_async.sync.aligned.m64n32k16.f32.bf16.bf16 {%0,%1,%2,%3,%4,%5,%6,%7,%8,%9,%10,%11,%12,%13,%14,%15}, "
               "{%16,%17,%18,%19}, %20, p, 1, 1, 0;\n}\n"
               : ACC8(d, 0), ACC8(d, 8) : "r"(a0), "r"(a1), "r"(a2), "r"(a3), "l"(db), "r"(acc));
}
template <int TA>
DI void wgmma_n32_ss(float* d, uint64_t da, uint64_t db, int acc) {
  asm volatile("{\n.reg .pred p;\nsetp.ne.b32 p, %18, 0;\n"
               "wgmma.mma_async.sync.aligned.m64n32k16.f32.bf16.bf16 {%0,%1,%2,%3,%4,%5,%6,%7,%8,%9,%10,%11,%12,%13,%14,%15}, "
               "%16, %17, p, 1, 1, %19, 1;\n}\n"
               : ACC8(d, 0), ACC8(d, 8) : "l"(da), "l"(db), "r"(acc), "n"(TA));
}
DI void tma_load(uint32_t dst, const CUtensorMap* m, int c0, int c1, uint32_t mb) {
  asm volatile("cp.async.bulk.tensor.2d.shared::cluster.global.mbarrier::complete_tx::bytes [%0], [%1, {%3, %4}], [%2];"
               :: "r"(dst), "l"(m), "r"(mb), "r"(c0), "r"(c1) : "memory");
}
DI void tma_load3(uint32_t dst, const CUtensorMap* m, int row, uint32_t mb) {
  asm volatile("cp.async.bulk.tensor.3d.shared::cluster.global.mbarrier::complete_tx::bytes [%0], [%1, {%3, %4, %3}], [%2];"
               :: "r"(dst), "l"(m), "r"(mb), "r"(0), "r"(row) : "memory");
}
DI bool elect_one() {
  uint32_t p;
  asm volatile("{\n.reg .pred p;\nelect.sync _|p, 0xffffffff;\nselp.u32 %0, 1, 0, p;\n}" : "=r"(p));
  return p;
}
DI void bulk_s2s(uint32_t dst, uint32_t src, uint32_t bytes, uint32_t mb) {
  asm volatile("cp.async.bulk.shared::cluster.shared::cta.mbarrier::complete_tx::bytes [%0], [%1], %2, [%3];"
               :: "r"(dst), "r"(src), "r"(bytes), "r"(mb) : "memory");
}
DI void tma_prefetch(const CUtensorMap* m, int c0, int c1) {
  asm volatile("cp.async.bulk.prefetch.tensor.2d.L2.global.tile [%0, {%1, %2}];" :: "l"(m), "r"(c0), "r"(c1) : "memory");
}
DI void tma_store(const CUtensorMap* m, uint32_t src, int c0, int c1) {
  asm volatile("cp.async.bulk.tensor.2d.global.shared::cta.bulk_group [%0, {%2, %3}], [%1];" :: "l"(m), "r"(src), "r"(c0), "r"(c1) : "memory");
}
DI uint4 ldg_relaxed(const void* p) {
  uint4 v;
  asm volatile("ld.relaxed.gpu.global.v4.b32 {%0,%1,%2,%3}, [%4];" : "=r"(v.x), "=r"(v.y), "=r"(v.z), "=r"(v.w) : "l"(p) : "memory");
  return v;
}
DI void stg_relaxed(void* p, uint32_t x, uint32_t y, uint32_t z, uint32_t w) {
  asm volatile("st.relaxed.gpu.global.v4.b32 [%0], {%1,%2,%3,%4};" :: "l"(p), "r"(x), "r"(y), "r"(z), "r"(w) : "memory");
}
DI void red_f16x8(void* p, uint32_t x, uint32_t y, uint32_t z, uint32_t w) {
  asm volatile("red.relaxed.gpu.global.add.noftz.v4.f16x2 [%0], {%1,%2,%3,%4};" :: "l"(p), "r"(x), "r"(y), "r"(z), "r"(w) : "memory");
}
DI void sq_acc(uint32_t& a, uint32_t x) { asm("fma.rn.bf16x2 %0, %1, %1, %0;" : "+r"(a) : "r"(x)); }
DI __half2 amax4(__half2 h, const uint32_t* v) {
  h = __hmax2_nan(__hmax2_nan(h, __habs2(*(const __half2*)&v[0])), __habs2(*(const __half2*)&v[1]));
  return __hmax2_nan(__hmax2_nan(h, __habs2(*(const __half2*)&v[2])), __habs2(*(const __half2*)&v[3]));
}
DI uint32_t wexp(__half2 h) { const uint32_t u = *(const uint32_t*)&h; return __reduce_max_sync(0xffffffffu, max((u >> 16) & 0x7fffu, u & 0x7fffu)) >> 7; }
DI float max10(const float* a) {
  return fmaxf(fmaxf(fmaxf(fmaxf(a[0], a[1]), fmaxf(a[2], a[3])), fmaxf(fmaxf(a[4], a[5]), fmaxf(a[6], a[7]))), fmaxf(a[8], a[9]));
}
DI float quad_max(float m) {
  return fmaxf(fmaxf(m, __shfl_xor_sync(0xffffffffu, m, 1)), fmaxf(__shfl_xor_sync(0xffffffffu, m, 2), __shfl_xor_sync(0xffffffffu, m, 3)));
}
DI float warp_sum(float v) {
#pragma unroll
  for (int o = 16; o; o >>= 1) v += __shfl_xor_sync(0xffffffffu, v, o);
  return v;
}

constexpr int SM_WO3 = 0;
constexpr int SM_X = 16384;
constexpr int XT = 36864;
constexpr int SM_EXP = 126976;
constexpr int SEGB = 10240;
constexpr int SM_BLK = SM_EXP + 8192;
constexpr int SM_VC = SM_BLK + 4 * SEGB;
constexpr int SM_PART = SM_VC + 16384;
constexpr int SM_QM = SM_PART + 4096;
constexpr int SM_E = SM_QM + 1024;
constexpr int SM_VM = SM_E + 1536;
constexpr int SM_OB = SM_VM + 2048;
constexpr int SM_FB = SM_OB + 2048;
constexpr int SM_STAGE = SM_X + XT;
constexpr int SM_MISC = 210944;
constexpr int SM_WOST = 212992;
constexpr int SM_MEM = SM_WOST;
constexpr int SM_MAX = SM_MEM + 11264;
#define MEM_BLK(q) ((q) / 3 * 4096 + (q) % 3 * 1024)
constexpr int SM_TOTAL = 229376;
constexpr int MB_W = SM_MISC;
constexpr int MB_WO = SM_MISC + 24;
constexpr int MB_WO3 = SM_MISC + 32;
constexpr int MB_X = SM_MISC + 40;
constexpr int MB_S = SM_MISC + 64;
constexpr int MB_F = SM_MISC + 72;
constexpr int MB_VX = SM_MISC + 80;
constexpr int SC_FPAR = SM_MISC + 136;
constexpr int SC_DEAD = SM_MISC + 96;
constexpr int SC_UNSC = SM_MISC + 112;
constexpr int SC_EPOCH = SM_MISC + 128;
constexpr int SC_EXPW = SM_MISC + 132;
constexpr int SC_ONES = SM_MISC + 144;
constexpr int SC_SS = SM_MISC + 160;
constexpr int SC_LAT = SM_MISC + 224;
constexpr int MB_T = SM_MISC + 232;
constexpr int T_SX = SM_X + XT;
constexpr int T_OB = SM_X + 2 * XT;
constexpr int T_WA = T_OB + 16384;
constexpr int T_OA = T_WA + 9216;
constexpr int T_P = T_OA + 4096 + 128;
constexpr int T_UN = T_OA + 4096;
constexpr int T_RED = 131072;
constexpr int SC_XMAX = SM_MISC + 256;
constexpr int SC_PROF = 229376;

constexpr float SM_SCALE = 0.08838834764831845f;
constexpr float LOG2E = 1.4426950408889634f;
constexpr float E_LIM = 20.f;

template <bool B> struct BoolC { static constexpr bool value = B; };
struct RMaps { CUtensorMap x, wq, wk, wv, wo, woa, oa; unsigned char* red; bf16* out; uint32_t poll; };

DI uint32_t latest_hint(uint32_t h, uint32_t d, int s) {
  const uint32_t x = (((h | 0xc0c0c0c0u) - ((d >> 5) & 63) * 0x01010101u) & 0x3f3f3f3fu) | ((h ^ (((s >> 2) + 1) & 3) * 0x40404040u) & 0xc0c0c0c0u);
  const uint32_t y = __vmaxu2(x & 0x00ff00ffu, (x >> 8) & 0x00ff00ffu);
  return __reduce_max_sync(0xffffffffu, max(y & 0xffffu, y >> 16));
}
DI uint32_t near_half(uint32_t sb) {
  uint32_t a, b; lds64(sb + SC_LAT, a, b);
  return a > b;
}

template <int RT, int K0, int K1, bool D32 = false, int BAR = 0, int KB = 18>
DI void xproj(float* acc, const uint32_t (&wa)[2][18][4], uint64_t xd) {
  if (XP & 1) return;
  WG_FENCE();
#pragma unroll
  for (int k = K0; k < ((XP & 128) ? K0 + 1 : K1); k++)
  {
    uint64_t d = xd + (uint64_t)(((k >> 1) * 4096 + (k & 1) * 32) >> 4);
    if (D32) asm("mov.b64 %0, {%1, %2};" : "=l"(d) : "r"((uint32_t)xd + (((k >> 1) * 4096 + (k & 1) * 32) >> 4)), "r"((uint32_t)(xd >> 32)));
    wgmma_n32_rs(acc, wa[RT][k][0], wa[RT][k][1], wa[RT][k][2], wa[RT][k][3], d, k != 0);
    if (BAR && k == KB - 1 && KB < 18) bar_arrive(BAR, 256);
  }
  WG_COMMIT();
}

DI void seg_store(int seg, uint32_t sb, uint32_t off, uint32_t bytes) {
  asm volatile("cp.async.bulk.global.shared::cta.bulk_group [%0], [%1], %2;"
               :: "l"(g_seg + ((size_t)(seg % NRING) * 96 + blockIdx.x) * SEGB + off), "r"(sb + SM_BLK + (seg & 3) * SEGB + off), "r"(bytes) : "memory");
  asm volatile("cp.async.bulk.commit_group;" ::: "memory");
}
DI void seg_publish(int seg) {
  asm volatile("cp.async.bulk.wait_group 0;" ::: "memory");
  asm volatile("red.relaxed.gpu.global.add.u32 [%0], 1;" :: "l"(&g_scnt[(seg * 32 + blockIdx.x / 3) * 8]) : "memory");
  SSTAMP(10, seg);
}

#define NAP 64
DI uint32_t movm(uint32_t x) { uint32_t r; asm volatile("movmatrix.sync.aligned.m8n8.trans.b16 %0, %1;" : "=r"(r) : "r"(x)); return r; }
DI bool wait_count(const unsigned* p, unsigned target, bool nap = true) {
  int n = 0;
  unsigned v;
  while (true) {
    asm volatile("ld.acquire.gpu.global.b32 %0, [%1];" : "=r"(v) : "l"(p) : "memory");
    if ((int)(v - target) >= 0 || ++n > SPIN_LIMIT) break;
    if (nap) __nanosleep(NAP);
  }
  return n;
}
#define PACE 1200
#define PACE2 600
#define PACE3 (3 * PACE)
#define PORD 0
DI void load_weights(uint32_t sb, const RMaps& tm, uint32_t rank, int c) {
  const int h = blockIdx.x / 3;
  if (c < 3) {
    mbar_expect(sb + MB_W + 8 * c, 49152);
    tma_load(sb + SM_STAGE + c * 49152, rank < 2 ? &tm.wk : &tm.wv, h * DH + (rank == 1 ? 64 : 0), c * 192, sb + MB_W + 8 * c);
    tma_load(sb + SM_STAGE + c * 49152 + 24576, rank < 2 ? &tm.wq : &tm.wv, h * DH + (rank == 0 ? 0 : 64), c * 192, sb + MB_W + 8 * c);
  } else {
    tma_prefetch(&tm.wo, rank * 192, h * DH);
    mbar_expect(sb + MB_WO, 16384);
    mbar_expect(sb + MB_WO3, 32768);
    tma_load(sb + SM_WOST, &tm.wo, rank * 192 + 64, h * DH, sb + MB_WO3);
    tma_load(sb + SM_WO3, &tm.wo, rank * 192 + 128, h * DH, sb + MB_WO3);
  }
}

DI void tail_attention(const uint32_t sb, const uint32_t rank, const int w, const int lane, const int sg, const int bar) {
  const int m = lane >> 3, g = lane >> 2, t = lane & 3;
  const uint32_t l16 = sb + lane * 16, src = l16 + T_SX + sg * 10240 + w * 1280;
  const float2 gt = __ldcg((const float2*)&g_gate[(NAUXSEG + sg) * 32 + w * 8 + 2 * t]);
  if (rank < 2) {
    const uint32_t base = l16 + SM_BLK + (2 + sg) * SEGB, dst = src + rank * 5120;
    uint32_t qb[2][4];
    ldsm4t(qb[0], base + w * 1024); ldsm4t(qb[1], base + w * 1024 + 512);
#pragma unroll
    for (int j = 0; j < 3; j++) {
      uint32_t kb[4][4];
      float c[4][4];
      const uint32_t ka = base + 4096 + j * 2048 + (m & 1) * (j == 2 ? 128 : 896) - (m >> 1) * 128;
#pragma unroll
      for (int k = 0; k < 4; k += j == 2 ? 2 : 1) ldsm4t(kb[k], ka + k * 256);
      mma16816z(c[0], kb[0], qb[0][0], qb[0][1]); mma16816z(c[1], kb[j == 2 ? 0 : 1], qb[0][2], qb[0][3]);
      mma16816z(c[2], kb[2], qb[1][0], qb[1][1]); mma16816z(c[3], kb[j == 2 ? 2 : 3], qb[1][2], qb[1][3]);
      uint32_t r[4];
#pragma unroll
      for (int i = 0; i < (j == 2 ? 2 : 4); i++) r[i] = __float_as_uint((c[0][i] + c[1][j == 2 ? i + 2 : i]) + (c[2][i] + c[3][j == 2 ? i + 2 : i]));
#pragma unroll
      for (int d = 0; d < 2; d++) {
        const uint32_t to = d ? 2 : rank ^ 1, mb = mapa(sb + MB_T + 8 + 8 * sg, to);
        if (j < 2) st_async4(mapa(dst + j * 512, to), r[0], r[1], r[2], r[3], mb);
        else st_async2(mapa(dst + 1024 - lane * 8, to), r[0], r[1], mb);
      }
      if (j < 2) sts128(dst + j * 512, r[0], r[1], r[2], r[3]); else sts64(dst + 1024 - lane * 8, r[0], r[1]);
    }
  }
  TSTAMP(50 + 2 * sg);
  uint32_t vx[4][4], vm[4];
  const uint32_t va = l16 + (rank < 2 ? SM_VC + sg * 8192 : SM_BLK + (2 + sg) * SEGB) + w * 1024 + (m & 1) * 384 - (m >> 1) * 128;
#pragma unroll
  for (int i = 0; i < 4; i++) ldsm4(vx[i], va + (i & 1) * 4096 + (i >> 1) * 256);
  if (sg && rank < 2) mbar_wait(sb + MB_T, 0);
  lds128(l16 + (sg ? SM_FB : SM_VM) + w * 512, vm);
  float a[10], b[10];
  mbar_wait(sb + MB_T + 8 + 8 * sg, 0);
  TSTAMP(58 + 2 * sg);
  lds128f(src, a); lds128f(src + 512, a + 4); lds64f(src + 1024 - lane * 8, a + 8);
  lds128f(src + 5120, b); lds128f(src + 5632, b + 4); lds64f(src + 6144 - lane * 8, b + 8);
#pragma unroll
  for (int i = 0; i < 10; i++) {
    a[i] = (a[i] + b[i]) * (SM_SCALE * LOG2E);
    if (i < 8 && (i >> 1) * 8 + g > w * 8 + 2 * t + (i & 1)) a[i] = -1.0e9f * LOG2E;
  }
  float m0 = fmaxf(fmaxf(fmaxf(a[0], a[2]), fmaxf(a[4], a[6])), a[8]), m1 = fmaxf(fmaxf(fmaxf(a[1], a[3]), fmaxf(a[5], a[7])), a[9]);
#pragma unroll
  for (int o = 4; o < 32; o <<= 1) { m0 = fmaxf(m0, __shfl_xor_sync(0xffffffffu, m0, o)); m1 = fmaxf(m1, __shfl_xor_sync(0xffffffffu, m1, o)); }
#pragma unroll
  for (int i = 0; i < 10; i++) a[i] = ex2(a[i] - (i & 1 ? m1 : m0));
  float s0 = ((a[0] + a[2]) + (a[4] + a[6])) + a[8], s1 = ((a[1] + a[3]) + (a[5] + a[7])) + a[9];
#pragma unroll
  for (int o = 4; o < 32; o <<= 1) { s0 += __shfl_xor_sync(0xffffffffu, s0, o); s1 += __shfl_xor_sync(0xffffffffu, s1, o); }
  s0 = (1.f - gt.x) * rcp(s0); s1 = (1.f - gt.y) * rcp(s1);
#pragma unroll
  for (int i = 0; i < 5; i++) sts32(sb + T_P + sg * 2560 + w * 640 + i * 128 + lane * 4, pack_bf16(a[2 * i] * s0, a[2 * i + 1] * s1));
  bar_sync(bar, 128);
  TSTAMP(59 + 2 * sg);
#pragma unroll
  for (int j = 0; j < 4; j++) {
    uint32_t p[5];
    float o0[4], o1[4];
    ldsm4t(p, l16 + T_P + sg * 2560 + j * 640);
    asm volatile("ldmatrix.sync.aligned.m8n8.x1.trans.shared.b16 {%0}, [%1];" : "=r"(p[4]) : "r"(l16 + T_P + sg * 2560 + j * 640 + 512) : "memory");
    mma16816z(o0, vx[0], p[0], p[1]); mma16816z(o1, vx[1], p[0], p[1]);
    mma16816(o0, vx[2], p[2], p[3]); mma16816(o1, vx[3], p[2], p[3]);
    mma1688(o0, vm[0], vm[1], p[4]); mma1688(o1, vm[2], vm[3], p[4]);
    stsm4(l16 + T_OB + sg * 8192 + j * 2048 + w * 512, pack_bf16(o0[0], o0[1]), pack_bf16(o0[2], o0[3]), pack_bf16(o1[0], o1[1]), pack_bf16(o1[2], o1[3]));
  }
}

DI void proj_role(const uint32_t sb, const RMaps& tm, const uint32_t rank, const int wg, const int w, const int lane) {
  const bool qk = rank < 2;
  uint32_t wa[2][18][4];
  {
    const int rr = (lane & 7) + ((lane >> 4) << 3);
    const uint32_t col = ((2 * w + ((lane >> 3) & 1)) ^ (lane & 7)) << 4;
    float ss = 0.f;
#pragma unroll
    for (int c = 0; c < 3; c++) {
      mbar_wait(sb + MB_W + 8 * c, 0);
      if (threadIdx.x == 0) SSTAMP(11, c);
#pragma unroll
      for (int rt = 0; rt < 2; rt++)
#pragma unroll
        for (int k = 0; k < 6; k++)
          ldsm4t(wa[rt][c * 6 + k], sb + SM_STAGE + c * 49152 + (rt ^ wg) * 24576 + (64 * (k >> 1) + 32 * wg + 16 * (k & 1) + rr) * 128 + col);
      if (c < 2) {
        fence_async();
        bar_sync(3, 256);
        if (threadIdx.x == 0) {
          if (c == 0) tma_load3(sb + SM_X + XT, &tm.x, 32, sb + MB_X + 8);
          else { tma_load(sb + SM_X + 2 * XT, &tm.wo, rank * 192, (blockIdx.x / 3) * DH, sb + MB_WO); SSTAMP(11, 11); }
        }
        __syncwarp();
      }
      uint32_t q[4] = {0, 0, 0, 0};
#pragma unroll
      for (int rt = 0; rt < 2; rt++)
#pragma unroll
        for (int k = 0; k < 6; k++)
#pragma unroll
          for (int i = 0; i < 4; i++) sq_acc(q[i], wa[rt][c * 6 + k][i]);
#pragma unroll
      for (int i = 0; i < 4; i++) ss += bf_lo(q[i]) + bf_hi(q[i]);
    }
    ss = warp_sum(ss);
    fence_async();
    cluster_arrive();
    if (lane == 0) sts32(sb + SC_SS + 4 * (wg * 4 + w), qk ? 0 : __float_as_uint(ss));
    bar_arrive(11, 384);
  }
  STAMP(1);
  MSTAMP(0);
  mbar_wait(sb + MB_X, 0);
  STAMP(2);

  uint32_t t16 = sb + (w * 32 + lane) * 16;
  uint32_t mem_a = sb + SM_MEM + wg * 512 + lane * 16;
  uint32_t fin_a = sb + (lane & 7) * 16 + SM_BLK + (qk ? (wg ^ 1) * 4096 + w * 256 + (lane & 8) * 16 + (lane & 16) * 64
                                              : wg * 4096 + w * 1024 + (lane & 8) * 64 + (lane & 16) * 8);
  PIN(t16); PIN(mem_a); PIN(fin_a);
  const uint32_t fence_reg = mem_a;
  const uint32_t fin2 = qk ? 2048 : 256;
  float acc[16];
  const uint64_t xd0 = make_desc(sb + SM_X + wg * 64, 16, 1024, 1);
  auto do_export = [&]() {
    WG_WAIT(0);
    uint32_t q[8];
#pragma unroll
    for (int j = 0; j < 8; j++) q[j] = pack_bf16(acc[2 * j], acc[2 * j + 1]);
    sts128(t16 + SM_EXP + wg * 4096, q[0], q[1], q[2], q[3]);
    sts128(t16 + SM_EXP + wg * 4096 + 2048, q[4], q[5], q[6], q[7]);
    if (RET) asm volatile("{\n.reg .pred p;\nsetp.eq.u32 p, %2, 0;\n@p add.u32 %0, %0, 1;\n@p add.u32 %1, %1, 1;\nsetp.eq.and.u32 p, %0, %1, p;\n@p exit;\n}"
                          : "+r"(q[3]), "+r"(q[7]) : "r"(t16) : "memory");
  };
  uint32_t o[8];
  auto import = [&]() { lds128(t16 + SM_EXP + (wg ^ 1) * 4096, o); lds128(t16 + SM_EXP + (wg ^ 1) * 4096 + 2048, o + 4); };
  auto finish = [&](int seg) {
    const uint32_t a = fin_a + (seg & 3) * SEGB;
    WG_WAIT(0);
#pragma unroll
    for (int i = 0; i < 8; i++) o[i] = FIN16 ? add_bf16(pack_bf16(acc[2 * i], acc[2 * i + 1]), o[i]) : pack_bf16(acc[2 * i] + bf_lo(o[i]), acc[2 * i + 1] + bf_hi(o[i]));
    stsm4(a, o[0], o[1], o[2], o[3]);
    stsm4(a + fin2, o[4], o[5], o[6], o[7]);
  };
  auto send_v = [&](int seg, int dst) {
    fence_async();
    if (seg < NSEG && !(XP & 2) && elect_one())
      bulk_s2s(mapa(sb + SM_VC + (seg & 1) * 8192, dst), sb + SM_BLK + (seg & 3) * SEGB, 8192, mapa(sb + MB_VX + (seg & 1) * 8, dst));
    __syncwarp();
  };
  auto wait_v = [&](int seg) {
    if (seg < NSEG && !(XP & 2)) {
      mbar_wait(sb + MB_VX + (seg & 1) * 8, (seg >> 1) & 1);
      if (elect_one()) mbar_expect(sb + MB_VX + (seg & 1) * 8, 8192);
      __syncwarp();
    }
  };
  bar_sync(3, 256);
  xproj<1, 0, 18>(acc, wa, xd0);
  do_export();
  SCHED_FENCE(11);
  xproj<0, 0, 18>(acc, wa, xd0);
  bar_sync(3, 256);
  if (threadIdx.x == 0) SSTAMP(11, 12);
  MSTAMP(1);
  cluster_wait();
  if (threadIdx.x == 0) SSTAMP(11, 13);
  mbar_wait(sb + MB_X + 8, 0);
  import();
  finish(0);
  SCHED_FENCE(12);
  bar_sync(3, 256);
  uint64_t dA = xd0 + (XT >> 4);
  xproj<1, 0, 18>(acc, wa, dA);
  if (!qk && wg == 0 && w < 2) send_v(0, w);
  do_export();
  if (qk && wg == 0 && w == 0) wait_v(0);
  bar_arrive(13, 384);
  if (!qk) {
    SCHED_FENCE(15);
    xproj<0, 0, 18>(acc, wa, dA);
    if (threadIdx.x == 0 && !(XP & 8)) { mbar_expect(sb + MB_X, XT); tma_load3(sb + SM_X, &tm.x, 96, sb + MB_X); }
    bar_sync(3, 256);
    mbar_wait(sb + MB_X + 16, 0);
    import();
    finish(1);
    SCHED_FENCE(16);
    bar_sync(3, 256);
    dA += XT >> 4;
    xproj<1, 0, 18>(acc, wa, dA);
    if (wg == 0 && ((w == 0 && VS0) || (w == 1 && VS1))) send_v(1, w);
    do_export();
  }
  if (threadIdx.x == 0) SSTAMP(11, 14);
  MSTAMP(2);
  bar_sync(0, 384);
  const int ro = __shfl_sync(0xffffffffu, near_half(sb) ^ wg, 0);
  STAMP(5);
  const uint32_t always = __shfl_sync(0xffffffffu, lds32(sb + SC_DEAD + 12), 0);
  const int ah = qk ? 1 : 2;
  int b2 = qk ? 2 : 0;
  int s = 0;
  uint32_t hint_lo = (uint32_t)(uint64_t)tm.red + HINT_OFF + blockIdx.x + (lane & 1) * 4096 + (lane >> 1) * 16384;
  PIN(hint_lo);
  auto post_hint = [&]() {
    asm volatile("{\n.reg .pred p;\n.reg .b64 a;\n.reg .u32 t;\nsetp.lt.u32 p, %0, %1;\nmov.b64 a, {%2, %3};\nmov.u32 t, %%globaltimer_lo;\n"
                 "bfe.u32 t, t, 5, 6;\nor.b32 t, t, %4;\n@p st.relaxed.gpu.global.u8 [a], t;\n}"
                 :: "r"(t16), "r"(sb + 128), "r"(hint_lo + RED_SLOT(s)), "r"((uint32_t)((uint64_t)tm.red >> 32)), "r"(((s >> 2) + 1) << 6) : "memory");
  };
  auto memproj = [&](auto second, int id, float u0, float u1, float* r) {
    constexpr bool R1 = decltype(second)::value;
    uint32_t b[NUP][4], b0[4];
    SCHED_FENCE(id);
    bar_sync(R1 ? 2 : 1, 256);
    PROF(0);
    ldsm4t(b0, mem_a);
#pragma unroll
    for (int q = 0; q < NUP; q++) {
      if (R1 && q == 2) {
        bar_sync(11, 256);
        SCHED_FENCE(id + 1);
      }
      ldsm4t(b[q], mem_a + MEM_BLK(q + 1));
    }
    mma16816z(&acc[0], wa[0][0], b0[0], b0[1]);
    mma16816z(&acc[4], wa[1][0], b0[0], b0[1]);
    mma16816z(&acc[8], wa[0][1], b0[2], b0[3]);
    mma16816z(&acc[12], wa[1][1], b0[2], b0[3]);
#pragma unroll
    for (int q = 1; q < 9; q++) {
      uint32_t* const c = b[(q - 1) % NUP];
      mma16816(&acc[0], wa[0][2 * q], c[0], c[1]);
      mma16816(&acc[4], wa[1][2 * q], c[0], c[1]);
      mma16816(&acc[8], wa[0][2 * q + 1], c[2], c[3]);
      mma16816(&acc[12], wa[1][2 * q + 1], c[2], c[3]);
      if (R1 && q + NUP == B3Q) bar_sync(3, 256);
      if (q + NUP < 9) ldsm4t_in(c, mem_a + MEM_BLK(q + NUP), always);
      else if (R1 && q + NUP < 11) lds128_in(c, t16 + SM_PART + (10 - q - NUP) * 2048, always);
      else if (!R1 && GATE && q == GATE) { bar_arrive(11, 256); lds128_in(c, sb + SC_DEAD, always); u0 = u1 = __uint_as_float(c[3]); }
    }
#pragma unroll
    for (int i = 0; i < 8; i++) {
      const float u = i < 4 ? u0 : u1;
      r[i] = R1 ? fmaf(acc[8 + i], u, (acc[i] + __uint_as_float(b[(8 + i / 4) % NUP][i & 3])) * u) : (GATE ? fmaf(acc[i], u, acc[8 + i]) : acc[i] + acc[8 + i]);
    }
  };
  if (ro == 0) {
    auto set_scale = [&]() {
      uint32_t m[8];
      lds128(t16 + SM_MAX - 512, m); lds128(t16 + SM_MAX, m + 4);
      const int em = (wexp(amax4(amax4(*(const __half2*)&m[0], m), m + 4)) >> 3) + (int)(lds32(sb + SC_UNSC + (s & 1) * 8) >> 23) - 15;
      const int ex = max(s ? em : 0, (int)lds32(sb + SC_XMAX + 4 * s)) - 127 + (int)lds32(sb + SC_EXPW);
      sts32(sb + SC_UNSC + (~s & 1) * 8, (127 + min(max(ex, -120), 120)) << 23);
    };
#pragma unroll 1
    while (true) {
      if (s == 8) STAMP(6);
      float r[8];
      memproj(BoolC<false>(), 30, 0.f, 0.f, r);
      sts128(t16 + SM_PART, __float_as_uint(r[0]), __float_as_uint(r[1]), __float_as_uint(r[2]), __float_as_uint(r[3]));
      sts128(t16 + SM_PART + 2048, __float_as_uint(r[4]), __float_as_uint(r[5]), __float_as_uint(r[6]), __float_as_uint(r[7]));
      bar_arrive(3, 256);
      PROF(1);
      bar_sync(9, 256);
      if (s == NSEG - 1) break;
      post_hint();
      if (w == 1) {
        set_scale();
        __syncwarp();
        if (elect_one()) mbar_arrive(sb + MB_S);
      }
      SCHED_FENCE(9);
      bar_sync(5, qk ? N5 : 256);
      PROF(2);
      import();
      xproj<0, 0, NII, (DD & 1) != 0>(acc, wa, dA);
      if (NII < 18) {
        if (qk) bar_sync(7, 384);
        xproj<0, NII, 18>(acc, wa, dA);
        if (!qk) bar_sync(7, 384);
      } else {
        if (F10) WG_WAIT(0);
        bar_sync(10, 256);
        if (F10) SCHED_FENCE(17);
      }
      dA += (int64_t)(b2 ? XT >> 4 : -(XT >> 3));
      finish(s + ah);
      if (qk || !VLATE(w)) bar_arrive(13, 384);
      PROF(6);
      SCHED_FENCE(14);
      bar_sync(12, 256);
      PROF(7);
      xproj<1, 0, 18, (DD & 2) != 0, 14, N14>(acc, wa, dA);
      if (N14 == 18) bar_arrive(14, 256);
      b2 = b2 == 2 ? 0 : b2 + 1;
      s++;
      if (!qk && VLATE(w)) { bar_sync(13, 384); send_v(s + 1, w); }
      PROFP(8);
      do_export();
      s--; RSTAMP(6); s++;
      PROFP(3);
    }
    if (!qk) bar_arrive(5, 256);
    if (w == 0 && elect_one()) {
      const uint32_t h18 = blockIdx.x / 3 * 18;
      mbar_expect(sb + MB_WO, 9216 + 4096);
      tma_load(sb + T_OA, &tm.oa, 4096 + (h18 & ~7), NAUXSEG * 32, sb + MB_WO);
#pragma unroll 1
      for (int j = 0; j < 3; j++) tma_load(sb + T_WA + j * 3072, &tm.woa, rank * 192 + j * 64, h18, sb + MB_WO);
    }
    if (w == 1) {
      const int ea = (int)ldg_relaxed32(&g_amax[0]) + (int)ldg_relaxed32(&g_amax[16]) - 254 + 2 + 10 - 15;
      set_scale();
      __syncwarp();
      sts32(sb + T_UN + (lane & 1) * 4, (128 + max(min(ea, 120), (int)(lds32(sb + SC_UNSC + 8 - (lane & 1) * 8) >> 23) - 127)) << 23);
    }
    bar_arrive(8, 256);
  } else {
    uint32_t r0;
    float un;
    auto prepare = [&]() {
      un = __uint_as_float(lds32(sb + SC_UNSC + (s & 1) * 8));
      r0 = qk ? (t16 & ~256u) - w * 256 + (((t16 >> 8) ^ wg) & 1 ? SM_QM : SM_BLK + 8192 + (s & 3) * SEGB) : mapa(t16 + (s < NSEG - 1 ? SM_VM : SM_FB), 0);
      PIN(r0); PIN(un);
    };
    auto mem_out = [&](int off, uint32_t lo, uint32_t hi) {
      unsigned char* const d = g_seg + ((size_t)(s % NRING) * 96 + blockIdx.x) * SEGB + 8192 + off + w * 256 + ((t16 >> 2) & 124);
      if (!(XP & 4)) { stg_relaxed32(d, lo); stg_relaxed32(d + 128, hi); }
    };
    prepare();
#pragma unroll 1
    while (true) {
      if (s == 8) STAMP(6);
      float r[8];
      if (qk) {
        const float u0 = wg ? un * (SM_SCALE * LOG2E) : un, u1 = wg ? un : un * (SM_SCALE * LOG2E);
        memproj(BoolC<true>(), 32, u0, u1, r);
        const uint32_t p0 = pack_bf16(r[0], r[1]), p1 = pack_bf16(r[2], r[3]), p2 = pack_bf16(r[4], r[5]), p3 = pack_bf16(r[6], r[7]);
        stsm4(r0, p0, p1, p2, p3);
        bar_arrive(4, 256);
        if (EXM) { SCHED_FENCE(18); mem_out(0, wg ? p2 : p0, wg ? p3 : p1); }
      } else {
        const uint32_t mb = sb + (s < NSEG - 1 ? MB_S : MB_T), r1 = r0 + (1 << 24);
        memproj(BoolC<true>(), 34, un, un, r);
        const uint32_t p0 = pack_bf16(r[0], r[1]), p1 = pack_bf16(r[2], r[3]), p2 = pack_bf16(r[4], r[5]), p3 = pack_bf16(r[6], r[7]);
        const uint32_t v0 = wg ? p2 : p0, v1 = wg ? p3 : p1, v2 = wg ? p0 : p2, v3 = wg ? p1 : p3;
        st_async4(r0, v0, v1, v2, v3, mapa(mb, 0));
        st_async4(r1, v0, v1, v2, v3, mapa(mb, 1));
        bar_arrive(5, 256);
        sts128(r0 + (2 << 24), v0, v1, v2, v3);
        stsm4((t16 & ~256u) - w * 256 + SM_BLK + 8192 + (s & 3) * SEGB + (((t16 >> 8) ^ wg) & 1) * 1024, p0, p1, p2, p3);
        __syncwarp();
        if (elect_one()) mbar_arrive(sb + MB_S);
        __syncwarp();
        if (EXM) { SCHED_FENCE(19); mem_out(0, v0, v1); mem_out(1024, v2, v3); }
      }
      if (s == NSEG - 1) break;
      if (!qk && !EXM) bar_arrive(15, 160);
      PROF(1);
      auto rearm = [&]() { mbar_wait(sb + MB_S, s & 1); if (elect_one()) mbar_expect(sb + MB_S, qk ? 640 + 2048 : 1280); __syncwarp(); };
      if (w == 1) {
        if ((t16 & 384) == 0) stg_relaxed(tm.red + (RED_SLOT(s + 2) + RED_LINE(blockIdx.x)) + (t16 & 112), 0, 0, 0, 0);
      } else if (w == 0) {
        const int tn = s + ah + 1;
        if (RFW) mbar_wait(sb + MB_S, s & 1);
        if (tn + 1 < NSEG && !(XP & 8) && elect_one()) {
          const int b0 = b2 == 2 ? 0 : b2 + 1;
          mbar_expect(sb + MB_X + 8 * b0, XT);
          tma_load3(sb + SM_X + b0 * XT, &tm.x, (tn + 1) * 32, sb + MB_X + 8 * b0);
        }
        if (tn < NSEG && (!(XP & 8) || tn < 3)) mbar_wait(sb + MB_X + 8 * b2, (tn / 3) & 1);
      } else if (w == 2) {
        if (!qk) { if (VS0 == 0) send_v(s + 1, 0); if (VS1 == 0) send_v(s + 1, 1); }
      } else if (qk || !NIC) {
        rearm();
      }
      __syncwarp();
      import();
      PROF(4);
      SCHED_FENCE(10);
      if (NIC) {
        if (qk) bar_sync(7, NII < 18 ? 384 : 256);
        xproj<0, 0, NIC>(acc, wa, dA);
        if (!qk) { if (w == 3) rearm(); bar_sync(7, NII < 18 ? 384 : 256); }
      } else {
        bar_sync(7, NII < 18 ? 384 : 256);
      }
      xproj<0, NIC, 18, (DD & 4) != 0, 12, N12>(acc, wa, dA);
      if (N12 == 18) bar_arrive(12, 256);
      dA += (int64_t)(b2 ? XT >> 4 : -(XT >> 3));
      finish(s + ah);
      if (qk && w == 0) wait_v(s + 1);
      bar_arrive(13, 384);
      PROF(6);
      SCHED_FENCE(13);
      bar_sync(14, 256);
      PROF(7);
      xproj<1, 0, 18, (DD & 8) != 0>(acc, wa, dA);
      b2 = b2 == 2 ? 0 : b2 + 1;
      s++;
      if (HOIST) prepare();
      PROFP(8);
      do_export();
      if (!HOIST) prepare();
      s--; RSTAMP(7); s++;
      PROFP(3);
    }
    TSTAMP(2);
    bar_sync(3, 128);
    tail_attention(sb, rank, w, lane, 1, 3);
    bar_arrive(0, 256);
  }
  STAMP(3);
  if (CSY) cluster_sync();
  STAMP(4);
}

DI void attn_role(const uint32_t sb, unsigned char* smem_raw, const RMaps& tm, const uint32_t RANK, const bf16* __restrict__ x, const bf16* __restrict__ mem0,
                  const int w, const int lane) {
  const int t2 = w * 32 + lane;
  uint32_t wo[8][4], w1[8][4];
  const uint32_t wo_lane = sb + ((lane & 7) + ((lane >> 4) << 3)) * 128 + (((w + 4 * ((lane >> 3) & 1)) ^ (lane & 7)) << 4);
  unsigned char* const g_red = tm.red;
  {
    const uint32_t t0 = gtime();
    const uint32_t tag = *(volatile unsigned*)&g_epoch + 1;
    if (w == 0) {
      stg_relaxed(g_red + RED_SLOT(t2 >> 3) + RED_LINE(blockIdx.x) + (t2 & 7) * 16, 0, 0, 0, 0);
      stg_relaxed(g_red + T_RED + blockIdx.x * 1024 + t2 * 16, 0, 0, 0, 0);
      stg_relaxed(g_red + T_RED + blockIdx.x * 1024 + 512 + t2 * 16, 0, 0, 0, 0);
      asm volatile("st.relaxed.gpu.global.u8 [%0], 0;" :: "l"(g_red + RED_SLOT(t2) + HINT_OFF + (t2 & 4) * 1024 + (t2 >> 3) * 16384 + blockIdx.x) : "memory");
    }
    bar_sync(0, 384);
    cluster_arrive();
    if (PACE && w == 3) {
#pragma unroll 1
      for (int c = 1; c < 4; c++) {
        wait_until(t0 + (c == 3 ? PACE3 : c * (RANK < 2 ? PACE : PACE2)));
        if (elect_one()) load_weights(sb, tm, RANK, PORD ? (c == 1 ? 3 : c - 1) : c);
        __syncwarp();
      }
    }
    uint4 xv[18];
    uint32_t mv[20];
#pragma unroll
    for (int i = 0; i < 20; i++) mv[i] = i < 18 ? ((const uint32_t*)mem0)[(lane >> 2) * (DM / 2) + (w * 18 + i) * 4 + (lane & 3)] : 0;
#pragma unroll
    for (int i = 0; i < 18; i++) xv[i] = blockIdx.x < NSEG ? ((const uint4*)(x + blockIdx.x * 32 * DM))[t2 + 128 * i] : make_uint4(0, 0, 0, 0);
    __half2 hx = __float2half2_rn(0.f);
#pragma unroll
    for (int i = 0; i < 18; i++) hx = amax4(hx, &xv[i].x);
    if (blockIdx.x == 0)
#pragma unroll
      for (int i = 0; i < 5; i++) hx = amax4(hx, &mv[4 * i]);
    sts32(sb + SC_SS + 4 * (12 + w), wexp(hx));
    if (t2 == 0) { sts32(sb + SC_EPOCH, (tag - 1) * NSEG + 2 - NRING); sts32(sb + SC_UNSC, __float_as_uint(1.f)); sts128(sb + SC_DEAD, 0, 0, 0, 0x3f800000u); sts64(sb + SC_FPAR, 0, 0); sts128(sb + SC_ONES, 0x3f803f80u, 0x3f803f80u, 0x3f803f80u, 0x3f803f80u); }
    WSTAMP(27);
    if (w == 0) __threadfence();
    uint32_t q[8] = {0, 0, 0, 0, 0, 0, 0, 0};
    mbar_wait(sb + MB_WO3, 0);
    if (t2 == 0) SSTAMP(11, 3);
    MSTAMP(3);
#pragma unroll
    for (int k = 0; k < 8; k++) {
      ldsm4t(wo[k], wo_lane + SM_WO3 + k * 2048); ldsm4t(w1[k], wo_lane + SM_WOST + k * 2048);
#pragma unroll
      for (int i = 0; i < 4; i++) { sq_acc(q[i], wo[k][i]); sq_acc(q[i], w1[k][i]); }
    }
    bar_sync(6, 128);
    if (t2 == 0) SSTAMP(11, 7);
#pragma unroll
    for (int k = 0; k < 8; k++) sts128(sb + SM_WO3 + t2 * 16 + k * 2048, wo[k][0], wo[k][1], wo[k][2], wo[k][3]);
#pragma unroll
    for (int i = 0; i < 5; i++) {
      const int j = w * 18 + 4 * i + (lane >> 3), c = i < 4 || lane < 16 ? j * 8 + j / 24 * 64 : 192;
      stsm4t(sb + SM_MEM + (c + (lane & 7)) * 16, mv[4 * i], mv[4 * i + 1], mv[4 * i + 2], mv[4 * i + 3]);
    }
    bar_arrive(1, 256); bar_arrive(2, 256); bar_arrive(9, 256);
    if (t2 == 0) SSTAMP(11, 8);
    mbar_wait(sb + MB_WO, 0);
    if (t2 == 0) SSTAMP(11, 4);
#pragma unroll
    for (int k = 0; k < 8; k++) ldsm4t(wo[k], wo_lane + SM_X + 2 * XT + k * 2048);
    fence_async();
    bar_sync(6, 128);
    if (t2 == 32) tma_load3(sb + SM_X + 2 * XT, &tm.x, 64, sb + MB_X + 16);
    __syncwarp();
#pragma unroll
    for (int k = 0; k < 8; k++)
#pragma unroll
      for (int i = 0; i < 4; i++) sq_acc(q[4 + i], wo[k][i]);
    float ss = 0.f;
#pragma unroll
    for (int i = 0; i < 8; i++) ss += bf_lo(q[i]) + bf_hi(q[i]);
    ss = warp_sum(ss);
    if (lane == 0) sts32(sb + SC_SS + 4 * (8 + w), __float_as_uint(ss));
    if (t2 == 0) SSTAMP(11, 9);
    bar_sync(11, 384);
    if (t2 == 0) SSTAMP(11, 10);
    if (t2 == 0) {
      float a[16];
#pragma unroll
      for (int i = 0; i < 4; i++) lds128f(sb + SC_SS + 16 * i, &a[4 * i]);
      stg_relaxed(&g_stats[blockIdx.x * 2], __float_as_uint(((a[0] + a[1]) + (a[2] + a[3])) + ((a[4] + a[5]) + (a[6] + a[7]))),
                  __float_as_uint((a[8] + a[9]) + (a[10] + a[11])),
                  max(max(__float_as_uint(a[12]), __float_as_uint(a[13])), max(__float_as_uint(a[14]), __float_as_uint(a[15]))), tag);
    }
    __syncwarp();
    WSTAMP(24);
    MSTAMP(4);
    cluster_wait();
    if (w == 0) {
      uint4 v[3];
      int n = 0;
      while (true) {
#pragma unroll
        for (int i = 0; i < 3; i++) v[i] = ldg_relaxed(&g_stats[(i * 32 + lane) * 2]);
        if (__all_sync(0xffffffffu, v[0].w == tag && v[1].w == tag && v[2].w == tag) || ++n > SPIN_LIMIT) break;
        __nanosleep(100);
      }
      WSTAMP(25);
      MSTAMP(5);
      const float sv = warp_sum(__uint_as_float(v[0].x) + __uint_as_float(v[1].x) + __uint_as_float(v[2].x));
      const float so = warp_sum(__uint_as_float(v[0].y) + __uint_as_float(v[1].y) + __uint_as_float(v[2].y));
      const int expW = ((int)(__float_as_uint(sv) >> 23) + (int)(__float_as_uint(so) >> 23) - 254 + 2 + 10 + 1) >> 1;
      sts32(sb + SC_XMAX + 4 * lane, v[0].z); sts32(sb + SC_XMAX + 128 + 4 * lane, v[1].z);
      sts32(sb + SC_EXPW, expW + 1 - 15);
      if (blockIdx.x == 0 && lane == 0) *(volatile unsigned*)&g_epoch = tag;
      sts32(sb + SC_FPAR + 4, 1);
    } else if (w < 3) {
      const uint32_t u = blockIdx.x >> 4;
      unsigned char* const z = g_red + 98304 + (blockIdx.x & 15) * 128 + (u & 1) * 2048 + (u & 6) * 4096 + (((u >> 1) ^ w) & 1) * 4096 + lane * 4;
      stg_relaxed32(z, 0);
      uint32_t best = 0xffffffffu;
#pragma unroll 1
      for (int i = 0; i < 64; i++) {
        uint32_t last, dt;
        asm volatile("{\n.reg .pred p;\n.reg .u32 c, v;\nld.volatile.shared.u32 %0, [%3];\nmov.u32 c, %%clock;\n"
                     "atom.relaxed.gpu.global.exch.b32 v, [%2], 0;\nsetp.eq.u32 p, v, 0;\nmov.u32 %1, 0;\n@p mov.u32 %1, %%clock;\nsub.u32 %1, %1, c;\n}"
                     : "=r"(last), "=r"(dt) : "l"(z), "r"(sb + SC_FPAR + 4) : "memory");
        best = min(best, dt);
        if ((last || PFIX) && i >= NPROBE - 1) break;
      }
      sts32(sb + SC_LAT + (w - 1) * 4, best);
    }
    bar_sync(13, 384);
    bar_arrive(0, 384);
    WSTAMP(26);
    TSTAMP(1);
    MSTAMP(6);
  }

  const uint32_t nh = __shfl_sync(0xffffffffu, near_half(sb), 0);
  uint32_t l16 = sb + lane * 16;
  PIN(l16);
#define LV ((l16 >> 4) & 31)
#define fence_reg l16
  const uint32_t red_lo = (uint32_t)(uint64_t)g_red, red_hi = (uint32_t)((uint64_t)g_red >> 32);
  uint32_t lp;
  auto slot = [&](int s, uint32_t c, uint32_t ofs) {
    const uint32_t lo = lp | (red_lo + ((w >> 1) * 4 + (w & 1) * 2 + ((w ^ c) & 1)) * 4096 + RED_SLOT(s) + ofs);
    uint64_t a; asm("mov.b64 %0, {%1, %2};" : "=l"(a) : "r"(lo), "r"(red_hi));
    return (unsigned char*)a;
  };
  const uint32_t always = __shfl_sync(0xffffffffu, lds32(sb + SC_DEAD + 12), 0);
  const int mode0 = RANK < 2 ? w : w | 4;
  auto hint_addr = [&](int s) { return min(LV, 23u) * 4 + (red_lo + HINT_OFF + nh * 4096 + w * 16384 + RED_SLOT(s)); };
  auto load_hints = [&](uint32_t lo) {
    uint64_t a; asm("mov.b64 %0, {%1, %2};" : "=l"(a) : "r"(lo), "r"(red_hi));
    return ldg_relaxed32((const void*)a);
  };
  const uint32_t blk = RANK < 2 ? 9216 : SEGB;
  auto send_v = [&](int seg, int pos) {
    if (RANK == 2 && ((w == 0 && VS0 == pos) || (w == 1 && VS1 == pos)) && seg > 1 && seg < NSEG && !(XP & 2)) {
      if (elect_one()) {
        fence_async();
        bulk_s2s(mapa(sb + SM_VC + (seg & 1) * 8192, w), sb + SM_BLK + (seg & 3) * SEGB, 8192, mapa(sb + MB_VX + (seg & 1) * 8, w));
      }
      __syncwarp();
    }
  };
  int s = 0;
  uint32_t dl = __shfl_sync(0xffffffffu, gtime() - 768, 0);
  uint32_t vx[4][4];
  auto load_vx = [&](int s) {
    const uint32_t va = l16 + (RANK < 2 ? SM_VC + (s & 1) * 8192 : SM_BLK + (s & 3) * SEGB) + w * 1024 + ((LV >> 3) & 1) * 384 - (LV >> 4) * 128;
#pragma unroll
    for (int i = 0; i < 4; i++) ldsm4(vx[i], va + (i & 1) * 4096 + (i >> 1) * 256);
  };
  if (VE) load_vx(0);
  bool bad = false;
#pragma unroll 1
  while (true) {
    const uint32_t par = s & 1;
    uint32_t oc[4], hints;
    if (HP == 2) { hints = hint_addr(s); PIN(hints); }
    auto retire = [&](uint32_t x) {
      asm volatile("{\n.reg .pred p;\nsetp.eq.u32 p, %0, 0;\n@p exit;\n}" :: "r"(vx[0][0] | vx[1][0] | vx[2][0] | vx[3][0] | x | ((WL & 4) ? oc[0] : 0)) : "memory");
    };
    auto scores = [&](auto memkeys, auto first, float* sc) {
      constexpr bool MK = decltype(memkeys)::value, FIRST = decltype(first)::value;
      uint32_t kb[4][4], qb[2][4];
      const uint32_t m = LV >> 3;
      uint32_t kaddr = l16 + SM_BLK + 4096 + (s & 3) * SEGB + w * 2048 + (m & 1) * (MK ? 128 : 896) - (m >> 1) * 128;
      if (MK) { PIN(kaddr); }
      else {
#pragma unroll
        for (int k = 0; k < 4; k++) ldsm4t(kb[k], kaddr + k * 256);
      }
      if (FIRST) { if (!VE) load_vx(s); if (WL & 4) lds128(sb + SC_ONES, oc); retire(MK ? kaddr : kb[0][0] | kb[1][0] | kb[2][0] | kb[3][0] | l16); bar_sync(4, 256); RSTAMP(4); PROF(4); }
      ldsm4t(qb[0], l16 + SM_QM);
      if (MK) ldsm4t(kb[0], kaddr);
      ldsm4t(qb[1], l16 + SM_QM + 512);
      if (MK) ldsm4t(kb[2], kaddr + 512);
      float c[4][4];
      mma16816z(c[0], kb[0], qb[0][0], qb[0][1]); mma16816z(c[1], kb[MK ? 0 : 1], qb[0][2], qb[0][3]);
      mma16816z(c[2], kb[2], qb[1][0], qb[1][1]); mma16816z(c[3], kb[MK ? 2 : 3], qb[1][2], qb[1][3]);
      if (FIRST && B5POS == 0) bar_arrive(5, N5);
#pragma unroll
      for (int i = 0; i < (MK ? 2 : 4); i++) sc[i] = ((c[0][i] + c[1][MK ? i + 2 : i]) + c[2][i]) + c[3][MK ? i + 2 : i];
    };
    auto send = [&](auto memkeys) {
      constexpr bool MK = decltype(memkeys)::value;
      constexpr int N = MK ? 1 : 2;
      const uint32_t sa = sb + LV * 4 + SM_E + (MK ? 1024 + RANK * 128 : RANK * 512 + w * 256);
      uint32_t ra[N][2], mb[N][2];
#pragma unroll
      for (int i = 0; i < N; i++)
#pragma unroll
        for (int j = 0; j < 2; j++) {
          ra[i][j] = mapa(sa + i * 128, j ? 2 : RANK ^ 1); mb[i][j] = mapa(sb + MB_S, j ? 2 : RANK ^ 1);
          PIN(ra[i][j]);
        }
      float sc[4];
      scores(memkeys, BoolC<true>(), sc);
      uint32_t e[N];
#pragma unroll
      for (int i = 0; i < N; i++) {
        e[i] = pack_bf16(ex2(sc[2 * i]), ex2(sc[2 * i + 1]));
        if (!(fmaxf(fabsf(sc[2 * i]), fabsf(sc[2 * i + 1])) <= E_LIM)) e[i] = 0x7fff7fffu;
        st_async1(ra[i][0], e[i], mb[i][0]);
        st_async1(ra[i][1], e[i], mb[i][1]);
      }
#pragma unroll
      for (int i = 0; i < N; i++) sts32(sa + i * 128, e[i]);
      __syncwarp();
      if (l16 == sb) mbar_arrive(sb + MB_S);
      PROF(5);
    };
    const int mode = bad ? 8 : mode0;
    if (mode < 2) {
      send(BoolC<false>());
    } else if (mode == 2) {
      send(BoolC<true>());
    } else if (mode == 8) {
      load_vx(s);
      if (WL & 4) lds128(sb + SC_ONES, oc);
      retire(l16);
      const uint32_t fp = lds32(sb + SC_FPAR);
      bar_sync(6, 128);
      if (w == 0 && l16 == sb) { sts32(sb + SC_FPAR, fp ^ 1); mbar_expect(sb + MB_F, 3072); }
      if (RANK < 2 && w < 3) {
        float sc[4] = {0.f, 0.f, 0.f, 0.f};
        if (w < 2) scores(BoolC<false>(), BoolC<false>(), sc); else scores(BoolC<true>(), BoolC<false>(), sc);
#pragma unroll 1
        for (int r = 0; r < 3; r++)
          st_async4(mapa(l16 + SM_FB + RANK * 1536 + w * 512, r), __float_as_uint(sc[0]), __float_as_uint(sc[1]), __float_as_uint(sc[2]), __float_as_uint(sc[3]), mapa(sb + MB_F, r));
      }
      mbar_wait(sb + MB_F, fp);
      float a[12];
#pragma unroll
      for (int j = 0; j < 3; j++) {
        float b[4];
        lds128f(l16 + SM_FB + j * 512, a + 4 * j); lds128f(l16 + SM_FB + 1536 + j * 512, b);
#pragma unroll
        for (int i = 0; i < 4; i++) a[4 * j + i] += b[i];
      }
      float m0 = fmaxf(fmaxf(fmaxf(a[0], a[2]), fmaxf(a[4], a[6])), a[8]), m1 = fmaxf(fmaxf(fmaxf(a[1], a[3]), fmaxf(a[5], a[7])), a[9]);
#pragma unroll
      for (int o = 4; o < 32; o <<= 1) { m0 = fmaxf(m0, __shfl_xor_sync(0xffffffffu, m0, o)); m1 = fmaxf(m1, __shfl_xor_sync(0xffffffffu, m1, o)); }
#pragma unroll
      for (int i = 0; i < 5; i++) {
        const uint32_t ea = sb + SM_E + LV * 4 + (i < 4 ? i * 128 : 1024);
        sts32(ea, pack_bf16(ex2(a[2 * i] - m0), ex2(a[2 * i + 1] - m1)));
        sts32(ea + (i < 4 ? 512 : 128), 0x3f803f80u);
      }
      __syncwarp();
    } else {
      if (!VE) load_vx(s);
      if (WL & 4) lds128(sb + SC_ONES, oc);
      if (EXM && mode == 3) bar_arrive(4, 256);
      retire(l16 + 1);
      if (VS0 == 2 || VS1 == 2) send_v(s + 1, 2);
      if (w == 3) {
        uint32_t used = ldg_relaxed32(&g_used[blockIdx.x / 3 * 32]);
        if (!(XP & 4) && elect_one()) {
          if (s > 0) seg_publish(s - 1);
          fence_async();
          seg_store(s, sb, 0, 8192);
        }
        __syncwarp();
        if (!EXM) {
          bar_sync(RANK < 2 ? 4 : 15, RANK < 2 ? 256 : 160);
          if (!(XP & 4) && elect_one()) { fence_async(); seg_store(s, sb, 8192, blk - 8192); }
          __syncwarp();
        }
        const uint32_t need = lds32(sb + SC_EPOCH) + (s >= NRING - 1 ? s : -4 * NSEG);
#pragma unroll 1
        for (int n = 0; (int)(used - need) < 0 && n < ((XP & 64) ? 1 : SPIN_LIMIT); n++) used = ldg_relaxed32(&g_used[blockIdx.x / 3 * 32]);
      }
    }
    {
      uint32_t wa[4], wb[4];
      constexpr int WS = 2048;
      const uint32_t w3a = l16 + SM_WO3 + w * 512;
      if (HP == 1) { hints = hint_addr(s); PIN(hints); }
      if (!(WL & 1)) { lds128(w3a + KP(0) * WS, wa); lds128(w3a + KP(1) * WS, wb); }
      if (WL & 2) {
#pragma unroll
        for (int i = 0; i < 4; i++) oc[i] = always | (always >> 16) | (always & (i + 1));
      } else if (!(WL & 4)) lds128(sb + SC_ONES, oc);
      if (B5POS == 1 && mode < 3) bar_arrive(5, N5);
      uint32_t e[10], p[5], vm[4], ob[4];
      float o0[4], o1[4], f[3][2][4], rs[4];
      if (!(RV & 1)) { reserve2(vm); reserve2(vm + 2); }
      if (!(RV & 2)) reserve2(e + 8);
      if (!HP) { hints = hint_addr(s); PIN(hints); }
      if (CLR & 2) asm volatile("{\n.reg .pred p;\nsetp.eq.u32 p, %0, 0;\n@p exit;\n}" :: "r"(wa[0] | wb[0] | oc[0] | hints) : "memory");
      if (RV & 4) mbar_wait_fast(sb + MB_S, par); else mbar_wait(sb + MB_S, par);
      RSTAMP(5);
      PROF(6);
      if (RV & 2) { ldsm4t(e, l16 + SM_E); ldsm4t(e + 4, l16 + SM_E + 512); ldsm2t(e + 8, l16 + SM_E + 1024); }
      else { ldsm4t(e, l16 + SM_E); ldsm2t_in(e + 8, l16 + SM_E + 1024, always); ldsm4t(e + 4, l16 + SM_E + 512); }
      if (RV & 1) lds128(l16 + w * 512 + SM_VM, vm); else lds128_in(vm, l16 + w * 512 + SM_VM, always);
      const float scl = __uint_as_float(lds32(sb + SC_UNSC + 8 - par * 8));
      if (HL == 0) hints = load_hints(hints);
      if (GF & 1) SCHED_FENCE(4);
#pragma unroll
      for (int i = 0; i < 4; i++) p[i] = mul_bf16(e[i], e[4 + i]);
      p[4] = mul_bf16(e[8], e[9]);
      if (HL) hints = load_hints(hints | (p[HL - 1] & always & 1));
      mma16816z(o0, vx[0], p[0], p[1]);
      if (WL & 1) { lds128_in(vx[0], w3a + KP(0) * WS, always); }
      mma16816z(o1, vx[1], p[0], p[1]);
      if (WL & 1) { lds128_in(vx[1], w3a + KP(1) * WS, always); }
      if (PV2) {
        float u0[4], u1[4];
        mma16816z(u0, vx[2], p[2], p[3]); lds128_in(vx[2], w3a + KP(2) * WS, always);
        mma16816z(u1, vx[3], p[2], p[3]); lds128_in(vx[3], w3a + KP(3) * WS, always);
        mma16816z(rs, oc, p[0], p[1]);
        mma1688(o0, vm[0], vm[1], p[4]); mma1688(o1, vm[2], vm[3], p[4]);
        mma16816(rs, oc, p[2], p[3]);
#pragma unroll
        for (int i = 0; i < 4; i++) { o0[i] += u0[i]; o1[i] += u1[i]; }
        if (PV2 == 1) mma1688(rs, oc[0], oc[1], p[4]);
      } else {
      mma16816z(rs, oc, p[0], p[1]);
      mma16816(o0, vx[2], p[2], p[3]); lds128_in(vx[2], w3a + KP(2) * WS, always);
      mma16816(o1, vx[3], p[2], p[3]); lds128_in(vx[3], w3a + KP(3) * WS, always);
      mma16816(rs, oc, p[2], p[3]);
      mma1688(o0, vm[0], vm[1], p[4]); mma1688(o1, vm[2], vm[3], p[4]); mma1688(rs, oc[0], oc[1], p[4]);
      }
      stsm4(l16 + w * 512 + SM_OB, pack_bf16(o0[0], o0[1]), pack_bf16(o0[2], o0[3]), pack_bf16(o1[0], o1[1]), pack_bf16(o1[2], o1[3]));
      if (PV2 == 2) mma1688(rs, oc[0], oc[1], p[4]);
      bar_sync(6, 128);
      RSTAMP(3);
      PROF(7);
      ldsm4t_in(oc, l16 + SM_OB, always);
      bad = __any_sync(0xffffffffu, !(rs[0] + rs[1] > 0.f) && !bad);
      rs[0] *= scl; rs[1] *= scl;
      asm volatile("{\n.reg .pred p;\nsetp.ne.u32 p, %1, 0;\n@p rcp.approx.ftz.f32 %0, %0;\n}" : "+f"(rs[0]) : "r"(always));
      asm volatile("{\n.reg .pred p;\nsetp.ne.u32 p, %1, 1;\n@p rcp.approx.ftz.f32 %0, %0;\n}" : "+f"(rs[1]) : "r"(always));
      asm volatile("lop3.b32 %0, %1, %2, %3, 0xfe;" : "=r"(lp) : "r"((l16 & 128) * 2), "r"((l16 & 256) * 4), "r"(l16 & 112));
      if (bad) continue;
      ldsm4t(ob, l16 + SM_OB + 512);
      mma16816z(f[2][0], WL & 1 ? vx[0] : wa, oc[0], oc[1]); mma16816z(f[2][1], WL & 1 ? vx[1] : wb, oc[2], oc[3]);
      mma16816z(f[0][0], wo[0], oc[0], oc[1]); mma16816z(f[0][1], wo[4], oc[2], oc[3]);
      mma16816z(f[1][0], w1[0], oc[0], oc[1]); mma16816z(f[1][1], w1[4], oc[2], oc[3]);
      ldsm4t_in(oc, l16 + SM_OB + 1024, always);
      mma16816(f[2][0], vx[2], ob[0], ob[1]); lds128_in(vx[2], w3a + KP(4) * WS, always);
      mma16816(f[2][1], vx[3], ob[2], ob[3]); lds128_in(vx[3], w3a + KP(5) * WS, always);
      mma16816(f[0][0], wo[1], ob[0], ob[1]); mma16816(f[0][1], wo[5], ob[2], ob[3]);
      mma16816(f[1][0], w1[1], ob[0], ob[1]); mma16816(f[1][1], w1[5], ob[2], ob[3]);
      ldsm4t_in(ob, l16 + SM_OB + 1536, always);
      mma16816(f[0][0], wo[2], oc[0], oc[1]); mma16816(f[0][1], wo[6], oc[2], oc[3]);
      mma16816(f[2][0], vx[2], oc[0], oc[1]); lds128_in(vx[2], w3a + KP(6) * WS, always);
      mma16816(f[2][1], vx[3], oc[2], oc[3]); lds128_in(vx[3], w3a + KP(7) * WS, always);
      mma16816(f[1][0], w1[2], oc[0], oc[1]); mma16816(f[1][1], w1[6], oc[2], oc[3]);
      mma16816(f[0][0], wo[3], ob[0], ob[1]); mma16816(f[0][1], wo[7], ob[2], ob[3]);
      mma16816(f[1][0], w1[3], ob[0], ob[1]); mma16816(f[1][1], w1[7], ob[2], ob[3]);
      mma16816(f[2][0], vx[2], ob[0], ob[1]); mma16816(f[2][1], vx[3], ob[2], ob[3]);
      bar_arrive(7, NII < 18 ? 384 : 256);
      lds128_in(ob, sb + SC_DEAD, always);
      uint32_t h[3][2];
#pragma unroll
      for (int j = 0; j < 3; j++)
#pragma unroll
        for (int i = 0; i < 2; i++)
        {
          scale_sum(f[j][1][2 * i], f[j][0][2 * i], rs[0], always); scale_sum(f[j][1][2 * i + 1], f[j][0][2 * i + 1], rs[1], always);
          h[j][i] = pack_f16(f[j][1][2 * i], f[j][1][2 * i + 1]);
        }
      const uint32_t rofs = RANK * 32768;
      red_f16x8(slot(s, RANK >> 1, rofs), h[0][0], h[1][0], h[2][0], 0x3c00u);
      red_f16x8(slot(s, (RANK >> 1) ^ 1, rofs), h[0][1], h[1][1], h[2][1], 0x3c00u);
      if (NII == 18) bar_arrive(10, 256);
      SCHED_FENCE(5);
      RSTAMP(0);
      l16 += ob[B7R];
    }
    {
    PROF(8);
    if (VS0 == 3 || VS1 == 3) send_v(s + 1, 3);
    const uint32_t ma0 = l16 + SM_MEM + w * 128 + (LV >> 3) * 896 + nh * 512;
    const unsigned char* const sl[2] = {slot(s, nh, 0), slot(s, nh ^ 1, 0)};
    uint32_t late = latest_hint(hints, dl, s);
    if (late >= 64) {
      int n = 0;
#pragma unroll 1
      do {
        late = latest_hint(load_hints(hint_addr(s)), dl, s);
      } while (late >= 64 && ++n < SPIN_LIMIT);
    }
    dl += late * 32 + tm.poll;
    if (s == 0 && PSTAMP) MSTAMP(7);
    PROF(9);
    {
      auto wait_until = [&](uint32_t t) {
        asm volatile("{\n.reg .pred p;\n.reg .s32 c;\n.reg .u64 t;\nTL: mov.u64 t, %%globaltimer;\ncvt.u32.u64 c, t;\nsub.s32 c, c, %0;\nsetp.lt.s32 p, c, 0;\n@p bra.uni TL;\n}" :: "r"(t + (l16 & 15)) : "memory");
      };
      uint4 v[2][3];
      auto load = [&](int c) {
#pragma unroll
        for (int r = 0; r < 3; r++) v[c][r] = ldg_relaxed(sl[c ^ (r >> 1)] + r * 32768);
      };
      auto decode = [&](int c, int n) {
        uint32_t q[9];
        __half2 hm;
        const uint32_t ma = ma0 ^ (c * 512);
#pragma unroll
        for (int i = 0; i < 9; i++) {
          const uint32_t h = i % 3 == 0 ? v[c][i / 3].x : (i % 3 == 1 ? v[c][i / 3].y : v[c][i / 3].z);
          const float2 f = __half22float2(*(const __half2*)&h);
          q[i] = pack_bf16(f.x, f.y);
          hm = i ? __hmax2(hm, __habs2(*(const __half2*)&h)) : __habs2(*(const __half2*)&h);
        }
#pragma unroll
        for (int r = 0; r < 3; r++) stsm4(ma + r * 4096, q[3 * r], q[3 * r + 1], q[3 * r + 2], r < 2 ? v[c][r].w : *(const uint32_t*)&hm);
        const bool done = __all_sync(0xffffffffu, v[c][0].w == 0x5000u && v[c][1].w == 0x5000u && v[c][2].w == 0x5000u) || n > SPIN_LIMIT;
        asm volatile("{\n.reg .pred p;\nsetp.ne.u32 p, %0, 0;\n@p bar.arrive %1, 256;\n}" :: "r"((int)done), "r"(1 + c) : "memory");
        return done;
      };
      if (LEAD) { wait_until(dl - LEAD); load(1); }
      wait_until(dl);
      PROF(10);
      int n = 0;
#pragma unroll 1
      do {
        load(0);
        if (!LEAD) load(1);
        asm volatile("{\n.reg .pred p;\nsetp.eq.u32 p, %0, 0;\n@p bar.sync 13, 384;\n}" :: "r"(n) : "memory");
      } while (!decode(0, n++));
      if (VE) load_vx(s + 1);
      PROF(11);
      RSTAMP(1);
#pragma unroll 1
      while (!decode(1, n++)) load(1);
      bar_arrive(9, 256);
      RSTAMP(2);
      PROF(12);
    }
    PROF(13);
    if (++s == NSEG - 1) break;
    }
  }
#undef fence_reg
  if (RANK < 2) bar_arrive(4, 256);
  TSTAMP(49);
  {
    PIN(l16);
    tail_attention(sb, RANK, w, LV, 0, 6);
    TSTAMP(51);
    mbar_wait(sb + MB_WO, 1);
    TSTAMP(53);
#pragma unroll 1
    for (int sg = 0; sg < 2; sg++) {
      PIN(l16);
      const int lane = LV, m = lane >> 3, g = lane >> 2, t = lane & 3;
      const uint32_t ob = l16 + T_OB + sg * 8192;
      bar_sync(sg ? 0 : 8, 256);
      TSTAMP(54 + 2 * sg);
      const float inv = __uint_as_float(0x7f000000u - lds32(sb + T_UN + sg * 4));
#pragma unroll 1
      for (int j = 0; j < 4; j += 2) {
        float c[2][3][4];
        uint32_t x[4], y[4], z[2][4];
#pragma unroll
        for (int e = 0; e < 2; e++) {
          const uint32_t oa = sb + T_OA + ((sg * 4 + j + e) * 8 + g) * 64 + (blockIdx.x / 3 * 36 & 15) + t * 4;
          z[e][0] = lds32(oa); z[e][1] = lds32(oa + 16); z[e][2] = t ? 0u : lds32(oa + 32);
        }
#pragma unroll
        for (int i = 0; i < 3; i++) {
          const uint32_t wa = sb + T_WA + ((lane & 7) + ((lane >> 4) << 3)) * 128 + (((w + 4 * (m & 1)) ^ (lane & 7)) << 4);
          ldsm4t(x, wa + i * 3072); ldsm2t(y, wa + i * 3072 + 2048);
#pragma unroll
          for (int e = 0; e < 2; e++) { mma1688z(c[e][i], y[0], y[1], z[e][2]); mma16816(c[e][i], x, z[e][0], z[e][1]); }
        }
#pragma unroll
        for (int r = 0; r < 4; r++) {
          ldsm4t(z[0], ob + j * 2048 + r * 512); ldsm4t(z[1], ob + j * 2048 + 2048 + r * 512);
          lds128(l16 + SM_WO3 + w * 512 + r * 2048, x); lds128(l16 + SM_WO3 + w * 512 + (r + 4) * 2048, y);
#pragma unroll
          for (int e = 0; e < 2; e++) { mma16816(c[e][0], wo[r], z[e][0], z[e][1]); mma16816(c[e][1], w1[r], z[e][0], z[e][1]); mma16816(c[e][2], x, z[e][0], z[e][1]); }
#pragma unroll
          for (int e = 0; e < 2; e++) { mma16816(c[e][0], wo[r + 4], z[e][2], z[e][3]); mma16816(c[e][1], w1[r + 4], z[e][2], z[e][3]); mma16816(c[e][2], y, z[e][2], z[e][3]); }
        }
#pragma unroll
        for (int i = 0; i < 4; i++) {
          const float (&d)[3][4] = c[i >> 1];
          const int q = (i & 1) * 2;
          red_f16x8(g_red + T_RED + ((((sg * 4 + j + (i >> 1)) * 3 + RANK) * 4 + w) * 2 + (i & 1)) * 512 + lane * 16, pack_f16(d[0][q] * inv, d[0][q + 1] * inv),
                    pack_f16(d[1][q] * inv, d[1][q + 1] * inv), pack_f16(d[2][q] * inv, d[2][q + 1] * inv), 0x3c00u);
        }
      }
      TSTAMP(55 + 2 * sg);
    }
    if (RSLOW) { wait_until(gtime() + 8000); wait_until(gtime() + 8000); wait_until(gtime() + 4000); }
    if (w < 2) {
      const int b = blockIdx.x, lane = LV, g = lane >> 2, t = lane & 3;
      uint4 v;
#pragma unroll 1
      for (int n = 0; n < SPIN_LIMIT; n++) {
        v = ldg_relaxed(g_red + T_RED + (w * 96 + b) * 512 + lane * 16);
        if (__all_sync(0xffffffffu, v.w == 0x5000u)) break;
        __nanosleep(40);
      }
      const float un = __uint_as_float(lds32(sb + T_UN + w * 4));
      uint32_t* const o = (uint32_t*)(tm.out + (size_t)((NAUXSEG + w) * 32 + b / 24 * 8 + g) * DM + (b >> 3) % 3 * 192 + (b & 1) * 32 + (b & 6) * 4) + t;
#pragma unroll
      for (int j = 0; j < 3; j++) {
        const float2 f = __half22float2(*(const __half2*)(&v.x + j));
        o[j * 32] = movm(pack_bf16(f.x * un, f.y * un));
      }
    }
  }
  TSTAMP(3);
  MSTAMP(8);
  if (CSY) cluster_sync();
}

__global__ void __cluster_dims__(3, 1, 1) __launch_bounds__(384, 1)
rec_kernel(const __grid_constant__ RMaps tm, const bf16* __restrict__ x, const bf16* __restrict__ mem0) {
  extern __shared__ __align__(1024) unsigned char smem_raw[];
  const uint32_t sb = smem_u32(smem_raw);
  const int tid = threadIdx.x, lane = tid & 31;
  const int wg = __shfl_sync(0xffffffffu, tid >> 7, 0);
  const int w = __shfl_sync(0xffffffffu, (tid >> 5) & 3, 0);
  uint32_t rank; asm("mov.u32 %0, %%cluster_ctarank;" : "=r"(rank));
  STAMP(0);
  TSTAMP(0);
  asm volatile("griddepcontrol.launch_dependents;" ::: "memory");

#define PFT 1
  if (PFT && wg == 1 && lane == 0) asm volatile("prefetch.tensormap [%0];\nprefetch.tensormap [%1];" :: "l"(w & 1 ? &tm.woa : &tm.oa), "l"(w == 0 ? (rank < 2 ? &tm.wk : &tm.wv) : w == 1 ? &tm.wq : w == 2 ? &tm.x : &tm.wo) : "memory");
  if (wg < 2) {
    asm volatile("setmaxnreg.inc.sync.aligned.u32 192;");
    if (tid == 0) {
      for (int i = 0; i < 3; i++) { mbar_init(sb + MB_W + 8 * i, 1); mbar_init(sb + MB_X + 8 * i, 1); }
      mbar_init(sb + MB_WO, 1); mbar_init(sb + MB_WO3, 1);
      mbar_init(sb + MB_S, rank < 2 ? 5 : 6);
      mbar_init(sb + MB_F, 1);
      for (int i = 0; i < 3; i++) mbar_init(sb + MB_T + 8 * i, 1);
      mbar_init(sb + MB_VX, 1); mbar_init(sb + MB_VX + 8, 1);
      asm volatile("fence.mbarrier_init.release.cluster;" ::: "memory");
      fence_async();
      SSTAMP(11, 6);
      load_weights(sb, tm, rank, 0);
      for (int i = 0; i < 3; i++) mbar_expect(sb + MB_X + 8 * i, XT);
      tma_load3(sb + SM_X, &tm.x, 0, sb + MB_X);
      if (!PACE) for (int c = 1; c < 4; c++) load_weights(sb, tm, rank, c);
      mbar_expect(sb + MB_S, rank < 2 ? 640 + 2048 : 1280);
      mbar_expect(sb + MB_VX, 8192); mbar_expect(sb + MB_VX + 8, 8192);
      mbar_expect(sb + MB_T, 2048);
      for (int i = 1; i < 3; i++) mbar_expect(sb + MB_T + 8 * i, rank < 2 ? 5120 : 10240);
      SSTAMP(11, 5);
    }
    __syncwarp();
    bar_sync(0, 384);
    proj_role(sb, tm, rank, wg, w, lane);
  } else {
    asm volatile("setmaxnreg.dec.sync.aligned.u32 120;");
    attn_role(sb, smem_raw, tm, rank, x, mem0, w, lane);
  }
}

constexpr int A_XH = 73728;
constexpr int A_NS = 9, A_WM = 6144, A_WT = 768;
constexpr int A_RING = 2 * A_XH, A_TAIL = A_RING + A_NS * A_WM, A_GW = A_TAIL + A_NS * A_WT;
constexpr int A_EPI = 212864, A_EPW = 9344;
constexpr int A_XW = 4 * XT, A_XT = A_XW + 4096, A_NR = 4;
constexpr int A_IN = A_XT + 2048, A_INS = 2 * 9216 + SEGB, A_OST = A_IN + 2 * A_INS;
constexpr int A_GATE = A_EPI + 2 * A_EPW, A_BAR = A_GATE + 512;
constexpr int A_TOTAL = A_BAR + 384;
struct AMaps { CUtensorMap x, wa, wt, oa, o, o3, o8, wob, woa, wo8; };

DI void wgmma_n192_ss_nt(float* d, uint64_t da, uint64_t db, int acc) {
  asm volatile("{\n.reg .pred p;\nsetp.ne.b32 p, %98, 0;\n"
               "wgmma.mma_async.sync.aligned.m64n192k16.f32.bf16.bf16 {"
               "%0,%1,%2,%3,%4,%5,%6,%7,%8,%9,%10,%11,%12,%13,%14,%15,%16,%17,%18,%19,%20,%21,%22,%23,%24,%25,%26,%27,%28,%29,%30,%31,"
               "%32,%33,%34,%35,%36,%37,%38,%39,%40,%41,%42,%43,%44,%45,%46,%47,%48,%49,%50,%51,%52,%53,%54,%55,%56,%57,%58,%59,%60,%61,%62,%63,"
               "%64,%65,%66,%67,%68,%69,%70,%71,%72,%73,%74,%75,%76,%77,%78,%79,%80,%81,%82,%83,%84,%85,%86,%87,%88,%89,%90,%91,%92,%93,%94,%95"
               "}, %96, %97, p, 1, 1, 0, 1;\n}\n"
               : ACC8(d, 0), ACC8(d, 8), ACC8(d, 16), ACC8(d, 24), ACC8(d, 32), ACC8(d, 40), ACC8(d, 48), ACC8(d, 56),
                 ACC8(d, 64), ACC8(d, 72), ACC8(d, 80), ACC8(d, 88) : "l"(da), "l"(db), "r"(acc));
}
#define ACC4(d, o) "+f"(d[o]), "+f"(d[o + 1]), "+f"(d[o + 2]), "+f"(d[o + 3])
DI void wgmma_n24_ss_nt(float* d, uint64_t da, uint64_t db, int acc) {
  asm volatile("{\n.reg .pred p;\nsetp.ne.b32 p, %14, 0;\n"
               "wgmma.mma_async.sync.aligned.m64n24k16.f32.bf16.bf16 {%0,%1,%2,%3,%4,%5,%6,%7,%8,%9,%10,%11}, %12, %13, p, 1, 1, 0, 1;\n}\n"
               : ACC8(d, 0), ACC4(d, 8) : "l"(da), "l"(db), "r"(acc));
}
DI void wgmma_n8_ss(float* d, uint64_t da, uint64_t db, int acc) {
  asm volatile("{\n.reg .pred p;\nsetp.ne.b32 p, %6, 0;\n"
               "wgmma.mma_async.sync.aligned.m64n8k16.f32.bf16.bf16 {%0,%1,%2,%3}, %4, %5, p, 1, 1, 0, 0;\n}\n"
               : ACC4(d, 0) : "l"(da), "l"(db), "r"(acc));
}
DI void wgmma_n40_ss_tt(float* d, uint64_t da, uint64_t db, int acc) {
  asm volatile("{\n.reg .pred p;\nsetp.ne.b32 p, %22, 0;\n"
               "wgmma.mma_async.sync.aligned.m64n40k16.f32.bf16.bf16 {%0,%1,%2,%3,%4,%5,%6,%7,%8,%9,%10,%11,%12,%13,%14,%15,%16,%17,%18,%19}, "
               "%20, %21, p, 1, 1, 1, 1;\n}\n"
               : ACC8(d, 0), ACC8(d, 8), ACC4(d, 16) : "l"(da), "l"(db), "r"(acc));
}
DI void wgmma_n64_rs(float* d, const uint32_t* a, uint64_t db, int acc) {
  asm volatile("{\n.reg .pred p;\nsetp.ne.b32 p, %37, 0;\n"
               "wgmma.mma_async.sync.aligned.m64n64k16.f32.bf16.bf16 {"
               "%0,%1,%2,%3,%4,%5,%6,%7,%8,%9,%10,%11,%12,%13,%14,%15,%16,%17,%18,%19,%20,%21,%22,%23,%24,%25,%26,%27,%28,%29,%30,%31"
               "}, {%32,%33,%34,%35}, %36, p, 1, 1, 0;\n}\n"
               : ACC8(d, 0), ACC8(d, 8), ACC8(d, 16), ACC8(d, 24) : "r"(a[0]), "r"(a[1]), "r"(a[2]), "r"(a[3]), "l"(db), "r"(acc));
}
DI void wgmma_n32_ss_tn(float* d, uint64_t da, uint64_t db, int acc) {
  asm volatile("{\n.reg .pred p;\nsetp.ne.b32 p, %18, 0;\n"
               "wgmma.mma_async.sync.aligned.m64n32k16.f32.bf16.bf16 {%0,%1,%2,%3,%4,%5,%6,%7,%8,%9,%10,%11,%12,%13,%14,%15}, "
               "%16, %17, p, 1, 1, 1, 0;\n}\n"
               : ACC8(d, 0), ACC8(d, 8) : "l"(da), "l"(db), "r"(acc));
}
DI void tma_load3c(uint32_t dst, const CUtensorMap* m, int c0, int c1, int c2, uint32_t mb) {
  asm volatile("cp.async.bulk.tensor.3d.shared::cluster.global.mbarrier::complete_tx::bytes [%0], [%1, {%3, %4, %5}], [%2];"
               :: "r"(dst), "l"(m), "r"(mb), "r"(c0), "r"(c1), "r"(c2) : "memory");
}
DI void count_up(unsigned* p) {
  asm volatile("fence.proxy.async;" ::: "memory");
  asm volatile("red.release.gpu.global.add.u32 [%0], 1;" :: "l"(p) : "memory");
}
#define AX 0
#define FDLY 400
#define FEND 59
DI void publish(unsigned* p) {
  asm volatile("cp.async.bulk.wait_group 0;\nfence.proxy.async;" ::: "memory");
  asm volatile("red.relaxed.gpu.global.add.u32 [%0], 1;" :: "l"(p) : "memory");
}
#define PL 2
#define SER 35
#define DRAIN 0
#define PR 4
#define NQ 3
#define PUB 0
#define LA 1
#define LAG0 12
#define LEND 58
#define PDLY 0
#define ADLY 0

__global__ void __launch_bounds__(512, 1)
aux_kernel(const __grid_constant__ AMaps tm, const bf16* __restrict__ wqkv, const bf16* __restrict__ woa, const bf16* __restrict__ gate_w, bf16* __restrict__ out) {
  extern __shared__ __align__(1024) unsigned char smem_raw[];
  const uint32_t sb = smem_u32(smem_raw);
  const uint32_t fullx = sb + A_BAR, full1 = fullx + 24, empty1 = full1 + 8 * A_NS, fullw = empty1 + 8 * A_NS, full3 = fullw + 8, empty3 = full3 + 8 * A_NR,
                 fullq = empty3 + 8 * A_NR, emptyq = fullq + 24, fullo = emptyq + 24, emptyo = fullo + 16;
  const int tid = threadIdx.x, lane = tid & 31, cta = blockIdx.x;
  const int wg = __shfl_sync(0xffffffffu, tid >> 7, 0), w = __shfl_sync(0xffffffffu, (tid >> 5) & 3, 0);
  ASTAMP(14);
  if (tid == 384) {
    for (int i = 0; i < 3; i++) mbar_init(fullx + 8 * i, 1);
    for (int i = 0; i < A_NS; i++) { mbar_init(full1 + 8 * i, 1); mbar_init(empty1 + 8 * i, 8); }
    mbar_init(fullw, 1);
    for (int i = 0; i < 3; i++) { mbar_init(fullq + 8 * i, 1); mbar_init(emptyq + 8 * i, 4); }
    for (int i = 0; i < 2; i++) { mbar_init(fullo + 8 * i, 4); mbar_init(emptyo + 8 * i, 1); }
    for (int i = 0; i < A_NR; i++) { mbar_init(full3 + 8 * i, 1); mbar_init(empty3 + 8 * i, cta < NH ? 8 : 4); }
    fence_async();
  }
  __syncthreads();
  ASTAMP(0);
  const int tile = cta >> 1, hh = cta & 1;
  auto p3_n = [&](int g) { return cta < NH ? (cta & 3) * 2 + g : 8; };
  auto p3_next = [&](int& sl, int& ph) {
    sl += cta < NH ? 1 : 2;
    if (sl >= (cta < NH ? 6 - NQ : 4)) { sl -= cta < NH ? 6 - NQ : 4; ph ^= 1; }
  };
  auto p3_k = [&](int g) { return cta < NH ? cta >> 2 : (cta & 3) * 2 + g; };
  if (wg == 3) {
    asm volatile("setmaxnreg.dec.sync.aligned.u32 24;");
    const bool lead = lane == 0;
    if (w < 3) {
      if (ADLY) wait_until(gtime() + ADLY);
      if (elect_one()) {
        mbar_expect(fullx + 8 * w, 49152);
        for (int p = 0; p < 2; p++)
          asm volatile("cp.async.bulk.tensor.4d.shared::cluster.global.mbarrier::complete_tx::bytes [%0], [%1, {%3, %4, %5, %6}], [%2];"
                       :: "r"(sb + p * A_XH + w * 24576), "l"(&tm.x), "r"(fullx + 8 * w), "r"(0), "r"(p), "r"(57 * tile - 7), "r"(3 * w) : "memory");
      }
#pragma unroll 1
      for (int r = 0; r < 17; r++) {
#pragma unroll 1
        for (int st = w; st < A_NS; st += 3) {
          if (r > 0) mbar_wait(empty1 + 8 * st, ~r & 1);
          if (r < 16 && elect_one()) {
            const int col = hh * 288 + (r >> 2) * 72, row = (r & 3) * 144 + st * 16;
            mbar_expect(full1 + 8 * st, A_WM + (AX & 1 ? 0 : A_WT));
            tma_load3c(sb + A_RING + st * A_WM, &tm.wa, col, row, 0, full1 + 8 * st);
            if (!(AX & 1)) tma_load3c(sb + A_TAIL + st * A_WT, &tm.wt, col + 64, row, 0, full1 + 8 * st);
          }
          __syncwarp();
        }
        if (r == 0 && elect_one())
          for (int j = 0; j < 3; j++)
            asm volatile("cp.async.bulk.prefetch.L2.global [%0], %1;" :: "l"((const char*)wqkv + cta * 55296 + (w * 3 + j) * 6144), "r"(6144) : "memory");
        __syncwarp();
      }
      bar_sync(8, 96);
    }
    const unsigned epoch = lds32(sb + A_BAR + 376);
    if (w == 2 && cta < NH) {
      if (lead) {
        int avail = 0, q = 0, ph = 1;
#pragma unroll 1
        for (int seg = 0; seg < NAUXSEG; seg++) {
          const unsigned char* const src = g_seg + ((size_t)(AX & 128 ? 0 : seg % NRING) * 96 + cta * 3) * SEGB;
          SSTAMP(0, seg);
          const int ref = seg + max(LAG0 * (LEND - seg) / LEND, 0);
          if (ref >= avail) {
            const unsigned* const c = &g_scnt[(ref * 32 + cta) * 8];
            const int c2 = ldg_relaxed32(c + 512) - 3 * (epoch + 1), c0 = ldg_acquire32(c) - 3 * (epoch + 1);
            avail = ref + (c2 >= 0 && LA ? 3 : 1);
            if (c0 < 0) {
              wait_count(c, 3 * (epoch + 1), !(TL & 2) || seg < NAUXSEG - 2);
              if (FDLY && seg < FEND) wait_until(gtime() + FDLY);
            }
          }
          SSTAMP(1, seg);
          const uint32_t mb = fullq + q * 8;
          mbar_wait(emptyq + q * 8, q == 2 ? ph ^ 1 : ph);
          if (AX & 8) mbar_arrive(mb); else mbar_expect(mb, A_INS);
#pragma unroll 1
          for (int r = 0; r < ((AX & 8) ? 0 : 3); r++)
            asm volatile("cp.async.bulk.shared::cluster.global.mbarrier::complete_tx::bytes [%0], [%1], %2, [%3];"
                         :: "r"(sb + (q < 2 ? A_IN + q * A_INS : 3 * XT) + r * 9216), "l"(src + r * SEGB), "r"(r < 2 ? 9216 : SEGB), "r"(mb) : "memory");
          if (seg == 1) wait_count(&g_abar[32], NAUX * (epoch + 1));
          if (seg > 1) stg_relaxed32(&g_used[cta * 32], epoch * NSEG + seg + 1 - NQ);
          if (++q == NQ) { q = 0; ph ^= 1; }
        }
      }
      return;
    }
    if (w == 3) {
#pragma unroll 1
      for (int c = 0; c < 4; c++) {
        if (lead) asm volatile("cp.async.bulk.wait_group.read 0;" ::: "memory");
        __syncwarp();
        bar_arrive(11, 160); bar_arrive(12, 160);
#pragma unroll 1
        for (int g = 0; g < 2; g++) {
          bar_sync(13 + g, 160);
          if (lead) {
            asm volatile("cp.async.bulk.tensor.3d.global.shared::cta.bulk_group [%0, {%2, %3, %4}], [%1];"
                         :: "l"(&tm.oa), "r"(sb + A_EPI + g * A_EPW + 1024), "r"(4096 + hh * 288 + c * 72), "r"(g), "r"(57 * tile) : "memory");
            asm volatile("cp.async.bulk.commit_group;" ::: "memory");
          }
        }
      }
      if (lead) {
        asm volatile("cp.async.bulk.wait_group.read 0;" ::: "memory");
        mbar_arrive(emptyo); mbar_arrive(emptyo + 8);
        publish(&g_abar[32]);
      }
      __syncwarp();
    }
    if ((w & 1) && cta < NH) {
#pragma unroll 1
      for (int seg = w >> 1; seg < NAUXSEG; seg += 2) {
        if (lead) {
          mbar_wait(fullo + (w >> 1) * 8, (seg >> 1) & 1);
          fence_async();
          tma_store(&tm.o, sb + A_OST + (w >> 1) * 8192, cta * DH, seg * 32);
          tma_store(&tm.o, sb + A_OST + (w >> 1) * 8192 + 4096, cta * DH + 64, seg * 32);
          asm volatile("cp.async.bulk.commit_group;\ncp.async.bulk.wait_group.read 0;" ::: "memory");
          mbar_arrive(emptyo + (w >> 1) * 8);
          if (PUB == 0 || seg >= NAUXSEG - 2) publish(&g_ocnt[seg * 64 + 2 * cta / 9 * 8]);
          else {
            if (PUB == 1) asm volatile("fence.acq_rel.gpu;" ::: "memory"); else if (PUB > 2) wait_until(gtime() + PUB);
            asm volatile("red.relaxed.gpu.global.add.u32 [%0], 1;" :: "l"(&g_ocnt[seg * 64 + 2 * cta / 9 * 8]) : "memory");
          }
          if (2 * cta / 9 != (2 * cta + 1) / 9) asm volatile("red.relaxed.gpu.global.add.u32 [%0], 1;" :: "l"(&g_ocnt[seg * 64 + (2 * cta + 1) / 9 * 8]) : "memory");
          SSTAMP(9, seg);
        }
        __syncwarp();
      }
    }
    if (w & 1) return;
    if (w == 0) {
      if (lead) {
        mbar_expect(fullw, 18 * 8192 + 2048);
#pragma unroll 1
        for (int k = 0; k < 18; k++) {
          const int g = k / 9, kb = p3_k(g) * 9 + k - 9 * g;
          if (kb < 64) tma_load(sb + k * 8192, &tm.wob, p3_n(g) * 64, kb * 64, fullw);
          else tma_load(sb + k * 8192, &tm.woa, p3_n(g) * 64, (kb - 64) * 64, fullw);
        }
        for (int g = 0; g < 2; g++) tma_load(sb + A_XW + g * 2048, &tm.wo8, p3_n(g) * 64, 512 + p3_k(g) * 8, fullw);
      }
      __syncwarp();
    }
    bar_sync(6, cta >= NH ? 320 : 288);
    if (lead) {
      if (NQ == 3) for (int i = 0; i < 4; i++) mbar_arrive(emptyq + 16);
      wait_count(&g_abar[32], NAUX * (epoch + 1));
      int avail = 0, sl = w >> 1, ph = 1;
      const int ke = p3_k(w >> 1);
      const unsigned nheads = (ke < 7 ? 5 : 1) * (epoch + 1);
#pragma unroll 1
      for (int seg = 0; seg < NAUXSEG; seg++) {
        bool waited = false;
        if (seg >= avail) {
          const unsigned* const c = &g_ocnt[seg * 64 + ke * 8];
          const int c2 = ldg_relaxed32(c + 128) - nheads, c1 = ldg_relaxed32(c + 64) - nheads, c0 = ldg_acquire32(c) - nheads;
          waited = c0 < 0;
          if (waited) { wait_count(c, nheads, !(TL & 2) || seg < NAUXSEG - 2); if (PDLY && seg < FEND) wait_until(gtime() + PDLY); }
          else if (c1 >= 0) avail = seg + (c2 >= 0 ? 3 : 2);
        }
        SSTAMP(5, seg);
        mbar_wait(empty3 + 8 * sl, ph);
        if (AX & 4) mbar_arrive(full3 + 8 * sl);
        else {
          mbar_expect(full3 + 8 * sl, XT + 512);
          tma_load3c(sb + sl * XT, &tm.o3, 0, seg * 32, ke * 9, full3 + 8 * sl);
          tma_load(sb + A_XT + sl * 512, &tm.o8, 72 * 64 + ke * 8, seg * 32, full3 + 8 * sl);
        }
        p3_next(sl, ph);
      }
    }
  } else if (wg == 2) {
    asm volatile("setmaxnreg.dec.sync.aligned.u32 88;");
    {
      const unsigned epoch = *(volatile unsigned*)&g_epoch2;
      if ((tid & 127) < 80) { const uint4 g = __ldg((const uint4*)gate_w + min(tid & 127, 71)); sts128(sb + A_GW + (tid & 127) * 16, g.x, g.y, g.z, g.w); }
      fence_async();
      bar_sync(3, 128);
      float gt[2][4];
      const uint32_t d0 = (sb & 0x3FFFF) >> 4;
#pragma unroll 1
      for (int j = 0; j < 3; j++) {
        mbar_wait(fullx + 8 * j, 0);
        WG_FENCE();
#pragma unroll
        for (int k = 0; k < 24; k++)
          wgmma_n8_ss(gt[k & 1], desc_at(d0 + (k & 1) * (A_XH >> 4) + j * 1536 + (k >> 3) * 512 + (k & 6), 16, 1024, 1), desc_at(d0 + (A_GW >> 4) + j * 24 + (k & 30), 16, 128, 0), j | (k >> 1));
        WG_COMMIT();
      }
      WG_WAIT(0);
      if ((lane & 3) == 0)
#pragma unroll
        for (int i = 0; i < 4; i++) {
          const float gv = 1.f / (1.f + __expf(-gt[i >> 1][(i & 1) * 2]));
          const int r = w * 16 + (lane >> 2) + (i & 1) * 8, tok = 2 * (57 * tile - 7 + r) + (i >> 1);
          sts32(sb + A_GATE + ((i >> 1) * 64 + r) * 4, __float_as_uint(gv));
          if (hh == 0 && r >= 7 && tok < S_LEN) g_gate[tok] = gv;
        }
      if (tid == 256) sts32(sb + A_BAR + 376, epoch);
      __syncwarp();
      bar_arrive(7, 384);
      __half2 hw = __float2half2_rn(0.f);
#pragma unroll
      for (int i = 0; i < 9; i++) { const uint4 v = __ldg((const uint4*)woa + cta * 1152 + i * 128 + (tid & 127)); hw = amax4(hw, &v.x); }
      const uint32_t ew = wexp(hw);
      if (lane == 0) atomicMax(&g_amax[0], (unsigned long long)(epoch + 1) << 32 | ew);
      bar_sync(3, 128);
      if (tid == 256) {
        count_up(&g_abar[0]);
        wait_count(&g_abar[0], NAUX * (epoch + 1));
        if (cta == 0) *(volatile unsigned*)&g_epoch2 = epoch + 1;
      }
      __syncwarp();
      bar_sync(3, 128);
    }
    if (cta < NH) {
      const int lim = w * 8 + (lane >> 2) - 2 * (lane & 3);
      int q = 0, ph = 0;
      uint32_t p[5][4];
#pragma unroll
      for (int n = 0; n < 10; n++) p[n >> 1][1 + (n & 1)] = __shfl_sync(0xffffffffu, lane ^ n, n);
#pragma unroll 1
      for (int seg = 0; seg < NAUXSEG; seg++) {
        const float gt = __ldcg(&g_gate[seg * 32 + w * 8 + (lane >> 2)]);
        float sc[20], d[32];
        const uint32_t d0 = ((sb & 0x3FFFF) + (q < 2 ? A_IN + q * A_INS : 3 * XT)) >> 4;
        mbar_wait(fullq + q * 8, ph);
        if (tid == 256) SSTAMP(2, seg);
        WG_FENCE();
#pragma unroll
        for (int k = 0; k < 8; k++) {
          const int o = ((k >> 2) * 9216 + (k & 3) * 256) >> 4;
          wgmma_n40_ss_tt(sc, desc_at(d0 + o, 128, 512, 0), desc_at(d0 + o + 256, 128, 1024, 0), k > 0);
        }
        WG_COMMIT();
        WG_WAIT(0);
        if (tid == 256) SSTAMP(12, seg);
        float a[10];
#pragma unroll
        for (int i = 0; i < 10; i++) {
          a[i] = sc[(i >> 1) * 4 + (i & 1)] * (SM_SCALE * LOG2E);
          if (i < 8 && (i >> 1) * 8 + (i & 1) > lim) a[i] = -1.0e9f * LOG2E;
        }
        float m = max10(a);
        m = fmaxf(m, __shfl_xor_sync(0xffffffffu, m, 1)); m = fmaxf(m, __shfl_xor_sync(0xffffffffu, m, 2));
#pragma unroll
        for (int i = 0; i < 10; i++) a[i] = ex2(a[i] - m);
#pragma unroll
        for (int n = 0; n < 5; n++) {
          p[n][0] = pack_bf16(a[2 * n], a[2 * n + 1]); p[n][3] = p[n][0] | p[n][1];
          asm volatile("" : "+r"(p[n][0]), "+r"(p[n][3]) :: "memory");
        }
        float sum = ((a[0] + a[1]) + (a[2] + a[3])) + ((a[4] + a[5]) + (a[6] + a[7])) + (a[8] + a[9]);
        sum += __shfl_xor_sync(0xffffffffu, sum, 1);
        if (tid == 256) SSTAMP(3, seg);
        WG_FENCE();
#pragma unroll
        for (int n = 0; n < 5; n++) wgmma_n64_rs(d, p[n], n < 4 ? desc_at(d0 + 1152 + 8 * n, 4096, 512, 0) : desc_at(d0 + 1152 + 512, 1024, 128, 0), n);
        WG_COMMIT();
        sum += __shfl_xor_sync(0xffffffffu, sum, 2);
        const float f = (1.f - gt) * rcp(sum);
        WG_WAIT(0);
        if (lane == 0) mbar_arrive(emptyq + q * 8);
        if (++q == NQ) { q = 0; ph ^= 1; }
        if (tid == 256) SSTAMP(4, seg);
        mbar_wait(emptyo + (seg & 1) * 8, (seg >> 1) & 1);
#pragma unroll
        for (int n = 0; n < 4; n++) {
          const float* const v = d + (n & 1) * 16 + (n & 2);
          stsm4(sb + A_OST + (seg & 1) * 8192 + (n >> 1) * 4096 + (w * 8 + (lane & 7)) * 128 + ((((n & 1) * 4 + (lane >> 3)) ^ (lane & 7)) << 4),
                pack_bf16(v[0] * f, v[1] * f), pack_bf16(v[4] * f, v[5] * f), pack_bf16(v[8] * f, v[9] * f), pack_bf16(v[12] * f, v[13] * f));
        }
        __syncwarp();
        if (lane == 0) mbar_arrive(fullo + (seg & 1) * 8);
        if (tid == 256) SSTAMP(13, seg);
      }
    }
  } else {
    asm volatile("setmaxnreg.inc.sync.aligned.u32 200;");
    {
      const int g = lane >> 2, t = lane & 3;
      const uint32_t eb = sb + A_EPI + wg * A_EPW, d0 = (sb & 0x3FFFF) >> 4;
      const uint32_t own = (2 * t <= g ? 0xffffu : 0u) | (2 * t < g ? 0xffff0000u : 0u);
      const int kmin = 7 - 57 * tile - 16 * w;
      __half2 ho = __float2half2_rn(0.f);
#pragma unroll 1
      for (int c = 0; c < 4; c++) {
        float acc[96], tl[12];
#pragma unroll 1
        for (int r = 0; r < 4; r++) {
#pragma unroll
          for (int st = 0; st < A_NS; st++) {
            const int ks = r * 9 + st;
            if (c == 0 && st % 3 == 0 && ks % 12 == 0) mbar_wait(fullx + 8 * (ks / 12), 0);
            mbar_wait(full1 + 8 * st, r & 1);
            const uint64_t da = desc_at(d0 + wg * (A_XH >> 4) + (ks >> 2) * 512 + (ks & 3) * 2, 16, 1024, 1);
            WG_FENCE();
            wgmma_n192_ss_nt(acc, da, desc_at(d0 + ((A_RING + st * A_WM) >> 4), 2048, 1024, 1), ks);
            if (!(AX & 2)) wgmma_n24_ss_nt(tl, da, desc_at(d0 + ((A_TAIL + st * A_WT) >> 4), 128, 256, 0), ks);
            WG_COMMIT();
            if (st == 0 && r == 2) bar_sync(11 + wg, 160);
            WG_WAIT(1);
            if (ks > 0 && lane == 0) mbar_arrive(empty1 + 8 * ((st + A_NS - 1) % A_NS));
          }
        }
        WG_WAIT(0);
        if (lane == 0) mbar_arrive(empty1 + 8 * (A_NS - 1));
        ASTAMP(16 + (c & 3));
        uint32_t ql[9], qh[9], kl[9], kh[9], kx[10], vl[9], vh[9], vx[10];
#pragma unroll
        for (int j = 0; j < 9; j++) {
          const float* const q = j < 8 ? acc + 4 * j : tl, * const k = j < 8 ? acc + 32 + 4 * j : tl + 4, * const v = j < 8 ? acc + 64 + 4 * j : tl + 8;
          kh[j] = pack_bf16(k[2], k[3]); vh[j] = pack_bf16(v[2], v[3]);
          ql[j] = pack_bf16(q[0], q[1]); qh[j] = pack_bf16(q[2], q[3]); kl[j] = pack_bf16(k[0], k[1]); vl[j] = pack_bf16(v[0], v[1]);
        }
        if (w < 3) {
          const uint32_t ha = eb + 1024 + w * 2304 + lane * 16;
          stsm4(ha, kh[0], kh[1], kh[2], kh[3]); stsm4(ha + 512, kh[4], kh[5], kh[6], kh[7]);
          stsm4(ha + 1024, vh[0], vh[1], vh[2], vh[3]); stsm4(ha + 1536, vh[4], vh[5], vh[6], vh[7]);
          asm volatile("stmatrix.sync.aligned.m8n8.x2.shared.b16 [%0], {%1,%2};" :: "r"(ha + 2048), "r"(kh[8]), "r"(vh[8]) : "memory");
        }
        if (c == 0) bar_sync(7, 384); else bar_sync(1 + wg, 128);
        {
          const uint32_t ha = eb + 1024 + max(w - 1, 0) * 2304 + lane * 16;
          ldsm4(kx, ha); ldsm4(kx + 4, ha + 512); ldsm4t(vx, ha + 1024); ldsm4t(vx + 4, ha + 1536);
          asm volatile("ldmatrix.sync.aligned.m8n8.x1.shared.b16 {%0}, [%1];" : "=r"(kx[8]) : "r"(ha + 2048) : "memory");
          asm volatile("ldmatrix.sync.aligned.m8n8.x1.trans.shared.b16 {%0}, [%1];" : "=r"(vx[8]) : "r"(ha + 2176) : "memory");
        }
        const float gl = __uint_as_float(lds32(sb + A_GATE + (wg * 64 + w * 16 + g) * 4)), gh = __uint_as_float(lds32(sb + A_GATE + (wg * 64 + w * 16 + g + 8) * 4));
#pragma unroll
        for (int j = 0; j < 9; j++) { vl[j] = movm(vl[j]); vh[j] = movm(vh[j]); }
        bar_sync(1 + wg, 128);
        uint32_t ol[9], oh[9];
#pragma unroll
        for (int i = 0; i < 4; i++) {
          const int b = 2 * i;
          const uint32_t a[4] = {t >= i ? ql[b] : 0u, t >= i ? qh[b] : 0u, ql[b + 1], qh[b + 1]}, a4 = t <= i ? ql[b + 2] : 0u, a5 = t <= i ? qh[b + 2] : 0u;
          float sx[4], sl[4], sh[4];
          mma16816z(sx, a, kx[b], kx[b + 1]); mma16816z(sl, a, kl[b], kl[b + 1]); mma16816z(sh, a, kh[b], kh[b + 1]);
          mma1688(sx, a4, a5, kx[b + 2]); mma1688(sl, a4, a5, kl[b + 2]); mma1688(sh, a4, a5, kh[b + 2]);
          float e[4];
#pragma unroll
          for (int u = 0; u < 4; u++) {
            const int cc = 2 * t + (u & 1);
            e[u] = (cc <= g ? (u < 2 ? sl[u] : sh[u]) : (u < 2 ? sx[u] : sl[u])) * (0.23570226039551584f * LOG2E);
            if ((cc <= g ? cc : cc - 8) + (u & 2) * 4 < kmin) e[u] = -1.0e9f * LOG2E;
          }
          float m0 = fmaxf(e[0], e[1]), m1 = fmaxf(e[2], e[3]);
#pragma unroll
          for (int o = 1; o < 4; o <<= 1) { m0 = fmaxf(m0, __shfl_xor_sync(0xffffffffu, m0, o)); m1 = fmaxf(m1, __shfl_xor_sync(0xffffffffu, m1, o)); }
          e[0] = ex2(e[0] - m0); e[1] = ex2(e[1] - m0); e[2] = ex2(e[2] - m1); e[3] = ex2(e[3] - m1);
          const uint32_t p0 = pack_bf16(e[0], e[1]), p1 = pack_bf16(e[2], e[3]);
          const uint32_t p[4] = {p0 & ~own, 0u, p0 & own, p1 & ~own};
          float s0 = e[0] + e[1], s1 = e[2] + e[3];
#pragma unroll
          for (int o = 1; o < 4; o <<= 1) { s0 += __shfl_xor_sync(0xffffffffu, s0, o); s1 += __shfl_xor_sync(0xffffffffu, s1, o); }
          const float f0 = gl * rcp(s0), f1 = gh * rcp(s1);
#pragma unroll
          for (int j = b; j < b + 3; j++) {
            float o[4];
            mma16816z(o, p, vx[j], vl[j]);
            mma1688(o, 0u, p1 & own, vh[j]);
            const uint32_t lo = pack_bf16(o[0] * f0, o[1] * f0), hi = pack_bf16(o[2] * f1, o[3] * f1);
            if (j > b || i == 0) { ol[j] = lo; oh[j] = hi; }
            else { ol[j] = t >= i ? lo : ol[j]; oh[j] = t >= i ? hi : oh[j]; }
          }
        }
        const uint32_t sa = eb + 16 + (w * 16 + (lane & 15)) * 144 + (lane >> 4) * 16;
#pragma unroll
        for (int j = 0; j < 8; j += 2) stsm4(sa + j * 16, ol[j], oh[j], ol[j + 1], oh[j + 1]);
        asm volatile("stmatrix.sync.aligned.m8n8.x2.shared.b16 [%0], {%1,%2};" :: "r"(sa + 128), "r"(ol[8]), "r"(oh[8]) : "memory");
        ho = amax4(amax4(amax4(amax4(ho, ol), ol + 4), oh), oh + 4);
        ho = __hmax2_nan(__hmax2_nan(ho, __habs2(*(const __half2*)&ol[8])), __habs2(*(const __half2*)&oh[8]));
        if (c == 3 && tile == 17) {
          const uint32_t eo = wexp(ho);
          if (lane == 0) atomicMax(&g_amax[16], (unsigned long long)(lds32(sb + A_BAR + 376) + 1) << 32 | eo);
        }
        fence_async();
        bar_arrive(13 + wg, 160);
        ASTAMP(20 + (c & 3));
      }
    }
    ASTAMP(3);
    uint32_t wa[36][4];
    mbar_wait(fullw, 0);
    const uint32_t la = sb + wg * 73728 + ((lane & 7) + ((lane >> 4) << 3)) * 128 + (((2 * w + ((lane >> 3) & 1)) ^ (lane & 7)) << 4);
#pragma unroll
    for (int k = 0; k < 36; k++) ldsm4t(wa[k], la + k * 2048);
    sts64(sb + A_XW + wg * 2048 + 1024 + (tid & 127) * 8, 0, 0);
    fence_async();
    bar_arrive(6, cta >= NH ? 320 : 288);
    bar_sync(1 + wg, 128);
    ASTAMP(4);
    const int nsl = p3_n(wg), ke = p3_k(wg), t = lane & 3;
    const unsigned epoch = lds32(sb + A_BAR + 376);
    uint2* const part = g_part + nsl * 4096 + w * 16 + (lane >> 2) * 2 + (t & 1);
    auto tag = [&](int seg) { return PR == 8 ? ((seg >> 3) + 1 + (epoch & (seg >> 1) & (seg >> 2))) & 1 : ((seg >> 2) + 1 + (epoch & (seg >> 1))) & 1; };
    uint2 v[4];
    auto fetch = [&](int seg) {
#pragma unroll
      for (int j = 0; j < 4; j++)
        asm volatile("ld.relaxed.gpu.global.v2.b32 {%0,%1}, [%2];" : "=r"(v[j].x), "=r"(v[j].y) : "l"(part + (seg & (PR - 1)) * 36864 + ke * 512 + ((t >> 1) * 4 + j) * 64) : "memory");
    };
    auto finish = [&](int seg) {
      int n = 0;
#pragma unroll 1
      while (!(AX & 16) && __any_sync(0xffffffffu, (((v[0].x ^ tag(seg)) | (v[1].x ^ tag(seg)) | (v[2].x ^ tag(seg)) | (v[3].x ^ tag(seg))) & 1) != 0) && ++n < SPIN_LIMIT) {
        if (seg < NAUXSEG - ((TL & 2) ? 2 : 1)) __nanosleep(100);
        fetch(seg);
      }
      const float a0 = (bf_lo(v[0].x) + bf_lo(v[1].x)) + (bf_lo(v[2].x) + bf_lo(v[3].x)), a1 = (bf_hi(v[0].x) + bf_hi(v[1].x)) + (bf_hi(v[2].x) + bf_hi(v[3].x));
      const float b0 = (bf_lo(v[0].y) + bf_lo(v[1].y)) + (bf_lo(v[2].y) + bf_lo(v[3].y)), b1 = (bf_hi(v[0].y) + bf_hi(v[1].y)) + (bf_hi(v[2].y) + bf_hi(v[3].y));
      const float c0 = (t < 2 ? a0 : b0) + __shfl_xor_sync(0xffffffffu, t < 2 ? b0 : a0, 2), c1 = (t < 2 ? a1 : b1) + __shfl_xor_sync(0xffffffffu, t < 2 ? b1 : a1, 2);
      ((uint32_t*)(out + (size_t)(seg * 32 + ke * 4 + ((lane >> 2) & 3)) * DM + nsl * 64 + w * 16 + (lane >> 4) * 8))[t] = movm(pack_bf16(c0, c1));
    };
    float acc[16];
    if (AX & 64) for (int i = 0; i < 16; i++) acc[i] = 0.f;
    int done = 0, sl = cta < NH ? 0 : wg, ph = 0;
    const uint32_t d0 = (sb & 0x3FFFF) >> 4;
#pragma unroll 1
    for (int seg = 0; seg < NAUXSEG; seg++) {
      if (DRAIN) {
#pragma unroll 1
        while (done < seg && !mbar_test(full3 + 8 * sl, ph)) { fetch(done); finish(done); done++; }
      }
      mbar_wait(full3 + 8 * sl, ph);
      if (SER && !(AX & 64) && (wg == 1 || seg > 0)) bar_sync(10 - wg, 256);
      if (tid == 128) SSTAMP(6, seg);
      if (!(AX & 16)) fetch(done);
      if (!(AX & 64)) {
        const uint64_t db = desc_at(d0 + sl * (XT >> 4), 16, 1024, 1);
        WG_FENCE();
        wgmma_n32_ss_tn(acc, desc_at(d0 + ((A_XW + wg * 2048) >> 4), 8192, 1024, 1), desc_at(d0 + (A_XT >> 4) + sl * 32, 0, 128, 0), 0);
#pragma unroll
        for (int k = 0; k < 36; k++) {
          wgmma_n32_rs(acc, wa[k][0], wa[k][1], wa[k][2], wa[k][3], db + (k >> 2) * 256 + (k & 3) * 2, 1);
          if (SER && k == SER && (wg == 0 || seg < NAUXSEG - 1)) bar_arrive(9 + wg, 256);
        }
        WG_COMMIT();
      }
      if (done <= seg - PL) finish(done++);
      WG_WAIT(0);
      if (lane == 0) mbar_arrive(empty3 + 8 * sl);
      p3_next(sl, ph);
#pragma unroll
      for (int j = 0; j < 4; j++)
        if (!(AX & 16) || acc[4 * j] == 1.2345678f)
          asm volatile("st.relaxed.gpu.global.v2.b32 [%0], {%1,%2};" :: "l"(part + (seg & (PR - 1)) * 36864 + (2 * j + (t >> 1)) * 512 + ke * 64),
                       "r"((pack_bf16(0.f, acc[4 * j + 1]) | tag(seg)) + ((__float_as_uint(acc[4 * j]) + ((tag(seg) ^ 1) << 16)) >> 17 << 1)),   "r"(pack_bf16(acc[4 * j + 2], acc[4 * j + 3])) : "memory");
      if (tid == 128) SSTAMP(7, seg);
      if (tid == 128) SSTAMP(8, seg);
      if ((seg & 7) == 6) ASTAMP(5 + (seg >> 3));
    }
#pragma unroll 1
    for (; done < NAUXSEG; done++) { fetch(done); finish(done); }
    ASTAMP(13);
    TSTAMP(48);
    MSTAMP(9);
  }
}

typedef CUresult (*EncodeFn)(CUtensorMap*, CUtensorMapDataType, cuuint32_t, void*, const cuuint64_t*, const cuuint64_t*,
                             const cuuint32_t*, const cuuint32_t*, CUtensorMapInterleave, CUtensorMapSwizzle,
                             CUtensorMapL2promotion, CUtensorMapFloatOOBfill);
static void make_map(EncodeFn enc, CUtensorMap* m, const void* p, int rows, int cols, int box_rows) {
  cuuint64_t dims[2] = {(cuuint64_t)cols, (cuuint64_t)rows};
  cuuint64_t strides[1] = {(cuuint64_t)cols * 2};
  cuuint32_t box[2] = {64, (cuuint32_t)box_rows};
  cuuint32_t es[2] = {1, 1};
  enc(m, CU_TENSOR_MAP_DATA_TYPE_BFLOAT16, 2, (void*)p, dims, strides, box, es, CU_TENSOR_MAP_INTERLEAVE_NONE,
      CU_TENSOR_MAP_SWIZZLE_128B, CU_TENSOR_MAP_L2_PROMOTION_L2_128B, CU_TENSOR_MAP_FLOAT_OOB_FILL_NONE);
}

constexpr int g_poll = POLL_NS;
extern "C" void kernel_launch(void* const* d_in, const int* in_sizes, int n_in, void* d_out, int out_size) {
  const bf16* x = (const bf16*)d_in[0];
  const bf16* wqkvA = (const bf16*)d_in[1];
  const bf16* woA = (const bf16*)d_in[2];
  const bf16* mem0 = (const bf16*)d_in[4];
  const bf16* Wq = (const bf16*)d_in[5];
  const bf16* Wk = (const bf16*)d_in[6];
  const bf16* Wv = (const bf16*)d_in[7];
  const bf16* Wo = (const bf16*)d_in[8];
  const bf16* gate_w = (const bf16*)d_in[10];
  static EncodeFn enc = nullptr;
  static void *pO = nullptr, *pR = nullptr;
  if (!enc) {
    cudaDriverEntryPointQueryResult qr;
    cudaGetDriverEntryPoint("cuTensorMapEncodeTiled", (void**)&enc, cudaEnableDefault, &qr);
    cudaGetSymbolAddress(&pO, g_Ocat);
    cudaGetSymbolAddress(&pR, g_red_raw);
    cudaFuncSetAttribute(rec_kernel, cudaFuncAttributeMaxDynamicSharedMemorySize, SM_TOTAL);
    cudaFuncSetAttribute(aux_kernel, cudaFuncAttributeMaxDynamicSharedMemorySize, A_TOTAL);
  }
  RMaps rm;
  rm.poll = g_poll; rm.out = (bf16*)d_out;
  make_map(enc, &rm.woa, woA, DM, DM, 24);
  {
    cuuint64_t dims[2] = {KCAT, S_LEN}, strides[1] = {KCAT * 2};
    cuuint32_t box[2] = {32, 64}, es[2] = {1, 1};
    enc(&rm.oa, CU_TENSOR_MAP_DATA_TYPE_BFLOAT16, 2, pO, dims, strides, box, es, CU_TENSOR_MAP_INTERLEAVE_NONE,
        CU_TENSOR_MAP_SWIZZLE_NONE, CU_TENSOR_MAP_L2_PROMOTION_NONE, CU_TENSOR_MAP_FLOAT_OOB_FILL_NONE);
  }
  rm.red = (unsigned char*)(((uintptr_t)pR + 262143) & ~(uintptr_t)262143);
  {
    cuuint64_t dims[3] = {64, S_LEN, 9}, strides[2] = {DM * 2, 128};
    cuuint32_t box[3] = {64, 32, 9}, es[3] = {1, 1, 1};
    enc(&rm.x, CU_TENSOR_MAP_DATA_TYPE_BFLOAT16, 3, (void*)x, dims, strides, box, es, CU_TENSOR_MAP_INTERLEAVE_NONE,
        CU_TENSOR_MAP_SWIZZLE_128B, CU_TENSOR_MAP_L2_PROMOTION_L2_128B, CU_TENSOR_MAP_FLOAT_OOB_FILL_NONE);
  }
  make_map(enc, &rm.wq, Wq, DM, 4096, 192);
  make_map(enc, &rm.wk, Wk, DM, 4096, 192);
  make_map(enc, &rm.wv, Wv, DM, 4096, 192);
  make_map(enc, &rm.wo, Wo, 4096, DM, 128);
  AMaps am;
  {
    cuuint32_t es[4] = {1, 1, 1, 1};
    cuuint64_t dx[4] = {64, 2, S_LEN / 2, 9}, sx[3] = {DM * 2, DM * 4, 128};
    cuuint32_t bx[4] = {64, 1, 64, 3};
    enc(&am.x, CU_TENSOR_MAP_DATA_TYPE_BFLOAT16, 4, (void*)x, dx, sx, bx, es, CU_TENSOR_MAP_INTERLEAVE_NONE,
        CU_TENSOR_MAP_SWIZZLE_128B, CU_TENSOR_MAP_L2_PROMOTION_L2_128B, CU_TENSOR_MAP_FLOAT_OOB_FILL_NONE);
    cuuint64_t dw[3] = {DM, DM, 3}, sw[2] = {DM * 6, DM * 2};
    cuuint32_t bw[3] = {64, 16, 3}, bt[3] = {8, 16, 3};
    enc(&am.wa, CU_TENSOR_MAP_DATA_TYPE_BFLOAT16, 3, (void*)wqkvA, dw, sw, bw, es, CU_TENSOR_MAP_INTERLEAVE_NONE,
        CU_TENSOR_MAP_SWIZZLE_128B, CU_TENSOR_MAP_L2_PROMOTION_L2_128B, CU_TENSOR_MAP_FLOAT_OOB_FILL_NONE);
    enc(&am.wt, CU_TENSOR_MAP_DATA_TYPE_BFLOAT16, 3, (void*)wqkvA, dw, sw, bt, es, CU_TENSOR_MAP_INTERLEAVE_NONE,
        CU_TENSOR_MAP_SWIZZLE_NONE, CU_TENSOR_MAP_L2_PROMOTION_NONE, CU_TENSOR_MAP_FLOAT_OOB_FILL_NONE);
    cuuint64_t dz[3] = {KCAT, 2, S_LEN / 2}, sz[2] = {KCAT * 2, KCAT * 4};
    cuuint32_t bz[3] = {72, 1, 57};
    enc(&am.oa, CU_TENSOR_MAP_DATA_TYPE_BFLOAT16, 3, pO, dz, sz, bz, es, CU_TENSOR_MAP_INTERLEAVE_NONE,
        CU_TENSOR_MAP_SWIZZLE_NONE, CU_TENSOR_MAP_L2_PROMOTION_NONE, CU_TENSOR_MAP_FLOAT_OOB_FILL_NONE);
  }
  {
    cuuint64_t dims[3] = {64, S_LEN, KCAT / 64}, strides[2] = {KCAT * 2, 128};
    cuuint32_t box[3] = {64, 32, 9}, es[3] = {1, 1, 1};
    make_map(enc, &am.o, pO, S_LEN, KCAT, 32);
    enc(&am.o3, CU_TENSOR_MAP_DATA_TYPE_BFLOAT16, 3, pO, dims, strides, box, es, CU_TENSOR_MAP_INTERLEAVE_NONE,
        CU_TENSOR_MAP_SWIZZLE_128B, CU_TENSOR_MAP_L2_PROMOTION_L2_128B, CU_TENSOR_MAP_FLOAT_OOB_FILL_NONE);
  }
  make_map(enc, &am.wob, Wo, 4096, DM, 64);
  make_map(enc, &am.woa, woA, DM, DM, 64);
  make_map(enc, &am.wo8, woA, DM, DM, 8);
  {
    cuuint64_t dims[2] = {KCAT, S_LEN}, strides[1] = {KCAT * 2};
    cuuint32_t box[2] = {8, 32}, es[2] = {1, 1};
    enc(&am.o8, CU_TENSOR_MAP_DATA_TYPE_BFLOAT16, 2, pO, dims, strides, box, es, CU_TENSOR_MAP_INTERLEAVE_NONE,
        CU_TENSOR_MAP_SWIZZLE_NONE, CU_TENSOR_MAP_L2_PROMOTION_NONE, CU_TENSOR_MAP_FLOAT_OOB_FILL_NONE);
  }

  rec_kernel<<<96, 384, SM_TOTAL, cudaStreamPerThread>>>(rm, x, mem0);
  cudaLaunchConfig_t cfg = {};
  cfg.gridDim = dim3(NAUX); cfg.blockDim = dim3(512); cfg.dynamicSmemBytes = A_TOTAL; cfg.stream = cudaStreamPerThread;
  cudaLaunchAttribute at[1];
  at[0].id = cudaLaunchAttributeProgrammaticStreamSerialization; at[0].val.programmaticStreamSerializationAllowed = 1;
  cfg.attrs = at; cfg.numAttrs = 1;
  if (XP & 16) cfg.numAttrs = 0;
  if (!(XP & 64)) cudaLaunchKernelEx(&cfg, aux_kernel, am, wqkvA, woA, gate_w, (bf16*)d_out);
}
```

```cpp
#include <cuda_runtime.h>
#include <cuda_bf16.h>
#include <cuda_fp16.h>
#include <cuda.h>
#include <stdint.h>

typedef __nv_bfloat16 bf16;

constexpr int S_LEN = 2048, DM = 576, NH = 32, DH = 128, NSEG = 64, KCAT = 4096 + 576;
constexpr int NAUXSEG = NSEG - 2;
constexpr int NAUX = 36;
#define RED_LINE(i) (((i) >> 2) * 4096 + ((i) & 1) * 256 + ((i) & 2) * 512)
#define RED_SLOT(s) (((s) & 1) * 128 + ((s) & 2) * 256)

#define POLL_NS 848
#define NII 14
#define NUP 4
#define B3Q 9
#define GATE 7
#define PSTAMP 0
#define NRING 20
#define NPROBE 2
#define N5 224
#define KP(i) (((i) >> 1) + 4 * ((i) & 1))
#define SPIN_LIMIT (1 << 14)
#define XP 0

__device__ __align__(1024) bf16 g_Ocat[S_LEN * KCAT];
__device__ __align__(1024) unsigned char g_red_raw[2 * 262144];
constexpr int HINT_OFF = 2048;
__device__ __align__(16) float g_gate[S_LEN];
__device__ __align__(128) uint4 g_stats[96 * 2];
__device__ unsigned g_epoch;
__device__ unsigned g_epoch2;
__device__ unsigned g_ocnt[NSEG * 64];
__device__ unsigned g_abar[3 * 32];
__device__ unsigned long long g_amax[2 * 16];
__device__ unsigned g_scnt[NSEG * 32 * 8];
__device__ __align__(1024) unsigned char g_seg[NRING * 96 * 10240];
__device__ unsigned g_used[NH * 32];
__device__ __align__(1024) uint2 g_part[4 * 9 * 64 * 64];
__device__ int g_err;
#define MSTAMP(i)
#define TSTAMP(i)
#define PROF(idx)
#define PROFP(idx)
#define RSTAMP(k)
#define STAMP(idx)
#define ASTAMP(idx)
#define SSTAMP(k, seg)
#define WSTAMP(idx)

#define DI __device__ __forceinline__
DI uint32_t smem_u32(const void* p) { return (uint32_t)__cvta_generic_to_shared(p); }
DI uint32_t clock32() { uint32_t c; asm volatile("mov.u32 %0, %%clock;" : "=r"(c) :: "memory"); return c; }
DI uint32_t gtime() { uint32_t c; asm volatile("mov.u32 %0, %%globaltimer_lo;" : "=r"(c) :: "memory"); return c; }
DI uint32_t ldg_relaxed32(const void* p) { uint32_t v; asm volatile("ld.relaxed.gpu.global.b32 %0, [%1];" : "=r"(v) : "l"(p) : "memory"); return v; }
DI uint32_t ldg_acquire32(const void* p) { uint32_t v; asm volatile("ld.acquire.gpu.global.b32 %0, [%1];" : "=r"(v) : "l"(p) : "memory"); return v; }
DI void stg_relaxed32(void* p, uint32_t v) { asm volatile("st.relaxed.gpu.global.b32 [%0], %1;" :: "l"(p), "r"(v) : "memory"); }
DI uint32_t mapa(uint32_t a, uint32_t r) { uint32_t o; asm("mapa.shared::cluster.u32 %0, %1, %2;" : "=r"(o) : "r"(a), "r"(r)); return o; }
DI void cluster_arrive() { asm volatile("barrier.cluster.arrive.relaxed.aligned;" ::: "memory"); }
DI void cluster_wait() { asm volatile("barrier.cluster.wait.aligned;" ::: "memory"); }
DI void mbar_init(uint32_t b, uint32_t c) { asm volatile("mbarrier.init.shared::cta.b64 [%0], %1;" :: "r"(b), "r"(c) : "memory"); }
DI void mbar_expect(uint32_t b, uint32_t tx) { asm volatile("mbarrier.arrive.expect_tx.shared::cta.b64 _, [%0], %1;" :: "r"(b), "r"(tx) : "memory"); }
DI void mbar_arrive(uint32_t b) { asm volatile("mbarrier.arrive.shared::cta.b64 _, [%0];" :: "r"(b) : "memory"); }
DI void mbar_wait(uint32_t b, uint32_t par) {
  asm volatile("{\n.reg .pred p;\n.reg .u32 n, q;\nmov.u32 n, 0;\n"
               "WL: add.u32 n, n, 1;\nshr.u32 q, n, 12;\nxor.b32 q, q, %1;\n"
               "mbarrier.try_wait.parity.shared::cta.b64 p, [%0], q;\n@!p bra.uni WL;\n}"
               :: "r"(b), "r"(par) : "memory");
}
DI bool mbar_test(uint32_t b, uint32_t par) {
  uint32_t r;
  asm volatile("{\n.reg .pred p;\nmbarrier.test_wait.parity.shared::cta.b64 p, [%1], %2;\nselp.u32 %0, 1, 0, p;\n}" : "=r"(r) : "r"(b), "r"(par) : "memory");
  return r;
}
DI void mbar_wait_fast(uint32_t b, uint32_t par) {
  asm volatile("{\n.reg .pred p;\n.reg .u32 n, q;\nmbarrier.try_wait.parity.shared::cta.b64 p, [%0], %1;\n@p bra.uni WD;\nmov.u32 n, 0;\n"
               "WL: add.u32 n, n, 1;\nshr.u32 q, n, 12;\nxor.b32 q, q, %1;\n"
               "mbarrier.try_wait.parity.shared::cta.b64 p, [%0], q;\n@!p bra.uni WL;\nWD:\n}"
               :: "r"(b), "r"(par) : "memory");
}
DI void wait_until(uint32_t t) {
  const uint32_t now = gtime();
  t = min(t, now + 8192);
  asm volatile("{\n.reg .pred p;\n.reg .u32 c;\nTL: mov.u32 c, %%globaltimer_lo;\nsetp.lt.u32 p, c, %0;\n@p bra.uni TL;\n}" :: "r"(t) : "memory");
}
#define PIN(v) v = __shfl_xor_sync(0xffffffffu, v, 0)
#define SCHED_FENCE(k) asm volatile("{\n.reg .pred p;\nsetp.eq.u32 p, %0, %1;\n@p exit;\n}" :: "r"(fence_reg), "r"(k) : "memory")
#define MEM_ORDER(k) asm volatile("{\n.reg .pred p;\nsetp.eq.u32 p, %0, %1;\n@p st.shared.u32 [%0], %0;\n}" :: "r"(fence_reg), "r"(k + 64) : "memory")
DI void bar_sync(int id, int n) { asm volatile("bar.sync %0, %1;" :: "r"(id), "r"(n) : "memory"); }
DI void bar_arrive(int id, int n) { asm volatile("bar.arrive %0, %1;" :: "r"(id), "r"(n) : "memory"); }
DI void fence_async() { asm volatile("fence.proxy.async.shared::cta;" ::: "memory"); }
DI void st_async4(uint32_t a, uint32_t x, uint32_t y, uint32_t z, uint32_t w, uint32_t mb) {
  asm volatile("st.async.weak.shared::cluster.mbarrier::complete_tx::bytes.v4.b32 [%0], {%1,%2,%3,%4}, [%5];"
               :: "r"(a), "r"(x), "r"(y), "r"(z), "r"(w), "r"(mb) : "memory");
}
DI void st_async2(uint32_t a, uint32_t x, uint32_t y, uint32_t mb) {
  asm volatile("st.async.weak.shared::cluster.mbarrier::complete_tx::bytes.v2.b32 [%0], {%1,%2}, [%3];"
               :: "r"(a), "r"(x), "r"(y), "r"(mb) : "memory");
}
DI void sts32(uint32_t a, uint32_t x) { asm volatile("st.shared.b32 [%0], %1;" :: "r"(a), "r"(x) : "memory"); }
DI void sts64(uint32_t a, uint32_t x, uint32_t y) { asm volatile("st.shared.v2.b32 [%0], {%1,%2};" :: "r"(a), "r"(x), "r"(y) : "memory"); }
DI void sts128(uint32_t a, uint32_t x, uint32_t y, uint32_t z, uint32_t w) {
  asm volatile("st.shared.v4.b32 [%0], {%1,%2,%3,%4};" :: "r"(a), "r"(x), "r"(y), "r"(z), "r"(w) : "memory");
}
DI uint32_t lds32(uint32_t a) { uint32_t x; asm volatile("ld.shared.b32 %0, [%1];" : "=r"(x) : "r"(a) : "memory"); return x; }
DI void lds64(uint32_t a, uint32_t& x, uint32_t& y) { asm volatile("ld.shared.v2.b32 {%0,%1}, [%2];" : "=r"(x), "=r"(y) : "r"(a) : "memory"); }
DI void lds128(uint32_t a, uint32_t* r) {
  asm volatile("ld.shared.v4.b32 {%0,%1,%2,%3}, [%4];" : "=r"(r[0]), "=r"(r[1]), "=r"(r[2]), "=r"(r[3]) : "r"(a) : "memory");
}
DI void lds128f(uint32_t a, float* r) {
  asm volatile("ld.shared.v4.f32 {%0,%1,%2,%3}, [%4];" : "=f"(r[0]), "=f"(r[1]), "=f"(r[2]), "=f"(r[3]) : "r"(a) : "memory");
}
DI void lds64f(uint32_t a, float* r) { asm volatile("ld.shared.v2.f32 {%0,%1}, [%2];" : "=f"(r[0]), "=f"(r[1]) : "r"(a) : "memory"); }
DI void ldsm4t(uint32_t* r, uint32_t a) {
  asm volatile("ldmatrix.sync.aligned.m8n8.x4.trans.shared.b16 {%0,%1,%2,%3}, [%4];"
               : "=r"(r[0]), "=r"(r[1]), "=r"(r[2]), "=r"(r[3]) : "r"(a) : "memory");
}
DI void ldsm4t_in(uint32_t* r, uint32_t a, uint32_t t) {
  asm volatile("{\n.reg .pred p;\nsetp.ne.u32 p, %5, 0;\n@p ldmatrix.sync.aligned.m8n8.x4.trans.shared.b16 {%0,%1,%2,%3}, [%4];\n}"
               : "+r"(r[0]), "+r"(r[1]), "+r"(r[2]), "+r"(r[3]) : "r"(a), "r"(t) : "memory");
}
DI void lds128_in(uint32_t* r, uint32_t a, uint32_t t) {
  asm volatile("{\n.reg .pred p;\nsetp.ne.u32 p, %5, 0;\n@p ld.shared.v4.b32 {%0,%1,%2,%3}, [%4];\n}"
               : "+r"(r[0]), "+r"(r[1]), "+r"(r[2]), "+r"(r[3]) : "r"(a), "r"(t) : "memory");
}
DI void scale_sum(float& x, float& y, float s, uint32_t t) {
  asm volatile("{\n.reg .pred p;\nsetp.ne.u32 p, %2, 0;\n@p mul.f32 %0, %0, %1;\n}" : "+f"(y) : "f"(s), "r"(t));
  asm volatile("{\n.reg .pred p;\nsetp.ne.u32 p, %3, 1;\n@p fma.rn.f32 %0, %0, %1, %2;\n}" : "+f"(x) : "f"(s), "f"(y), "r"(t));
}
DI void ldsm4(uint32_t* r, uint32_t a) {
  asm volatile("ldmatrix.sync.aligned.m8n8.x4.shared.b16 {%0,%1,%2,%3}, [%4];"
               : "=r"(r[0]), "=r"(r[1]), "=r"(r[2]), "=r"(r[3]) : "r"(a) : "memory");
}
DI void st_async1(uint32_t a, uint32_t x, uint32_t mb) {
  asm volatile("st.async.weak.shared::cluster.mbarrier::complete_tx::bytes.b32 [%0], %1, [%2];" :: "r"(a), "r"(x), "r"(mb) : "memory");
}
DI void stsm4(uint32_t a, uint32_t x, uint32_t y, uint32_t z, uint32_t w) {
  asm volatile("stmatrix.sync.aligned.m8n8.x4.shared.b16 [%0], {%1,%2,%3,%4};" :: "r"(a), "r"(x), "r"(y), "r"(z), "r"(w) : "memory");
}
DI void stsm4t(uint32_t a, uint32_t x, uint32_t y, uint32_t z, uint32_t w) {
  asm volatile("stmatrix.sync.aligned.m8n8.x4.trans.shared.b16 [%0], {%1,%2,%3,%4};" :: "r"(a), "r"(x), "r"(y), "r"(z), "r"(w) : "memory");
}
DI uint32_t pack_bf16(float lo, float hi) { uint32_t r; asm("cvt.rn.bf16x2.f32 %0, %1, %2;" : "=r"(r) : "f"(hi), "f"(lo)); return r; }
DI uint32_t pack_f16(float lo, float hi) { uint32_t r; asm("cvt.rn.f16x2.f32 %0, %1, %2;" : "=r"(r) : "f"(hi), "f"(lo)); return r; }
DI float ex2(float x) { float y; asm("ex2.approx.ftz.f32 %0, %1;" : "=f"(y) : "f"(x)); return y; }
DI float rcp(float x) { float y; asm("rcp.approx.ftz.f32 %0, %1;" : "=f"(y) : "f"(x)); return y; }
DI float bf_lo(uint32_t x) { return __uint_as_float(x << 16); }
DI float bf_hi(uint32_t x) { return __uint_as_float(x & 0xffff0000u); }
DI void mma16816(float* d, const uint32_t* a, uint32_t b0, uint32_t b1) {
  asm volatile("mma.sync.aligned.m16n8k16.row.col.f32.bf16.bf16.f32 {%0,%1,%2,%3}, {%4,%5,%6,%7}, {%8,%9}, {%0,%1,%2,%3};"
               : "+f"(d[0]), "+f"(d[1]), "+f"(d[2]), "+f"(d[3]) : "r"(a[0]), "r"(a[1]), "r"(a[2]), "r"(a[3]), "r"(b0), "r"(b1));
}
DI void mma16816z(float* d, const uint32_t* a, uint32_t b0, uint32_t b1) {
  asm volatile("mma.sync.aligned.m16n8k16.row.col.f32.bf16.bf16.f32 {%0,%1,%2,%3}, {%4,%5,%6,%7}, {%8,%9}, {%10,%10,%10,%10};"
               : "=f"(d[0]), "=f"(d[1]), "=f"(d[2]), "=f"(d[3]) : "r"(a[0]), "r"(a[1]), "r"(a[2]), "r"(a[3]), "r"(b0), "r"(b1), "f"(0.f));
}
DI void mma1688z(float* d, uint32_t a0, uint32_t a1, uint32_t b0) {
  asm volatile("mma.sync.aligned.m16n8k8.row.col.f32.bf16.bf16.f32 {%0,%1,%2,%3}, {%4,%5}, {%6}, {%7,%7,%7,%7};"
               : "=f"(d[0]), "=f"(d[1]), "=f"(d[2]), "=f"(d[3]) : "r"(a0), "r"(a1), "r"(b0), "f"(0.f));
}
DI void mma1688(float* d, uint32_t a0, uint32_t a1, uint32_t b0) {
  asm volatile("mma.sync.aligned.m16n8k8.row.col.f32.bf16.bf16.f32 {%0,%1,%2,%3}, {%4,%5}, {%6}, {%0,%1,%2,%3};"
               : "+f"(d[0]), "+f"(d[1]), "+f"(d[2]), "+f"(d[3]) : "r"(a0), "r"(a1), "r"(b0));
}
DI void ldsm2t(uint32_t* r, uint32_t a) {
  asm volatile("ldmatrix.sync.aligned.m8n8.x2.trans.shared.b16 {%0,%1}, [%2];" : "=r"(r[0]), "=r"(r[1]) : "r"(a) : "memory");
}
DI uint32_t add_bf16(uint32_t a, uint32_t b) { uint32_t r; asm("add.rn.bf16x2 %0, %1, %2;" : "=r"(r) : "r"(a), "r"(b)); return r; }
DI uint32_t mul_bf16(uint32_t a, uint32_t b) { uint32_t r; asm("mul.rn.bf16x2 %0, %1, %2;" : "=r"(r) : "r"(a), "r"(b)); return r; }
DI uint64_t make_desc(uint32_t addr, uint32_t lbo, uint32_t sbo, uint32_t swz) {
  return (uint64_t)((addr & 0x3FFFF) >> 4) | ((uint64_t)(lbo >> 4) << 16) | ((uint64_t)(sbo >> 4) << 32) | ((uint64_t)swz << 62);
}
DI uint64_t desc_at(uint32_t a16, uint32_t lbo, uint32_t sbo, uint32_t swz) {
  uint64_t d; asm("mov.b64 %0, {%1, %2};" : "=l"(d) : "r"(a16 + ((lbo >> 4) << 16)), "r"((sbo >> 4) | (swz << 30)));
  return d;
}
#define WG_FENCE() asm volatile("wgmma.fence.sync.aligned;" ::: "memory")
#define WG_COMMIT() asm volatile("wgmma.commit_group.sync.aligned;" ::: "memory")
#define WG_WAIT(n) asm volatile("wgmma.wait_group.sync.aligned %0;" :: "n"(n) : "memory")
#define ACC8(d, o) "+f"(d[o]), "+f"(d[o + 1]), "+f"(d[o + 2]), "+f"(d[o + 3]), "+f"(d[o + 4]), "+f"(d[o + 5]), "+f"(d[o + 6]), "+f"(d[o + 7])
DI void wgmma_n32_rs(float* d, uint32_t a0, uint32_t a1, uint32_t a2, uint32_t a3, uint64_t db, int acc) {
  asm volatile("{\n.reg .pred p;\nsetp.ne.b32 p, %21, 0;\n"
               "wgmma.mma_async.sync.aligned.m64n32k16.f32.bf16.bf16 {%0,%1,%2,%3,%4,%5,%6,%7,%8,%9,%10,%11,%12,%13,%14,%15}, "
               "{%16,%17,%18,%19}, %20, p, 1, 1, 0;\n}\n"
               : ACC8(d, 0), ACC8(d, 8) : "r"(a0), "r"(a1), "r"(a2), "r"(a3), "l"(db), "r"(acc));
}
DI void tma_load(uint32_t dst, const CUtensorMap* m, int c0, int c1, uint32_t mb) {
  asm volatile("cp.async.bulk.tensor.2d.shared::cluster.global.mbarrier::complete_tx::bytes [%0], [%1, {%3, %4}], [%2];"
               :: "r"(dst), "l"(m), "r"(mb), "r"(c0), "r"(c1) : "memory");
}
DI void tma_load3(uint32_t dst, const CUtensorMap* m, int row, uint32_t mb) {
  asm volatile("cp.async.bulk.tensor.3d.shared::cluster.global.mbarrier::complete_tx::bytes [%0], [%1, {%3, %4, %3}], [%2];"
               :: "r"(dst), "l"(m), "r"(mb), "r"(0), "r"(row) : "memory");
}
DI bool elect_one() {
  uint32_t p;
  asm volatile("{\n.reg .pred p;\nelect.sync _|p, 0xffffffff;\nselp.u32 %0, 1, 0, p;\n}" : "=r"(p));
  return p;
}
DI void bulk_s2s(uint32_t dst, uint32_t src, uint32_t bytes, uint32_t mb) {
  asm volatile("cp.async.bulk.shared::cluster.shared::cta.mbarrier::complete_tx::bytes [%0], [%1], %2, [%3];"
               :: "r"(dst), "r"(src), "r"(bytes), "r"(mb) : "memory");
}
DI void tma_prefetch(const CUtensorMap* m, int c0, int c1) {
  asm volatile("cp.async.bulk.prefetch.tensor.2d.L2.global.tile [%0, {%1, %2}];" :: "l"(m), "r"(c0), "r"(c1) : "memory");
}
DI void tma_store(const CUtensorMap* m, uint32_t src, int c0, int c1) {
  asm volatile("cp.async.bulk.tensor.2d.global.shared::cta.bulk_group [%0, {%2, %3}], [%1];" :: "l"(m), "r"(src), "r"(c0), "r"(c1) : "memory");
}
DI uint4 ldg_relaxed(const void* p) {
  uint4 v;
  asm volatile("ld.relaxed.gpu.global.v4.b32 {%0,%1,%2,%3}, [%4];" : "=r"(v.x), "=r"(v.y), "=r"(v.z), "=r"(v.w) : "l"(p) : "memory");
  return v;
}
DI void stg_relaxed(void* p, uint32_t x, uint32_t y, uint32_t z, uint32_t w) {
  asm volatile("st.relaxed.gpu.global.v4.b32 [%0], {%1,%2,%3,%4};" :: "l"(p), "r"(x), "r"(y), "r"(z), "r"(w) : "memory");
}
DI void red_f16x8(void* p, uint32_t x, uint32_t y, uint32_t z, uint32_t w) {
  asm volatile("red.relaxed.gpu.global.add.noftz.v4.f16x2 [%0], {%1,%2,%3,%4};" :: "l"(p), "r"(x), "r"(y), "r"(z), "r"(w) : "memory");
}
DI void sq_acc(uint32_t& a, uint32_t x) { asm("fma.rn.bf16x2 %0, %1, %1, %0;" : "+r"(a) : "r"(x)); }
DI __half2 amax4(__half2 h, const uint32_t* v) {
  h = __hmax2_nan(__hmax2_nan(h, __habs2(*(const __half2*)&v[0])), __habs2(*(const __half2*)&v[1]));
  return __hmax2_nan(__hmax2_nan(h, __habs2(*(const __half2*)&v[2])), __habs2(*(const __half2*)&v[3]));
}
DI uint32_t wexp(__half2 h) { const uint32_t u = *(const uint32_t*)&h; return __reduce_max_sync(0xffffffffu, max((u >> 16) & 0x7fffu, u & 0x7fffu)) >> 7; }
DI float max10(const float* a) {
  return fmaxf(fmaxf(fmaxf(fmaxf(a[0], a[1]), fmaxf(a[2], a[3])), fmaxf(fmaxf(a[4], a[5]), fmaxf(a[6], a[7]))), fmaxf(a[8], a[9]));
}
DI float warp_sum(float v) {
#pragma unroll
  for (int o = 16; o; o >>= 1) v += __shfl_xor_sync(0xffffffffu, v, o);
  return v;
}

constexpr int SM_WO3 = 0;
constexpr int SM_X = 16384;
constexpr int XT = 36864;
constexpr int SM_EXP = 126976;
constexpr int SEGB = 10240;
constexpr int SM_BLK = SM_EXP + 8192;
constexpr int SM_VC = SM_BLK + 4 * SEGB;
constexpr int SM_PART = SM_VC + 16384;
constexpr int SM_QM = SM_PART + 4096;
constexpr int SM_E = SM_QM + 1024;
constexpr int SM_VM = SM_E + 1536;
constexpr int SM_OB = SM_VM + 2048;
constexpr int SM_FB = SM_OB + 2048;
constexpr int SM_STAGE = SM_X + XT;
constexpr int SM_MISC = 210944;
constexpr int SM_WOST = 212992;
constexpr int SM_MEM = SM_WOST;
constexpr int SM_MAX = SM_MEM + 11264;
#define MEM_BLK(q) ((q) / 3 * 4096 + (q) % 3 * 1024)
constexpr int SM_TOTAL = 229376;
constexpr int MB_W = SM_MISC;
constexpr int MB_WO = SM_MISC + 24;
constexpr int MB_WO3 = SM_MISC + 32;
constexpr int MB_X = SM_MISC + 40;
constexpr int MB_S = SM_MISC + 64;
constexpr int MB_F = SM_MISC + 72;
constexpr int MB_VX = SM_MISC + 80;
constexpr int SC_FPAR = SM_MISC + 136;
constexpr int SC_DEAD = SM_MISC + 96;
constexpr int SC_UNSC = SM_MISC + 112;
constexpr int SC_EPOCH = SM_MISC + 128;
constexpr int SC_EXPW = SM_MISC + 132;
constexpr int SC_ONES = SM_MISC + 144;
constexpr int SC_SS = SM_MISC + 160;
constexpr int SC_LAT = SM_MISC + 224;
constexpr int MB_T = SM_MISC + 232;
constexpr int T_SX = SM_X + XT;
constexpr int T_OB = SM_X + 2 * XT;
constexpr int T_WA = T_OB + 16384;
constexpr int T_OA = T_WA + 9216;
constexpr int T_P = T_OA + 4096 + 128;
constexpr int T_UN = T_OA + 4096;
constexpr int T_RED = 131072;
constexpr int SC_XMAX = SM_MISC + 256;
constexpr int SC_PROF = 229376;

constexpr float SM_SCALE = 0.08838834764831845f;
constexpr float LOG2E = 1.4426950408889634f;
constexpr float E_LIM = 20.f;

template <bool B> struct BoolC { static constexpr bool value = B; };
struct RMaps { CUtensorMap x, wq, wk, wv, wo, woa, oa; unsigned char* red; bf16* out; uint32_t poll; };

DI uint32_t latest_hint(uint32_t h, uint32_t d, int s) {
  const uint32_t x = (((h | 0xc0c0c0c0u) - ((d >> 5) & 63) * 0x01010101u) & 0x3f3f3f3fu) | ((h ^ (((s >> 2) + 1) & 3) * 0x40404040u) & 0xc0c0c0c0u);
  const uint32_t y = __vmaxu2(x & 0x00ff00ffu, (x >> 8) & 0x00ff00ffu);
  return __reduce_max_sync(0xffffffffu, max(y & 0xffffu, y >> 16));
}
DI uint32_t near_half(uint32_t sb) {
  uint32_t a, b; lds64(sb + SC_LAT, a, b);
  return a > b;
}

template <int RT, int K0, int K1, bool D32 = false>
DI void xproj(float* acc, const uint32_t (&wa)[2][18][4], uint64_t xd) {
  if (XP & 1) return;
  WG_FENCE();
#pragma unroll
  for (int k = K0; k < ((XP & 128) ? K0 + 1 : K1); k++)
  {
    uint64_t d = xd + (uint64_t)(((k >> 1) * 4096 + (k & 1) * 32) >> 4);
    if (D32) asm("mov.b64 %0, {%1, %2};" : "=l"(d) : "r"((uint32_t)xd + (((k >> 1) * 4096 + (k & 1) * 32) >> 4)), "r"((uint32_t)(xd >> 32)));
    wgmma_n32_rs(acc, wa[RT][k][0], wa[RT][k][1], wa[RT][k][2], wa[RT][k][3], d, k != 0);
  }
  WG_COMMIT();
}

DI void seg_store(int seg, uint32_t sb, uint32_t off, uint32_t bytes) {
  asm volatile("cp.async.bulk.global.shared::cta.bulk_group [%0], [%1], %2;"
               :: "l"(g_seg + ((size_t)(seg % NRING) * 96 + blockIdx.x) * SEGB + off), "r"(sb + SM_BLK + (seg & 3) * SEGB + off), "r"(bytes) : "memory");
  asm volatile("cp.async.bulk.commit_group;" ::: "memory");
}
DI void seg_publish(int seg) {
  asm volatile("cp.async.bulk.wait_group 0;" ::: "memory");
  asm volatile("red.relaxed.gpu.global.add.u32 [%0], 1;" :: "l"(&g_scnt[(seg * 32 + blockIdx.x / 3) * 8]) : "memory");
  SSTAMP(10, seg);
}

#define NAP 64
DI uint32_t movm(uint32_t x) { uint32_t r; asm volatile("movmatrix.sync.aligned.m8n8.trans.b16 %0, %1;" : "=r"(r) : "r"(x)); return r; }
DI bool wait_count(const unsigned* p, unsigned target, bool nap = true) {
  int n = 0;
  unsigned v;
  while (true) {
    asm volatile("ld.acquire.gpu.global.b32 %0, [%1];" : "=r"(v) : "l"(p) : "memory");
    if ((int)(v - target) >= 0 || ++n > SPIN_LIMIT) break;
    if (nap) __nanosleep(NAP);
  }
  return n;
}
#define PACE 1200
#define PACE2 600
#define PACE3 (3 * PACE)
DI void load_weights(uint32_t sb, const RMaps& tm, uint32_t rank, int c) {
  const int h = blockIdx.x / 3;
  if (c < 3) {
    mbar_expect(sb + MB_W + 8 * c, 49152);
    tma_load(sb + SM_STAGE + c * 49152, rank < 2 ? &tm.wk : &tm.wv, h * DH + (rank == 1 ? 64 : 0), c * 192, sb + MB_W + 8 * c);
    tma_load(sb + SM_STAGE + c * 49152 + 24576, rank < 2 ? &tm.wq : &tm.wv, h * DH + (rank == 0 ? 0 : 64), c * 192, sb + MB_W + 8 * c);
  } else {
    tma_prefetch(&tm.wo, rank * 192, h * DH);
    mbar_expect(sb + MB_WO, 16384);
    mbar_expect(sb + MB_WO3, 32768);
    tma_load(sb + SM_WOST, &tm.wo, rank * 192 + 64, h * DH, sb + MB_WO3);
    tma_load(sb + SM_WO3, &tm.wo, rank * 192 + 128, h * DH, sb + MB_WO3);
  }
}

DI void tail_attention(const uint32_t sb, const uint32_t rank, const int w, const int lane, const int sg, const int bar) {
  const int m = lane >> 3, g = lane >> 2, t = lane & 3;
  const uint32_t l16 = sb + lane * 16, src = l16 + T_SX + sg * 10240 + w * 1280;
  const float2 gt = __ldcg((const float2*)&g_gate[(NAUXSEG + sg) * 32 + w * 8 + 2 * t]);
  if (rank < 2) {
    const uint32_t base = l16 + SM_BLK + (2 + sg) * SEGB, dst = src + rank * 5120;
    uint32_t qb[2][4];
    ldsm4t(qb[0], base + w * 1024); ldsm4t(qb[1], base + w * 1024 + 512);
#pragma unroll
    for (int j = 0; j < 3; j++) {
      uint32_t kb[4][4];
      float c[4][4];
      const uint32_t ka = base + 4096 + j * 2048 + (m & 1) * (j == 2 ? 128 : 896) - (m >> 1) * 128;
#pragma unroll
      for (int k = 0; k < 4; k += j == 2 ? 2 : 1) ldsm4t(kb[k], ka + k * 256);
      mma16816z(c[0], kb[0], qb[0][0], qb[0][1]); mma16816z(c[1], kb[j == 2 ? 0 : 1], qb[0][2], qb[0][3]);
      mma16816z(c[2], kb[2], qb[1][0], qb[1][1]); mma16816z(c[3], kb[j == 2 ? 2 : 3], qb[1][2], qb[1][3]);
      uint32_t r[4];
#pragma unroll
      for (int i = 0; i < (j == 2 ? 2 : 4); i++) r[i] = __float_as_uint((c[0][i] + c[1][j == 2 ? i + 2 : i]) + (c[2][i] + c[3][j == 2 ? i + 2 : i]));
#pragma unroll
      for (int d = 0; d < 2; d++) {
        const uint32_t to = d ? 2 : rank ^ 1, mb = mapa(sb + MB_T + 8 + 8 * sg, to);
        if (j < 2) st_async4(mapa(dst + j * 512, to), r[0], r[1], r[2], r[3], mb);
        else st_async2(mapa(dst + 1024 - lane * 8, to), r[0], r[1], mb);
      }
      if (j < 2) sts128(dst + j * 512, r[0], r[1], r[2], r[3]); else sts64(dst + 1024 - lane * 8, r[0], r[1]);
    }
  }
  TSTAMP(50 + 2 * sg);
  uint32_t vx[4][4], vm[4];
  const uint32_t va = l16 + (rank < 2 ? SM_VC + sg * 8192 : SM_BLK + (2 + sg) * SEGB) + w * 1024 + (m & 1) * 384 - (m >> 1) * 128;
#pragma unroll
  for (int i = 0; i < 4; i++) ldsm4(vx[i], va + (i & 1) * 4096 + (i >> 1) * 256);
  if (sg && rank < 2) mbar_wait(sb + MB_T, 0);
  lds128(l16 + (sg ? SM_FB : SM_VM) + w * 512, vm);
  float a[10], b[10];
  mbar_wait(sb + MB_T + 8 + 8 * sg, 0);
  TSTAMP(58 + 2 * sg);
  lds128f(src, a); lds128f(src + 512, a + 4); lds64f(src + 1024 - lane * 8, a + 8);
  lds128f(src + 5120, b); lds128f(src + 5632, b + 4); lds64f(src + 6144 - lane * 8, b + 8);
#pragma unroll
  for (int i = 0; i < 10; i++) {
    a[i] = (a[i] + b[i]) * (SM_SCALE * LOG2E);
    if (i < 8 && (i >> 1) * 8 + g > w * 8 + 2 * t + (i & 1)) a[i] = -1.0e9f * LOG2E;
  }
  float m0 = fmaxf(fmaxf(fmaxf(a[0], a[2]), fmaxf(a[4], a[6])), a[8]), m1 = fmaxf(fmaxf(fmaxf(a[1], a[3]), fmaxf(a[5], a[7])), a[9]);
#pragma unroll
  for (int o = 4; o < 32; o <<= 1) { m0 = fmaxf(m0, __shfl_xor_sync(0xffffffffu, m0, o)); m1 = fmaxf(m1, __shfl_xor_sync(0xffffffffu, m1, o)); }
#pragma unroll
  for (int i = 0; i < 10; i++) a[i] = ex2(a[i] - (i & 1 ? m1 : m0));
  float s0 = ((a[0] + a[2]) + (a[4] + a[6])) + a[8], s1 = ((a[1] + a[3]) + (a[5] + a[7])) + a[9];
#pragma unroll
  for (int o = 4; o < 32; o <<= 1) { s0 += __shfl_xor_sync(0xffffffffu, s0, o); s1 += __shfl_xor_sync(0xffffffffu, s1, o); }
  s0 = (1.f - gt.x) * rcp(s0); s1 = (1.f - gt.y) * rcp(s1);
#pragma unroll
  for (int i = 0; i < 5; i++) sts32(sb + T_P + sg * 2560 + w * 640 + i * 128 + lane * 4, pack_bf16(a[2 * i] * s0, a[2 * i + 1] * s1));
  bar_sync(bar, 128);
  TSTAMP(59 + 2 * sg);
#pragma unroll
  for (int j = 0; j < 4; j++) {
    uint32_t p[5];
    float o0[4], o1[4];
    ldsm4t(p, l16 + T_P + sg * 2560 + j * 640);
    asm volatile("ldmatrix.sync.aligned.m8n8.x1.trans.shared.b16 {%0}, [%1];" : "=r"(p[4]) : "r"(l16 + T_P + sg * 2560 + j * 640 + 512) : "memory");
    mma16816z(o0, vx[0], p[0], p[1]); mma16816z(o1, vx[1], p[0], p[1]);
    mma16816(o0, vx[2], p[2], p[3]); mma16816(o1, vx[3], p[2], p[3]);
    mma1688(o0, vm[0], vm[1], p[4]); mma1688(o1, vm[2], vm[3], p[4]);
    stsm4(l16 + T_OB + sg * 8192 + j * 2048 + w * 512, pack_bf16(o0[0], o0[1]), pack_bf16(o0[2], o0[3]), pack_bf16(o1[0], o1[1]), pack_bf16(o1[2], o1[3]));
  }
}

DI void proj_role(const uint32_t sb, const RMaps& tm, const uint32_t rank, const int wg, const int w, const int lane) {
  const bool qk = rank < 2;
  uint32_t wa[2][18][4];
  {
    const int rr = (lane & 7) + ((lane >> 4) << 3);
    const uint32_t col = ((2 * w + ((lane >> 3) & 1)) ^ (lane & 7)) << 4;
    float ss = 0.f;
#pragma unroll
    for (int c = 0; c < 3; c++) {
      mbar_wait(sb + MB_W + 8 * c, 0);
      if (threadIdx.x == 0) SSTAMP(11, c);
#pragma unroll
      for (int rt = 0; rt < 2; rt++)
#pragma unroll
        for (int k = 0; k < 6; k++)
          ldsm4t(wa[rt][c * 6 + k], sb + SM_STAGE + c * 49152 + (rt ^ wg) * 24576 + (64 * (k >> 1) + 32 * wg + 16 * (k & 1) + rr) * 128 + col);
      if (c < 2) {
        fence_async();
        bar_sync(3, 256);
        if (threadIdx.x == 0) {
          if (c == 0) tma_load3(sb + SM_X + XT, &tm.x, 32, sb + MB_X + 8);
          else { tma_load(sb + SM_X + 2 * XT, &tm.wo, rank * 192, (blockIdx.x / 3) * DH, sb + MB_WO); SSTAMP(11, 11); }
        }
        __syncwarp();
      }
      uint32_t q[4] = {0, 0, 0, 0};
#pragma unroll
      for (int rt = 0; rt < 2; rt++)
#pragma unroll
        for (int k = 0; k < 6; k++)
#pragma unroll
          for (int i = 0; i < 4; i++) sq_acc(q[i], wa[rt][c * 6 + k][i]);
#pragma unroll
      for (int i = 0; i < 4; i++) ss += bf_lo(q[i]) + bf_hi(q[i]);
    }
    ss = warp_sum(ss);
    fence_async();
    cluster_arrive();
    if (lane == 0) sts32(sb + SC_SS + 4 * (wg * 4 + w), qk ? 0 : __float_as_uint(ss));
    bar_arrive(11, 384);
  }
  STAMP(1);
  MSTAMP(0);
  mbar_wait(sb + MB_X, 0);
  STAMP(2);

  uint32_t t16 = sb + (w * 32 + lane) * 16;
  uint32_t mem_a = sb + SM_MEM + wg * 512 + lane * 16;
  uint32_t fin_a = sb + (lane & 7) * 16 + SM_BLK + (qk ? (wg ^ 1) * 4096 + w * 256 + (lane & 8) * 16 + (lane & 16) * 64
                                              : wg * 4096 + w * 1024 + (lane & 8) * 64 + (lane & 16) * 8);
  PIN(t16); PIN(mem_a); PIN(fin_a);
  const uint32_t fence_reg = mem_a;
  const uint32_t fin2 = qk ? 2048 : 256;
  float acc[16];
  const uint64_t xd0 = make_desc(sb + SM_X + wg * 64, 16, 1024, 1);
  auto do_export = [&]() {
    WG_WAIT(0);
    uint32_t q[8];
#pragma unroll
    for (int j = 0; j < 8; j++) q[j] = pack_bf16(acc[2 * j], acc[2 * j + 1]);
    sts128(t16 + SM_EXP + wg * 4096, q[0], q[1], q[2], q[3]);
    sts128(t16 + SM_EXP + wg * 4096 + 2048, q[4], q[5], q[6], q[7]);
    asm volatile("{\n.reg .pred p;\nsetp.eq.u32 p, %2, 0;\n@p add.u32 %0, %0, 1;\n@p add.u32 %1, %1, 1;\nsetp.eq.and.u32 p, %0, %1, p;\n@p exit;\n}"
                          : "+r"(q[3]), "+r"(q[7]) : "r"(t16) : "memory");
  };
  uint32_t o[8];
  auto import = [&]() { lds128(t16 + SM_EXP + (wg ^ 1) * 4096, o); lds128(t16 + SM_EXP + (wg ^ 1) * 4096 + 2048, o + 4); };
  auto finish = [&](int seg) {
    const uint32_t a = fin_a + (seg & 3) * SEGB;
    WG_WAIT(0);
#pragma unroll
    for (int i = 0; i < 8; i++) o[i] = add_bf16(pack_bf16(acc[2 * i], acc[2 * i + 1]), o[i]);
    stsm4(a, o[0], o[1], o[2], o[3]);
    stsm4(a + fin2, o[4], o[5], o[6], o[7]);
  };
  auto send_v = [&](int seg, int dst) {
    fence_async();
    if (seg < NSEG && !(XP & 2) && elect_one())
      bulk_s2s(mapa(sb + SM_VC + (seg & 1) * 8192, dst), sb + SM_BLK + (seg & 3) * SEGB, 8192, mapa(sb + MB_VX + (seg & 1) * 8, dst));
    __syncwarp();
  };
  auto wait_v = [&](int seg) {
    if (seg < NSEG && !(XP & 2)) {
      mbar_wait(sb + MB_VX + (seg & 1) * 8, (seg >> 1) & 1);
      if (elect_one()) mbar_expect(sb + MB_VX + (seg & 1) * 8, 8192);
      __syncwarp();
    }
  };
  bar_sync(3, 256);
  xproj<1, 0, 18>(acc, wa, xd0);
  do_export();
  SCHED_FENCE(11);
  xproj<0, 0, 18>(acc, wa, xd0);
  bar_sync(3, 256);
  if (threadIdx.x == 0) SSTAMP(11, 12);
  MSTAMP(1);
  cluster_wait();
  if (threadIdx.x == 0) SSTAMP(11, 13);
  mbar_wait(sb + MB_X + 8, 0);
  import();
  finish(0);
  SCHED_FENCE(12);
  bar_sync(3, 256);
  uint64_t dA = xd0 + (XT >> 4);
  xproj<1, 0, 18>(acc, wa, dA);
  if (!qk && wg == 0 && w < 2) send_v(0, w);
  do_export();
  if (qk && wg == 0 && w == 0) wait_v(0);
  bar_arrive(13, 384);
  if (!qk) {
    SCHED_FENCE(15);
    xproj<0, 0, 18>(acc, wa, dA);
    if (threadIdx.x == 0 && !(XP & 8)) { mbar_expect(sb + MB_X, XT); tma_load3(sb + SM_X, &tm.x, 96, sb + MB_X); }
    bar_sync(3, 256);
    mbar_wait(sb + MB_X + 16, 0);
    import();
    finish(1);
    SCHED_FENCE(16);
    bar_sync(3, 256);
    dA += XT >> 4;
    xproj<1, 0, 18>(acc, wa, dA);
    if (wg == 0 && w == 0) send_v(1, 0);
    do_export();
  }
  if (threadIdx.x == 0) SSTAMP(11, 14);
  MSTAMP(2);
  bar_sync(0, 384);
  const int ro = __shfl_sync(0xffffffffu, near_half(sb) ^ wg, 0);
  STAMP(5);
  const uint32_t always = __shfl_sync(0xffffffffu, lds32(sb + SC_DEAD + 12), 0);
  const int ah = qk ? 1 : 2;
  int b2 = qk ? 2 : 0;
  int s = 0;
  uint32_t hint_lo = (uint32_t)(uint64_t)tm.red + HINT_OFF + blockIdx.x + (lane & 1) * 4096 + (lane >> 1) * 16384;
  PIN(hint_lo);
  auto post_hint = [&]() {
    asm volatile("{\n.reg .pred p;\n.reg .b64 a;\n.reg .u32 t;\nsetp.lt.u32 p, %0, %1;\nmov.b64 a, {%2, %3};\nmov.u32 t, %%globaltimer_lo;\n"
                 "bfe.u32 t, t, 5, 6;\nor.b32 t, t, %4;\n@p st.relaxed.gpu.global.u8 [a], t;\n}"
                 :: "r"(t16), "r"(sb + 128), "r"(hint_lo + RED_SLOT(s)), "r"((uint32_t)((uint64_t)tm.red >> 32)), "r"(((s >> 2) + 1) << 6) : "memory");
  };
  auto memproj = [&](auto second, int id, float u0, float u1, float* r) {
    constexpr bool R1 = decltype(second)::value;
    uint32_t b[NUP][4], b0[4];
    SCHED_FENCE(id);
    bar_sync(R1 ? 2 : 1, 256);
    PROF(0);
    ldsm4t(b0, mem_a);
#pragma unroll
    for (int q = 0; q < NUP; q++) {
      if (R1 && q == 2) {
        bar_sync(11, 256);
        SCHED_FENCE(id + 1);
      }
      ldsm4t(b[q], mem_a + MEM_BLK(q + 1));
    }
    mma16816z(&acc[0], wa[0][0], b0[0], b0[1]);
    mma16816z(&acc[4], wa[1][0], b0[0], b0[1]);
    mma16816z(&acc[8], wa[0][1], b0[2], b0[3]);
    mma16816z(&acc[12], wa[1][1], b0[2], b0[3]);
#pragma unroll
    for (int q = 1; q < 9; q++) {
      uint32_t* const c = b[(q - 1) % NUP];
      mma16816(&acc[0], wa[0][2 * q], c[0], c[1]);
      mma16816(&acc[4], wa[1][2 * q], c[0], c[1]);
      mma16816(&acc[8], wa[0][2 * q + 1], c[2], c[3]);
      mma16816(&acc[12], wa[1][2 * q + 1], c[2], c[3]);
      if (R1 && q + NUP == B3Q) bar_sync(3, 256);
      if (q + NUP < 9) ldsm4t_in(c, mem_a + MEM_BLK(q + NUP), always);
      else if (R1 && q + NUP < 11) lds128_in(c, t16 + SM_PART + (10 - q - NUP) * 2048, always);
      else if (!R1 && GATE && q == GATE) { bar_arrive(11, 256); lds128_in(c, sb + SC_DEAD, always); u0 = u1 = __uint_as_float(c[3]); }
    }
#pragma unroll
    for (int i = 0; i < 8; i++) {
      const float u = i < 4 ? u0 : u1;
      r[i] = R1 ? fmaf(acc[8 + i], u, (acc[i] + __uint_as_float(b[(8 + i / 4) % NUP][i & 3])) * u) : (GATE ? fmaf(acc[i], u, acc[8 + i]) : acc[i] + acc[8 + i]);
    }
  };
  if (ro == 0) {
    auto set_scale = [&]() {
      uint32_t m[8];
      lds128(t16 + SM_MAX - 512, m); lds128(t16 + SM_MAX, m + 4);
      const int em = (wexp(amax4(amax4(*(const __half2*)&m[0], m), m + 4)) >> 3) + (int)(lds32(sb + SC_UNSC + (s & 1) * 8) >> 23) - 15;
      const int ex = max(s ? em : 0, (int)lds32(sb + SC_XMAX + 4 * s)) - 127 + (int)lds32(sb + SC_EXPW);
      sts32(sb + SC_UNSC + (~s & 1) * 8, (127 + min(max(ex, -120), 120)) << 23);
    };
#pragma unroll 1
    while (true) {
      if (s == 8) STAMP(6);
      float r[8];
      memproj(BoolC<false>(), 30, 0.f, 0.f, r);
      sts128(t16 + SM_PART, __float_as_uint(r[0]), __float_as_uint(r[1]), __float_as_uint(r[2]), __float_as_uint(r[3]));
      sts128(t16 + SM_PART + 2048, __float_as_uint(r[4]), __float_as_uint(r[5]), __float_as_uint(r[6]), __float_as_uint(r[7]));
      bar_arrive(3, 256);
      PROF(1);
      bar_sync(9, 256);
      if (s == NSEG - 1) break;
      post_hint();
      if (w == 1) {
        set_scale();
        __syncwarp();
        if (elect_one()) mbar_arrive(sb + MB_S);
      }
      SCHED_FENCE(9);
      bar_sync(5, qk ? N5 : 256);
      PROF(2);
      import();
      xproj<0, 0, NII>(acc, wa, dA);
      if (qk) bar_sync(7, 384);
      xproj<0, NII, 18>(acc, wa, dA);
      if (!qk) bar_sync(7, 384);
      dA += (int64_t)(b2 ? XT >> 4 : -(XT >> 3));
      finish(s + ah);
      if (qk || w != 0) bar_arrive(13, 384);
      PROF(6);
      SCHED_FENCE(14);
      bar_sync(12, 256);
      PROF(7);
      xproj<1, 0, 18, true>(acc, wa, dA);
      bar_arrive(14, 256);
      b2 = b2 == 2 ? 0 : b2 + 1;
      s++;
      if (!qk && w == 0) { bar_sync(13, 384); send_v(s + 1, w); }
      PROFP(8);
      do_export();
      s--; RSTAMP(6); s++;
      PROFP(3);
    }
    if (!qk) bar_arrive(5, 256);
    if (w == 0 && elect_one()) {
      const uint32_t h18 = blockIdx.x / 3 * 18;
      mbar_expect(sb + MB_WO, 9216 + 4096);
      tma_load(sb + T_OA, &tm.oa, 4096 + (h18 & ~7), NAUXSEG * 32, sb + MB_WO);
#pragma unroll 1
      for (int j = 0; j < 3; j++) tma_load(sb + T_WA + j * 3072, &tm.woa, rank * 192 + j * 64, h18, sb + MB_WO);
    }
    if (w == 1) {
      const int ea = (int)ldg_relaxed32(&g_amax[0]) + (int)ldg_relaxed32(&g_amax[16]) - 254 + 2 + 10 - 15;
      set_scale();
      __syncwarp();
      sts32(sb + T_UN + (lane & 1) * 4, (128 + max(min(ea, 120), (int)(lds32(sb + SC_UNSC + 8 - (lane & 1) * 8) >> 23) - 127)) << 23);
    }
    bar_arrive(8, 256);
  } else {
    uint32_t r0;
    float un;
    auto prepare = [&]() {
      un = __uint_as_float(lds32(sb + SC_UNSC + (s & 1) * 8));
      r0 = qk ? (t16 & ~256u) - w * 256 + (((t16 >> 8) ^ wg) & 1 ? SM_QM : SM_BLK + 8192 + (s & 3) * SEGB) : mapa(t16 + (s < NSEG - 1 ? SM_VM : SM_FB), 0);
      PIN(r0); PIN(un);
    };
    auto mem_out = [&](int off, uint32_t lo, uint32_t hi) {
      unsigned char* const d = g_seg + ((size_t)(s % NRING) * 96 + blockIdx.x) * SEGB + 8192 + off + w * 256 + ((t16 >> 2) & 124);
      if (!(XP & 4)) { stg_relaxed32(d, lo); stg_relaxed32(d + 128, hi); }
    };
    prepare();
#pragma unroll 1
    while (true) {
      if (s == 8) STAMP(6);
      float r[8];
      if (qk) {
        const float u0 = wg ? un * (SM_SCALE * LOG2E) : un, u1 = wg ? un : un * (SM_SCALE * LOG2E);
        memproj(BoolC<true>(), 32, u0, u1, r);
        const uint32_t p0 = pack_bf16(r[0], r[1]), p1 = pack_bf16(r[2], r[3]), p2 = pack_bf16(r[4], r[5]), p3 = pack_bf16(r[6], r[7]);
        stsm4(r0, p0, p1, p2, p3);
        bar_arrive(4, 256);
        SCHED_FENCE(18);
        mem_out(0, wg ? p2 : p0, wg ? p3 : p1);
      } else {
        const uint32_t mb = sb + (s < NSEG - 1 ? MB_S : MB_T), r1 = r0 + (1 << 24);
        memproj(BoolC<true>(), 34, un, un, r);
        const uint32_t p0 = pack_bf16(r[0], r[1]), p1 = pack_bf16(r[2], r[3]), p2 = pack_bf16(r[4], r[5]), p3 = pack_bf16(r[6], r[7]);
        const uint32_t v0 = wg ? p2 : p0, v1 = wg ? p3 : p1, v2 = wg ? p0 : p2, v3 = wg ? p1 : p3;
        st_async4(r0, v0, v1, v2, v3, mapa(mb, 0));
        st_async4(r1, v0, v1, v2, v3, mapa(mb, 1));
        bar_arrive(5, 256);
        sts128(r0 + (2 << 24), v0, v1, v2, v3);
        stsm4((t16 & ~256u) - w * 256 + SM_BLK + 8192 + (s & 3) * SEGB + (((t16 >> 8) ^ wg) & 1) * 1024, p0, p1, p2, p3);
        __syncwarp();
        if (elect_one()) mbar_arrive(sb + MB_S);
        __syncwarp();
        SCHED_FENCE(19);
        mem_out(0, v0, v1); mem_out(1024, v2, v3);
      }
      if (s == NSEG - 1) break;
      PROF(1);
      auto rearm = [&]() { mbar_wait(sb + MB_S, s & 1); if (elect_one()) mbar_expect(sb + MB_S, qk ? 640 + 2048 : 1280); __syncwarp(); };
      if (w == 1) {
        if ((t16 & 384) == 0) stg_relaxed(tm.red + (RED_SLOT(s + 2) + RED_LINE(blockIdx.x)) + (t16 & 112), 0, 0, 0, 0);
      } else if (w == 0) {
        const int tn = s + ah + 1;
        if (tn + 1 < NSEG && !(XP & 8) && elect_one()) {
          const int b0 = b2 == 2 ? 0 : b2 + 1;
          mbar_expect(sb + MB_X + 8 * b0, XT);
          tma_load3(sb + SM_X + b0 * XT, &tm.x, (tn + 1) * 32, sb + MB_X + 8 * b0);
        }
        if (tn < NSEG && (!(XP & 8) || tn < 3)) mbar_wait(sb + MB_X + 8 * b2, (tn / 3) & 1);
      } else if (w == 2) {
        if (!qk) send_v(s + 1, 1);
      } else {
        rearm();
      }
      __syncwarp();
      import();
      PROF(4);
      SCHED_FENCE(10);
      bar_sync(7, 384);
      xproj<0, 0, 18>(acc, wa, dA);
      bar_arrive(12, 256);
      dA += (int64_t)(b2 ? XT >> 4 : -(XT >> 3));
      finish(s + ah);
      if (qk && w == 0) wait_v(s + 1);
      bar_arrive(13, 384);
      PROF(6);
      SCHED_FENCE(13);
      bar_sync(14, 256);
      PROF(7);
      xproj<1, 0, 18>(acc, wa, dA);
      b2 = b2 == 2 ? 0 : b2 + 1;
      s++;
      PROFP(8);
      do_export();
      prepare();
      s--; RSTAMP(7); s++;
      PROFP(3);
    }
    TSTAMP(2);
    bar_sync(3, 128);
    tail_attention(sb, rank, w, lane, 1, 3);
    bar_arrive(0, 256);
  }
  STAMP(3);
  STAMP(4);
}

DI void attn_role(const uint32_t sb, unsigned char* smem_raw, const RMaps& tm, const uint32_t RANK, const bf16* __restrict__ x, const bf16* __restrict__ mem0,
                  const int w, const int lane) {
  const int t2 = w * 32 + lane;
  uint32_t wo[8][4], w1[8][4];
  const uint32_t wo_lane = sb + ((lane & 7) + ((lane >> 4) << 3)) * 128 + (((w + 4 * ((lane >> 3) & 1)) ^ (lane & 7)) << 4);
  unsigned char* const g_red = tm.red;
  {
    const uint32_t t0 = gtime();
    const uint32_t tag = *(volatile unsigned*)&g_epoch + 1;
    if (w == 0) {
      stg_relaxed(g_red + RED_SLOT(t2 >> 3) + RED_LINE(blockIdx.x) + (t2 & 7) * 16, 0, 0, 0, 0);
      stg_relaxed(g_red + T_RED + blockIdx.x * 1024 + t2 * 16, 0, 0, 0, 0);
      stg_relaxed(g_red + T_RED + blockIdx.x * 1024 + 512 + t2 * 16, 0, 0, 0, 0);
      asm volatile("st.relaxed.gpu.global.u8 [%0], 0;" :: "l"(g_red + RED_SLOT(t2) + HINT_OFF + (t2 & 4) * 1024 + (t2 >> 3) * 16384 + blockIdx.x) : "memory");
    }
    bar_sync(0, 384);
    cluster_arrive();
    if (PACE && w == 3) {
#pragma unroll 1
      for (int c = 1; c < 4; c++) {
        wait_until(t0 + (c == 3 ? PACE3 : c * (RANK < 2 ? PACE : PACE2)));
        if (elect_one()) load_weights(sb, tm, RANK, c);
        __syncwarp();
      }
    }
    uint4 xv[18];
    uint32_t mv[20];
#pragma unroll
    for (int i = 0; i < 20; i++) mv[i] = i < 18 ? ((const uint32_t*)mem0)[(lane >> 2) * (DM / 2) + (w * 18 + i) * 4 + (lane & 3)] : 0;
#pragma unroll
    for (int i = 0; i < 18; i++) xv[i] = blockIdx.x < NSEG ? ((const uint4*)(x + blockIdx.x * 32 * DM))[t2 + 128 * i] : make_uint4(0, 0, 0, 0);
    __half2 hx = __float2half2_rn(0.f);
#pragma unroll
    for (int i = 0; i < 18; i++) hx = amax4(hx, &xv[i].x);
    if (blockIdx.x == 0)
#pragma unroll
      for (int i = 0; i < 5; i++) hx = amax4(hx, &mv[4 * i]);
    sts32(sb + SC_SS + 4 * (12 + w), wexp(hx));
    if (t2 == 0) { sts32(sb + SC_EPOCH, (tag - 1) * NSEG + 2 - NRING); sts32(sb + SC_UNSC, __float_as_uint(1.f)); sts128(sb + SC_DEAD, 0, 0, 0, 0x3f800000u); sts64(sb + SC_FPAR, 0, 0); sts128(sb + SC_ONES, 0x3f803f80u, 0x3f803f80u, 0x3f803f80u, 0x3f803f80u); }
    WSTAMP(27);
    if (w == 0) __threadfence();
    uint32_t q[8] = {0, 0, 0, 0, 0, 0, 0, 0};
    mbar_wait(sb + MB_WO3, 0);
    if (t2 == 0) SSTAMP(11, 3);
    MSTAMP(3);
#pragma unroll
    for (int k = 0; k < 8; k++) {
      ldsm4t(wo[k], wo_lane + SM_WO3 + k * 2048); ldsm4t(w1[k], wo_lane + SM_WOST + k * 2048);
#pragma unroll
      for (int i = 0; i < 4; i++) { sq_acc(q[i], wo[k][i]); sq_acc(q[i], w1[k][i]); }
    }
    bar_sync(6, 128);
    if (t2 == 0) SSTAMP(11, 7);
#pragma unroll
    for (int k = 0; k < 8; k++) sts128(sb + SM_WO3 + t2 * 16 + k * 2048, wo[k][0], wo[k][1], wo[k][2], wo[k][3]);
#pragma unroll
    for (int i = 0; i < 5; i++) {
      const int j = w * 18 + 4 * i + (lane >> 3), c = i < 4 || lane < 16 ? j * 8 + j / 24 * 64 : 192;
      stsm4t(sb + SM_MEM + (c + (lane & 7)) * 16, mv[4 * i], mv[4 * i + 1], mv[4 * i + 2], mv[4 * i + 3]);
    }
    bar_arrive(1, 256); bar_arrive(2, 256); bar_arrive(9, 256);
    if (t2 == 0) SSTAMP(11, 8);
    mbar_wait(sb + MB_WO, 0);
    if (t2 == 0) SSTAMP(11, 4);
#pragma unroll
    for (int k = 0; k < 8; k++) ldsm4t(wo[k], wo_lane + SM_X + 2 * XT + k * 2048);
    fence_async();
    bar_sync(6, 128);
    if (t2 == 32) tma_load3(sb + SM_X + 2 * XT, &tm.x, 64, sb + MB_X + 16);
    __syncwarp();
#pragma unroll
    for (int k = 0; k < 8; k++)
#pragma unroll
      for (int i = 0; i < 4; i++) sq_acc(q[4 + i], wo[k][i]);
    float ss = 0.f;
#pragma unroll
    for (int i = 0; i < 8; i++) ss += bf_lo(q[i]) + bf_hi(q[i]);
    ss = warp_sum(ss);
    if (lane == 0) sts32(sb + SC_SS + 4 * (8 + w), __float_as_uint(ss));
    if (t2 == 0) SSTAMP(11, 9);
    bar_sync(11, 384);
    if (t2 == 0) SSTAMP(11, 10);
    if (t2 == 0) {
      float a[16];
#pragma unroll
      for (int i = 0; i < 4; i++) lds128f(sb + SC_SS + 16 * i, &a[4 * i]);
      stg_relaxed(&g_stats[blockIdx.x * 2], __float_as_uint(((a[0] + a[1]) + (a[2] + a[3])) + ((a[4] + a[5]) + (a[6] + a[7]))),
                  __float_as_uint((a[8] + a[9]) + (a[10] + a[11])),
                  max(max(__float_as_uint(a[12]), __float_as_uint(a[13])), max(__float_as_uint(a[14]), __float_as_uint(a[15]))), tag);
    }
    __syncwarp();
    WSTAMP(24);
    MSTAMP(4);
    cluster_wait();
    if (w == 0) {
      uint4 v[3];
      int n = 0;
      while (true) {
#pragma unroll
        for (int i = 0; i < 3; i++) v[i] = ldg_relaxed(&g_stats[(i * 32 + lane) * 2]);
        if (__all_sync(0xffffffffu, v[0].w == tag && v[1].w == tag && v[2].w == tag) || ++n > SPIN_LIMIT) break;
        __nanosleep(100);
      }
      WSTAMP(25);
      MSTAMP(5);
      const float sv = warp_sum(__uint_as_float(v[0].x) + __uint_as_float(v[1].x) + __uint_as_float(v[2].x));
      const float so = warp_sum(__uint_as_float(v[0].y) + __uint_as_float(v[1].y) + __uint_as_float(v[2].y));
      const int expW = ((int)(__float_as_uint(sv) >> 23) + (int)(__float_as_uint(so) >> 23) - 254 + 2 + 10 + 1) >> 1;
      sts32(sb + SC_XMAX + 4 * lane, v[0].z); sts32(sb + SC_XMAX + 128 + 4 * lane, v[1].z);
      sts32(sb + SC_EXPW, expW + 1 - 15);
      if (blockIdx.x == 0 && lane == 0) *(volatile unsigned*)&g_epoch = tag;
    } else if (w < 3) {
      const uint32_t u = blockIdx.x >> 4;
      unsigned char* const z = g_red + 98304 + (blockIdx.x & 15) * 128 + (u & 1) * 2048 + (u & 6) * 4096 + (((u >> 1) ^ w) & 1) * 4096 + lane * 4;
      stg_relaxed32(z, 0);
      uint32_t best = 0xffffffffu;
#pragma unroll 1
      for (int i = 0; i < NPROBE; i++) {
        uint32_t dt;
        asm volatile("{\n.reg .pred p;\n.reg .u32 c, v;\nmov.u32 c, %%clock;\natom.relaxed.gpu.global.exch.b32 v, [%1], 0;\n"
                     "setp.eq.u32 p, v, 0;\nmov.u32 %0, 0;\n@p mov.u32 %0, %%clock;\nsub.u32 %0, %0, c;\n}" : "=r"(dt) : "l"(z) : "memory");
        best = min(best, dt);
      }
      sts32(sb + SC_LAT + (w - 1) * 4, best);
    }
    bar_sync(13, 384);
    bar_arrive(0, 384);
    WSTAMP(26);
    TSTAMP(1);
    MSTAMP(6);
  }

  const uint32_t nh = __shfl_sync(0xffffffffu, near_half(sb), 0);
  uint32_t l16 = sb + lane * 16;
  PIN(l16);
#define LV ((l16 >> 4) & 31)
#define fence_reg l16
  const uint32_t red_lo = (uint32_t)(uint64_t)g_red, red_hi = (uint32_t)((uint64_t)g_red >> 32);
  uint32_t lp;
  auto slot = [&](int s, uint32_t c, uint32_t ofs) {
    const uint32_t lo = lp | (red_lo + ((w >> 1) * 4 + (w & 1) * 2 + ((w ^ c) & 1)) * 4096 + RED_SLOT(s) + ofs);
    uint64_t a; asm("mov.b64 %0, {%1, %2};" : "=l"(a) : "r"(lo), "r"(red_hi));
    return (unsigned char*)a;
  };
  const uint32_t always = __shfl_sync(0xffffffffu, lds32(sb + SC_DEAD + 12), 0);
  const int mode0 = RANK < 2 ? w : w | 4;
  auto hint_addr = [&](int s) { return min(LV, 23u) * 4 + (red_lo + HINT_OFF + nh * 4096 + w * 16384 + RED_SLOT(s)); };
  auto load_hints = [&](uint32_t lo) {
    uint64_t a; asm("mov.b64 %0, {%1, %2};" : "=l"(a) : "r"(lo), "r"(red_hi));
    return ldg_relaxed32((const void*)a);
  };
  int s = 0;
  uint32_t dl = __shfl_sync(0xffffffffu, gtime() - 768, 0);
  uint32_t vx[4][4];
  auto load_vx = [&](int s) {
    const uint32_t va = l16 + (RANK < 2 ? SM_VC + (s & 1) * 8192 : SM_BLK + (s & 3) * SEGB) + w * 1024 + ((LV >> 3) & 1) * 384 - (LV >> 4) * 128;
#pragma unroll
    for (int i = 0; i < 4; i++) ldsm4(vx[i], va + (i & 1) * 4096 + (i >> 1) * 256);
  };
  load_vx(0);
  bool bad = false;
#pragma unroll 1
  while (true) {
    const uint32_t par = s & 1;
    uint32_t oc[4], hints;
    hints = hint_addr(s);
    PIN(hints);
    auto retire = [&](uint32_t x) {
      asm volatile("{\n.reg .pred p;\nsetp.eq.u32 p, %0, 0;\n@p exit;\n}" :: "r"(vx[0][0] | vx[1][0] | vx[2][0] | vx[3][0] | x) : "memory");
    };
    auto scores = [&](auto memkeys, auto first, float* sc) {
      constexpr bool MK = decltype(memkeys)::value, FIRST = decltype(first)::value;
      uint32_t kb[4][4], qb[2][4];
      const uint32_t m = LV >> 3;
      uint32_t kaddr = l16 + SM_BLK + 4096 + (s & 3) * SEGB + w * 2048 + (m & 1) * (MK ? 128 : 896) - (m >> 1) * 128;
      if (MK) { PIN(kaddr); }
      else {
#pragma unroll
        for (int k = 0; k < 4; k++) ldsm4t(kb[k], kaddr + k * 256);
      }
      if (FIRST) { retire(MK ? kaddr : kb[0][0] | kb[1][0] | kb[2][0] | kb[3][0] | l16); bar_sync(4, 256); RSTAMP(4); PROF(4); }
      ldsm4t(qb[0], l16 + SM_QM);
      if (MK) ldsm4t(kb[0], kaddr);
      ldsm4t(qb[1], l16 + SM_QM + 512);
      if (MK) ldsm4t(kb[2], kaddr + 512);
      float c[4][4];
      mma16816z(c[0], kb[0], qb[0][0], qb[0][1]); mma16816z(c[1], kb[MK ? 0 : 1], qb[0][2], qb[0][3]);
      mma16816z(c[2], kb[2], qb[1][0], qb[1][1]); mma16816z(c[3], kb[MK ? 2 : 3], qb[1][2], qb[1][3]);
      if (FIRST) bar_arrive(5, N5);
#pragma unroll
      for (int i = 0; i < (MK ? 2 : 4); i++) sc[i] = ((c[0][i] + c[1][MK ? i + 2 : i]) + c[2][i]) + c[3][MK ? i + 2 : i];
    };
    auto send = [&](auto memkeys) {
      constexpr bool MK = decltype(memkeys)::value;
      constexpr int N = MK ? 1 : 2;
      const uint32_t sa = sb + LV * 4 + SM_E + (MK ? 1024 + RANK * 128 : RANK * 512 + w * 256);
      uint32_t ra[N][2], mb[N][2];
#pragma unroll
      for (int i = 0; i < N; i++)
#pragma unroll
        for (int j = 0; j < 2; j++) {
          ra[i][j] = mapa(sa + i * 128, j ? 2 : RANK ^ 1); mb[i][j] = mapa(sb + MB_S, j ? 2 : RANK ^ 1);
          PIN(ra[i][j]);
        }
      float sc[4];
      scores(memkeys, BoolC<true>(), sc);
      uint32_t e[N];
#pragma unroll
      for (int i = 0; i < N; i++) {
        e[i] = pack_bf16(ex2(sc[2 * i]), ex2(sc[2 * i + 1]));
        if (!(fmaxf(fabsf(sc[2 * i]), fabsf(sc[2 * i + 1])) <= E_LIM)) e[i] = 0x7fff7fffu;
        st_async1(ra[i][0], e[i], mb[i][0]);
        st_async1(ra[i][1], e[i], mb[i][1]);
      }
#pragma unroll
      for (int i = 0; i < N; i++) sts32(sa + i * 128, e[i]);
      __syncwarp();
      if (l16 == sb) mbar_arrive(sb + MB_S);
      PROF(5);
    };
    const int mode = bad ? 8 : mode0;
    if (mode < 2) {
      send(BoolC<false>());
    } else if (mode == 2) {
      send(BoolC<true>());
    } else if (mode == 8) {
      load_vx(s);
      retire(l16);
      const uint32_t fp = lds32(sb + SC_FPAR);
      bar_sync(6, 128);
      if (w == 0 && l16 == sb) { sts32(sb + SC_FPAR, fp ^ 1); mbar_expect(sb + MB_F, 3072); }
      if (RANK < 2 && w < 3) {
        float sc[4] = {0.f, 0.f, 0.f, 0.f};
        if (w < 2) scores(BoolC<false>(), BoolC<false>(), sc); else scores(BoolC<true>(), BoolC<false>(), sc);
#pragma unroll 1
        for (int r = 0; r < 3; r++)
          st_async4(mapa(l16 + SM_FB + RANK * 1536 + w * 512, r), __float_as_uint(sc[0]), __float_as_uint(sc[1]), __float_as_uint(sc[2]), __float_as_uint(sc[3]), mapa(sb + MB_F, r));
      }
      mbar_wait(sb + MB_F, fp);
      float a[12];
#pragma unroll
      for (int j = 0; j < 3; j++) {
        float b[4];
        lds128f(l16 + SM_FB + j * 512, a + 4 * j); lds128f(l16 + SM_FB + 1536 + j * 512, b);
#pragma unroll
        for (int i = 0; i < 4; i++) a[4 * j + i] += b[i];
      }
      float m0 = fmaxf(fmaxf(fmaxf(a[0], a[2]), fmaxf(a[4], a[6])), a[8]), m1 = fmaxf(fmaxf(fmaxf(a[1], a[3]), fmaxf(a[5], a[7])), a[9]);
#pragma unroll
      for (int o = 4; o < 32; o <<= 1) { m0 = fmaxf(m0, __shfl_xor_sync(0xffffffffu, m0, o)); m1 = fmaxf(m1, __shfl_xor_sync(0xffffffffu, m1, o)); }
#pragma unroll
      for (int i = 0; i < 5; i++) {
        const uint32_t ea = sb + SM_E + LV * 4 + (i < 4 ? i * 128 : 1024);
        sts32(ea, pack_bf16(ex2(a[2 * i] - m0), ex2(a[2 * i + 1] - m1)));
        sts32(ea + (i < 4 ? 512 : 128), 0x3f803f80u);
      }
      __syncwarp();
    } else {
      if (mode == 3) bar_arrive(4, 256);
      retire(l16 + 1);
      if (w == 3) {
        uint32_t used = ldg_relaxed32(&g_used[blockIdx.x / 3 * 32]);
        if (!(XP & 4) && elect_one()) {
          if (s > 0) seg_publish(s - 1);
          fence_async();
          seg_store(s, sb, 0, 8192);
        }
        __syncwarp();
        const uint32_t need = lds32(sb + SC_EPOCH) + (s >= NRING - 1 ? s : -4 * NSEG);
#pragma unroll 1
        for (int n = 0; (int)(used - need) < 0 && n < ((XP & 64) ? (int)(used == 0x12345) : SPIN_LIMIT); n++) used = ldg_relaxed32(&g_used[blockIdx.x / 3 * 32]);
      }
    }
    {
      constexpr int WS = 2048;
      const uint32_t w3a = l16 + SM_WO3 + w * 512;
      lds128(sb + SC_ONES, oc);
      uint32_t e[10], p[5], vm[4], ob[4];
      float o0[4], o1[4], f[3][2][4], rs[4];
      mbar_wait_fast(sb + MB_S, par);
      RSTAMP(5);
      PROF(6);
      ldsm4t(e, l16 + SM_E); ldsm4t(e + 4, l16 + SM_E + 512); ldsm2t(e + 8, l16 + SM_E + 1024);
      lds128(l16 + w * 512 + SM_VM, vm);
      const float scl = __uint_as_float(lds32(sb + SC_UNSC + 8 - par * 8));
      hints = load_hints(hints);
#pragma unroll
      for (int i = 0; i < 4; i++) p[i] = mul_bf16(e[i], e[4 + i]);
      p[4] = mul_bf16(e[8], e[9]);
      mma16816z(o0, vx[0], p[0], p[1]);
      lds128_in(vx[0], w3a + KP(0) * WS, always);
      mma16816z(o1, vx[1], p[0], p[1]);
      lds128_in(vx[1], w3a + KP(1) * WS, always);
      {
        float u0[4], u1[4];
        mma16816z(u0, vx[2], p[2], p[3]); lds128_in(vx[2], w3a + KP(2) * WS, always);
        mma16816z(u1, vx[3], p[2], p[3]); lds128_in(vx[3], w3a + KP(3) * WS, always);
        mma16816z(rs, oc, p[0], p[1]);
        mma1688(o0, vm[0], vm[1], p[4]); mma1688(o1, vm[2], vm[3], p[4]);
        mma16816(rs, oc, p[2], p[3]);
#pragma unroll
        for (int i = 0; i < 4; i++) { o0[i] += u0[i]; o1[i] += u1[i]; }
      }
      stsm4(l16 + w * 512 + SM_OB, pack_bf16(o0[0], o0[1]), pack_bf16(o0[2], o0[3]), pack_bf16(o1[0], o1[1]), pack_bf16(o1[2], o1[3]));
      mma1688(rs, oc[0], oc[1], p[4]);
      bar_sync(6, 128);
      RSTAMP(3);
      PROF(7);
      ldsm4t_in(oc, l16 + SM_OB, always);
      bad = __any_sync(0xffffffffu, !(rs[0] + rs[1] > 0.f) && !bad);
      rs[0] *= scl; rs[1] *= scl;
      asm volatile("{\n.reg .pred p;\nsetp.ne.u32 p, %1, 0;\n@p rcp.approx.ftz.f32 %0, %0;\n}" : "+f"(rs[0]) : "r"(always));
      asm volatile("{\n.reg .pred p;\nsetp.ne.u32 p, %1, 1;\n@p rcp.approx.ftz.f32 %0, %0;\n}" : "+f"(rs[1]) : "r"(always));
      asm volatile("lop3.b32 %0, %1, %2, %3, 0xfe;" : "=r"(lp) : "r"((l16 & 128) * 2), "r"((l16 & 256) * 4), "r"(l16 & 112));
      if (bad) continue;
      ldsm4t(ob, l16 + SM_OB + 512);
      mma16816z(f[2][0], vx[0], oc[0], oc[1]); mma16816z(f[2][1], vx[1], oc[2], oc[3]);
      mma16816z(f[0][0], wo[0], oc[0], oc[1]); mma16816z(f[0][1], wo[4], oc[2], oc[3]);
      mma16816z(f[1][0], w1[0], oc[0], oc[1]); mma16816z(f[1][1], w1[4], oc[2], oc[3]);
      ldsm4t_in(oc, l16 + SM_OB + 1024, always);
      mma16816(f[2][0], vx[2], ob[0], ob[1]); lds128_in(vx[2], w3a + KP(4) * WS, always);
      mma16816(f[2][1], vx[3], ob[2], ob[3]); lds128_in(vx[3], w3a + KP(5) * WS, always);
      mma16816(f[0][0], wo[1], ob[0], ob[1]); mma16816(f[0][1], wo[5], ob[2], ob[3]);
      mma16816(f[1][0], w1[1], ob[0], ob[1]); mma16816(f[1][1], w1[5], ob[2], ob[3]);
      ldsm4t_in(ob, l16 + SM_OB + 1536, always);
      mma16816(f[0][0], wo[2], oc[0], oc[1]); mma16816(f[0][1], wo[6], oc[2], oc[3]);
      mma16816(f[2][0], vx[2], oc[0], oc[1]); lds128_in(vx[2], w3a + KP(6) * WS, always);
      mma16816(f[2][1], vx[3], oc[2], oc[3]); lds128_in(vx[3], w3a + KP(7) * WS, always);
      mma16816(f[1][0], w1[2], oc[0], oc[1]); mma16816(f[1][1], w1[6], oc[2], oc[3]);
      mma16816(f[0][0], wo[3], ob[0], ob[1]); mma16816(f[0][1], wo[7], ob[2], ob[3]);
      mma16816(f[1][0], w1[3], ob[0], ob[1]); mma16816(f[1][1], w1[7], ob[2], ob[3]);
      mma16816(f[2][0], vx[2], ob[0], ob[1]); mma16816(f[2][1], vx[3], ob[2], ob[3]);
      bar_arrive(7, 384);
      lds128_in(ob, sb + SC_DEAD, always);
      uint32_t h[3][2];
#pragma unroll
      for (int j = 0; j < 3; j++)
#pragma unroll
        for (int i = 0; i < 2; i++)
        {
          scale_sum(f[j][1][2 * i], f[j][0][2 * i], rs[0], always); scale_sum(f[j][1][2 * i + 1], f[j][0][2 * i + 1], rs[1], always);
          h[j][i] = pack_f16(f[j][1][2 * i], f[j][1][2 * i + 1]);
        }
      const uint32_t rofs = RANK * 32768;
      red_f16x8(slot(s, RANK >> 1, rofs), h[0][0], h[1][0], h[2][0], 0x3c00u);
      red_f16x8(slot(s, (RANK >> 1) ^ 1, rofs), h[0][1], h[1][1], h[2][1], 0x3c00u);
      SCHED_FENCE(5);
      RSTAMP(0);
      l16 += ob[1];
    }
    {
    PROF(8);
    const uint32_t ma0 = l16 + SM_MEM + w * 128 + (LV >> 3) * 896 + nh * 512;
    const unsigned char* const sl[2] = {slot(s, nh, 0), slot(s, nh ^ 1, 0)};
    uint32_t late = latest_hint(hints, dl, s);
    if (late >= 64) {
      int n = 0;
#pragma unroll 1
      do {
        late = latest_hint(load_hints(hint_addr(s)), dl, s);
      } while (late >= 64 && ++n < SPIN_LIMIT);
    }
    dl += late * 32 + tm.poll;
    if (s == 0 && PSTAMP) MSTAMP(7);
    PROF(9);
    {
      auto wait_until = [&](uint32_t t) {
        asm volatile("{\n.reg .pred p;\n.reg .s32 c;\n.reg .u64 t;\nTL: mov.u64 t, %%globaltimer;\ncvt.u32.u64 c, t;\nsub.s32 c, c, %0;\nsetp.lt.s32 p, c, 0;\n@p bra.uni TL;\n}" :: "r"(t + (l16 & 15)) : "memory");
      };
      uint4 v[2][3];
      auto load = [&](int c) {
#pragma unroll
        for (int r = 0; r < 3; r++) v[c][r] = ldg_relaxed(sl[c ^ (r >> 1)] + r * 32768);
      };
      auto decode = [&](int c, int n) {
        uint32_t q[9];
        __half2 hm;
        const uint32_t ma = ma0 ^ (c * 512);
#pragma unroll
        for (int i = 0; i < 9; i++) {
          const uint32_t h = i % 3 == 0 ? v[c][i / 3].x : (i % 3 == 1 ? v[c][i / 3].y : v[c][i / 3].z);
          const float2 f = __half22float2(*(const __half2*)&h);
          q[i] = pack_bf16(f.x, f.y);
          hm = i ? __hmax2(hm, __habs2(*(const __half2*)&h)) : __habs2(*(const __half2*)&h);
        }
#pragma unroll
        for (int r = 0; r < 3; r++) stsm4(ma + r * 4096, q[3 * r], q[3 * r + 1], q[3 * r + 2], r < 2 ? v[c][r].w : *(const uint32_t*)&hm);
        const bool done = __all_sync(0xffffffffu, v[c][0].w == 0x5000u && v[c][1].w == 0x5000u && v[c][2].w == 0x5000u) || n > SPIN_LIMIT;
        asm volatile("{\n.reg .pred p;\nsetp.ne.u32 p, %0, 0;\n@p bar.arrive %1, 256;\n}" :: "r"((int)done), "r"(1 + c) : "memory");
        return done;
      };
      wait_until(dl);
      PROF(10);
      int n = 0;
#pragma unroll 1
      do {
        load(0);
        load(1);
        asm volatile("{\n.reg .pred p;\nsetp.eq.u32 p, %0, 0;\n@p bar.sync 13, 384;\n}" :: "r"(n) : "memory");
      } while (!decode(0, n++));
      load_vx(s + 1);
      PROF(11);
      RSTAMP(1);
#pragma unroll 1
      while (!decode(1, n++)) load(1);
      bar_arrive(9, 256);
      RSTAMP(2);
      PROF(12);
    }
    PROF(13);
    if (++s == NSEG - 1) break;
    }
  }
#undef fence_reg
  if (RANK < 2) bar_arrive(4, 256);
  TSTAMP(49);
  {
    PIN(l16);
    tail_attention(sb, RANK, w, LV, 0, 6);
    TSTAMP(51);
    mbar_wait(sb + MB_WO, 1);
    TSTAMP(53);
#pragma unroll 1
    for (int sg = 0; sg < 2; sg++) {
      PIN(l16);
      const int lane = LV, m = lane >> 3, g = lane >> 2, t = lane & 3;
      const uint32_t ob = l16 + T_OB + sg * 8192;
      bar_sync(sg ? 0 : 8, 256);
      TSTAMP(54 + 2 * sg);
      const float inv = __uint_as_float(0x7f000000u - lds32(sb + T_UN + sg * 4));
#pragma unroll 1
      for (int j = 0; j < 4; j += 2) {
        float c[2][3][4];
        uint32_t x[4], y[4], z[2][4];
#pragma unroll
        for (int e = 0; e < 2; e++) {
          const uint32_t oa = sb + T_OA + ((sg * 4 + j + e) * 8 + g) * 64 + (blockIdx.x / 3 * 36 & 15) + t * 4;
          z[e][0] = lds32(oa); z[e][1] = lds32(oa + 16); z[e][2] = t ? 0u : lds32(oa + 32);
        }
#pragma unroll
        for (int i = 0; i < 3; i++) {
          const uint32_t wa = sb + T_WA + ((lane & 7) + ((lane >> 4) << 3)) * 128 + (((w + 4 * (m & 1)) ^ (lane & 7)) << 4);
          ldsm4t(x, wa + i * 3072); ldsm2t(y, wa + i * 3072 + 2048);
#pragma unroll
          for (int e = 0; e < 2; e++) { mma1688z(c[e][i], y[0], y[1], z[e][2]); mma16816(c[e][i], x, z[e][0], z[e][1]); }
        }
#pragma unroll
        for (int r = 0; r < 4; r++) {
          ldsm4t(z[0], ob + j * 2048 + r * 512); ldsm4t(z[1], ob + j * 2048 + 2048 + r * 512);
          lds128(l16 + SM_WO3 + w * 512 + r * 2048, x); lds128(l16 + SM_WO3 + w * 512 + (r + 4) * 2048, y);
#pragma unroll
          for (int e = 0; e < 2; e++) { mma16816(c[e][0], wo[r], z[e][0], z[e][1]); mma16816(c[e][1], w1[r], z[e][0], z[e][1]); mma16816(c[e][2], x, z[e][0], z[e][1]); }
#pragma unroll
          for (int e = 0; e < 2; e++) { mma16816(c[e][0], wo[r + 4], z[e][2], z[e][3]); mma16816(c[e][1], w1[r + 4], z[e][2], z[e][3]); mma16816(c[e][2], y, z[e][2], z[e][3]); }
        }
#pragma unroll
        for (int i = 0; i < 4; i++) {
          const float (&d)[3][4] = c[i >> 1];
          const int q = (i & 1) * 2;
          red_f16x8(g_red + T_RED + ((((sg * 4 + j + (i >> 1)) * 3 + RANK) * 4 + w) * 2 + (i & 1)) * 512 + lane * 16, pack_f16(d[0][q] * inv, d[0][q + 1] * inv),
                    pack_f16(d[1][q] * inv, d[1][q + 1] * inv), pack_f16(d[2][q] * inv, d[2][q + 1] * inv), 0x3c00u);
        }
      }
      TSTAMP(55 + 2 * sg);
    }
    if (w < 2) {
      const int b = blockIdx.x, lane = LV, g = lane >> 2, t = lane & 3;
      uint4 v;
#pragma unroll 1
      for (int n = 0; n < SPIN_LIMIT; n++) {
        v = ldg_relaxed(g_red + T_RED + (w * 96 + b) * 512 + lane * 16);
        if (__all_sync(0xffffffffu, v.w == 0x5000u)) break;
        __nanosleep(40);
      }
      const float un = __uint_as_float(lds32(sb + T_UN + w * 4));
      uint32_t* const o = (uint32_t*)(tm.out + (size_t)((NAUXSEG + w) * 32 + b / 24 * 8 + g) * DM + (b >> 3) % 3 * 192 + (b & 1) * 32 + (b & 6) * 4) + t;
#pragma unroll
      for (int j = 0; j < 3; j++) {
        const float2 f = __half22float2(*(const __half2*)(&v.x + j));
        o[j * 32] = movm(pack_bf16(f.x * un, f.y * un));
      }
    }
  }
  TSTAMP(3);
  MSTAMP(8);
}

__global__ void __cluster_dims__(3, 1, 1) __launch_bounds__(384, 1)
rec_kernel(const __grid_constant__ RMaps tm, const bf16* __restrict__ x, const bf16* __restrict__ mem0) {
  extern __shared__ __align__(1024) unsigned char smem_raw[];
  const uint32_t sb = smem_u32(smem_raw);
  const int tid = threadIdx.x, lane = tid & 31;
  const int wg = __shfl_sync(0xffffffffu, tid >> 7, 0);
  const int w = __shfl_sync(0xffffffffu, (tid >> 5) & 3, 0);
  uint32_t rank; asm("mov.u32 %0, %%cluster_ctarank;" : "=r"(rank));
  STAMP(0);
  TSTAMP(0);
  asm volatile("griddepcontrol.launch_dependents;" ::: "memory");

  if (wg == 1 && lane == 0) asm volatile("prefetch.tensormap [%0];\nprefetch.tensormap [%1];" :: "l"(w & 1 ? &tm.woa : &tm.oa), "l"(w == 0 ? (rank < 2 ? &tm.wk : &tm.wv) : w == 1 ? &tm.wq : w == 2 ? &tm.x : &tm.wo) : "memory");
  if (wg < 2) {
    asm volatile("setmaxnreg.inc.sync.aligned.u32 192;");
    if (tid == 0) {
      for (int i = 0; i < 3; i++) { mbar_init(sb + MB_W + 8 * i, 1); mbar_init(sb + MB_X + 8 * i, 1); }
      mbar_init(sb + MB_WO, 1); mbar_init(sb + MB_WO3, 1);
      mbar_init(sb + MB_S, rank < 2 ? 5 : 6);
      mbar_init(sb + MB_F, 1);
      for (int i = 0; i < 3; i++) mbar_init(sb + MB_T + 8 * i, 1);
      mbar_init(sb + MB_VX, 1); mbar_init(sb + MB_VX + 8, 1);
      asm volatile("fence.mbarrier_init.release.cluster;" ::: "memory");
      fence_async();
      SSTAMP(11, 6);
      load_weights(sb, tm, rank, 0);
      for (int i = 0; i < 3; i++) mbar_expect(sb + MB_X + 8 * i, XT);
      tma_load3(sb + SM_X, &tm.x, 0, sb + MB_X);
      if (!PACE) for (int c = 1; c < 4; c++) load_weights(sb, tm, rank, c);
      mbar_expect(sb + MB_S, rank < 2 ? 640 + 2048 : 1280);
      mbar_expect(sb + MB_VX, 8192); mbar_expect(sb + MB_VX + 8, 8192);
      mbar_expect(sb + MB_T, 2048);
      for (int i = 1; i < 3; i++) mbar_expect(sb + MB_T + 8 * i, rank < 2 ? 5120 : 10240);
      SSTAMP(11, 5);
    }
    __syncwarp();
    bar_sync(0, 384);
    proj_role(sb, tm, rank, wg, w, lane);
  } else {
    asm volatile("setmaxnreg.dec.sync.aligned.u32 120;");
    attn_role(sb, smem_raw, tm, rank, x, mem0, w, lane);
  }
}

constexpr int A_XH = 73728;
constexpr int A_NS = 9, A_WM = 6144, A_WT = 768;
constexpr int A_RING = 2 * A_XH, A_TAIL = A_RING + A_NS * A_WM, A_GW = A_TAIL + A_NS * A_WT;
constexpr int A_EPI = 212864, A_EPW = 9344;
constexpr int A_XW = 4 * XT, A_XT = A_XW + 4096, A_NR = 4;
constexpr int A_IN = A_XT + 2048, A_INS = 2 * 9216 + SEGB, A_OST = A_IN + 2 * A_INS;
constexpr int A_GATE = A_EPI + 2 * A_EPW, A_BAR = A_GATE + 512;
constexpr int A_TOTAL = A_BAR + 384;
struct AMaps { CUtensorMap x, wa, wt, oa, o, o3, o8, wob, woa, wo8; };

DI void wgmma_n192_ss_nt(float* d, uint64_t da, uint64_t db, int acc) {
  asm volatile("{\n.reg .pred p;\nsetp.ne.b32 p, %98, 0;\n"
               "wgmma.mma_async.sync.aligned.m64n192k16.f32.bf16.bf16 {"
               "%0,%1,%2,%3,%4,%5,%6,%7,%8,%9,%10,%11,%12,%13,%14,%15,%16,%17,%18,%19,%20,%21,%22,%23,%24,%25,%26,%27,%28,%29,%30,%31,"
               "%32,%33,%34,%35,%36,%37,%38,%39,%40,%41,%42,%43,%44,%45,%46,%47,%48,%49,%50,%51,%52,%53,%54,%55,%56,%57,%58,%59,%60,%61,%62,%63,"
               "%64,%65,%66,%67,%68,%69,%70,%71,%72,%73,%74,%75,%76,%77,%78,%79,%80,%81,%82,%83,%84,%85,%86,%87,%88,%89,%90,%91,%92,%93,%94,%95"
               "}, %96, %97, p, 1, 1, 0, 1;\n}\n"
               : ACC8(d, 0), ACC8(d, 8), ACC8(d, 16), ACC8(d, 24), ACC8(d, 32), ACC8(d, 40), ACC8(d, 48), ACC8(d, 56),
                 ACC8(d, 64), ACC8(d, 72), ACC8(d, 80), ACC8(d, 88) : "l"(da), "l"(db), "r"(acc));
}
#define ACC4(d, o) "+f"(d[o]), "+f"(d[o + 1]), "+f"(d[o + 2]), "+f"(d[o + 3])
DI void wgmma_n24_ss_nt(float* d, uint64_t da, uint64_t db, int acc) {
  asm volatile("{\n.reg .pred p;\nsetp.ne.b32 p, %14, 0;\n"
               "wgmma.mma_async.sync.aligned.m64n24k16.f32.bf16.bf16 {%0,%1,%2,%3,%4,%5,%6,%7,%8,%9,%10,%11}, %12, %13, p, 1, 1, 0, 1;\n}\n"
               : ACC8(d, 0), ACC4(d, 8) : "l"(da), "l"(db), "r"(acc));
}
DI void wgmma_n8_ss(float* d, uint64_t da, uint64_t db, int acc) {
  asm volatile("{\n.reg .pred p;\nsetp.ne.b32 p, %6, 0;\n"
               "wgmma.mma_async.sync.aligned.m64n8k16.f32.bf16.bf16 {%0,%1,%2,%3}, %4, %5, p, 1, 1, 0, 0;\n}\n"
               : ACC4(d, 0) : "l"(da), "l"(db), "r"(acc));
}
DI void wgmma_n40_ss_tt(float* d, uint64_t da, uint64_t db, int acc) {
  asm volatile("{\n.reg .pred p;\nsetp.ne.b32 p, %22, 0;\n"
               "wgmma.mma_async.sync.aligned.m64n40k16.f32.bf16.bf16 {%0,%1,%2,%3,%4,%5,%6,%7,%8,%9,%10,%11,%12,%13,%14,%15,%16,%17,%18,%19}, "
               "%20, %21, p, 1, 1, 1, 1;\n}\n"
               : ACC8(d, 0), ACC8(d, 8), ACC4(d, 16) : "l"(da), "l"(db), "r"(acc));
}
DI void wgmma_n64_rs(float* d, const uint32_t* a, uint64_t db, int acc) {
  asm volatile("{\n.reg .pred p;\nsetp.ne.b32 p, %37, 0;\n"
               "wgmma.mma_async.sync.aligned.m64n64k16.f32.bf16.bf16 {"
               "%0,%1,%2,%3,%4,%5,%6,%7,%8,%9,%10,%11,%12,%13,%14,%15,%16,%17,%18,%19,%20,%21,%22,%23,%24,%25,%26,%27,%28,%29,%30,%31"
               "}, {%32,%33,%34,%35}, %36, p, 1, 1, 0;\n}\n"
               : ACC8(d, 0), ACC8(d, 8), ACC8(d, 16), ACC8(d, 24) : "r"(a[0]), "r"(a[1]), "r"(a[2]), "r"(a[3]), "l"(db), "r"(acc));
}
DI void wgmma_n32_ss_tn(float* d, uint64_t da, uint64_t db, int acc) {
  asm volatile("{\n.reg .pred p;\nsetp.ne.b32 p, %18, 0;\n"
               "wgmma.mma_async.sync.aligned.m64n32k16.f32.bf16.bf16 {%0,%1,%2,%3,%4,%5,%6,%7,%8,%9,%10,%11,%12,%13,%14,%15}, "
               "%16, %17, p, 1, 1, 1, 0;\n}\n"
               : ACC8(d, 0), ACC8(d, 8) : "l"(da), "l"(db), "r"(acc));
}
DI void tma_load3c(uint32_t dst, const CUtensorMap* m, int c0, int c1, int c2, uint32_t mb) {
  asm volatile("cp.async.bulk.tensor.3d.shared::cluster.global.mbarrier::complete_tx::bytes [%0], [%1, {%3, %4, %5}], [%2];"
               :: "r"(dst), "l"(m), "r"(mb), "r"(c0), "r"(c1), "r"(c2) : "memory");
}
DI void count_up(unsigned* p) {
  asm volatile("fence.proxy.async;" ::: "memory");
  asm volatile("red.release.gpu.global.add.u32 [%0], 1;" :: "l"(p) : "memory");
}
#define AX 0
#define FDLY 400
#define FEND 59
DI void publish(unsigned* p) {
  asm volatile("cp.async.bulk.wait_group 0;\nfence.proxy.async;" ::: "memory");
  asm volatile("red.relaxed.gpu.global.add.u32 [%0], 1;" :: "l"(p) : "memory");
}
#define SER 35
#define LAG0 12
#define LEND 58
#define ADLY 0

__global__ void __launch_bounds__(512, 1)
aux_kernel(const __grid_constant__ AMaps tm, const bf16* __restrict__ wqkv, const bf16* __restrict__ woa, const bf16* __restrict__ gate_w, bf16* __restrict__ out) {
  extern __shared__ __align__(1024) unsigned char smem_raw[];
  const uint32_t sb = smem_u32(smem_raw);
  const uint32_t fullx = sb + A_BAR, full1 = fullx + 24, empty1 = full1 + 8 * A_NS, fullw = empty1 + 8 * A_NS, full3 = fullw + 8, empty3 = full3 + 8 * A_NR,
                 fullq = empty3 + 8 * A_NR, emptyq = fullq + 24, fullo = emptyq + 24, emptyo = fullo + 16;
  const int tid = threadIdx.x, lane = tid & 31, cta = blockIdx.x;
  const int wg = __shfl_sync(0xffffffffu, tid >> 7, 0), w = __shfl_sync(0xffffffffu, (tid >> 5) & 3, 0);
  ASTAMP(14);
  if (tid == 384) {
    for (int i = 0; i < 3; i++) mbar_init(fullx + 8 * i, 1);
    for (int i = 0; i < A_NS; i++) { mbar_init(full1 + 8 * i, 1); mbar_init(empty1 + 8 * i, 8); }
    mbar_init(fullw, 1);
    for (int i = 0; i < 3; i++) { mbar_init(fullq + 8 * i, 1); mbar_init(emptyq + 8 * i, 4); }
    for (int i = 0; i < 2; i++) { mbar_init(fullo + 8 * i, 4); mbar_init(emptyo + 8 * i, 1); }
    for (int i = 0; i < A_NR; i++) { mbar_init(full3 + 8 * i, 1); mbar_init(empty3 + 8 * i, cta < NH ? 8 : 4); }
    fence_async();
  }
  __syncthreads();
  ASTAMP(0);
  const int tile = cta >> 1, hh = cta & 1;
  auto p3_n = [&](int g) { return cta < NH ? (cta & 3) * 2 + g : 8; };
  auto p3_next = [&](int& sl, int& ph) {
    sl += cta < NH ? 1 : 2;
    if (sl >= (cta < NH ? 3 : 4)) { sl -= cta < NH ? 3 : 4; ph ^= 1; }
  };
  auto p3_k = [&](int g) { return cta < NH ? cta >> 2 : (cta & 3) * 2 + g; };
  if (wg == 3) {
    asm volatile("setmaxnreg.dec.sync.aligned.u32 24;");
    const bool lead = lane == 0;
    if (w < 3) {
      if (ADLY) wait_until(gtime() + ADLY);
      if (elect_one()) {
        mbar_expect(fullx + 8 * w, 49152);
        for (int p = 0; p < 2; p++)
          asm volatile("cp.async.bulk.tensor.4d.shared::cluster.global.mbarrier::complete_tx::bytes [%0], [%1, {%3, %4, %5, %6}], [%2];"
                       :: "r"(sb + p * A_XH + w * 24576), "l"(&tm.x), "r"(fullx + 8 * w), "r"(0), "r"(p), "r"(57 * tile - 7), "r"(3 * w) : "memory");
      }
#pragma unroll 1
      for (int r = 0; r < 17; r++) {
#pragma unroll 1
        for (int st = w; st < A_NS; st += 3) {
          if (r > 0) mbar_wait(empty1 + 8 * st, ~r & 1);
          if (r < 16 && elect_one()) {
            const int col = hh * 288 + (r >> 2) * 72, row = (r & 3) * 144 + st * 16;
            mbar_expect(full1 + 8 * st, A_WM + (AX & 1 ? 0 : A_WT));
            tma_load3c(sb + A_RING + st * A_WM, &tm.wa, col, row, 0, full1 + 8 * st);
            if (!(AX & 1)) tma_load3c(sb + A_TAIL + st * A_WT, &tm.wt, col + 64, row, 0, full1 + 8 * st);
          }
          __syncwarp();
        }
        if (r == 0 && elect_one())
          for (int j = 0; j < 3; j++)
            asm volatile("cp.async.bulk.prefetch.L2.global [%0], %1;" :: "l"((const char*)wqkv + cta * 55296 + (w * 3 + j) * 6144), "r"(6144) : "memory");
        __syncwarp();
      }
      bar_sync(8, 96);
    }
    const unsigned epoch = lds32(sb + A_BAR + 376);
    if (w == 2 && cta < NH) {
      if (lead) {
        int avail = 0, q = 0, ph = 1;
#pragma unroll 1
        for (int seg = 0; seg < NAUXSEG; seg++) {
          const unsigned char* const src = g_seg + ((size_t)(AX & 128 ? 0 : seg % NRING) * 96 + cta * 3) * SEGB;
          SSTAMP(0, seg);
          const int ref = seg + max(LAG0 * (LEND - seg) / LEND, 0);
          if (ref >= avail) {
            const unsigned* const c = &g_scnt[(ref * 32 + cta) * 8];
            const int c2 = ldg_relaxed32(c + 512) - 3 * (epoch + 1), c0 = ldg_acquire32(c) - 3 * (epoch + 1);
            avail = ref + (c2 >= 0 ? 3 : 1);
            if (c0 < 0) {
              wait_count(c, 3 * (epoch + 1), seg < NAUXSEG - 2);
              if (FDLY && seg < FEND) wait_until(gtime() + FDLY);
            }
          }
          SSTAMP(1, seg);
          const uint32_t mb = fullq + q * 8;
          mbar_wait(emptyq + q * 8, q == 2 ? ph ^ 1 : ph);
          if (AX & 8) mbar_arrive(mb); else mbar_expect(mb, A_INS);
#pragma unroll 1
          for (int r = 0; r < ((AX & 8) ? 0 : 3); r++)
            asm volatile("cp.async.bulk.shared::cluster.global.mbarrier::complete_tx::bytes [%0], [%1], %2, [%3];"
                         :: "r"(sb + (q < 2 ? A_IN + q * A_INS : 3 * XT) + r * 9216), "l"(src + r * SEGB), "r"(r < 2 ? 9216 : SEGB), "r"(mb) : "memory");
          if (seg == 1) wait_count(&g_abar[32], NAUX * (epoch + 1));
          if (seg > 1) stg_relaxed32(&g_used[cta * 32], epoch * NSEG + seg - 2);
          if (++q == 3) { q = 0; ph ^= 1; }
        }
      }
      return;
    }
    if (w == 3) {
#pragma unroll 1
      for (int c = 0; c < 4; c++) {
        if (lead) asm volatile("cp.async.bulk.wait_group.read 0;" ::: "memory");
        __syncwarp();
        bar_arrive(11, 160); bar_arrive(12, 160);
#pragma unroll 1
        for (int g = 0; g < 2; g++) {
          bar_sync(13 + g, 160);
          if (lead) {
            asm volatile("cp.async.bulk.tensor.3d.global.shared::cta.bulk_group [%0, {%2, %3, %4}], [%1];"
                         :: "l"(&tm.oa), "r"(sb + A_EPI + g * A_EPW + 1024), "r"(4096 + hh * 288 + c * 72), "r"(g), "r"(57 * tile) : "memory");
            asm volatile("cp.async.bulk.commit_group;" ::: "memory");
          }
        }
      }
      if (lead) {
        asm volatile("cp.async.bulk.wait_group.read 0;" ::: "memory");
        mbar_arrive(emptyo); mbar_arrive(emptyo + 8);
        publish(&g_abar[32]);
      }
      __syncwarp();
    }
    if ((w & 1) && cta < NH) {
#pragma unroll 1
      for (int seg = w >> 1; seg < NAUXSEG; seg += 2) {
        if (lead) {
          mbar_wait(fullo + (w >> 1) * 8, (seg >> 1) & 1);
          fence_async();
          tma_store(&tm.o, sb + A_OST + (w >> 1) * 8192, cta * DH, seg * 32);
          tma_store(&tm.o, sb + A_OST + (w >> 1) * 8192 + 4096, cta * DH + 64, seg * 32);
          asm volatile("cp.async.bulk.commit_group;\ncp.async.bulk.wait_group.read 0;" ::: "memory");
          mbar_arrive(emptyo + (w >> 1) * 8);
          publish(&g_ocnt[seg * 64 + 2 * cta / 9 * 8]);
          if (2 * cta / 9 != (2 * cta + 1) / 9) asm volatile("red.relaxed.gpu.global.add.u32 [%0], 1;" :: "l"(&g_ocnt[seg * 64 + (2 * cta + 1) / 9 * 8]) : "memory");
          SSTAMP(9, seg);
        }
        __syncwarp();
      }
    }
    if (w & 1) return;
    if (w == 0) {
      if (lead) {
        mbar_expect(fullw, 18 * 8192 + 2048);
#pragma unroll 1
        for (int k = 0; k < 18; k++) {
          const int g = k / 9, kb = p3_k(g) * 9 + k - 9 * g;
          if (kb < 64) tma_load(sb + k * 8192, &tm.wob, p3_n(g) * 64, kb * 64, fullw);
          else tma_load(sb + k * 8192, &tm.woa, p3_n(g) * 64, (kb - 64) * 64, fullw);
        }
        for (int g = 0; g < 2; g++) tma_load(sb + A_XW + g * 2048, &tm.wo8, p3_n(g) * 64, 512 + p3_k(g) * 8, fullw);
      }
      __syncwarp();
    }
    bar_sync(6, cta >= NH ? 320 : 288);
    if (lead) {
      for (int i = 0; i < 4; i++) mbar_arrive(emptyq + 16);
      wait_count(&g_abar[32], NAUX * (epoch + 1));
      int avail = 0, sl = w >> 1, ph = 1;
      const int ke = p3_k(w >> 1);
      const unsigned nheads = (ke < 7 ? 5 : 1) * (epoch + 1);
#pragma unroll 1
      for (int seg = 0; seg < NAUXSEG; seg++) {
        bool waited = false;
        if (seg >= avail) {
          const unsigned* const c = &g_ocnt[seg * 64 + ke * 8];
          const int c2 = ldg_relaxed32(c + 128) - nheads, c1 = ldg_relaxed32(c + 64) - nheads, c0 = ldg_acquire32(c) - nheads;
          waited = c0 < 0;
          if (waited) wait_count(c, nheads, seg < NAUXSEG - 2);
          else if (c1 >= 0) avail = seg + (c2 >= 0 ? 3 : 2);
        }
        SSTAMP(5, seg);
        mbar_wait(empty3 + 8 * sl, ph);
        if (AX & 4) mbar_arrive(full3 + 8 * sl);
        else {
          mbar_expect(full3 + 8 * sl, XT + 512);
          tma_load3c(sb + sl * XT, &tm.o3, 0, seg * 32, ke * 9, full3 + 8 * sl);
          tma_load(sb + A_XT + sl * 512, &tm.o8, 72 * 64 + ke * 8, seg * 32, full3 + 8 * sl);
        }
        p3_next(sl, ph);
      }
    }
  } else if (wg == 2) {
    asm volatile("setmaxnreg.dec.sync.aligned.u32 88;");
    {
      const unsigned epoch = *(volatile unsigned*)&g_epoch2;
      if ((tid & 127) < 80) { const uint4 g = __ldg((const uint4*)gate_w + min(tid & 127, 71)); sts128(sb + A_GW + (tid & 127) * 16, g.x, g.y, g.z, g.w); }
      fence_async();
      bar_sync(3, 128);
      float gt[2][4];
      const uint32_t d0 = (sb & 0x3FFFF) >> 4;
#pragma unroll 1
      for (int j = 0; j < 3; j++) {
        mbar_wait(fullx + 8 * j, 0);
        WG_FENCE();
#pragma unroll
        for (int k = 0; k < 24; k++)
          wgmma_n8_ss(gt[k & 1], desc_at(d0 + (k & 1) * (A_XH >> 4) + j * 1536 + (k >> 3) * 512 + (k & 6), 16, 1024, 1), desc_at(d0 + (A_GW >> 4) + j * 24 + (k & 30), 16, 128, 0), j | (k >> 1));
        WG_COMMIT();
      }
      WG_WAIT(0);
      if ((lane & 3) == 0)
#pragma unroll
        for (int i = 0; i < 4; i++) {
          const float gv = 1.f / (1.f + __expf(-gt[i >> 1][(i & 1) * 2]));
          const int r = w * 16 + (lane >> 2) + (i & 1) * 8, tok = 2 * (57 * tile - 7 + r) + (i >> 1);
          sts32(sb + A_GATE + ((i >> 1) * 64 + r) * 4, __float_as_uint(gv));
          if (hh == 0 && r >= 7 && tok < S_LEN) g_gate[tok] = gv;
        }
      if (tid == 256) sts32(sb + A_BAR + 376, epoch);
      __syncwarp();
      bar_arrive(7, 384);
      __half2 hw = __float2half2_rn(0.f);
#pragma unroll
      for (int i = 0; i < 9; i++) { const uint4 v = __ldg((const uint4*)woa + cta * 1152 + i * 128 + (tid & 127)); hw = amax4(hw, &v.x); }
      const uint32_t ew = wexp(hw);
      if (lane == 0) atomicMax(&g_amax[0], (unsigned long long)(epoch + 1) << 32 | ew);
      bar_sync(3, 128);
      if (tid == 256) {
        count_up(&g_abar[0]);
        wait_count(&g_abar[0], NAUX * (epoch + 1));
        if (cta == 0) *(volatile unsigned*)&g_epoch2 = epoch + 1;
      }
      __syncwarp();
      bar_sync(3, 128);
    }
    if (cta < NH) {
      const int lim = w * 8 + (lane >> 2) - 2 * (lane & 3);
      int q = 0, ph = 0;
      uint32_t p[5][4];
#pragma unroll
      for (int n = 0; n < 10; n++) p[n >> 1][1 + (n & 1)] = __shfl_sync(0xffffffffu, lane ^ n, n);
#pragma unroll 1
      for (int seg = 0; seg < NAUXSEG; seg++) {
        const float gt = __ldcg(&g_gate[seg * 32 + w * 8 + (lane >> 2)]);
        float sc[20], d[32];
        const uint32_t d0 = ((sb & 0x3FFFF) + (q < 2 ? A_IN + q * A_INS : 3 * XT)) >> 4;
        mbar_wait(fullq + q * 8, ph);
        if (tid == 256) SSTAMP(2, seg);
        WG_FENCE();
#pragma unroll
        for (int k = 0; k < 8; k++) {
          const int o = ((k >> 2) * 9216 + (k & 3) * 256) >> 4;
          wgmma_n40_ss_tt(sc, desc_at(d0 + o, 128, 512, 0), desc_at(d0 + o + 256, 128, 1024, 0), k > 0);
        }
        WG_COMMIT();
        WG_WAIT(0);
        if (tid == 256) SSTAMP(12, seg);
        float a[10];
#pragma unroll
        for (int i = 0; i < 10; i++) {
          a[i] = sc[(i >> 1) * 4 + (i & 1)] * (SM_SCALE * LOG2E);
          if (i < 8 && (i >> 1) * 8 + (i & 1) > lim) a[i] = -1.0e9f * LOG2E;
        }
        float m = max10(a);
        m = fmaxf(m, __shfl_xor_sync(0xffffffffu, m, 1)); m = fmaxf(m, __shfl_xor_sync(0xffffffffu, m, 2));
#pragma unroll
        for (int i = 0; i < 10; i++) a[i] = ex2(a[i] - m);
#pragma unroll
        for (int n = 0; n < 5; n++) {
          p[n][0] = pack_bf16(a[2 * n], a[2 * n + 1]); p[n][3] = p[n][0] | p[n][1];
          asm volatile("" : "+r"(p[n][0]), "+r"(p[n][3]) :: "memory");
        }
        float sum = ((a[0] + a[1]) + (a[2] + a[3])) + ((a[4] + a[5]) + (a[6] + a[7])) + (a[8] + a[9]);
        sum += __shfl_xor_sync(0xffffffffu, sum, 1);
        if (tid == 256) SSTAMP(3, seg);
        WG_FENCE();
#pragma unroll
        for (int n = 0; n < 5; n++) wgmma_n64_rs(d, p[n], n < 4 ? desc_at(d0 + 1152 + 8 * n, 4096, 512, 0) : desc_at(d0 + 1152 + 512, 1024, 128, 0), n);
        WG_COMMIT();
        sum += __shfl_xor_sync(0xffffffffu, sum, 2);
        const float f = (1.f - gt) * rcp(sum);
        WG_WAIT(0);
        if (lane == 0) mbar_arrive(emptyq + q * 8);
        if (++q == 3) { q = 0; ph ^= 1; }
        if (tid == 256) SSTAMP(4, seg);
        mbar_wait(emptyo + (seg & 1) * 8, (seg >> 1) & 1);
#pragma unroll
        for (int n = 0; n < 4; n++) {
          const float* const v = d + (n & 1) * 16 + (n & 2);
          stsm4(sb + A_OST + (seg & 1) * 8192 + (n >> 1) * 4096 + (w * 8 + (lane & 7)) * 128 + ((((n & 1) * 4 + (lane >> 3)) ^ (lane & 7)) << 4),
                pack_bf16(v[0] * f, v[1] * f), pack_bf16(v[4] * f, v[5] * f), pack_bf16(v[8] * f, v[9] * f), pack_bf16(v[12] * f, v[13] * f));
        }
        __syncwarp();
        if (lane == 0) mbar_arrive(fullo + (seg & 1) * 8);
        if (tid == 256) SSTAMP(13, seg);
      }
    }
  } else {
    asm volatile("setmaxnreg.inc.sync.aligned.u32 200;");
    {
      const int g = lane >> 2, t = lane & 3;
      const uint32_t eb = sb + A_EPI + wg * A_EPW, d0 = (sb & 0x3FFFF) >> 4;
      const uint32_t own = (2 * t <= g ? 0xffffu : 0u) | (2 * t < g ? 0xffff0000u : 0u);
      const int kmin = 7 - 57 * tile - 16 * w;
      __half2 ho = __float2half2_rn(0.f);
#pragma unroll 1
      for (int c = 0; c < 4; c++) {
        float acc[96], tl[12];
#pragma unroll 1
        for (int r = 0; r < 4; r++) {
#pragma unroll
          for (int st = 0; st < A_NS; st++) {
            const int ks = r * 9 + st;
            if (c == 0 && st % 3 == 0 && ks % 12 == 0) mbar_wait(fullx + 8 * (ks / 12), 0);
            mbar_wait(full1 + 8 * st, r & 1);
            const uint64_t da = desc_at(d0 + wg * (A_XH >> 4) + (ks >> 2) * 512 + (ks & 3) * 2, 16, 1024, 1);
            WG_FENCE();
            wgmma_n192_ss_nt(acc, da, desc_at(d0 + ((A_RING + st * A_WM) >> 4), 2048, 1024, 1), ks);
            if (!(AX & 2)) wgmma_n24_ss_nt(tl, da, desc_at(d0 + ((A_TAIL + st * A_WT) >> 4), 128, 256, 0), ks);
            WG_COMMIT();
            if (st == 0 && r == 2) bar_sync(11 + wg, 160);
            WG_WAIT(1);
            if (ks > 0 && lane == 0) mbar_arrive(empty1 + 8 * ((st + A_NS - 1) % A_NS));
          }
        }
        WG_WAIT(0);
        if (lane == 0) mbar_arrive(empty1 + 8 * (A_NS - 1));
        ASTAMP(16 + (c & 3));
        uint32_t ql[9], qh[9], kl[9], kh[9], kx[10], vl[9], vh[9], vx[10];
#pragma unroll
        for (int j = 0; j < 9; j++) {
          const float* const q = j < 8 ? acc + 4 * j : tl, * const k = j < 8 ? acc + 32 + 4 * j : tl + 4, * const v = j < 8 ? acc + 64 + 4 * j : tl + 8;
          kh[j] = pack_bf16(k[2], k[3]); vh[j] = pack_bf16(v[2], v[3]);
          ql[j] = pack_bf16(q[0], q[1]); qh[j] = pack_bf16(q[2], q[3]); kl[j] = pack_bf16(k[0], k[1]); vl[j] = pack_bf16(v[0], v[1]);
        }
        if (w < 3) {
          const uint32_t ha = eb + 1024 + w * 2304 + lane * 16;
          stsm4(ha, kh[0], kh[1], kh[2], kh[3]); stsm4(ha + 512, kh[4], kh[5], kh[6], kh[7]);
          stsm4(ha + 1024, vh[0], vh[1], vh[2], vh[3]); stsm4(ha + 1536, vh[4], vh[5], vh[6], vh[7]);
          asm volatile("stmatrix.sync.aligned.m8n8.x2.shared.b16 [%0], {%1,%2};" :: "r"(ha + 2048), "r"(kh[8]), "r"(vh[8]) : "memory");
        }
        if (c == 0) bar_sync(7, 384); else bar_sync(1 + wg, 128);
        {
          const uint32_t ha = eb + 1024 + max(w - 1, 0) * 2304 + lane * 16;
          ldsm4(kx, ha); ldsm4(kx + 4, ha + 512); ldsm4t(vx, ha + 1024); ldsm4t(vx + 4, ha + 1536);
          asm volatile("ldmatrix.sync.aligned.m8n8.x1.shared.b16 {%0}, [%1];" : "=r"(kx[8]) : "r"(ha + 2048) : "memory");
          asm volatile("ldmatrix.sync.aligned.m8n8.x1.trans.shared.b16 {%0}, [%1];" : "=r"(vx[8]) : "r"(ha + 2176) : "memory");
        }
        const float gl = __uint_as_float(lds32(sb + A_GATE + (wg * 64 + w * 16 + g) * 4)), gh = __uint_as_float(lds32(sb + A_GATE + (wg * 64 + w * 16 + g + 8) * 4));
#pragma unroll
        for (int j = 0; j < 9; j++) { vl[j] = movm(vl[j]); vh[j] = movm(vh[j]); }
        bar_sync(1 + wg, 128);
        uint32_t ol[9], oh[9];
#pragma unroll
        for (int i = 0; i < 4; i++) {
          const int b = 2 * i;
          const uint32_t a[4] = {t >= i ? ql[b] : 0u, t >= i ? qh[b] : 0u, ql[b + 1], qh[b + 1]}, a4 = t <= i ? ql[b + 2] : 0u, a5 = t <= i ? qh[b + 2] : 0u;
          float sx[4], sl[4], sh[4];
          mma16816z(sx, a, kx[b], kx[b + 1]); mma16816z(sl, a, kl[b], kl[b + 1]); mma16816z(sh, a, kh[b], kh[b + 1]);
          mma1688(sx, a4, a5, kx[b + 2]); mma1688(sl, a4, a5, kl[b + 2]); mma1688(sh, a4, a5, kh[b + 2]);
          float e[4];
#pragma unroll
          for (int u = 0; u < 4; u++) {
            const int cc = 2 * t + (u & 1);
            e[u] = (cc <= g ? (u < 2 ? sl[u] : sh[u]) : (u < 2 ? sx[u] : sl[u])) * (0.23570226039551584f * LOG2E);
            if ((cc <= g ? cc : cc - 8) + (u & 2) * 4 < kmin) e[u] = -1.0e9f * LOG2E;
          }
          float m0 = fmaxf(e[0], e[1]), m1 = fmaxf(e[2], e[3]);
#pragma unroll
          for (int o = 1; o < 4; o <<= 1) { m0 = fmaxf(m0, __shfl_xor_sync(0xffffffffu, m0, o)); m1 = fmaxf(m1, __shfl_xor_sync(0xffffffffu, m1, o)); }
          e[0] = ex2(e[0] - m0); e[1] = ex2(e[1] - m0); e[2] = ex2(e[2] - m1); e[3] = ex2(e[3] - m1);
          const uint32_t p0 = pack_bf16(e[0], e[1]), p1 = pack_bf16(e[2], e[3]);
          const uint32_t p[4] = {p0 & ~own, 0u, p0 & own, p1 & ~own};
          float s0 = e[0] + e[1], s1 = e[2] + e[3];
#pragma unroll
          for (int o = 1; o < 4; o <<= 1) { s0 += __shfl_xor_sync(0xffffffffu, s0, o); s1 += __shfl_xor_sync(0xffffffffu, s1, o); }
          const float f0 = gl * rcp(s0), f1 = gh * rcp(s1);
#pragma unroll
          for (int j = b; j < b + 3; j++) {
            float o[4];
            mma16816z(o, p, vx[j], vl[j]);
            mma1688(o, 0u, p1 & own, vh[j]);
            const uint32_t lo = pack_bf16(o[0] * f0, o[1] * f0), hi = pack_bf16(o[2] * f1, o[3] * f1);
            if (j > b || i == 0) { ol[j] = lo; oh[j] = hi; }
            else { ol[j] = t >= i ? lo : ol[j]; oh[j] = t >= i ? hi : oh[j]; }
          }
        }
        const uint32_t sa = eb + 16 + (w * 16 + (lane & 15)) * 144 + (lane >> 4) * 16;
#pragma unroll
        for (int j = 0; j < 8; j += 2) stsm4(sa + j * 16, ol[j], oh[j], ol[j + 1], oh[j + 1]);
        asm volatile("stmatrix.sync.aligned.m8n8.x2.shared.b16 [%0], {%1,%2};" :: "r"(sa + 128), "r"(ol[8]), "r"(oh[8]) : "memory");
        ho = amax4(amax4(amax4(amax4(ho, ol), ol + 4), oh), oh + 4);
        ho = __hmax2_nan(__hmax2_nan(ho, __habs2(*(const __half2*)&ol[8])), __habs2(*(const __half2*)&oh[8]));
        if (c == 3 && tile == 17) {
          const uint32_t eo = wexp(ho);
          if (lane == 0) atomicMax(&g_amax[16], (unsigned long long)(lds32(sb + A_BAR + 376) + 1) << 32 | eo);
        }
        fence_async();
        bar_arrive(13 + wg, 160);
        ASTAMP(20 + (c & 3));
      }
    }
    ASTAMP(3);
    uint32_t wa[36][4];
    mbar_wait(fullw, 0);
    const uint32_t la = sb + wg * 73728 + ((lane & 7) + ((lane >> 4) << 3)) * 128 + (((2 * w + ((lane >> 3) & 1)) ^ (lane & 7)) << 4);
#pragma unroll
    for (int k = 0; k < 36; k++) ldsm4t(wa[k], la + k * 2048);
    sts64(sb + A_XW + wg * 2048 + 1024 + (tid & 127) * 8, 0, 0);
    fence_async();
    bar_arrive(6, cta >= NH ? 320 : 288);
    bar_sync(1 + wg, 128);
    ASTAMP(4);
    const int nsl = p3_n(wg), ke = p3_k(wg), t = lane & 3;
    const unsigned epoch = lds32(sb + A_BAR + 376);
    uint2* const part = g_part + nsl * 4096 + w * 16 + (lane >> 2) * 2 + (t & 1);
    auto tag = [&](int seg) { return ((seg >> 2) + 1 + (epoch & (seg >> 1))) & 1; };
    uint2 v[4];
    auto fetch = [&](int seg) {
#pragma unroll
      for (int j = 0; j < 4; j++)
        asm volatile("ld.relaxed.gpu.global.v2.b32 {%0,%1}, [%2];" : "=r"(v[j].x), "=r"(v[j].y) : "l"(part + (seg & 3) * 36864 + ke * 512 + ((t >> 1) * 4 + j) * 64) : "memory");
    };
    auto finish = [&](int seg) {
      int n = 0;
#pragma unroll 1
      while (!(AX & 16) && __any_sync(0xffffffffu, (((v[0].x ^ tag(seg)) | (v[1].x ^ tag(seg)) | (v[2].x ^ tag(seg)) | (v[3].x ^ tag(seg))) & 1) != 0) && ++n < SPIN_LIMIT) {
        if (seg < NAUXSEG - 2) __nanosleep(100);
        fetch(seg);
      }
      const float a0 = (bf_lo(v[0].x) + bf_lo(v[1].x)) + (bf_lo(v[2].x) + bf_lo(v[3].x)), a1 = (bf_hi(v[0].x) + bf_hi(v[1].x)) + (bf_hi(v[2].x) + bf_hi(v[3].x));
      const float b0 = (bf_lo(v[0].y) + bf_lo(v[1].y)) + (bf_lo(v[2].y) + bf_lo(v[3].y)), b1 = (bf_hi(v[0].y) + bf_hi(v[1].y)) + (bf_hi(v[2].y) + bf_hi(v[3].y));
      const float c0 = (t < 2 ? a0 : b0) + __shfl_xor_sync(0xffffffffu, t < 2 ? b0 : a0, 2), c1 = (t < 2 ? a1 : b1) + __shfl_xor_sync(0xffffffffu, t < 2 ? b1 : a1, 2);
      ((uint32_t*)(out + (size_t)(seg * 32 + ke * 4 + ((lane >> 2) & 3)) * DM + nsl * 64 + w * 16 + (lane >> 4) * 8))[t] = movm(pack_bf16(c0, c1));
    };
    float acc[16];
    if (AX & 64) for (int i = 0; i < 16; i++) acc[i] = 0.f;
    int done = 0, sl = cta < NH ? 0 : wg, ph = 0;
    const uint32_t d0 = (sb & 0x3FFFF) >> 4;
#pragma unroll 1
    for (int seg = 0; seg < NAUXSEG; seg++) {
      mbar_wait(full3 + 8 * sl, ph);
      if (SER && !(AX & 64) && (wg == 1 || seg > 0)) bar_sync(10 - wg, 256);
      if (tid == 128) SSTAMP(6, seg);
      if (!(AX & 16) && seg >= 2) fetch(done);
      if (!(AX & 64)) {
        const uint64_t db = desc_at(d0 + sl * (XT >> 4), 16, 1024, 1);
        WG_FENCE();
        wgmma_n32_ss_tn(acc, desc_at(d0 + ((A_XW + wg * 2048) >> 4), 8192, 1024, 1), desc_at(d0 + (A_XT >> 4) + sl * 32, 0, 128, 0), 0);
#pragma unroll
        for (int k = 0; k < 36; k++) {
          wgmma_n32_rs(acc, wa[k][0], wa[k][1], wa[k][2], wa[k][3], db + (k >> 2) * 256 + (k & 3) * 2, 1);
          if (SER && k == SER && (wg == 0 || seg < NAUXSEG - 1)) bar_arrive(9 + wg, 256);
        }
        WG_COMMIT();
      }
      if (done <= seg - 2) finish(done++);
      WG_WAIT(0);
      if (lane == 0) mbar_arrive(empty3 + 8 * sl);
      p3_next(sl, ph);
#pragma unroll
      for (int j = 0; j < 4; j++)
        if (!(AX & 16) || acc[4 * j] == 1.2345678f)
          asm volatile("st.relaxed.gpu.global.v2.b32 [%0], {%1,%2};" :: "l"(part + (seg & 3) * 36864 + (2 * j + (t >> 1)) * 512 + ke * 64),
                       "r"((pack_bf16(0.f, acc[4 * j + 1]) | tag(seg)) + ((__float_as_uint(acc[4 * j]) + ((tag(seg) ^ 1) << 16)) >> 17 << 1)),   "r"(pack_bf16(acc[4 * j + 2], acc[4 * j + 3])) : "memory");
      if (tid == 128) SSTAMP(7, seg);
      if (tid == 128) SSTAMP(8, seg);
      if ((seg & 7) == 6) ASTAMP(5 + (seg >> 3));
    }
#pragma unroll 1
    for (; done < NAUXSEG; done++) { fetch(done); finish(done); }
    ASTAMP(13);
    TSTAMP(48);
    MSTAMP(9);
  }
}

typedef CUresult (*EncodeFn)(CUtensorMap*, CUtensorMapDataType, cuuint32_t, void*, const cuuint64_t*, const cuuint64_t*,
                             const cuuint32_t*, const cuuint32_t*, CUtensorMapInterleave, CUtensorMapSwizzle,
                             CUtensorMapL2promotion, CUtensorMapFloatOOBfill);
static void make_map(EncodeFn enc, CUtensorMap* m, const void* p, int rows, int cols, int box_rows) {
  cuuint64_t dims[2] = {(cuuint64_t)cols, (cuuint64_t)rows};
  cuuint64_t strides[1] = {(cuuint64_t)cols * 2};
  cuuint32_t box[2] = {64, (cuuint32_t)box_rows};
  cuuint32_t es[2] = {1, 1};
  enc(m, CU_TENSOR_MAP_DATA_TYPE_BFLOAT16, 2, (void*)p, dims, strides, box, es, CU_TENSOR_MAP_INTERLEAVE_NONE,
      CU_TENSOR_MAP_SWIZZLE_128B, CU_TENSOR_MAP_L2_PROMOTION_L2_128B, CU_TENSOR_MAP_FLOAT_OOB_FILL_NONE);
}

constexpr int g_poll = POLL_NS;
extern "C" void kernel_launch(void* const* d_in, const int* in_sizes, int n_in, void* d_out, int out_size) {
  const bf16* x = (const bf16*)d_in[0];
  const bf16* wqkvA = (const bf16*)d_in[1];
  const bf16* woA = (const bf16*)d_in[2];
  const bf16* mem0 = (const bf16*)d_in[4];
  const bf16* Wq = (const bf16*)d_in[5];
  const bf16* Wk = (const bf16*)d_in[6];
  const bf16* Wv = (const bf16*)d_in[7];
  const bf16* Wo = (const bf16*)d_in[8];
  const bf16* gate_w = (const bf16*)d_in[10];
  static EncodeFn enc = nullptr;
  static void *pO = nullptr, *pR = nullptr;
  if (!enc) {
    cudaDriverEntryPointQueryResult qr;
    cudaGetDriverEntryPoint("cuTensorMapEncodeTiled", (void**)&enc, cudaEnableDefault, &qr);
    cudaGetSymbolAddress(&pO, g_Ocat);
    cudaGetSymbolAddress(&pR, g_red_raw);
    cudaFuncSetAttribute(rec_kernel, cudaFuncAttributeMaxDynamicSharedMemorySize, SM_TOTAL);
    cudaFuncSetAttribute(aux_kernel, cudaFuncAttributeMaxDynamicSharedMemorySize, A_TOTAL);
  }
  RMaps rm;
  rm.poll = g_poll; rm.out = (bf16*)d_out;
  make_map(enc, &rm.woa, woA, DM, DM, 24);
  {
    cuuint64_t dims[2] = {KCAT, S_LEN}, strides[1] = {KCAT * 2};
    cuuint32_t box[2] = {32, 64}, es[2] = {1, 1};
    enc(&rm.oa, CU_TENSOR_MAP_DATA_TYPE_BFLOAT16, 2, pO, dims, strides, box, es, CU_TENSOR_MAP_INTERLEAVE_NONE,
        CU_TENSOR_MAP_SWIZZLE_NONE, CU_TENSOR_MAP_L2_PROMOTION_NONE, CU_TENSOR_MAP_FLOAT_OOB_FILL_NONE);
  }
  rm.red = (unsigned char*)(((uintptr_t)pR + 262143) & ~(uintptr_t)262143);
  {
    cuuint64_t dims[3] = {64, S_LEN, 9}, strides[2] = {DM * 2, 128};
    cuuint32_t box[3] = {64, 32, 9}, es[3] = {1, 1, 1};
    enc(&rm.x, CU_TENSOR_MAP_DATA_TYPE_BFLOAT16, 3, (void*)x, dims, strides, box, es, CU_TENSOR_MAP_INTERLEAVE_NONE,
        CU_TENSOR_MAP_SWIZZLE_128B, CU_TENSOR_MAP_L2_PROMOTION_L2_128B, CU_TENSOR_MAP_FLOAT_OOB_FILL_NONE);
  }
  make_map(enc, &rm.wq, Wq, DM, 4096, 192);
  make_map(enc, &rm.wk, Wk, DM, 4096, 192);
  make_map(enc, &rm.wv, Wv, DM, 4096, 192);
  make_map(enc, &rm.wo, Wo, 4096, DM, 128);
  AMaps am;
  {
    cuuint32_t es[4] = {1, 1, 1, 1};
    cuuint64_t dx[4] = {64, 2, S_LEN / 2, 9}, sx[3] = {DM * 2, DM * 4, 128};
    cuuint32_t bx[4] = {64, 1, 64, 3};
    enc(&am.x, CU_TENSOR_MAP_DATA_TYPE_BFLOAT16, 4, (void*)x, dx, sx, bx, es, CU_TENSOR_MAP_INTERLEAVE_NONE,
        CU_TENSOR_MAP_SWIZZLE_128B, CU_TENSOR_MAP_L2_PROMOTION_L2_128B, CU_TENSOR_MAP_FLOAT_OOB_FILL_NONE);
    cuuint64_t dw[3] = {DM, DM, 3}, sw[2] = {DM * 6, DM * 2};
    cuuint32_t bw[3] = {64, 16, 3}, bt[3] = {8, 16, 3};
    enc(&am.wa, CU_TENSOR_MAP_DATA_TYPE_BFLOAT16, 3, (void*)wqkvA, dw, sw, bw, es, CU_TENSOR_MAP_INTERLEAVE_NONE,
        CU_TENSOR_MAP_SWIZZLE_128B, CU_TENSOR_MAP_L2_PROMOTION_L2_128B, CU_TENSOR_MAP_FLOAT_OOB_FILL_NONE);
    enc(&am.wt, CU_TENSOR_MAP_DATA_TYPE_BFLOAT16, 3, (void*)wqkvA, dw, sw, bt, es, CU_TENSOR_MAP_INTERLEAVE_NONE,
        CU_TENSOR_MAP_SWIZZLE_NONE, CU_TENSOR_MAP_L2_PROMOTION_NONE, CU_TENSOR_MAP_FLOAT_OOB_FILL_NONE);
    cuuint64_t dz[3] = {KCAT, 2, S_LEN / 2}, sz[2] = {KCAT * 2, KCAT * 4};
    cuuint32_t bz[3] = {72, 1, 57};
    enc(&am.oa, CU_TENSOR_MAP_DATA_TYPE_BFLOAT16, 3, pO, dz, sz, bz, es, CU_TENSOR_MAP_INTERLEAVE_NONE,
        CU_TENSOR_MAP_SWIZZLE_NONE, CU_TENSOR_MAP_L2_PROMOTION_NONE, CU_TENSOR_MAP_FLOAT_OOB_FILL_NONE);
  }
  {
    cuuint64_t dims[3] = {64, S_LEN, KCAT / 64}, strides[2] = {KCAT * 2, 128};
    cuuint32_t box[3] = {64, 32, 9}, es[3] = {1, 1, 1};
    make_map(enc, &am.o, pO, S_LEN, KCAT, 32);
    enc(&am.o3, CU_TENSOR_MAP_DATA_TYPE_BFLOAT16, 3, pO, dims, strides, box, es, CU_TENSOR_MAP_INTERLEAVE_NONE,
        CU_TENSOR_MAP_SWIZZLE_128B, CU_TENSOR_MAP_L2_PROMOTION_L2_128B, CU_TENSOR_MAP_FLOAT_OOB_FILL_NONE);
  }
  make_map(enc, &am.wob, Wo, 4096, DM, 64);
  make_map(enc, &am.woa, woA, DM, DM, 64);
  make_map(enc, &am.wo8, woA, DM, DM, 8);
  {
    cuuint64_t dims[2] = {KCAT, S_LEN}, strides[1] = {KCAT * 2};
    cuuint32_t box[2] = {8, 32}, es[2] = {1, 1};
    enc(&am.o8, CU_TENSOR_MAP_DATA_TYPE_BFLOAT16, 2, pO, dims, strides, box, es, CU_TENSOR_MAP_INTERLEAVE_NONE,
        CU_TENSOR_MAP_SWIZZLE_NONE, CU_TENSOR_MAP_L2_PROMOTION_NONE, CU_TENSOR_MAP_FLOAT_OOB_FILL_NONE);
  }

  rec_kernel<<<96, 384, SM_TOTAL, cudaStreamPerThread>>>(rm, x, mem0);
  cudaLaunchConfig_t cfg = {};
  cfg.gridDim = dim3(NAUX); cfg.blockDim = dim3(512); cfg.dynamicSmemBytes = A_TOTAL; cfg.stream = cudaStreamPerThread;
  cudaLaunchAttribute at[1];
  at[0].id = cudaLaunchAttributeProgrammaticStreamSerialization; at[0].val.programmaticStreamSerializationAllowed = 1;
  cfg.attrs = at; cfg.numAttrs = 1;
  if (XP & 16) cfg.numAttrs = 0;
  if (!(XP & 64)) cudaLaunchKernelEx(&cfg, aux_kernel, am, wqkvA, woA, gate_w, (bf16*)d_out);
}
```
